```python
import torch

def _softmax(x, axis=-1):
    return torch.softmax(x, dim=axis)
def _gelu(x):
    return torch.nn.functional.gelu(x, approximate="tanh")
def _silu(x):
    return torch.nn.functional.silu(x)
def _sigmoid(x):
    return torch.sigmoid(x)
def _layernorm(x, axis=-1, eps=1e-5):
    m = x.mean(dim=axis, keepdim=True)
    v = x.var(dim=axis, keepdim=True, unbiased=False)
    return (x - m) / torch.sqrt(v + eps)
def _scatter_add(tgt, idx, src, axis=0):
    return tgt.clone().index_add_(axis, idx, src)
def _segment_sum(src, seg, n):
    out = torch.zeros((n,) + src.shape[1:], dtype=src.dtype)
    return out.index_add_(0, seg, src)
def _pad(x, pw):
    flat = tuple(v for pair in reversed(pw) for v in pair)
    return torch.nn.functional.pad(x, flat)

kernel_name = 'gated_mix__ssm_conv_s4__ssm_conv_s4d__prompt'

def setup_inputs():

    _w = (lambda a: (lambda t: t.to(torch.bfloat16) if t.is_floating_point() else t)(torch.as_tensor(a)))
    def _A_setup():
        B, L, D, N = 1, 2048, 512, 128
        A_re = -(lambda _x: torch.exp(torch.as_tensor(_x)))((lambda *s: torch.randn(*s, dtype=torch.bfloat16) * 6.4)(D, N))
        A_im = torch.pi * (lambda *s: torch.randn(*s, dtype=torch.bfloat16) * 0.05)(D, N)
        B_re = (lambda *s: torch.randn(*s, dtype=torch.bfloat16) * 0.1)(D, N)
        B_im = (lambda *s: torch.randn(*s, dtype=torch.bfloat16) * 0.1)(D, N)
        C_re = (lambda *s: torch.randn(*s, dtype=torch.bfloat16) * 0.1)(D, N)
        C_im = (lambda *s: torch.randn(*s, dtype=torch.bfloat16) * 0.1)(D, N)
        log_dt = (lambda *s: torch.randn(*s, dtype=torch.bfloat16) * 0.05)(D) * 0.5 - 4.0
        Dskip = (lambda *s: torch.randn(*s, dtype=torch.bfloat16) * 0.05)(D)
        return {
            "u": _w((lambda *s: torch.randn(*s, dtype=torch.bfloat16) * 0.05)(B, L, D)),
            "A_re": _w(A_re),
            "A_im": _w(A_im),
            "B_re": _w(B_re),
            "B_im": _w(B_im),
            "C_re": _w(C_re),
            "C_im": _w(C_im),
            "log_dt": _w(log_dt),
            "Dskip": _w(Dskip),
        }
    _A_in = _A_setup()

    def _B_setup():
        Bsz, L, D, N = 1, 2048, 512, 128
        return {
            "u": _w((lambda *s: torch.randn(*s, dtype=torch.bfloat16) * 0.05)(Bsz, L, D)),
            "log_A_real": _w((lambda *s: torch.randn(*s, dtype=torch.bfloat16) * 6.4)(D, N) * 0.5),
            "A_imag": _w((lambda *s: torch.randn(*s, dtype=torch.bfloat16) * 0.05)(D, N) * 3.14),
            "C_real": _w((lambda *s: torch.randn(*s, dtype=torch.bfloat16) * 0.05)(D, N) / N ** 0.5),
            "C_imag": _w((lambda *s: torch.randn(*s, dtype=torch.bfloat16) * 0.05)(D, N) / N ** 0.5),
            "log_dt": _w((lambda *s: torch.randn(*s, dtype=torch.bfloat16) * 0.05)(D) * 0.5 - 4.0),
            "D_skip": _w((lambda *s: torch.randn(*s, dtype=torch.bfloat16) * 0.05)(D)),
        }
    _B_in = _B_setup()

    return {
        "A_u": _A_in["u"],
        "A_A_re": _A_in["A_re"],
        "A_A_im": _A_in["A_im"],
        "A_B_re": _A_in["B_re"],
        "A_B_im": _A_in["B_im"],
        "A_C_re": _A_in["C_re"],
        "A_C_im": _A_in["C_im"],
        "A_log_dt": _A_in["log_dt"],
        "A_Dskip": _A_in["Dskip"],
        "B_u": _B_in["u"],
        "B_log_A_real": _B_in["log_A_real"],
        "B_A_imag": _B_in["A_imag"],
        "B_C_real": _B_in["C_real"],
        "B_C_imag": _B_in["C_imag"],
        "B_log_dt": _B_in["log_dt"],
        "B_D_skip": _B_in["D_skip"],
        "gate_w": _w((lambda *s: torch.randn(*s, dtype=torch.bfloat16) * 0.05)(512) * 16.0),
    }

def reference(A_u, A_A_re, A_A_im, A_B_re, A_B_im, A_C_re, A_C_im, A_log_dt, A_Dskip, B_u, B_log_A_real, B_A_imag, B_C_real, B_C_imag, B_log_dt, B_D_skip, gate_w):
    def _A_ref(u, A_re, A_im, B_re, B_im, C_re, C_im, log_dt, Dskip):
        Bsz, L, D = u.shape
        dt = torch.exp(log_dt)[:, None]
        A = A_re + 1j * A_im
        Bc = B_re + 1j * B_im
        Cc = C_re + 1j * C_im
        logdA = dt * A
        dB = dt * Bc
        l = (lambda x, dt: x.to(dt))(torch.arange(L), A_re.dtype)
        P = torch.exp(logdA[:, :, None] * l[None, None, :])
        K = torch.einsum("dn,dnl,dn->dl", Cc, P, dB).real
        L2 = 2 * L
        Kp = _pad(K, ((0, 0), (0, L)))
        up = (lambda x, *d: x.permute(*d))(u, 0, 2, 1)
        up = _pad(up, ((0, 0), (0, 0), (0, L)))
        Kf = (lambda x, axes=(-2,-1): torch.fft.rfft2(x.float(), dim=axes))(Kp[:, None, :], axes=(-2, -1))
        Uf = (lambda x, axes=(-2,-1): torch.fft.rfft2(x.float(), dim=axes))(up[:, :, None, :], axes=(-2, -1))
        Yf = Uf * Kf[None, :, :, :]
        y = (lambda x, s, axes=(-2,-1): torch.fft.irfft2(x, s=s, dim=axes).to(torch.bfloat16))(Yf, (1, L2), axes=(-2, -1))[:, :, 0, :L]
        y = (lambda x, *d: x.permute(*d))(y, 0, 2, 1) + u * Dskip[None, None, :]
        return y

    def _B_ref(u, log_A_real, A_imag, C_real, C_imag, log_dt, D_skip):
        L = u.shape[1]
        dt = torch.exp(log_dt)
        A = -torch.exp(log_A_real) + 1j * A_imag
        C = (C_real + 1j * C_imag) * dt[:, None]
        pos = (lambda x, dt: x.to(dt))(torch.arange(L), log_dt.dtype)
        P = torch.exp((A * dt[:, None])[:, :, None] * pos[None, None, :])
        K = 2.0 * torch.einsum("dn,dnl->dl", C, P).real
        L2 = 2 * L
        u_t = (lambda x, *d: x.permute(*d))(u, 0, 2, 1)
        Kf = (lambda x, *a, **k: torch.fft.rfft(x.float(), *a, **k))(K, L2)
        Uf = (lambda x, *a, **k: torch.fft.rfft(x.float(), *a, **k))(u_t, L2)
        y = (lambda x, *a, **k: torch.fft.irfft(x, *a, **k).to(torch.bfloat16))(Uf * Kf[None, :, :], L2)[:, :, :L]
        y = (lambda x, *d: x.permute(*d))(y, 0, 2, 1)
        return y + u * D_skip[None, None, :]

    x = A_u
    g = _sigmoid((x * gate_w).sum(-1, keepdims=True))
    a = _A_ref(x, A_A_re, A_A_im, A_B_re, A_B_im, A_C_re, A_C_im, A_log_dt, A_Dskip)
    b = _B_ref(x, B_log_A_real, B_A_imag, B_C_real, B_C_imag, B_log_dt, B_D_skip)
    return g * a + (1 - g) * b
```

```cpp
#include <cuda_runtime.h>
#include <cuda_bf16.h>
#include <stdint.h>

namespace {

constexpr int L = 2048, D = 512, NM = 128;
constexpr int NCTA = 128;

constexpr int U_CS = 1184;
constexpr int U_OFF = 0;
constexpr int W5_OFF = 4736;
constexpr int W3_OFF = W5_OFF + 3072;
constexpr int W9_OFF = W3_OFF + 3072;
constexpr int W7_OFF = W9_OFF + 2048;
constexpr int S2_OFF = W7_OFF + 2048;
constexpr int R_OFF = S2_OFF + 2048;
constexpr int RD_CS = 1216;
constexpr int RS_CS = 320;
constexpr int R_E2 = 2 * RD_CS, R_O2 = R_E2 + 2 * RS_CS, R_E3 = R_O2 + 2 * RS_CS, R_O3 = R_E3 + 2 * RS_CS;
constexpr int R_BR = R_O3 + 2 * RS_CS;
constexpr int Y_OFF = R_OFF + 2 * R_BR;
constexpr int Y0_OFF = Y_OFF, Y2_OFF = Y_OFF + 8192, Y3_OFF = Y2_OFF + 6144;
constexpr int CH_BYTES = Y_OFF + 18432;
constexpr int MISC_OFF = 4 * CH_BYTES;
constexpr int SMEM_BYTES = MISC_OFF + 64;
static_assert(CH_BYTES % 128 == 0 || true, "");

__device__ unsigned int g_gate[L];
__device__ unsigned int g_epoch;
__device__ unsigned int g_ticket;

struct Params {
  const __nv_bfloat16 *u, *A_re, *A_im, *B_re, *B_im, *C_re, *C_im, *A_ldt, *A_D;
  const __nv_bfloat16 *B_lA, *B_Aim, *B_Cre, *B_Cim, *B_ldt, *B_D, *gw;
  __nv_bfloat16* out;
};

template <int N, int TB> __device__ __forceinline__ void wgmma_rs(float* d, uint32_t a0, uint32_t a1, uint32_t a2, uint32_t a3, uint64_t desc, int sc);
template <> __device__ __forceinline__ void wgmma_rs<64, 0>(float* d, uint32_t a0, uint32_t a1, uint32_t a2, uint32_t a3, uint64_t desc, int sc) {
  asm volatile("{\n.reg .pred p;\nsetp.ne.b32 p, %37, 0;\n"
    "wgmma.mma_async.sync.aligned.m64n64k16.f32.bf16.bf16 {%0,%1,%2,%3,%4,%5,%6,%7,%8,%9,%10,%11,%12,%13,%14,%15,%16,%17,%18,%19,%20,%21,%22,%23,%24,%25,%26,%27,%28,%29,%30,%31}, {%32,%33,%34,%35}, %36, p, 1, 1, 0;\n}"
    : "+f"(d[0]), "+f"(d[1]), "+f"(d[2]), "+f"(d[3]), "+f"(d[4]), "+f"(d[5]), "+f"(d[6]), "+f"(d[7]), "+f"(d[8]), "+f"(d[9]), "+f"(d[10]), "+f"(d[11]), "+f"(d[12]), "+f"(d[13]), "+f"(d[14]), "+f"(d[15]), "+f"(d[16]), "+f"(d[17]), "+f"(d[18]), "+f"(d[19]), "+f"(d[20]), "+f"(d[21]), "+f"(d[22]), "+f"(d[23]), "+f"(d[24]), "+f"(d[25]), "+f"(d[26]), "+f"(d[27]), "+f"(d[28]), "+f"(d[29]), "+f"(d[30]), "+f"(d[31]) : "r"(a0), "r"(a1), "r"(a2), "r"(a3), "l"(desc), "r"(sc));
}
template <> __device__ __forceinline__ void wgmma_rs<56, 0>(float* d, uint32_t a0, uint32_t a1, uint32_t a2, uint32_t a3, uint64_t desc, int sc) {
  asm volatile("{\n.reg .pred p;\nsetp.ne.b32 p, %33, 0;\n"
    "wgmma.mma_async.sync.aligned.m64n56k16.f32.bf16.bf16 {%0,%1,%2,%3,%4,%5,%6,%7,%8,%9,%10,%11,%12,%13,%14,%15,%16,%17,%18,%19,%20,%21,%22,%23,%24,%25,%26,%27}, {%28,%29,%30,%31}, %32, p, 1, 1, 0;\n}"
    : "+f"(d[0]), "+f"(d[1]), "+f"(d[2]), "+f"(d[3]), "+f"(d[4]), "+f"(d[5]), "+f"(d[6]), "+f"(d[7]), "+f"(d[8]), "+f"(d[9]), "+f"(d[10]), "+f"(d[11]), "+f"(d[12]), "+f"(d[13]), "+f"(d[14]), "+f"(d[15]), "+f"(d[16]), "+f"(d[17]), "+f"(d[18]), "+f"(d[19]), "+f"(d[20]), "+f"(d[21]), "+f"(d[22]), "+f"(d[23]), "+f"(d[24]), "+f"(d[25]), "+f"(d[26]), "+f"(d[27]) : "r"(a0), "r"(a1), "r"(a2), "r"(a3), "l"(desc), "r"(sc));
}
template <> __device__ __forceinline__ void wgmma_rs<48, 0>(float* d, uint32_t a0, uint32_t a1, uint32_t a2, uint32_t a3, uint64_t desc, int sc) {
  asm volatile("{\n.reg .pred p;\nsetp.ne.b32 p, %29, 0;\n"
    "wgmma.mma_async.sync.aligned.m64n48k16.f32.bf16.bf16 {%0,%1,%2,%3,%4,%5,%6,%7,%8,%9,%10,%11,%12,%13,%14,%15,%16,%17,%18,%19,%20,%21,%22,%23}, {%24,%25,%26,%27}, %28, p, 1, 1, 0;\n}"
    : "+f"(d[0]), "+f"(d[1]), "+f"(d[2]), "+f"(d[3]), "+f"(d[4]), "+f"(d[5]), "+f"(d[6]), "+f"(d[7]), "+f"(d[8]), "+f"(d[9]), "+f"(d[10]), "+f"(d[11]), "+f"(d[12]), "+f"(d[13]), "+f"(d[14]), "+f"(d[15]), "+f"(d[16]), "+f"(d[17]), "+f"(d[18]), "+f"(d[19]), "+f"(d[20]), "+f"(d[21]), "+f"(d[22]), "+f"(d[23]) : "r"(a0), "r"(a1), "r"(a2), "r"(a3), "l"(desc), "r"(sc));
}
template <> __device__ __forceinline__ void wgmma_rs<48, 1>(float* d, uint32_t a0, uint32_t a1, uint32_t a2, uint32_t a3, uint64_t desc, int sc) {
  asm volatile("{\n.reg .pred p;\nsetp.ne.b32 p, %29, 0;\n"
    "wgmma.mma_async.sync.aligned.m64n48k16.f32.bf16.bf16 {%0,%1,%2,%3,%4,%5,%6,%7,%8,%9,%10,%11,%12,%13,%14,%15,%16,%17,%18,%19,%20,%21,%22,%23}, {%24,%25,%26,%27}, %28, p, 1, 1, 1;\n}"
    : "+f"(d[0]), "+f"(d[1]), "+f"(d[2]), "+f"(d[3]), "+f"(d[4]), "+f"(d[5]), "+f"(d[6]), "+f"(d[7]), "+f"(d[8]), "+f"(d[9]), "+f"(d[10]), "+f"(d[11]), "+f"(d[12]), "+f"(d[13]), "+f"(d[14]), "+f"(d[15]), "+f"(d[16]), "+f"(d[17]), "+f"(d[18]), "+f"(d[19]), "+f"(d[20]), "+f"(d[21]), "+f"(d[22]), "+f"(d[23]) : "r"(a0), "r"(a1), "r"(a2), "r"(a3), "l"(desc), "r"(sc));
}
template <> __device__ __forceinline__ void wgmma_rs<40, 1>(float* d, uint32_t a0, uint32_t a1, uint32_t a2, uint32_t a3, uint64_t desc, int sc) {
  asm volatile("{\n.reg .pred p;\nsetp.ne.b32 p, %25, 0;\n"
    "wgmma.mma_async.sync.aligned.m64n40k16.f32.bf16.bf16 {%0,%1,%2,%3,%4,%5,%6,%7,%8,%9,%10,%11,%12,%13,%14,%15,%16,%17,%18,%19}, {%20,%21,%22,%23}, %24, p, 1, 1, 1;\n}"
    : "+f"(d[0]), "+f"(d[1]), "+f"(d[2]), "+f"(d[3]), "+f"(d[4]), "+f"(d[5]), "+f"(d[6]), "+f"(d[7]), "+f"(d[8]), "+f"(d[9]), "+f"(d[10]), "+f"(d[11]), "+f"(d[12]), "+f"(d[13]), "+f"(d[14]), "+f"(d[15]), "+f"(d[16]), "+f"(d[17]), "+f"(d[18]), "+f"(d[19]) : "r"(a0), "r"(a1), "r"(a2), "r"(a3), "l"(desc), "r"(sc));
}
template <> __device__ __forceinline__ void wgmma_rs<32, 1>(float* d, uint32_t a0, uint32_t a1, uint32_t a2, uint32_t a3, uint64_t desc, int sc) {
  asm volatile("{\n.reg .pred p;\nsetp.ne.b32 p, %21, 0;\n"
    "wgmma.mma_async.sync.aligned.m64n32k16.f32.bf16.bf16 {%0,%1,%2,%3,%4,%5,%6,%7,%8,%9,%10,%11,%12,%13,%14,%15}, {%16,%17,%18,%19}, %20, p, 1, 1, 1;\n}"
    : "+f"(d[0]), "+f"(d[1]), "+f"(d[2]), "+f"(d[3]), "+f"(d[4]), "+f"(d[5]), "+f"(d[6]), "+f"(d[7]), "+f"(d[8]), "+f"(d[9]), "+f"(d[10]), "+f"(d[11]), "+f"(d[12]), "+f"(d[13]), "+f"(d[14]), "+f"(d[15]) : "r"(a0), "r"(a1), "r"(a2), "r"(a3), "l"(desc), "r"(sc));
}
template <> __device__ __forceinline__ void wgmma_rs<16, 1>(float* d, uint32_t a0, uint32_t a1, uint32_t a2, uint32_t a3, uint64_t desc, int sc) {
  asm volatile("{\n.reg .pred p;\nsetp.ne.b32 p, %13, 0;\n"
    "wgmma.mma_async.sync.aligned.m64n16k16.f32.bf16.bf16 {%0,%1,%2,%3,%4,%5,%6,%7}, {%8,%9,%10,%11}, %12, p, 1, 1, 1;\n}"
    : "+f"(d[0]), "+f"(d[1]), "+f"(d[2]), "+f"(d[3]), "+f"(d[4]), "+f"(d[5]), "+f"(d[6]), "+f"(d[7]) : "r"(a0), "r"(a1), "r"(a2), "r"(a3), "l"(desc), "r"(sc));
}


__device__ __forceinline__ uint32_t pack_bf16(float lo, float hi) {
  uint32_t r; asm("cvt.rn.bf16x2.f32 %0, %1, %2;" : "=r"(r) : "f"(hi), "f"(lo)); return r;
}
__device__ __forceinline__ float bf_lo(uint32_t v) { return __uint_as_float(v << 16); }
__device__ __forceinline__ float bf_hi(uint32_t v) { return __uint_as_float(v & 0xffff0000u); }
__device__ __forceinline__ float bf_round(float x) { return __bfloat162float(__float2bfloat16_rn(x)); }
__device__ __forceinline__ uint32_t hmul2(uint32_t a, uint32_t b) { uint32_t r; asm("mul.rn.bf16x2 %0, %1, %2;" : "=r"(r) : "r"(a), "r"(b)); return r; }
__device__ __forceinline__ uint32_t hadd2(uint32_t a, uint32_t b) { uint32_t r; asm("add.rn.bf16x2 %0, %1, %2;" : "=r"(r) : "r"(a), "r"(b)); return r; }
__device__ __forceinline__ uint32_t hsub2(uint32_t a, uint32_t b) { uint32_t r; asm("sub.rn.bf16x2 %0, %1, %2;" : "=r"(r) : "r"(a), "r"(b)); return r; }
__device__ __forceinline__ uint32_t hfma2(uint32_t a, uint32_t b, uint32_t c) { uint32_t r; asm("fma.rn.bf16x2 %0, %1, %2, %3;" : "=r"(r) : "r"(a), "r"(b), "r"(c)); return r; }
__device__ __forceinline__ uint32_t hneg2(uint32_t a) { return a ^ 0x80008000u; }

__device__ __forceinline__ void sts16(uint32_t a, uint32_t v) { asm volatile("st.shared.b16 [%0], %1;" ::"r"(a), "h"((unsigned short)v) : "memory"); }
__device__ __forceinline__ void sts32(uint32_t a, uint32_t v) { asm volatile("st.shared.b32 [%0], %1;" ::"r"(a), "r"(v) : "memory"); }
__device__ __forceinline__ void sts64(uint32_t a, uint32_t x, uint32_t y) { asm volatile("st.shared.v2.b32 [%0], {%1,%2};" ::"r"(a), "r"(x), "r"(y) : "memory"); }
__device__ __forceinline__ void sts128(uint32_t a, uint32_t x, uint32_t y, uint32_t z, uint32_t w) {
  asm volatile("st.shared.v4.b32 [%0], {%1,%2,%3,%4};" ::"r"(a), "r"(x), "r"(y), "r"(z), "r"(w) : "memory");
}
__device__ __forceinline__ uint32_t lds32(uint32_t a) { uint32_t v; asm volatile("ld.shared.b32 %0, [%1];" : "=r"(v) : "r"(a) : "memory"); return v; }
__device__ __forceinline__ uint2 lds64(uint32_t a) { uint2 v; asm volatile("ld.shared.v2.b32 {%0,%1}, [%2];" : "=r"(v.x), "=r"(v.y) : "r"(a) : "memory"); return v; }
__device__ __forceinline__ uint4 lds128(uint32_t a) {
  uint4 v; asm volatile("ld.shared.v4.b32 {%0,%1,%2,%3}, [%4];" : "=r"(v.x), "=r"(v.y), "=r"(v.z), "=r"(v.w) : "r"(a) : "memory"); return v;
}
__device__ __forceinline__ void ldsm4(uint32_t a, uint32_t& r0, uint32_t& r1, uint32_t& r2, uint32_t& r3) {
  asm volatile("ldmatrix.sync.aligned.m8n8.x4.shared.b16 {%0,%1,%2,%3}, [%4];" : "=r"(r0), "=r"(r1), "=r"(r2), "=r"(r3) : "r"(a) : "memory");
}
__device__ __forceinline__ void ldsm4t(uint32_t a, uint32_t& r0, uint32_t& r1, uint32_t& r2, uint32_t& r3) {
  asm volatile("ldmatrix.sync.aligned.m8n8.x4.trans.shared.b16 {%0,%1,%2,%3}, [%4];" : "=r"(r0), "=r"(r1), "=r"(r2), "=r"(r3) : "r"(a) : "memory");
}
__device__ __forceinline__ void stsm4(uint32_t a, uint32_t r0, uint32_t r1, uint32_t r2, uint32_t r3) {
  asm volatile("stmatrix.sync.aligned.m8n8.x4.shared.b16 [%0], {%1,%2,%3,%4};" ::"r"(a), "r"(r0), "r"(r1), "r"(r2), "r"(r3) : "memory");
}
__device__ __forceinline__ void stsm4t(uint32_t a, uint32_t r0, uint32_t r1, uint32_t r2, uint32_t r3) {
  asm volatile("stmatrix.sync.aligned.m8n8.x4.trans.shared.b16 [%0], {%1,%2,%3,%4};" ::"r"(a), "r"(r0), "r"(r1), "r"(r2), "r"(r3) : "memory");
}
__device__ __forceinline__ void mma16816(float* c, uint32_t a0, uint32_t a1, uint32_t a2, uint32_t a3, uint32_t b0, uint32_t b1) {
  asm volatile("mma.sync.aligned.m16n8k16.row.col.f32.bf16.bf16.f32 {%0,%1,%2,%3}, {%4,%5,%6,%7}, {%8,%9}, {%0,%1,%2,%3};"
               : "+f"(c[0]), "+f"(c[1]), "+f"(c[2]), "+f"(c[3]) : "r"(a0), "r"(a1), "r"(a2), "r"(a3), "r"(b0), "r"(b1));
}
__device__ __forceinline__ void bar_sync(int id, int n) { asm volatile("bar.sync %0, %1;" ::"r"(id), "r"(n) : "memory"); }
__device__ __forceinline__ void wg_fence() { asm volatile("wgmma.fence.sync.aligned;" ::: "memory"); }
__device__ __forceinline__ void wg_commit() { asm volatile("wgmma.commit_group.sync.aligned;" ::: "memory"); }
__device__ __forceinline__ void wg_wait0() { asm volatile("wgmma.wait_group.sync.aligned 0;" ::: "memory"); }
__device__ __forceinline__ void fence_async() { asm volatile("fence.proxy.async.shared::cta;" ::: "memory"); }
__device__ __forceinline__ uint64_t mkdesc(uint32_t addr, uint32_t lbo, uint32_t sbo) {
  return (uint64_t)((addr & 0x3FFFF) >> 4) | ((uint64_t)(lbo >> 4) << 16) | ((uint64_t)(sbo >> 4) << 32);
}

struct cf { float re, im; };
__device__ __forceinline__ cf cmul(cf a, cf b) { return {fmaf(a.re, b.re, -a.im * b.im), fmaf(a.re, b.im, a.im * b.re)}; }
__device__ __forceinline__ cf csq(cf a) { return {fmaf(a.re, a.re, -a.im * a.im), (a.re + a.re) * a.im}; }
__device__ __forceinline__ cf cexp_p(float xl, float y, float p) {
  float mag; asm("ex2.approx.ftz.f32 %0, %1;" : "=f"(mag) : "f"(xl * p));
  float th = y * p;
  float k = rintf(th * 0.15915494309189535f);
  float r = fmaf(k, -6.2831854820251465f, th);
  r = fmaf(k, 1.7484555314695172e-07f, r);
  return {mag * __cosf(r), mag * __sinf(r)};
}

__device__ __forceinline__ void put_tap(uint32_t arr, uint32_t cs, int x, uint32_t v) {
  sts16(arr + 2 * x, v);
  sts16(arr + cs + 2 * x + 2, v);
}
__device__ __forceinline__ uint32_t ysw(int c) { return (uint32_t)(c ^ ((c >> 3) & 3)) * 16u; }

__global__ void __launch_bounds__(512, 1) ssm_kernel(const Params p) {
  extern __shared__ __align__(128) unsigned char smem_raw[];
  const uint32_t sb = (uint32_t)__cvta_generic_to_shared(smem_raw);
  const int tid = threadIdx.x, lane = tid & 31;
  const int warp = __shfl_sync(0xffffffffu, tid >> 5, 0);
  const int ch = warp >> 2, wq = warp & 3, br = wq >> 1, hf = wq & 1;
  const int g = lane >> 2, t = lane & 3;
  const int d = blockIdx.x * 4 + ch;
  const uint32_t cb = sb + ch * CH_BYTES;
  const int wtid = tid & 127;

  const int moff = d * NM + hf * 64 + lane * 2;
  uint32_t q0, q1, q2, q3, q4 = 0, q5 = 0;
  float ldt;
  if (br == 0) {
    q0 = *(const uint32_t*)(p.A_re + moff); q1 = *(const uint32_t*)(p.A_im + moff);
    q2 = *(const uint32_t*)(p.C_re + moff); q3 = *(const uint32_t*)(p.C_im + moff);
    q4 = *(const uint32_t*)(p.B_re + moff); q5 = *(const uint32_t*)(p.B_im + moff);
    ldt = __bfloat162float(p.A_ldt[d]);
  } else {
    q0 = *(const uint32_t*)(p.B_lA + moff); q1 = *(const uint32_t*)(p.B_Aim + moff);
    q2 = *(const uint32_t*)(p.B_Cre + moff); q3 = *(const uint32_t*)(p.B_Cim + moff);
    ldt = __bfloat162float(p.B_ldt[d]);
  }
  uint2 ur[4];
#pragma unroll
  for (int i = 0; i < 4; i++) ur[i] = *(const uint2*)(p.u + (size_t)(tid * 4 + i) * D + blockIdx.x * 4);
  const int grow = blockIdx.x * 16 + warp;
  const uint4 gx0 = *(const uint4*)(p.u + (size_t)grow * D + lane * 8), gx1 = *(const uint4*)(p.u + (size_t)grow * D + 256 + lane * 8);
  const uint4 gw0 = *(const uint4*)(p.gw + lane * 8), gw1 = *(const uint4*)(p.gw + 256 + lane * 8);
  unsigned int epoch;
  asm volatile("ld.relaxed.gpu.global.u32 %0, [%1];" : "=r"(epoch) : "l"(&g_epoch) : "memory");
  const uint32_t tag = (epoch + 1) & 0xffffu;

  for (int i = wtid; i < 2 * R_BR / 16; i += 128) sts128(cb + R_OFF + i * 16, 0, 0, 0, 0);
  if (wtid < 32) sts128(cb + U_OFF + (wtid >> 3) * U_CS + (wtid & 7) * 16, 0, 0, 0, 0);
  __syncthreads();
  if (tid == 0) {
    unsigned int tk = atomicAdd(&g_ticket, 1u);
    if (tk == NCTA - 1) { g_ticket = 0; __threadfence(); g_epoch = epoch + 1; }
  }

  {
    const uint32_t scr = cb + Y_OFF + wq * 4608;
    const float dt = bf_round(expf(ldt));
    float acc[5][4];
#pragma unroll
    for (int i = 0; i < 5; i++) acc[i][0] = acc[i][1] = acc[i][2] = acc[i][3] = 0.f;
    float k2048 = 0.f;
#pragma unroll 1
    for (int r = 0; r < 2; r++) {
      float v0 = r ? bf_hi(q0) : bf_lo(q0), v1 = r ? bf_hi(q1) : bf_lo(q1), v2 = r ? bf_hi(q2) : bf_lo(q2);
      float v3 = r ? bf_hi(q3) : bf_lo(q3), v4 = r ? bf_hi(q4) : bf_lo(q4), v5 = r ? bf_hi(q5) : bf_lo(q5);
      cf c;
      if (br == 0) { c = cmul(cf{v2, v3}, cf{dt * v4, dt * v5}); }
      else { v0 = -bf_round(expf(v0)); c = cf{2.f * dt * v2, 2.f * dt * v3}; }
      const float xl = (dt * v0) * 1.4426950408889634f, y = dt * v1;
      const cf z1 = cexp_p(xl, y, 1.f), z8 = cexp_p(xl, y, 8.f), z128 = cexp_p(xl, y, 128.f);
      const cf z2 = csq(z1), z4 = csq(z2);
      const cf z16 = csq(z8), z24 = cmul(z16, z8), z32 = csq(z16), z40 = cmul(z32, z8), z48 = csq(z24), z56 = cmul(z32, z24), z64 = csq(z32);
      __syncwarp();
      sts128(scr + 0 * 512 + lane * 16, pack_bf16(1.f, z8.re), pack_bf16(z16.re, z24.re), pack_bf16(z32.re, z40.re), pack_bf16(z48.re, z56.re));
      sts128(scr + 1 * 512 + lane * 16, pack_bf16(0.f, -z8.im), pack_bf16(-z16.im, -z24.im), pack_bf16(-z32.im, -z40.im), pack_bf16(-z48.im, -z56.im));
      const cf z256 = csq(z128), z512 = csq(z256), z1024 = csq(z512);
      const cf h1 = cmul(c, z128), h2 = cmul(c, z256), h3 = cmul(h1, z256), h4 = cmul(c, z512), h5 = cmul(h1, z512), h6 = cmul(h2, z512), h7 = cmul(h3, z512);
      sts128(scr + 4 * 512 + lane * 16, pack_bf16(c.re, h1.re), pack_bf16(h2.re, h3.re), pack_bf16(h4.re, h5.re), pack_bf16(h6.re, h7.re));
      sts128(scr + 5 * 512 + lane * 16, pack_bf16(c.im, h1.im), pack_bf16(h2.im, h3.im), pack_bf16(h4.im, h5.im), pack_bf16(h6.im, h7.im));
      const cf e1 = cmul(c, z1), e3 = cmul(e1, z2), e129 = cmul(h1, z1), e131 = cmul(e129, z2);
      const cf e2 = cmul(c, z2), e130 = cmul(h1, z2), e258 = cmul(h2, z2), e386 = cmul(h3, z2);
      sts128(scr + 2 * 512 + lane * 16, pack_bf16(e1.re, e3.re), pack_bf16(e129.re, e131.re), pack_bf16(e2.re, e130.re), pack_bf16(e258.re, e386.re));
      sts128(scr + 3 * 512 + lane * 16, pack_bf16(e1.im, e3.im), pack_bf16(e129.im, e131.im), pack_bf16(e2.im, e130.im), pack_bf16(e258.im, e386.im));
      {
        uint32_t m0 = pack_bf16(z64.re, -z64.im), m1 = pack_bf16(z4.re, z4.im), m2 = pack_bf16(z1024.re, z1024.im);
        const uint32_t mu = scr + 3072 + lane * 2;
        sts16(mu, m0); sts16(mu + 64, m0 >> 16); sts16(mu + 128, m1); sts16(mu + 192, m1 >> 16); sts16(mu + 256, m2); sts16(mu + 320, m2 >> 16);
      }
      const cf z2048 = csq(z1024);
      k2048 += fmaf(c.re, z2048.re, -c.im * z2048.im);
      __syncwarp();
      const uint32_t ta = scr + (lane >> 3) * 512 + (lane & 7) * 16;
      const uint32_t tb2 = scr + 2048 + ((lane >> 3) & 1) * 512 + (lane >> 4) * 128 + (lane & 7) * 16;
      const uint32_t ma = scr + 3072 + (lane >> 3) * 64;
      const uint32_t mb2 = scr + 3072 + 256 + ((lane >> 3) & 1) * 64 + (lane >> 4) * 16;
#pragma unroll
      for (int kp = 0; kp < 2; kp++) {
        uint32_t h2r[2], h2i[2], yr[2], yi[2];
        ldsm4t(tb2 + kp * 256, h2r[0], h2i[0], h2r[1], h2i[1]);
        ldsm4(mb2 + kp * 32, yr[0], yi[0], yr[1], yi[1]);
#pragma unroll
        for (int k2 = 0; k2 < 2; k2++) {
          const int kk = kp * 2 + k2;
          uint32_t m1r, m1i, h1r, h1i, ar, ai, br_, bi;
          ldsm4t(ta + kk * 128, m1r, m1i, h1r, h1i);
          ldsm4(ma + kk * 16, ar, ai, br_, bi);
          const uint32_t m2r = hfma2(m1r, ar, hneg2(hmul2(m1i, ai))), m2i = hfma2(m1r, ai, hmul2(m1i, ar));
          mma16816(acc[0], m1r, m2r, m1i, m2i, h1r, h1i);
          mma16816(acc[2], m1r, m2r, m1i, m2i, h2r[k2], h2i[k2]);
          const uint32_t xr = hfma2(h1r, br_, hneg2(hmul2(h1i, bi))), xi = hfma2(h1r, bi, hmul2(h1i, br_));
          mma16816(acc[1], m1r, m2r, m1i, m2i, xr, xi);
          const uint32_t wr = hfma2(h2r[k2], br_, hneg2(hmul2(h2i[k2], bi))), wi = hfma2(h2r[k2], bi, hmul2(h2i[k2], br_));
          mma16816(acc[3], m1r, m2r, m1i, m2i, wr, wi);
          const uint32_t vr = hfma2(h2r[k2], yr[k2], hneg2(hmul2(h2i[k2], yi[k2]))), vi = hfma2(h2r[k2], yi[k2], hmul2(h2i[k2], yr[k2]));
          mma16816(acc[4], m1r, m2r, m1i, m2i, vr, vi);
        }
      }
    }
#pragma unroll
    for (int o = 16; o; o >>= 1) k2048 += __shfl_xor_sync(0xffffffffu, k2048, o);
    __syncwarp();
    {
      const uint32_t xs = scr + lane * 16;
      if (hf == 0) {
        sts128(xs, __float_as_uint(acc[2][0]), __float_as_uint(acc[2][1]), __float_as_uint(acc[2][2]), __float_as_uint(acc[2][3]));
        sts128(xs + 512, __float_as_uint(acc[3][0]), __float_as_uint(acc[3][1]), __float_as_uint(acc[3][2]), __float_as_uint(acc[3][3]));
        sts128(xs + 1024, __float_as_uint(acc[4][2]), __float_as_uint(acc[4][3]), __float_as_uint(k2048), 0);
      } else {
        sts128(xs, __float_as_uint(acc[0][0]), __float_as_uint(acc[0][1]), __float_as_uint(acc[0][2]), __float_as_uint(acc[0][3]));
        sts128(xs + 512, __float_as_uint(acc[1][0]), __float_as_uint(acc[1][1]), __float_as_uint(acc[1][2]), __float_as_uint(acc[1][3]));
        sts128(xs + 1024, __float_as_uint(acc[4][0]), __float_as_uint(acc[4][1]), 0, 0);
      }
      bar_sync(1 + (warp >> 1), 64);
      const uint32_t xo = cb + Y_OFF + (wq ^ 1) * 4608 + lane * 16;
      const uint4 o0 = lds128(xo), o1 = lds128(xo + 512), o2 = lds128(xo + 1024);
      const uint32_t rb = cb + R_OFF + br * R_BR;
      float v[10];
      const int ti = hf * 2;
      v[0] = (hf ? acc[2][0] : acc[0][0]) + __uint_as_float(o0.x); v[1] = (hf ? acc[2][1] : acc[0][1]) + __uint_as_float(o0.y);
      v[2] = (hf ? acc[2][2] : acc[0][2]) + __uint_as_float(o0.z); v[3] = (hf ? acc[2][3] : acc[0][3]) + __uint_as_float(o0.w);
      v[4] = (hf ? acc[3][0] : acc[1][0]) + __uint_as_float(o1.x); v[5] = (hf ? acc[3][1] : acc[1][1]) + __uint_as_float(o1.y);
      v[6] = (hf ? acc[3][2] : acc[1][2]) + __uint_as_float(o1.z); v[7] = (hf ? acc[3][3] : acc[1][3]) + __uint_as_float(o1.w);
      v[8] = (hf ? acc[4][2] : acc[4][0]) + __uint_as_float(o2.x); v[9] = (hf ? acc[4][3] : acc[4][1]) + __uint_as_float(o2.y);
      (void)ti;
      if (hf == 0) {
        const int a0 = (t & 2) ? ((t & 1) ? 258 : 2) : ((t & 1) ? 129 : 1), da = (t & 2) ? 128 : 2;
#pragma unroll
        for (int i = 0; i < 8; i++) {
          const int pp = a0 + (i & 1) * da + 8 * g + ((i >> 1) & 1) * 64 + (i >> 2) * 4;
          put_tap(rb, RD_CS, 559 - pp, pack_bf16(v[i], 0.f));
        }
      } else {
#pragma unroll
        for (int i = 0; i < 8; i++) {
          const int pp = 256 * t + (i & 1) * 128 + 8 * g + ((i >> 1) & 1) * 64 + (i >> 2) * 4;
          const uint32_t val = pack_bf16(v[i], 0.f);
          if (pp <= 512) {
            put_tap(rb, RD_CS, 559 - pp, val);
            if (pp >= 256) {
              put_tap(rb, RD_CS, 559 - pp - 1, val);
              if (pp > 256) put_tap(rb, RD_CS, 559 - pp + 1, val);
              if (pp == 512) put_tap(rb, RD_CS, 559 - 514, val);
            }
          } else if (i < 4) put_tap(rb + R_E2, RS_CS, 159 - (pp / 8 - 1), val);
          else put_tap(rb + R_O2, RS_CS, 159 - (pp - 4) / 8, val);
        }
        if (lane == 0) put_tap(rb + R_E3, RS_CS, 159 - 127, pack_bf16(k2048 + __uint_as_float(o2.z), 0.f));
      }
#pragma unroll
      for (int i = 0; i < 2; i++) {
        const int pp = 1024 + 128 * (2 * t + i) + 8 * g + 64 * hf;
        const uint32_t val = pack_bf16(v[8 + i], 0.f);
        if (pp == 1024) {
          put_tap(rb + R_E2, RS_CS, 159 - 127, val);
          sts32(sb + MISC_OFF + (ch * 2 + br) * 4, val << 16);
        } else if (g & 1) put_tap(rb + R_O3, RS_CS, 159 - (pp - 8) / 16, val);
        else put_tap(rb + R_E3, RS_CS, 159 - (pp / 16 - 1), val);
      }
    }
  }

  {
    const uint32_t xs[8] = {gx0.x, gx0.y, gx0.z, gx0.w, gx1.x, gx1.y, gx1.z, gx1.w};
    const uint32_t ws[8] = {gw0.x, gw0.y, gw0.z, gw0.w, gw1.x, gw1.y, gw1.z, gw1.w};
    float s = 0.f;
#pragma unroll
    for (int i = 0; i < 8; i++) { const uint32_t pr = hmul2(xs[i], ws[i]); s += bf_lo(pr); s += bf_hi(pr); }
#pragma unroll
    for (int o = 16; o; o >>= 1) s += __shfl_xor_sync(0xffffffffu, s, o);
    if (lane == 0) {
      s = bf_round(s);
      const float gv = 1.f / (1.f + expf(-s));
      const uint32_t w = (tag << 16) | (pack_bf16(gv, 0.f) & 0xffffu);
      asm volatile("st.relaxed.gpu.global.u32 [%0], %1;" ::"l"(&g_gate[grow]), "r"(w) : "memory");
    }
  }

  {
    const int c = tid >> 1;
    const uint32_t ua = sb + U_OFF + (c & 3) * U_CS + (8 + (c >> 2)) * 16 + (tid & 1) * 8;
    sts64(ua + 0 * CH_BYTES, __byte_perm(ur[0].x, ur[1].x, 0x5410), __byte_perm(ur[2].x, ur[3].x, 0x5410));
    sts64(ua + 1 * CH_BYTES, __byte_perm(ur[0].x, ur[1].x, 0x7632), __byte_perm(ur[2].x, ur[3].x, 0x7632));
    sts64(ua + 2 * CH_BYTES, __byte_perm(ur[0].y, ur[1].y, 0x5410), __byte_perm(ur[2].y, ur[3].y, 0x5410));
    sts64(ua + 3 * CH_BYTES, __byte_perm(ur[0].y, ur[1].y, 0x7632), __byte_perm(ur[2].y, ur[3].y, 0x7632));
  }
  __syncthreads();
  {
    const int c0 = (wq < 2) ? 3 * wtid - 2 : 2 * (wtid - 64) - 3;
    float pf[41];
    pf[0] = 0.f;
#pragma unroll
    for (int j = 0; j < 5; j++) {
      const int c = c0 + j + 32;
      const uint4 v = lds128(cb + U_OFF + (c & 3) * U_CS + (c >> 2) * 16);
      const uint32_t w[4] = {v.x, v.y, v.z, v.w};
#pragma unroll
      for (int i = 0; i < 4; i++) {
        pf[j * 8 + 2 * i + 1] = pf[j * 8 + 2 * i] + bf_lo(w[i]);
        pf[j * 8 + 2 * i + 2] = pf[j * 8 + 2 * i + 1] + bf_hi(w[i]);
      }
    }
    if (wq < 2) {
#pragma unroll
      for (int j = 0; j < 3; j++) {
        uint32_t a[4], b[4];
#pragma unroll
        for (int i = 0; i < 4; i++) {
          const int ix = 16 + j * 8 + 2 * i;
          a[i] = pack_bf16(pf[ix - 5] - pf[ix - 10], pf[ix - 4] - pf[ix - 9]);
          b[i] = pack_bf16(pf[ix - 2] - pf[ix - 5], pf[ix - 1] - pf[ix - 4]);
        }
        sts128(cb + W5_OFF + (3 * wtid + j) * 16, a[0], a[1], a[2], a[3]);
        sts128(cb + W3_OFF + (3 * wtid + j) * 16, b[0], b[1], b[2], b[3]);
      }
    } else {
      const int q = wtid - 64;
#pragma unroll
      for (int j = 0; j < 2; j++) {
        uint32_t a[4], b[4], s[4];
#pragma unroll
        for (int i = 0; i < 4; i++) {
          const int ix = 24 + j * 8 + 2 * i;
          a[i] = pack_bf16(pf[ix - 11] - pf[ix - 20], pf[ix - 10] - pf[ix - 19]);
          b[i] = pack_bf16(pf[ix - 4] - pf[ix - 11], pf[ix - 3] - pf[ix - 10]);
          s[i] = pack_bf16(pf[ix - 2] - pf[ix - 4], pf[ix - 1] - pf[ix - 3]);
        }
        const uint32_t po = ((q >> 5) * 64 + j * 32 + (q & 31)) * 16;
        sts128(cb + W9_OFF + po, a[0], a[1], a[2], a[3]);
        sts128(cb + W7_OFF + po, b[0], b[1], b[2], b[3]);
        sts128(cb + S2_OFF + (2 * q + j) * 16, s[0], s[1], s[2], s[3]);
      }
    }
  }
  fence_async();
  bar_sync(9 + ch, 128);

  {
    const uint32_t rb = cb + R_OFF + br * R_BR;
    const int eo = 16 * hf + g - 2 * t;
    {
      const int x0 = 559 - (eo + 536);
      const uint32_t fa = rb + ((g & 1) ? 2 * x0 : RD_CS + 2 * x0 + 2);
      const uint64_t ub = mkdesc(cb + U_OFF, U_CS, 128);
      float acc[32];
      uint32_t f[2][9];
#pragma unroll
      for (int i = 0; i < 9; i++) f[0][i] = lds32(fa + (62 + i) * 16);
#pragma unroll
      for (int j = 0; j < 9; j++) {
        wg_fence();
#pragma unroll
        for (int k = 0; k < 4; k++) {
          const int s = 34 - 4 * j - k;
          if (s >= 0) {
            const int o = 2 * s - 66 + 128;
            const int cc = o & 3, rs = (o >> 2) - 32;
            const int n0 = ((-rs) >> 3) * 8;
            const uint64_t desc = ub + (uint64_t)((cc * U_CS + (8 + rs + n0) * 16) >> 4);
            const int fi = 2 * (3 - k);
            const uint32_t a1 = f[j & 1][fi], a0 = f[j & 1][fi + 1], a2 = f[j & 1][fi + 2];
            if (n0 == 0) wgmma_rs<64, 0>(acc, a0, a1, a2, a0, desc, s != 34);
            else if (n0 == 8) wgmma_rs<56, 0>(acc + 4, a0, a1, a2, a0, desc, 1);
            else wgmma_rs<48, 0>(acc + 8, a0, a1, a2, a0, desc, 1);
          }
        }
        wg_commit();
        if (j < 8) {
#pragma unroll
          for (int i = 0; i < 9; i++) {
            const int idx = 62 - 8 * (j + 1) + i;
            if (idx >= 0) f[(j + 1) & 1][i] = lds32(fa + idx * 16);
          }
        }
        wg_wait0();
      }
      const uint32_t yb = cb + Y0_OFF + br * 4096;
      bar_sync(9 + ch, 128);
#pragma unroll
      for (int i = 0; i < 8; i += 2) {
        const int mi = lane >> 3;
        const int cidx = 4 * (8 * (i + (mi >> 1)) + (lane & 7)) + 2 * hf + (mi & 1);
        stsm4t(yb + ysw(cidx), pack_bf16(acc[4 * i], acc[4 * i + 1]), pack_bf16(acc[4 * i + 2], acc[4 * i + 3]),
               pack_bf16(acc[4 * i + 4], acc[4 * i + 5]), pack_bf16(acc[4 * i + 6], acc[4 * i + 7]));
      }
    }
    const int x1 = 159 - (eo + 136);
    const uint32_t fs = rb + ((g & 1) ? 2 * x1 : RS_CS + 2 * x1 + 2);
    {
      float acc[24];
      uint32_t fe[13], fo[13];
#pragma unroll
      for (int i = 0; i < 13; i++) { fe[i] = lds32(fs + R_E2 + i * 16); fo[i] = lds32(fs + R_O2 + i * 16); }
      const uint64_t d5 = mkdesc(cb + W5_OFF, 128, 512), d3 = mkdesc(cb + W3_OFF, 128, 512);
#pragma unroll
      for (int m = 2; m <= 4; m++) {
        wg_fence();
#pragma unroll
        for (int kk = 0; kk < 2; kk++) {
          const int s = 2 * (4 - m) + kk;
          if (m == 2) {
            wgmma_rs<48, 1>(acc, fe[2 * s + 1], fe[2 * s], fe[2 * s + 2], fe[2 * s + 1], d5 + kk * 16, kk);
            wgmma_rs<48, 1>(acc, fo[2 * s + 1], fo[2 * s], fo[2 * s + 2], fo[2 * s + 1], d3 + kk * 16, 1);
          } else if (m == 3) {
            wgmma_rs<40, 1>(acc + 4, fe[2 * s + 1], fe[2 * s], fe[2 * s + 2], fe[2 * s + 1], d5 + kk * 16, 1);
            wgmma_rs<40, 1>(acc + 4, fo[2 * s + 1], fo[2 * s], fo[2 * s + 2], fo[2 * s + 1], d3 + kk * 16, 1);
          } else {
            wgmma_rs<32, 1>(acc + 8, fe[2 * s + 1], fe[2 * s], fe[2 * s + 2], fe[2 * s + 1], d5 + kk * 16, 1);
            wgmma_rs<32, 1>(acc + 8, fo[2 * s + 1], fo[2 * s], fo[2 * s + 2], fo[2 * s + 1], d3 + kk * 16, 1);
          }
        }
        wg_commit();
        wg_wait0();
      }
      const uint32_t yb = cb + Y2_OFF + br * 3072;
#pragma unroll
      for (int i = 0; i < 6; i += 2) {
        const int mi = lane >> 3;
        const int cidx = 32 * (i + (mi >> 1)) + 16 * hf + 8 * (mi & 1) + (lane & 7);
        stsm4(yb + ysw(cidx), pack_bf16(acc[4 * i], acc[4 * i + 1]), pack_bf16(acc[4 * i + 2], acc[4 * i + 3]),
              pack_bf16(acc[4 * i + 4], acc[4 * i + 5]), pack_bf16(acc[4 * i + 6], acc[4 * i + 7]));
      }
    }
    {
      float acc[16];
      uint32_t fe[9], fo[9];
#pragma unroll
      for (int i = 0; i < 9; i++) { fe[i] = lds32(fs + R_E3 + (i + 4) * 16); fo[i] = lds32(fs + R_O3 + (i + 4) * 16); }
      const uint64_t d9 = mkdesc(cb + W9_OFF, 128, 512), d7 = mkdesc(cb + W7_OFF, 128, 512);
#pragma unroll
      for (int m = 2; m <= 3; m++) {
        wg_fence();
#pragma unroll
        for (int kk = 0; kk < 2; kk++) {
          const int s = 2 * (3 - m) + kk;
          if (m == 2) {
            wgmma_rs<32, 1>(acc, fe[2 * s + 1], fe[2 * s], fe[2 * s + 2], fe[2 * s + 1], d9 + kk * 16, kk);
            wgmma_rs<32, 1>(acc, fo[2 * s + 1], fo[2 * s], fo[2 * s + 2], fo[2 * s + 1], d7 + kk * 16, 1);
          } else {
            wgmma_rs<16, 1>(acc + 8, fe[2 * s + 1], fe[2 * s], fe[2 * s + 2], fe[2 * s + 1], d9 + kk * 16, 1);
            wgmma_rs<16, 1>(acc + 8, fo[2 * s + 1], fo[2 * s], fo[2 * s + 2], fo[2 * s + 1], d7 + kk * 16, 1);
          }
        }
        wg_commit();
        wg_wait0();
      }
      const uint32_t yb = cb + Y3_OFF + br * 2048;
#pragma unroll
      for (int i = 0; i < 4; i += 2) {
        const int mi = lane >> 3;
        const int cidx = 64 * (i >> 1) + 2 * (16 * hf + 8 * (mi & 1) + (lane & 7)) + (mi >> 1);
        stsm4(yb + ysw(cidx), pack_bf16(acc[4 * i], acc[4 * i + 1]), pack_bf16(acc[4 * i + 2], acc[4 * i + 3]),
              pack_bf16(acc[4 * i + 4], acc[4 * i + 5]), pack_bf16(acc[4 * i + 6], acc[4 * i + 7]));
      }
    }
  }
  __syncthreads();

  {
    uint4 gv;
    const unsigned int* gp = g_gate + tid * 4;
    int spins = 0;
    while (true) {
      asm volatile("ld.relaxed.gpu.global.v4.u32 {%0,%1,%2,%3}, [%4];" : "=r"(gv.x), "=r"(gv.y), "=r"(gv.z), "=r"(gv.w) : "l"(gp) : "memory");
      if ((gv.x >> 16) == tag && (gv.y >> 16) == tag && (gv.z >> 16) == tag && (gv.w >> 16) == tag) break;
      if (++spins > (1 << 16)) {
        uint32_t r[4];
        for (int i = 0; i < 4; i++) {
          float s = 0.f;
          const uint32_t* xr = (const uint32_t*)(p.u + (size_t)(tid * 4 + i) * D);
          const uint32_t* wr = (const uint32_t*)p.gw;
          for (int j = 0; j < D / 2; j++) { const uint32_t pr = hmul2(xr[j], wr[j]); s += bf_lo(pr); s += bf_hi(pr); }
          s = bf_round(s);
          r[i] = pack_bf16(1.f / (1.f + expf(-s)), 0.f);
        }
        gv = make_uint4(r[0], r[1], r[2], r[3]);
        break;
      }
    }
    const uint32_t g01 = __byte_perm(gv.x, gv.y, 0x5410), g23 = __byte_perm(gv.z, gv.w, 0x5410);
    const uint32_t one2 = 0x3f803f80u;
    const uint32_t h01 = hsub2(one2, g01), h23 = hsub2(one2, g23);
    const int c = tid >> 1;
    const uint32_t ho = (tid & 1) * 8;
    uint32_t o01[4], o23[4];
#pragma unroll
    for (int k = 0; k < 4; k++) {
      const uint32_t b = sb + k * CH_BYTES;
      float ya[4], yb[4];
      {
        const uint2 a = lds64(b + Y0_OFF + ysw(c) + ho), bb = lds64(b + Y0_OFF + 4096 + ysw(c) + ho);
        ya[0] = bf_lo(a.x); ya[1] = bf_hi(a.x); ya[2] = bf_lo(a.y); ya[3] = bf_hi(a.y);
        yb[0] = bf_lo(bb.x); yb[1] = bf_hi(bb.x); yb[2] = bf_lo(bb.y); yb[3] = bf_hi(bb.y);
      }
      if (c >= 64) {
        const uint2 a = lds64(b + Y2_OFF + ysw(c - 64) + ho), bb = lds64(b + Y2_OFF + 3072 + ysw(c - 64) + ho);
        ya[0] += bf_lo(a.x); ya[1] += bf_hi(a.x); ya[2] += bf_lo(a.y); ya[3] += bf_hi(a.y);
        yb[0] += bf_lo(bb.x); yb[1] += bf_hi(bb.x); yb[2] += bf_lo(bb.y); yb[3] += bf_hi(bb.y);
      }
      if (c >= 128) {
        const uint2 a = lds64(b + Y3_OFF + ysw(c - 128) + ho), bb = lds64(b + Y3_OFF + 2048 + ysw(c - 128) + ho);
        const uint2 s = lds64(b + S2_OFF + (c - 128) * 16 + ho);
        const uint2 kk = lds64(sb + MISC_OFF + k * 8);
        const float ka = __uint_as_float(kk.x), kb = __uint_as_float(kk.y);
        ya[0] += fmaf(ka, bf_lo(s.x), bf_lo(a.x)); ya[1] += fmaf(ka, bf_hi(s.x), bf_hi(a.x));
        ya[2] += fmaf(ka, bf_lo(s.y), bf_lo(a.y)); ya[3] += fmaf(ka, bf_hi(s.y), bf_hi(a.y));
        yb[0] += fmaf(kb, bf_lo(s.x), bf_lo(bb.x)); yb[1] += fmaf(kb, bf_hi(s.x), bf_hi(bb.x));
        yb[2] += fmaf(kb, bf_lo(s.y), bf_lo(bb.y)); yb[3] += fmaf(kb, bf_hi(s.y), bf_hi(bb.y));
      }
      const uint2 uu = lds64(b + U_OFF + (c & 3) * U_CS + (8 + (c >> 2)) * 16 + ho);
      const unsigned short da = __bfloat16_as_ushort(p.A_D[blockIdx.x * 4 + k]), db = __bfloat16_as_ushort(p.B_D[blockIdx.x * 4 + k]);
      const uint32_t da2 = da * 0x10001u, db2 = db * 0x10001u;
      const uint32_t a01 = hadd2(pack_bf16(ya[0], ya[1]), hmul2(uu.x, da2)), a23 = hadd2(pack_bf16(ya[2], ya[3]), hmul2(uu.y, da2));
      const uint32_t b01 = hadd2(pack_bf16(yb[0], yb[1]), hmul2(uu.x, db2)), b23 = hadd2(pack_bf16(yb[2], yb[3]), hmul2(uu.y, db2));
      o01[k] = hadd2(hmul2(g01, a01), hmul2(h01, b01));
      o23[k] = hadd2(hmul2(g23, a23), hmul2(h23, b23));
    }
    __nv_bfloat16* op = p.out + (size_t)(tid * 4) * D + blockIdx.x * 4;
    *(uint2*)(op + 0 * D) = make_uint2(__byte_perm(o01[0], o01[1], 0x5410), __byte_perm(o01[2], o01[3], 0x5410));
    *(uint2*)(op + 1 * D) = make_uint2(__byte_perm(o01[0], o01[1], 0x7632), __byte_perm(o01[2], o01[3], 0x7632));
    *(uint2*)(op + 2 * D) = make_uint2(__byte_perm(o23[0], o23[1], 0x5410), __byte_perm(o23[2], o23[3], 0x5410));
    *(uint2*)(op + 3 * D) = make_uint2(__byte_perm(o23[0], o23[1], 0x7632), __byte_perm(o23[2], o23[3], 0x7632));
  }
}

}

extern "C" void kernel_launch(void* const* d_in, const int* in_sizes, int n_in, void* d_out, int out_size) {
  (void)in_sizes; (void)n_in; (void)out_size;
  typedef const __nv_bfloat16* bp;
  Params p;
  p.u = (bp)d_in[0]; p.A_re = (bp)d_in[1]; p.A_im = (bp)d_in[2]; p.B_re = (bp)d_in[3]; p.B_im = (bp)d_in[4];
  p.C_re = (bp)d_in[5]; p.C_im = (bp)d_in[6]; p.A_ldt = (bp)d_in[7]; p.A_D = (bp)d_in[8];
  p.B_lA = (bp)d_in[10]; p.B_Aim = (bp)d_in[11]; p.B_Cre = (bp)d_in[12]; p.B_Cim = (bp)d_in[13];
  p.B_ldt = (bp)d_in[14]; p.B_D = (bp)d_in[15]; p.gw = (bp)d_in[16];
  p.out = (__nv_bfloat16*)d_out;
  static bool init = false;
  if (!init) { cudaFuncSetAttribute(ssm_kernel, cudaFuncAttributeMaxDynamicSharedMemorySize, SMEM_BYTES); init = true; }
  ssm_kernel<<<NCTA, 512, SMEM_BYTES, cudaStreamPerThread>>>(p);
}
```

```cpp
#include <cuda_runtime.h>
#include <cuda.h>
#include <cuda_bf16.h>
#include <stdint.h>

namespace {

constexpr int L = 2048, D = 512, NM = 128;
constexpr int NCTA = 128;

constexpr int RAW_OFF = 0;
constexpr int BAR_OFF = 16384;
constexpr int CH_OFF = 16384 + 128;
constexpr int U_CS = 1184;
constexpr int U_OFF = 0;
constexpr int W5_OFF = 4736;
constexpr int W3_OFF = W5_OFF + 3072;
constexpr int W9_OFF = W3_OFF + 3072;
constexpr int W7_OFF = W9_OFF + 2048;
constexpr int S2_OFF = W7_OFF + 2048;
constexpr int R_OFF = S2_OFF + 2048;
constexpr int RD_CS = 1216;
constexpr int RS_CS = 320;
constexpr int R_E2 = 2 * RD_CS, R_O2 = R_E2 + 2 * RS_CS, R_E3 = R_O2 + 2 * RS_CS, R_O3 = R_E3 + 2 * RS_CS;
constexpr int R_BR = R_O3 + 2 * RS_CS;
constexpr int Y_OFF = R_OFF + 2 * R_BR;
constexpr int Y0_OFF = Y_OFF, Y2_OFF = Y_OFF + 8192, Y3_OFF = Y2_OFF + 6144;
constexpr int CH_BYTES = Y_OFF + 18432 + 16;
constexpr int SMEM_BYTES = CH_OFF + 4 * CH_BYTES;
static_assert(CH_BYTES % 128 == 16, "bank staggering of the channel blocks");
constexpr int B_RAW = BAR_OFF, B_U = BAR_OFF + 8, B_O1 = BAR_OFF + 16, B_O2 = BAR_OFF + 24, B_O3 = BAR_OFF + 32;
constexpr int K1024_OFF = BAR_OFF + 64;

__device__ unsigned int g_gate[L];
__device__ unsigned int g_epoch;
__device__ unsigned int g_ticket;

#define STAMP(k)

struct Params {
  const __nv_bfloat16 *u, *A_re, *A_im, *B_re, *B_im, *C_re, *C_im, *A_ldt, *A_D;
  const __nv_bfloat16 *B_lA, *B_Aim, *B_Cre, *B_Cim, *B_ldt, *B_D, *gw;
};

template <int N, int TB> __device__ __forceinline__ void wgmma_rs(float* d, uint32_t a0, uint32_t a1, uint32_t a2, uint32_t a3, uint64_t desc, int sc);
template <> __device__ __forceinline__ void wgmma_rs<64, 0>(float* d, uint32_t a0, uint32_t a1, uint32_t a2, uint32_t a3, uint64_t desc, int sc) {
  asm volatile("{\n.reg .pred p;\nsetp.ne.b32 p, %37, 0;\n"
    "wgmma.mma_async.sync.aligned.m64n64k16.f32.bf16.bf16 {%0,%1,%2,%3,%4,%5,%6,%7,%8,%9,%10,%11,%12,%13,%14,%15,%16,%17,%18,%19,%20,%21,%22,%23,%24,%25,%26,%27,%28,%29,%30,%31}, {%32,%33,%34,%35}, %36, p, 1, 1, 0;\n}"
    : "+f"(d[0]), "+f"(d[1]), "+f"(d[2]), "+f"(d[3]), "+f"(d[4]), "+f"(d[5]), "+f"(d[6]), "+f"(d[7]), "+f"(d[8]), "+f"(d[9]), "+f"(d[10]), "+f"(d[11]), "+f"(d[12]), "+f"(d[13]), "+f"(d[14]), "+f"(d[15]), "+f"(d[16]), "+f"(d[17]), "+f"(d[18]), "+f"(d[19]), "+f"(d[20]), "+f"(d[21]), "+f"(d[22]), "+f"(d[23]), "+f"(d[24]), "+f"(d[25]), "+f"(d[26]), "+f"(d[27]), "+f"(d[28]), "+f"(d[29]), "+f"(d[30]), "+f"(d[31]) : "r"(a0), "r"(a1), "r"(a2), "r"(a3), "l"(desc), "r"(sc));
}
template <> __device__ __forceinline__ void wgmma_rs<56, 0>(float* d, uint32_t a0, uint32_t a1, uint32_t a2, uint32_t a3, uint64_t desc, int sc) {
  asm volatile("{\n.reg .pred p;\nsetp.ne.b32 p, %33, 0;\n"
    "wgmma.mma_async.sync.aligned.m64n56k16.f32.bf16.bf16 {%0,%1,%2,%3,%4,%5,%6,%7,%8,%9,%10,%11,%12,%13,%14,%15,%16,%17,%18,%19,%20,%21,%22,%23,%24,%25,%26,%27}, {%28,%29,%30,%31}, %32, p, 1, 1, 0;\n}"
    : "+f"(d[0]), "+f"(d[1]), "+f"(d[2]), "+f"(d[3]), "+f"(d[4]), "+f"(d[5]), "+f"(d[6]), "+f"(d[7]), "+f"(d[8]), "+f"(d[9]), "+f"(d[10]), "+f"(d[11]), "+f"(d[12]), "+f"(d[13]), "+f"(d[14]), "+f"(d[15]), "+f"(d[16]), "+f"(d[17]), "+f"(d[18]), "+f"(d[19]), "+f"(d[20]), "+f"(d[21]), "+f"(d[22]), "+f"(d[23]), "+f"(d[24]), "+f"(d[25]), "+f"(d[26]), "+f"(d[27]) : "r"(a0), "r"(a1), "r"(a2), "r"(a3), "l"(desc), "r"(sc));
}
template <> __device__ __forceinline__ void wgmma_rs<48, 0>(float* d, uint32_t a0, uint32_t a1, uint32_t a2, uint32_t a3, uint64_t desc, int sc) {
  asm volatile("{\n.reg .pred p;\nsetp.ne.b32 p, %29, 0;\n"
    "wgmma.mma_async.sync.aligned.m64n48k16.f32.bf16.bf16 {%0,%1,%2,%3,%4,%5,%6,%7,%8,%9,%10,%11,%12,%13,%14,%15,%16,%17,%18,%19,%20,%21,%22,%23}, {%24,%25,%26,%27}, %28, p, 1, 1, 0;\n}"
    : "+f"(d[0]), "+f"(d[1]), "+f"(d[2]), "+f"(d[3]), "+f"(d[4]), "+f"(d[5]), "+f"(d[6]), "+f"(d[7]), "+f"(d[8]), "+f"(d[9]), "+f"(d[10]), "+f"(d[11]), "+f"(d[12]), "+f"(d[13]), "+f"(d[14]), "+f"(d[15]), "+f"(d[16]), "+f"(d[17]), "+f"(d[18]), "+f"(d[19]), "+f"(d[20]), "+f"(d[21]), "+f"(d[22]), "+f"(d[23]) : "r"(a0), "r"(a1), "r"(a2), "r"(a3), "l"(desc), "r"(sc));
}
template <> __device__ __forceinline__ void wgmma_rs<48, 1>(float* d, uint32_t a0, uint32_t a1, uint32_t a2, uint32_t a3, uint64_t desc, int sc) {
  asm volatile("{\n.reg .pred p;\nsetp.ne.b32 p, %29, 0;\n"
    "wgmma.mma_async.sync.aligned.m64n48k16.f32.bf16.bf16 {%0,%1,%2,%3,%4,%5,%6,%7,%8,%9,%10,%11,%12,%13,%14,%15,%16,%17,%18,%19,%20,%21,%22,%23}, {%24,%25,%26,%27}, %28, p, 1, 1, 1;\n}"
    : "+f"(d[0]), "+f"(d[1]), "+f"(d[2]), "+f"(d[3]), "+f"(d[4]), "+f"(d[5]), "+f"(d[6]), "+f"(d[7]), "+f"(d[8]), "+f"(d[9]), "+f"(d[10]), "+f"(d[11]), "+f"(d[12]), "+f"(d[13]), "+f"(d[14]), "+f"(d[15]), "+f"(d[16]), "+f"(d[17]), "+f"(d[18]), "+f"(d[19]), "+f"(d[20]), "+f"(d[21]), "+f"(d[22]), "+f"(d[23]) : "r"(a0), "r"(a1), "r"(a2), "r"(a3), "l"(desc), "r"(sc));
}
template <> __device__ __forceinline__ void wgmma_rs<40, 1>(float* d, uint32_t a0, uint32_t a1, uint32_t a2, uint32_t a3, uint64_t desc, int sc) {
  asm volatile("{\n.reg .pred p;\nsetp.ne.b32 p, %25, 0;\n"
    "wgmma.mma_async.sync.aligned.m64n40k16.f32.bf16.bf16 {%0,%1,%2,%3,%4,%5,%6,%7,%8,%9,%10,%11,%12,%13,%14,%15,%16,%17,%18,%19}, {%20,%21,%22,%23}, %24, p, 1, 1, 1;\n}"
    : "+f"(d[0]), "+f"(d[1]), "+f"(d[2]), "+f"(d[3]), "+f"(d[4]), "+f"(d[5]), "+f"(d[6]), "+f"(d[7]), "+f"(d[8]), "+f"(d[9]), "+f"(d[10]), "+f"(d[11]), "+f"(d[12]), "+f"(d[13]), "+f"(d[14]), "+f"(d[15]), "+f"(d[16]), "+f"(d[17]), "+f"(d[18]), "+f"(d[19]) : "r"(a0), "r"(a1), "r"(a2), "r"(a3), "l"(desc), "r"(sc));
}
template <> __device__ __forceinline__ void wgmma_rs<32, 1>(float* d, uint32_t a0, uint32_t a1, uint32_t a2, uint32_t a3, uint64_t desc, int sc) {
  asm volatile("{\n.reg .pred p;\nsetp.ne.b32 p, %21, 0;\n"
    "wgmma.mma_async.sync.aligned.m64n32k16.f32.bf16.bf16 {%0,%1,%2,%3,%4,%5,%6,%7,%8,%9,%10,%11,%12,%13,%14,%15}, {%16,%17,%18,%19}, %20, p, 1, 1, 1;\n}"
    : "+f"(d[0]), "+f"(d[1]), "+f"(d[2]), "+f"(d[3]), "+f"(d[4]), "+f"(d[5]), "+f"(d[6]), "+f"(d[7]), "+f"(d[8]), "+f"(d[9]), "+f"(d[10]), "+f"(d[11]), "+f"(d[12]), "+f"(d[13]), "+f"(d[14]), "+f"(d[15]) : "r"(a0), "r"(a1), "r"(a2), "r"(a3), "l"(desc), "r"(sc));
}
template <> __device__ __forceinline__ void wgmma_rs<16, 1>(float* d, uint32_t a0, uint32_t a1, uint32_t a2, uint32_t a3, uint64_t desc, int sc) {
  asm volatile("{\n.reg .pred p;\nsetp.ne.b32 p, %13, 0;\n"
    "wgmma.mma_async.sync.aligned.m64n16k16.f32.bf16.bf16 {%0,%1,%2,%3,%4,%5,%6,%7}, {%8,%9,%10,%11}, %12, p, 1, 1, 1;\n}"
    : "+f"(d[0]), "+f"(d[1]), "+f"(d[2]), "+f"(d[3]), "+f"(d[4]), "+f"(d[5]), "+f"(d[6]), "+f"(d[7]) : "r"(a0), "r"(a1), "r"(a2), "r"(a3), "l"(desc), "r"(sc));
}

__device__ __forceinline__ uint32_t pack_bf16(float lo, float hi) {
  uint32_t r; asm("cvt.rn.bf16x2.f32 %0, %1, %2;" : "=r"(r) : "f"(hi), "f"(lo)); return r;
}
__device__ __forceinline__ float bf_lo(uint32_t v) { return __uint_as_float(v << 16); }
__device__ __forceinline__ float bf_hi(uint32_t v) { return __uint_as_float(v & 0xffff0000u); }
__device__ __forceinline__ float bf_round(float x) { return bf_lo(pack_bf16(x, 0.f)); }
__device__ __forceinline__ uint32_t hmul2(uint32_t a, uint32_t b) { uint32_t r; asm("mul.rn.bf16x2 %0, %1, %2;" : "=r"(r) : "r"(a), "r"(b)); return r; }
__device__ __forceinline__ uint32_t hadd2(uint32_t a, uint32_t b) { uint32_t r; asm("add.rn.bf16x2 %0, %1, %2;" : "=r"(r) : "r"(a), "r"(b)); return r; }
__device__ __forceinline__ uint32_t hsub2(uint32_t a, uint32_t b) { uint32_t r; asm("sub.rn.bf16x2 %0, %1, %2;" : "=r"(r) : "r"(a), "r"(b)); return r; }
__device__ __forceinline__ uint32_t hfma2(uint32_t a, uint32_t b, uint32_t c) { uint32_t r; asm("fma.rn.bf16x2 %0, %1, %2, %3;" : "=r"(r) : "r"(a), "r"(b), "r"(c)); return r; }
__device__ __forceinline__ uint32_t hfms2(uint32_t a, uint32_t b, uint32_t c) {
  uint32_t r; asm("{\n.reg .b32 n;\nneg.bf16x2 n, %3;\nfma.rn.bf16x2 %0, %1, %2, n;\n}" : "=r"(r) : "r"(a), "r"(b), "r"(c)); return r;
}

__device__ __forceinline__ void sts16(uint32_t a, uint32_t v) { asm volatile("st.shared.b16 [%0], %1;" ::"r"(a), "h"((unsigned short)v) : "memory"); }
__device__ __forceinline__ void sts32(uint32_t a, uint32_t v) { asm volatile("st.shared.b32 [%0], %1;" ::"r"(a), "r"(v) : "memory"); }
__device__ __forceinline__ void sts128(uint32_t a, uint32_t x, uint32_t y, uint32_t z, uint32_t w) {
  asm volatile("st.shared.v4.b32 [%0], {%1,%2,%3,%4};" ::"r"(a), "r"(x), "r"(y), "r"(z), "r"(w) : "memory");
}
__device__ __forceinline__ uint32_t lds32(uint32_t a) { uint32_t v; asm volatile("ld.shared.b32 %0, [%1];" : "=r"(v) : "r"(a) : "memory"); return v; }
__device__ __forceinline__ uint2 lds64(uint32_t a) { uint2 v; asm volatile("ld.shared.v2.b32 {%0,%1}, [%2];" : "=r"(v.x), "=r"(v.y) : "r"(a) : "memory"); return v; }
__device__ __forceinline__ uint4 lds128(uint32_t a) {
  uint4 v; asm volatile("ld.shared.v4.b32 {%0,%1,%2,%3}, [%4];" : "=r"(v.x), "=r"(v.y), "=r"(v.z), "=r"(v.w) : "r"(a) : "memory"); return v;
}
__device__ __forceinline__ void ldsm4(uint32_t a, uint32_t& r0, uint32_t& r1, uint32_t& r2, uint32_t& r3) {
  asm volatile("ldmatrix.sync.aligned.m8n8.x4.shared.b16 {%0,%1,%2,%3}, [%4];" : "=r"(r0), "=r"(r1), "=r"(r2), "=r"(r3) : "r"(a) : "memory");
}
__device__ __forceinline__ void ldsm4t(uint32_t a, uint32_t& r0, uint32_t& r1, uint32_t& r2, uint32_t& r3) {
  asm volatile("ldmatrix.sync.aligned.m8n8.x4.trans.shared.b16 {%0,%1,%2,%3}, [%4];" : "=r"(r0), "=r"(r1), "=r"(r2), "=r"(r3) : "r"(a) : "memory");
}
__device__ __forceinline__ void stsm4(uint32_t a, uint32_t r0, uint32_t r1, uint32_t r2, uint32_t r3) {
  asm volatile("stmatrix.sync.aligned.m8n8.x4.shared.b16 [%0], {%1,%2,%3,%4};" ::"r"(a), "r"(r0), "r"(r1), "r"(r2), "r"(r3) : "memory");
}
__device__ __forceinline__ void stsm4t(uint32_t a, uint32_t r0, uint32_t r1, uint32_t r2, uint32_t r3) {
  asm volatile("stmatrix.sync.aligned.m8n8.x4.trans.shared.b16 [%0], {%1,%2,%3,%4};" ::"r"(a), "r"(r0), "r"(r1), "r"(r2), "r"(r3) : "memory");
}
__device__ __forceinline__ void mma16816(float* c, uint32_t a0, uint32_t a1, uint32_t a2, uint32_t a3, uint32_t b0, uint32_t b1) {
  asm("mma.sync.aligned.m16n8k16.row.col.f32.bf16.bf16.f32 {%0,%1,%2,%3}, {%4,%5,%6,%7}, {%8,%9}, {%0,%1,%2,%3};"
      : "+f"(c[0]), "+f"(c[1]), "+f"(c[2]), "+f"(c[3]) : "r"(a0), "r"(a1), "r"(a2), "r"(a3), "r"(b0), "r"(b1));
}
__device__ __forceinline__ void bar_sync(int id, int n) { asm volatile("bar.sync %0, %1;" ::"r"(id), "r"(n) : "memory"); }
__device__ __forceinline__ void bar_arrive(int id, int n) { asm volatile("bar.arrive %0, %1;" ::"r"(id), "r"(n) : "memory"); }
__device__ __forceinline__ void wg_fence() { asm volatile("wgmma.fence.sync.aligned;" ::: "memory"); }
__device__ __forceinline__ void wg_commit() { asm volatile("wgmma.commit_group.sync.aligned;" ::: "memory"); }
__device__ __forceinline__ void wg_wait0() { asm volatile("wgmma.wait_group.sync.aligned 0;" ::: "memory"); }
__device__ __forceinline__ void fence_async() { asm volatile("fence.proxy.async.shared::cta;" ::: "memory"); }
__device__ __forceinline__ uint32_t copy_reg(uint32_t v) { uint32_t r; asm volatile("mov.b32 %0, %1;" : "=r"(r) : "r"(v)); return r; }
__device__ __forceinline__ uint64_t mkdesc(uint32_t addr, uint32_t lbo, uint32_t sbo) {
  return (uint64_t)((addr & 0x3FFFF) >> 4) | ((uint64_t)(lbo >> 4) << 16) | ((uint64_t)(sbo >> 4) << 32);
}
__device__ __forceinline__ uint32_t mapa(uint32_t a, uint32_t rank) {
  uint32_t r; asm("mapa.shared::cluster.u32 %0, %1, %2;" : "=r"(r) : "r"(a), "r"(rank)); return r;
}
__device__ __forceinline__ void mbar_init_expect(uint32_t bar, uint32_t bytes) {
  asm volatile("mbarrier.init.shared::cta.b64 [%0], 1;" ::"r"(bar) : "memory");
  asm volatile("mbarrier.arrive.expect_tx.shared::cta.b64 _, [%0], %1;" ::"r"(bar), "r"(bytes) : "memory");
}
__device__ __forceinline__ void mbar_wait(uint32_t bar) {
  for (int it = 0; it < (1 << 22); it++) {
    uint32_t ok;
    asm volatile("{\n.reg .pred p;\nmbarrier.try_wait.parity.acquire.cluster.shared::cta.b64 p, [%1], 0;\nselp.u32 %0, 1, 0, p;\n}"
                 : "=r"(ok) : "r"(bar) : "memory");
    if (ok) return;
  }
  __trap();
}
__device__ __forceinline__ void st_async4(uint32_t a, uint32_t bar, uint32_t x, uint32_t y, uint32_t z, uint32_t w) {
  asm volatile("st.async.weak.shared::cluster.mbarrier::complete_tx::bytes.v4.b32 [%0], {%2,%3,%4,%5}, [%1];"
               ::"r"(a), "r"(bar), "r"(x), "r"(y), "r"(z), "r"(w) : "memory");
}
__device__ __forceinline__ void st_async2(uint32_t a, uint32_t bar, uint32_t x, uint32_t y) {
  asm volatile("st.async.weak.shared::cluster.mbarrier::complete_tx::bytes.v2.b32 [%0], {%2,%3}, [%1];"
               ::"r"(a), "r"(bar), "r"(x), "r"(y) : "memory");
}

struct cf { float re, im; };
__device__ __forceinline__ cf cmul(cf a, cf b) { return {fmaf(a.re, b.re, -a.im * b.im), fmaf(a.re, b.im, a.im * b.re)}; }
__device__ __forceinline__ cf csq(cf a) { return {fmaf(a.re, a.re, -a.im * a.im), (a.re + a.re) * a.im}; }
__device__ __forceinline__ cf cexp_p(float xl, float y, float p) {
  float mag; asm("ex2.approx.ftz.f32 %0, %1;" : "=f"(mag) : "f"(xl * p));
  const float th = y * p;
  const float k = rintf(th * 0.15915494309189535f);
  float r = fmaf(k, -6.2831854820251465f, th);
  r = fmaf(k, 1.7484555314695172e-07f, r);
  return {mag * __cosf(r), mag * __sinf(r)};
}
__device__ __forceinline__ uint32_t ysw(int c) { return (uint32_t)(c ^ ((c >> 3) & 3)) * 16u; }

__device__ __forceinline__ float make_tables(cf c, cf z1, cf z128, uint32_t tb, uint32_t mu) {
  const cf z2 = csq(z1), z4 = csq(z2), z8 = csq(z4);
  const cf z16 = csq(z8), z24 = cmul(z16, z8), z32 = csq(z16), z40 = cmul(z32, z8), z48 = csq(z24), z56 = cmul(z32, z24), z64 = csq(z32);
  sts128(tb + 0 * 512, pack_bf16(1.f, z8.re), pack_bf16(z16.re, z24.re), pack_bf16(z32.re, z40.re), pack_bf16(z48.re, z56.re));
  sts128(tb + 1 * 512, pack_bf16(0.f, -z8.im), pack_bf16(-z16.im, -z24.im), pack_bf16(-z32.im, -z40.im), pack_bf16(-z48.im, -z56.im));
  const cf z256 = csq(z128), z512 = csq(z256), z1024 = csq(z512);
  const cf h1 = cmul(c, z128), h2 = cmul(c, z256), h3 = cmul(h1, z256), h4 = cmul(c, z512), h5 = cmul(h1, z512), h6 = cmul(h2, z512), h7 = cmul(h3, z512);
  sts128(tb + 4 * 512, pack_bf16(c.re, h1.re), pack_bf16(h2.re, h3.re), pack_bf16(h4.re, h5.re), pack_bf16(h6.re, h7.re));
  sts128(tb + 5 * 512, pack_bf16(c.im, h1.im), pack_bf16(h2.im, h3.im), pack_bf16(h4.im, h5.im), pack_bf16(h6.im, h7.im));
  const cf e1 = cmul(c, z1), e3 = cmul(e1, z2), e129 = cmul(h1, z1), e131 = cmul(e129, z2);
  const cf e2 = cmul(c, z2), e130 = cmul(h1, z2), e258 = cmul(h2, z2), e386 = cmul(h3, z2);
  sts128(tb + 2 * 512, pack_bf16(e1.re, e3.re), pack_bf16(e129.re, e131.re), pack_bf16(e2.re, e130.re), pack_bf16(e258.re, e386.re));
  sts128(tb + 3 * 512, pack_bf16(e1.im, e3.im), pack_bf16(e129.im, e131.im), pack_bf16(e2.im, e130.im), pack_bf16(e258.im, e386.im));
  const uint32_t m0 = pack_bf16(z64.re, -z64.im), m1 = pack_bf16(z4.re, z4.im), m2 = pack_bf16(z1024.re, z1024.im);
  sts16(mu, m0); sts16(mu + 64, m0 >> 16); sts16(mu + 128, m1); sts16(mu + 192, m1 >> 16); sts16(mu + 256, m2); sts16(mu + 320, m2 >> 16);
  const cf z2048 = csq(z1024);
  return fmaf(c.re, z2048.re, -c.im * z2048.im);
}

__device__ __forceinline__ void use_tables(float (*acc)[4], uint32_t tb, uint32_t mu, int lane) {
  const uint32_t ta = tb + (lane >> 3) * 512 + (lane & 7) * 16;
  const uint32_t tb2 = tb + 2048 + ((lane >> 3) & 1) * 512 + (lane >> 4) * 128 + (lane & 7) * 16;
  const uint32_t ma = mu + (lane >> 3) * 64;
  const uint32_t mb2 = mu + 256 + ((lane >> 3) & 1) * 64 + (lane >> 4) * 16;
#pragma unroll
  for (int kp = 0; kp < 2; kp++) {
    uint32_t h2r[2], h2i[2], yr[2], yi[2];
    ldsm4t(tb2 + kp * 256, h2r[0], h2i[0], h2r[1], h2i[1]);
    ldsm4(mb2 + kp * 32, yr[0], yi[0], yr[1], yi[1]);
#pragma unroll
    for (int k2 = 0; k2 < 2; k2++) {
      const int kk = kp * 2 + k2;
      uint32_t m1r, m1i, h1r, h1i, ar, ai, br_, bi;
      ldsm4t(ta + kk * 128, m1r, m1i, h1r, h1i);
      ldsm4(ma + kk * 16, ar, ai, br_, bi);
      const uint32_t m2r = hfms2(m1r, ar, hmul2(m1i, ai)), m2i = hfma2(m1r, ai, hmul2(m1i, ar));
      mma16816(acc[0], m1r, m2r, m1i, m2i, h1r, h1i);
      mma16816(acc[2], m1r, m2r, m1i, m2i, h2r[k2], h2i[k2]);
      const uint32_t xr = hfms2(h1r, br_, hmul2(h1i, bi)), xi = hfma2(h1r, bi, hmul2(h1i, br_));
      mma16816(acc[1], m1r, m2r, m1i, m2i, xr, xi);
      const uint32_t wr = hfms2(h2r[k2], br_, hmul2(h2i[k2], bi)), wi = hfma2(h2r[k2], bi, hmul2(h2i[k2], br_));
      mma16816(acc[3], m1r, m2r, m1i, m2i, wr, wi);
      const uint32_t vr = hfms2(h2r[k2], yr[k2], hmul2(h2i[k2], yi[k2])), vi = hfma2(h2r[k2], yi[k2], hmul2(h2i[k2], yr[k2]));
      mma16816(acc[4], m1r, m2r, m1i, m2i, vr, vi);
    }
  }
}

template <int LVL>
__device__ __forceinline__ void final_pass(const Params& p, uint32_t sb, int x, uint32_t tag, uint32_t rank, uint32_t dab) {
  uint4 gv;
  const unsigned int* gp = g_gate + x * 4;
  int spins = 0;
  while (true) {
    asm volatile("ld.relaxed.gpu.global.v4.u32 {%0,%1,%2,%3}, [%4];" : "=r"(gv.x), "=r"(gv.y), "=r"(gv.z), "=r"(gv.w) : "l"(gp) : "memory");
    if ((gv.x >> 16) == tag && (gv.y >> 16) == tag && (gv.z >> 16) == tag && (gv.w >> 16) == tag) break;
    if (++spins > (1 << 16)) {
      uint32_t r[4];
#pragma unroll 1
      for (int i = 0; i < 4; i++) {
        float s = 0.f;
        const uint32_t* xr = (const uint32_t*)(p.u + (size_t)(x * 4 + i) * D);
        const uint32_t* wr = (const uint32_t*)p.gw;
#pragma unroll 1
        for (int j = 0; j < D / 2; j++) { const uint32_t pr = hmul2(xr[j], wr[j]); s += bf_lo(pr); s += bf_hi(pr); }
        s = bf_round(s);
        const uint32_t w = pack_bf16(1.f / (1.f + expf(-s)), 0.f);
        if (i == 0) r[0] = w; else if (i == 1) r[1] = w; else if (i == 2) r[2] = w; else r[3] = w;
      }
      gv = make_uint4(r[0], r[1], r[2], r[3]);
      break;
    }
  }
  const uint32_t g01 = __byte_perm(gv.x, gv.y, 0x5410), g23 = __byte_perm(gv.z, gv.w, 0x5410);
  const uint32_t one2 = 0x3f803f80u;
  const uint32_t h01 = hsub2(one2, g01), h23 = hsub2(one2, g23);
  const int c = x >> 1;
  const uint32_t ho = (x & 1) * 8;
  uint32_t o01[4], o23[4];
#pragma unroll
  for (int k = 0; k < 4; k++) {
    const uint32_t b = sb + CH_OFF + k * CH_BYTES;
    uint32_t a01, a23, b01, b23;
    const uint2 a = lds64(b + Y0_OFF + ysw(c) + ho), bb = lds64(b + Y0_OFF + 4096 + ysw(c) + ho);
    if (LVL == 0) { a01 = a.x; a23 = a.y; b01 = bb.x; b23 = bb.y; }
    else {
      float ya[4], yb[4];
      const uint2 a2 = lds64(b + Y2_OFF + ysw(c - 64) + ho), b2 = lds64(b + Y2_OFF + 3072 + ysw(c - 64) + ho);
      ya[0] = bf_lo(a.x) + bf_lo(a2.x); ya[1] = bf_hi(a.x) + bf_hi(a2.x); ya[2] = bf_lo(a.y) + bf_lo(a2.y); ya[3] = bf_hi(a.y) + bf_hi(a2.y);
      yb[0] = bf_lo(bb.x) + bf_lo(b2.x); yb[1] = bf_hi(bb.x) + bf_hi(b2.x); yb[2] = bf_lo(bb.y) + bf_lo(b2.y); yb[3] = bf_hi(bb.y) + bf_hi(b2.y);
      if (LVL == 2) {
        const uint2 a3 = lds64(b + Y3_OFF + ysw(c - 128) + ho), b3 = lds64(b + Y3_OFF + 2048 + ysw(c - 128) + ho);
        const uint2 s = lds64(b + S2_OFF + (c - 128) * 16 + ho);
        const uint2 kk = lds64(sb + K1024_OFF + k * 8);
        const float ka = __uint_as_float(kk.x), kb = __uint_as_float(kk.y);
        ya[0] += fmaf(ka, bf_lo(s.x), bf_lo(a3.x)); ya[1] += fmaf(ka, bf_hi(s.x), bf_hi(a3.x));
        ya[2] += fmaf(ka, bf_lo(s.y), bf_lo(a3.y)); ya[3] += fmaf(ka, bf_hi(s.y), bf_hi(a3.y));
        yb[0] += fmaf(kb, bf_lo(s.x), bf_lo(b3.x)); yb[1] += fmaf(kb, bf_hi(s.x), bf_hi(b3.x));
        yb[2] += fmaf(kb, bf_lo(s.y), bf_lo(b3.y)); yb[3] += fmaf(kb, bf_hi(s.y), bf_hi(b3.y));
      }
      a01 = pack_bf16(ya[0], ya[1]); a23 = pack_bf16(ya[2], ya[3]); b01 = pack_bf16(yb[0], yb[1]); b23 = pack_bf16(yb[2], yb[3]);
    }
    const uint2 uu = lds64(b + U_OFF + (c & 3) * U_CS + (63 - (c >> 2)) * 16 + ho);
    const uint32_t dk = __shfl_sync(0xffffffffu, dab, k);
    const uint32_t da2 = __byte_perm(dk, dk, 0x1010), db2 = __byte_perm(dk, dk, 0x3232);
    a01 = hadd2(a01, hmul2(uu.x, da2)); a23 = hadd2(a23, hmul2(uu.y, da2));
    b01 = hadd2(b01, hmul2(uu.x, db2)); b23 = hadd2(b23, hmul2(uu.y, db2));
    o01[k] = hadd2(hmul2(g01, a01), hmul2(h01, b01));
    o23[k] = hadd2(hmul2(g23, a23), hmul2(h23, b23));
  }
  const uint32_t owner = (x >> 6) & 1;
  const uint32_t dst = mapa(sb + RAW_OFF + (x >> 7) * 4096 + (x & 63) * 16 + rank * 8, owner);
  const uint32_t bar = mapa(sb + (LVL == 0 ? B_O1 : LVL == 1 ? B_O2 : B_O3), owner);
  st_async2(dst, bar, __byte_perm(o01[0], o01[1], 0x5410), __byte_perm(o01[2], o01[3], 0x5410));
  st_async2(dst + 1024, bar, __byte_perm(o01[0], o01[1], 0x7632), __byte_perm(o01[2], o01[3], 0x7632));
  st_async2(dst + 2048, bar, __byte_perm(o23[0], o23[1], 0x5410), __byte_perm(o23[2], o23[3], 0x5410));
  st_async2(dst + 3072, bar, __byte_perm(o23[0], o23[1], 0x7632), __byte_perm(o23[2], o23[3], 0x7632));
}

__device__ __forceinline__ void tma_store_box(const CUtensorMap* tm, uint32_t src, int c0, int x0) {
  asm volatile("cp.async.bulk.tensor.3d.global.shared::cta.bulk_group [%0, {%2, %3, %4}], [%1];"
               ::"l"(tm), "r"(src), "r"(c0), "r"(x0), "r"(0) : "memory");
}

__global__ void __cluster_dims__(2, 1, 1) __launch_bounds__(512, 1)
ssm_kernel(const Params p, const __grid_constant__ CUtensorMap tm_in, const __grid_constant__ CUtensorMap tm_out) {
  extern __shared__ __align__(1024) unsigned char smem_raw[];
  const uint32_t sb = (uint32_t)__cvta_generic_to_shared(smem_raw);
  const int tid = threadIdx.x, lane = tid & 31;
  const int warp = __shfl_sync(0xffffffffu, tid >> 5, 0);
  const int ch = warp >> 2, wq = warp & 3, br = wq >> 1, hf = wq & 1;
  const int g = lane >> 2, t = lane & 3;
  const int d = blockIdx.x * 4 + ch;
  const uint32_t rank = blockIdx.x & 1;
  const uint32_t cb = sb + CH_OFF + ch * CH_BYTES;
  const int wtid = tid & 127;
  STAMP(0);

  if (tid == 0) {
    mbar_init_expect(sb + B_RAW, 16384);
    asm volatile("fence.proxy.async.shared::cta;" ::: "memory");
    asm volatile("cp.async.bulk.tensor.5d.shared::cluster.global.mbarrier::complete_tx::bytes [%0], [%1, {%3, %4, %4, %4, %5}], [%2];"
                 ::"r"(sb + RAW_OFF), "l"(&tm_in), "r"(sb + B_RAW), "r"((int)(blockIdx.x >> 1) * 8), "r"(0), "r"((int)rank * 32) : "memory");
    mbar_init_expect(sb + B_U, 16384);
    mbar_init_expect(sb + B_O1, 4096);
    mbar_init_expect(sb + B_O2, 4096);
    mbar_init_expect(sb + B_O3, 8192);
    asm volatile("fence.mbarrier_init.release.cluster;" ::: "memory");
  }
  __syncwarp();
  asm volatile("barrier.cluster.arrive.relaxed.aligned;" ::: "memory");

  const int moff = d * NM + hf * 64 + lane * 2;
  uint32_t q0, q1, q2, q3, q4 = 0, q5 = 0;
  float ldt;
  if (br == 0) {
    q0 = *(const uint32_t*)(p.A_re + moff); q1 = *(const uint32_t*)(p.A_im + moff);
    q2 = *(const uint32_t*)(p.C_re + moff); q3 = *(const uint32_t*)(p.C_im + moff);
    q4 = *(const uint32_t*)(p.B_re + moff); q5 = *(const uint32_t*)(p.B_im + moff);
    ldt = __bfloat162float(p.A_ldt[d]);
  } else {
    q0 = *(const uint32_t*)(p.B_lA + moff); q1 = *(const uint32_t*)(p.B_Aim + moff);
    q2 = *(const uint32_t*)(p.B_Cre + moff); q3 = *(const uint32_t*)(p.B_Cim + moff);
    ldt = __bfloat162float(p.B_ldt[d]);
  }
  const int grow = blockIdx.x * 16 + warp;
  const uint4 gx0 = *(const uint4*)(p.u + (size_t)grow * D + lane * 8), gx1 = *(const uint4*)(p.u + (size_t)grow * D + 256 + lane * 8);
  const uint4 gw0 = *(const uint4*)(p.gw + lane * 8), gw1 = *(const uint4*)(p.gw + 256 + lane * 8);
  unsigned int epoch;
  asm volatile("ld.relaxed.gpu.global.u32 %0, [%1];" : "=r"(epoch) : "l"(&g_epoch) : "memory");
  const uint32_t dab = (uint32_t)__bfloat16_as_ushort(p.A_D[blockIdx.x * 4 + t]) | ((uint32_t)__bfloat16_as_ushort(p.B_D[blockIdx.x * 4 + t]) << 16);

  for (int i = wtid & 63; i < R_BR / 16; i += 64) sts128(cb + R_OFF + br * R_BR + i * 16, 0, 0, 0, 0);
  if (wtid < 32) sts128(cb + U_OFF + (wtid >> 3) * U_CS + (64 + (wtid & 7)) * 16, 0, 0, 0, 0);
  STAMP(1);

  float acc[5][4];
  float k2048;
  const uint32_t scr = cb + Y_OFF + wq * 4608;
  {
    const uint32_t scr1 = cb + W5_OFF + wq * 3072;
    const float dt = bf_round(expf(ldt));
#pragma unroll
    for (int i = 0; i < 5; i++) acc[i][0] = acc[i][1] = acc[i][2] = acc[i][3] = 0.f;
    cf c[2], z1[2], z128[2];
#pragma unroll
    for (int r = 0; r < 2; r++) {
      float v0 = r ? bf_hi(q0) : bf_lo(q0), v1 = r ? bf_hi(q1) : bf_lo(q1), v2 = r ? bf_hi(q2) : bf_lo(q2);
      float v3 = r ? bf_hi(q3) : bf_lo(q3), v4 = r ? bf_hi(q4) : bf_lo(q4), v5 = r ? bf_hi(q5) : bf_lo(q5);
      if (br == 0) { c[r] = cmul(cf{v2, v3}, cf{dt * v4, dt * v5}); }
      else { v0 = -bf_round(expf(v0)); c[r] = cf{2.f * dt * v2, 2.f * dt * v3}; }
      const float xl = (dt * v0) * 1.4426950408889634f, y = dt * v1;
      z1[r] = cexp_p(xl, y, 1.f); z128[r] = cexp_p(xl, y, 128.f);
    }
    STAMP(2);
    k2048 = make_tables(c[0], z1[0], z128[0], scr + lane * 16, scr + 3072 + lane * 2);
    __syncwarp();
    k2048 += make_tables(c[1], z1[1], z128[1], scr1 + lane * 16, scr + 3456 + lane * 2);
    use_tables(acc, scr, scr + 3072, lane);
    __syncwarp();
    use_tables(acc, scr1, scr + 3456, lane);
#pragma unroll
    for (int o = 16; o; o >>= 1) k2048 += __shfl_xor_sync(0xffffffffu, k2048, o);
  }
  STAMP(3);
  __syncwarp();
  {
    const uint32_t xs = scr + lane * 16;
    sts128(xs, __float_as_uint(hf ? acc[0][0] : acc[1][0]), __float_as_uint(hf ? acc[0][1] : acc[1][1]),
           __float_as_uint(hf ? acc[0][2] : acc[1][2]), __float_as_uint(hf ? acc[0][3] : acc[1][3]));
    sts128(xs + 512, __float_as_uint(hf ? acc[2][0] : acc[3][0]), __float_as_uint(hf ? acc[2][1] : acc[3][1]),
           __float_as_uint(hf ? acc[2][2] : acc[3][2]), __float_as_uint(hf ? acc[2][3] : acc[3][3]));
    sts128(xs + 1024, __float_as_uint(hf ? acc[4][0] : acc[4][2]), __float_as_uint(hf ? acc[4][1] : acc[4][3]), __float_as_uint(k2048), 0);
  }

  asm volatile("barrier.cluster.wait.aligned;" ::: "memory");
  mbar_wait(sb + B_RAW);
  STAMP(4);
  {
    const uint32_t dst = mapa(sb + CH_OFF + (g & 3) * CH_BYTES + U_OFF + t * U_CS + (63 - rank * 32 - warp * 2) * 16, g >> 2);
    const uint32_t bar = mapa(sb + B_U, g >> 2);
#pragma unroll
    for (int i = 0; i < 2; i++) {
      uint32_t r0, r1, r2, r3;
      ldsm4t(sb + RAW_OFF + (warp * 2 + i) * 512 + lane * 16, r0, r1, r2, r3);
      st_async4(dst - i * 16, bar, r0, r1, r2, r3);
    }
  }

  bar_sync(1 + (warp >> 1), 64);
  {
    const uint32_t xo = cb + Y_OFF + (wq ^ 1) * 4608 + lane * 16;
    const uint4 o0 = lds128(xo), o1 = lds128(xo + 512), o2 = lds128(xo + 1024);
    const uint32_t rb = cb + R_OFF + br * R_BR;
    const uint32_t v01 = pack_bf16((hf ? acc[1][0] : acc[0][0]) + __uint_as_float(o0.x), (hf ? acc[1][1] : acc[0][1]) + __uint_as_float(o0.y));
    const uint32_t v23 = pack_bf16((hf ? acc[1][2] : acc[0][2]) + __uint_as_float(o0.z), (hf ? acc[1][3] : acc[0][3]) + __uint_as_float(o0.w));
    const uint32_t v45 = pack_bf16((hf ? acc[3][0] : acc[2][0]) + __uint_as_float(o1.x), (hf ? acc[3][1] : acc[2][1]) + __uint_as_float(o1.y));
    const uint32_t v67 = pack_bf16((hf ? acc[3][2] : acc[2][2]) + __uint_as_float(o1.z), (hf ? acc[3][3] : acc[2][3]) + __uint_as_float(o1.w));
    const uint32_t v89 = pack_bf16((hf ? acc[4][2] : acc[4][0]) + __uint_as_float(o2.x), (hf ? acc[4][3] : acc[4][1]) + __uint_as_float(o2.y));
    {
      const int a0 = (t & 2) ? ((t & 1) ? 258 : 2) : ((t & 1) ? 129 : 1), da = (t & 2) ? 128 : 2;
      const uint32_t a = rb + 2 * (559 - (a0 + 8 * g + 4 * hf)), b = a - 2 * da;
      sts16(a, v01); sts16(a + RD_CS + 2, v01); sts16(b, v01 >> 16); sts16(b + RD_CS + 2, v01 >> 16);
      sts16(a - 128, v23); sts16(a - 128 + RD_CS + 2, v23); sts16(b - 128, v23 >> 16); sts16(b - 128 + RD_CS + 2, v23 >> 16);
    }
    {
      const bool lo = t < 2;
      const uint32_t a = lo ? rb + 2 * (559 - (256 * t + 8 * g + 4 * hf)) : rb + (hf ? R_O2 : R_E2 + 2) + 2 * (159 - (32 * t + g));
      const uint32_t s1 = lo ? 256 : 32, s2 = lo ? 128 : 16, cs = lo ? RD_CS + 2 : RS_CS + 2;
      const bool p512 = (lane == 2) && (hf == 0);
      const uint32_t a00 = p512 ? rb + 2 * (559 - 512) : a, c00 = p512 ? RD_CS + 2 : cs;
      sts16(a00, v45); sts16(a00 + c00, v45);
      sts16(a - s1, v45 >> 16); sts16(a - s1 + cs, v45 >> 16);
      sts16(a - s2, v67); sts16(a - s2 + cs, v67);
      sts16(a - s1 - s2, v67 >> 16); sts16(a - s1 - s2 + cs, v67 >> 16);
      if (t == 1 || p512) {
        const bool p256 = (lane == 1) && (hf == 0);
        sts16(a00 - 2, v45); sts16(a00 - 2 + RD_CS + 2, v45);
        if (!p256) { sts16(a00 + 2, v45); sts16(a00 + 2 + RD_CS + 2, v45); }
        if (p512) { sts16(a00 - 4, v45); sts16(a00 - 4 + RD_CS + 2, v45); }
        else {
          sts16(a - 256 - 2, v45 >> 16); sts16(a - 256 + RD_CS, v45 >> 16); sts16(a - 256 + 2, v45 >> 16); sts16(a - 256 + RD_CS + 4, v45 >> 16);
          sts16(a - 128 - 2, v67); sts16(a - 128 + RD_CS, v67); sts16(a - 128 + 2, v67); sts16(a - 128 + RD_CS + 4, v67);
          sts16(a - 384 - 2, v67 >> 16); sts16(a - 384 + RD_CS, v67 >> 16); sts16(a - 384 + 2, v67 >> 16); sts16(a - 384 + RD_CS + 4, v67 >> 16);
        }
      }
    }
    {
      const int idx = 64 + 16 * t + 4 * hf + (g >> 1);
      const uint32_t a = rb + ((g & 1) ? R_O3 : R_E3 + 2) + 2 * (159 - idx);
      const bool p1024 = (lane == 0) && (hf == 0);
      const uint32_t a00 = p1024 ? rb + R_E2 + 2 * (159 - 127) : a;
      sts16(a00, v89); sts16(a00 + RS_CS + 2, v89);
      sts16(a - 16, v89 >> 16); sts16(a - 16 + RS_CS + 2, v89 >> 16);
      if (p1024) {
        sts32(sb + K1024_OFF + (ch * 2 + br) * 4, v89 << 16);
        const uint32_t kv = pack_bf16(k2048 + __uint_as_float(o2.z), 0.f);
        sts16(rb + R_E3 + 2 * (159 - 127), kv); sts16(rb + R_E3 + 2 * (159 - 127) + RS_CS + 2, kv);
      }
    }
  }
  STAMP(5);

  const uint32_t tag = (epoch + 1) & 0xffffu;
  {
    const uint32_t xs[8] = {gx0.x, gx0.y, gx0.z, gx0.w, gx1.x, gx1.y, gx1.z, gx1.w};
    const uint32_t ws[8] = {gw0.x, gw0.y, gw0.z, gw0.w, gw1.x, gw1.y, gw1.z, gw1.w};
    float s = 0.f;
#pragma unroll
    for (int i = 0; i < 8; i++) { const uint32_t pr = hmul2(xs[i], ws[i]); s += bf_lo(pr); s += bf_hi(pr); }
#pragma unroll
    for (int o = 16; o; o >>= 1) s += __shfl_xor_sync(0xffffffffu, s, o);
    if (lane == 0) {
      s = bf_round(s);
      const float gv = 1.f / (1.f + expf(-s));
      const uint32_t w = (tag << 16) | (pack_bf16(gv, 0.f) & 0xffffu);
      asm volatile("st.relaxed.gpu.global.u32 [%0], %1;" ::"l"(&g_gate[grow]), "r"(w) : "memory");
      const unsigned int tk = atomicAdd(&g_ticket, 1u);
      if (tk == NCTA * 16 - 1) { g_ticket = 0; __threadfence(); g_epoch = epoch + 1; }
    }
  }

  bar_sync(9 + ch, 128);
  mbar_wait(sb + B_U);
  STAMP(6);
  {
    const int c0 = (wq < 2) ? 3 * wtid - 2 : 2 * (wtid - 64) - 3;
    float pf[41];
    pf[0] = 0.f;
#pragma unroll
    for (int j = 0; j < 5; j++) {
      const int c = c0 + j;
      const uint4 v = lds128(cb + U_OFF + (c & 3) * U_CS + (63 - (c >> 2)) * 16);
      const uint32_t w[4] = {v.x, v.y, v.z, v.w};
#pragma unroll
      for (int i = 0; i < 4; i++) {
        pf[j * 8 + 2 * i + 1] = pf[j * 8 + 2 * i] + bf_lo(w[i]);
        pf[j * 8 + 2 * i + 2] = pf[j * 8 + 2 * i + 1] + bf_hi(w[i]);
      }
    }
    if (wq < 2) {
#pragma unroll
      for (int j = 0; j < 3; j++) {
        uint32_t a[4], b[4];
#pragma unroll
        for (int i = 0; i < 4; i++) {
          const int ix = 16 + j * 8 + 2 * i;
          a[i] = pack_bf16(pf[ix - 5] - pf[ix - 10], pf[ix - 4] - pf[ix - 9]);
          b[i] = pack_bf16(pf[ix - 2] - pf[ix - 5], pf[ix - 1] - pf[ix - 4]);
        }
        const int c = 3 * wtid + j;
        const uint32_t po = ((5 - (c >> 5)) * 32 + (c & 31)) * 16;
        sts128(cb + W5_OFF + po, a[0], a[1], a[2], a[3]);
        sts128(cb + W3_OFF + po, b[0], b[1], b[2], b[3]);
      }
    } else {
      const int q = wtid - 64;
#pragma unroll
      for (int j = 0; j < 2; j++) {
        uint32_t a[4], b[4], s[4];
#pragma unroll
        for (int i = 0; i < 4; i++) {
          const int ix = 24 + j * 8 + 2 * i;
          a[i] = pack_bf16(pf[ix - 11] - pf[ix - 20], pf[ix - 10] - pf[ix - 19]);
          b[i] = pack_bf16(pf[ix - 4] - pf[ix - 11], pf[ix - 3] - pf[ix - 10]);
          s[i] = pack_bf16(pf[ix - 2] - pf[ix - 4], pf[ix - 1] - pf[ix - 3]);
        }
        const uint32_t po = ((1 - (q >> 5)) * 64 + j * 32 + (q & 31)) * 16;
        sts128(cb + W9_OFF + po, a[0], a[1], a[2], a[3]);
        sts128(cb + W7_OFF + po, b[0], b[1], b[2], b[3]);
        sts128(cb + S2_OFF + (2 * q + j) * 16, s[0], s[1], s[2], s[3]);
      }
    }
  }
  fence_async();
  bar_sync(9 + ch, 128);
  STAMP(7);

  const uint32_t rb = cb + R_OFF + br * R_BR;
  const int eo = 16 * hf + g - 2 * t;
  float dacc[32];
  {
    const int x0 = 559 - (eo + 536);
    const uint32_t fa = rb + ((g & 1) ? 2 * x0 : RD_CS + 2 * x0 + 2);
    const uint64_t ub = mkdesc(cb + U_OFF, U_CS, 128);
    uint32_t f[2][9];
#pragma unroll
    for (int i = 0; i < 9; i++) f[0][i] = lds32(fa + (62 + i) * 16);
#pragma unroll
    for (int j = 0; j < 9; j++) {
      wg_fence();
#pragma unroll
      for (int k = 0; k < 4; k++) {
        const int s = 34 - 4 * j - k;
        if (s >= 0) {
          const int o = 2 * s - 66 + 128;
          const int cc = o & 3, rs = (o >> 2) - 32;
          const int n0 = ((-rs) >> 3) * 8;
          const uint64_t desc = ub + (uint64_t)((cc * U_CS - rs * 16) >> 4);
          const int fi = 2 * (3 - k);
          const uint32_t a1 = f[j & 1][fi], a0 = f[j & 1][fi + 1], a2 = f[j & 1][fi + 2];
          if (n0 == 0) wgmma_rs<64, 0>(dacc, a0, a1, a2, a0, desc, s != 34);
          else if (n0 == 8) wgmma_rs<56, 0>(dacc, a0, a1, a2, a0, desc, 1);
          else wgmma_rs<48, 0>(dacc, a0, a1, a2, a0, desc, 1);
        }
      }
      wg_commit();
      if (j < 8) {
#pragma unroll
        for (int i = 0; i < 9; i++) {
          const int idx = 62 - 8 * (j + 1) + i;
          if (idx >= 0) f[(j + 1) & 1][i] = lds32(fa + idx * 16);
        }
      }
      wg_wait0();
    }
    const uint32_t yb = cb + Y0_OFF + br * 4096;
#pragma unroll
    for (int i = 0; i < 8; i += 2) {
      const int mi = lane >> 3;
      const int cidx = 4 * (63 - 8 * (i + (mi >> 1)) - (lane & 7)) + 2 * hf + (mi & 1);
      stsm4t(yb + ysw(cidx), pack_bf16(dacc[4 * i], dacc[4 * i + 1]), pack_bf16(dacc[4 * i + 2], dacc[4 * i + 3]),
             pack_bf16(dacc[4 * i + 4], dacc[4 * i + 5]), pack_bf16(dacc[4 * i + 6], dacc[4 * i + 7]));
    }
  }
  STAMP(8);
  const int oc0 = (int)(blockIdx.x >> 1) * 8;
  if (ch == 0) {
    bar_sync(13, 512);
    final_pass<0>(p, sb, wtid, tag, rank, dab);
    if (tid == 0) {
      mbar_wait(sb + B_O1);
      fence_async();
      tma_store_box(&tm_out, sb + RAW_OFF, oc0, rank * 64);
      asm volatile("cp.async.bulk.commit_group;" ::: "memory");
    }
    __syncwarp();
  } else bar_arrive(13, 512);
  STAMP(9);
  const int x1 = 159 - (eo + 136);
  const uint32_t fs = rb + ((g & 1) ? 2 * x1 : RS_CS + 2 * x1 + 2);
  {
    uint32_t A[2][4][4];
    const uint64_t d5 = mkdesc(cb + W5_OFF, 128, 512), d3 = mkdesc(cb + W3_OFF, 128, 512);
    auto loadA = [&](int m) {
#pragma unroll
      for (int a = 0; a < 2; a++) {
        const uint32_t base = fs + (a ? R_O2 : R_E2) + (4 * (4 - m)) * 16;
        uint32_t* k0 = A[m & 1][2 * a];
        uint32_t* k1 = A[m & 1][2 * a + 1];
        k0[1] = lds32(base); k0[0] = lds32(base + 16); k0[2] = lds32(base + 32); k1[0] = lds32(base + 48); k1[2] = lds32(base + 64);
        k0[3] = copy_reg(k0[0]); k1[1] = copy_reg(k0[2]); k1[3] = copy_reg(k1[0]);
      }
    };
    loadA(2);
#pragma unroll
    for (int m = 2; m <= 4; m++) {
      wg_fence();
#pragma unroll
      for (int k = 0; k < 4; k++) {
        const uint32_t* a = A[m & 1][k];
        const uint64_t desc = ((k >> 1) ? d3 : d5) + (k & 1) * 16 + (m - 2) * 32;
        if (m == 2) wgmma_rs<48, 1>(dacc, a[0], a[1], a[2], a[3], desc, k);
        else if (m == 3) wgmma_rs<40, 1>(dacc, a[0], a[1], a[2], a[3], desc, 1);
        else wgmma_rs<32, 1>(dacc, a[0], a[1], a[2], a[3], desc, 1);
      }
      wg_commit();
      if (m < 4) loadA(m + 1);
      wg_wait0();
    }
    const uint32_t yb = cb + Y2_OFF + br * 3072;
#pragma unroll
    for (int i = 0; i < 6; i += 2) {
      const int mi = lane >> 3;
      const int cidx = 32 * (5 - i - (mi >> 1)) + 16 * hf + 8 * (mi & 1) + (lane & 7);
      stsm4(yb + ysw(cidx), pack_bf16(dacc[4 * i], dacc[4 * i + 1]), pack_bf16(dacc[4 * i + 2], dacc[4 * i + 3]),
            pack_bf16(dacc[4 * i + 4], dacc[4 * i + 5]), pack_bf16(dacc[4 * i + 6], dacc[4 * i + 7]));
    }
  }
  if (ch != 1) bar_arrive(14, 512);
  STAMP(10);
  {
    uint32_t A[2][4][4];
    const uint64_t d9 = mkdesc(cb + W9_OFF, 128, 512), d7 = mkdesc(cb + W7_OFF, 128, 512);
    auto loadA = [&](int m) {
#pragma unroll
      for (int a = 0; a < 2; a++) {
        const uint32_t base = fs + (a ? R_O3 : R_E3) + (4 * (4 - m)) * 16;
        uint32_t* k0 = A[m & 1][2 * a];
        uint32_t* k1 = A[m & 1][2 * a + 1];
        k0[1] = lds32(base); k0[0] = lds32(base + 16); k0[2] = lds32(base + 32); k1[0] = lds32(base + 48); k1[2] = lds32(base + 64);
        k0[3] = copy_reg(k0[0]); k1[1] = copy_reg(k0[2]); k1[3] = copy_reg(k1[0]);
      }
    };
    loadA(2);
#pragma unroll
    for (int m = 2; m <= 3; m++) {
      wg_fence();
#pragma unroll
      for (int k = 0; k < 4; k++) {
        const uint32_t* a = A[m & 1][k];
        const uint64_t desc = ((k >> 1) ? d7 : d9) + (k & 1) * 16 + (m - 2) * 64;
        if (m == 2) wgmma_rs<32, 1>(dacc, a[0], a[1], a[2], a[3], desc, k);
        else wgmma_rs<16, 1>(dacc, a[0], a[1], a[2], a[3], desc, 1);
      }
      wg_commit();
      if (m < 3) loadA(m + 1);
      wg_wait0();
    }
    const uint32_t yb = cb + Y3_OFF + br * 2048;
#pragma unroll
    for (int i = 0; i < 4; i += 2) {
      const int mi = lane >> 3;
      const int cidx = 64 * (1 - (i >> 1)) + 2 * (16 * hf + 8 * (mi & 1) + (lane & 7)) + (mi >> 1);
      stsm4(yb + ysw(cidx), pack_bf16(dacc[4 * i], dacc[4 * i + 1]), pack_bf16(dacc[4 * i + 2], dacc[4 * i + 3]),
            pack_bf16(dacc[4 * i + 4], dacc[4 * i + 5]), pack_bf16(dacc[4 * i + 6], dacc[4 * i + 7]));
    }
  }
  STAMP(11);
  if (ch < 2) {
    bar_arrive(15, 512);
    if (ch == 1) {
      bar_sync(14, 512);
      final_pass<1>(p, sb, 128 + wtid, tag, rank, dab);
      if (wtid == 0) {
        mbar_wait(sb + B_O2);
        fence_async();
        tma_store_box(&tm_out, sb + RAW_OFF + 4096, oc0, 128 + rank * 64);
        asm volatile("cp.async.bulk.commit_group;" ::: "memory");
        asm volatile("cp.async.bulk.wait_group.read 0;" ::: "memory");
      }
    } else if (tid == 0) {
      asm volatile("cp.async.bulk.wait_group.read 0;" ::: "memory");
    }
  } else {
    bar_sync(15, 512);
    final_pass<2>(p, sb, tid, tag, rank, dab);
    STAMP(12);
    if (tid == 256) {
      mbar_wait(sb + B_O3);
      fence_async();
      tma_store_box(&tm_out, sb + RAW_OFF + 8192, oc0, 256 + rank * 64);
      tma_store_box(&tm_out, sb + RAW_OFF + 12288, oc0, 384 + rank * 64);
      asm volatile("cp.async.bulk.commit_group;" ::: "memory");
      asm volatile("cp.async.bulk.wait_group.read 0;" ::: "memory");
    }
  }
  STAMP(13);
}

typedef CUresult (*EncodeFn)(CUtensorMap*, CUtensorMapDataType, cuuint32_t, void*, const cuuint64_t*, const cuuint64_t*,
                             const cuuint32_t*, const cuuint32_t*, CUtensorMapInterleave, CUtensorMapSwizzle,
                             CUtensorMapL2promotion, CUtensorMapFloatOOBfill);

}

extern "C" void kernel_launch(void* const* d_in, const int* in_sizes, int n_in, void* d_out, int out_size) {
  (void)in_sizes; (void)n_in; (void)out_size;
  typedef const __nv_bfloat16* bp;
  Params p;
  p.u = (bp)d_in[0]; p.A_re = (bp)d_in[1]; p.A_im = (bp)d_in[2]; p.B_re = (bp)d_in[3]; p.B_im = (bp)d_in[4];
  p.C_re = (bp)d_in[5]; p.C_im = (bp)d_in[6]; p.A_ldt = (bp)d_in[7]; p.A_D = (bp)d_in[8];
  p.B_lA = (bp)d_in[10]; p.B_Aim = (bp)d_in[11]; p.B_Cre = (bp)d_in[12]; p.B_Cim = (bp)d_in[13];
  p.B_ldt = (bp)d_in[14]; p.B_D = (bp)d_in[15]; p.gw = (bp)d_in[16];
  static EncodeFn enc = nullptr;
  if (!enc) {
    cudaDriverEntryPointQueryResult qr;
    cudaGetDriverEntryPoint("cuTensorMapEncodeTiled", (void**)&enc, cudaEnableDefault, &qr);
    cudaFuncSetAttribute(ssm_kernel, cudaFuncAttributeMaxDynamicSharedMemorySize, SMEM_BYTES);
  }
  CUtensorMap tm_in, tm_out;
  {
    cuuint64_t gd[5] = {512, 2, 4, 4, 64};
    cuuint64_t gs[4] = {1024, 8192, 2048, 32768};
    cuuint32_t bx[5] = {8, 2, 4, 4, 32};
    cuuint32_t es[5] = {1, 1, 1, 1, 1};
    enc(&tm_in, CU_TENSOR_MAP_DATA_TYPE_BFLOAT16, 5, d_in[0], gd, gs, bx, es, CU_TENSOR_MAP_INTERLEAVE_NONE,
        CU_TENSOR_MAP_SWIZZLE_NONE, CU_TENSOR_MAP_L2_PROMOTION_NONE, CU_TENSOR_MAP_FLOAT_OOB_FILL_NONE);
  }
  {
    cuuint64_t gd[3] = {512, 512, 4};
    cuuint64_t gs[2] = {4096, 1024};
    cuuint32_t bx[3] = {8, 64, 4};
    cuuint32_t es[3] = {1, 1, 1};
    enc(&tm_out, CU_TENSOR_MAP_DATA_TYPE_BFLOAT16, 3, d_out, gd, gs, bx, es, CU_TENSOR_MAP_INTERLEAVE_NONE,
        CU_TENSOR_MAP_SWIZZLE_NONE, CU_TENSOR_MAP_L2_PROMOTION_NONE, CU_TENSOR_MAP_FLOAT_OOB_FILL_NONE);
  }
  ssm_kernel<<<NCTA, 512, SMEM_BYTES, cudaStreamPerThread>>>(p, tm_in, tm_out);
}
```

```cpp
#include <cuda_runtime.h>
#include <cuda.h>
#include <cuda_bf16.h>
#include <stdint.h>

namespace {

constexpr int L = 2048, D = 512, NM = 128;
constexpr int NCTA = 128;

constexpr int RAW_OFF = 0;
constexpr int BAR_OFF = 16384;
constexpr int CH_OFF = 16384 + 128;
constexpr int U_CS = 1184;
constexpr int U_OFF = 0;
constexpr int W5_OFF = 4736;
constexpr int W3_OFF = W5_OFF + 3072;
constexpr int W9_OFF = W3_OFF + 3072;
constexpr int W7_OFF = W9_OFF + 2048;
constexpr int S2_OFF = W7_OFF + 2048;
constexpr int R_OFF = S2_OFF + 2048;
constexpr int RD_CS = 1216;
constexpr int RS_CS = 320;
constexpr int R_E2 = 2 * RD_CS, R_O2 = R_E2 + 2 * RS_CS, R_E3 = R_O2 + 2 * RS_CS, R_O3 = R_E3 + 2 * RS_CS;
constexpr int R_BR = R_O3 + 2 * RS_CS;
constexpr int Y_OFF = R_OFF + 2 * R_BR;
constexpr int Y0_OFF = Y_OFF, Y2_OFF = Y_OFF + 8192, Y3_OFF = Y2_OFF + 6144;
constexpr int CH_BYTES = Y_OFF + 18432 + 16;
constexpr int SMEM_BYTES = CH_OFF + 4 * CH_BYTES;
static_assert(CH_BYTES % 128 == 16, "bank staggering of the channel blocks");
constexpr int B_RAW = BAR_OFF, B_U = BAR_OFF + 8, B_O1 = BAR_OFF + 16, B_O2 = BAR_OFF + 24, B_O3 = BAR_OFF + 32;
constexpr int K1024_OFF = BAR_OFF + 64;

__device__ unsigned int g_gate[L];
__device__ unsigned int g_epoch;
__device__ unsigned int g_ticket;

#define STAMP(k)
#define GT(k)

struct Params {
  const __nv_bfloat16 *u, *A_re, *A_im, *B_re, *B_im, *C_re, *C_im, *A_ldt, *A_D;
  const __nv_bfloat16 *B_lA, *B_Aim, *B_Cre, *B_Cim, *B_ldt, *B_D, *gw;
};

template <int N, int TB> __device__ __forceinline__ void wgmma_rs(float* d, uint32_t a0, uint32_t a1, uint32_t a2, uint32_t a3, uint64_t desc, int sc);
template <> __device__ __forceinline__ void wgmma_rs<64, 0>(float* d, uint32_t a0, uint32_t a1, uint32_t a2, uint32_t a3, uint64_t desc, int sc) {
  asm volatile("{\n.reg .pred p;\nsetp.ne.b32 p, %37, 0;\n"
    "wgmma.mma_async.sync.aligned.m64n64k16.f32.bf16.bf16 {%0,%1,%2,%3,%4,%5,%6,%7,%8,%9,%10,%11,%12,%13,%14,%15,%16,%17,%18,%19,%20,%21,%22,%23,%24,%25,%26,%27,%28,%29,%30,%31}, {%32,%33,%34,%35}, %36, p, 1, 1, 0;\n}"
    : "+f"(d[0]), "+f"(d[1]), "+f"(d[2]), "+f"(d[3]), "+f"(d[4]), "+f"(d[5]), "+f"(d[6]), "+f"(d[7]), "+f"(d[8]), "+f"(d[9]), "+f"(d[10]), "+f"(d[11]), "+f"(d[12]), "+f"(d[13]), "+f"(d[14]), "+f"(d[15]), "+f"(d[16]), "+f"(d[17]), "+f"(d[18]), "+f"(d[19]), "+f"(d[20]), "+f"(d[21]), "+f"(d[22]), "+f"(d[23]), "+f"(d[24]), "+f"(d[25]), "+f"(d[26]), "+f"(d[27]), "+f"(d[28]), "+f"(d[29]), "+f"(d[30]), "+f"(d[31]) : "r"(a0), "r"(a1), "r"(a2), "r"(a3), "l"(desc), "r"(sc));
}
template <> __device__ __forceinline__ void wgmma_rs<56, 0>(float* d, uint32_t a0, uint32_t a1, uint32_t a2, uint32_t a3, uint64_t desc, int sc) {
  asm volatile("{\n.reg .pred p;\nsetp.ne.b32 p, %33, 0;\n"
    "wgmma.mma_async.sync.aligned.m64n56k16.f32.bf16.bf16 {%0,%1,%2,%3,%4,%5,%6,%7,%8,%9,%10,%11,%12,%13,%14,%15,%16,%17,%18,%19,%20,%21,%22,%23,%24,%25,%26,%27}, {%28,%29,%30,%31}, %32, p, 1, 1, 0;\n}"
    : "+f"(d[0]), "+f"(d[1]), "+f"(d[2]), "+f"(d[3]), "+f"(d[4]), "+f"(d[5]), "+f"(d[6]), "+f"(d[7]), "+f"(d[8]), "+f"(d[9]), "+f"(d[10]), "+f"(d[11]), "+f"(d[12]), "+f"(d[13]), "+f"(d[14]), "+f"(d[15]), "+f"(d[16]), "+f"(d[17]), "+f"(d[18]), "+f"(d[19]), "+f"(d[20]), "+f"(d[21]), "+f"(d[22]), "+f"(d[23]), "+f"(d[24]), "+f"(d[25]), "+f"(d[26]), "+f"(d[27]) : "r"(a0), "r"(a1), "r"(a2), "r"(a3), "l"(desc), "r"(sc));
}
template <> __device__ __forceinline__ void wgmma_rs<48, 0>(float* d, uint32_t a0, uint32_t a1, uint32_t a2, uint32_t a3, uint64_t desc, int sc) {
  asm volatile("{\n.reg .pred p;\nsetp.ne.b32 p, %29, 0;\n"
    "wgmma.mma_async.sync.aligned.m64n48k16.f32.bf16.bf16 {%0,%1,%2,%3,%4,%5,%6,%7,%8,%9,%10,%11,%12,%13,%14,%15,%16,%17,%18,%19,%20,%21,%22,%23}, {%24,%25,%26,%27}, %28, p, 1, 1, 0;\n}"
    : "+f"(d[0]), "+f"(d[1]), "+f"(d[2]), "+f"(d[3]), "+f"(d[4]), "+f"(d[5]), "+f"(d[6]), "+f"(d[7]), "+f"(d[8]), "+f"(d[9]), "+f"(d[10]), "+f"(d[11]), "+f"(d[12]), "+f"(d[13]), "+f"(d[14]), "+f"(d[15]), "+f"(d[16]), "+f"(d[17]), "+f"(d[18]), "+f"(d[19]), "+f"(d[20]), "+f"(d[21]), "+f"(d[22]), "+f"(d[23]) : "r"(a0), "r"(a1), "r"(a2), "r"(a3), "l"(desc), "r"(sc));
}
template <> __device__ __forceinline__ void wgmma_rs<48, 1>(float* d, uint32_t a0, uint32_t a1, uint32_t a2, uint32_t a3, uint64_t desc, int sc) {
  asm volatile("{\n.reg .pred p;\nsetp.ne.b32 p, %29, 0;\n"
    "wgmma.mma_async.sync.aligned.m64n48k16.f32.bf16.bf16 {%0,%1,%2,%3,%4,%5,%6,%7,%8,%9,%10,%11,%12,%13,%14,%15,%16,%17,%18,%19,%20,%21,%22,%23}, {%24,%25,%26,%27}, %28, p, 1, 1, 1;\n}"
    : "+f"(d[0]), "+f"(d[1]), "+f"(d[2]), "+f"(d[3]), "+f"(d[4]), "+f"(d[5]), "+f"(d[6]), "+f"(d[7]), "+f"(d[8]), "+f"(d[9]), "+f"(d[10]), "+f"(d[11]), "+f"(d[12]), "+f"(d[13]), "+f"(d[14]), "+f"(d[15]), "+f"(d[16]), "+f"(d[17]), "+f"(d[18]), "+f"(d[19]), "+f"(d[20]), "+f"(d[21]), "+f"(d[22]), "+f"(d[23]) : "r"(a0), "r"(a1), "r"(a2), "r"(a3), "l"(desc), "r"(sc));
}
template <> __device__ __forceinline__ void wgmma_rs<40, 1>(float* d, uint32_t a0, uint32_t a1, uint32_t a2, uint32_t a3, uint64_t desc, int sc) {
  asm volatile("{\n.reg .pred p;\nsetp.ne.b32 p, %25, 0;\n"
    "wgmma.mma_async.sync.aligned.m64n40k16.f32.bf16.bf16 {%0,%1,%2,%3,%4,%5,%6,%7,%8,%9,%10,%11,%12,%13,%14,%15,%16,%17,%18,%19}, {%20,%21,%22,%23}, %24, p, 1, 1, 1;\n}"
    : "+f"(d[0]), "+f"(d[1]), "+f"(d[2]), "+f"(d[3]), "+f"(d[4]), "+f"(d[5]), "+f"(d[6]), "+f"(d[7]), "+f"(d[8]), "+f"(d[9]), "+f"(d[10]), "+f"(d[11]), "+f"(d[12]), "+f"(d[13]), "+f"(d[14]), "+f"(d[15]), "+f"(d[16]), "+f"(d[17]), "+f"(d[18]), "+f"(d[19]) : "r"(a0), "r"(a1), "r"(a2), "r"(a3), "l"(desc), "r"(sc));
}
template <> __device__ __forceinline__ void wgmma_rs<32, 1>(float* d, uint32_t a0, uint32_t a1, uint32_t a2, uint32_t a3, uint64_t desc, int sc) {
  asm volatile("{\n.reg .pred p;\nsetp.ne.b32 p, %21, 0;\n"
    "wgmma.mma_async.sync.aligned.m64n32k16.f32.bf16.bf16 {%0,%1,%2,%3,%4,%5,%6,%7,%8,%9,%10,%11,%12,%13,%14,%15}, {%16,%17,%18,%19}, %20, p, 1, 1, 1;\n}"
    : "+f"(d[0]), "+f"(d[1]), "+f"(d[2]), "+f"(d[3]), "+f"(d[4]), "+f"(d[5]), "+f"(d[6]), "+f"(d[7]), "+f"(d[8]), "+f"(d[9]), "+f"(d[10]), "+f"(d[11]), "+f"(d[12]), "+f"(d[13]), "+f"(d[14]), "+f"(d[15]) : "r"(a0), "r"(a1), "r"(a2), "r"(a3), "l"(desc), "r"(sc));
}
template <> __device__ __forceinline__ void wgmma_rs<16, 1>(float* d, uint32_t a0, uint32_t a1, uint32_t a2, uint32_t a3, uint64_t desc, int sc) {
  asm volatile("{\n.reg .pred p;\nsetp.ne.b32 p, %13, 0;\n"
    "wgmma.mma_async.sync.aligned.m64n16k16.f32.bf16.bf16 {%0,%1,%2,%3,%4,%5,%6,%7}, {%8,%9,%10,%11}, %12, p, 1, 1, 1;\n}"
    : "+f"(d[0]), "+f"(d[1]), "+f"(d[2]), "+f"(d[3]), "+f"(d[4]), "+f"(d[5]), "+f"(d[6]), "+f"(d[7]) : "r"(a0), "r"(a1), "r"(a2), "r"(a3), "l"(desc), "r"(sc));
}

__device__ __forceinline__ uint32_t pack_bf16(float lo, float hi) {
  uint32_t r; asm("cvt.rn.bf16x2.f32 %0, %1, %2;" : "=r"(r) : "f"(hi), "f"(lo)); return r;
}
__device__ __forceinline__ float bf_lo(uint32_t v) { return __uint_as_float(v << 16); }
__device__ __forceinline__ float bf_hi(uint32_t v) { return __uint_as_float(v & 0xffff0000u); }
__device__ __forceinline__ float bf_round(float x) { return bf_lo(pack_bf16(x, 0.f)); }
__device__ __forceinline__ uint32_t hmul2(uint32_t a, uint32_t b) { uint32_t r; asm("mul.rn.bf16x2 %0, %1, %2;" : "=r"(r) : "r"(a), "r"(b)); return r; }
__device__ __forceinline__ uint32_t hadd2(uint32_t a, uint32_t b) { uint32_t r; asm("add.rn.bf16x2 %0, %1, %2;" : "=r"(r) : "r"(a), "r"(b)); return r; }
__device__ __forceinline__ uint32_t hsub2(uint32_t a, uint32_t b) { uint32_t r; asm("sub.rn.bf16x2 %0, %1, %2;" : "=r"(r) : "r"(a), "r"(b)); return r; }
__device__ __forceinline__ uint32_t hfma2(uint32_t a, uint32_t b, uint32_t c) { uint32_t r; asm("fma.rn.bf16x2 %0, %1, %2, %3;" : "=r"(r) : "r"(a), "r"(b), "r"(c)); return r; }
__device__ __forceinline__ uint32_t hfms2(uint32_t a, uint32_t b, uint32_t c) {
  uint32_t r; asm("{\n.reg .b32 n;\nneg.bf16x2 n, %3;\nfma.rn.bf16x2 %0, %1, %2, n;\n}" : "=r"(r) : "r"(a), "r"(b), "r"(c)); return r;
}

__device__ __forceinline__ void sts16(uint32_t a, uint32_t v) { asm volatile("st.shared.b16 [%0], %1;" ::"r"(a), "h"((unsigned short)v) : "memory"); }
__device__ __forceinline__ void sts32(uint32_t a, uint32_t v) { asm volatile("st.shared.b32 [%0], %1;" ::"r"(a), "r"(v) : "memory"); }
__device__ __forceinline__ void sts128(uint32_t a, uint32_t x, uint32_t y, uint32_t z, uint32_t w) {
  asm volatile("st.shared.v4.b32 [%0], {%1,%2,%3,%4};" ::"r"(a), "r"(x), "r"(y), "r"(z), "r"(w) : "memory");
}
__device__ __forceinline__ uint32_t lds32(uint32_t a) { uint32_t v; asm volatile("ld.shared.b32 %0, [%1];" : "=r"(v) : "r"(a) : "memory"); return v; }
__device__ __forceinline__ uint2 lds64(uint32_t a) { uint2 v; asm volatile("ld.shared.v2.b32 {%0,%1}, [%2];" : "=r"(v.x), "=r"(v.y) : "r"(a) : "memory"); return v; }
__device__ __forceinline__ uint4 lds128(uint32_t a) {
  uint4 v; asm volatile("ld.shared.v4.b32 {%0,%1,%2,%3}, [%4];" : "=r"(v.x), "=r"(v.y), "=r"(v.z), "=r"(v.w) : "r"(a) : "memory"); return v;
}
__device__ __forceinline__ void ldsm4(uint32_t a, uint32_t& r0, uint32_t& r1, uint32_t& r2, uint32_t& r3) {
  asm volatile("ldmatrix.sync.aligned.m8n8.x4.shared.b16 {%0,%1,%2,%3}, [%4];" : "=r"(r0), "=r"(r1), "=r"(r2), "=r"(r3) : "r"(a) : "memory");
}
__device__ __forceinline__ void ldsm4t(uint32_t a, uint32_t& r0, uint32_t& r1, uint32_t& r2, uint32_t& r3) {
  asm volatile("ldmatrix.sync.aligned.m8n8.x4.trans.shared.b16 {%0,%1,%2,%3}, [%4];" : "=r"(r0), "=r"(r1), "=r"(r2), "=r"(r3) : "r"(a) : "memory");
}
__device__ __forceinline__ void stsm4(uint32_t a, uint32_t r0, uint32_t r1, uint32_t r2, uint32_t r3) {
  asm volatile("stmatrix.sync.aligned.m8n8.x4.shared.b16 [%0], {%1,%2,%3,%4};" ::"r"(a), "r"(r0), "r"(r1), "r"(r2), "r"(r3) : "memory");
}
__device__ __forceinline__ void stsm4t(uint32_t a, uint32_t r0, uint32_t r1, uint32_t r2, uint32_t r3) {
  asm volatile("stmatrix.sync.aligned.m8n8.x4.trans.shared.b16 [%0], {%1,%2,%3,%4};" ::"r"(a), "r"(r0), "r"(r1), "r"(r2), "r"(r3) : "memory");
}
__device__ __forceinline__ void mma16816(float* c, uint32_t a0, uint32_t a1, uint32_t a2, uint32_t a3, uint32_t b0, uint32_t b1) {
  asm("mma.sync.aligned.m16n8k16.row.col.f32.bf16.bf16.f32 {%0,%1,%2,%3}, {%4,%5,%6,%7}, {%8,%9}, {%0,%1,%2,%3};"
      : "+f"(c[0]), "+f"(c[1]), "+f"(c[2]), "+f"(c[3]) : "r"(a0), "r"(a1), "r"(a2), "r"(a3), "r"(b0), "r"(b1));
}
__device__ __forceinline__ void bar_sync(int id, int n) { asm volatile("bar.sync %0, %1;" ::"r"(id), "r"(n) : "memory"); }
__device__ __forceinline__ void bar_arrive(int id, int n) { asm volatile("bar.arrive %0, %1;" ::"r"(id), "r"(n) : "memory"); }
__device__ __forceinline__ void wg_fence() { asm volatile("wgmma.fence.sync.aligned;" ::: "memory"); }
__device__ __forceinline__ void wg_commit() { asm volatile("wgmma.commit_group.sync.aligned;" ::: "memory"); }
__device__ __forceinline__ void wg_wait0() { asm volatile("wgmma.wait_group.sync.aligned 0;" ::: "memory"); }
__device__ __forceinline__ void fence_async() { asm volatile("fence.proxy.async.shared::cta;" ::: "memory"); }
__device__ __forceinline__ uint32_t copy_reg(uint32_t v) { uint32_t r; asm volatile("mov.b32 %0, %1;" : "=r"(r) : "r"(v)); return r; }
__device__ __forceinline__ uint64_t mkdesc(uint32_t addr, uint32_t lbo, uint32_t sbo) {
  return (uint64_t)((addr & 0x3FFFF) >> 4) | ((uint64_t)(lbo >> 4) << 16) | ((uint64_t)(sbo >> 4) << 32);
}
__device__ __forceinline__ uint32_t mapa(uint32_t a, uint32_t rank) {
  uint32_t r; asm("mapa.shared::cluster.u32 %0, %1, %2;" : "=r"(r) : "r"(a), "r"(rank)); return r;
}
__device__ __forceinline__ void mbar_init_expect(uint32_t bar, uint32_t bytes) {
  asm volatile("mbarrier.init.shared::cta.b64 [%0], 1;" ::"r"(bar) : "memory");
  asm volatile("mbarrier.arrive.expect_tx.shared::cta.b64 _, [%0], %1;" ::"r"(bar), "r"(bytes) : "memory");
}
__device__ __forceinline__ void mbar_wait(uint32_t bar) {
  for (int it = 0; it < (1 << 22); it++) {
    uint32_t ok;
    asm volatile("{\n.reg .pred p;\nmbarrier.try_wait.parity.acquire.cluster.shared::cta.b64 p, [%1], 0;\nselp.u32 %0, 1, 0, p;\n}"
                 : "=r"(ok) : "r"(bar) : "memory");
    if (ok) return;
  }
  __trap();
}
__device__ __forceinline__ void st_async4(uint32_t a, uint32_t bar, uint32_t x, uint32_t y, uint32_t z, uint32_t w) {
  asm volatile("st.async.weak.shared::cluster.mbarrier::complete_tx::bytes.v4.b32 [%0], {%2,%3,%4,%5}, [%1];"
               ::"r"(a), "r"(bar), "r"(x), "r"(y), "r"(z), "r"(w) : "memory");
}
__device__ __forceinline__ void st_async2(uint32_t a, uint32_t bar, uint32_t x, uint32_t y) {
  asm volatile("st.async.weak.shared::cluster.mbarrier::complete_tx::bytes.v2.b32 [%0], {%2,%3}, [%1];"
               ::"r"(a), "r"(bar), "r"(x), "r"(y) : "memory");
}

struct cf { float re, im; };
__device__ __forceinline__ cf cmul(cf a, cf b) { return {fmaf(a.re, b.re, -a.im * b.im), fmaf(a.re, b.im, a.im * b.re)}; }
__device__ __forceinline__ cf csq(cf a) { return {fmaf(a.re, a.re, -a.im * a.im), (a.re + a.re) * a.im}; }
__device__ __forceinline__ cf cexp_p(float xl, float y, float p) {
  float mag; asm("ex2.approx.ftz.f32 %0, %1;" : "=f"(mag) : "f"(xl * p));
  const float th = y * p;
  const float k = rintf(th * 0.15915494309189535f);
  float r = fmaf(k, -6.2831854820251465f, th);
  r = fmaf(k, 1.7484555314695172e-07f, r);
  return {mag * __cosf(r), mag * __sinf(r)};
}
__device__ __forceinline__ uint32_t ysw(int c) { return (uint32_t)(c ^ ((c >> 3) & 3)) * 16u; }

__device__ __forceinline__ float make_tables(cf c, cf z1, cf z128, uint32_t tb, uint32_t mu) {
  const cf z2 = csq(z1), z4 = csq(z2), z8 = csq(z4);
  const cf z16 = csq(z8), z24 = cmul(z16, z8), z32 = csq(z16), z40 = cmul(z32, z8), z48 = csq(z24), z56 = cmul(z32, z24), z64 = csq(z32);
  sts128(tb + 0 * 512, pack_bf16(1.f, z8.re), pack_bf16(z16.re, z24.re), pack_bf16(z32.re, z40.re), pack_bf16(z48.re, z56.re));
  sts128(tb + 1 * 512, pack_bf16(0.f, -z8.im), pack_bf16(-z16.im, -z24.im), pack_bf16(-z32.im, -z40.im), pack_bf16(-z48.im, -z56.im));
  const cf z256 = csq(z128), z512 = csq(z256), z1024 = csq(z512);
  const cf h1 = cmul(c, z128), h2 = cmul(c, z256), h3 = cmul(h1, z256), h4 = cmul(c, z512), h5 = cmul(h1, z512), h6 = cmul(h2, z512), h7 = cmul(h3, z512);
  sts128(tb + 4 * 512, pack_bf16(c.re, h1.re), pack_bf16(h2.re, h3.re), pack_bf16(h4.re, h5.re), pack_bf16(h6.re, h7.re));
  sts128(tb + 5 * 512, pack_bf16(c.im, h1.im), pack_bf16(h2.im, h3.im), pack_bf16(h4.im, h5.im), pack_bf16(h6.im, h7.im));
  const cf e1 = cmul(c, z1), e3 = cmul(e1, z2), e129 = cmul(h1, z1), e131 = cmul(e129, z2);
  const cf e2 = cmul(c, z2), e130 = cmul(h1, z2), e258 = cmul(h2, z2), e386 = cmul(h3, z2);
  sts128(tb + 2 * 512, pack_bf16(e1.re, e3.re), pack_bf16(e129.re, e131.re), pack_bf16(e2.re, e130.re), pack_bf16(e258.re, e386.re));
  sts128(tb + 3 * 512, pack_bf16(e1.im, e3.im), pack_bf16(e129.im, e131.im), pack_bf16(e2.im, e130.im), pack_bf16(e258.im, e386.im));
  const uint32_t m0 = pack_bf16(z64.re, -z64.im), m1 = pack_bf16(z4.re, z4.im), m2 = pack_bf16(z1024.re, z1024.im);
  sts16(mu, m0); sts16(mu + 64, m0 >> 16); sts16(mu + 128, m1); sts16(mu + 192, m1 >> 16); sts16(mu + 256, m2); sts16(mu + 320, m2 >> 16);
  const cf z2048 = csq(z1024);
  return fmaf(c.re, z2048.re, -c.im * z2048.im);
}

__device__ __forceinline__ void use_tables(float (*acc)[4], uint32_t tb, uint32_t mu, int lane) {
  const uint32_t ta = tb + (lane >> 3) * 512 + (lane & 7) * 16;
  const uint32_t tb2 = tb + 2048 + ((lane >> 3) & 1) * 512 + (lane >> 4) * 128 + (lane & 7) * 16;
  const uint32_t ma = mu + (lane >> 3) * 64;
  const uint32_t mb2 = mu + 256 + ((lane >> 3) & 1) * 64 + (lane >> 4) * 16;
#pragma unroll
  for (int kp = 0; kp < 2; kp++) {
    uint32_t h2r[2], h2i[2], yr[2], yi[2];
    ldsm4t(tb2 + kp * 256, h2r[0], h2i[0], h2r[1], h2i[1]);
    ldsm4(mb2 + kp * 32, yr[0], yi[0], yr[1], yi[1]);
#pragma unroll
    for (int k2 = 0; k2 < 2; k2++) {
      const int kk = kp * 2 + k2;
      uint32_t m1r, m1i, h1r, h1i, ar, ai, br_, bi;
      ldsm4t(ta + kk * 128, m1r, m1i, h1r, h1i);
      ldsm4(ma + kk * 16, ar, ai, br_, bi);
      const uint32_t m2r = hfms2(m1r, ar, hmul2(m1i, ai)), m2i = hfma2(m1r, ai, hmul2(m1i, ar));
      mma16816(acc[0], m1r, m2r, m1i, m2i, h1r, h1i);
      mma16816(acc[2], m1r, m2r, m1i, m2i, h2r[k2], h2i[k2]);
      const uint32_t xr = hfms2(h1r, br_, hmul2(h1i, bi)), xi = hfma2(h1r, bi, hmul2(h1i, br_));
      mma16816(acc[1], m1r, m2r, m1i, m2i, xr, xi);
      const uint32_t wr = hfms2(h2r[k2], br_, hmul2(h2i[k2], bi)), wi = hfma2(h2r[k2], bi, hmul2(h2i[k2], br_));
      mma16816(acc[3], m1r, m2r, m1i, m2i, wr, wi);
      const uint32_t vr = hfms2(h2r[k2], yr[k2], hmul2(h2i[k2], yi[k2])), vi = hfma2(h2r[k2], yi[k2], hmul2(h2i[k2], yr[k2]));
      mma16816(acc[4], m1r, m2r, m1i, m2i, vr, vi);
    }
  }
}

__device__ __noinline__ uint32_t gate_slow(const __nv_bfloat16* u, const __nv_bfloat16* gw, int row) {
  float s = 0.f;
  const uint32_t* xr = (const uint32_t*)(u + (size_t)row * D);
  const uint32_t* wr = (const uint32_t*)gw;
#pragma unroll 1
  for (int j = 0; j < D / 2; j++) { const uint32_t pr = hmul2(xr[j], wr[j]); s += bf_lo(pr); s += bf_hi(pr); }
  s = bf_round(s);
  return pack_bf16(1.f / (1.f + expf(-s)), 0.f);
}

template <int LVL>
__device__ __forceinline__ void final_pass(const Params& p, uint32_t sb, int x, uint32_t tag, uint32_t rank) {
  const uint2 dA = *(const uint2*)(p.A_D + blockIdx.x * 4), dB = *(const uint2*)(p.B_D + blockIdx.x * 4);
  uint4 gv;
  const unsigned int* gp = g_gate + x * 4;
  int spins = 0;
  while (true) {
    asm volatile("ld.relaxed.gpu.global.v4.u32 {%0,%1,%2,%3}, [%4];" : "=r"(gv.x), "=r"(gv.y), "=r"(gv.z), "=r"(gv.w) : "l"(gp) : "memory");
    if ((gv.x >> 16) == tag && (gv.y >> 16) == tag && (gv.z >> 16) == tag && (gv.w >> 16) == tag) break;
    if (++spins > (1 << 16)) {
      gv = make_uint4(gate_slow(p.u, p.gw, x * 4), gate_slow(p.u, p.gw, x * 4 + 1), gate_slow(p.u, p.gw, x * 4 + 2), gate_slow(p.u, p.gw, x * 4 + 3));
      break;
    }
  }
  const uint32_t g01 = __byte_perm(gv.x, gv.y, 0x5410), g23 = __byte_perm(gv.z, gv.w, 0x5410);
  const uint32_t one2 = 0x3f803f80u;
  const uint32_t h01 = hsub2(one2, g01), h23 = hsub2(one2, g23);
  const int c = x >> 1;
  const uint32_t ho = (x & 1) * 8;
  uint32_t o01[4], o23[4];
#pragma unroll
  for (int k = 0; k < 4; k++) {
    const uint32_t b = sb + CH_OFF + k * CH_BYTES;
    uint32_t a01, a23, b01, b23;
    const uint2 a = lds64(b + Y0_OFF + ysw(c) + ho), bb = lds64(b + Y0_OFF + 4096 + ysw(c) + ho);
    if (LVL == 0) { a01 = a.x; a23 = a.y; b01 = bb.x; b23 = bb.y; }
    else {
      float ya[4], yb[4];
      const uint2 a2 = lds64(b + Y2_OFF + ysw(c - 64) + ho), b2 = lds64(b + Y2_OFF + 3072 + ysw(c - 64) + ho);
      ya[0] = bf_lo(a.x) + bf_lo(a2.x); ya[1] = bf_hi(a.x) + bf_hi(a2.x); ya[2] = bf_lo(a.y) + bf_lo(a2.y); ya[3] = bf_hi(a.y) + bf_hi(a2.y);
      yb[0] = bf_lo(bb.x) + bf_lo(b2.x); yb[1] = bf_hi(bb.x) + bf_hi(b2.x); yb[2] = bf_lo(bb.y) + bf_lo(b2.y); yb[3] = bf_hi(bb.y) + bf_hi(b2.y);
      if (LVL == 2) {
        const uint2 a3 = lds64(b + Y3_OFF + ysw(c - 128) + ho), b3 = lds64(b + Y3_OFF + 2048 + ysw(c - 128) + ho);
        const uint2 s = lds64(b + S2_OFF + (c - 128) * 16 + ho);
        const uint2 kk = lds64(sb + K1024_OFF + k * 8);
        const float ka = __uint_as_float(kk.x), kb = __uint_as_float(kk.y);
        ya[0] += fmaf(ka, bf_lo(s.x), bf_lo(a3.x)); ya[1] += fmaf(ka, bf_hi(s.x), bf_hi(a3.x));
        ya[2] += fmaf(ka, bf_lo(s.y), bf_lo(a3.y)); ya[3] += fmaf(ka, bf_hi(s.y), bf_hi(a3.y));
        yb[0] += fmaf(kb, bf_lo(s.x), bf_lo(b3.x)); yb[1] += fmaf(kb, bf_hi(s.x), bf_hi(b3.x));
        yb[2] += fmaf(kb, bf_lo(s.y), bf_lo(b3.y)); yb[3] += fmaf(kb, bf_hi(s.y), bf_hi(b3.y));
      }
      a01 = pack_bf16(ya[0], ya[1]); a23 = pack_bf16(ya[2], ya[3]); b01 = pack_bf16(yb[0], yb[1]); b23 = pack_bf16(yb[2], yb[3]);
    }
    const uint2 uu = lds64(b + U_OFF + (c & 3) * U_CS + (63 - (c >> 2)) * 16 + ho);
    const uint32_t da2 = __byte_perm((k & 2) ? dA.y : dA.x, 0, (k & 1) ? 0x3232 : 0x1010);
    const uint32_t db2 = __byte_perm((k & 2) ? dB.y : dB.x, 0, (k & 1) ? 0x3232 : 0x1010);
    a01 = hadd2(a01, hmul2(uu.x, da2)); a23 = hadd2(a23, hmul2(uu.y, da2));
    b01 = hadd2(b01, hmul2(uu.x, db2)); b23 = hadd2(b23, hmul2(uu.y, db2));
    o01[k] = hadd2(hmul2(g01, a01), hmul2(h01, b01));
    o23[k] = hadd2(hmul2(g23, a23), hmul2(h23, b23));
  }
  const uint32_t owner = (x >> 6) & 1;
  const uint32_t dst = mapa(sb + RAW_OFF + (x >> 7) * 4096 + (x & 63) * 16 + rank * 8, owner);
  const uint32_t bar = mapa(sb + (LVL == 0 ? B_O1 : LVL == 1 ? B_O2 : B_O3), owner);
  st_async2(dst, bar, __byte_perm(o01[0], o01[1], 0x5410), __byte_perm(o01[2], o01[3], 0x5410));
  st_async2(dst + 1024, bar, __byte_perm(o01[0], o01[1], 0x7632), __byte_perm(o01[2], o01[3], 0x7632));
  st_async2(dst + 2048, bar, __byte_perm(o23[0], o23[1], 0x5410), __byte_perm(o23[2], o23[3], 0x5410));
  st_async2(dst + 3072, bar, __byte_perm(o23[0], o23[1], 0x7632), __byte_perm(o23[2], o23[3], 0x7632));
}

__device__ __forceinline__ void tma_store_box(const CUtensorMap* tm, uint32_t src, int c0, int x0) {
  asm volatile("cp.async.bulk.tensor.3d.global.shared::cta.bulk_group [%0, {%2, %3, %4}], [%1];"
               ::"l"(tm), "r"(src), "r"(c0), "r"(x0), "r"(0) : "memory");
}

__global__ void __cluster_dims__(2, 1, 1) __launch_bounds__(512, 1)
ssm_kernel(const Params p, const __grid_constant__ CUtensorMap tm_in, const __grid_constant__ CUtensorMap tm_out) {
  extern __shared__ __align__(1024) unsigned char smem_raw[];
  const uint32_t sb = (uint32_t)__cvta_generic_to_shared(smem_raw);
  const int tid = threadIdx.x, lane = tid & 31;
  const int warp = __shfl_sync(0xffffffffu, tid >> 5, 0);
  const int ch = warp >> 2, wq = warp & 3, br = wq >> 1, hf = wq & 1;
  const int g = lane >> 2, t = lane & 3;
  const int d = blockIdx.x * 4 + ch;
  const uint32_t rank = blockIdx.x & 1;
  const uint32_t cb = sb + CH_OFF + ch * CH_BYTES;
  const int wtid = tid & 127;
  STAMP(0); GT(0);

  if (tid == 0) {
    mbar_init_expect(sb + B_RAW, 16384);
    asm volatile("fence.proxy.async.shared::cta;" ::: "memory");
    asm volatile("cp.async.bulk.tensor.5d.shared::cluster.global.mbarrier::complete_tx::bytes [%0], [%1, {%3, %4, %4, %4, %5}], [%2];"
                 ::"r"(sb + RAW_OFF), "l"(&tm_in), "r"(sb + B_RAW), "r"((int)(blockIdx.x >> 1) * 8), "r"(0), "r"((int)rank * 32) : "memory");
    mbar_init_expect(sb + B_U, 16384);
    mbar_init_expect(sb + B_O1, 4096);
    mbar_init_expect(sb + B_O2, 4096);
    mbar_init_expect(sb + B_O3, 8192);
    asm volatile("fence.mbarrier_init.release.cluster;" ::: "memory");
  }
  __syncwarp();
  asm volatile("barrier.cluster.arrive.relaxed.aligned;" ::: "memory");

  const int moff = d * NM + hf * 64 + lane * 2;
  const uint32_t q0 = *(const uint32_t*)((br ? p.B_lA : p.A_re) + moff), q1 = *(const uint32_t*)((br ? p.B_Aim : p.A_im) + moff);
  const uint32_t q2 = *(const uint32_t*)((br ? p.B_Cre : p.C_re) + moff), q3 = *(const uint32_t*)((br ? p.B_Cim : p.C_im) + moff);
  const uint32_t q4 = *(const uint32_t*)((br ? p.B_Cre : p.B_re) + moff), q5 = *(const uint32_t*)((br ? p.B_Cim : p.B_im) + moff);
  const uint2 ldt4 = *(const uint2*)((br ? p.B_ldt : p.A_ldt) + blockIdx.x * 4);
  const int grow = blockIdx.x * 16 + warp;
  const uint4 gx0 = *(const uint4*)(p.u + (size_t)grow * D + lane * 8), gx1 = *(const uint4*)(p.u + (size_t)grow * D + 256 + lane * 8);
  const uint4 gw0 = *(const uint4*)(p.gw + lane * 8), gw1 = *(const uint4*)(p.gw + 256 + lane * 8);
  unsigned int epoch;
  asm volatile("ld.relaxed.gpu.global.u32 %0, [%1];" : "=r"(epoch) : "l"(&g_epoch) : "memory");

  for (int i = wtid & 63; i < R_BR / 16; i += 64) sts128(cb + R_OFF + br * R_BR + i * 16, 0, 0, 0, 0);
  if (wtid < 32) sts128(cb + U_OFF + (wtid >> 3) * U_CS + (64 + (wtid & 7)) * 16, 0, 0, 0, 0);
  STAMP(1);

  float acc[5][4];
  float k2048;
  const uint32_t scr = cb + Y_OFF + wq * 4608;
  {
    const uint32_t scr1 = cb + W5_OFF + wq * 3072;
    const uint32_t ldt2 = (ch & 2) ? ldt4.y : ldt4.x;
    const float dt = bf_round(expf((ch & 1) ? bf_hi(ldt2) : bf_lo(ldt2)));
#pragma unroll
    for (int i = 0; i < 5; i++) acc[i][0] = acc[i][1] = acc[i][2] = acc[i][3] = 0.f;
    cf c[2], z1[2], z128[2];
#pragma unroll
    for (int r = 0; r < 2; r++) {
      float v0 = r ? bf_hi(q0) : bf_lo(q0), v1 = r ? bf_hi(q1) : bf_lo(q1), v2 = r ? bf_hi(q2) : bf_lo(q2);
      float v3 = r ? bf_hi(q3) : bf_lo(q3), v4 = r ? bf_hi(q4) : bf_lo(q4), v5 = r ? bf_hi(q5) : bf_lo(q5);
      if (br == 0) { c[r] = cmul(cf{v2, v3}, cf{dt * v4, dt * v5}); }
      else { v0 = -bf_round(expf(v0)); c[r] = cf{2.f * dt * v2, 2.f * dt * v3}; }
      const float xl = (dt * v0) * 1.4426950408889634f, y = dt * v1;
      z1[r] = cexp_p(xl, y, 1.f); z128[r] = cexp_p(xl, y, 128.f);
    }
    STAMP(2);
    k2048 = 0.f;
#pragma unroll 1
    for (int step = 0; step < 4; step++) {
      const int mid = (step == 1 || step == 2);
      const int isC = mid ? ((step ^ ch) & 1) : (step == 3);
      const int r = mid ? (isC ^ 1) : (step == 3);
      const uint32_t tbl = r ? scr1 : scr, mu = scr + 3072 + r * 384;
      if (isC) { __syncwarp(); use_tables(acc, tbl, mu, lane); }
      else k2048 += make_tables(r ? c[1] : c[0], r ? z1[1] : z1[0], r ? z128[1] : z128[0], tbl + lane * 16, mu + lane * 2);
    }
#pragma unroll
    for (int o = 16; o; o >>= 1) k2048 += __shfl_xor_sync(0xffffffffu, k2048, o);
  }
  STAMP(3);
  __syncwarp();
  {
    const uint32_t xs = scr + lane * 16;
    sts128(xs, __float_as_uint(hf ? acc[0][0] : acc[1][0]), __float_as_uint(hf ? acc[0][1] : acc[1][1]),
           __float_as_uint(hf ? acc[0][2] : acc[1][2]), __float_as_uint(hf ? acc[0][3] : acc[1][3]));
    sts128(xs + 512, __float_as_uint(hf ? acc[2][0] : acc[3][0]), __float_as_uint(hf ? acc[2][1] : acc[3][1]),
           __float_as_uint(hf ? acc[2][2] : acc[3][2]), __float_as_uint(hf ? acc[2][3] : acc[3][3]));
    sts128(xs + 1024, __float_as_uint(hf ? acc[4][0] : acc[4][2]), __float_as_uint(hf ? acc[4][1] : acc[4][3]), __float_as_uint(k2048), 0);
  }

  asm volatile("barrier.cluster.wait.aligned;" ::: "memory");
  mbar_wait(sb + B_RAW);
  STAMP(4);
  {
    const uint32_t dst = mapa(sb + CH_OFF + (g & 3) * CH_BYTES + U_OFF + t * U_CS + (63 - rank * 32 - warp * 2) * 16, g >> 2);
    const uint32_t bar = mapa(sb + B_U, g >> 2);
#pragma unroll
    for (int i = 0; i < 2; i++) {
      uint32_t r0, r1, r2, r3;
      ldsm4t(sb + RAW_OFF + (warp * 2 + i) * 512 + lane * 16, r0, r1, r2, r3);
      st_async4(dst - i * 16, bar, r0, r1, r2, r3);
    }
  }

  STAMP(14);
  bar_sync(1 + (warp >> 1), 64);
  STAMP(15);
  {
    const uint32_t xo = cb + Y_OFF + (wq ^ 1) * 4608 + lane * 16;
    const uint4 o0 = lds128(xo), o1 = lds128(xo + 512), o2 = lds128(xo + 1024);
    const uint32_t rb = cb + R_OFF + br * R_BR;
    const uint32_t v01 = pack_bf16((hf ? acc[1][0] : acc[0][0]) + __uint_as_float(o0.x), (hf ? acc[1][1] : acc[0][1]) + __uint_as_float(o0.y));
    const uint32_t v23 = pack_bf16((hf ? acc[1][2] : acc[0][2]) + __uint_as_float(o0.z), (hf ? acc[1][3] : acc[0][3]) + __uint_as_float(o0.w));
    const uint32_t v45 = pack_bf16((hf ? acc[3][0] : acc[2][0]) + __uint_as_float(o1.x), (hf ? acc[3][1] : acc[2][1]) + __uint_as_float(o1.y));
    const uint32_t v67 = pack_bf16((hf ? acc[3][2] : acc[2][2]) + __uint_as_float(o1.z), (hf ? acc[3][3] : acc[2][3]) + __uint_as_float(o1.w));
    const uint32_t v89 = pack_bf16((hf ? acc[4][2] : acc[4][0]) + __uint_as_float(o2.x), (hf ? acc[4][3] : acc[4][1]) + __uint_as_float(o2.y));
    {
      const int a0 = (t & 2) ? ((t & 1) ? 258 : 2) : ((t & 1) ? 129 : 1), da = (t & 2) ? 128 : 2;
      const uint32_t a = rb + 2 * (559 - (a0 + 8 * g + 4 * hf)), b = a - 2 * da;
      sts16(a, v01); sts16(a + RD_CS + 2, v01); sts16(b, v01 >> 16); sts16(b + RD_CS + 2, v01 >> 16);
      sts16(a - 128, v23); sts16(a - 128 + RD_CS + 2, v23); sts16(b - 128, v23 >> 16); sts16(b - 128 + RD_CS + 2, v23 >> 16);
    }
    {
      const bool lo = t < 2;
      const uint32_t a = lo ? rb + 2 * (559 - (256 * t + 8 * g + 4 * hf)) : rb + (hf ? R_O2 : R_E2 + 2) + 2 * (159 - (32 * t + g));
      const uint32_t s1 = lo ? 256 : 32, s2 = lo ? 128 : 16, cs = lo ? RD_CS + 2 : RS_CS + 2;
      const bool p512 = (lane == 2) && (hf == 0);
      const uint32_t a00 = p512 ? rb + 2 * (559 - 512) : a, c00 = p512 ? RD_CS + 2 : cs;
      sts16(a00, v45); sts16(a00 + c00, v45);
      sts16(a - s1, v45 >> 16); sts16(a - s1 + cs, v45 >> 16);
      sts16(a - s2, v67); sts16(a - s2 + cs, v67);
      sts16(a - s1 - s2, v67 >> 16); sts16(a - s1 - s2 + cs, v67 >> 16);
      if (t == 1 || p512) {
        const bool p256 = (lane == 1) && (hf == 0);
        sts16(a00 - 2, v45); sts16(a00 - 2 + RD_CS + 2, v45);
        if (!p256) { sts16(a00 + 2, v45); sts16(a00 + 2 + RD_CS + 2, v45); }
        if (p512) { sts16(a00 - 4, v45); sts16(a00 - 4 + RD_CS + 2, v45); }
        else {
          sts16(a - 256 - 2, v45 >> 16); sts16(a - 256 + RD_CS, v45 >> 16); sts16(a - 256 + 2, v45 >> 16); sts16(a - 256 + RD_CS + 4, v45 >> 16);
          sts16(a - 128 - 2, v67); sts16(a - 128 + RD_CS, v67); sts16(a - 128 + 2, v67); sts16(a - 128 + RD_CS + 4, v67);
          sts16(a - 384 - 2, v67 >> 16); sts16(a - 384 + RD_CS, v67 >> 16); sts16(a - 384 + 2, v67 >> 16); sts16(a - 384 + RD_CS + 4, v67 >> 16);
        }
      }
    }
    {
      const int idx = 64 + 16 * t + 4 * hf + (g >> 1);
      const uint32_t a = rb + ((g & 1) ? R_O3 : R_E3 + 2) + 2 * (159 - idx);
      const bool p1024 = (lane == 0) && (hf == 0);
      const uint32_t a00 = p1024 ? rb + R_E2 + 2 * (159 - 127) : a;
      sts16(a00, v89); sts16(a00 + RS_CS + 2, v89);
      sts16(a - 16, v89 >> 16); sts16(a - 16 + RS_CS + 2, v89 >> 16);
      if (p1024) {
        sts32(sb + K1024_OFF + (ch * 2 + br) * 4, v89 << 16);
        const uint32_t kv = pack_bf16(k2048 + __uint_as_float(o2.z), 0.f);
        sts16(rb + R_E3 + 2 * (159 - 127), kv); sts16(rb + R_E3 + 2 * (159 - 127) + RS_CS + 2, kv);
      }
    }
  }
  STAMP(5);

  const uint32_t tag = (epoch + 1) & 0xffffu;
  {
    const uint32_t xs[8] = {gx0.x, gx0.y, gx0.z, gx0.w, gx1.x, gx1.y, gx1.z, gx1.w};
    const uint32_t ws[8] = {gw0.x, gw0.y, gw0.z, gw0.w, gw1.x, gw1.y, gw1.z, gw1.w};
    float s = 0.f;
#pragma unroll
    for (int i = 0; i < 8; i++) { const uint32_t pr = hmul2(xs[i], ws[i]); s += bf_lo(pr); s += bf_hi(pr); }
#pragma unroll
    for (int o = 16; o; o >>= 1) s += __shfl_xor_sync(0xffffffffu, s, o);
    if (lane == 0) {
      s = bf_round(s);
      const float gv = 1.f / (1.f + expf(-s));
      const uint32_t w = (tag << 16) | (pack_bf16(gv, 0.f) & 0xffffu);
      asm volatile("st.relaxed.gpu.global.u32 [%0], %1;" ::"l"(&g_gate[grow]), "r"(w) : "memory");
    }
  }

  bar_sync(9 + ch, 128);
  mbar_wait(sb + B_U);
  STAMP(6);
  {
    const int c0 = (wq < 2) ? 3 * wtid - 2 : 2 * (wtid - 64) - 3;
    float pf[41];
    pf[0] = 0.f;
#pragma unroll
    for (int j = 0; j < 5; j++) {
      const int c = c0 + j;
      const uint4 v = lds128(cb + U_OFF + (c & 3) * U_CS + (63 - (c >> 2)) * 16);
      const uint32_t w[4] = {v.x, v.y, v.z, v.w};
#pragma unroll
      for (int i = 0; i < 4; i++) {
        pf[j * 8 + 2 * i + 1] = pf[j * 8 + 2 * i] + bf_lo(w[i]);
        pf[j * 8 + 2 * i + 2] = pf[j * 8 + 2 * i + 1] + bf_hi(w[i]);
      }
    }
    if (wq < 2) {
#pragma unroll
      for (int j = 0; j < 3; j++) {
        uint32_t a[4], b[4];
#pragma unroll
        for (int i = 0; i < 4; i++) {
          const int ix = 16 + j * 8 + 2 * i;
          a[i] = pack_bf16(pf[ix - 5] - pf[ix - 10], pf[ix - 4] - pf[ix - 9]);
          b[i] = pack_bf16(pf[ix - 2] - pf[ix - 5], pf[ix - 1] - pf[ix - 4]);
        }
        const int c = 3 * wtid + j;
        const uint32_t po = ((5 - (c >> 5)) * 32 + (c & 31)) * 16;
        sts128(cb + W5_OFF + po, a[0], a[1], a[2], a[3]);
        sts128(cb + W3_OFF + po, b[0], b[1], b[2], b[3]);
      }
    } else {
      const int q = wtid - 64;
#pragma unroll
      for (int j = 0; j < 2; j++) {
        uint32_t a[4], b[4], s[4];
#pragma unroll
        for (int i = 0; i < 4; i++) {
          const int ix = 24 + j * 8 + 2 * i;
          a[i] = pack_bf16(pf[ix - 11] - pf[ix - 20], pf[ix - 10] - pf[ix - 19]);
          b[i] = pack_bf16(pf[ix - 4] - pf[ix - 11], pf[ix - 3] - pf[ix - 10]);
          s[i] = pack_bf16(pf[ix - 2] - pf[ix - 4], pf[ix - 1] - pf[ix - 3]);
        }
        const uint32_t po = ((1 - (q >> 5)) * 64 + j * 32 + (q & 31)) * 16;
        sts128(cb + W9_OFF + po, a[0], a[1], a[2], a[3]);
        sts128(cb + W7_OFF + po, b[0], b[1], b[2], b[3]);
        sts128(cb + S2_OFF + (2 * q + j) * 16, s[0], s[1], s[2], s[3]);
      }
    }
  }
  fence_async();
  bar_sync(9 + ch, 128);
  STAMP(7);

  const uint32_t rb = cb + R_OFF + br * R_BR;
  const int eo = 16 * hf + g - 2 * t;
  float dacc[32];
  {
    const int x0 = 559 - (eo + 536);
    const uint32_t fa = rb + ((g & 1) ? 2 * x0 : RD_CS + 2 * x0 + 2);
    const uint64_t ub = mkdesc(cb + U_OFF, U_CS, 128);
    uint32_t f[2][9];
#pragma unroll
    for (int i = 0; i < 9; i++) f[0][i] = lds32(fa + (62 + i) * 16);
#pragma unroll
    for (int j = 0; j < 9; j++) {
      wg_fence();
#pragma unroll
      for (int k = 0; k < 4; k++) {
        const int s = 34 - 4 * j - k;
        if (s >= 0) {
          const int o = 2 * s - 66 + 128;
          const int cc = o & 3, rs = (o >> 2) - 32;
          const int n0 = ((-rs) >> 3) * 8;
          const uint64_t desc = ub + (uint64_t)((cc * U_CS - rs * 16) >> 4);
          const int fi = 2 * (3 - k);
          const uint32_t a1 = f[j & 1][fi], a0 = f[j & 1][fi + 1], a2 = f[j & 1][fi + 2];
          if (n0 == 0) wgmma_rs<64, 0>(dacc, a0, a1, a2, a0, desc, s != 34);
          else if (n0 == 8) wgmma_rs<56, 0>(dacc, a0, a1, a2, a0, desc, 1);
          else wgmma_rs<48, 0>(dacc, a0, a1, a2, a0, desc, 1);
        }
      }
      wg_commit();
      if (j < 8) {
#pragma unroll
        for (int i = 0; i < 9; i++) {
          const int idx = 62 - 8 * (j + 1) + i;
          if (idx >= 0) f[(j + 1) & 1][i] = lds32(fa + idx * 16);
        }
      }
      wg_wait0();
    }
    const uint32_t yb = cb + Y0_OFF + br * 4096;
#pragma unroll
    for (int i = 0; i < 8; i += 2) {
      const int mi = lane >> 3;
      const int cidx = 4 * (63 - 8 * (i + (mi >> 1)) - (lane & 7)) + 2 * hf + (mi & 1);
      stsm4t(yb + ysw(cidx), pack_bf16(dacc[4 * i], dacc[4 * i + 1]), pack_bf16(dacc[4 * i + 2], dacc[4 * i + 3]),
             pack_bf16(dacc[4 * i + 4], dacc[4 * i + 5]), pack_bf16(dacc[4 * i + 6], dacc[4 * i + 7]));
    }
  }
  STAMP(8);
  const int oc0 = (int)(blockIdx.x >> 1) * 8;
  unsigned int ticket = 0;
  if (ch == 0) {
    bar_sync(13, 512);
    if (tid == 0) ticket = atomicAdd(&g_ticket, 1u);
    final_pass<0>(p, sb, wtid, tag, rank);
    if (tid == 0) {
      mbar_wait(sb + B_O1);
      fence_async();
      tma_store_box(&tm_out, sb + RAW_OFF, oc0, rank * 64);
      asm volatile("cp.async.bulk.commit_group;" ::: "memory");
    }
    __syncwarp();
  } else bar_arrive(13, 512);
  STAMP(9);
  const int x1 = 159 - (eo + 136);
  const uint32_t fs = rb + ((g & 1) ? 2 * x1 : RS_CS + 2 * x1 + 2);
  {
    uint32_t A[2][4][4];
    const uint64_t d5 = mkdesc(cb + W5_OFF, 128, 512), d3 = mkdesc(cb + W3_OFF, 128, 512);
    auto loadA = [&](int m) {
#pragma unroll
      for (int a = 0; a < 2; a++) {
        const uint32_t base = fs + (a ? R_O2 : R_E2) + (4 * (4 - m)) * 16;
        uint32_t* k0 = A[m & 1][2 * a];
        uint32_t* k1 = A[m & 1][2 * a + 1];
        k0[1] = lds32(base); k0[0] = lds32(base + 16); k0[2] = lds32(base + 32); k1[0] = lds32(base + 48); k1[2] = lds32(base + 64);
        k0[3] = copy_reg(k0[0]); k1[1] = copy_reg(k0[2]); k1[3] = copy_reg(k1[0]);
      }
    };
    loadA(2);
#pragma unroll
    for (int m = 2; m <= 4; m++) {
      wg_fence();
#pragma unroll
      for (int k = 0; k < 4; k++) {
        const uint32_t* a = A[m & 1][k];
        const uint64_t desc = ((k >> 1) ? d3 : d5) + (k & 1) * 16 + (m - 2) * 32;
        if (m == 2) wgmma_rs<48, 1>(dacc, a[0], a[1], a[2], a[3], desc, k);
        else if (m == 3) wgmma_rs<40, 1>(dacc, a[0], a[1], a[2], a[3], desc, 1);
        else wgmma_rs<32, 1>(dacc, a[0], a[1], a[2], a[3], desc, 1);
      }
      wg_commit();
      if (m < 4) loadA(m + 1);
      wg_wait0();
    }
    const uint32_t yb = cb + Y2_OFF + br * 3072;
#pragma unroll
    for (int i = 0; i < 6; i += 2) {
      const int mi = lane >> 3;
      const int cidx = 32 * (5 - i - (mi >> 1)) + 16 * hf + 8 * (mi & 1) + (lane & 7);
      stsm4(yb + ysw(cidx), pack_bf16(dacc[4 * i], dacc[4 * i + 1]), pack_bf16(dacc[4 * i + 2], dacc[4 * i + 3]),
            pack_bf16(dacc[4 * i + 4], dacc[4 * i + 5]), pack_bf16(dacc[4 * i + 6], dacc[4 * i + 7]));
    }
  }
  if (ch != 1) bar_arrive(14, 512);
  STAMP(10);
  {
    uint32_t A[2][4][4];
    const uint64_t d9 = mkdesc(cb + W9_OFF, 128, 512), d7 = mkdesc(cb + W7_OFF, 128, 512);
    auto loadA = [&](int m) {
#pragma unroll
      for (int a = 0; a < 2; a++) {
        const uint32_t base = fs + (a ? R_O3 : R_E3) + (4 * (4 - m)) * 16;
        uint32_t* k0 = A[m & 1][2 * a];
        uint32_t* k1 = A[m & 1][2 * a + 1];
        k0[1] = lds32(base); k0[0] = lds32(base + 16); k0[2] = lds32(base + 32); k1[0] = lds32(base + 48); k1[2] = lds32(base + 64);
        k0[3] = copy_reg(k0[0]); k1[1] = copy_reg(k0[2]); k1[3] = copy_reg(k1[0]);
      }
    };
    loadA(2);
#pragma unroll
    for (int m = 2; m <= 3; m++) {
      wg_fence();
#pragma unroll
      for (int k = 0; k < 4; k++) {
        const uint32_t* a = A[m & 1][k];
        const uint64_t desc = ((k >> 1) ? d7 : d9) + (k & 1) * 16 + (m - 2) * 64;
        if (m == 2) wgmma_rs<32, 1>(dacc, a[0], a[1], a[2], a[3], desc, k);
        else wgmma_rs<16, 1>(dacc, a[0], a[1], a[2], a[3], desc, 1);
      }
      wg_commit();
      if (m < 3) loadA(m + 1);
      wg_wait0();
    }
    const uint32_t yb = cb + Y3_OFF + br * 2048;
#pragma unroll
    for (int i = 0; i < 4; i += 2) {
      const int mi = lane >> 3;
      const int cidx = 64 * (1 - (i >> 1)) + 2 * (16 * hf + 8 * (mi & 1) + (lane & 7)) + (mi >> 1);
      stsm4(yb + ysw(cidx), pack_bf16(dacc[4 * i], dacc[4 * i + 1]), pack_bf16(dacc[4 * i + 2], dacc[4 * i + 3]),
            pack_bf16(dacc[4 * i + 4], dacc[4 * i + 5]), pack_bf16(dacc[4 * i + 6], dacc[4 * i + 7]));
    }
  }
  STAMP(11);
  if (ch < 2) {
    bar_arrive(15, 512);
    if (ch == 1) {
      bar_sync(14, 512);
      final_pass<1>(p, sb, 128 + wtid, tag, rank);
      if (wtid == 0) {
        mbar_wait(sb + B_O2);
        fence_async();
        tma_store_box(&tm_out, sb + RAW_OFF + 4096, oc0, 128 + rank * 64);
        asm volatile("cp.async.bulk.commit_group;" ::: "memory");
        asm volatile("cp.async.bulk.wait_group.read 0;" ::: "memory");
      }
    } else if (tid == 0) {
      if (ticket == NCTA - 1) { g_ticket = 0; g_epoch = epoch + 1; }
      asm volatile("cp.async.bulk.wait_group.read 0;" ::: "memory");
    }
  } else {
    bar_sync(15, 512);
    final_pass<2>(p, sb, tid, tag, rank);
    STAMP(12);
    if (tid == 256) {
      mbar_wait(sb + B_O3);
      fence_async();
      tma_store_box(&tm_out, sb + RAW_OFF + 8192, oc0, 256 + rank * 64);
      tma_store_box(&tm_out, sb + RAW_OFF + 12288, oc0, 384 + rank * 64);
      asm volatile("cp.async.bulk.commit_group;" ::: "memory");
      asm volatile("cp.async.bulk.wait_group.read 0;" ::: "memory");
    }
  }
  STAMP(13); GT(1);
}

typedef CUresult (*EncodeFn)(CUtensorMap*, CUtensorMapDataType, cuuint32_t, void*, const cuuint64_t*, const cuuint64_t*,
                             const cuuint32_t*, const cuuint32_t*, CUtensorMapInterleave, CUtensorMapSwizzle,
                             CUtensorMapL2promotion, CUtensorMapFloatOOBfill);

}

extern "C" void kernel_launch(void* const* d_in, const int* in_sizes, int n_in, void* d_out, int out_size) {
  (void)in_sizes; (void)n_in; (void)out_size;
  typedef const __nv_bfloat16* bp;
  Params p;
  p.u = (bp)d_in[0]; p.A_re = (bp)d_in[1]; p.A_im = (bp)d_in[2]; p.B_re = (bp)d_in[3]; p.B_im = (bp)d_in[4];
  p.C_re = (bp)d_in[5]; p.C_im = (bp)d_in[6]; p.A_ldt = (bp)d_in[7]; p.A_D = (bp)d_in[8];
  p.B_lA = (bp)d_in[10]; p.B_Aim = (bp)d_in[11]; p.B_Cre = (bp)d_in[12]; p.B_Cim = (bp)d_in[13];
  p.B_ldt = (bp)d_in[14]; p.B_D = (bp)d_in[15]; p.gw = (bp)d_in[16];
  static EncodeFn enc = nullptr;
  if (!enc) {
    cudaDriverEntryPointQueryResult qr;
    cudaGetDriverEntryPoint("cuTensorMapEncodeTiled", (void**)&enc, cudaEnableDefault, &qr);
    cudaFuncSetAttribute(ssm_kernel, cudaFuncAttributeMaxDynamicSharedMemorySize, SMEM_BYTES);
  }
  CUtensorMap tm_in, tm_out;
  {
    cuuint64_t gd[5] = {512, 2, 4, 4, 64};
    cuuint64_t gs[4] = {1024, 8192, 2048, 32768};
    cuuint32_t bx[5] = {8, 2, 4, 4, 32};
    cuuint32_t es[5] = {1, 1, 1, 1, 1};
    enc(&tm_in, CU_TENSOR_MAP_DATA_TYPE_BFLOAT16, 5, d_in[0], gd, gs, bx, es, CU_TENSOR_MAP_INTERLEAVE_NONE,
        CU_TENSOR_MAP_SWIZZLE_NONE, CU_TENSOR_MAP_L2_PROMOTION_NONE, CU_TENSOR_MAP_FLOAT_OOB_FILL_NONE);
  }
  {
    cuuint64_t gd[3] = {512, 512, 4};
    cuuint64_t gs[2] = {4096, 1024};
    cuuint32_t bx[3] = {8, 64, 4};
    cuuint32_t es[3] = {1, 1, 1};
    enc(&tm_out, CU_TENSOR_MAP_DATA_TYPE_BFLOAT16, 3, d_out, gd, gs, bx, es, CU_TENSOR_MAP_INTERLEAVE_NONE,
        CU_TENSOR_MAP_SWIZZLE_NONE, CU_TENSOR_MAP_L2_PROMOTION_NONE, CU_TENSOR_MAP_FLOAT_OOB_FILL_NONE);
  }
  ssm_kernel<<<NCTA, 512, SMEM_BYTES, cudaStreamPerThread>>>(p, tm_in, tm_out);
}
```

```cpp
#include <cuda_runtime.h>
#include <cuda.h>
#include <cuda_bf16.h>
#include <stdint.h>

namespace {

constexpr int L = 2048, D = 512, NM = 128;
constexpr int NCTA = 128;

constexpr int RAW_OFF = 0;
constexpr int XIN_OFF = 32768;
constexpr int BAR_OFF = XIN_OFF + 8192;
constexpr int CH_OFF = BAR_OFF + 128;
constexpr int U_CS = 1184;
constexpr int U_OFF = 0;
constexpr int R_OFF = 4736;
constexpr int RD_X0 = 565;
constexpr int RD_CS = 1216;
constexpr int RS_CS = 320;
constexpr int R_E2 = 2 * RD_CS, R_O2 = R_E2 + 2 * RS_CS, R_E3 = R_O2 + 2 * RS_CS, R_O3 = R_E3 + 2 * RS_CS;
constexpr int R_BR = R_O3 + 2 * RS_CS;
constexpr int W5_OFF = R_OFF + 2 * R_BR;
constexpr int W3_OFF = W5_OFF + 3456;
constexpr int W9_OFF = W3_OFF + 3456;
constexpr int W7_OFF = W9_OFF + 2304;
constexpr int S2_OFF = W7_OFF + 2304;
constexpr int Y0_OFF = S2_OFF + 2304;
constexpr int Y2_OFF = Y0_OFF + 8192, Y3_OFF = Y2_OFF + 6144;
constexpr int CH_BYTES = Y0_OFF + 18432 + 16;
constexpr int SCR_BYTES = 8064;
constexpr int SMEM_BYTES = CH_OFF + 4 * CH_BYTES;
static_assert(CH_BYTES % 128 == 16, "bank staggering of the channel blocks");
static_assert(SMEM_BYTES <= 232448, "smem");
constexpr int B_RAW = BAR_OFF, B_X = BAR_OFF + 8;
constexpr int K1024_OFF = BAR_OFF + 64;

__device__ unsigned int g_gate[L];
__device__ unsigned int g_epoch;
__device__ unsigned int g_ticket;

#define STAMP(k)
#define GT(k)

struct Params {
  const __nv_bfloat16 *u, *A_re, *A_im, *B_re, *B_im, *C_re, *C_im, *A_ldt, *A_D;
  const __nv_bfloat16 *B_lA, *B_Aim, *B_Cre, *B_Cim, *B_ldt, *B_D, *gw;
};

template <int N, int TB> __device__ __forceinline__ void wgmma_rs(float* d, uint32_t a0, uint32_t a1, uint32_t a2, uint32_t a3, uint64_t desc, int sc);
template <> __device__ __forceinline__ void wgmma_rs<64, 0>(float* d, uint32_t a0, uint32_t a1, uint32_t a2, uint32_t a3, uint64_t desc, int sc) {
  asm volatile("{\n.reg .pred p;\nsetp.ne.b32 p, %37, 0;\n"
    "wgmma.mma_async.sync.aligned.m64n64k16.f32.bf16.bf16 {%0,%1,%2,%3,%4,%5,%6,%7,%8,%9,%10,%11,%12,%13,%14,%15,%16,%17,%18,%19,%20,%21,%22,%23,%24,%25,%26,%27,%28,%29,%30,%31}, {%32,%33,%34,%35}, %36, p, 1, 1, 0;\n}"
    : "+f"(d[0]), "+f"(d[1]), "+f"(d[2]), "+f"(d[3]), "+f"(d[4]), "+f"(d[5]), "+f"(d[6]), "+f"(d[7]), "+f"(d[8]), "+f"(d[9]), "+f"(d[10]), "+f"(d[11]), "+f"(d[12]), "+f"(d[13]), "+f"(d[14]), "+f"(d[15]), "+f"(d[16]), "+f"(d[17]), "+f"(d[18]), "+f"(d[19]), "+f"(d[20]), "+f"(d[21]), "+f"(d[22]), "+f"(d[23]), "+f"(d[24]), "+f"(d[25]), "+f"(d[26]), "+f"(d[27]), "+f"(d[28]), "+f"(d[29]), "+f"(d[30]), "+f"(d[31]) : "r"(a0), "r"(a1), "r"(a2), "r"(a3), "l"(desc), "r"(sc));
}
template <> __device__ __forceinline__ void wgmma_rs<56, 0>(float* d, uint32_t a0, uint32_t a1, uint32_t a2, uint32_t a3, uint64_t desc, int sc) {
  asm volatile("{\n.reg .pred p;\nsetp.ne.b32 p, %33, 0;\n"
    "wgmma.mma_async.sync.aligned.m64n56k16.f32.bf16.bf16 {%0,%1,%2,%3,%4,%5,%6,%7,%8,%9,%10,%11,%12,%13,%14,%15,%16,%17,%18,%19,%20,%21,%22,%23,%24,%25,%26,%27}, {%28,%29,%30,%31}, %32, p, 1, 1, 0;\n}"
    : "+f"(d[0]), "+f"(d[1]), "+f"(d[2]), "+f"(d[3]), "+f"(d[4]), "+f"(d[5]), "+f"(d[6]), "+f"(d[7]), "+f"(d[8]), "+f"(d[9]), "+f"(d[10]), "+f"(d[11]), "+f"(d[12]), "+f"(d[13]), "+f"(d[14]), "+f"(d[15]), "+f"(d[16]), "+f"(d[17]), "+f"(d[18]), "+f"(d[19]), "+f"(d[20]), "+f"(d[21]), "+f"(d[22]), "+f"(d[23]), "+f"(d[24]), "+f"(d[25]), "+f"(d[26]), "+f"(d[27]) : "r"(a0), "r"(a1), "r"(a2), "r"(a3), "l"(desc), "r"(sc));
}
template <> __device__ __forceinline__ void wgmma_rs<48, 0>(float* d, uint32_t a0, uint32_t a1, uint32_t a2, uint32_t a3, uint64_t desc, int sc) {
  asm volatile("{\n.reg .pred p;\nsetp.ne.b32 p, %29, 0;\n"
    "wgmma.mma_async.sync.aligned.m64n48k16.f32.bf16.bf16 {%0,%1,%2,%3,%4,%5,%6,%7,%8,%9,%10,%11,%12,%13,%14,%15,%16,%17,%18,%19,%20,%21,%22,%23}, {%24,%25,%26,%27}, %28, p, 1, 1, 0;\n}"
    : "+f"(d[0]), "+f"(d[1]), "+f"(d[2]), "+f"(d[3]), "+f"(d[4]), "+f"(d[5]), "+f"(d[6]), "+f"(d[7]), "+f"(d[8]), "+f"(d[9]), "+f"(d[10]), "+f"(d[11]), "+f"(d[12]), "+f"(d[13]), "+f"(d[14]), "+f"(d[15]), "+f"(d[16]), "+f"(d[17]), "+f"(d[18]), "+f"(d[19]), "+f"(d[20]), "+f"(d[21]), "+f"(d[22]), "+f"(d[23]) : "r"(a0), "r"(a1), "r"(a2), "r"(a3), "l"(desc), "r"(sc));
}
template <> __device__ __forceinline__ void wgmma_rs<48, 1>(float* d, uint32_t a0, uint32_t a1, uint32_t a2, uint32_t a3, uint64_t desc, int sc) {
  asm volatile("{\n.reg .pred p;\nsetp.ne.b32 p, %29, 0;\n"
    "wgmma.mma_async.sync.aligned.m64n48k16.f32.bf16.bf16 {%0,%1,%2,%3,%4,%5,%6,%7,%8,%9,%10,%11,%12,%13,%14,%15,%16,%17,%18,%19,%20,%21,%22,%23}, {%24,%25,%26,%27}, %28, p, 1, 1, 1;\n}"
    : "+f"(d[0]), "+f"(d[1]), "+f"(d[2]), "+f"(d[3]), "+f"(d[4]), "+f"(d[5]), "+f"(d[6]), "+f"(d[7]), "+f"(d[8]), "+f"(d[9]), "+f"(d[10]), "+f"(d[11]), "+f"(d[12]), "+f"(d[13]), "+f"(d[14]), "+f"(d[15]), "+f"(d[16]), "+f"(d[17]), "+f"(d[18]), "+f"(d[19]), "+f"(d[20]), "+f"(d[21]), "+f"(d[22]), "+f"(d[23]) : "r"(a0), "r"(a1), "r"(a2), "r"(a3), "l"(desc), "r"(sc));
}
template <> __device__ __forceinline__ void wgmma_rs<40, 1>(float* d, uint32_t a0, uint32_t a1, uint32_t a2, uint32_t a3, uint64_t desc, int sc) {
  asm volatile("{\n.reg .pred p;\nsetp.ne.b32 p, %25, 0;\n"
    "wgmma.mma_async.sync.aligned.m64n40k16.f32.bf16.bf16 {%0,%1,%2,%3,%4,%5,%6,%7,%8,%9,%10,%11,%12,%13,%14,%15,%16,%17,%18,%19}, {%20,%21,%22,%23}, %24, p, 1, 1, 1;\n}"
    : "+f"(d[0]), "+f"(d[1]), "+f"(d[2]), "+f"(d[3]), "+f"(d[4]), "+f"(d[5]), "+f"(d[6]), "+f"(d[7]), "+f"(d[8]), "+f"(d[9]), "+f"(d[10]), "+f"(d[11]), "+f"(d[12]), "+f"(d[13]), "+f"(d[14]), "+f"(d[15]), "+f"(d[16]), "+f"(d[17]), "+f"(d[18]), "+f"(d[19]) : "r"(a0), "r"(a1), "r"(a2), "r"(a3), "l"(desc), "r"(sc));
}
template <> __device__ __forceinline__ void wgmma_rs<32, 1>(float* d, uint32_t a0, uint32_t a1, uint32_t a2, uint32_t a3, uint64_t desc, int sc) {
  asm volatile("{\n.reg .pred p;\nsetp.ne.b32 p, %21, 0;\n"
    "wgmma.mma_async.sync.aligned.m64n32k16.f32.bf16.bf16 {%0,%1,%2,%3,%4,%5,%6,%7,%8,%9,%10,%11,%12,%13,%14,%15}, {%16,%17,%18,%19}, %20, p, 1, 1, 1;\n}"
    : "+f"(d[0]), "+f"(d[1]), "+f"(d[2]), "+f"(d[3]), "+f"(d[4]), "+f"(d[5]), "+f"(d[6]), "+f"(d[7]), "+f"(d[8]), "+f"(d[9]), "+f"(d[10]), "+f"(d[11]), "+f"(d[12]), "+f"(d[13]), "+f"(d[14]), "+f"(d[15]) : "r"(a0), "r"(a1), "r"(a2), "r"(a3), "l"(desc), "r"(sc));
}
template <> __device__ __forceinline__ void wgmma_rs<16, 1>(float* d, uint32_t a0, uint32_t a1, uint32_t a2, uint32_t a3, uint64_t desc, int sc) {
  asm volatile("{\n.reg .pred p;\nsetp.ne.b32 p, %13, 0;\n"
    "wgmma.mma_async.sync.aligned.m64n16k16.f32.bf16.bf16 {%0,%1,%2,%3,%4,%5,%6,%7}, {%8,%9,%10,%11}, %12, p, 1, 1, 1;\n}"
    : "+f"(d[0]), "+f"(d[1]), "+f"(d[2]), "+f"(d[3]), "+f"(d[4]), "+f"(d[5]), "+f"(d[6]), "+f"(d[7]) : "r"(a0), "r"(a1), "r"(a2), "r"(a3), "l"(desc), "r"(sc));
}

__device__ __forceinline__ uint32_t pack_bf16(float lo, float hi) {
  uint32_t r; asm("cvt.rn.bf16x2.f32 %0, %1, %2;" : "=r"(r) : "f"(hi), "f"(lo)); return r;
}
__device__ __forceinline__ float bf_lo(uint32_t v) { return __uint_as_float(v << 16); }
__device__ __forceinline__ float bf_hi(uint32_t v) { return __uint_as_float(v & 0xffff0000u); }
__device__ __forceinline__ float bf_round(float x) { return bf_lo(pack_bf16(x, 0.f)); }
__device__ __forceinline__ uint32_t hmul2(uint32_t a, uint32_t b) { uint32_t r; asm("mul.rn.bf16x2 %0, %1, %2;" : "=r"(r) : "r"(a), "r"(b)); return r; }
__device__ __forceinline__ uint32_t hadd2(uint32_t a, uint32_t b) { uint32_t r; asm("add.rn.bf16x2 %0, %1, %2;" : "=r"(r) : "r"(a), "r"(b)); return r; }
__device__ __forceinline__ uint32_t hsub2(uint32_t a, uint32_t b) { uint32_t r; asm("sub.rn.bf16x2 %0, %1, %2;" : "=r"(r) : "r"(a), "r"(b)); return r; }
__device__ __forceinline__ uint32_t hfma2(uint32_t a, uint32_t b, uint32_t c) { uint32_t r; asm("fma.rn.bf16x2 %0, %1, %2, %3;" : "=r"(r) : "r"(a), "r"(b), "r"(c)); return r; }

__device__ __forceinline__ void sts16(uint32_t a, uint32_t v) { asm volatile("st.shared.b16 [%0], %1;" ::"r"(a), "h"((unsigned short)v) : "memory"); }
__device__ __forceinline__ void sts32(uint32_t a, uint32_t v) { asm volatile("st.shared.b32 [%0], %1;" ::"r"(a), "r"(v) : "memory"); }
__device__ __forceinline__ void sts64(uint32_t a, uint32_t x, uint32_t y) { asm volatile("st.shared.v2.b32 [%0], {%1,%2};" ::"r"(a), "r"(x), "r"(y) : "memory"); }
__device__ __forceinline__ void sts128(uint32_t a, uint32_t x, uint32_t y, uint32_t z, uint32_t w) {
  asm volatile("st.shared.v4.b32 [%0], {%1,%2,%3,%4};" ::"r"(a), "r"(x), "r"(y), "r"(z), "r"(w) : "memory");
}
__device__ __forceinline__ uint32_t lds32(uint32_t a) { uint32_t v; asm volatile("ld.shared.b32 %0, [%1];" : "=r"(v) : "r"(a) : "memory"); return v; }
__device__ __forceinline__ uint2 lds64(uint32_t a) { uint2 v; asm volatile("ld.shared.v2.b32 {%0,%1}, [%2];" : "=r"(v.x), "=r"(v.y) : "r"(a) : "memory"); return v; }
__device__ __forceinline__ uint4 lds128(uint32_t a) {
  uint4 v; asm volatile("ld.shared.v4.b32 {%0,%1,%2,%3}, [%4];" : "=r"(v.x), "=r"(v.y), "=r"(v.z), "=r"(v.w) : "r"(a) : "memory"); return v;
}
__device__ __forceinline__ void ldsm4(uint32_t a, uint32_t& r0, uint32_t& r1, uint32_t& r2, uint32_t& r3) {
  asm volatile("ldmatrix.sync.aligned.m8n8.x4.shared.b16 {%0,%1,%2,%3}, [%4];" : "=r"(r0), "=r"(r1), "=r"(r2), "=r"(r3) : "r"(a) : "memory");
}
__device__ __forceinline__ void ldsm4t(uint32_t a, uint32_t& r0, uint32_t& r1, uint32_t& r2, uint32_t& r3) {
  asm volatile("ldmatrix.sync.aligned.m8n8.x4.trans.shared.b16 {%0,%1,%2,%3}, [%4];" : "=r"(r0), "=r"(r1), "=r"(r2), "=r"(r3) : "r"(a) : "memory");
}
__device__ __forceinline__ void stsm4(uint32_t a, uint32_t r0, uint32_t r1, uint32_t r2, uint32_t r3) {
  asm volatile("stmatrix.sync.aligned.m8n8.x4.shared.b16 [%0], {%1,%2,%3,%4};" ::"r"(a), "r"(r0), "r"(r1), "r"(r2), "r"(r3) : "memory");
}
__device__ __forceinline__ void stsm4t(uint32_t a, uint32_t r0, uint32_t r1, uint32_t r2, uint32_t r3) {
  asm volatile("stmatrix.sync.aligned.m8n8.x4.trans.shared.b16 [%0], {%1,%2,%3,%4};" ::"r"(a), "r"(r0), "r"(r1), "r"(r2), "r"(r3) : "memory");
}
__device__ __forceinline__ void mma16816(float* c, uint32_t a0, uint32_t a1, uint32_t a2, uint32_t a3, uint32_t b0, uint32_t b1) {
  asm("mma.sync.aligned.m16n8k16.row.col.f32.bf16.bf16.f32 {%0,%1,%2,%3}, {%4,%5,%6,%7}, {%8,%9}, {%0,%1,%2,%3};"
      : "+f"(c[0]), "+f"(c[1]), "+f"(c[2]), "+f"(c[3]) : "r"(a0), "r"(a1), "r"(a2), "r"(a3), "r"(b0), "r"(b1));
}
__device__ __forceinline__ void bar_sync(int id, int n) { asm volatile("bar.sync %0, %1;" ::"r"(id), "r"(n) : "memory"); }
__device__ __forceinline__ void bar_arrive(int id, int n) { asm volatile("bar.arrive %0, %1;" ::"r"(id), "r"(n) : "memory"); }
__device__ __forceinline__ void wg_fence() { asm volatile("wgmma.fence.sync.aligned;" ::: "memory"); }
__device__ __forceinline__ void wg_commit() { asm volatile("wgmma.commit_group.sync.aligned;" ::: "memory"); }
__device__ __forceinline__ void wg_wait0() { asm volatile("wgmma.wait_group.sync.aligned 0;" ::: "memory"); }
__device__ __forceinline__ void fence_async() { asm volatile("fence.proxy.async.shared::cta;" ::: "memory"); }
__device__ __forceinline__ uint64_t mkdesc(uint32_t addr, uint32_t lbo, uint32_t sbo) {
  return (uint64_t)((addr & 0x3FFFF) >> 4) | ((uint64_t)(lbo >> 4) << 16) | ((uint64_t)(sbo >> 4) << 32);
}
__device__ __forceinline__ uint32_t mapa(uint32_t a, uint32_t rank) {
  uint32_t r; asm("mapa.shared::cluster.u32 %0, %1, %2;" : "=r"(r) : "r"(a), "r"(rank)); return r;
}
__device__ __forceinline__ void mbar_init_expect(uint32_t bar, uint32_t bytes) {
  asm volatile("mbarrier.init.shared::cta.b64 [%0], 1;" ::"r"(bar) : "memory");
  asm volatile("mbarrier.arrive.expect_tx.shared::cta.b64 _, [%0], %1;" ::"r"(bar), "r"(bytes) : "memory");
}
__device__ __forceinline__ void mbar_wait(uint32_t bar) {
#pragma unroll 1
  for (int it = 0; it < (1 << 22); it++) {
    uint32_t ok;
    asm volatile("{\n.reg .pred p;\nmbarrier.try_wait.parity.acquire.cluster.shared::cta.b64 p, [%1], 0;\nselp.u32 %0, 1, 0, p;\n}"
                 : "=r"(ok) : "r"(bar) : "memory");
    if (ok) return;
  }
  __trap();
}
__device__ __forceinline__ void st_async4(uint32_t a, uint32_t bar, uint32_t x, uint32_t y, uint32_t z, uint32_t w) {
  asm volatile("st.async.weak.shared::cluster.mbarrier::complete_tx::bytes.v4.b32 [%0], {%2,%3,%4,%5}, [%1];"
               ::"r"(a), "r"(bar), "r"(x), "r"(y), "r"(z), "r"(w) : "memory");
}

struct cf { float re, im; };
__device__ __forceinline__ cf cmul(cf a, cf b) { return {fmaf(a.re, b.re, -a.im * b.im), fmaf(a.re, b.im, a.im * b.re)}; }
__device__ __forceinline__ cf csq(cf a) { return {fmaf(a.re, a.re, -a.im * a.im), (a.re + a.re) * a.im}; }
__device__ __forceinline__ cf cexp_p(float xl, float y, float p) {
  float mag; asm("ex2.approx.ftz.f32 %0, %1;" : "=f"(mag) : "f"(xl * p));
  const float th = y * p;
  const float k = rintf(th * 0.15915494309189535f);
  float r = fmaf(k, -6.2831854820251465f, th);
  r = fmaf(k, 1.7484555314695172e-07f, r);
  return {mag * __cosf(r), mag * __sinf(r)};
}
__device__ __forceinline__ uint32_t ysw(int c) { return (uint32_t)(c ^ ((c >> 3) & 3)) * 16u; }

#define CMUL2(OR, OI, xr, xi, yr, yi, nyi) do { OR = hfma2(xr, yr, hmul2(xi, nyi)); OI = hfma2(xr, yi, hmul2(xi, yr)); } while (0)

__device__ __noinline__ uint32_t gate_slow(const __nv_bfloat16* u, const __nv_bfloat16* gw, int row) {
  float s = 0.f;
  const uint32_t* xr = (const uint32_t*)(u + (size_t)row * D);
  const uint32_t* wr = (const uint32_t*)gw;
#pragma unroll 1
  for (int j = 0; j < D / 2; j++) { const uint32_t pr = hmul2(xr[j], wr[j]); s += bf_lo(pr); s += bf_hi(pr); }
  s = bf_round(s);
  return pack_bf16(1.f / (1.f + expf(-s)), 0.f);
}

__device__ __forceinline__ void prefix6(float* pf, uint32_t ub, int c0) {
  pf[0] = 0.f;
#pragma unroll
  for (int j = 0; j < 6; j++) {
    const int c = c0 + j;
    const uint4 v = lds128(ub + (c & 3) * U_CS + (63 - (c >> 2)) * 16);
    const uint32_t w[4] = {v.x, v.y, v.z, v.w};
#pragma unroll
    for (int i = 0; i < 4; i++) {
      pf[j * 8 + 2 * i + 1] = pf[j * 8 + 2 * i] + bf_lo(w[i]);
      pf[j * 8 + 2 * i + 2] = pf[j * 8 + 2 * i + 1] + bf_hi(w[i]);
    }
  }
}
template <int A, int B>
__device__ __forceinline__ void put_win(const float* pf, int ix, uint32_t addr) {
  uint32_t a[4];
#pragma unroll
  for (int i = 0; i < 4; i++) a[i] = pack_bf16(pf[ix + 2 * i - B + 1] - pf[ix + 2 * i - A], pf[ix + 2 * i - B + 2] - pf[ix + 2 * i - A + 1]);
  sts128(addr, a[0], a[1], a[2], a[3]);
}

__device__ __noinline__ void window_sums(uint32_t cb, int wq, int lane) {
      float pf[49];
      if (wq == 0 || wq == 3) {
        if (wq == 0 || lane < 16) {
          const int nu = wq ? 32 + lane : lane;
          prefix6(pf, cb + U_OFF, 4 * nu - 2);
          const uint32_t po = (5 - (nu >> 3)) * 576 + ((nu & 7) >> 1) * 144 + (nu & 1) * 64;
#pragma unroll
          for (int k = 0; k < 4; k++) { put_win<10, 6>(pf, 16 + 8 * k, cb + W5_OFF + po + k * 16); put_win<5, 3>(pf, 16 + 8 * k, cb + W3_OFF + po + k * 16); }
        }
      } else {
        const uint32_t po = (1 - (lane >> 4)) * 1152 + ((lane & 15) >> 2) * 144 + (lane & 3) * 32;
        if (wq == 1) {
          prefix6(pf, cb + U_OFF, 4 * lane - 3);
#pragma unroll
          for (int k = 0; k < 4; k++) put_win<20, 12>(pf, 24 + 8 * k, cb + W9_OFF + po + (k & 1) * 576 + (k >> 1) * 16);
        } else {
          prefix6(pf, cb + U_OFF, 4 * lane - 2);
          const uint32_t so = cb + S2_OFF + (lane >> 1) * 144 + (lane & 1) * 64;
#pragma unroll
          for (int k = 0; k < 4; k++) { put_win<11, 5>(pf, 16 + 8 * k, cb + W7_OFF + po + (k & 1) * 576 + (k >> 1) * 16); put_win<4, 3>(pf, 16 + 8 * k, so + k * 16); }
        }
      }
      fence_async();
}

__global__ void __cluster_dims__(2, 1, 1) __launch_bounds__(512, 1)
ssm_kernel(const Params p, const __grid_constant__ CUtensorMap tm_in, const __grid_constant__ CUtensorMap tm_out) {
  extern __shared__ __align__(1024) unsigned char smem_raw[];
  const uint32_t sb = (uint32_t)__cvta_generic_to_shared(smem_raw);
  const int tid = threadIdx.x, lane = tid & 31;
  const int warp = __shfl_sync(0xffffffffu, tid >> 5, 0);
  const int ch = warp >> 2, wq = warp & 3, br = wq >> 1, hf = wq & 1;
  const int g = lane >> 2, t = lane & 3;
  const int d = blockIdx.x * 4 + ch;
  const uint32_t rank = blockIdx.x & 1;
  const uint32_t cb = sb + CH_OFF + ch * CH_BYTES;
  const int wtid = tid & 127;
  const int oc0 = (int)(blockIdx.x >> 1) * 8;
  STAMP(0); GT(0);

  if (tid == 0) {
    mbar_init_expect(sb + B_RAW, 32768);
#pragma unroll
    for (int i = 0; i < 4; i++) mbar_init_expect(sb + B_X + 8 * i, 2048);
    asm volatile("fence.mbarrier_init.release.cluster;" ::: "memory");
    asm volatile("fence.proxy.async.shared::cta;" ::: "memory");
  }
  __syncwarp();
  asm volatile("barrier.cluster.arrive.relaxed.aligned;" ::: "memory");

  const int moff = d * NM + hf * 64 + lane * 2;
  const uint32_t q0 = *(const uint32_t*)((br ? p.B_lA : p.A_re) + moff), q1 = *(const uint32_t*)((br ? p.B_Aim : p.A_im) + moff);
  const uint32_t q2 = *(const uint32_t*)((br ? p.B_Cre : p.C_re) + moff), q3 = *(const uint32_t*)((br ? p.B_Cim : p.C_im) + moff);
  const uint32_t q4 = *(const uint32_t*)((br ? p.B_Cre : p.B_re) + moff), q5 = *(const uint32_t*)((br ? p.B_Cim : p.B_im) + moff);
  const uint2 ldt4 = *(const uint2*)((br ? p.B_ldt : p.A_ldt) + blockIdx.x * 4);
  unsigned int epoch;
  asm volatile("ld.relaxed.gpu.global.u32 %0, [%1];" : "=r"(epoch) : "l"(&g_epoch) : "memory");

  asm volatile("barrier.cluster.wait.aligned;" ::: "memory");
  if (tid == 0) {
    asm volatile("cp.async.bulk.tensor.5d.shared::cluster.global.mbarrier::complete_tx::bytes.multicast::cluster [%0], [%1, {%3, %4, %4, %4, %5}], [%2], %6;"
                 ::"r"(sb + RAW_OFF + rank * 16384), "l"(&tm_in), "r"(sb + B_RAW), "r"(oc0), "r"(0), "r"((int)rank * 32), "h"((unsigned short)3) : "memory");
  }
  for (int i = wtid & 63; i < R_BR / 16; i += 64) sts128(cb + R_OFF + br * R_BR + i * 16, 0, 0, 0, 0);
  if (wtid < 32) sts128(cb + U_OFF + (wtid >> 3) * U_CS + (64 + (wtid & 7)) * 16, 0, 0, 0, 0);
  STAMP(1);

  float acc[5][4];
  float k2048 = 0.f;
  const uint32_t scr = cb + W5_OFF + wq * SCR_BYTES;
  {
    const uint32_t ldt2 = (ch & 2) ? ldt4.y : ldt4.x;
    const float dt = bf_round(expf((ch & 1) ? bf_hi(ldt2) : bf_lo(ldt2)));
#pragma unroll
    for (int i = 0; i < 5; i++) acc[i][0] = acc[i][1] = acc[i][2] = acc[i][3] = 0.f;
    cf cc[2], zz1[2], zz128[2];
#pragma unroll
    for (int r = 0; r < 2; r++) {
      float v0 = r ? bf_hi(q0) : bf_lo(q0), v1 = r ? bf_hi(q1) : bf_lo(q1), v2 = r ? bf_hi(q2) : bf_lo(q2);
      float v3 = r ? bf_hi(q3) : bf_lo(q3), v4 = r ? bf_hi(q4) : bf_lo(q4), v5 = r ? bf_hi(q5) : bf_lo(q5);
      if (br == 0) { cc[r] = cmul(cf{v2, v3}, cf{dt * v4, dt * v5}); }
      else { v0 = -bf_round(expf(v0)); cc[r] = cf{2.f * dt * v2, 2.f * dt * v3}; }
      const float xl = (dt * v0) * 1.4426950408889634f, y = dt * v1;
      zz1[r] = cexp_p(xl, y, 1.f); zz128[r] = cexp_p(xl, y, 128.f);
    }
    STAMP(2);
    const uint32_t tb = scr + lane * 16;
    const uint32_t ta = scr + (lane >> 3) * 512 + (lane & 7) * 16;
    const uint32_t tc = scr + 4096 + ((lane >> 3) & 1) * 512 + (lane >> 4) * 128 + (lane & 7) * 16;
    const uint32_t tm = scr + 5120 + ((lane >> 3) & 1) * 64 + (lane >> 4) * 16;
#pragma unroll 1
    for (int r = 0; r < 2; r++) {
      const cf c = r ? cc[1] : cc[0], z1 = r ? zz1[1] : zz1[0], z128 = r ? zz128[1] : zz128[0];
      const cf z2 = csq(z1), z4 = csq(z2), z8 = csq(z4);
      const cf z16 = csq(z8), z24 = cmul(z16, z8), z32 = csq(z16), z40 = cmul(z32, z8), z48 = csq(z24), z56 = cmul(z32, z24), z64 = csq(z32);
      const cf z256 = csq(z128), z512 = csq(z256), z1024 = csq(z512), z2048 = csq(z1024);
      k2048 += fmaf(c.re, z2048.re, -c.im * z2048.im);
      __syncwarp();
      {
        uint32_t xr[4] = {pack_bf16(1.f, z8.re), pack_bf16(z16.re, z24.re), pack_bf16(z32.re, z40.re), pack_bf16(z48.re, z56.re)};
        uint32_t xi[4] = {pack_bf16(0.f, -z8.im), pack_bf16(-z16.im, -z24.im), pack_bf16(-z32.im, -z40.im), pack_bf16(-z48.im, -z56.im)};
        sts128(tb + 0 * 512, xr[0], xr[1], xr[2], xr[3]);
        sts128(tb + 2 * 512, xi[0], xi[1], xi[2], xi[3]);
        const uint32_t yr = pack_bf16(z64.re, z64.re), nyi = pack_bf16(z64.im, z64.im), yi = nyi ^ 0x80008000u;
        uint32_t o[4], q[4];
#pragma unroll
        for (int i = 0; i < 4; i++) CMUL2(o[i], q[i], xr[i], xi[i], yr, yi, nyi);
        sts128(tb + 1 * 512, o[0], o[1], o[2], o[3]);
        sts128(tb + 3 * 512, q[0], q[1], q[2], q[3]);
      }
      {
        const cf h1 = cmul(c, z128), h2 = cmul(c, z256), h3 = cmul(h1, z256), h4 = cmul(c, z512), h5 = cmul(h1, z512), h6 = cmul(h2, z512), h7 = cmul(h3, z512);
        const cf e1 = cmul(c, z1), e2 = cmul(c, z2), e3 = cmul(e1, z2), e129 = cmul(h1, z1), e130 = cmul(h1, z2), e131 = cmul(e129, z2);
        const cf e258 = cmul(h2, z2), e386 = cmul(h3, z2);
        const uint32_t pr0 = pack_bf16(c.re, e1.re), pr2 = pack_bf16(h1.re, e129.re), pi0 = pack_bf16(c.im, e1.im), pi2 = pack_bf16(h1.im, e129.im);
        sts128(tb + 4 * 512, pr0, pack_bf16(e2.re, e3.re), pr2, pack_bf16(e130.re, e131.re));
        sts128(tb + 5 * 512, pi0, pack_bf16(e2.im, e3.im), pi2, pack_bf16(e130.im, e131.im));
        uint32_t xr[4] = {pack_bf16(h2.re, e258.re), pack_bf16(h3.re, e386.re), pack_bf16(h4.re, h5.re), pack_bf16(h6.re, h7.re)};
        uint32_t xi[4] = {pack_bf16(h2.im, e258.im), pack_bf16(h3.im, e386.im), pack_bf16(h4.im, h5.im), pack_bf16(h6.im, h7.im)};
        sts128(tb + 6 * 512, xr[0], xr[1], xr[2], xr[3]);
        sts128(tb + 7 * 512, xi[0], xi[1], xi[2], xi[3]);
        xr[1] = __byte_perm(xr[0], xr[1], 0x5410); xi[1] = __byte_perm(xi[0], xi[1], 0x5410);
        xr[0] = __byte_perm(pr0, pr2, 0x5410); xi[0] = __byte_perm(pi0, pi2, 0x5410);
        const uint32_t yr = pack_bf16(z1024.re, z1024.re), yi = pack_bf16(z1024.im, z1024.im), nyi = yi ^ 0x80008000u;
        uint32_t o[4], q[4];
#pragma unroll
        for (int i = 0; i < 4; i++) CMUL2(o[i], q[i], xr[i], xi[i], yr, yi, nyi);
        sts128(tb + 8 * 512, o[0], o[1], o[2], o[3]);
        sts128(tb + 9 * 512, q[0], q[1], q[2], q[3]);
        const uint32_t m4 = pack_bf16(z4.re, z4.im);
        sts16(scr + 5120 + lane * 2, m4); sts16(scr + 5184 + lane * 2, m4 >> 16);
      }
      __syncwarp();
#pragma unroll
      for (int kp = 0; kp < 2; kp++) {
        uint32_t rr[2], ri[2], yr[2], yi[2];
        ldsm4t(tc + kp * 256, rr[0], ri[0], rr[1], ri[1]);
        ldsm4(tm + kp * 32, yr[0], yi[0], yr[1], yi[1]);
#pragma unroll
        for (int k2 = 0; k2 < 2; k2++) {
          const int kk = kp * 2 + k2;
          uint32_t a0, a1, a2, a3, pr, pi, qr, qi, xr, xi;
          ldsm4t(ta + kk * 128, a0, a1, a2, a3);
          ldsm4t(ta + 2048 + kk * 128, pr, pi, qr, qi);
          const uint32_t nyi = yi[k2] ^ 0x80008000u;
          mma16816(acc[0], a0, a1, a2, a3, pr, pi);
          mma16816(acc[2], a0, a1, a2, a3, qr, qi);
          mma16816(acc[4], a0, a1, a2, a3, rr[k2], ri[k2]);
          CMUL2(xr, xi, pr, pi, yr[k2], yi[k2], nyi);
          mma16816(acc[1], a0, a1, a2, a3, xr, xi);
          CMUL2(xr, xi, qr, qi, yr[k2], yi[k2], nyi);
          mma16816(acc[3], a0, a1, a2, a3, xr, xi);
        }
      }
    }
#pragma unroll
    for (int o = 16; o; o >>= 1) k2048 += __shfl_xor_sync(0xffffffffu, k2048, o);
  }
  STAMP(3);
  __syncwarp();
  {
    const uint32_t xs = scr + lane * 16;
#define OTH(i, k) __float_as_uint(hf ? acc[i][k] : acc[i][2 + (k)])
    sts128(xs, OTH(0, 0), OTH(0, 1), OTH(1, 0), OTH(1, 1));
    sts128(xs + 512, OTH(2, 0), OTH(2, 1), OTH(3, 0), OTH(3, 1));
    sts128(xs + 1024, OTH(4, 0), OTH(4, 1), __float_as_uint(k2048), 0);
#undef OTH
  }

  mbar_wait(sb + B_RAW);
  STAMP(4);
  {
    const uint32_t dst = sb + CH_OFF + (g & 3) * CH_BYTES + U_OFF + t * U_CS + (63 - warp * 4) * 16;
#pragma unroll
    for (int i = 0; i < 4; i++) {
      uint32_t r0, r1, r2, r3;
      ldsm4t(sb + RAW_OFF + (warp * 4 + i) * 512 + lane * 16, r0, r1, r2, r3);
      if ((uint32_t)(g >> 2) == rank) sts128(dst - i * 16, r0, r1, r2, r3);
    }
  }

  bar_sync(1 + (warp >> 1), 64);
  {
    const uint32_t xo = cb + W5_OFF + (wq ^ 1) * SCR_BYTES + lane * 16;
    const uint4 o0 = lds128(xo), o1 = lds128(xo + 512), o2 = lds128(xo + 1024);
    const uint32_t rb = cb + R_OFF + br * R_BR;
#define OWN(i, k) (hf ? acc[i][2 + (k)] : acc[i][k])
    const uint32_t vP = pack_bf16(OWN(0, 1) + __uint_as_float(o0.y), OWN(0, 0) + __uint_as_float(o0.x));
    const uint32_t vP4 = pack_bf16(OWN(1, 1) + __uint_as_float(o0.w), OWN(1, 0) + __uint_as_float(o0.z));
    const uint32_t vQ = pack_bf16(OWN(2, 1) + __uint_as_float(o1.y), OWN(2, 0) + __uint_as_float(o1.x));
    const uint32_t vQ4 = pack_bf16(OWN(3, 1) + __uint_as_float(o1.w), OWN(3, 0) + __uint_as_float(o1.z));
    const uint32_t vR = pack_bf16(OWN(4, 1) + __uint_as_float(o2.y), OWN(4, 0) + __uint_as_float(o2.x));
#undef OWN
    const int j = g + 8 * hf;
    {
      const int a = 2 * (t & 1) + 64 * (t & 2) + 8 * j;
      const uint32_t ad = rb + 2 * (RD_X0 - 1 - a);
      const uint32_t a1 = (t & 2) ? ad - 8 : ad, a2 = (t & 2) ? ad : ad - 8;
      const uint32_t w1 = (t & 2) ? vP4 : vP, w2 = (t & 2) ? vP : vP4;
      sts32(a1, w1); sts32(a2, w2);
      sts16(a1 + RD_CS + 2, w1); sts16(a1 + RD_CS + 4, w1 >> 16);
      sts16(a2 + RD_CS + 2, w2); sts16(a2 + RD_CS + 4, w2 >> 16);
    }
    if (t < 2) {
      const int b = 256 + 128 * t + 8 * j;
      const uint32_t ad = rb + 2 * (RD_X0 - 6 - b);
      const uint32_t v22 = __byte_perm(vQ4, 0, 0x3232), v00 = __byte_perm(vQ, 0, 0x3232);
      sts16(ad, vQ4);
      sts64(ad + 2, v22, __byte_perm(vQ4, vQ, 0x5432));
      sts32(ad + 10, v00);
      if (b != 256) { sts16(ad + 14, v00); sts128(ad + RD_CS + 2, vQ4, v22, vQ, v00); }
      else { sts64(ad + RD_CS + 2, vQ4, v22); sts32(ad + RD_CS + 10, vQ); sts16(ad + RD_CS + 14, v00); }
    } else {
      const uint32_t ao = rb + R_O2 + 2 * (159 - (32 * t + j)), ae = ao - (R_O2 - R_E2) + 2;
      sts16(ao, vQ4 >> 16); sts16(ao + RS_CS + 2, vQ4 >> 16); sts16(ao - 32, vQ4); sts16(ao - 32 + RS_CS + 2, vQ4);
      sts16(ae - 32, vQ); sts16(ae - 32 + RS_CS + 2, vQ);
      if (lane != 2 || hf) { sts16(ae, vQ >> 16); sts16(ae + RS_CS + 2, vQ >> 16); }
      else {
        const uint32_t vv = __byte_perm(vQ, 0, 0x3232), ad = rb + 2 * (RD_X0 - 514);
        sts16(ad, vv); sts32(ad + 2, vv); sts16(ad + 6, vv); sts64(ad + RD_CS + 2, vv, vv);
      }
    }
    {
      const uint32_t a = rb + ((g & 1) ? R_O3 : R_E3 + 2) + 2 * (159 - (64 + 16 * t + (j >> 1)));
      const bool p1024 = (lane == 0) && (hf == 0);
      const uint32_t a00 = p1024 ? rb + R_E2 + 2 * (159 - 127) : a;
      sts16(a00, vR >> 16); sts16(a00 + RS_CS + 2, vR >> 16);
      sts16(a - 16, vR); sts16(a - 16 + RS_CS + 2, vR);
      if (p1024) {
        sts32(sb + K1024_OFF + (ch * 2 + br) * 4, vR & 0xffff0000u);
        const uint32_t kv = pack_bf16(k2048 + __uint_as_float(o2.z), 0.f);
        sts16(rb + R_E3 + 2 * (159 - 127), kv); sts16(rb + R_E3 + 2 * (159 - 127) + RS_CS + 2, kv);
      }
    }
  }
  STAMP(5);
  const uint32_t tag = (epoch + 1) & 0xffffu;
  const int grow = blockIdx.x * 16 + warp;
  const uint4 gx0 = *(const uint4*)(p.u + (size_t)grow * D + lane * 8), gx1 = *(const uint4*)(p.u + (size_t)grow * D + 256 + lane * 8);
  const uint4 gw0 = *(const uint4*)(p.gw + lane * 8), gw1 = *(const uint4*)(p.gw + 256 + lane * 8);
  fence_async();
  __syncthreads();
  unsigned int ticket = 0;
  if (tid == 0) ticket = atomicAdd(&g_ticket, 1u);
  STAMP(6);

  const uint32_t rb = cb + R_OFF + br * R_BR;
  const int eo = 16 * hf + g - 2 * t;
  float dacc[32];
  const int early = ch >> 1;
  if (!early) window_sums(cb, wq, lane);
  STAMP(7);
  {
      {
        const uint32_t xs[8] = {gx0.x, gx0.y, gx0.z, gx0.w, gx1.x, gx1.y, gx1.z, gx1.w};
        const uint32_t ws[8] = {gw0.x, gw0.y, gw0.z, gw0.w, gw1.x, gw1.y, gw1.z, gw1.w};
        const int x0 = RD_X0 - (eo + 536);
        const uint32_t fa = rb + ((g & 1) ? 2 * x0 : RD_CS + 2 * x0 + 2);
        const uint64_t ub = mkdesc(cb + U_OFF, U_CS, 128);
        uint32_t f[2][9];
#pragma unroll
        for (int i = 0; i < 9; i++) f[0][i] = lds32(fa + (62 + i) * 16);
#pragma unroll
        for (int j = 0; j < 9; j++) {
          wg_fence();
#pragma unroll
          for (int k = 0; k < 4; k++) {
            const int s = 34 - 4 * j - k;
            if (s >= 0) {
              const int o = 2 * s - 66 + 128;
              const int cc = o & 3, rs = (o >> 2) - 32;
              const int n0 = ((-rs) >> 3) * 8;
              const uint64_t desc = ub + (uint64_t)((cc * U_CS - rs * 16) >> 4);
              const int fi = 2 * (3 - k);
              const uint32_t a1 = f[j & 1][fi], a0 = f[j & 1][fi + 1], a2 = f[j & 1][fi + 2];
              if (n0 == 0) wgmma_rs<64, 0>(dacc, a0, a1, a2, a0, desc, s != 34);
              else if (n0 == 8) wgmma_rs<56, 0>(dacc, a0, a1, a2, a0, desc, 1);
              else wgmma_rs<48, 0>(dacc, a0, a1, a2, a0, desc, 1);
            }
          }
          wg_commit();
          if (j < 8) {
#pragma unroll
            for (int i = 0; i < 9; i++) {
              const int idx = 62 - 8 * (j + 1) + i;
              if (idx >= 0) f[(j + 1) & 1][i] = lds32(fa + idx * 16);
            }
          }
          if (j == 2) {
            float s = 0.f;
#pragma unroll
            for (int i = 0; i < 8; i++) { const uint32_t pr = hmul2(xs[i], ws[i]); s += bf_lo(pr); s += bf_hi(pr); }
#pragma unroll
            for (int o = 16; o; o >>= 1) s += __shfl_xor_sync(0xffffffffu, s, o);
            s = bf_round(s);
            const float gv = __fdividef(1.f, 1.f + expf(-s));
            const uint32_t w = (tag << 16) | (pack_bf16(gv, 0.f) & 0xffffu);
            if (lane == 0) asm volatile("st.relaxed.gpu.global.u32 [%0], %1;" ::"l"(&g_gate[grow]), "r"(w) : "memory");
          }
          wg_wait0();
        }
      }
      const uint32_t yb = cb + Y0_OFF + br * 4096;
#pragma unroll
      for (int i = 0; i < 8; i += 2) {
        const int mi = lane >> 3;
        const int cidx = 4 * (63 - 8 * (i + (mi >> 1)) - (lane & 7)) + 2 * hf + (mi & 1);
        stsm4t(yb + ysw(cidx), pack_bf16(dacc[4 * i], dacc[4 * i + 1]), pack_bf16(dacc[4 * i + 2], dacc[4 * i + 3]),
               pack_bf16(dacc[4 * i + 4], dacc[4 * i + 5]), pack_bf16(dacc[4 * i + 6], dacc[4 * i + 7]));
      }
      if (!early) bar_arrive(13, 512);
      STAMP(8);
  }
  if (early) window_sums(cb, wq, lane);
  bar_sync(9 + ch, 128);
  const int x1 = 159 - (eo + 136);
  const uint32_t fs = rb + ((g & 1) ? 2 * x1 : RS_CS + 2 * x1 + 2);
  {
    uint32_t f[2][10];
    const uint64_t d5 = mkdesc(cb + W5_OFF, 144, 576), d3 = mkdesc(cb + W3_OFF, 144, 576);
#pragma unroll
    for (int i = 0; i < 5; i++) { f[0][i] = lds32(fs + R_E2 + (8 + i) * 16); f[0][5 + i] = lds32(fs + R_O2 + (8 + i) * 16); }
#pragma unroll
    for (int m = 2; m <= 4; m++) {
      wg_fence();
#pragma unroll
      for (int k = 0; k < 4; k++) {
        const uint32_t* a = &f[m & 1][(k >> 1) * 5 + (k & 1) * 2];
        const uint64_t desc = ((k >> 1) ? d3 : d5) + (k & 1) * 18 + (m - 2) * 36;
        if (m == 2) wgmma_rs<48, 1>(dacc, a[1], a[0], a[2], a[1], desc, k);
        else if (m == 3) wgmma_rs<40, 1>(dacc, a[1], a[0], a[2], a[1], desc, 1);
        else wgmma_rs<32, 1>(dacc, a[1], a[0], a[2], a[1], desc, 1);
      }
      wg_commit();
#pragma unroll
      for (int i = 0; i < 5; i++) {
        if (m < 4) { f[(m + 1) & 1][i] = lds32(fs + R_E2 + (4 * (3 - m) + i) * 16); f[(m + 1) & 1][5 + i] = lds32(fs + R_O2 + (4 * (3 - m) + i) * 16); }
        else { f[1][i] = lds32(fs + R_E3 + (8 + i) * 16); f[1][5 + i] = lds32(fs + R_O3 + (8 + i) * 16); }
      }
      wg_wait0();
    }
    {
      const uint32_t yb = cb + Y2_OFF + br * 3072;
#pragma unroll
      for (int i = 0; i < 6; i += 2) {
        const int mi = lane >> 3;
        const int cidx = 32 * (5 - i - (mi >> 1)) + 16 * hf + 8 * (mi & 1) + (lane & 7);
        stsm4(yb + ysw(cidx), pack_bf16(dacc[4 * i], dacc[4 * i + 1]), pack_bf16(dacc[4 * i + 2], dacc[4 * i + 3]),
              pack_bf16(dacc[4 * i + 4], dacc[4 * i + 5]), pack_bf16(dacc[4 * i + 6], dacc[4 * i + 7]));
      }
    }
    if (!early) bar_arrive(14, 512);
    STAMP(9);
    const uint64_t d9 = mkdesc(cb + W9_OFF, 144, 576), d7 = mkdesc(cb + W7_OFF, 144, 576);
#pragma unroll
    for (int m = 2; m <= 3; m++) {
      wg_fence();
#pragma unroll
      for (int k = 0; k < 4; k++) {
        const uint32_t* a = &f[(m + 1) & 1][(k >> 1) * 5 + (k & 1) * 2];
        const uint64_t desc = ((k >> 1) ? d7 : d9) + (k & 1) * 18 + (m - 2) * 72;
        if (m == 2) wgmma_rs<32, 1>(dacc, a[1], a[0], a[2], a[1], desc, k);
        else wgmma_rs<16, 1>(dacc, a[1], a[0], a[2], a[1], desc, 1);
      }
      wg_commit();
      if (m == 2) {
#pragma unroll
        for (int i = 0; i < 5; i++) { f[0][i] = lds32(fs + R_E3 + (4 + i) * 16); f[0][5 + i] = lds32(fs + R_O3 + (4 + i) * 16); }
      }
      wg_wait0();
    }
    const uint32_t yb = cb + Y3_OFF + br * 2048;
#pragma unroll
    for (int i = 0; i < 4; i += 2) {
      const int mi = lane >> 3;
      const int cidx = 64 * (1 - (i >> 1)) + 2 * (16 * hf + 8 * (mi & 1) + (lane & 7)) + (mi >> 1);
      stsm4(yb + ysw(cidx), pack_bf16(dacc[4 * i], dacc[4 * i + 1]), pack_bf16(dacc[4 * i + 2], dacc[4 * i + 3]),
            pack_bf16(dacc[4 * i + 4], dacc[4 * i + 5]), pack_bf16(dacc[4 * i + 6], dacc[4 * i + 7]));
    }
  }
  STAMP(10);

  {
    const uint2 dA = *(const uint2*)(p.A_D + blockIdx.x * 4), dB = *(const uint2*)(p.B_D + blockIdx.x * 4);
#pragma unroll 1
    for (int lvl = early ? 0 : 2; lvl < 3; lvl++) {
      const int box = (lvl == 2) ? 4 + ch : 2 * lvl + (ch & 1);
      const int x = box * 128 + wtid;
      uint2 gv;
      {
        const unsigned int* gp = g_gate + x * 2;
        int spins = 0;
#pragma unroll 1
        while (true) {
          asm volatile("ld.relaxed.gpu.global.v2.u32 {%0,%1}, [%2];" : "=r"(gv.x), "=r"(gv.y) : "l"(gp) : "memory");
          if ((gv.x >> 16) == tag && (gv.y >> 16) == tag) break;
          if (++spins > (1 << 16)) {
            gv.x = gate_slow(p.u, p.gw, x * 2); gv.y = gate_slow(p.u, p.gw, x * 2 + 1);
            break;
          }
        }
      }
      const uint32_t g2 = __byte_perm(gv.x, gv.y, 0x5410), h2 = hsub2(0x3f803f80u, g2);
      const int c = x >> 2;
      const uint32_t ho = sb + CH_OFF + (x & 3) * 4;
      const uint32_t y0 = ho + Y0_OFF + ysw(c), y2 = ho + Y2_OFF + ysw(c - 64), y3 = ho + Y3_OFF + ysw(c - 128);
      const uint32_t s2 = ho + S2_OFF + ((c - 128) + ((c - 128) >> 3)) * 16, uo = ho + U_OFF + (c & 3) * U_CS + (63 - (c >> 2)) * 16;
      bar_sync(13 + lvl, 512);
      STAMP(11 + lvl);
      uint32_t o[4];
#pragma unroll
      for (int k = 0; k < 4; k++) {
        uint32_t a = lds32(y0 + k * CH_BYTES), b = lds32(y0 + k * CH_BYTES + 4096);
        const uint32_t uu = lds32(uo + k * CH_BYTES);
        if (lvl) {
          const uint32_t a2 = lds32(y2 + k * CH_BYTES), b2 = lds32(y2 + k * CH_BYTES + 3072);
          float ya0 = bf_lo(a) + bf_lo(a2), ya1 = bf_hi(a) + bf_hi(a2), yb0 = bf_lo(b) + bf_lo(b2), yb1 = bf_hi(b) + bf_hi(b2);
          if (lvl == 2) {
            const uint32_t a3 = lds32(y3 + k * CH_BYTES), b3 = lds32(y3 + k * CH_BYTES + 2048), s = lds32(s2 + k * CH_BYTES);
            const uint2 kk = lds64(sb + K1024_OFF + k * 8);
            const float ka = __uint_as_float(kk.x), kb = __uint_as_float(kk.y), s0 = bf_lo(s), s1 = bf_hi(s);
            ya0 += fmaf(ka, s0, bf_lo(a3)); ya1 += fmaf(ka, s1, bf_hi(a3));
            yb0 += fmaf(kb, s0, bf_lo(b3)); yb1 += fmaf(kb, s1, bf_hi(b3));
          }
          a = pack_bf16(ya0, ya1); b = pack_bf16(yb0, yb1);
        }
        const uint32_t da2 = __byte_perm((k & 2) ? dA.y : dA.x, 0, (k & 1) ? 0x3232 : 0x1010);
        const uint32_t db2 = __byte_perm((k & 2) ? dB.y : dB.x, 0, (k & 1) ? 0x3232 : 0x1010);
        a = hadd2(a, hmul2(uu, da2)); b = hadd2(b, hmul2(uu, db2));
        o[k] = hadd2(hmul2(g2, a), hmul2(h2, b));
      }
      const uint32_t r00 = __byte_perm(o[0], o[1], 0x5410), r01 = __byte_perm(o[2], o[3], 0x5410);
      const uint32_t r10 = __byte_perm(o[0], o[1], 0x7632), r11 = __byte_perm(o[2], o[3], 0x7632);
      const int slot = box >> 1;
      const uint32_t xin = sb + XIN_OFF + slot * 2048 + wtid * 16, xbar = sb + B_X + slot * 8;
      if ((uint32_t)(box & 1) != rank) {
        st_async4(mapa(xin, rank ^ 1), mapa(xbar, rank ^ 1), r00, r01, r10, r11);
      } else {
        mbar_wait(xbar);
        const uint4 q = lds128(xin);
        const uint32_t st = sb + RAW_OFF + slot * 4096 + wtid * 16;
        if (rank == 0) { sts128(st, r00, r01, q.x, q.y); sts128(st + 2048, r10, r11, q.z, q.w); }
        else { sts128(st, q.x, q.y, r00, r01); sts128(st + 2048, q.z, q.w, r10, r11); }
        fence_async();
        bar_sync(9 + ch, 128);
        if (wtid == 0) {
          asm volatile("cp.async.bulk.tensor.3d.global.shared::cta.bulk_group [%0, {%2, %3, %4}], [%1];"
                       ::"l"(&tm_out), "r"(sb + RAW_OFF + slot * 4096), "r"(oc0), "r"(box * 128), "r"(0) : "memory");
          asm volatile("cp.async.bulk.commit_group;" ::: "memory");
        }
      }
    }
    STAMP(14);
    if (tid == 0 && ticket == NCTA - 1) { g_ticket = 0; g_epoch = epoch + 1; }
    if (wtid == 0) asm volatile("cp.async.bulk.wait_group.read 0;" ::: "memory");
  }
  STAMP(15); GT(1);
}

typedef CUresult (*EncodeFn)(CUtensorMap*, CUtensorMapDataType, cuuint32_t, void*, const cuuint64_t*, const cuuint64_t*,
                             const cuuint32_t*, const cuuint32_t*, CUtensorMapInterleave, CUtensorMapSwizzle,
                             CUtensorMapL2promotion, CUtensorMapFloatOOBfill);

}

extern "C" void kernel_launch(void* const* d_in, const int* in_sizes, int n_in, void* d_out, int out_size) {
  (void)in_sizes; (void)n_in; (void)out_size;
  typedef const __nv_bfloat16* bp;
  Params p;
  p.u = (bp)d_in[0]; p.A_re = (bp)d_in[1]; p.A_im = (bp)d_in[2]; p.B_re = (bp)d_in[3]; p.B_im = (bp)d_in[4];
  p.C_re = (bp)d_in[5]; p.C_im = (bp)d_in[6]; p.A_ldt = (bp)d_in[7]; p.A_D = (bp)d_in[8];
  p.B_lA = (bp)d_in[10]; p.B_Aim = (bp)d_in[11]; p.B_Cre = (bp)d_in[12]; p.B_Cim = (bp)d_in[13];
  p.B_ldt = (bp)d_in[14]; p.B_D = (bp)d_in[15]; p.gw = (bp)d_in[16];
  static EncodeFn enc = nullptr;
  if (!enc) {
    cudaDriverEntryPointQueryResult qr;
    cudaGetDriverEntryPoint("cuTensorMapEncodeTiled", (void**)&enc, cudaEnableDefault, &qr);
    cudaFuncSetAttribute(ssm_kernel, cudaFuncAttributeMaxDynamicSharedMemorySize, SMEM_BYTES);
  }
  CUtensorMap tm_in, tm_out;
  {
    cuuint64_t gd[5] = {512, 2, 4, 4, 64};
    cuuint64_t gs[4] = {1024, 8192, 2048, 32768};
    cuuint32_t bx[5] = {8, 2, 4, 4, 32};
    cuuint32_t es[5] = {1, 1, 1, 1, 1};
    enc(&tm_in, CU_TENSOR_MAP_DATA_TYPE_BFLOAT16, 5, d_in[0], gd, gs, bx, es, CU_TENSOR_MAP_INTERLEAVE_NONE,
        CU_TENSOR_MAP_SWIZZLE_NONE, CU_TENSOR_MAP_L2_PROMOTION_NONE, CU_TENSOR_MAP_FLOAT_OOB_FILL_NONE);
  }
  {
    cuuint64_t gd[3] = {512, 1024, 2};
    cuuint64_t gs[2] = {2048, 1024};
    cuuint32_t bx[3] = {8, 128, 2};
    cuuint32_t es[3] = {1, 1, 1};
    enc(&tm_out, CU_TENSOR_MAP_DATA_TYPE_BFLOAT16, 3, d_out, gd, gs, bx, es, CU_TENSOR_MAP_INTERLEAVE_NONE,
        CU_TENSOR_MAP_SWIZZLE_NONE, CU_TENSOR_MAP_L2_PROMOTION_NONE, CU_TENSOR_MAP_FLOAT_OOB_FILL_NONE);
  }
  ssm_kernel<<<NCTA, 512, SMEM_BYTES, cudaStreamPerThread>>>(p, tm_in, tm_out);
}
```

```cpp
#include <cuda_runtime.h>
#include <cuda.h>
#include <cuda_bf16.h>
#include <stdint.h>

namespace {

constexpr int L = 2048, D = 512, NM = 128;
constexpr int NCTA = 128;

constexpr int RAW_OFF = 0;
constexpr int XIN_OFF = 32768;
constexpr int BAR_OFF = XIN_OFF + 10240;
constexpr int CH_OFF = BAR_OFF + 128;
constexpr int U_CS = 1184;
constexpr int U_OFF = 0;
constexpr int R_OFF = 4736;
constexpr int RD_X0 = 565;
constexpr int RD_CS = 1216;
constexpr int RS_CS = 320;
constexpr int R_E2 = 2 * RD_CS, R_O2 = R_E2 + 2 * RS_CS, R_E3 = R_O2 + 2 * RS_CS, R_O3 = R_E3 + 2 * RS_CS;
constexpr int R_BR = R_O3 + 2 * RS_CS;
constexpr int W5_OFF = R_OFF + 2 * R_BR;
constexpr int W3_OFF = W5_OFF + 3456;
constexpr int W9_OFF = W3_OFF + 3456;
constexpr int W7_OFF = W9_OFF + 2304;
constexpr int S2_OFF = W7_OFF + 2304;
constexpr int Y0_OFF = S2_OFF + 2304;
constexpr int Y2_OFF = Y0_OFF + 8192, Y3_OFF = Y2_OFF + 6144;
constexpr int CH_BYTES = Y0_OFF + 18432 + 16;
constexpr int SCR_BYTES = 4608;
constexpr int SMEM_BYTES = CH_OFF + 4 * CH_BYTES;
static_assert(CH_BYTES % 128 == 16, "bank staggering of the channel blocks");
static_assert(SMEM_BYTES <= 232448, "smem");
constexpr int B_RAW = BAR_OFF, B_X = BAR_OFF + 8, B_U = BAR_OFF + 40, B_W = BAR_OFF + 48;
constexpr int K1024_OFF = BAR_OFF + 64;

__device__ unsigned int g_gate[L];
__device__ unsigned int g_epoch;
__device__ unsigned int g_ticket;

#define STAMP(k)
#define GT(k)

struct Params {
  const __nv_bfloat16 *u, *A_re, *A_im, *B_re, *B_im, *C_re, *C_im, *A_ldt, *A_D;
  const __nv_bfloat16 *B_lA, *B_Aim, *B_Cre, *B_Cim, *B_ldt, *B_D, *gw;
};

template <int N, int TB> __device__ __forceinline__ void wgmma_rs(float* d, uint32_t a0, uint32_t a1, uint32_t a2, uint32_t a3, uint64_t desc, int sc);
template <> __device__ __forceinline__ void wgmma_rs<64, 0>(float* d, uint32_t a0, uint32_t a1, uint32_t a2, uint32_t a3, uint64_t desc, int sc) {
  asm volatile("{\n.reg .pred p;\nsetp.ne.b32 p, %37, 0;\n"
    "wgmma.mma_async.sync.aligned.m64n64k16.f32.bf16.bf16 {%0,%1,%2,%3,%4,%5,%6,%7,%8,%9,%10,%11,%12,%13,%14,%15,%16,%17,%18,%19,%20,%21,%22,%23,%24,%25,%26,%27,%28,%29,%30,%31}, {%32,%33,%34,%35}, %36, p, 1, 1, 0;\n}"
    : "+f"(d[0]), "+f"(d[1]), "+f"(d[2]), "+f"(d[3]), "+f"(d[4]), "+f"(d[5]), "+f"(d[6]), "+f"(d[7]), "+f"(d[8]), "+f"(d[9]), "+f"(d[10]), "+f"(d[11]), "+f"(d[12]), "+f"(d[13]), "+f"(d[14]), "+f"(d[15]), "+f"(d[16]), "+f"(d[17]), "+f"(d[18]), "+f"(d[19]), "+f"(d[20]), "+f"(d[21]), "+f"(d[22]), "+f"(d[23]), "+f"(d[24]), "+f"(d[25]), "+f"(d[26]), "+f"(d[27]), "+f"(d[28]), "+f"(d[29]), "+f"(d[30]), "+f"(d[31]) : "r"(a0), "r"(a1), "r"(a2), "r"(a3), "l"(desc), "r"(sc));
}
template <> __device__ __forceinline__ void wgmma_rs<56, 0>(float* d, uint32_t a0, uint32_t a1, uint32_t a2, uint32_t a3, uint64_t desc, int sc) {
  asm volatile("{\n.reg .pred p;\nsetp.ne.b32 p, %33, 0;\n"
    "wgmma.mma_async.sync.aligned.m64n56k16.f32.bf16.bf16 {%0,%1,%2,%3,%4,%5,%6,%7,%8,%9,%10,%11,%12,%13,%14,%15,%16,%17,%18,%19,%20,%21,%22,%23,%24,%25,%26,%27}, {%28,%29,%30,%31}, %32, p, 1, 1, 0;\n}"
    : "+f"(d[0]), "+f"(d[1]), "+f"(d[2]), "+f"(d[3]), "+f"(d[4]), "+f"(d[5]), "+f"(d[6]), "+f"(d[7]), "+f"(d[8]), "+f"(d[9]), "+f"(d[10]), "+f"(d[11]), "+f"(d[12]), "+f"(d[13]), "+f"(d[14]), "+f"(d[15]), "+f"(d[16]), "+f"(d[17]), "+f"(d[18]), "+f"(d[19]), "+f"(d[20]), "+f"(d[21]), "+f"(d[22]), "+f"(d[23]), "+f"(d[24]), "+f"(d[25]), "+f"(d[26]), "+f"(d[27]) : "r"(a0), "r"(a1), "r"(a2), "r"(a3), "l"(desc), "r"(sc));
}
template <> __device__ __forceinline__ void wgmma_rs<48, 0>(float* d, uint32_t a0, uint32_t a1, uint32_t a2, uint32_t a3, uint64_t desc, int sc) {
  asm volatile("{\n.reg .pred p;\nsetp.ne.b32 p, %29, 0;\n"
    "wgmma.mma_async.sync.aligned.m64n48k16.f32.bf16.bf16 {%0,%1,%2,%3,%4,%5,%6,%7,%8,%9,%10,%11,%12,%13,%14,%15,%16,%17,%18,%19,%20,%21,%22,%23}, {%24,%25,%26,%27}, %28, p, 1, 1, 0;\n}"
    : "+f"(d[0]), "+f"(d[1]), "+f"(d[2]), "+f"(d[3]), "+f"(d[4]), "+f"(d[5]), "+f"(d[6]), "+f"(d[7]), "+f"(d[8]), "+f"(d[9]), "+f"(d[10]), "+f"(d[11]), "+f"(d[12]), "+f"(d[13]), "+f"(d[14]), "+f"(d[15]), "+f"(d[16]), "+f"(d[17]), "+f"(d[18]), "+f"(d[19]), "+f"(d[20]), "+f"(d[21]), "+f"(d[22]), "+f"(d[23]) : "r"(a0), "r"(a1), "r"(a2), "r"(a3), "l"(desc), "r"(sc));
}
template <> __device__ __forceinline__ void wgmma_rs<48, 1>(float* d, uint32_t a0, uint32_t a1, uint32_t a2, uint32_t a3, uint64_t desc, int sc) {
  asm volatile("{\n.reg .pred p;\nsetp.ne.b32 p, %29, 0;\n"
    "wgmma.mma_async.sync.aligned.m64n48k16.f32.bf16.bf16 {%0,%1,%2,%3,%4,%5,%6,%7,%8,%9,%10,%11,%12,%13,%14,%15,%16,%17,%18,%19,%20,%21,%22,%23}, {%24,%25,%26,%27}, %28, p, 1, 1, 1;\n}"
    : "+f"(d[0]), "+f"(d[1]), "+f"(d[2]), "+f"(d[3]), "+f"(d[4]), "+f"(d[5]), "+f"(d[6]), "+f"(d[7]), "+f"(d[8]), "+f"(d[9]), "+f"(d[10]), "+f"(d[11]), "+f"(d[12]), "+f"(d[13]), "+f"(d[14]), "+f"(d[15]), "+f"(d[16]), "+f"(d[17]), "+f"(d[18]), "+f"(d[19]), "+f"(d[20]), "+f"(d[21]), "+f"(d[22]), "+f"(d[23]) : "r"(a0), "r"(a1), "r"(a2), "r"(a3), "l"(desc), "r"(sc));
}
template <> __device__ __forceinline__ void wgmma_rs<40, 1>(float* d, uint32_t a0, uint32_t a1, uint32_t a2, uint32_t a3, uint64_t desc, int sc) {
  asm volatile("{\n.reg .pred p;\nsetp.ne.b32 p, %25, 0;\n"
    "wgmma.mma_async.sync.aligned.m64n40k16.f32.bf16.bf16 {%0,%1,%2,%3,%4,%5,%6,%7,%8,%9,%10,%11,%12,%13,%14,%15,%16,%17,%18,%19}, {%20,%21,%22,%23}, %24, p, 1, 1, 1;\n}"
    : "+f"(d[0]), "+f"(d[1]), "+f"(d[2]), "+f"(d[3]), "+f"(d[4]), "+f"(d[5]), "+f"(d[6]), "+f"(d[7]), "+f"(d[8]), "+f"(d[9]), "+f"(d[10]), "+f"(d[11]), "+f"(d[12]), "+f"(d[13]), "+f"(d[14]), "+f"(d[15]), "+f"(d[16]), "+f"(d[17]), "+f"(d[18]), "+f"(d[19]) : "r"(a0), "r"(a1), "r"(a2), "r"(a3), "l"(desc), "r"(sc));
}
template <> __device__ __forceinline__ void wgmma_rs<32, 1>(float* d, uint32_t a0, uint32_t a1, uint32_t a2, uint32_t a3, uint64_t desc, int sc) {
  asm volatile("{\n.reg .pred p;\nsetp.ne.b32 p, %21, 0;\n"
    "wgmma.mma_async.sync.aligned.m64n32k16.f32.bf16.bf16 {%0,%1,%2,%3,%4,%5,%6,%7,%8,%9,%10,%11,%12,%13,%14,%15}, {%16,%17,%18,%19}, %20, p, 1, 1, 1;\n}"
    : "+f"(d[0]), "+f"(d[1]), "+f"(d[2]), "+f"(d[3]), "+f"(d[4]), "+f"(d[5]), "+f"(d[6]), "+f"(d[7]), "+f"(d[8]), "+f"(d[9]), "+f"(d[10]), "+f"(d[11]), "+f"(d[12]), "+f"(d[13]), "+f"(d[14]), "+f"(d[15]) : "r"(a0), "r"(a1), "r"(a2), "r"(a3), "l"(desc), "r"(sc));
}
template <> __device__ __forceinline__ void wgmma_rs<16, 1>(float* d, uint32_t a0, uint32_t a1, uint32_t a2, uint32_t a3, uint64_t desc, int sc) {
  asm volatile("{\n.reg .pred p;\nsetp.ne.b32 p, %13, 0;\n"
    "wgmma.mma_async.sync.aligned.m64n16k16.f32.bf16.bf16 {%0,%1,%2,%3,%4,%5,%6,%7}, {%8,%9,%10,%11}, %12, p, 1, 1, 1;\n}"
    : "+f"(d[0]), "+f"(d[1]), "+f"(d[2]), "+f"(d[3]), "+f"(d[4]), "+f"(d[5]), "+f"(d[6]), "+f"(d[7]) : "r"(a0), "r"(a1), "r"(a2), "r"(a3), "l"(desc), "r"(sc));
}

__device__ __forceinline__ uint32_t pack_bf16(float lo, float hi) {
  uint32_t r; asm("cvt.rn.bf16x2.f32 %0, %1, %2;" : "=r"(r) : "f"(hi), "f"(lo)); return r;
}
__device__ __forceinline__ float bf_lo(uint32_t v) { return __uint_as_float(v << 16); }
__device__ __forceinline__ float bf_hi(uint32_t v) { return __uint_as_float(v & 0xffff0000u); }
__device__ __forceinline__ float bf_round(float x) { return bf_lo(pack_bf16(x, 0.f)); }
__device__ __forceinline__ uint32_t hmul2(uint32_t a, uint32_t b) { uint32_t r; asm("mul.rn.bf16x2 %0, %1, %2;" : "=r"(r) : "r"(a), "r"(b)); return r; }
__device__ __forceinline__ uint32_t hadd2(uint32_t a, uint32_t b) { uint32_t r; asm("add.rn.bf16x2 %0, %1, %2;" : "=r"(r) : "r"(a), "r"(b)); return r; }
__device__ __forceinline__ uint32_t hsub2(uint32_t a, uint32_t b) { uint32_t r; asm("sub.rn.bf16x2 %0, %1, %2;" : "=r"(r) : "r"(a), "r"(b)); return r; }
__device__ __forceinline__ uint32_t hfma2(uint32_t a, uint32_t b, uint32_t c) { uint32_t r; asm("fma.rn.bf16x2 %0, %1, %2, %3;" : "=r"(r) : "r"(a), "r"(b), "r"(c)); return r; }

__device__ __forceinline__ void sts16(uint32_t a, uint32_t v) { asm volatile("st.shared.b16 [%0], %1;" ::"r"(a), "h"((unsigned short)v) : "memory"); }
__device__ __forceinline__ void sts32(uint32_t a, uint32_t v) { asm volatile("st.shared.b32 [%0], %1;" ::"r"(a), "r"(v) : "memory"); }
__device__ __forceinline__ void sts64(uint32_t a, uint32_t x, uint32_t y) { asm volatile("st.shared.v2.b32 [%0], {%1,%2};" ::"r"(a), "r"(x), "r"(y) : "memory"); }
__device__ __forceinline__ void sts128(uint32_t a, uint32_t x, uint32_t y, uint32_t z, uint32_t w) {
  asm volatile("st.shared.v4.b32 [%0], {%1,%2,%3,%4};" ::"r"(a), "r"(x), "r"(y), "r"(z), "r"(w) : "memory");
}
__device__ __forceinline__ uint32_t lds32(uint32_t a) { uint32_t v; asm volatile("ld.shared.b32 %0, [%1];" : "=r"(v) : "r"(a) : "memory"); return v; }
__device__ __forceinline__ uint2 lds64(uint32_t a) { uint2 v; asm volatile("ld.shared.v2.b32 {%0,%1}, [%2];" : "=r"(v.x), "=r"(v.y) : "r"(a) : "memory"); return v; }
__device__ __forceinline__ uint4 lds128(uint32_t a) {
  uint4 v; asm volatile("ld.shared.v4.b32 {%0,%1,%2,%3}, [%4];" : "=r"(v.x), "=r"(v.y), "=r"(v.z), "=r"(v.w) : "r"(a) : "memory"); return v;
}
__device__ __forceinline__ void ldsm4(uint32_t a, uint32_t& r0, uint32_t& r1, uint32_t& r2, uint32_t& r3) {
  asm volatile("ldmatrix.sync.aligned.m8n8.x4.shared.b16 {%0,%1,%2,%3}, [%4];" : "=r"(r0), "=r"(r1), "=r"(r2), "=r"(r3) : "r"(a) : "memory");
}
__device__ __forceinline__ void ldsm4t(uint32_t a, uint32_t& r0, uint32_t& r1, uint32_t& r2, uint32_t& r3) {
  asm volatile("ldmatrix.sync.aligned.m8n8.x4.trans.shared.b16 {%0,%1,%2,%3}, [%4];" : "=r"(r0), "=r"(r1), "=r"(r2), "=r"(r3) : "r"(a) : "memory");
}
__device__ __forceinline__ void stsm4(uint32_t a, uint32_t r0, uint32_t r1, uint32_t r2, uint32_t r3) {
  asm volatile("stmatrix.sync.aligned.m8n8.x4.shared.b16 [%0], {%1,%2,%3,%4};" ::"r"(a), "r"(r0), "r"(r1), "r"(r2), "r"(r3) : "memory");
}
__device__ __forceinline__ void stsm4t(uint32_t a, uint32_t r0, uint32_t r1, uint32_t r2, uint32_t r3) {
  asm volatile("stmatrix.sync.aligned.m8n8.x4.trans.shared.b16 [%0], {%1,%2,%3,%4};" ::"r"(a), "r"(r0), "r"(r1), "r"(r2), "r"(r3) : "memory");
}
__device__ __forceinline__ void mma16816(float* c, uint32_t a0, uint32_t a1, uint32_t a2, uint32_t a3, uint32_t b0, uint32_t b1) {
  asm("mma.sync.aligned.m16n8k16.row.col.f32.bf16.bf16.f32 {%0,%1,%2,%3}, {%4,%5,%6,%7}, {%8,%9}, {%0,%1,%2,%3};"
      : "+f"(c[0]), "+f"(c[1]), "+f"(c[2]), "+f"(c[3]) : "r"(a0), "r"(a1), "r"(a2), "r"(a3), "r"(b0), "r"(b1));
}
__device__ __forceinline__ void bar_sync(int id, int n) { asm volatile("bar.sync %0, %1;" ::"r"(id), "r"(n) : "memory"); }
__device__ __forceinline__ void bar_arrive(int id, int n) { asm volatile("bar.arrive %0, %1;" ::"r"(id), "r"(n) : "memory"); }
__device__ __forceinline__ void wg_fence() { asm volatile("wgmma.fence.sync.aligned;" ::: "memory"); }
__device__ __forceinline__ void wg_commit() { asm volatile("wgmma.commit_group.sync.aligned;" ::: "memory"); }
__device__ __forceinline__ void wg_wait0() { asm volatile("wgmma.wait_group.sync.aligned 0;" ::: "memory"); }
__device__ __forceinline__ void fence_async() { asm volatile("fence.proxy.async.shared::cta;" ::: "memory"); }
__device__ __forceinline__ uint64_t mkdesc(uint32_t addr, uint32_t lbo, uint32_t sbo) {
  return (uint64_t)((addr & 0x3FFFF) >> 4) | ((uint64_t)(lbo >> 4) << 16) | ((uint64_t)(sbo >> 4) << 32);
}
__device__ __forceinline__ uint32_t mapa(uint32_t a, uint32_t rank) {
  uint32_t r; asm("mapa.shared::cluster.u32 %0, %1, %2;" : "=r"(r) : "r"(a), "r"(rank)); return r;
}
__device__ __forceinline__ void mbar_init_expect(uint32_t bar, uint32_t bytes) {
  asm volatile("mbarrier.init.shared::cta.b64 [%0], 1;" ::"r"(bar) : "memory");
  asm volatile("mbarrier.arrive.expect_tx.shared::cta.b64 _, [%0], %1;" ::"r"(bar), "r"(bytes) : "memory");
}
__device__ __forceinline__ void mbar_wait(uint32_t bar) {
#pragma unroll 1
  for (int it = 0; it < (1 << 22); it++) {
    uint32_t ok;
    asm volatile("{\n.reg .pred p;\nmbarrier.try_wait.parity.acquire.cluster.shared::cta.b64 p, [%1], 0;\nselp.u32 %0, 1, 0, p;\n}"
                 : "=r"(ok) : "r"(bar) : "memory");
    if (ok) return;
  }
  __trap();
}
__device__ __forceinline__ void st_async4(uint32_t a, uint32_t bar, uint32_t x, uint32_t y, uint32_t z, uint32_t w) {
  asm volatile("st.async.weak.shared::cluster.mbarrier::complete_tx::bytes.v4.b32 [%0], {%2,%3,%4,%5}, [%1];"
               ::"r"(a), "r"(bar), "r"(x), "r"(y), "r"(z), "r"(w) : "memory");
}

struct cf { float re, im; };
__device__ __forceinline__ cf cmul(cf a, cf b) { return {fmaf(a.re, b.re, -a.im * b.im), fmaf(a.re, b.im, a.im * b.re)}; }
__device__ __forceinline__ cf csq(cf a) { return {fmaf(a.re, a.re, -a.im * a.im), (a.re + a.re) * a.im}; }
__device__ __forceinline__ cf cexp_p(float xl, float y, float p) {
  float mag; asm("ex2.approx.ftz.f32 %0, %1;" : "=f"(mag) : "f"(xl * p));
  const float th = y * p;
  const float k = rintf(th * 0.15915494309189535f);
  float r = fmaf(k, -6.2831854820251465f, th);
  r = fmaf(k, 1.7484555314695172e-07f, r);
  return {mag * __cosf(r), mag * __sinf(r)};
}
__device__ __forceinline__ uint32_t ysw(int c) { return (uint32_t)(c ^ ((c >> 3) & 3)) * 16u; }

#define CMUL2(OR, OI, xr, xi, yr, yi, nyi) do { OR = hfma2(xr, yr, hmul2(xi, nyi)); OI = hfma2(xr, yi, hmul2(xi, yr)); } while (0)

__device__ __noinline__ uint32_t gate_slow(const __nv_bfloat16* u, const __nv_bfloat16* gw, int row) {
  float s = 0.f;
  const uint32_t* xr = (const uint32_t*)(u + (size_t)row * D);
  const uint32_t* wr = (const uint32_t*)gw;
#pragma unroll 1
  for (int j = 0; j < D / 2; j++) { const uint32_t pr = hmul2(xr[j], wr[j]); s += bf_lo(pr); s += bf_hi(pr); }
  s = bf_round(s);
  return pack_bf16(1.f / (1.f + expf(-s)), 0.f);
}

__device__ __forceinline__ void prefix6(float* pf, uint32_t ub, int c0) {
  pf[0] = 0.f;
#pragma unroll
  for (int j = 0; j < 6; j++) {
    const int c = c0 + j;
    const uint4 v = lds128(ub + (c & 3) * U_CS + (63 - (c >> 2)) * 16);
    const uint32_t w[4] = {v.x, v.y, v.z, v.w};
#pragma unroll
    for (int i = 0; i < 4; i++) {
      pf[j * 8 + 2 * i + 1] = pf[j * 8 + 2 * i] + bf_lo(w[i]);
      pf[j * 8 + 2 * i + 2] = pf[j * 8 + 2 * i + 1] + bf_hi(w[i]);
    }
  }
}
template <int A, int B>
__device__ __forceinline__ void put_win(const float* pf, int ix, uint32_t addr) {
  uint32_t a[4];
#pragma unroll
  for (int i = 0; i < 4; i++) a[i] = pack_bf16(pf[ix + 2 * i - B + 1] - pf[ix + 2 * i - A], pf[ix + 2 * i - B + 2] - pf[ix + 2 * i - A + 1]);
  sts128(addr, a[0], a[1], a[2], a[3]);
}

__device__ __forceinline__ uint32_t get_gate(const Params& p, int x, uint32_t tag) {
  uint2 gv;
  const unsigned int* gp = g_gate + x * 2;
  int spins = 0;
#pragma unroll 1
  while (true) {
    asm volatile("ld.relaxed.gpu.global.v2.u32 {%0,%1}, [%2];" : "=r"(gv.x), "=r"(gv.y) : "l"(gp) : "memory");
    if ((gv.x >> 16) == tag && (gv.y >> 16) == tag) break;
    if (++spins > (1 << 16)) {
      gv.x = gate_slow(p.u, p.gw, x * 2); gv.y = gate_slow(p.u, p.gw, x * 2 + 1);
      break;
    }
  }
  return __byte_perm(gv.x, gv.y, 0x5410);
}

__device__ __noinline__ void final_box(uint32_t sb, const CUtensorMap* tm_out, int lvl, int box, int wtid, uint32_t rank, int oc0,
                                       uint32_t g2, uint2 dA, uint2 dB, int barid) {
  const int x = box * 128 + wtid;
  const uint32_t h2 = hsub2(0x3f803f80u, g2);
  const int c = x >> 2;
  const uint32_t ho = sb + CH_OFF + (x & 3) * 4;
  const uint32_t y0 = ho + Y0_OFF + ysw(c), y2 = ho + Y2_OFF + ysw(c - 64), y3 = ho + Y3_OFF + ysw(c - 128);
  const uint32_t s2 = ho + S2_OFF + ((c - 128) + ((c - 128) >> 3)) * 16, uo = ho + U_OFF + (c & 3) * U_CS + (63 - (c >> 2)) * 16;
  uint32_t o[4], a[4], b[4], uu[4];
#pragma unroll
  for (int k = 0; k < 4; k++) { a[k] = lds32(y0 + k * CH_BYTES); b[k] = lds32(y0 + k * CH_BYTES + 4096); uu[k] = lds32(uo + k * CH_BYTES); }
  if (lvl) {
    uint32_t a2[4], b2[4];
    float ya0[4], ya1[4], yb0[4], yb1[4];
#pragma unroll
    for (int k = 0; k < 4; k++) { a2[k] = lds32(y2 + k * CH_BYTES); b2[k] = lds32(y2 + k * CH_BYTES + 3072); }
    if (lvl == 2) {
      uint32_t a3[4], b3[4], s[4];
#pragma unroll
      for (int k = 0; k < 4; k++) { a3[k] = lds32(y3 + k * CH_BYTES); b3[k] = lds32(y3 + k * CH_BYTES + 2048); s[k] = lds32(s2 + k * CH_BYTES); }
      const uint4 k0 = lds128(sb + K1024_OFF), k1 = lds128(sb + K1024_OFF + 16);
      const uint32_t kk[8] = {k0.x, k0.y, k0.z, k0.w, k1.x, k1.y, k1.z, k1.w};
#pragma unroll
      for (int k = 0; k < 4; k++) {
        const float ka = __uint_as_float(kk[2 * k]), kb = __uint_as_float(kk[2 * k + 1]), s0 = bf_lo(s[k]), s1 = bf_hi(s[k]);
        ya0[k] = fmaf(ka, s0, bf_lo(a3[k])) + bf_lo(a2[k]); ya1[k] = fmaf(ka, s1, bf_hi(a3[k])) + bf_hi(a2[k]);
        yb0[k] = fmaf(kb, s0, bf_lo(b3[k])) + bf_lo(b2[k]); yb1[k] = fmaf(kb, s1, bf_hi(b3[k])) + bf_hi(b2[k]);
      }
    } else {
#pragma unroll
      for (int k = 0; k < 4; k++) { ya0[k] = bf_lo(a2[k]); ya1[k] = bf_hi(a2[k]); yb0[k] = bf_lo(b2[k]); yb1[k] = bf_hi(b2[k]); }
    }
#pragma unroll
    for (int k = 0; k < 4; k++) {
      a[k] = pack_bf16(ya0[k] + bf_lo(a[k]), ya1[k] + bf_hi(a[k]));
      b[k] = pack_bf16(yb0[k] + bf_lo(b[k]), yb1[k] + bf_hi(b[k]));
    }
  }
#pragma unroll
  for (int k = 0; k < 4; k++) {
    const uint32_t da2 = __byte_perm((k & 2) ? dA.y : dA.x, 0, (k & 1) ? 0x3232 : 0x1010);
    const uint32_t db2 = __byte_perm((k & 2) ? dB.y : dB.x, 0, (k & 1) ? 0x3232 : 0x1010);
    o[k] = hadd2(hmul2(g2, hadd2(a[k], hmul2(uu[k], da2))), hmul2(h2, hadd2(b[k], hmul2(uu[k], db2))));
  }
  const uint32_t r00 = __byte_perm(o[0], o[1], 0x5410), r01 = __byte_perm(o[2], o[3], 0x5410);
  const uint32_t r10 = __byte_perm(o[0], o[1], 0x7632), r11 = __byte_perm(o[2], o[3], 0x7632);
  const int slot = box >> 1;
  const uint32_t xin = sb + XIN_OFF + slot * 2048 + wtid * 16, xbar = sb + B_X + slot * 8;
  if ((uint32_t)(box & 1) != rank) {
    st_async4(mapa(xin, rank ^ 1), mapa(xbar, rank ^ 1), r00, r01, r10, r11);
  } else {
    mbar_wait(xbar);
    const uint4 q = lds128(xin);
    const uint32_t st = sb + RAW_OFF + slot * 4096 + wtid * 16;
    if (rank == 0) { sts128(st, r00, r01, q.x, q.y); sts128(st + 2048, r10, r11, q.z, q.w); }
    else { sts128(st, q.x, q.y, r00, r01); sts128(st + 2048, q.z, q.w, r10, r11); }
    fence_async();
    bar_sync(barid, 128);
    if (wtid == 0) {
      asm volatile("cp.async.bulk.tensor.3d.global.shared::cta.bulk_group [%0, {%2, %3, %4}], [%1];"
                   ::"l"(tm_out), "r"(sb + RAW_OFF + slot * 4096), "r"(oc0), "r"(box * 128), "r"(0) : "memory");
      asm volatile("cp.async.bulk.commit_group;" ::: "memory");
    }
  }
}

__device__ __forceinline__ void window_sums(uint32_t cb, int wq, int lane) {
      float pf[49];
      if (wq == 0 || wq == 3) {
        if (wq == 0 || lane < 16) {
          const int nu = wq ? 32 + lane : lane;
          prefix6(pf, cb + U_OFF, 4 * nu - 2);
          const uint32_t po = (5 - (nu >> 3)) * 576 + ((nu & 7) >> 1) * 144 + (nu & 1) * 64;
#pragma unroll
          for (int k = 0; k < 4; k++) { put_win<10, 6>(pf, 16 + 8 * k, cb + W5_OFF + po + k * 16); put_win<5, 3>(pf, 16 + 8 * k, cb + W3_OFF + po + k * 16); }
        }
      } else {
        const uint32_t po = (1 - (lane >> 4)) * 1152 + ((lane & 15) >> 2) * 144 + (lane & 3) * 32;
        if (wq == 1) {
          prefix6(pf, cb + U_OFF, 4 * lane - 3);
#pragma unroll
          for (int k = 0; k < 4; k++) put_win<20, 12>(pf, 24 + 8 * k, cb + W9_OFF + po + (k & 1) * 576 + (k >> 1) * 16);
        } else {
          prefix6(pf, cb + U_OFF, 4 * lane - 2);
          const uint32_t so = cb + S2_OFF + (lane >> 1) * 144 + (lane & 1) * 64;
#pragma unroll
          for (int k = 0; k < 4; k++) { put_win<11, 5>(pf, 16 + 8 * k, cb + W7_OFF + po + (k & 1) * 576 + (k >> 1) * 16); put_win<4, 3>(pf, 16 + 8 * k, so + k * 16); }
        }
      }
}

__global__ void __cluster_dims__(2, 1, 1) __launch_bounds__(640, 1)
ssm_kernel(const Params p, const __grid_constant__ CUtensorMap tm_in, const __grid_constant__ CUtensorMap tm_out) {
  extern __shared__ __align__(1024) unsigned char smem_raw[];
  const uint32_t sb = (uint32_t)__cvta_generic_to_shared(smem_raw);
  const int tid = threadIdx.x, lane = tid & 31;
  const int warp = __shfl_sync(0xffffffffu, tid >> 5, 0);
  const int ch = warp >> 2, wq = warp & 3, br = wq >> 1, hf = wq & 1;
  const int g = lane >> 2, t = lane & 3;
  const int d = blockIdx.x * 4 + ch;
  const uint32_t rank = blockIdx.x & 1;
  const uint32_t cb = sb + CH_OFF + ch * CH_BYTES;
  const int wtid = tid & 127;
  const int oc0 = (int)(blockIdx.x >> 1) * 8;
  STAMP(0); GT(0);

  if (warp >= 16) {
    if (wtid == 0) {
      mbar_init_expect(sb + B_RAW, 32768);
#pragma unroll
      for (int i = 0; i < 4; i++) mbar_init_expect(sb + B_X + 8 * i, 2048);
      asm volatile("mbarrier.init.shared::cta.b64 [%0], 128;" ::"r"(sb + B_U) : "memory");
      asm volatile("mbarrier.init.shared::cta.b64 [%0], 128;" ::"r"(sb + B_W) : "memory");
      asm volatile("fence.mbarrier_init.release.cluster;" ::: "memory");
      asm volatile("fence.proxy.async.shared::cta;" ::: "memory");
    }
    __syncwarp();
    asm volatile("barrier.cluster.arrive.relaxed.aligned;" ::: "memory");
    unsigned int epoch;
    asm volatile("ld.relaxed.gpu.global.u32 %0, [%1];" : "=r"(epoch) : "l"(&g_epoch) : "memory");
    const uint2 dA = *(const uint2*)(p.A_D + blockIdx.x * 4), dB = *(const uint2*)(p.B_D + blockIdx.x * 4);
    const uint4 gw0 = *(const uint4*)(p.gw + lane * 8), gw1 = *(const uint4*)(p.gw + 256 + lane * 8);
    asm volatile("barrier.cluster.wait.aligned;" ::: "memory");
    if (wtid == 0) {
      asm volatile("cp.async.bulk.tensor.5d.shared::cluster.global.mbarrier::complete_tx::bytes.multicast::cluster [%0], [%1, {%3, %4, %4, %4, %5}], [%2], %6;"
                   ::"r"(sb + RAW_OFF + rank * 16384), "l"(&tm_in), "r"(sb + B_RAW), "r"(oc0), "r"(0), "r"((int)rank * 32), "h"((unsigned short)3) : "memory");
    }
    sts128(sb + CH_OFF + wq * CH_BYTES + U_OFF + (lane >> 3) * U_CS + (64 + (lane & 7)) * 16, 0, 0, 0, 0);
    mbar_wait(sb + B_RAW);
    STAMP(4);
    {
      const uint32_t dst = sb + CH_OFF + (g & 3) * CH_BYTES + U_OFF + t * U_CS + (63 - wq * 16) * 16;
#pragma unroll 4
      for (int i = 0; i < 16; i++) {
        uint32_t r0, r1, r2, r3;
        ldsm4t(sb + RAW_OFF + (wq * 16 + i) * 512 + lane * 16, r0, r1, r2, r3);
        if ((uint32_t)(g >> 2) == rank) sts128(dst - i * 16, r0, r1, r2, r3);
      }
    }
    fence_async();
    asm volatile("mbarrier.arrive.shared::cta.b64 _, [%0];" ::"r"(sb + B_U) : "memory");
    bar_sync(5, 128);
    STAMP(5);
#pragma unroll 1
    for (int k = 0; k < 4; k++) window_sums(sb + CH_OFF + k * CH_BYTES, wq, lane);
    fence_async();
    asm volatile("mbarrier.arrive.shared::cta.b64 _, [%0];" ::"r"(sb + B_W) : "memory");
    STAMP(7);
    const uint32_t tag = (epoch + 1) & 0xffffu;
    {
      const int grow = blockIdx.x * 16 + wq * 4;
      uint4 gx[4][2];
#pragma unroll
      for (int i = 0; i < 4; i++) {
        gx[i][0] = *(const uint4*)(p.u + (size_t)(grow + i) * D + lane * 8);
        gx[i][1] = *(const uint4*)(p.u + (size_t)(grow + i) * D + 256 + lane * 8);
      }
      const uint32_t ws[8] = {gw0.x, gw0.y, gw0.z, gw0.w, gw1.x, gw1.y, gw1.z, gw1.w};
      float sm[4];
#pragma unroll
      for (int i = 0; i < 4; i++) {
        const uint32_t xs[8] = {gx[i][0].x, gx[i][0].y, gx[i][0].z, gx[i][0].w, gx[i][1].x, gx[i][1].y, gx[i][1].z, gx[i][1].w};
        float s = 0.f;
#pragma unroll
        for (int j = 0; j < 8; j++) { const uint32_t pr = hmul2(xs[j], ws[j]); s += bf_lo(pr); s += bf_hi(pr); }
        sm[i] = s;
      }
      {
        const bool b0 = lane & 1, b1 = lane & 2;
        float u0 = b0 ? sm[1] : sm[0], v0 = b0 ? sm[0] : sm[1], u1 = b0 ? sm[3] : sm[2], v1 = b0 ? sm[2] : sm[3];
        u0 += __shfl_xor_sync(0xffffffffu, v0, 1); u1 += __shfl_xor_sync(0xffffffffu, v1, 1);
        float s = b1 ? u1 : u0; const float v = b1 ? u0 : u1;
        s += __shfl_xor_sync(0xffffffffu, v, 2);
#pragma unroll
        for (int o = 4; o < 32; o <<= 1) s += __shfl_xor_sync(0xffffffffu, s, o);
        s = bf_round(s);
        const float gv = 1.f / (1.f + expf(-s));
        const uint32_t w = (tag << 16) | (pack_bf16(gv, 0.f) & 0xffffu);
        if (lane < 4) asm volatile("st.relaxed.gpu.global.u32 [%0], %1;" ::"l"(&g_gate[grow + lane]), "r"(w) : "memory");
      }
    }
    STAMP(8);
    unsigned int ticket = 0;
#pragma unroll 1
    for (int lvl = 0; lvl < 2; lvl++) {
      const int bs = 2 * lvl + (int)(rank ^ 1), bm = 2 * lvl + (int)rank;
      const uint32_t gs = get_gate(p, bs * 128 + wtid, tag), gm = get_gate(p, bm * 128 + wtid, tag);
      bar_sync(8 + lvl, 640);
      STAMP(10 + lvl);
      if (lvl == 0 && wtid == 0) ticket = atomicAdd(&g_ticket, 1u);
      final_box(sb, &tm_out, lvl, bs, wtid, rank, oc0, gs, dA, dB, 5);
      final_box(sb, &tm_out, lvl, bm, wtid, rank, oc0, gm, dA, dB, 5);
      STAMP(12 + lvl);
    }
    if (wtid == 0) {
      if (ticket == NCTA - 1) { g_ticket = 0; g_epoch = epoch + 1; }
      asm volatile("cp.async.bulk.wait_group.read 0;" ::: "memory");
    }
    STAMP(15);
    return;
  }
  asm volatile("barrier.cluster.arrive.relaxed.aligned;" ::: "memory");

  const int moff = d * NM + hf * 64 + lane * 2;
  const uint32_t q0 = *(const uint32_t*)((br ? p.B_lA : p.A_re) + moff), q1 = *(const uint32_t*)((br ? p.B_Aim : p.A_im) + moff);
  const uint32_t q2 = *(const uint32_t*)((br ? p.B_Cre : p.C_re) + moff), q3 = *(const uint32_t*)((br ? p.B_Cim : p.C_im) + moff);
  const uint32_t q4 = *(const uint32_t*)((br ? p.B_Cre : p.B_re) + moff), q5 = *(const uint32_t*)((br ? p.B_Cim : p.B_im) + moff);
  const uint2 ldt4 = *(const uint2*)((br ? p.B_ldt : p.A_ldt) + blockIdx.x * 4);
  unsigned int epoch;
  asm volatile("ld.relaxed.gpu.global.u32 %0, [%1];" : "=r"(epoch) : "l"(&g_epoch) : "memory");

  for (int i = wtid & 63; i < R_BR / 16; i += 64) sts128(cb + R_OFF + br * R_BR + i * 16, 0, 0, 0, 0);
  STAMP(1);

  float acc[5][4];
  float k2048 = 0.f;
  const uint32_t scr = cb + Y0_OFF + wq * SCR_BYTES;
  const uint32_t scr2 = sb + XIN_OFF + warp * 640;
  {
    const uint32_t ldt2 = (ch & 2) ? ldt4.y : ldt4.x;
    const float dt = bf_round(expf((ch & 1) ? bf_hi(ldt2) : bf_lo(ldt2)));
#pragma unroll
    for (int i = 0; i < 5; i++) acc[i][0] = acc[i][1] = acc[i][2] = acc[i][3] = 0.f;
    cf cc[2], zz1[2], zz128[2];
#pragma unroll
    for (int r = 0; r < 2; r++) {
      float v0 = r ? bf_hi(q0) : bf_lo(q0), v1 = r ? bf_hi(q1) : bf_lo(q1), v2 = r ? bf_hi(q2) : bf_lo(q2);
      float v3 = r ? bf_hi(q3) : bf_lo(q3), v4 = r ? bf_hi(q4) : bf_lo(q4), v5 = r ? bf_hi(q5) : bf_lo(q5);
      if (br == 0) { cc[r] = cmul(cf{v2, v3}, cf{dt * v4, dt * v5}); }
      else { v0 = -bf_round(expf(v0)); cc[r] = cf{2.f * dt * v2, 2.f * dt * v3}; }
      const float xl = (dt * v0) * 1.4426950408889634f, y = dt * v1;
      zz1[r] = cexp_p(xl, y, 1.f); zz128[r] = cexp_p(xl, y, 128.f);
    }
    STAMP(2);
    const uint32_t tb = scr + lane * 16;
    const uint32_t ta = scr + (lane >> 3) * 512 + (lane & 7) * 16;
    const uint32_t tc = ((lane & 8) ? scr2 : scr + 4096) + (lane >> 4) * 128 + (lane & 7) * 16;
    const uint32_t tm = scr2 + 512 + ((lane >> 3) & 1) * 64 + (lane >> 4) * 16;
#pragma unroll 1
    for (int r = 0; r < 2; r++) {
      const cf c = r ? cc[1] : cc[0], z1 = r ? zz1[1] : zz1[0], z128 = r ? zz128[1] : zz128[0];
      const cf z2 = csq(z1), z4 = csq(z2), z8 = csq(z4);
      const cf z16 = csq(z8), z24 = cmul(z16, z8), z32 = csq(z16), z40 = cmul(z32, z8), z48 = csq(z24), z56 = cmul(z32, z24), z64 = csq(z32);
      const cf z256 = csq(z128), z512 = csq(z256), z1024 = csq(z512), z2048 = csq(z1024);
      k2048 += fmaf(c.re, z2048.re, -c.im * z2048.im);
      __syncwarp();
      {
        uint32_t xr[4] = {pack_bf16(1.f, z8.re), pack_bf16(z16.re, z24.re), pack_bf16(z32.re, z40.re), pack_bf16(z48.re, z56.re)};
        uint32_t xi[4] = {pack_bf16(0.f, -z8.im), pack_bf16(-z16.im, -z24.im), pack_bf16(-z32.im, -z40.im), pack_bf16(-z48.im, -z56.im)};
        sts128(tb + 0 * 512, xr[0], xr[1], xr[2], xr[3]);
        sts128(tb + 2 * 512, xi[0], xi[1], xi[2], xi[3]);
        const uint32_t yr = pack_bf16(z64.re, z64.re), nyi = pack_bf16(z64.im, z64.im), yi = nyi ^ 0x80008000u;
        uint32_t o[4], q[4];
#pragma unroll
        for (int i = 0; i < 4; i++) CMUL2(o[i], q[i], xr[i], xi[i], yr, yi, nyi);
        sts128(tb + 1 * 512, o[0], o[1], o[2], o[3]);
        sts128(tb + 3 * 512, q[0], q[1], q[2], q[3]);
      }
      {
        const cf h1 = cmul(c, z128), h2 = cmul(c, z256), h3 = cmul(h1, z256), h4 = cmul(c, z512), h5 = cmul(h1, z512), h6 = cmul(h2, z512), h7 = cmul(h3, z512);
        const cf e1 = cmul(c, z1), e2 = cmul(c, z2), e3 = cmul(e1, z2), e129 = cmul(h1, z1), e130 = cmul(h1, z2), e131 = cmul(e129, z2);
        const cf e258 = cmul(h2, z2), e386 = cmul(h3, z2);
        const uint32_t pr0 = pack_bf16(c.re, e1.re), pr2 = pack_bf16(h1.re, e129.re), pi0 = pack_bf16(c.im, e1.im), pi2 = pack_bf16(h1.im, e129.im);
        sts128(tb + 4 * 512, pr0, pack_bf16(e2.re, e3.re), pr2, pack_bf16(e130.re, e131.re));
        sts128(tb + 5 * 512, pi0, pack_bf16(e2.im, e3.im), pi2, pack_bf16(e130.im, e131.im));
        uint32_t xr[4] = {pack_bf16(h2.re, e258.re), pack_bf16(h3.re, e386.re), pack_bf16(h4.re, h5.re), pack_bf16(h6.re, h7.re)};
        uint32_t xi[4] = {pack_bf16(h2.im, e258.im), pack_bf16(h3.im, e386.im), pack_bf16(h4.im, h5.im), pack_bf16(h6.im, h7.im)};
        sts128(tb + 6 * 512, xr[0], xr[1], xr[2], xr[3]);
        sts128(tb + 7 * 512, xi[0], xi[1], xi[2], xi[3]);
        xr[1] = __byte_perm(xr[0], xr[1], 0x5410); xi[1] = __byte_perm(xi[0], xi[1], 0x5410);
        xr[0] = __byte_perm(pr0, pr2, 0x5410); xi[0] = __byte_perm(pi0, pi2, 0x5410);
        const uint32_t yr = pack_bf16(z1024.re, z1024.re), yi = pack_bf16(z1024.im, z1024.im), nyi = yi ^ 0x80008000u;
        uint32_t o[4], q[4];
#pragma unroll
        for (int i = 0; i < 4; i++) CMUL2(o[i], q[i], xr[i], xi[i], yr, yi, nyi);
        sts128(tb + 8 * 512, o[0], o[1], o[2], o[3]);
        sts128(scr2 + lane * 16, q[0], q[1], q[2], q[3]);
        const uint32_t m4 = pack_bf16(z4.re, z4.im);
        sts16(scr2 + 512 + lane * 2, m4); sts16(scr2 + 576 + lane * 2, m4 >> 16);
      }
      __syncwarp();
#pragma unroll
      for (int kp = 0; kp < 2; kp++) {
        uint32_t rr[2], ri[2], yr[2], yi[2];
        ldsm4t(tc + kp * 256, rr[0], ri[0], rr[1], ri[1]);
        ldsm4(tm + kp * 32, yr[0], yi[0], yr[1], yi[1]);
#pragma unroll
        for (int k2 = 0; k2 < 2; k2++) {
          const int kk = kp * 2 + k2;
          uint32_t a0, a1, a2, a3, pr, pi, qr, qi, xr, xi;
          ldsm4t(ta + kk * 128, a0, a1, a2, a3);
          ldsm4t(ta + 2048 + kk * 128, pr, pi, qr, qi);
          const uint32_t nyi = yi[k2] ^ 0x80008000u;
          mma16816(acc[0], a0, a1, a2, a3, pr, pi);
          mma16816(acc[2], a0, a1, a2, a3, qr, qi);
          mma16816(acc[4], a0, a1, a2, a3, rr[k2], ri[k2]);
          CMUL2(xr, xi, pr, pi, yr[k2], yi[k2], nyi);
          mma16816(acc[1], a0, a1, a2, a3, xr, xi);
          CMUL2(xr, xi, qr, qi, yr[k2], yi[k2], nyi);
          mma16816(acc[3], a0, a1, a2, a3, xr, xi);
        }
      }
    }
#pragma unroll
    for (int o = 16; o; o >>= 1) k2048 += __shfl_xor_sync(0xffffffffu, k2048, o);
  }
  STAMP(3);
  __syncwarp();
  {
    const uint32_t xs = scr + lane * 16;
#define OTH(i, k) __float_as_uint(hf ? acc[i][k] : acc[i][2 + (k)])
    sts128(xs, OTH(0, 0), OTH(0, 1), OTH(1, 0), OTH(1, 1));
    sts128(xs + 512, OTH(2, 0), OTH(2, 1), OTH(3, 0), OTH(3, 1));
    sts128(xs + 1024, OTH(4, 0), OTH(4, 1), __float_as_uint(k2048), 0);
#undef OTH
  }

  bar_sync(1 + ch, 128);
  STAMP(4);
  {
    const uint32_t xo = cb + Y0_OFF + (wq ^ 1) * SCR_BYTES + lane * 16;
    const uint4 o0 = lds128(xo), o1 = lds128(xo + 512), o2 = lds128(xo + 1024);
    const uint32_t rb = cb + R_OFF + br * R_BR;
#define OWN(i, k) (hf ? acc[i][2 + (k)] : acc[i][k])
    const uint32_t vP = pack_bf16(OWN(0, 1) + __uint_as_float(o0.y), OWN(0, 0) + __uint_as_float(o0.x));
    const uint32_t vP4 = pack_bf16(OWN(1, 1) + __uint_as_float(o0.w), OWN(1, 0) + __uint_as_float(o0.z));
    const uint32_t vQ = pack_bf16(OWN(2, 1) + __uint_as_float(o1.y), OWN(2, 0) + __uint_as_float(o1.x));
    const uint32_t vQ4 = pack_bf16(OWN(3, 1) + __uint_as_float(o1.w), OWN(3, 0) + __uint_as_float(o1.z));
    const uint32_t vR = pack_bf16(OWN(4, 1) + __uint_as_float(o2.y), OWN(4, 0) + __uint_as_float(o2.x));
#undef OWN
    const int j = g + 8 * hf;
    {
      const int a = 2 * (t & 1) + 64 * (t & 2) + 8 * j;
      const uint32_t ad = rb + 2 * (RD_X0 - 1 - a);
      const uint32_t a1 = (t & 2) ? ad - 8 : ad, a2 = (t & 2) ? ad : ad - 8;
      const uint32_t w1 = (t & 2) ? vP4 : vP, w2 = (t & 2) ? vP : vP4;
      sts32(a1, w1); sts32(a2, w2);
      sts16(a1 + RD_CS + 2, w1); sts16(a1 + RD_CS + 4, w1 >> 16);
      sts16(a2 + RD_CS + 2, w2); sts16(a2 + RD_CS + 4, w2 >> 16);
    }
    if (t < 2) {
      const int b = 256 + 128 * t + 8 * j;
      const uint32_t ad = rb + 2 * (RD_X0 - 6 - b);
      const uint32_t v22 = __byte_perm(vQ4, 0, 0x3232), v00 = __byte_perm(vQ, 0, 0x3232);
      sts16(ad, vQ4);
      sts64(ad + 2, v22, __byte_perm(vQ4, vQ, 0x5432));
      sts32(ad + 10, v00);
      if (b != 256) { sts16(ad + 14, v00); sts128(ad + RD_CS + 2, vQ4, v22, vQ, v00); }
      else { sts64(ad + RD_CS + 2, vQ4, v22); sts32(ad + RD_CS + 10, vQ); sts16(ad + RD_CS + 14, v00); }
    } else {
      const uint32_t ao = rb + R_O2 + 2 * (159 - (32 * t + j)), ae = ao - (R_O2 - R_E2) + 2;
      sts16(ao, vQ4 >> 16); sts16(ao + RS_CS + 2, vQ4 >> 16); sts16(ao - 32, vQ4); sts16(ao - 32 + RS_CS + 2, vQ4);
      sts16(ae - 32, vQ); sts16(ae - 32 + RS_CS + 2, vQ);
      if (lane != 2 || hf) { sts16(ae, vQ >> 16); sts16(ae + RS_CS + 2, vQ >> 16); }
      else {
        const uint32_t vv = __byte_perm(vQ, 0, 0x3232), ad = rb + 2 * (RD_X0 - 514);
        sts16(ad, vv); sts32(ad + 2, vv); sts16(ad + 6, vv); sts64(ad + RD_CS + 2, vv, vv);
      }
    }
    {
      const uint32_t a = rb + ((g & 1) ? R_O3 : R_E3 + 2) + 2 * (159 - (64 + 16 * t + (j >> 1)));
      const bool p1024 = (lane == 0) && (hf == 0);
      const uint32_t a00 = p1024 ? rb + R_E2 + 2 * (159 - 127) : a;
      sts16(a00, vR >> 16); sts16(a00 + RS_CS + 2, vR >> 16);
      sts16(a - 16, vR); sts16(a - 16 + RS_CS + 2, vR);
      if (p1024) {
        sts32(sb + K1024_OFF + (ch * 2 + br) * 4, vR & 0xffff0000u);
        const uint32_t kv = pack_bf16(k2048 + __uint_as_float(o2.z), 0.f);
        sts16(rb + R_E3 + 2 * (159 - 127), kv); sts16(rb + R_E3 + 2 * (159 - 127) + RS_CS + 2, kv);
      }
    }
  }
  STAMP(5);
  const uint32_t tag = (epoch + 1) & 0xffffu;
  asm volatile("barrier.cluster.wait.aligned;" ::: "memory");
  bar_sync(1 + ch, 128);
  mbar_wait(sb + B_U);
  STAMP(6);

  const uint32_t rb = cb + R_OFF + br * R_BR;
  const int eo = 16 * hf + g - 2 * t;
  float dacc[32];
  {
      {
        const int x0 = RD_X0 - (eo + 536);
        const uint32_t fa = rb + ((g & 1) ? 2 * x0 : RD_CS + 2 * x0 + 2);
        const uint64_t ub = mkdesc(cb + U_OFF, U_CS, 128);
        uint32_t f[2][9];
#pragma unroll
        for (int i = 0; i < 9; i++) f[0][i] = lds32(fa + (62 + i) * 16);
#pragma unroll
        for (int j = 0; j < 9; j++) {
          wg_fence();
#pragma unroll
          for (int k = 0; k < 4; k++) {
            const int s = 34 - 4 * j - k;
            if (s >= 0) {
              const int o = 2 * s - 66 + 128;
              const int cc = o & 3, rs = (o >> 2) - 32;
              const int n0 = ((-rs) >> 3) * 8;
              const uint64_t desc = ub + (uint64_t)((cc * U_CS - rs * 16) >> 4);
              const int fi = 2 * (3 - k);
              const uint32_t a1 = f[j & 1][fi], a0 = f[j & 1][fi + 1], a2 = f[j & 1][fi + 2];
              if (n0 == 0) wgmma_rs<64, 0>(dacc, a0, a1, a2, a0, desc, s != 34);
              else if (n0 == 8) wgmma_rs<56, 0>(dacc, a0, a1, a2, a0, desc, 1);
              else wgmma_rs<48, 0>(dacc, a0, a1, a2, a0, desc, 1);
            }
          }
          wg_commit();
          if (j < 8) {
#pragma unroll
            for (int i = 0; i < 9; i++) {
              const int idx = 62 - 8 * (j + 1) + i;
              if (idx >= 0) f[(j + 1) & 1][i] = lds32(fa + idx * 16);
            }
          }
          wg_wait0();
        }
      }
      const uint32_t yb = cb + Y0_OFF + br * 4096;
#pragma unroll
      for (int i = 0; i < 8; i += 2) {
        const int mi = lane >> 3;
        const int cidx = 4 * (63 - 8 * (i + (mi >> 1)) - (lane & 7)) + 2 * hf + (mi & 1);
        stsm4t(yb + ysw(cidx), pack_bf16(dacc[4 * i], dacc[4 * i + 1]), pack_bf16(dacc[4 * i + 2], dacc[4 * i + 3]),
               pack_bf16(dacc[4 * i + 4], dacc[4 * i + 5]), pack_bf16(dacc[4 * i + 6], dacc[4 * i + 7]));
      }
      bar_arrive(8, 640);
      STAMP(8);
  }
  const uint2 dA = *(const uint2*)(p.A_D + blockIdx.x * 4), dB = *(const uint2*)(p.B_D + blockIdx.x * 4);
  mbar_wait(sb + B_W);
  const int x1 = 159 - (eo + 136);
  const uint32_t fs = rb + ((g & 1) ? 2 * x1 : RS_CS + 2 * x1 + 2);
  {
    uint32_t f[2][10];
    const uint64_t d5 = mkdesc(cb + W5_OFF, 144, 576), d3 = mkdesc(cb + W3_OFF, 144, 576);
#pragma unroll
    for (int i = 0; i < 5; i++) { f[0][i] = lds32(fs + R_E2 + (8 + i) * 16); f[0][5 + i] = lds32(fs + R_O2 + (8 + i) * 16); }
#pragma unroll
    for (int m = 2; m <= 4; m++) {
      wg_fence();
#pragma unroll
      for (int k = 0; k < 4; k++) {
        const uint32_t* a = &f[m & 1][(k >> 1) * 5 + (k & 1) * 2];
        const uint64_t desc = ((k >> 1) ? d3 : d5) + (k & 1) * 18 + (m - 2) * 36;
        if (m == 2) wgmma_rs<48, 1>(dacc, a[1], a[0], a[2], a[1], desc, k);
        else if (m == 3) wgmma_rs<40, 1>(dacc, a[1], a[0], a[2], a[1], desc, 1);
        else wgmma_rs<32, 1>(dacc, a[1], a[0], a[2], a[1], desc, 1);
      }
      wg_commit();
#pragma unroll
      for (int i = 0; i < 5; i++) {
        if (m < 4) { f[(m + 1) & 1][i] = lds32(fs + R_E2 + (4 * (3 - m) + i) * 16); f[(m + 1) & 1][5 + i] = lds32(fs + R_O2 + (4 * (3 - m) + i) * 16); }
        else { f[1][i] = lds32(fs + R_E3 + (8 + i) * 16); f[1][5 + i] = lds32(fs + R_O3 + (8 + i) * 16); }
      }
      wg_wait0();
    }
    {
      const uint32_t yb = cb + Y2_OFF + br * 3072;
#pragma unroll
      for (int i = 0; i < 6; i += 2) {
        const int mi = lane >> 3;
        const int cidx = 32 * (5 - i - (mi >> 1)) + 16 * hf + 8 * (mi & 1) + (lane & 7);
        stsm4(yb + ysw(cidx), pack_bf16(dacc[4 * i], dacc[4 * i + 1]), pack_bf16(dacc[4 * i + 2], dacc[4 * i + 3]),
              pack_bf16(dacc[4 * i + 4], dacc[4 * i + 5]), pack_bf16(dacc[4 * i + 6], dacc[4 * i + 7]));
      }
    }
    bar_arrive(9, 640);
    STAMP(9);
    const uint64_t d9 = mkdesc(cb + W9_OFF, 144, 576), d7 = mkdesc(cb + W7_OFF, 144, 576);
#pragma unroll
    for (int m = 2; m <= 3; m++) {
      wg_fence();
#pragma unroll
      for (int k = 0; k < 4; k++) {
        const uint32_t* a = &f[(m + 1) & 1][(k >> 1) * 5 + (k & 1) * 2];
        const uint64_t desc = ((k >> 1) ? d7 : d9) + (k & 1) * 18 + (m - 2) * 72;
        if (m == 2) wgmma_rs<32, 1>(dacc, a[1], a[0], a[2], a[1], desc, k);
        else wgmma_rs<16, 1>(dacc, a[1], a[0], a[2], a[1], desc, 1);
      }
      wg_commit();
      if (m == 2) {
#pragma unroll
        for (int i = 0; i < 5; i++) { f[0][i] = lds32(fs + R_E3 + (4 + i) * 16); f[0][5 + i] = lds32(fs + R_O3 + (4 + i) * 16); }
      }
      wg_wait0();
    }
    const uint32_t yb = cb + Y3_OFF + br * 2048;
#pragma unroll
    for (int i = 0; i < 4; i += 2) {
      const int mi = lane >> 3;
      const int cidx = 64 * (1 - (i >> 1)) + 2 * (16 * hf + 8 * (mi & 1) + (lane & 7)) + (mi >> 1);
      stsm4(yb + ysw(cidx), pack_bf16(dacc[4 * i], dacc[4 * i + 1]), pack_bf16(dacc[4 * i + 2], dacc[4 * i + 3]),
            pack_bf16(dacc[4 * i + 4], dacc[4 * i + 5]), pack_bf16(dacc[4 * i + 6], dacc[4 * i + 7]));
    }
  }
  STAMP(10);
  const uint32_t g2 = get_gate(p, (4 + ch) * 128 + wtid, tag);

  bar_sync(10, 512);
  STAMP(11);
  final_box(sb, &tm_out, 2, 4 + ch, wtid, rank, oc0, g2, dA, dB, 1 + ch);
  STAMP(14);
  if (wtid == 0) asm volatile("cp.async.bulk.wait_group.read 0;" ::: "memory");
  STAMP(15); GT(1);
}

typedef CUresult (*EncodeFn)(CUtensorMap*, CUtensorMapDataType, cuuint32_t, void*, const cuuint64_t*, const cuuint64_t*,
                             const cuuint32_t*, const cuuint32_t*, CUtensorMapInterleave, CUtensorMapSwizzle,
                             CUtensorMapL2promotion, CUtensorMapFloatOOBfill);

}

extern "C" void kernel_launch(void* const* d_in, const int* in_sizes, int n_in, void* d_out, int out_size) {
  (void)in_sizes; (void)n_in; (void)out_size;
  typedef const __nv_bfloat16* bp;
  Params p;
  p.u = (bp)d_in[0]; p.A_re = (bp)d_in[1]; p.A_im = (bp)d_in[2]; p.B_re = (bp)d_in[3]; p.B_im = (bp)d_in[4];
  p.C_re = (bp)d_in[5]; p.C_im = (bp)d_in[6]; p.A_ldt = (bp)d_in[7]; p.A_D = (bp)d_in[8];
  p.B_lA = (bp)d_in[10]; p.B_Aim = (bp)d_in[11]; p.B_Cre = (bp)d_in[12]; p.B_Cim = (bp)d_in[13];
  p.B_ldt = (bp)d_in[14]; p.B_D = (bp)d_in[15]; p.gw = (bp)d_in[16];
  static EncodeFn enc = nullptr;
  if (!enc) {
    cudaDriverEntryPointQueryResult qr;
    cudaGetDriverEntryPoint("cuTensorMapEncodeTiled", (void**)&enc, cudaEnableDefault, &qr);
    cudaFuncSetAttribute(ssm_kernel, cudaFuncAttributeMaxDynamicSharedMemorySize, SMEM_BYTES);
  }
  CUtensorMap tm_in, tm_out;
  {
    cuuint64_t gd[5] = {512, 2, 4, 4, 64};
    cuuint64_t gs[4] = {1024, 8192, 2048, 32768};
    cuuint32_t bx[5] = {8, 2, 4, 4, 32};
    cuuint32_t es[5] = {1, 1, 1, 1, 1};
    enc(&tm_in, CU_TENSOR_MAP_DATA_TYPE_BFLOAT16, 5, d_in[0], gd, gs, bx, es, CU_TENSOR_MAP_INTERLEAVE_NONE,
        CU_TENSOR_MAP_SWIZZLE_NONE, CU_TENSOR_MAP_L2_PROMOTION_NONE, CU_TENSOR_MAP_FLOAT_OOB_FILL_NONE);
  }
  {
    cuuint64_t gd[3] = {512, 1024, 2};
    cuuint64_t gs[2] = {2048, 1024};
    cuuint32_t bx[3] = {8, 128, 2};
    cuuint32_t es[3] = {1, 1, 1};
    enc(&tm_out, CU_TENSOR_MAP_DATA_TYPE_BFLOAT16, 3, d_out, gd, gs, bx, es, CU_TENSOR_MAP_INTERLEAVE_NONE,
        CU_TENSOR_MAP_SWIZZLE_NONE, CU_TENSOR_MAP_L2_PROMOTION_NONE, CU_TENSOR_MAP_FLOAT_OOB_FILL_NONE);
  }
  ssm_kernel<<<NCTA, 640, SMEM_BYTES, cudaStreamPerThread>>>(p, tm_in, tm_out);
}
```

```cpp
#include <cuda_runtime.h>
#include <cuda.h>
#include <cuda_bf16.h>
#include <stdint.h>

namespace {

constexpr int L = 2048, D = 512, NM = 128;
constexpr int NCTA = 128;

constexpr int RAW_OFF = 0;
constexpr int XIN_OFF = 32768;
constexpr int BAR_OFF = XIN_OFF + 10240;
constexpr int CH_OFF = BAR_OFF + 128;
constexpr int U_CS = 1184;
constexpr int U_OFF = 0;
constexpr int R_OFF = 4736;
constexpr int RD_X0 = 565;
constexpr int RD_CS = 1216;
constexpr int RS_CS = 320;
constexpr int R_E2 = 2 * RD_CS, R_O2 = R_E2 + 2 * RS_CS, R_E3 = R_O2 + 2 * RS_CS, R_O3 = R_E3 + 2 * RS_CS;
constexpr int R_BR = R_O3 + 2 * RS_CS;
constexpr int W5_OFF = R_OFF + 2 * R_BR;
constexpr int W3_OFF = W5_OFF + 3456;
constexpr int W9_OFF = W3_OFF + 3456;
constexpr int W7_OFF = W9_OFF + 2304;
constexpr int S2_OFF = W7_OFF + 2304;
constexpr int Y0_OFF = S2_OFF + 2304;
constexpr int Y2_OFF = Y0_OFF + 8192, Y3_OFF = Y2_OFF + 6144;
constexpr int CH_BYTES = Y0_OFF + 18432 + 16;
constexpr int SCR_BYTES = 4608;
constexpr int SMEM_BYTES = CH_OFF + 4 * CH_BYTES;
static_assert(CH_BYTES % 128 == 16, "bank staggering of the channel blocks");
static_assert(SMEM_BYTES <= 232448, "smem");
constexpr int B_RAW = BAR_OFF, B_X = BAR_OFF + 8, B_U = BAR_OFF + 40, B_W = BAR_OFF + 48;
constexpr int K1024_OFF = BAR_OFF + 64;

__device__ unsigned int g_gate[L];
__device__ unsigned int g_epoch;
__device__ unsigned int g_ticket;

#define STAMP(k)
#define GT(k)

struct Params {
  const __nv_bfloat16 *u, *A_re, *A_im, *B_re, *B_im, *C_re, *C_im, *A_ldt, *A_D;
  const __nv_bfloat16 *B_lA, *B_Aim, *B_Cre, *B_Cim, *B_ldt, *B_D, *gw;
};

template <int N, int TB> __device__ __forceinline__ void wgmma_rs(float* d, uint32_t a0, uint32_t a1, uint32_t a2, uint32_t a3, uint64_t desc, int sc);
template <> __device__ __forceinline__ void wgmma_rs<64, 0>(float* d, uint32_t a0, uint32_t a1, uint32_t a2, uint32_t a3, uint64_t desc, int sc) {
  asm volatile("{\n.reg .pred p;\nsetp.ne.b32 p, %37, 0;\n"
    "wgmma.mma_async.sync.aligned.m64n64k16.f32.bf16.bf16 {%0,%1,%2,%3,%4,%5,%6,%7,%8,%9,%10,%11,%12,%13,%14,%15,%16,%17,%18,%19,%20,%21,%22,%23,%24,%25,%26,%27,%28,%29,%30,%31}, {%32,%33,%34,%35}, %36, p, 1, 1, 0;\n}"
    : "+f"(d[0]), "+f"(d[1]), "+f"(d[2]), "+f"(d[3]), "+f"(d[4]), "+f"(d[5]), "+f"(d[6]), "+f"(d[7]), "+f"(d[8]), "+f"(d[9]), "+f"(d[10]), "+f"(d[11]), "+f"(d[12]), "+f"(d[13]), "+f"(d[14]), "+f"(d[15]), "+f"(d[16]), "+f"(d[17]), "+f"(d[18]), "+f"(d[19]), "+f"(d[20]), "+f"(d[21]), "+f"(d[22]), "+f"(d[23]), "+f"(d[24]), "+f"(d[25]), "+f"(d[26]), "+f"(d[27]), "+f"(d[28]), "+f"(d[29]), "+f"(d[30]), "+f"(d[31]) : "r"(a0), "r"(a1), "r"(a2), "r"(a3), "l"(desc), "r"(sc));
}
template <> __device__ __forceinline__ void wgmma_rs<56, 0>(float* d, uint32_t a0, uint32_t a1, uint32_t a2, uint32_t a3, uint64_t desc, int sc) {
  asm volatile("{\n.reg .pred p;\nsetp.ne.b32 p, %33, 0;\n"
    "wgmma.mma_async.sync.aligned.m64n56k16.f32.bf16.bf16 {%0,%1,%2,%3,%4,%5,%6,%7,%8,%9,%10,%11,%12,%13,%14,%15,%16,%17,%18,%19,%20,%21,%22,%23,%24,%25,%26,%27}, {%28,%29,%30,%31}, %32, p, 1, 1, 0;\n}"
    : "+f"(d[0]), "+f"(d[1]), "+f"(d[2]), "+f"(d[3]), "+f"(d[4]), "+f"(d[5]), "+f"(d[6]), "+f"(d[7]), "+f"(d[8]), "+f"(d[9]), "+f"(d[10]), "+f"(d[11]), "+f"(d[12]), "+f"(d[13]), "+f"(d[14]), "+f"(d[15]), "+f"(d[16]), "+f"(d[17]), "+f"(d[18]), "+f"(d[19]), "+f"(d[20]), "+f"(d[21]), "+f"(d[22]), "+f"(d[23]), "+f"(d[24]), "+f"(d[25]), "+f"(d[26]), "+f"(d[27]) : "r"(a0), "r"(a1), "r"(a2), "r"(a3), "l"(desc), "r"(sc));
}
template <> __device__ __forceinline__ void wgmma_rs<48, 0>(float* d, uint32_t a0, uint32_t a1, uint32_t a2, uint32_t a3, uint64_t desc, int sc) {
  asm volatile("{\n.reg .pred p;\nsetp.ne.b32 p, %29, 0;\n"
    "wgmma.mma_async.sync.aligned.m64n48k16.f32.bf16.bf16 {%0,%1,%2,%3,%4,%5,%6,%7,%8,%9,%10,%11,%12,%13,%14,%15,%16,%17,%18,%19,%20,%21,%22,%23}, {%24,%25,%26,%27}, %28, p, 1, 1, 0;\n}"
    : "+f"(d[0]), "+f"(d[1]), "+f"(d[2]), "+f"(d[3]), "+f"(d[4]), "+f"(d[5]), "+f"(d[6]), "+f"(d[7]), "+f"(d[8]), "+f"(d[9]), "+f"(d[10]), "+f"(d[11]), "+f"(d[12]), "+f"(d[13]), "+f"(d[14]), "+f"(d[15]), "+f"(d[16]), "+f"(d[17]), "+f"(d[18]), "+f"(d[19]), "+f"(d[20]), "+f"(d[21]), "+f"(d[22]), "+f"(d[23]) : "r"(a0), "r"(a1), "r"(a2), "r"(a3), "l"(desc), "r"(sc));
}
template <> __device__ __forceinline__ void wgmma_rs<48, 1>(float* d, uint32_t a0, uint32_t a1, uint32_t a2, uint32_t a3, uint64_t desc, int sc) {
  asm volatile("{\n.reg .pred p;\nsetp.ne.b32 p, %29, 0;\n"
    "wgmma.mma_async.sync.aligned.m64n48k16.f32.bf16.bf16 {%0,%1,%2,%3,%4,%5,%6,%7,%8,%9,%10,%11,%12,%13,%14,%15,%16,%17,%18,%19,%20,%21,%22,%23}, {%24,%25,%26,%27}, %28, p, 1, 1, 1;\n}"
    : "+f"(d[0]), "+f"(d[1]), "+f"(d[2]), "+f"(d[3]), "+f"(d[4]), "+f"(d[5]), "+f"(d[6]), "+f"(d[7]), "+f"(d[8]), "+f"(d[9]), "+f"(d[10]), "+f"(d[11]), "+f"(d[12]), "+f"(d[13]), "+f"(d[14]), "+f"(d[15]), "+f"(d[16]), "+f"(d[17]), "+f"(d[18]), "+f"(d[19]), "+f"(d[20]), "+f"(d[21]), "+f"(d[22]), "+f"(d[23]) : "r"(a0), "r"(a1), "r"(a2), "r"(a3), "l"(desc), "r"(sc));
}
template <> __device__ __forceinline__ void wgmma_rs<40, 1>(float* d, uint32_t a0, uint32_t a1, uint32_t a2, uint32_t a3, uint64_t desc, int sc) {
  asm volatile("{\n.reg .pred p;\nsetp.ne.b32 p, %25, 0;\n"
    "wgmma.mma_async.sync.aligned.m64n40k16.f32.bf16.bf16 {%0,%1,%2,%3,%4,%5,%6,%7,%8,%9,%10,%11,%12,%13,%14,%15,%16,%17,%18,%19}, {%20,%21,%22,%23}, %24, p, 1, 1, 1;\n}"
    : "+f"(d[0]), "+f"(d[1]), "+f"(d[2]), "+f"(d[3]), "+f"(d[4]), "+f"(d[5]), "+f"(d[6]), "+f"(d[7]), "+f"(d[8]), "+f"(d[9]), "+f"(d[10]), "+f"(d[11]), "+f"(d[12]), "+f"(d[13]), "+f"(d[14]), "+f"(d[15]), "+f"(d[16]), "+f"(d[17]), "+f"(d[18]), "+f"(d[19]) : "r"(a0), "r"(a1), "r"(a2), "r"(a3), "l"(desc), "r"(sc));
}
template <> __device__ __forceinline__ void wgmma_rs<32, 1>(float* d, uint32_t a0, uint32_t a1, uint32_t a2, uint32_t a3, uint64_t desc, int sc) {
  asm volatile("{\n.reg .pred p;\nsetp.ne.b32 p, %21, 0;\n"
    "wgmma.mma_async.sync.aligned.m64n32k16.f32.bf16.bf16 {%0,%1,%2,%3,%4,%5,%6,%7,%8,%9,%10,%11,%12,%13,%14,%15}, {%16,%17,%18,%19}, %20, p, 1, 1, 1;\n}"
    : "+f"(d[0]), "+f"(d[1]), "+f"(d[2]), "+f"(d[3]), "+f"(d[4]), "+f"(d[5]), "+f"(d[6]), "+f"(d[7]), "+f"(d[8]), "+f"(d[9]), "+f"(d[10]), "+f"(d[11]), "+f"(d[12]), "+f"(d[13]), "+f"(d[14]), "+f"(d[15]) : "r"(a0), "r"(a1), "r"(a2), "r"(a3), "l"(desc), "r"(sc));
}
template <> __device__ __forceinline__ void wgmma_rs<16, 1>(float* d, uint32_t a0, uint32_t a1, uint32_t a2, uint32_t a3, uint64_t desc, int sc) {
  asm volatile("{\n.reg .pred p;\nsetp.ne.b32 p, %13, 0;\n"
    "wgmma.mma_async.sync.aligned.m64n16k16.f32.bf16.bf16 {%0,%1,%2,%3,%4,%5,%6,%7}, {%8,%9,%10,%11}, %12, p, 1, 1, 1;\n}"
    : "+f"(d[0]), "+f"(d[1]), "+f"(d[2]), "+f"(d[3]), "+f"(d[4]), "+f"(d[5]), "+f"(d[6]), "+f"(d[7]) : "r"(a0), "r"(a1), "r"(a2), "r"(a3), "l"(desc), "r"(sc));
}

__device__ __forceinline__ uint32_t pack_bf16(float lo, float hi) {
  uint32_t r; asm("cvt.rn.bf16x2.f32 %0, %1, %2;" : "=r"(r) : "f"(hi), "f"(lo)); return r;
}
__device__ __forceinline__ float bf_lo(uint32_t v) { return __uint_as_float(v << 16); }
__device__ __forceinline__ float bf_hi(uint32_t v) { return __uint_as_float(v & 0xffff0000u); }
__device__ __forceinline__ float bf_round(float x) { return bf_lo(pack_bf16(x, 0.f)); }
__device__ __forceinline__ uint32_t hmul2(uint32_t a, uint32_t b) { uint32_t r; asm("mul.rn.bf16x2 %0, %1, %2;" : "=r"(r) : "r"(a), "r"(b)); return r; }
__device__ __forceinline__ uint32_t hadd2(uint32_t a, uint32_t b) { uint32_t r; asm("add.rn.bf16x2 %0, %1, %2;" : "=r"(r) : "r"(a), "r"(b)); return r; }
__device__ __forceinline__ uint32_t hsub2(uint32_t a, uint32_t b) { uint32_t r; asm("sub.rn.bf16x2 %0, %1, %2;" : "=r"(r) : "r"(a), "r"(b)); return r; }
__device__ __forceinline__ uint32_t hfma2(uint32_t a, uint32_t b, uint32_t c) { uint32_t r; asm("fma.rn.bf16x2 %0, %1, %2, %3;" : "=r"(r) : "r"(a), "r"(b), "r"(c)); return r; }

__device__ __forceinline__ void sts16(uint32_t a, uint32_t v) { asm volatile("st.shared.b16 [%0], %1;" ::"r"(a), "h"((unsigned short)v) : "memory"); }
__device__ __forceinline__ void sts32(uint32_t a, uint32_t v) { asm volatile("st.shared.b32 [%0], %1;" ::"r"(a), "r"(v) : "memory"); }
__device__ __forceinline__ void sts64(uint32_t a, uint32_t x, uint32_t y) { asm volatile("st.shared.v2.b32 [%0], {%1,%2};" ::"r"(a), "r"(x), "r"(y) : "memory"); }
__device__ __forceinline__ void sts128(uint32_t a, uint32_t x, uint32_t y, uint32_t z, uint32_t w) {
  asm volatile("st.shared.v4.b32 [%0], {%1,%2,%3,%4};" ::"r"(a), "r"(x), "r"(y), "r"(z), "r"(w) : "memory");
}
__device__ __forceinline__ uint32_t lds32(uint32_t a) { uint32_t v; asm volatile("ld.shared.b32 %0, [%1];" : "=r"(v) : "r"(a) : "memory"); return v; }
__device__ __forceinline__ uint2 lds64(uint32_t a) { uint2 v; asm volatile("ld.shared.v2.b32 {%0,%1}, [%2];" : "=r"(v.x), "=r"(v.y) : "r"(a) : "memory"); return v; }
__device__ __forceinline__ uint4 lds128(uint32_t a) {
  uint4 v; asm volatile("ld.shared.v4.b32 {%0,%1,%2,%3}, [%4];" : "=r"(v.x), "=r"(v.y), "=r"(v.z), "=r"(v.w) : "r"(a) : "memory"); return v;
}
__device__ __forceinline__ void ldsm4(uint32_t a, uint32_t& r0, uint32_t& r1, uint32_t& r2, uint32_t& r3) {
  asm volatile("ldmatrix.sync.aligned.m8n8.x4.shared.b16 {%0,%1,%2,%3}, [%4];" : "=r"(r0), "=r"(r1), "=r"(r2), "=r"(r3) : "r"(a) : "memory");
}
__device__ __forceinline__ void ldsm4t(uint32_t a, uint32_t& r0, uint32_t& r1, uint32_t& r2, uint32_t& r3) {
  asm volatile("ldmatrix.sync.aligned.m8n8.x4.trans.shared.b16 {%0,%1,%2,%3}, [%4];" : "=r"(r0), "=r"(r1), "=r"(r2), "=r"(r3) : "r"(a) : "memory");
}
__device__ __forceinline__ void stsm4(uint32_t a, uint32_t r0, uint32_t r1, uint32_t r2, uint32_t r3) {
  asm volatile("stmatrix.sync.aligned.m8n8.x4.shared.b16 [%0], {%1,%2,%3,%4};" ::"r"(a), "r"(r0), "r"(r1), "r"(r2), "r"(r3) : "memory");
}
__device__ __forceinline__ void stsm4t(uint32_t a, uint32_t r0, uint32_t r1, uint32_t r2, uint32_t r3) {
  asm volatile("stmatrix.sync.aligned.m8n8.x4.trans.shared.b16 [%0], {%1,%2,%3,%4};" ::"r"(a), "r"(r0), "r"(r1), "r"(r2), "r"(r3) : "memory");
}
__device__ __forceinline__ void mma16816(float* c, uint32_t a0, uint32_t a1, uint32_t a2, uint32_t a3, uint32_t b0, uint32_t b1) {
  asm("mma.sync.aligned.m16n8k16.row.col.f32.bf16.bf16.f32 {%0,%1,%2,%3}, {%4,%5,%6,%7}, {%8,%9}, {%0,%1,%2,%3};"
      : "+f"(c[0]), "+f"(c[1]), "+f"(c[2]), "+f"(c[3]) : "r"(a0), "r"(a1), "r"(a2), "r"(a3), "r"(b0), "r"(b1));
}
__device__ __forceinline__ void bar_sync(int id, int n) { asm volatile("bar.sync %0, %1;" ::"r"(id), "r"(n) : "memory"); }
__device__ __forceinline__ void bar_arrive(int id, int n) { asm volatile("bar.arrive %0, %1;" ::"r"(id), "r"(n) : "memory"); }
__device__ __forceinline__ void wg_fence() { asm volatile("wgmma.fence.sync.aligned;" ::: "memory"); }
__device__ __forceinline__ void wg_commit() { asm volatile("wgmma.commit_group.sync.aligned;" ::: "memory"); }
__device__ __forceinline__ void wg_wait0() { asm volatile("wgmma.wait_group.sync.aligned 0;" ::: "memory"); }
__device__ __forceinline__ void fence_async() { asm volatile("fence.proxy.async.shared::cta;" ::: "memory"); }
__device__ __forceinline__ uint64_t mkdesc(uint32_t addr, uint32_t lbo, uint32_t sbo) {
  return (uint64_t)((addr & 0x3FFFF) >> 4) | ((uint64_t)(lbo >> 4) << 16) | ((uint64_t)(sbo >> 4) << 32);
}
__device__ __forceinline__ uint32_t mapa(uint32_t a, uint32_t rank) {
  uint32_t r; asm("mapa.shared::cluster.u32 %0, %1, %2;" : "=r"(r) : "r"(a), "r"(rank)); return r;
}
__device__ __forceinline__ void mbar_init_expect(uint32_t bar, uint32_t bytes) {
  asm volatile("mbarrier.init.shared::cta.b64 [%0], 1;" ::"r"(bar) : "memory");
  asm volatile("mbarrier.arrive.expect_tx.shared::cta.b64 _, [%0], %1;" ::"r"(bar), "r"(bytes) : "memory");
}
__device__ __forceinline__ void mbar_wait(uint32_t bar) {
#pragma unroll 1
  for (int it = 0; it < (1 << 22); it++) {
    uint32_t ok;
    asm volatile("{\n.reg .pred p;\nmbarrier.try_wait.parity.acquire.cluster.shared::cta.b64 p, [%1], 0;\nselp.u32 %0, 1, 0, p;\n}"
                 : "=r"(ok) : "r"(bar) : "memory");
    if (ok) return;
  }
  __trap();
}
__device__ __forceinline__ void st_async4(uint32_t a, uint32_t bar, uint32_t x, uint32_t y, uint32_t z, uint32_t w) {
  asm volatile("st.async.weak.shared::cluster.mbarrier::complete_tx::bytes.v4.b32 [%0], {%2,%3,%4,%5}, [%1];"
               ::"r"(a), "r"(bar), "r"(x), "r"(y), "r"(z), "r"(w) : "memory");
}

struct cf { float re, im; };
__device__ __forceinline__ cf cmul(cf a, cf b) { return {fmaf(a.re, b.re, -a.im * b.im), fmaf(a.re, b.im, a.im * b.re)}; }
__device__ __forceinline__ cf csq(cf a) { return {fmaf(a.re, a.re, -a.im * a.im), (a.re + a.re) * a.im}; }
__device__ __forceinline__ cf cexp_p(float xl, float y, float p) {
  float mag; asm("ex2.approx.ftz.f32 %0, %1;" : "=f"(mag) : "f"(xl * p));
  const float th = y * p;
  const float k = rintf(th * 0.15915494309189535f);
  float r = fmaf(k, -6.2831854820251465f, th);
  r = fmaf(k, 1.7484555314695172e-07f, r);
  return {mag * __cosf(r), mag * __sinf(r)};
}
__device__ __forceinline__ uint32_t ysw(int c) { return (uint32_t)(c ^ ((c >> 3) & 3)) * 16u; }

#define CMUL2(OR, OI, xr, xi, yr, yi, nyi) do { OR = hfma2(xr, yr, hmul2(xi, nyi)); OI = hfma2(xr, yi, hmul2(xi, yr)); } while (0)

__device__ __noinline__ uint32_t gate_slow(const __nv_bfloat16* u, const __nv_bfloat16* gw, int row) {
  float s = 0.f;
  const uint32_t* xr = (const uint32_t*)(u + (size_t)row * D);
  const uint32_t* wr = (const uint32_t*)gw;
#pragma unroll 1
  for (int j = 0; j < D / 2; j++) { const uint32_t pr = hmul2(xr[j], wr[j]); s += bf_lo(pr); s += bf_hi(pr); }
  s = bf_round(s);
  return pack_bf16(1.f / (1.f + expf(-s)), 0.f);
}

__device__ __forceinline__ void prefix6(float* pf, uint32_t ub, int c0) {
  pf[0] = 0.f;
#pragma unroll
  for (int j = 0; j < 6; j++) {
    const int c = c0 + j;
    const uint4 v = lds128(ub + (c & 3) * U_CS + (63 - (c >> 2)) * 16);
    const uint32_t w[4] = {v.x, v.y, v.z, v.w};
#pragma unroll
    for (int i = 0; i < 4; i++) {
      pf[j * 8 + 2 * i + 1] = pf[j * 8 + 2 * i] + bf_lo(w[i]);
      pf[j * 8 + 2 * i + 2] = pf[j * 8 + 2 * i + 1] + bf_hi(w[i]);
    }
  }
}
template <int A, int B>
__device__ __forceinline__ void put_win(const float* pf, int ix, uint32_t addr) {
  uint32_t a[4];
#pragma unroll
  for (int i = 0; i < 4; i++) a[i] = pack_bf16(pf[ix + 2 * i - B + 1] - pf[ix + 2 * i - A], pf[ix + 2 * i - B + 2] - pf[ix + 2 * i - A + 1]);
  sts128(addr, a[0], a[1], a[2], a[3]);
}

__device__ __forceinline__ uint32_t get_gate(const Params& p, int x, uint32_t tag) {
  uint2 gv;
  const unsigned int* gp = g_gate + x * 2;
  int spins = 0;
#pragma unroll 1
  while (true) {
    asm volatile("ld.relaxed.gpu.global.v2.u32 {%0,%1}, [%2];" : "=r"(gv.x), "=r"(gv.y) : "l"(gp) : "memory");
    if ((gv.x >> 16) == tag && (gv.y >> 16) == tag) break;
    if (++spins > (1 << 16)) {
      gv.x = gate_slow(p.u, p.gw, x * 2); gv.y = gate_slow(p.u, p.gw, x * 2 + 1);
      break;
    }
  }
  return __byte_perm(gv.x, gv.y, 0x5410);
}

__device__ __noinline__ void final_box(uint32_t sb, const CUtensorMap* tm_out, int lvl, int box, int wtid, uint32_t rank, int oc0,
                                       uint32_t g2, uint2 dA, uint2 dB, int barid) {
  const int x = box * 128 + wtid;
  const uint32_t h2 = hsub2(0x3f803f80u, g2);
  const int c = x >> 2;
  const uint32_t ho = sb + CH_OFF + (x & 3) * 4;
  const uint32_t y0 = ho + Y0_OFF + ysw(c), y2 = ho + Y2_OFF + ysw(c - 64), y3 = ho + Y3_OFF + ysw(c - 128);
  const uint32_t s2 = ho + S2_OFF + ((c - 128) + ((c - 128) >> 3)) * 16, uo = ho + U_OFF + (c & 3) * U_CS + (63 - (c >> 2)) * 16;
  uint32_t o[4], a[4], b[4], uu[4];
#pragma unroll
  for (int k = 0; k < 4; k++) { a[k] = lds32(y0 + k * CH_BYTES); b[k] = lds32(y0 + k * CH_BYTES + 4096); uu[k] = lds32(uo + k * CH_BYTES); }
  if (lvl) {
    uint32_t a2[4], b2[4];
    float ya0[4], ya1[4], yb0[4], yb1[4];
#pragma unroll
    for (int k = 0; k < 4; k++) { a2[k] = lds32(y2 + k * CH_BYTES); b2[k] = lds32(y2 + k * CH_BYTES + 3072); }
    if (lvl == 2) {
      uint32_t a3[4], b3[4], s[4];
#pragma unroll
      for (int k = 0; k < 4; k++) { a3[k] = lds32(y3 + k * CH_BYTES); b3[k] = lds32(y3 + k * CH_BYTES + 2048); s[k] = lds32(s2 + k * CH_BYTES); }
      const uint4 k0 = lds128(sb + K1024_OFF), k1 = lds128(sb + K1024_OFF + 16);
      const uint32_t kk[8] = {k0.x, k0.y, k0.z, k0.w, k1.x, k1.y, k1.z, k1.w};
#pragma unroll
      for (int k = 0; k < 4; k++) {
        const float ka = __uint_as_float(kk[2 * k]), kb = __uint_as_float(kk[2 * k + 1]), s0 = bf_lo(s[k]), s1 = bf_hi(s[k]);
        ya0[k] = fmaf(ka, s0, bf_lo(a3[k])) + bf_lo(a2[k]); ya1[k] = fmaf(ka, s1, bf_hi(a3[k])) + bf_hi(a2[k]);
        yb0[k] = fmaf(kb, s0, bf_lo(b3[k])) + bf_lo(b2[k]); yb1[k] = fmaf(kb, s1, bf_hi(b3[k])) + bf_hi(b2[k]);
      }
    } else {
#pragma unroll
      for (int k = 0; k < 4; k++) { ya0[k] = bf_lo(a2[k]); ya1[k] = bf_hi(a2[k]); yb0[k] = bf_lo(b2[k]); yb1[k] = bf_hi(b2[k]); }
    }
#pragma unroll
    for (int k = 0; k < 4; k++) {
      a[k] = pack_bf16(ya0[k] + bf_lo(a[k]), ya1[k] + bf_hi(a[k]));
      b[k] = pack_bf16(yb0[k] + bf_lo(b[k]), yb1[k] + bf_hi(b[k]));
    }
  }
#pragma unroll
  for (int k = 0; k < 4; k++) {
    const uint32_t da2 = __byte_perm((k & 2) ? dA.y : dA.x, 0, (k & 1) ? 0x3232 : 0x1010);
    const uint32_t db2 = __byte_perm((k & 2) ? dB.y : dB.x, 0, (k & 1) ? 0x3232 : 0x1010);
    o[k] = hadd2(hmul2(g2, hadd2(a[k], hmul2(uu[k], da2))), hmul2(h2, hadd2(b[k], hmul2(uu[k], db2))));
  }
  const uint32_t r00 = __byte_perm(o[0], o[1], 0x5410), r01 = __byte_perm(o[2], o[3], 0x5410);
  const uint32_t r10 = __byte_perm(o[0], o[1], 0x7632), r11 = __byte_perm(o[2], o[3], 0x7632);
  const int slot = box >> 1;
  const uint32_t xin = sb + XIN_OFF + slot * 2048 + wtid * 16, xbar = sb + B_X + slot * 8;
  if ((uint32_t)(box & 1) != rank) {
    st_async4(mapa(xin, rank ^ 1), mapa(xbar, rank ^ 1), r00, r01, r10, r11);
  } else {
    mbar_wait(xbar);
    const uint4 q = lds128(xin);
    const uint32_t st = sb + RAW_OFF + slot * 4096 + wtid * 16;
    if (rank == 0) { sts128(st, r00, r01, q.x, q.y); sts128(st + 2048, r10, r11, q.z, q.w); }
    else { sts128(st, q.x, q.y, r00, r01); sts128(st + 2048, q.z, q.w, r10, r11); }
    fence_async();
    bar_sync(barid, 128);
    if (wtid == 0) {
      asm volatile("cp.async.bulk.tensor.3d.global.shared::cta.bulk_group [%0, {%2, %3, %4}], [%1];"
                   ::"l"(tm_out), "r"(sb + RAW_OFF + slot * 4096), "r"(oc0), "r"(box * 128), "r"(0) : "memory");
      asm volatile("cp.async.bulk.commit_group;" ::: "memory");
    }
  }
}

__device__ __forceinline__ void window_sums(uint32_t cb, int wq, int lane) {
      float pf[49];
      if (wq == 0 || wq == 3) {
        if (wq == 0 || lane < 16) {
          const int nu = wq ? 32 + lane : lane;
          prefix6(pf, cb + U_OFF, 4 * nu - 2);
          const uint32_t po = (5 - (nu >> 3)) * 576 + ((nu & 7) >> 1) * 144 + (nu & 1) * 64;
#pragma unroll
          for (int k = 0; k < 4; k++) { put_win<10, 6>(pf, 16 + 8 * k, cb + W5_OFF + po + k * 16); put_win<5, 3>(pf, 16 + 8 * k, cb + W3_OFF + po + k * 16); }
        }
      } else {
        const uint32_t po = (1 - (lane >> 4)) * 1152 + ((lane & 15) >> 2) * 144 + (lane & 3) * 32;
        if (wq == 1) {
          prefix6(pf, cb + U_OFF, 4 * lane - 3);
#pragma unroll
          for (int k = 0; k < 4; k++) put_win<20, 12>(pf, 24 + 8 * k, cb + W9_OFF + po + (k & 1) * 576 + (k >> 1) * 16);
        } else {
          prefix6(pf, cb + U_OFF, 4 * lane - 2);
          const uint32_t so = cb + S2_OFF + (lane >> 1) * 144 + (lane & 1) * 64;
#pragma unroll
          for (int k = 0; k < 4; k++) { put_win<11, 5>(pf, 16 + 8 * k, cb + W7_OFF + po + (k & 1) * 576 + (k >> 1) * 16); put_win<4, 3>(pf, 16 + 8 * k, so + k * 16); }
        }
      }
}

__global__ void __cluster_dims__(2, 1, 1) __launch_bounds__(640, 1)
ssm_kernel(const Params p, const __grid_constant__ CUtensorMap tm_in, const __grid_constant__ CUtensorMap tm_out) {
  extern __shared__ __align__(1024) unsigned char smem_raw[];
  const uint32_t sb = (uint32_t)__cvta_generic_to_shared(smem_raw);
  const int tid = threadIdx.x, lane = tid & 31;
  const int warp = __shfl_sync(0xffffffffu, tid >> 5, 0);
  const int ch = warp >> 2, wq = warp & 3, br = wq >> 1, hf = wq & 1;
  const int g = lane >> 2, t = lane & 3;
  const int d = blockIdx.x * 4 + ch;
  const uint32_t rank = blockIdx.x & 1;
  const uint32_t cb = sb + CH_OFF + ch * CH_BYTES;
  const int wtid = tid & 127;
  const int oc0 = (int)(blockIdx.x >> 1) * 8;
  STAMP(0); GT(0);

  if (warp >= 16) {
    if (wtid == 0) {
      mbar_init_expect(sb + B_RAW, 32768);
#pragma unroll
      for (int i = 0; i < 4; i++) mbar_init_expect(sb + B_X + 8 * i, 2048);
      asm volatile("mbarrier.init.shared::cta.b64 [%0], 128;" ::"r"(sb + B_U) : "memory");
      asm volatile("mbarrier.init.shared::cta.b64 [%0], 128;" ::"r"(sb + B_W) : "memory");
      asm volatile("fence.mbarrier_init.release.cluster;" ::: "memory");
      asm volatile("fence.proxy.async.shared::cta;" ::: "memory");
    }
    __syncwarp();
    asm volatile("barrier.cluster.arrive.relaxed.aligned;" ::: "memory");
    unsigned int epoch;
    asm volatile("ld.relaxed.gpu.global.u32 %0, [%1];" : "=r"(epoch) : "l"(&g_epoch) : "memory");
    const uint2 dA = *(const uint2*)(p.A_D + blockIdx.x * 4), dB = *(const uint2*)(p.B_D + blockIdx.x * 4);
    const uint4 gw0 = *(const uint4*)(p.gw + lane * 8), gw1 = *(const uint4*)(p.gw + 256 + lane * 8);
    asm volatile("barrier.cluster.wait.aligned;" ::: "memory");
    if (wtid == 0) {
      asm volatile("cp.async.bulk.tensor.5d.shared::cluster.global.mbarrier::complete_tx::bytes.multicast::cluster [%0], [%1, {%3, %4, %4, %4, %5}], [%2], %6;"
                   ::"r"(sb + RAW_OFF + rank * 16384), "l"(&tm_in), "r"(sb + B_RAW), "r"(oc0), "r"(0), "r"((int)rank * 32), "h"((unsigned short)3) : "memory");
    }
    sts128(sb + CH_OFF + wq * CH_BYTES + U_OFF + (lane >> 3) * U_CS + (64 + (lane & 7)) * 16, 0, 0, 0, 0);
    const uint32_t tag = (epoch + 1) & 0xffffu;
    {
      const int grow = blockIdx.x * 16 + wq * 4;
      uint4 gx[4][2];
#pragma unroll
      for (int i = 0; i < 4; i++) {
        gx[i][0] = *(const uint4*)(p.u + (size_t)(grow + i) * D + lane * 8);
        gx[i][1] = *(const uint4*)(p.u + (size_t)(grow + i) * D + 256 + lane * 8);
      }
      const uint32_t ws[8] = {gw0.x, gw0.y, gw0.z, gw0.w, gw1.x, gw1.y, gw1.z, gw1.w};
      float sm[4];
#pragma unroll
      for (int i = 0; i < 4; i++) {
        const uint32_t xs[8] = {gx[i][0].x, gx[i][0].y, gx[i][0].z, gx[i][0].w, gx[i][1].x, gx[i][1].y, gx[i][1].z, gx[i][1].w};
        float s = 0.f;
#pragma unroll
        for (int j = 0; j < 8; j++) { const uint32_t pr = hmul2(xs[j], ws[j]); s += bf_lo(pr); s += bf_hi(pr); }
        sm[i] = s;
      }
      {
        const bool b0 = lane & 1, b1 = lane & 2;
        float u0 = b0 ? sm[1] : sm[0], v0 = b0 ? sm[0] : sm[1], u1 = b0 ? sm[3] : sm[2], v1 = b0 ? sm[2] : sm[3];
        u0 += __shfl_xor_sync(0xffffffffu, v0, 1); u1 += __shfl_xor_sync(0xffffffffu, v1, 1);
        float s = b1 ? u1 : u0; const float v = b1 ? u0 : u1;
        s += __shfl_xor_sync(0xffffffffu, v, 2);
#pragma unroll
        for (int o = 4; o < 32; o <<= 1) s += __shfl_xor_sync(0xffffffffu, s, o);
        s = bf_round(s);
        const float gv = 1.f / (1.f + expf(-s));
        const uint32_t w = (tag << 16) | (pack_bf16(gv, 0.f) & 0xffffu);
        if (lane < 4) asm volatile("st.relaxed.gpu.global.u32 [%0], %1;" ::"l"(&g_gate[grow + lane]), "r"(w) : "memory");
      }
    }
    STAMP(3);
    mbar_wait(sb + B_RAW);
    STAMP(4);
    {
      const uint32_t dst = sb + CH_OFF + (g & 3) * CH_BYTES + U_OFF + t * U_CS + (63 - wq * 16) * 16;
#pragma unroll
      for (int h = 0; h < 2; h++) {
        uint32_t r[8][4];
#pragma unroll
        for (int i = 0; i < 8; i++) ldsm4t(sb + RAW_OFF + (wq * 16 + h * 8 + i) * 512 + lane * 16, r[i][0], r[i][1], r[i][2], r[i][3]);
        if ((uint32_t)(g >> 2) == rank) {
#pragma unroll
          for (int i = 0; i < 8; i++) sts128(dst - (h * 8 + i) * 16, r[i][0], r[i][1], r[i][2], r[i][3]);
        }
      }
    }
    fence_async();
    asm volatile("mbarrier.arrive.shared::cta.b64 _, [%0];" ::"r"(sb + B_U) : "memory");
    bar_sync(5, 128);
    STAMP(5);
#pragma unroll 1
    for (int k = 0; k < 4; k++) window_sums(sb + CH_OFF + k * CH_BYTES, wq, lane);
    fence_async();
    asm volatile("mbarrier.arrive.shared::cta.b64 _, [%0];" ::"r"(sb + B_W) : "memory");
    STAMP(7);
    STAMP(8);
    unsigned int ticket = 0;
    uint32_t gg[4];
#pragma unroll
    for (int i = 0; i < 4; i++) gg[i] = get_gate(p, (i ^ (int)rank ^ 1) * 128 + wtid, tag);
#pragma unroll 1
    for (int lvl = 0; lvl < 2; lvl++) {
      const int bs = 2 * lvl + (int)(rank ^ 1), bm = 2 * lvl + (int)rank;
      const uint32_t gs = lvl ? gg[2] : gg[0], gm = lvl ? gg[3] : gg[1];
      bar_sync(8 + lvl, 640);
      STAMP(10 + lvl);
      if (lvl == 0 && wtid == 0) ticket = atomicAdd(&g_ticket, 1u);
      final_box(sb, &tm_out, lvl, bs, wtid, rank, oc0, gs, dA, dB, 5);
      final_box(sb, &tm_out, lvl, bm, wtid, rank, oc0, gm, dA, dB, 5);
      STAMP(12 + lvl);
    }
    if (wtid == 0) {
      if (ticket == NCTA - 1) { g_ticket = 0; g_epoch = epoch + 1; }
      asm volatile("cp.async.bulk.wait_group.read 0;" ::: "memory");
    }
    STAMP(15);
    return;
  }
  asm volatile("barrier.cluster.arrive.relaxed.aligned;" ::: "memory");

  const int moff = d * NM + hf * 64 + lane * 2;
  const uint32_t q0 = *(const uint32_t*)((br ? p.B_lA : p.A_re) + moff), q1 = *(const uint32_t*)((br ? p.B_Aim : p.A_im) + moff);
  const uint32_t q2 = *(const uint32_t*)((br ? p.B_Cre : p.C_re) + moff), q3 = *(const uint32_t*)((br ? p.B_Cim : p.C_im) + moff);
  const uint32_t q4 = *(const uint32_t*)((br ? p.B_Cre : p.B_re) + moff), q5 = *(const uint32_t*)((br ? p.B_Cim : p.B_im) + moff);
  const uint2 ldt4 = *(const uint2*)((br ? p.B_ldt : p.A_ldt) + blockIdx.x * 4);
  unsigned int epoch;
  asm volatile("ld.relaxed.gpu.global.u32 %0, [%1];" : "=r"(epoch) : "l"(&g_epoch) : "memory");

  for (int i = wtid & 63; i < R_BR / 16; i += 64) sts128(cb + R_OFF + br * R_BR + i * 16, 0, 0, 0, 0);
  STAMP(1);

  float acc[5][4];
  float k2048 = 0.f;
  const uint32_t scr = cb + Y0_OFF + wq * SCR_BYTES;
  const uint32_t scr2 = sb + XIN_OFF + warp * 640;
  {
    const uint32_t ldt2 = (ch & 2) ? ldt4.y : ldt4.x;
    const float dt = bf_round(expf((ch & 1) ? bf_hi(ldt2) : bf_lo(ldt2)));
#pragma unroll
    for (int i = 0; i < 5; i++) acc[i][0] = acc[i][1] = acc[i][2] = acc[i][3] = 0.f;
    cf cc[2], zz1[2], zz128[2];
#pragma unroll
    for (int r = 0; r < 2; r++) {
      float v0 = r ? bf_hi(q0) : bf_lo(q0), v1 = r ? bf_hi(q1) : bf_lo(q1), v2 = r ? bf_hi(q2) : bf_lo(q2);
      float v3 = r ? bf_hi(q3) : bf_lo(q3), v4 = r ? bf_hi(q4) : bf_lo(q4), v5 = r ? bf_hi(q5) : bf_lo(q5);
      if (br == 0) { cc[r] = cmul(cf{v2, v3}, cf{dt * v4, dt * v5}); }
      else { v0 = -bf_round(expf(v0)); cc[r] = cf{2.f * dt * v2, 2.f * dt * v3}; }
      const float xl = (dt * v0) * 1.4426950408889634f, y = dt * v1;
      zz1[r] = cexp_p(xl, y, 1.f); zz128[r] = cexp_p(xl, y, 128.f);
    }
    STAMP(2);
    const uint32_t tb = scr + lane * 16;
    const uint32_t ta = scr + (lane >> 3) * 512 + (lane & 7) * 16;
    const uint32_t tc = ((lane & 8) ? scr2 : scr + 4096) + (lane >> 4) * 128 + (lane & 7) * 16;
    const uint32_t tm = scr2 + 512 + ((lane >> 3) & 1) * 64 + (lane >> 4) * 16;
#pragma unroll 1
    for (int r = 0; r < 2; r++) {
      const cf c = r ? cc[1] : cc[0], z1 = r ? zz1[1] : zz1[0], z128 = r ? zz128[1] : zz128[0];
      const cf z2 = csq(z1), z4 = csq(z2), z8 = csq(z4);
      const cf z16 = csq(z8), z24 = cmul(z16, z8), z32 = csq(z16), z40 = cmul(z32, z8), z48 = csq(z24), z56 = cmul(z32, z24), z64 = csq(z32);
      const cf z256 = csq(z128), z512 = csq(z256), z1024 = csq(z512), z2048 = csq(z1024);
      k2048 += fmaf(c.re, z2048.re, -c.im * z2048.im);
      __syncwarp();
      {
        uint32_t xr[4] = {pack_bf16(1.f, z8.re), pack_bf16(z16.re, z24.re), pack_bf16(z32.re, z40.re), pack_bf16(z48.re, z56.re)};
        uint32_t xi[4] = {pack_bf16(0.f, -z8.im), pack_bf16(-z16.im, -z24.im), pack_bf16(-z32.im, -z40.im), pack_bf16(-z48.im, -z56.im)};
        sts128(tb + 0 * 512, xr[0], xr[1], xr[2], xr[3]);
        sts128(tb + 2 * 512, xi[0], xi[1], xi[2], xi[3]);
        const uint32_t yr = pack_bf16(z64.re, z64.re), nyi = pack_bf16(z64.im, z64.im), yi = nyi ^ 0x80008000u;
        uint32_t o[4], q[4];
#pragma unroll
        for (int i = 0; i < 4; i++) CMUL2(o[i], q[i], xr[i], xi[i], yr, yi, nyi);
        sts128(tb + 1 * 512, o[0], o[1], o[2], o[3]);
        sts128(tb + 3 * 512, q[0], q[1], q[2], q[3]);
      }
      {
        const cf h1 = cmul(c, z128), h2 = cmul(c, z256), h3 = cmul(h1, z256), h4 = cmul(c, z512), h5 = cmul(h1, z512), h6 = cmul(h2, z512), h7 = cmul(h3, z512);
        const cf e1 = cmul(c, z1), e2 = cmul(c, z2), e3 = cmul(e1, z2), e129 = cmul(h1, z1), e130 = cmul(h1, z2), e131 = cmul(e129, z2);
        const cf e258 = cmul(h2, z2), e386 = cmul(h3, z2);
        const uint32_t pr0 = pack_bf16(c.re, e1.re), pr2 = pack_bf16(h1.re, e129.re), pi0 = pack_bf16(c.im, e1.im), pi2 = pack_bf16(h1.im, e129.im);
        sts128(tb + 4 * 512, pr0, pack_bf16(e2.re, e3.re), pr2, pack_bf16(e130.re, e131.re));
        sts128(tb + 5 * 512, pi0, pack_bf16(e2.im, e3.im), pi2, pack_bf16(e130.im, e131.im));
        uint32_t xr[4] = {pack_bf16(h2.re, e258.re), pack_bf16(h3.re, e386.re), pack_bf16(h4.re, h5.re), pack_bf16(h6.re, h7.re)};
        uint32_t xi[4] = {pack_bf16(h2.im, e258.im), pack_bf16(h3.im, e386.im), pack_bf16(h4.im, h5.im), pack_bf16(h6.im, h7.im)};
        sts128(tb + 6 * 512, xr[0], xr[1], xr[2], xr[3]);
        sts128(tb + 7 * 512, xi[0], xi[1], xi[2], xi[3]);
        xr[1] = __byte_perm(xr[0], xr[1], 0x5410); xi[1] = __byte_perm(xi[0], xi[1], 0x5410);
        xr[0] = __byte_perm(pr0, pr2, 0x5410); xi[0] = __byte_perm(pi0, pi2, 0x5410);
        const uint32_t yr = pack_bf16(z1024.re, z1024.re), yi = pack_bf16(z1024.im, z1024.im), nyi = yi ^ 0x80008000u;
        uint32_t o[4], q[4];
#pragma unroll
        for (int i = 0; i < 4; i++) CMUL2(o[i], q[i], xr[i], xi[i], yr, yi, nyi);
        sts128(tb + 8 * 512, o[0], o[1], o[2], o[3]);
        sts128(scr2 + lane * 16, q[0], q[1], q[2], q[3]);
        const uint32_t m4 = pack_bf16(z4.re, z4.im);
        sts16(scr2 + 512 + lane * 2, m4); sts16(scr2 + 576 + lane * 2, m4 >> 16);
      }
      __syncwarp();
#pragma unroll
      for (int kp = 0; kp < 2; kp++) {
        uint32_t rr[2], ri[2], yr[2], yi[2];
        ldsm4t(tc + kp * 256, rr[0], ri[0], rr[1], ri[1]);
        ldsm4(tm + kp * 32, yr[0], yi[0], yr[1], yi[1]);
#pragma unroll
        for (int k2 = 0; k2 < 2; k2++) {
          const int kk = kp * 2 + k2;
          uint32_t a0, a1, a2, a3, pr, pi, qr, qi, xr, xi;
          ldsm4t(ta + kk * 128, a0, a1, a2, a3);
          ldsm4t(ta + 2048 + kk * 128, pr, pi, qr, qi);
          const uint32_t nyi = yi[k2] ^ 0x80008000u;
          mma16816(acc[0], a0, a1, a2, a3, pr, pi);
          mma16816(acc[2], a0, a1, a2, a3, qr, qi);
          mma16816(acc[4], a0, a1, a2, a3, rr[k2], ri[k2]);
          CMUL2(xr, xi, pr, pi, yr[k2], yi[k2], nyi);
          mma16816(acc[1], a0, a1, a2, a3, xr, xi);
          CMUL2(xr, xi, qr, qi, yr[k2], yi[k2], nyi);
          mma16816(acc[3], a0, a1, a2, a3, xr, xi);
        }
      }
    }
#pragma unroll
    for (int o = 16; o; o >>= 1) k2048 += __shfl_xor_sync(0xffffffffu, k2048, o);
  }
  STAMP(3);
  __syncwarp();
  {
    const uint32_t xs = scr + lane * 16;
#define OTH(i, k) __float_as_uint(hf ? acc[i][k] : acc[i][2 + (k)])
    sts128(xs, OTH(0, 0), OTH(0, 1), OTH(1, 0), OTH(1, 1));
    sts128(xs + 512, OTH(2, 0), OTH(2, 1), OTH(3, 0), OTH(3, 1));
    sts128(xs + 1024, OTH(4, 0), OTH(4, 1), __float_as_uint(k2048), 0);
#undef OTH
  }

  bar_sync(1 + ch, 128);
  STAMP(4);
  {
    const uint32_t xo = cb + Y0_OFF + (wq ^ 1) * SCR_BYTES + lane * 16;
    const uint4 o0 = lds128(xo), o1 = lds128(xo + 512), o2 = lds128(xo + 1024);
    const uint32_t rb = cb + R_OFF + br * R_BR;
#define OWN(i, k) (hf ? acc[i][2 + (k)] : acc[i][k])
    const uint32_t vP = pack_bf16(OWN(0, 1) + __uint_as_float(o0.y), OWN(0, 0) + __uint_as_float(o0.x));
    const uint32_t vP4 = pack_bf16(OWN(1, 1) + __uint_as_float(o0.w), OWN(1, 0) + __uint_as_float(o0.z));
    const uint32_t vQ = pack_bf16(OWN(2, 1) + __uint_as_float(o1.y), OWN(2, 0) + __uint_as_float(o1.x));
    const uint32_t vQ4 = pack_bf16(OWN(3, 1) + __uint_as_float(o1.w), OWN(3, 0) + __uint_as_float(o1.z));
    const uint32_t vR = pack_bf16(OWN(4, 1) + __uint_as_float(o2.y), OWN(4, 0) + __uint_as_float(o2.x));
#undef OWN
    const int j = g + 8 * hf;
    {
      const int a = 2 * (t & 1) + 64 * (t & 2) + 8 * j;
      const uint32_t ad = rb + 2 * (RD_X0 - 1 - a);
      const uint32_t a1 = (t & 2) ? ad - 8 : ad, a2 = (t & 2) ? ad : ad - 8;
      const uint32_t w1 = (t & 2) ? vP4 : vP, w2 = (t & 2) ? vP : vP4;
      sts32(a1, w1); sts32(a2, w2);
      sts16(a1 + RD_CS + 2, w1); sts16(a1 + RD_CS + 4, w1 >> 16);
      sts16(a2 + RD_CS + 2, w2); sts16(a2 + RD_CS + 4, w2 >> 16);
    }
    if (t < 2) {
      const int b = 256 + 128 * t + 8 * j;
      const uint32_t ad = rb + 2 * (RD_X0 - 6 - b);
      const uint32_t v22 = __byte_perm(vQ4, 0, 0x3232), v00 = __byte_perm(vQ, 0, 0x3232);
      sts16(ad, vQ4);
      sts64(ad + 2, v22, __byte_perm(vQ4, vQ, 0x5432));
      sts32(ad + 10, v00);
      if (b != 256) { sts16(ad + 14, v00); sts128(ad + RD_CS + 2, vQ4, v22, vQ, v00); }
      else { sts64(ad + RD_CS + 2, vQ4, v22); sts32(ad + RD_CS + 10, vQ); sts16(ad + RD_CS + 14, v00); }
    } else {
      const uint32_t ao = rb + R_O2 + 2 * (159 - (32 * t + j)), ae = ao - (R_O2 - R_E2) + 2;
      sts16(ao, vQ4 >> 16); sts16(ao + RS_CS + 2, vQ4 >> 16); sts16(ao - 32, vQ4); sts16(ao - 32 + RS_CS + 2, vQ4);
      sts16(ae - 32, vQ); sts16(ae - 32 + RS_CS + 2, vQ);
      if (lane != 2 || hf) { sts16(ae, vQ >> 16); sts16(ae + RS_CS + 2, vQ >> 16); }
      else {
        const uint32_t vv = __byte_perm(vQ, 0, 0x3232), ad = rb + 2 * (RD_X0 - 514);
        sts16(ad, vv); sts32(ad + 2, vv); sts16(ad + 6, vv); sts64(ad + RD_CS + 2, vv, vv);
      }
    }
    {
      const uint32_t a = rb + ((g & 1) ? R_O3 : R_E3 + 2) + 2 * (159 - (64 + 16 * t + (j >> 1)));
      const bool p1024 = (lane == 0) && (hf == 0);
      const uint32_t a00 = p1024 ? rb + R_E2 + 2 * (159 - 127) : a;
      sts16(a00, vR >> 16); sts16(a00 + RS_CS + 2, vR >> 16);
      sts16(a - 16, vR); sts16(a - 16 + RS_CS + 2, vR);
      if (p1024) {
        sts32(sb + K1024_OFF + (ch * 2 + br) * 4, vR & 0xffff0000u);
        const uint32_t kv = pack_bf16(k2048 + __uint_as_float(o2.z), 0.f);
        sts16(rb + R_E3 + 2 * (159 - 127), kv); sts16(rb + R_E3 + 2 * (159 - 127) + RS_CS + 2, kv);
      }
    }
  }
  STAMP(5);
  const uint32_t tag = (epoch + 1) & 0xffffu;
  asm volatile("barrier.cluster.wait.aligned;" ::: "memory");
  bar_sync(1 + ch, 128);
  mbar_wait(sb + B_U);
  STAMP(6);

  const uint32_t rb = cb + R_OFF + br * R_BR;
  const int eo = 16 * hf + g - 2 * t;
  float dacc[32];
  {
      {
        const int x0 = RD_X0 - (eo + 536);
        const uint32_t fa = rb + ((g & 1) ? 2 * x0 : RD_CS + 2 * x0 + 2);
        const uint64_t ub = mkdesc(cb + U_OFF, U_CS, 128);
        uint32_t f[2][9];
#pragma unroll
        for (int i = 0; i < 9; i++) f[0][i] = lds32(fa + (62 + i) * 16);
#pragma unroll
        for (int j = 0; j < 9; j++) {
          wg_fence();
#pragma unroll
          for (int k = 0; k < 4; k++) {
            const int s = 34 - 4 * j - k;
            if (s >= 0) {
              const int o = 2 * s - 66 + 128;
              const int cc = o & 3, rs = (o >> 2) - 32;
              const int n0 = ((-rs) >> 3) * 8;
              const uint64_t desc = ub + (uint64_t)((cc * U_CS - rs * 16) >> 4);
              const int fi = 2 * (3 - k);
              const uint32_t a1 = f[j & 1][fi], a0 = f[j & 1][fi + 1], a2 = f[j & 1][fi + 2];
              if (n0 == 0) wgmma_rs<64, 0>(dacc, a0, a1, a2, a0, desc, s != 34);
              else if (n0 == 8) wgmma_rs<56, 0>(dacc, a0, a1, a2, a0, desc, 1);
              else wgmma_rs<48, 0>(dacc, a0, a1, a2, a0, desc, 1);
            }
          }
          wg_commit();
          if (j < 8) {
#pragma unroll
            for (int i = 0; i < 9; i++) {
              const int idx = 62 - 8 * (j + 1) + i;
              if (idx >= 0) f[(j + 1) & 1][i] = lds32(fa + idx * 16);
            }
          }
          wg_wait0();
        }
      }
      const uint32_t yb = cb + Y0_OFF + br * 4096;
#pragma unroll
      for (int i = 0; i < 8; i += 2) {
        const int mi = lane >> 3;
        const int cidx = 4 * (63 - 8 * (i + (mi >> 1)) - (lane & 7)) + 2 * hf + (mi & 1);
        stsm4t(yb + ysw(cidx), pack_bf16(dacc[4 * i], dacc[4 * i + 1]), pack_bf16(dacc[4 * i + 2], dacc[4 * i + 3]),
               pack_bf16(dacc[4 * i + 4], dacc[4 * i + 5]), pack_bf16(dacc[4 * i + 6], dacc[4 * i + 7]));
      }
      bar_arrive(8, 640);
      STAMP(8);
  }
  const uint2 dA = *(const uint2*)(p.A_D + blockIdx.x * 4), dB = *(const uint2*)(p.B_D + blockIdx.x * 4);
  const uint32_t g2 = get_gate(p, (4 + ch) * 128 + wtid, tag);
  mbar_wait(sb + B_W);
  const int x1 = 159 - (eo + 136);
  const uint32_t fs = rb + ((g & 1) ? 2 * x1 : RS_CS + 2 * x1 + 2);
  {
    uint32_t f[2][10];
    const uint64_t d5 = mkdesc(cb + W5_OFF, 144, 576), d3 = mkdesc(cb + W3_OFF, 144, 576);
#pragma unroll
    for (int i = 0; i < 5; i++) { f[0][i] = lds32(fs + R_E2 + (8 + i) * 16); f[0][5 + i] = lds32(fs + R_O2 + (8 + i) * 16); }
#pragma unroll
    for (int m = 2; m <= 4; m++) {
      wg_fence();
#pragma unroll
      for (int k = 0; k < 4; k++) {
        const uint32_t* a = &f[m & 1][(k >> 1) * 5 + (k & 1) * 2];
        const uint64_t desc = ((k >> 1) ? d3 : d5) + (k & 1) * 18 + (m - 2) * 36;
        if (m == 2) wgmma_rs<48, 1>(dacc, a[1], a[0], a[2], a[1], desc, k);
        else if (m == 3) wgmma_rs<40, 1>(dacc, a[1], a[0], a[2], a[1], desc, 1);
        else wgmma_rs<32, 1>(dacc, a[1], a[0], a[2], a[1], desc, 1);
      }
      wg_commit();
#pragma unroll
      for (int i = 0; i < 5; i++) {
        if (m < 4) { f[(m + 1) & 1][i] = lds32(fs + R_E2 + (4 * (3 - m) + i) * 16); f[(m + 1) & 1][5 + i] = lds32(fs + R_O2 + (4 * (3 - m) + i) * 16); }
        else { f[1][i] = lds32(fs + R_E3 + (8 + i) * 16); f[1][5 + i] = lds32(fs + R_O3 + (8 + i) * 16); }
      }
      wg_wait0();
    }
    {
      const uint32_t yb = cb + Y2_OFF + br * 3072;
#pragma unroll
      for (int i = 0; i < 6; i += 2) {
        const int mi = lane >> 3;
        const int cidx = 32 * (5 - i - (mi >> 1)) + 16 * hf + 8 * (mi & 1) + (lane & 7);
        stsm4(yb + ysw(cidx), pack_bf16(dacc[4 * i], dacc[4 * i + 1]), pack_bf16(dacc[4 * i + 2], dacc[4 * i + 3]),
              pack_bf16(dacc[4 * i + 4], dacc[4 * i + 5]), pack_bf16(dacc[4 * i + 6], dacc[4 * i + 7]));
      }
    }
    bar_arrive(9, 640);
    STAMP(9);
    const uint64_t d9 = mkdesc(cb + W9_OFF, 144, 576), d7 = mkdesc(cb + W7_OFF, 144, 576);
#pragma unroll
    for (int m = 2; m <= 3; m++) {
      wg_fence();
#pragma unroll
      for (int k = 0; k < 4; k++) {
        const uint32_t* a = &f[(m + 1) & 1][(k >> 1) * 5 + (k & 1) * 2];
        const uint64_t desc = ((k >> 1) ? d7 : d9) + (k & 1) * 18 + (m - 2) * 72;
        if (m == 2) wgmma_rs<32, 1>(dacc, a[1], a[0], a[2], a[1], desc, k);
        else wgmma_rs<16, 1>(dacc, a[1], a[0], a[2], a[1], desc, 1);
      }
      wg_commit();
      if (m == 2) {
#pragma unroll
        for (int i = 0; i < 5; i++) { f[0][i] = lds32(fs + R_E3 + (4 + i) * 16); f[0][5 + i] = lds32(fs + R_O3 + (4 + i) * 16); }
      }
      wg_wait0();
    }
    const uint32_t yb = cb + Y3_OFF + br * 2048;
#pragma unroll
    for (int i = 0; i < 4; i += 2) {
      const int mi = lane >> 3;
      const int cidx = 64 * (1 - (i >> 1)) + 2 * (16 * hf + 8 * (mi & 1) + (lane & 7)) + (mi >> 1);
      stsm4(yb + ysw(cidx), pack_bf16(dacc[4 * i], dacc[4 * i + 1]), pack_bf16(dacc[4 * i + 2], dacc[4 * i + 3]),
            pack_bf16(dacc[4 * i + 4], dacc[4 * i + 5]), pack_bf16(dacc[4 * i + 6], dacc[4 * i + 7]));
    }
  }
  STAMP(10);

  bar_sync(10, 512);
  STAMP(11);
  final_box(sb, &tm_out, 2, 4 + ch, wtid, rank, oc0, g2, dA, dB, 1 + ch);
  STAMP(14);
  if (wtid == 0) asm volatile("cp.async.bulk.wait_group.read 0;" ::: "memory");
  STAMP(15); GT(1);
}

typedef CUresult (*EncodeFn)(CUtensorMap*, CUtensorMapDataType, cuuint32_t, void*, const cuuint64_t*, const cuuint64_t*,
                             const cuuint32_t*, const cuuint32_t*, CUtensorMapInterleave, CUtensorMapSwizzle,
                             CUtensorMapL2promotion, CUtensorMapFloatOOBfill);

}

extern "C" void kernel_launch(void* const* d_in, const int* in_sizes, int n_in, void* d_out, int out_size) {
  (void)in_sizes; (void)n_in; (void)out_size;
  typedef const __nv_bfloat16* bp;
  Params p;
  p.u = (bp)d_in[0]; p.A_re = (bp)d_in[1]; p.A_im = (bp)d_in[2]; p.B_re = (bp)d_in[3]; p.B_im = (bp)d_in[4];
  p.C_re = (bp)d_in[5]; p.C_im = (bp)d_in[6]; p.A_ldt = (bp)d_in[7]; p.A_D = (bp)d_in[8];
  p.B_lA = (bp)d_in[10]; p.B_Aim = (bp)d_in[11]; p.B_Cre = (bp)d_in[12]; p.B_Cim = (bp)d_in[13];
  p.B_ldt = (bp)d_in[14]; p.B_D = (bp)d_in[15]; p.gw = (bp)d_in[16];
  static EncodeFn enc = nullptr;
  if (!enc) {
    cudaDriverEntryPointQueryResult qr;
    cudaGetDriverEntryPoint("cuTensorMapEncodeTiled", (void**)&enc, cudaEnableDefault, &qr);
    cudaFuncSetAttribute(ssm_kernel, cudaFuncAttributeMaxDynamicSharedMemorySize, SMEM_BYTES);
  }
  CUtensorMap tm_in, tm_out;
  {
    cuuint64_t gd[5] = {512, 2, 4, 4, 64};
    cuuint64_t gs[4] = {1024, 8192, 2048, 32768};
    cuuint32_t bx[5] = {8, 2, 4, 4, 32};
    cuuint32_t es[5] = {1, 1, 1, 1, 1};
    enc(&tm_in, CU_TENSOR_MAP_DATA_TYPE_BFLOAT16, 5, d_in[0], gd, gs, bx, es, CU_TENSOR_MAP_INTERLEAVE_NONE,
        CU_TENSOR_MAP_SWIZZLE_NONE, CU_TENSOR_MAP_L2_PROMOTION_NONE, CU_TENSOR_MAP_FLOAT_OOB_FILL_NONE);
  }
  {
    cuuint64_t gd[3] = {512, 1024, 2};
    cuuint64_t gs[2] = {2048, 1024};
    cuuint32_t bx[3] = {8, 128, 2};
    cuuint32_t es[3] = {1, 1, 1};
    enc(&tm_out, CU_TENSOR_MAP_DATA_TYPE_BFLOAT16, 3, d_out, gd, gs, bx, es, CU_TENSOR_MAP_INTERLEAVE_NONE,
        CU_TENSOR_MAP_SWIZZLE_NONE, CU_TENSOR_MAP_L2_PROMOTION_NONE, CU_TENSOR_MAP_FLOAT_OOB_FILL_NONE);
  }
  ssm_kernel<<<NCTA, 640, SMEM_BYTES, cudaStreamPerThread>>>(p, tm_in, tm_out);
}
```

```cpp
#include <cuda_runtime.h>
#include <cuda.h>
#include <cuda_bf16.h>
#include <stdint.h>

namespace {

constexpr int L = 2048, D = 512, NM = 128;
constexpr int NCTA = 128;

constexpr int RAW_OFF = 0;
constexpr int XIN_OFF = 32768;
constexpr int BAR_OFF = XIN_OFF + 10240;
constexpr int CH_OFF = BAR_OFF + 128;
constexpr int U_CS = 1184;
constexpr int U_OFF = 0;
constexpr int R_OFF = 4736;
constexpr int RD_X0 = 565;
constexpr int RD_CS = 1216;
constexpr int RS_CS = 320;
constexpr int R_E2 = 2 * RD_CS, R_O2 = R_E2 + 2 * RS_CS, R_E3 = R_O2 + 2 * RS_CS, R_O3 = R_E3 + 2 * RS_CS;
constexpr int R_BR = R_O3 + 2 * RS_CS;
constexpr int W5_OFF = R_OFF + 2 * R_BR;
constexpr int W3_OFF = W5_OFF + 3456;
constexpr int W9_OFF = W3_OFF + 3456;
constexpr int W7_OFF = W9_OFF + 2304;
constexpr int S2_OFF = W7_OFF + 2304;
constexpr int Y0_OFF = S2_OFF + 2304;
constexpr int Y2_OFF = Y0_OFF + 8192, Y3_OFF = Y2_OFF + 6144;
constexpr int CH_BYTES = Y0_OFF + 18432 + 16;
constexpr int SCR_BYTES = 4608;
constexpr int SMEM_BYTES = CH_OFF + 4 * CH_BYTES;
static_assert(CH_BYTES % 128 == 16, "bank staggering of the channel blocks");
static_assert(SMEM_BYTES <= 232448, "smem");
constexpr int B_RAW = BAR_OFF, B_X = BAR_OFF + 8, B_U = BAR_OFF + 40, B_W = BAR_OFF + 48;
constexpr int K1024_OFF = BAR_OFF + 64;

__device__ unsigned int g_gate[L];
__device__ unsigned int g_epoch;
__device__ unsigned int g_ticket;

#define STAMP(k)
#define GT(k)

struct Params {
  const __nv_bfloat16 *u, *A_re, *A_im, *B_re, *B_im, *C_re, *C_im, *A_ldt, *A_D;
  const __nv_bfloat16 *B_lA, *B_Aim, *B_Cre, *B_Cim, *B_ldt, *B_D, *gw;
};

template <int N, int TB> __device__ __forceinline__ void wgmma_rs(float* d, uint32_t a0, uint32_t a1, uint32_t a2, uint32_t a3, uint64_t desc, int sc);
template <> __device__ __forceinline__ void wgmma_rs<64, 0>(float* d, uint32_t a0, uint32_t a1, uint32_t a2, uint32_t a3, uint64_t desc, int sc) {
  asm volatile("{\n.reg .pred p;\nsetp.ne.b32 p, %37, 0;\n"
    "wgmma.mma_async.sync.aligned.m64n64k16.f32.bf16.bf16 {%0,%1,%2,%3,%4,%5,%6,%7,%8,%9,%10,%11,%12,%13,%14,%15,%16,%17,%18,%19,%20,%21,%22,%23,%24,%25,%26,%27,%28,%29,%30,%31}, {%32,%33,%34,%35}, %36, p, 1, 1, 0;\n}"
    : "+f"(d[0]), "+f"(d[1]), "+f"(d[2]), "+f"(d[3]), "+f"(d[4]), "+f"(d[5]), "+f"(d[6]), "+f"(d[7]), "+f"(d[8]), "+f"(d[9]), "+f"(d[10]), "+f"(d[11]), "+f"(d[12]), "+f"(d[13]), "+f"(d[14]), "+f"(d[15]), "+f"(d[16]), "+f"(d[17]), "+f"(d[18]), "+f"(d[19]), "+f"(d[20]), "+f"(d[21]), "+f"(d[22]), "+f"(d[23]), "+f"(d[24]), "+f"(d[25]), "+f"(d[26]), "+f"(d[27]), "+f"(d[28]), "+f"(d[29]), "+f"(d[30]), "+f"(d[31]) : "r"(a0), "r"(a1), "r"(a2), "r"(a3), "l"(desc), "r"(sc));
}
template <> __device__ __forceinline__ void wgmma_rs<56, 0>(float* d, uint32_t a0, uint32_t a1, uint32_t a2, uint32_t a3, uint64_t desc, int sc) {
  asm volatile("{\n.reg .pred p;\nsetp.ne.b32 p, %33, 0;\n"
    "wgmma.mma_async.sync.aligned.m64n56k16.f32.bf16.bf16 {%0,%1,%2,%3,%4,%5,%6,%7,%8,%9,%10,%11,%12,%13,%14,%15,%16,%17,%18,%19,%20,%21,%22,%23,%24,%25,%26,%27}, {%28,%29,%30,%31}, %32, p, 1, 1, 0;\n}"
    : "+f"(d[0]), "+f"(d[1]), "+f"(d[2]), "+f"(d[3]), "+f"(d[4]), "+f"(d[5]), "+f"(d[6]), "+f"(d[7]), "+f"(d[8]), "+f"(d[9]), "+f"(d[10]), "+f"(d[11]), "+f"(d[12]), "+f"(d[13]), "+f"(d[14]), "+f"(d[15]), "+f"(d[16]), "+f"(d[17]), "+f"(d[18]), "+f"(d[19]), "+f"(d[20]), "+f"(d[21]), "+f"(d[22]), "+f"(d[23]), "+f"(d[24]), "+f"(d[25]), "+f"(d[26]), "+f"(d[27]) : "r"(a0), "r"(a1), "r"(a2), "r"(a3), "l"(desc), "r"(sc));
}
template <> __device__ __forceinline__ void wgmma_rs<48, 0>(float* d, uint32_t a0, uint32_t a1, uint32_t a2, uint32_t a3, uint64_t desc, int sc) {
  asm volatile("{\n.reg .pred p;\nsetp.ne.b32 p, %29, 0;\n"
    "wgmma.mma_async.sync.aligned.m64n48k16.f32.bf16.bf16 {%0,%1,%2,%3,%4,%5,%6,%7,%8,%9,%10,%11,%12,%13,%14,%15,%16,%17,%18,%19,%20,%21,%22,%23}, {%24,%25,%26,%27}, %28, p, 1, 1, 0;\n}"
    : "+f"(d[0]), "+f"(d[1]), "+f"(d[2]), "+f"(d[3]), "+f"(d[4]), "+f"(d[5]), "+f"(d[6]), "+f"(d[7]), "+f"(d[8]), "+f"(d[9]), "+f"(d[10]), "+f"(d[11]), "+f"(d[12]), "+f"(d[13]), "+f"(d[14]), "+f"(d[15]), "+f"(d[16]), "+f"(d[17]), "+f"(d[18]), "+f"(d[19]), "+f"(d[20]), "+f"(d[21]), "+f"(d[22]), "+f"(d[23]) : "r"(a0), "r"(a1), "r"(a2), "r"(a3), "l"(desc), "r"(sc));
}
template <> __device__ __forceinline__ void wgmma_rs<48, 1>(float* d, uint32_t a0, uint32_t a1, uint32_t a2, uint32_t a3, uint64_t desc, int sc) {
  asm volatile("{\n.reg .pred p;\nsetp.ne.b32 p, %29, 0;\n"
    "wgmma.mma_async.sync.aligned.m64n48k16.f32.bf16.bf16 {%0,%1,%2,%3,%4,%5,%6,%7,%8,%9,%10,%11,%12,%13,%14,%15,%16,%17,%18,%19,%20,%21,%22,%23}, {%24,%25,%26,%27}, %28, p, 1, 1, 1;\n}"
    : "+f"(d[0]), "+f"(d[1]), "+f"(d[2]), "+f"(d[3]), "+f"(d[4]), "+f"(d[5]), "+f"(d[6]), "+f"(d[7]), "+f"(d[8]), "+f"(d[9]), "+f"(d[10]), "+f"(d[11]), "+f"(d[12]), "+f"(d[13]), "+f"(d[14]), "+f"(d[15]), "+f"(d[16]), "+f"(d[17]), "+f"(d[18]), "+f"(d[19]), "+f"(d[20]), "+f"(d[21]), "+f"(d[22]), "+f"(d[23]) : "r"(a0), "r"(a1), "r"(a2), "r"(a3), "l"(desc), "r"(sc));
}
template <> __device__ __forceinline__ void wgmma_rs<40, 1>(float* d, uint32_t a0, uint32_t a1, uint32_t a2, uint32_t a3, uint64_t desc, int sc) {
  asm volatile("{\n.reg .pred p;\nsetp.ne.b32 p, %25, 0;\n"
    "wgmma.mma_async.sync.aligned.m64n40k16.f32.bf16.bf16 {%0,%1,%2,%3,%4,%5,%6,%7,%8,%9,%10,%11,%12,%13,%14,%15,%16,%17,%18,%19}, {%20,%21,%22,%23}, %24, p, 1, 1, 1;\n}"
    : "+f"(d[0]), "+f"(d[1]), "+f"(d[2]), "+f"(d[3]), "+f"(d[4]), "+f"(d[5]), "+f"(d[6]), "+f"(d[7]), "+f"(d[8]), "+f"(d[9]), "+f"(d[10]), "+f"(d[11]), "+f"(d[12]), "+f"(d[13]), "+f"(d[14]), "+f"(d[15]), "+f"(d[16]), "+f"(d[17]), "+f"(d[18]), "+f"(d[19]) : "r"(a0), "r"(a1), "r"(a2), "r"(a3), "l"(desc), "r"(sc));
}
template <> __device__ __forceinline__ void wgmma_rs<32, 1>(float* d, uint32_t a0, uint32_t a1, uint32_t a2, uint32_t a3, uint64_t desc, int sc) {
  asm volatile("{\n.reg .pred p;\nsetp.ne.b32 p, %21, 0;\n"
    "wgmma.mma_async.sync.aligned.m64n32k16.f32.bf16.bf16 {%0,%1,%2,%3,%4,%5,%6,%7,%8,%9,%10,%11,%12,%13,%14,%15}, {%16,%17,%18,%19}, %20, p, 1, 1, 1;\n}"
    : "+f"(d[0]), "+f"(d[1]), "+f"(d[2]), "+f"(d[3]), "+f"(d[4]), "+f"(d[5]), "+f"(d[6]), "+f"(d[7]), "+f"(d[8]), "+f"(d[9]), "+f"(d[10]), "+f"(d[11]), "+f"(d[12]), "+f"(d[13]), "+f"(d[14]), "+f"(d[15]) : "r"(a0), "r"(a1), "r"(a2), "r"(a3), "l"(desc), "r"(sc));
}
template <> __device__ __forceinline__ void wgmma_rs<16, 1>(float* d, uint32_t a0, uint32_t a1, uint32_t a2, uint32_t a3, uint64_t desc, int sc) {
  asm volatile("{\n.reg .pred p;\nsetp.ne.b32 p, %13, 0;\n"
    "wgmma.mma_async.sync.aligned.m64n16k16.f32.bf16.bf16 {%0,%1,%2,%3,%4,%5,%6,%7}, {%8,%9,%10,%11}, %12, p, 1, 1, 1;\n}"
    : "+f"(d[0]), "+f"(d[1]), "+f"(d[2]), "+f"(d[3]), "+f"(d[4]), "+f"(d[5]), "+f"(d[6]), "+f"(d[7]) : "r"(a0), "r"(a1), "r"(a2), "r"(a3), "l"(desc), "r"(sc));
}

__device__ __forceinline__ uint32_t pack_bf16(float lo, float hi) {
  uint32_t r; asm("cvt.rn.bf16x2.f32 %0, %1, %2;" : "=r"(r) : "f"(hi), "f"(lo)); return r;
}
__device__ __forceinline__ float bf_lo(uint32_t v) { return __uint_as_float(v << 16); }
__device__ __forceinline__ float bf_hi(uint32_t v) { return __uint_as_float(v & 0xffff0000u); }
__device__ __forceinline__ float bf_round(float x) { return bf_lo(pack_bf16(x, 0.f)); }
__device__ __forceinline__ uint32_t hmul2(uint32_t a, uint32_t b) { uint32_t r; asm("mul.rn.bf16x2 %0, %1, %2;" : "=r"(r) : "r"(a), "r"(b)); return r; }
__device__ __forceinline__ uint32_t hadd2(uint32_t a, uint32_t b) { uint32_t r; asm("add.rn.bf16x2 %0, %1, %2;" : "=r"(r) : "r"(a), "r"(b)); return r; }
__device__ __forceinline__ uint32_t hsub2(uint32_t a, uint32_t b) { uint32_t r; asm("sub.rn.bf16x2 %0, %1, %2;" : "=r"(r) : "r"(a), "r"(b)); return r; }
__device__ __forceinline__ uint32_t hfma2(uint32_t a, uint32_t b, uint32_t c) { uint32_t r; asm("fma.rn.bf16x2 %0, %1, %2, %3;" : "=r"(r) : "r"(a), "r"(b), "r"(c)); return r; }

__device__ __forceinline__ void sts16(uint32_t a, uint32_t v) { asm volatile("st.shared.b16 [%0], %1;" ::"r"(a), "h"((unsigned short)v) : "memory"); }
__device__ __forceinline__ void sts32(uint32_t a, uint32_t v) { asm volatile("st.shared.b32 [%0], %1;" ::"r"(a), "r"(v) : "memory"); }
__device__ __forceinline__ void sts64(uint32_t a, uint32_t x, uint32_t y) { asm volatile("st.shared.v2.b32 [%0], {%1,%2};" ::"r"(a), "r"(x), "r"(y) : "memory"); }
__device__ __forceinline__ void sts128(uint32_t a, uint32_t x, uint32_t y, uint32_t z, uint32_t w) {
  asm volatile("st.shared.v4.b32 [%0], {%1,%2,%3,%4};" ::"r"(a), "r"(x), "r"(y), "r"(z), "r"(w) : "memory");
}
__device__ __forceinline__ uint32_t lds32(uint32_t a) { uint32_t v; asm volatile("ld.shared.b32 %0, [%1];" : "=r"(v) : "r"(a) : "memory"); return v; }
__device__ __forceinline__ uint2 lds64(uint32_t a) { uint2 v; asm volatile("ld.shared.v2.b32 {%0,%1}, [%2];" : "=r"(v.x), "=r"(v.y) : "r"(a) : "memory"); return v; }
__device__ __forceinline__ uint4 lds128(uint32_t a) {
  uint4 v; asm volatile("ld.shared.v4.b32 {%0,%1,%2,%3}, [%4];" : "=r"(v.x), "=r"(v.y), "=r"(v.z), "=r"(v.w) : "r"(a) : "memory"); return v;
}
__device__ __forceinline__ void ldsm4(uint32_t a, uint32_t& r0, uint32_t& r1, uint32_t& r2, uint32_t& r3) {
  asm volatile("ldmatrix.sync.aligned.m8n8.x4.shared.b16 {%0,%1,%2,%3}, [%4];" : "=r"(r0), "=r"(r1), "=r"(r2), "=r"(r3) : "r"(a) : "memory");
}
__device__ __forceinline__ void ldsm4t(uint32_t a, uint32_t& r0, uint32_t& r1, uint32_t& r2, uint32_t& r3) {
  asm volatile("ldmatrix.sync.aligned.m8n8.x4.trans.shared.b16 {%0,%1,%2,%3}, [%4];" : "=r"(r0), "=r"(r1), "=r"(r2), "=r"(r3) : "r"(a) : "memory");
}
__device__ __forceinline__ void stsm4(uint32_t a, uint32_t r0, uint32_t r1, uint32_t r2, uint32_t r3) {
  asm volatile("stmatrix.sync.aligned.m8n8.x4.shared.b16 [%0], {%1,%2,%3,%4};" ::"r"(a), "r"(r0), "r"(r1), "r"(r2), "r"(r3) : "memory");
}
__device__ __forceinline__ void stsm4t(uint32_t a, uint32_t r0, uint32_t r1, uint32_t r2, uint32_t r3) {
  asm volatile("stmatrix.sync.aligned.m8n8.x4.trans.shared.b16 [%0], {%1,%2,%3,%4};" ::"r"(a), "r"(r0), "r"(r1), "r"(r2), "r"(r3) : "memory");
}
__device__ __forceinline__ void mma16816(float* c, uint32_t a0, uint32_t a1, uint32_t a2, uint32_t a3, uint32_t b0, uint32_t b1) {
  asm("mma.sync.aligned.m16n8k16.row.col.f32.bf16.bf16.f32 {%0,%1,%2,%3}, {%4,%5,%6,%7}, {%8,%9}, {%0,%1,%2,%3};"
      : "+f"(c[0]), "+f"(c[1]), "+f"(c[2]), "+f"(c[3]) : "r"(a0), "r"(a1), "r"(a2), "r"(a3), "r"(b0), "r"(b1));
}
__device__ __forceinline__ void bar_sync(int id, int n) { asm volatile("bar.sync %0, %1;" ::"r"(id), "r"(n) : "memory"); }
__device__ __forceinline__ void bar_arrive(int id, int n) { asm volatile("bar.arrive %0, %1;" ::"r"(id), "r"(n) : "memory"); }
__device__ __forceinline__ void wg_fence() { asm volatile("wgmma.fence.sync.aligned;" ::: "memory"); }
__device__ __forceinline__ void wg_commit() { asm volatile("wgmma.commit_group.sync.aligned;" ::: "memory"); }
__device__ __forceinline__ void wg_wait0() { asm volatile("wgmma.wait_group.sync.aligned 0;" ::: "memory"); }
__device__ __forceinline__ void fence_async() { asm volatile("fence.proxy.async.shared::cta;" ::: "memory"); }
__device__ __forceinline__ uint64_t mkdesc(uint32_t addr, uint32_t lbo, uint32_t sbo) {
  return (uint64_t)((addr & 0x3FFFF) >> 4) | ((uint64_t)(lbo >> 4) << 16) | ((uint64_t)(sbo >> 4) << 32);
}
__device__ __forceinline__ uint32_t mapa(uint32_t a, uint32_t rank) {
  uint32_t r; asm("mapa.shared::cluster.u32 %0, %1, %2;" : "=r"(r) : "r"(a), "r"(rank)); return r;
}
__device__ __forceinline__ void mbar_init_expect(uint32_t bar, uint32_t bytes) {
  asm volatile("mbarrier.init.shared::cta.b64 [%0], 1;" ::"r"(bar) : "memory");
  asm volatile("mbarrier.arrive.expect_tx.shared::cta.b64 _, [%0], %1;" ::"r"(bar), "r"(bytes) : "memory");
}
__device__ __forceinline__ void mbar_wait(uint32_t bar) {
#pragma unroll 1
  for (int it = 0; it < (1 << 22); it++) {
    uint32_t ok;
    asm volatile("{\n.reg .pred p;\nmbarrier.try_wait.parity.acquire.cluster.shared::cta.b64 p, [%1], 0;\nselp.u32 %0, 1, 0, p;\n}"
                 : "=r"(ok) : "r"(bar) : "memory");
    if (ok) return;
  }
  __trap();
}
__device__ __forceinline__ void st_async4(uint32_t a, uint32_t bar, uint32_t x, uint32_t y, uint32_t z, uint32_t w) {
  asm volatile("st.async.weak.shared::cluster.mbarrier::complete_tx::bytes.v4.b32 [%0], {%2,%3,%4,%5}, [%1];"
               ::"r"(a), "r"(bar), "r"(x), "r"(y), "r"(z), "r"(w) : "memory");
}

struct cf { float re, im; };
__device__ __forceinline__ cf cmul(cf a, cf b) { return {fmaf(a.re, b.re, -a.im * b.im), fmaf(a.re, b.im, a.im * b.re)}; }
__device__ __forceinline__ cf csq(cf a) { return {fmaf(a.re, a.re, -a.im * a.im), (a.re + a.re) * a.im}; }
__device__ __forceinline__ cf cexp_p(float xl, float y, float p) {
  float mag; asm("ex2.approx.ftz.f32 %0, %1;" : "=f"(mag) : "f"(xl * p));
  const float th = y * p;
  const float k = rintf(th * 0.15915494309189535f);
  float r = fmaf(k, -6.2831854820251465f, th);
  r = fmaf(k, 1.7484555314695172e-07f, r);
  return {mag * __cosf(r), mag * __sinf(r)};
}
__device__ __forceinline__ uint32_t ysw(int c) { return (uint32_t)(c ^ ((c >> 3) & 3)) * 16u; }

#define CMUL2(OR, OI, xr, xi, yr, yi, nyi) do { OR = hfma2(xr, yr, hmul2(xi, nyi)); OI = hfma2(xr, yi, hmul2(xi, yr)); } while (0)

__device__ __forceinline__ uint32_t gate_slow(const __nv_bfloat16* u, const __nv_bfloat16* gw, int row) {
  float s = 0.f;
  const uint32_t* xr = (const uint32_t*)(u + (size_t)row * D);
  const uint32_t* wr = (const uint32_t*)gw;
#pragma unroll 1
  for (int j = 0; j < D / 2; j++) { const uint32_t pr = hmul2(xr[j], wr[j]); s += bf_lo(pr); s += bf_hi(pr); }
  s = bf_round(s);
  return pack_bf16(1.f / (1.f + expf(-s)), 0.f);
}

__device__ __forceinline__ void prefix6(float* pf, uint32_t ub, int c0) {
  pf[0] = 0.f;
#pragma unroll
  for (int j = 0; j < 6; j++) {
    const int c = c0 + j;
    const uint4 v = lds128(ub + (c & 3) * U_CS + (63 - (c >> 2)) * 16);
    const uint32_t w[4] = {v.x, v.y, v.z, v.w};
#pragma unroll
    for (int i = 0; i < 4; i++) {
      pf[j * 8 + 2 * i + 1] = pf[j * 8 + 2 * i] + bf_lo(w[i]);
      pf[j * 8 + 2 * i + 2] = pf[j * 8 + 2 * i + 1] + bf_hi(w[i]);
    }
  }
}
template <int A, int B>
__device__ __forceinline__ void put_win(const float* pf, int ix, uint32_t addr) {
  uint32_t a[4];
#pragma unroll
  for (int i = 0; i < 4; i++) a[i] = pack_bf16(pf[ix + 2 * i - B + 1] - pf[ix + 2 * i - A], pf[ix + 2 * i - B + 2] - pf[ix + 2 * i - A + 1]);
  sts128(addr, a[0], a[1], a[2], a[3]);
}

__device__ __forceinline__ uint2 gate_ld(int x) {
  uint2 gv;
  asm volatile("ld.relaxed.gpu.global.v2.u32 {%0,%1}, [%2];" : "=r"(gv.x), "=r"(gv.y) : "l"(g_gate + x * 2) : "memory");
  return gv;
}
__device__ __noinline__ uint32_t gate_poll(const __nv_bfloat16* u, const __nv_bfloat16* gw, int x, uint32_t tag) {
  uint2 gv;
#pragma unroll 1
  for (int spins = 0; spins < (1 << 16); spins++) {
    gv = gate_ld(x);
    if ((gv.x >> 16) == tag && (gv.y >> 16) == tag) return __byte_perm(gv.x, gv.y, 0x5410);
  }
  return __byte_perm(gate_slow(u, gw, x * 2), gate_slow(u, gw, x * 2 + 1), 0x5410);
}
__device__ __forceinline__ uint32_t gate_fin(const Params& p, uint2 gv, int x, uint32_t tag) {
  if ((gv.x >> 16) == tag && (gv.y >> 16) == tag) return __byte_perm(gv.x, gv.y, 0x5410);
  return gate_poll(p.u, p.gw, x, tag);
}

__device__ __noinline__ void final_box(uint32_t sb, const CUtensorMap* tm_out, int lvl, int box, int wtid, uint32_t rank, int oc0,
                                       uint32_t g2, uint2 dA, uint2 dB, int barid) {
  const int x = box * 128 + wtid;
  const uint32_t h2 = hsub2(0x3f803f80u, g2);
  const int c = x >> 2;
  const uint32_t ho = sb + CH_OFF + (x & 3) * 4;
  const uint32_t y0 = ho + Y0_OFF + ysw(c), y2 = ho + Y2_OFF + ysw(c - 64), y3 = ho + Y3_OFF + ysw(c - 128);
  const uint32_t s2 = ho + S2_OFF + ((c - 128) + ((c - 128) >> 3)) * 16, uo = ho + U_OFF + (c & 3) * U_CS + (63 - (c >> 2)) * 16;
  uint32_t o[4], a[4], b[4], uu[4];
#pragma unroll
  for (int k = 0; k < 4; k++) { a[k] = lds32(y0 + k * CH_BYTES); b[k] = lds32(y0 + k * CH_BYTES + 4096); uu[k] = lds32(uo + k * CH_BYTES); }
  if (lvl) {
    uint32_t a2[4], b2[4];
#pragma unroll
    for (int k = 0; k < 4; k++) { a2[k] = lds32(y2 + k * CH_BYTES); b2[k] = lds32(y2 + k * CH_BYTES + 3072); }
    if (lvl == 2) {
      uint32_t a3[4], b3[4], s[4];
#pragma unroll
      for (int k = 0; k < 4; k++) { a3[k] = lds32(y3 + k * CH_BYTES); b3[k] = lds32(y3 + k * CH_BYTES + 2048); s[k] = lds32(s2 + k * CH_BYTES); }
      const uint4 k0 = lds128(sb + K1024_OFF), k1 = lds128(sb + K1024_OFF + 16);
      const uint32_t kk[8] = {k0.x, k0.y, k0.z, k0.w, k1.x, k1.y, k1.z, k1.w};
#pragma unroll
      for (int k = 0; k < 4; k++) {
        a2[k] = hadd2(a2[k], hfma2(kk[2 * k], s[k], a3[k]));
        b2[k] = hadd2(b2[k], hfma2(kk[2 * k + 1], s[k], b3[k]));
      }
    }
#pragma unroll
    for (int k = 0; k < 4; k++) { a[k] = hadd2(a[k], a2[k]); b[k] = hadd2(b[k], b2[k]); }
  }
#pragma unroll
  for (int k = 0; k < 4; k++) {
    const uint32_t da2 = __byte_perm((k & 2) ? dA.y : dA.x, 0, (k & 1) ? 0x3232 : 0x1010);
    const uint32_t db2 = __byte_perm((k & 2) ? dB.y : dB.x, 0, (k & 1) ? 0x3232 : 0x1010);
    o[k] = hadd2(hmul2(g2, hadd2(a[k], hmul2(uu[k], da2))), hmul2(h2, hadd2(b[k], hmul2(uu[k], db2))));
  }
  const uint32_t r00 = __byte_perm(o[0], o[1], 0x5410), r01 = __byte_perm(o[2], o[3], 0x5410);
  const uint32_t r10 = __byte_perm(o[0], o[1], 0x7632), r11 = __byte_perm(o[2], o[3], 0x7632);
  const int slot = box >> 1;
  const uint32_t xin = sb + XIN_OFF + slot * 2048 + wtid * 16, xbar = sb + B_X + slot * 8;
  if ((uint32_t)(box & 1) != rank) {
    st_async4(mapa(xin, rank ^ 1), mapa(xbar, rank ^ 1), r00, r01, r10, r11);
  } else {
    mbar_wait(xbar);
    const uint4 q = lds128(xin);
    const uint32_t st = sb + RAW_OFF + slot * 4096 + wtid * 16;
    if (rank == 0) { sts128(st, r00, r01, q.x, q.y); sts128(st + 2048, r10, r11, q.z, q.w); }
    else { sts128(st, q.x, q.y, r00, r01); sts128(st + 2048, q.z, q.w, r10, r11); }
    fence_async();
    bar_sync(barid, 128);
    if (wtid == 0) {
      asm volatile("cp.async.bulk.tensor.3d.global.shared::cta.bulk_group [%0, {%2, %3, %4}], [%1];"
                   ::"l"(tm_out), "r"(sb + RAW_OFF + slot * 4096), "r"(oc0), "r"(box * 128), "r"(0) : "memory");
      asm volatile("cp.async.bulk.commit_group;" ::: "memory");
    }
  }
}

__device__ __forceinline__ void window_sums(uint32_t cb, int wq, int lane) {
      float pf[49];
      if (wq == 0 || wq == 3) {
        if (wq == 0 || lane < 16) {
          const int nu = wq ? 32 + lane : lane;
          prefix6(pf, cb + U_OFF, 4 * nu - 2);
          const uint32_t po = (5 - (nu >> 3)) * 576 + ((nu & 7) >> 1) * 144 + (nu & 1) * 64;
#pragma unroll
          for (int k = 0; k < 4; k++) { put_win<10, 6>(pf, 16 + 8 * k, cb + W5_OFF + po + k * 16); put_win<5, 3>(pf, 16 + 8 * k, cb + W3_OFF + po + k * 16); }
        }
      } else {
        const uint32_t po = (1 - (lane >> 4)) * 1152 + ((lane & 15) >> 2) * 144 + (lane & 3) * 32;
        if (wq == 1) {
          prefix6(pf, cb + U_OFF, 4 * lane - 3);
#pragma unroll
          for (int k = 0; k < 4; k++) put_win<20, 12>(pf, 24 + 8 * k, cb + W9_OFF + po + (k & 1) * 576 + (k >> 1) * 16);
        } else {
          prefix6(pf, cb + U_OFF, 4 * lane - 2);
          const uint32_t so = cb + S2_OFF + (lane >> 1) * 144 + (lane & 1) * 64;
#pragma unroll
          for (int k = 0; k < 4; k++) { put_win<11, 5>(pf, 16 + 8 * k, cb + W7_OFF + po + (k & 1) * 576 + (k >> 1) * 16); put_win<4, 3>(pf, 16 + 8 * k, so + k * 16); }
        }
      }
}

__global__ void __cluster_dims__(2, 1, 1) __launch_bounds__(640, 1)
ssm_kernel(const Params p, const __grid_constant__ CUtensorMap tm_in, const __grid_constant__ CUtensorMap tm_out) {
  extern __shared__ __align__(1024) unsigned char smem_raw[];
  const uint32_t sb = (uint32_t)__cvta_generic_to_shared(smem_raw);
  const int tid = threadIdx.x, lane = tid & 31;
  const int warp = __shfl_sync(0xffffffffu, tid >> 5, 0);
  const int ch = warp >> 2, wq = warp & 3, br = wq >> 1, hf = wq & 1;
  const int g = lane >> 2, t = lane & 3;
  const int d = blockIdx.x * 4 + ch;
  const uint32_t rank = blockIdx.x & 1;
  const uint32_t cb = sb + CH_OFF + ch * CH_BYTES;
  const int wtid = tid & 127;
  const int oc0 = (int)(blockIdx.x >> 1) * 8;
  STAMP(0); GT(0);

  if (warp >= 16) {
    if (wtid == 0) {
      mbar_init_expect(sb + B_RAW, 32768);
#pragma unroll
      for (int i = 0; i < 4; i++) mbar_init_expect(sb + B_X + 8 * i, 2048);
      asm volatile("mbarrier.init.shared::cta.b64 [%0], 128;" ::"r"(sb + B_U) : "memory");
      asm volatile("mbarrier.init.shared::cta.b64 [%0], 128;" ::"r"(sb + B_W) : "memory");
      asm volatile("fence.mbarrier_init.release.cluster;" ::: "memory");
      asm volatile("fence.proxy.async.shared::cta;" ::: "memory");
    }
    __syncwarp();
    asm volatile("barrier.cluster.arrive.relaxed.aligned;" ::: "memory");
    unsigned int epoch;
    asm volatile("ld.relaxed.gpu.global.u32 %0, [%1];" : "=r"(epoch) : "l"(&g_epoch) : "memory");
    const uint2 dA = *(const uint2*)(p.A_D + blockIdx.x * 4), dB = *(const uint2*)(p.B_D + blockIdx.x * 4);
    const uint4 gw0 = *(const uint4*)(p.gw + lane * 8), gw1 = *(const uint4*)(p.gw + 256 + lane * 8);
    asm volatile("barrier.cluster.wait.aligned;" ::: "memory");
    if (wtid == 0) {
      asm volatile("cp.async.bulk.tensor.5d.shared::cluster.global.mbarrier::complete_tx::bytes.multicast::cluster [%0], [%1, {%3, %4, %4, %4, %5}], [%2], %6;"
                   ::"r"(sb + RAW_OFF + rank * 16384), "l"(&tm_in), "r"(sb + B_RAW), "r"(oc0), "r"(0), "r"((int)rank * 32), "h"((unsigned short)3) : "memory");
    }
    sts128(sb + CH_OFF + wq * CH_BYTES + U_OFF + (lane >> 3) * U_CS + (64 + (lane & 7)) * 16, 0, 0, 0, 0);
    const uint32_t tag = (epoch + 1) & 0xffffu;
    {
      const int grow = blockIdx.x * 16 + wq * 4;
      uint4 gx[4][2];
#pragma unroll
      for (int i = 0; i < 4; i++) {
        gx[i][0] = *(const uint4*)(p.u + (size_t)(grow + i) * D + lane * 8);
        gx[i][1] = *(const uint4*)(p.u + (size_t)(grow + i) * D + 256 + lane * 8);
      }
      const uint32_t ws[8] = {gw0.x, gw0.y, gw0.z, gw0.w, gw1.x, gw1.y, gw1.z, gw1.w};
      float sm[4];
#pragma unroll
      for (int i = 0; i < 4; i++) {
        const uint32_t xs[8] = {gx[i][0].x, gx[i][0].y, gx[i][0].z, gx[i][0].w, gx[i][1].x, gx[i][1].y, gx[i][1].z, gx[i][1].w};
        float s = 0.f;
#pragma unroll
        for (int j = 0; j < 8; j++) { const uint32_t pr = hmul2(xs[j], ws[j]); s += bf_lo(pr); s += bf_hi(pr); }
        sm[i] = s;
      }
      {
        const bool b0 = lane & 1, b1 = lane & 2;
        float u0 = b0 ? sm[1] : sm[0], v0 = b0 ? sm[0] : sm[1], u1 = b0 ? sm[3] : sm[2], v1 = b0 ? sm[2] : sm[3];
        u0 += __shfl_xor_sync(0xffffffffu, v0, 1); u1 += __shfl_xor_sync(0xffffffffu, v1, 1);
        float s = b1 ? u1 : u0; const float v = b1 ? u0 : u1;
        s += __shfl_xor_sync(0xffffffffu, v, 2);
#pragma unroll
        for (int o = 4; o < 32; o <<= 1) s += __shfl_xor_sync(0xffffffffu, s, o);
        s = bf_round(s);
        const float gv = 1.f / (1.f + expf(-s));
        const uint32_t w = (tag << 16) | (pack_bf16(gv, 0.f) & 0xffffu);
        if (lane < 4) asm volatile("st.relaxed.gpu.global.u32 [%0], %1;" ::"l"(&g_gate[grow + lane]), "r"(w) : "memory");
      }
    }
    STAMP(3);
    mbar_wait(sb + B_RAW);
    STAMP(4);
    {
      const uint32_t dst = sb + CH_OFF + (g & 3) * CH_BYTES + U_OFF + t * U_CS + (63 - wq * 16) * 16;
#pragma unroll
      for (int h = 0; h < 2; h++) {
        uint32_t r[8][4];
#pragma unroll
        for (int i = 0; i < 8; i++) ldsm4t(sb + RAW_OFF + (wq * 16 + h * 8 + i) * 512 + lane * 16, r[i][0], r[i][1], r[i][2], r[i][3]);
        if ((uint32_t)(g >> 2) == rank) {
#pragma unroll
          for (int i = 0; i < 8; i++) sts128(dst - (h * 8 + i) * 16, r[i][0], r[i][1], r[i][2], r[i][3]);
        }
      }
    }
    fence_async();
    asm volatile("mbarrier.arrive.shared::cta.b64 _, [%0];" ::"r"(sb + B_U) : "memory");
    bar_sync(5, 128);
    STAMP(5);
#pragma unroll 1
    for (int k = 0; k < 4; k++) window_sums(sb + CH_OFF + k * CH_BYTES, wq, lane);
    fence_async();
    asm volatile("mbarrier.arrive.shared::cta.b64 _, [%0];" ::"r"(sb + B_W) : "memory");
    STAMP(7);
    STAMP(8);
    unsigned int ticket = 0;
    uint32_t gg[4];
    {
      uint2 gl[4];
#pragma unroll
      for (int i = 0; i < 4; i++) gl[i] = gate_ld((i ^ (int)rank ^ 1) * 128 + wtid);
#pragma unroll
      for (int i = 0; i < 4; i++) gg[i] = gate_fin(p, gl[i], (i ^ (int)rank ^ 1) * 128 + wtid, tag);
    }
#pragma unroll 1
    for (int lvl = 0; lvl < 2; lvl++) {
      const int bs = 2 * lvl + (int)(rank ^ 1), bm = 2 * lvl + (int)rank;
      const uint32_t gs = lvl ? gg[2] : gg[0], gm = lvl ? gg[3] : gg[1];
      bar_sync(8 + lvl, 640);
      STAMP(10 + lvl);
      if (lvl == 0 && wtid == 0) ticket = atomicAdd(&g_ticket, 1u);
      final_box(sb, &tm_out, lvl, bs, wtid, rank, oc0, gs, dA, dB, 5);
      final_box(sb, &tm_out, lvl, bm, wtid, rank, oc0, gm, dA, dB, 5);
      STAMP(12 + lvl);
    }
    if (wtid == 0) {
      if (ticket == NCTA - 1) { g_ticket = 0; g_epoch = epoch + 1; }
      asm volatile("cp.async.bulk.wait_group.read 0;" ::: "memory");
    }
    STAMP(15);
    return;
  }
  asm volatile("barrier.cluster.arrive.relaxed.aligned;" ::: "memory");

  const int moff = d * NM + hf * 64 + lane * 2;
  const uint32_t q0 = *(const uint32_t*)((br ? p.B_lA : p.A_re) + moff), q1 = *(const uint32_t*)((br ? p.B_Aim : p.A_im) + moff);
  const uint32_t q2 = *(const uint32_t*)((br ? p.B_Cre : p.C_re) + moff), q3 = *(const uint32_t*)((br ? p.B_Cim : p.C_im) + moff);
  const uint32_t q4 = *(const uint32_t*)((br ? p.B_Cre : p.B_re) + moff), q5 = *(const uint32_t*)((br ? p.B_Cim : p.B_im) + moff);
  const uint2 ldt4 = *(const uint2*)((br ? p.B_ldt : p.A_ldt) + blockIdx.x * 4);
  unsigned int epoch;
  asm volatile("ld.relaxed.gpu.global.u32 %0, [%1];" : "=r"(epoch) : "l"(&g_epoch) : "memory");

  for (int i = wtid & 63; i < R_BR / 16; i += 64) sts128(cb + R_OFF + br * R_BR + i * 16, 0, 0, 0, 0);
  STAMP(1);

  float acc[5][4];
  float k2048 = 0.f;
  const uint32_t scr = cb + Y0_OFF + wq * SCR_BYTES;
  const uint32_t scr2 = sb + XIN_OFF + warp * 640;
  {
    const uint32_t ldt2 = (ch & 2) ? ldt4.y : ldt4.x;
    const float dt = bf_round(expf((ch & 1) ? bf_hi(ldt2) : bf_lo(ldt2)));
#pragma unroll
    for (int i = 0; i < 5; i++) acc[i][0] = acc[i][1] = acc[i][2] = acc[i][3] = 0.f;
    cf cc[2], zz1[2], zz128[2];
#pragma unroll
    for (int r = 0; r < 2; r++) {
      float v0 = r ? bf_hi(q0) : bf_lo(q0), v1 = r ? bf_hi(q1) : bf_lo(q1), v2 = r ? bf_hi(q2) : bf_lo(q2);
      float v3 = r ? bf_hi(q3) : bf_lo(q3), v4 = r ? bf_hi(q4) : bf_lo(q4), v5 = r ? bf_hi(q5) : bf_lo(q5);
      if (br == 0) { cc[r] = cmul(cf{v2, v3}, cf{dt * v4, dt * v5}); }
      else { v0 = -bf_round(expf(v0)); cc[r] = cf{2.f * dt * v2, 2.f * dt * v3}; }
      const float xl = (dt * v0) * 1.4426950408889634f, y = dt * v1;
      zz1[r] = cexp_p(xl, y, 1.f); zz128[r] = cexp_p(xl, y, 128.f);
    }
    STAMP(2);
    const uint32_t tb = scr + lane * 16;
    const uint32_t ta = scr + (lane >> 3) * 512 + (lane & 7) * 16;
    const uint32_t tc = ((lane & 8) ? scr2 : scr + 4096) + (lane >> 4) * 128 + (lane & 7) * 16;
    const uint32_t tm = scr2 + 512 + ((lane >> 3) & 1) * 64 + (lane >> 4) * 16;
#pragma unroll 1
    for (int r = 0; r < 2; r++) {
      const cf c = r ? cc[1] : cc[0], z1 = r ? zz1[1] : zz1[0], z128 = r ? zz128[1] : zz128[0];
      const cf z2 = csq(z1), z4 = csq(z2), z8 = csq(z4);
      const cf z16 = csq(z8), z24 = cmul(z16, z8), z32 = csq(z16), z40 = cmul(z32, z8), z48 = csq(z24), z56 = cmul(z32, z24), z64 = csq(z32);
      const cf z256 = csq(z128), z512 = csq(z256), z1024 = csq(z512), z2048 = csq(z1024);
      k2048 += fmaf(c.re, z2048.re, -c.im * z2048.im);
      __syncwarp();
      {
        uint32_t xr[4] = {pack_bf16(1.f, z8.re), pack_bf16(z16.re, z24.re), pack_bf16(z32.re, z40.re), pack_bf16(z48.re, z56.re)};
        uint32_t xi[4] = {pack_bf16(0.f, -z8.im), pack_bf16(-z16.im, -z24.im), pack_bf16(-z32.im, -z40.im), pack_bf16(-z48.im, -z56.im)};
        sts128(tb + 0 * 512, xr[0], xr[1], xr[2], xr[3]);
        sts128(tb + 2 * 512, xi[0], xi[1], xi[2], xi[3]);
        const uint32_t yr = pack_bf16(z64.re, z64.re), nyi = pack_bf16(z64.im, z64.im), yi = nyi ^ 0x80008000u;
        uint32_t o[4], q[4];
#pragma unroll
        for (int i = 0; i < 4; i++) CMUL2(o[i], q[i], xr[i], xi[i], yr, yi, nyi);
        sts128(tb + 1 * 512, o[0], o[1], o[2], o[3]);
        sts128(tb + 3 * 512, q[0], q[1], q[2], q[3]);
      }
      {
        const cf h1 = cmul(c, z128), h2 = cmul(c, z256), h3 = cmul(h1, z256), h4 = cmul(c, z512), h5 = cmul(h1, z512), h6 = cmul(h2, z512), h7 = cmul(h3, z512);
        const cf e1 = cmul(c, z1), e2 = cmul(c, z2), e3 = cmul(e1, z2), e129 = cmul(h1, z1), e130 = cmul(h1, z2), e131 = cmul(e129, z2);
        const cf e258 = cmul(h2, z2), e386 = cmul(h3, z2);
        const uint32_t pr0 = pack_bf16(c.re, e1.re), pr2 = pack_bf16(h1.re, e129.re), pi0 = pack_bf16(c.im, e1.im), pi2 = pack_bf16(h1.im, e129.im);
        sts128(tb + 4 * 512, pr0, pack_bf16(e2.re, e3.re), pr2, pack_bf16(e130.re, e131.re));
        sts128(tb + 5 * 512, pi0, pack_bf16(e2.im, e3.im), pi2, pack_bf16(e130.im, e131.im));
        uint32_t xr[4] = {pack_bf16(h2.re, e258.re), pack_bf16(h3.re, e386.re), pack_bf16(h4.re, h5.re), pack_bf16(h6.re, h7.re)};
        uint32_t xi[4] = {pack_bf16(h2.im, e258.im), pack_bf16(h3.im, e386.im), pack_bf16(h4.im, h5.im), pack_bf16(h6.im, h7.im)};
        sts128(tb + 6 * 512, xr[0], xr[1], xr[2], xr[3]);
        sts128(tb + 7 * 512, xi[0], xi[1], xi[2], xi[3]);
        xr[1] = __byte_perm(xr[0], xr[1], 0x5410); xi[1] = __byte_perm(xi[0], xi[1], 0x5410);
        xr[0] = __byte_perm(pr0, pr2, 0x5410); xi[0] = __byte_perm(pi0, pi2, 0x5410);
        const uint32_t yr = pack_bf16(z1024.re, z1024.re), yi = pack_bf16(z1024.im, z1024.im), nyi = yi ^ 0x80008000u;
        uint32_t o[4], q[4];
#pragma unroll
        for (int i = 0; i < 4; i++) CMUL2(o[i], q[i], xr[i], xi[i], yr, yi, nyi);
        sts128(tb + 8 * 512, o[0], o[1], o[2], o[3]);
        sts128(scr2 + lane * 16, q[0], q[1], q[2], q[3]);
        const uint32_t m4 = pack_bf16(z4.re, z4.im);
        sts16(scr2 + 512 + lane * 2, m4); sts16(scr2 + 576 + lane * 2, m4 >> 16);
      }
      __syncwarp();
#pragma unroll
      for (int kp = 0; kp < 2; kp++) {
        uint32_t rr[2], ri[2], yr[2], yi[2];
        ldsm4t(tc + kp * 256, rr[0], ri[0], rr[1], ri[1]);
        ldsm4(tm + kp * 32, yr[0], yi[0], yr[1], yi[1]);
#pragma unroll
        for (int k2 = 0; k2 < 2; k2++) {
          const int kk = kp * 2 + k2;
          uint32_t a0, a1, a2, a3, pr, pi, qr, qi, xr, xi;
          ldsm4t(ta + kk * 128, a0, a1, a2, a3);
          ldsm4t(ta + 2048 + kk * 128, pr, pi, qr, qi);
          const uint32_t nyi = yi[k2] ^ 0x80008000u;
          mma16816(acc[0], a0, a1, a2, a3, pr, pi);
          mma16816(acc[2], a0, a1, a2, a3, qr, qi);
          mma16816(acc[4], a0, a1, a2, a3, rr[k2], ri[k2]);
          CMUL2(xr, xi, pr, pi, yr[k2], yi[k2], nyi);
          mma16816(acc[1], a0, a1, a2, a3, xr, xi);
          CMUL2(xr, xi, qr, qi, yr[k2], yi[k2], nyi);
          mma16816(acc[3], a0, a1, a2, a3, xr, xi);
        }
      }
    }
#pragma unroll
    for (int o = 16; o; o >>= 1) k2048 += __shfl_xor_sync(0xffffffffu, k2048, o);
  }
  STAMP(3);
  __syncwarp();
  {
    const uint32_t xs = scr + lane * 16;
#define OTH(i, k) __float_as_uint(hf ? acc[i][k] : acc[i][2 + (k)])
    sts128(xs, OTH(0, 0), OTH(0, 1), OTH(1, 0), OTH(1, 1));
    sts128(xs + 512, OTH(2, 0), OTH(2, 1), OTH(3, 0), OTH(3, 1));
    sts128(xs + 1024, OTH(4, 0), OTH(4, 1), __float_as_uint(k2048), 0);
#undef OTH
  }

  bar_sync(1 + ch, 128);
  STAMP(4);
  {
    const uint32_t xo = cb + Y0_OFF + (wq ^ 1) * SCR_BYTES + lane * 16;
    const uint4 o0 = lds128(xo), o1 = lds128(xo + 512), o2 = lds128(xo + 1024);
    const uint32_t rb = cb + R_OFF + br * R_BR;
#define OWN(i, k) (hf ? acc[i][2 + (k)] : acc[i][k])
    const uint32_t vP = pack_bf16(OWN(0, 1) + __uint_as_float(o0.y), OWN(0, 0) + __uint_as_float(o0.x));
    const uint32_t vP4 = pack_bf16(OWN(1, 1) + __uint_as_float(o0.w), OWN(1, 0) + __uint_as_float(o0.z));
    const uint32_t vQ = pack_bf16(OWN(2, 1) + __uint_as_float(o1.y), OWN(2, 0) + __uint_as_float(o1.x));
    const uint32_t vQ4 = pack_bf16(OWN(3, 1) + __uint_as_float(o1.w), OWN(3, 0) + __uint_as_float(o1.z));
    const uint32_t vR = pack_bf16(OWN(4, 1) + __uint_as_float(o2.y), OWN(4, 0) + __uint_as_float(o2.x));
#undef OWN
    const int j = g + 8 * hf;
    {
      const int a = 2 * (t & 1) + 64 * (t & 2) + 8 * j;
      const uint32_t ad = rb + 2 * (RD_X0 - 1 - a);
      const uint32_t a1 = (t & 2) ? ad - 8 : ad, a2 = (t & 2) ? ad : ad - 8;
      const uint32_t w1 = (t & 2) ? vP4 : vP, w2 = (t & 2) ? vP : vP4;
      sts32(a1, w1); sts32(a2, w2);
      sts16(a1 + RD_CS + 2, w1); sts16(a1 + RD_CS + 4, w1 >> 16);
      sts16(a2 + RD_CS + 2, w2); sts16(a2 + RD_CS + 4, w2 >> 16);
    }
    if (t < 2) {
      const int b = 256 + 128 * t + 8 * j;
      const uint32_t ad = rb + 2 * (RD_X0 - 6 - b);
      const uint32_t v22 = __byte_perm(vQ4, 0, 0x3232), v00 = __byte_perm(vQ, 0, 0x3232);
      sts16(ad, vQ4);
      sts64(ad + 2, v22, __byte_perm(vQ4, vQ, 0x5432));
      sts32(ad + 10, v00);
      if (b != 256) { sts16(ad + 14, v00); sts128(ad + RD_CS + 2, vQ4, v22, vQ, v00); }
      else { sts64(ad + RD_CS + 2, vQ4, v22); sts32(ad + RD_CS + 10, vQ); sts16(ad + RD_CS + 14, v00); }
    } else {
      const uint32_t ao = rb + R_O2 + 2 * (159 - (32 * t + j)), ae = ao - (R_O2 - R_E2) + 2;
      sts16(ao, vQ4 >> 16); sts16(ao + RS_CS + 2, vQ4 >> 16); sts16(ao - 32, vQ4); sts16(ao - 32 + RS_CS + 2, vQ4);
      sts16(ae - 32, vQ); sts16(ae - 32 + RS_CS + 2, vQ);
      if (lane != 2 || hf) { sts16(ae, vQ >> 16); sts16(ae + RS_CS + 2, vQ >> 16); }
      else {
        const uint32_t vv = __byte_perm(vQ, 0, 0x3232), ad = rb + 2 * (RD_X0 - 514);
        sts16(ad, vv); sts32(ad + 2, vv); sts16(ad + 6, vv); sts64(ad + RD_CS + 2, vv, vv);
      }
    }
    {
      const uint32_t a = rb + ((g & 1) ? R_O3 : R_E3 + 2) + 2 * (159 - (64 + 16 * t + (j >> 1)));
      const bool p1024 = (lane == 0) && (hf == 0);
      const uint32_t a00 = p1024 ? rb + R_E2 + 2 * (159 - 127) : a;
      sts16(a00, vR >> 16); sts16(a00 + RS_CS + 2, vR >> 16);
      sts16(a - 16, vR); sts16(a - 16 + RS_CS + 2, vR);
      if (p1024) {
        sts32(sb + K1024_OFF + (ch * 2 + br) * 4, __byte_perm(vR, 0, 0x3232));
        const uint32_t kv = pack_bf16(k2048 + __uint_as_float(o2.z), 0.f);
        sts16(rb + R_E3 + 2 * (159 - 127), kv); sts16(rb + R_E3 + 2 * (159 - 127) + RS_CS + 2, kv);
      }
    }
  }
  STAMP(5);
  const uint32_t tag = (epoch + 1) & 0xffffu;
  asm volatile("barrier.cluster.wait.aligned;" ::: "memory");
  bar_sync(1 + ch, 128);
  mbar_wait(sb + B_U);
  STAMP(6);

  const uint32_t rb = cb + R_OFF + br * R_BR;
  const int eo = 16 * hf + g - 2 * t;
  float dacc[32];
  {
      {
        const int x0 = RD_X0 - (eo + 536);
        const uint32_t fa = rb + ((g & 1) ? 2 * x0 : RD_CS + 2 * x0 + 2);
        const uint64_t ub = mkdesc(cb + U_OFF, U_CS, 128);
        uint32_t f[2][9];
#pragma unroll
        for (int i = 0; i < 9; i++) f[0][i] = lds32(fa + (62 + i) * 16);
#pragma unroll
        for (int j = 0; j < 9; j++) {
          wg_fence();
#pragma unroll
          for (int k = 0; k < 4; k++) {
            const int s = 34 - 4 * j - k;
            if (s >= 0) {
              const int o = 2 * s - 66 + 128;
              const int cc = o & 3, rs = (o >> 2) - 32;
              const int n0 = ((-rs) >> 3) * 8;
              const uint64_t desc = ub + (uint64_t)((cc * U_CS - rs * 16) >> 4);
              const int fi = 2 * (3 - k);
              const uint32_t a1 = f[j & 1][fi], a0 = f[j & 1][fi + 1], a2 = f[j & 1][fi + 2];
              if (n0 == 0) wgmma_rs<64, 0>(dacc, a0, a1, a2, a0, desc, s != 34);
              else if (n0 == 8) wgmma_rs<56, 0>(dacc, a0, a1, a2, a0, desc, 1);
              else wgmma_rs<48, 0>(dacc, a0, a1, a2, a0, desc, 1);
            }
          }
          wg_commit();
          if (j < 8) {
#pragma unroll
            for (int i = 0; i < 9; i++) {
              const int idx = 62 - 8 * (j + 1) + i;
              if (idx >= 0) f[(j + 1) & 1][i] = lds32(fa + idx * 16);
            }
          }
          wg_wait0();
        }
      }
      const uint32_t yb = cb + Y0_OFF + br * 4096;
#pragma unroll
      for (int i = 0; i < 8; i += 2) {
        const int mi = lane >> 3;
        const int cidx = 4 * (63 - 8 * (i + (mi >> 1)) - (lane & 7)) + 2 * hf + (mi & 1);
        stsm4t(yb + ysw(cidx), pack_bf16(dacc[4 * i], dacc[4 * i + 1]), pack_bf16(dacc[4 * i + 2], dacc[4 * i + 3]),
               pack_bf16(dacc[4 * i + 4], dacc[4 * i + 5]), pack_bf16(dacc[4 * i + 6], dacc[4 * i + 7]));
      }
      bar_arrive(8, 640);
      STAMP(8);
  }
  const uint2 dA = *(const uint2*)(p.A_D + blockIdx.x * 4), dB = *(const uint2*)(p.B_D + blockIdx.x * 4);
  const uint2 gl = gate_ld((4 + ch) * 128 + wtid);
  mbar_wait(sb + B_W);
  const int x1 = 159 - (eo + 136);
  const uint32_t fs = rb + ((g & 1) ? 2 * x1 : RS_CS + 2 * x1 + 2);
  {
    uint32_t f[2][10];
    const uint64_t d5 = mkdesc(cb + W5_OFF, 144, 576), d3 = mkdesc(cb + W3_OFF, 144, 576);
#pragma unroll
    for (int i = 0; i < 5; i++) { f[0][i] = lds32(fs + R_E2 + (8 + i) * 16); f[0][5 + i] = lds32(fs + R_O2 + (8 + i) * 16); }
#pragma unroll
    for (int m = 2; m <= 4; m++) {
      wg_fence();
#pragma unroll
      for (int k = 0; k < 4; k++) {
        const uint32_t* a = &f[m & 1][(k >> 1) * 5 + (k & 1) * 2];
        const uint64_t desc = ((k >> 1) ? d3 : d5) + (k & 1) * 18 + (m - 2) * 36;
        if (m == 2) wgmma_rs<48, 1>(dacc, a[1], a[0], a[2], a[1], desc, k);
        else if (m == 3) wgmma_rs<40, 1>(dacc, a[1], a[0], a[2], a[1], desc, 1);
        else wgmma_rs<32, 1>(dacc, a[1], a[0], a[2], a[1], desc, 1);
      }
      wg_commit();
#pragma unroll
      for (int i = 0; i < 5; i++) {
        if (m < 4) { f[(m + 1) & 1][i] = lds32(fs + R_E2 + (4 * (3 - m) + i) * 16); f[(m + 1) & 1][5 + i] = lds32(fs + R_O2 + (4 * (3 - m) + i) * 16); }
        else { f[1][i] = lds32(fs + R_E3 + (8 + i) * 16); f[1][5 + i] = lds32(fs + R_O3 + (8 + i) * 16); }
      }
      wg_wait0();
    }
    {
      const uint32_t yb = cb + Y2_OFF + br * 3072;
#pragma unroll
      for (int i = 0; i < 6; i += 2) {
        const int mi = lane >> 3;
        const int cidx = 32 * (5 - i - (mi >> 1)) + 16 * hf + 8 * (mi & 1) + (lane & 7);
        stsm4(yb + ysw(cidx), pack_bf16(dacc[4 * i], dacc[4 * i + 1]), pack_bf16(dacc[4 * i + 2], dacc[4 * i + 3]),
              pack_bf16(dacc[4 * i + 4], dacc[4 * i + 5]), pack_bf16(dacc[4 * i + 6], dacc[4 * i + 7]));
      }
    }
    bar_arrive(9, 640);
    STAMP(9);
    const uint64_t d9 = mkdesc(cb + W9_OFF, 144, 576), d7 = mkdesc(cb + W7_OFF, 144, 576);
#pragma unroll
    for (int m = 2; m <= 3; m++) {
      wg_fence();
#pragma unroll
      for (int k = 0; k < 4; k++) {
        const uint32_t* a = &f[(m + 1) & 1][(k >> 1) * 5 + (k & 1) * 2];
        const uint64_t desc = ((k >> 1) ? d7 : d9) + (k & 1) * 18 + (m - 2) * 72;
        if (m == 2) wgmma_rs<32, 1>(dacc, a[1], a[0], a[2], a[1], desc, k);
        else wgmma_rs<16, 1>(dacc, a[1], a[0], a[2], a[1], desc, 1);
      }
      wg_commit();
      if (m == 2) {
#pragma unroll
        for (int i = 0; i < 5; i++) { f[0][i] = lds32(fs + R_E3 + (4 + i) * 16); f[0][5 + i] = lds32(fs + R_O3 + (4 + i) * 16); }
      }
      wg_wait0();
    }
    const uint32_t yb = cb + Y3_OFF + br * 2048;
#pragma unroll
    for (int i = 0; i < 4; i += 2) {
      const int mi = lane >> 3;
      const int cidx = 64 * (1 - (i >> 1)) + 2 * (16 * hf + 8 * (mi & 1) + (lane & 7)) + (mi >> 1);
      stsm4(yb + ysw(cidx), pack_bf16(dacc[4 * i], dacc[4 * i + 1]), pack_bf16(dacc[4 * i + 2], dacc[4 * i + 3]),
            pack_bf16(dacc[4 * i + 4], dacc[4 * i + 5]), pack_bf16(dacc[4 * i + 6], dacc[4 * i + 7]));
    }
  }
  STAMP(10);
  const uint32_t g2 = gate_fin(p, gl, (4 + ch) * 128 + wtid, tag);

  bar_sync(10, 512);
  STAMP(11);
  final_box(sb, &tm_out, 2, 4 + ch, wtid, rank, oc0, g2, dA, dB, 1 + ch);
  STAMP(14);
  if (wtid == 0) asm volatile("cp.async.bulk.wait_group.read 0;" ::: "memory");
  STAMP(15); GT(1);
}

typedef CUresult (*EncodeFn)(CUtensorMap*, CUtensorMapDataType, cuuint32_t, void*, const cuuint64_t*, const cuuint64_t*,
                             const cuuint32_t*, const cuuint32_t*, CUtensorMapInterleave, CUtensorMapSwizzle,
                             CUtensorMapL2promotion, CUtensorMapFloatOOBfill);

}

extern "C" void kernel_launch(void* const* d_in, const int* in_sizes, int n_in, void* d_out, int out_size) {
  (void)in_sizes; (void)n_in; (void)out_size;
  typedef const __nv_bfloat16* bp;
  Params p;
  p.u = (bp)d_in[0]; p.A_re = (bp)d_in[1]; p.A_im = (bp)d_in[2]; p.B_re = (bp)d_in[3]; p.B_im = (bp)d_in[4];
  p.C_re = (bp)d_in[5]; p.C_im = (bp)d_in[6]; p.A_ldt = (bp)d_in[7]; p.A_D = (bp)d_in[8];
  p.B_lA = (bp)d_in[10]; p.B_Aim = (bp)d_in[11]; p.B_Cre = (bp)d_in[12]; p.B_Cim = (bp)d_in[13];
  p.B_ldt = (bp)d_in[14]; p.B_D = (bp)d_in[15]; p.gw = (bp)d_in[16];
  static EncodeFn enc = nullptr;
  if (!enc) {
    cudaDriverEntryPointQueryResult qr;
    cudaGetDriverEntryPoint("cuTensorMapEncodeTiled", (void**)&enc, cudaEnableDefault, &qr);
    cudaFuncSetAttribute(ssm_kernel, cudaFuncAttributeMaxDynamicSharedMemorySize, SMEM_BYTES);
  }
  CUtensorMap tm_in, tm_out;
  {
    cuuint64_t gd[5] = {512, 2, 4, 4, 64};
    cuuint64_t gs[4] = {1024, 8192, 2048, 32768};
    cuuint32_t bx[5] = {8, 2, 4, 4, 32};
    cuuint32_t es[5] = {1, 1, 1, 1, 1};
    enc(&tm_in, CU_TENSOR_MAP_DATA_TYPE_BFLOAT16, 5, d_in[0], gd, gs, bx, es, CU_TENSOR_MAP_INTERLEAVE_NONE,
        CU_TENSOR_MAP_SWIZZLE_NONE, CU_TENSOR_MAP_L2_PROMOTION_NONE, CU_TENSOR_MAP_FLOAT_OOB_FILL_NONE);
  }
  {
    cuuint64_t gd[3] = {512, 1024, 2};
    cuuint64_t gs[2] = {2048, 1024};
    cuuint32_t bx[3] = {8, 128, 2};
    cuuint32_t es[3] = {1, 1, 1};
    enc(&tm_out, CU_TENSOR_MAP_DATA_TYPE_BFLOAT16, 3, d_out, gd, gs, bx, es, CU_TENSOR_MAP_INTERLEAVE_NONE,
        CU_TENSOR_MAP_SWIZZLE_NONE, CU_TENSOR_MAP_L2_PROMOTION_NONE, CU_TENSOR_MAP_FLOAT_OOB_FILL_NONE);
  }
  ssm_kernel<<<NCTA, 640, SMEM_BYTES, cudaStreamPerThread>>>(p, tm_in, tm_out);
}
```

```cpp
#include <cuda_runtime.h>
#include <cuda.h>
#include <cuda_bf16.h>
#include <stdint.h>

namespace {

constexpr int L = 2048, D = 512, NM = 128;
constexpr int NCTA = 128;

constexpr int RAW_OFF = 0;
constexpr int XIN_OFF = 32768;
constexpr int BAR_OFF = XIN_OFF + 10240;
constexpr int CH_OFF = BAR_OFF + 128;
constexpr int U_CS = 1184;
constexpr int U_OFF = 0;
constexpr int R_OFF = 4736;
constexpr int RD_X0 = 565;
constexpr int RD_CS = 1216;
constexpr int RS_CS = 320;
constexpr int R_E2 = 2 * RD_CS, R_O2 = R_E2 + 2 * RS_CS, R_E3 = R_O2 + 2 * RS_CS, R_O3 = R_E3 + 2 * RS_CS;
constexpr int R_BR = R_O3 + 2 * RS_CS;
constexpr int W5_OFF = R_OFF + 2 * R_BR;
constexpr int W3_OFF = W5_OFF + 3456;
constexpr int W9_OFF = W3_OFF + 3456;
constexpr int W7_OFF = W9_OFF + 2304;
constexpr int S2_OFF = W7_OFF + 2304;
constexpr int Y0_OFF = S2_OFF + 2304;
constexpr int Y2_OFF = Y0_OFF + 8192, Y3_OFF = Y2_OFF + 6144;
constexpr int CH_BYTES = Y0_OFF + 18432 + 16;
constexpr int SCR_BYTES = 4608;
constexpr int SMEM_BYTES = CH_OFF + 4 * CH_BYTES;
static_assert(CH_BYTES % 128 == 16, "bank staggering of the channel blocks");
static_assert(SMEM_BYTES <= 232448, "smem");
constexpr int B_RAW = BAR_OFF, B_X = BAR_OFF + 8, B_U = BAR_OFF + 40, B_W = BAR_OFF + 48, B_Y2 = BAR_OFF + 56, B_Y3 = BAR_OFF + 96;
constexpr int K1024_OFF = BAR_OFF + 64;

__device__ unsigned int g_gate[L];
__device__ unsigned int g_epoch;
__device__ unsigned int g_ticket;

#define STAMP(k)
#define GT(k)

struct Params {
  const __nv_bfloat16 *u, *A_re, *A_im, *B_re, *B_im, *C_re, *C_im, *A_ldt, *A_D;
  const __nv_bfloat16 *B_lA, *B_Aim, *B_Cre, *B_Cim, *B_ldt, *B_D, *gw;
};

template <int N, int TB> __device__ __forceinline__ void wgmma_rs(float* d, uint32_t a0, uint32_t a1, uint32_t a2, uint32_t a3, uint64_t desc, int sc);
template <> __device__ __forceinline__ void wgmma_rs<64, 0>(float* d, uint32_t a0, uint32_t a1, uint32_t a2, uint32_t a3, uint64_t desc, int sc) {
  asm volatile("{\n.reg .pred p;\nsetp.ne.b32 p, %37, 0;\n"
    "wgmma.mma_async.sync.aligned.m64n64k16.f32.bf16.bf16 {%0,%1,%2,%3,%4,%5,%6,%7,%8,%9,%10,%11,%12,%13,%14,%15,%16,%17,%18,%19,%20,%21,%22,%23,%24,%25,%26,%27,%28,%29,%30,%31}, {%32,%33,%34,%35}, %36, p, 1, 1, 0;\n}"
    : "+f"(d[0]), "+f"(d[1]), "+f"(d[2]), "+f"(d[3]), "+f"(d[4]), "+f"(d[5]), "+f"(d[6]), "+f"(d[7]), "+f"(d[8]), "+f"(d[9]), "+f"(d[10]), "+f"(d[11]), "+f"(d[12]), "+f"(d[13]), "+f"(d[14]), "+f"(d[15]), "+f"(d[16]), "+f"(d[17]), "+f"(d[18]), "+f"(d[19]), "+f"(d[20]), "+f"(d[21]), "+f"(d[22]), "+f"(d[23]), "+f"(d[24]), "+f"(d[25]), "+f"(d[26]), "+f"(d[27]), "+f"(d[28]), "+f"(d[29]), "+f"(d[30]), "+f"(d[31]) : "r"(a0), "r"(a1), "r"(a2), "r"(a3), "l"(desc), "r"(sc));
}
template <> __device__ __forceinline__ void wgmma_rs<56, 0>(float* d, uint32_t a0, uint32_t a1, uint32_t a2, uint32_t a3, uint64_t desc, int sc) {
  asm volatile("{\n.reg .pred p;\nsetp.ne.b32 p, %33, 0;\n"
    "wgmma.mma_async.sync.aligned.m64n56k16.f32.bf16.bf16 {%0,%1,%2,%3,%4,%5,%6,%7,%8,%9,%10,%11,%12,%13,%14,%15,%16,%17,%18,%19,%20,%21,%22,%23,%24,%25,%26,%27}, {%28,%29,%30,%31}, %32, p, 1, 1, 0;\n}"
    : "+f"(d[0]), "+f"(d[1]), "+f"(d[2]), "+f"(d[3]), "+f"(d[4]), "+f"(d[5]), "+f"(d[6]), "+f"(d[7]), "+f"(d[8]), "+f"(d[9]), "+f"(d[10]), "+f"(d[11]), "+f"(d[12]), "+f"(d[13]), "+f"(d[14]), "+f"(d[15]), "+f"(d[16]), "+f"(d[17]), "+f"(d[18]), "+f"(d[19]), "+f"(d[20]), "+f"(d[21]), "+f"(d[22]), "+f"(d[23]), "+f"(d[24]), "+f"(d[25]), "+f"(d[26]), "+f"(d[27]) : "r"(a0), "r"(a1), "r"(a2), "r"(a3), "l"(desc), "r"(sc));
}
template <> __device__ __forceinline__ void wgmma_rs<48, 0>(float* d, uint32_t a0, uint32_t a1, uint32_t a2, uint32_t a3, uint64_t desc, int sc) {
  asm volatile("{\n.reg .pred p;\nsetp.ne.b32 p, %29, 0;\n"
    "wgmma.mma_async.sync.aligned.m64n48k16.f32.bf16.bf16 {%0,%1,%2,%3,%4,%5,%6,%7,%8,%9,%10,%11,%12,%13,%14,%15,%16,%17,%18,%19,%20,%21,%22,%23}, {%24,%25,%26,%27}, %28, p, 1, 1, 0;\n}"
    : "+f"(d[0]), "+f"(d[1]), "+f"(d[2]), "+f"(d[3]), "+f"(d[4]), "+f"(d[5]), "+f"(d[6]), "+f"(d[7]), "+f"(d[8]), "+f"(d[9]), "+f"(d[10]), "+f"(d[11]), "+f"(d[12]), "+f"(d[13]), "+f"(d[14]), "+f"(d[15]), "+f"(d[16]), "+f"(d[17]), "+f"(d[18]), "+f"(d[19]), "+f"(d[20]), "+f"(d[21]), "+f"(d[22]), "+f"(d[23]) : "r"(a0), "r"(a1), "r"(a2), "r"(a3), "l"(desc), "r"(sc));
}
template <> __device__ __forceinline__ void wgmma_rs<48, 1>(float* d, uint32_t a0, uint32_t a1, uint32_t a2, uint32_t a3, uint64_t desc, int sc) {
  asm volatile("{\n.reg .pred p;\nsetp.ne.b32 p, %29, 0;\n"
    "wgmma.mma_async.sync.aligned.m64n48k16.f32.bf16.bf16 {%0,%1,%2,%3,%4,%5,%6,%7,%8,%9,%10,%11,%12,%13,%14,%15,%16,%17,%18,%19,%20,%21,%22,%23}, {%24,%25,%26,%27}, %28, p, 1, 1, 1;\n}"
    : "+f"(d[0]), "+f"(d[1]), "+f"(d[2]), "+f"(d[3]), "+f"(d[4]), "+f"(d[5]), "+f"(d[6]), "+f"(d[7]), "+f"(d[8]), "+f"(d[9]), "+f"(d[10]), "+f"(d[11]), "+f"(d[12]), "+f"(d[13]), "+f"(d[14]), "+f"(d[15]), "+f"(d[16]), "+f"(d[17]), "+f"(d[18]), "+f"(d[19]), "+f"(d[20]), "+f"(d[21]), "+f"(d[22]), "+f"(d[23]) : "r"(a0), "r"(a1), "r"(a2), "r"(a3), "l"(desc), "r"(sc));
}
template <> __device__ __forceinline__ void wgmma_rs<40, 1>(float* d, uint32_t a0, uint32_t a1, uint32_t a2, uint32_t a3, uint64_t desc, int sc) {
  asm volatile("{\n.reg .pred p;\nsetp.ne.b32 p, %25, 0;\n"
    "wgmma.mma_async.sync.aligned.m64n40k16.f32.bf16.bf16 {%0,%1,%2,%3,%4,%5,%6,%7,%8,%9,%10,%11,%12,%13,%14,%15,%16,%17,%18,%19}, {%20,%21,%22,%23}, %24, p, 1, 1, 1;\n}"
    : "+f"(d[0]), "+f"(d[1]), "+f"(d[2]), "+f"(d[3]), "+f"(d[4]), "+f"(d[5]), "+f"(d[6]), "+f"(d[7]), "+f"(d[8]), "+f"(d[9]), "+f"(d[10]), "+f"(d[11]), "+f"(d[12]), "+f"(d[13]), "+f"(d[14]), "+f"(d[15]), "+f"(d[16]), "+f"(d[17]), "+f"(d[18]), "+f"(d[19]) : "r"(a0), "r"(a1), "r"(a2), "r"(a3), "l"(desc), "r"(sc));
}
template <> __device__ __forceinline__ void wgmma_rs<32, 1>(float* d, uint32_t a0, uint32_t a1, uint32_t a2, uint32_t a3, uint64_t desc, int sc) {
  asm volatile("{\n.reg .pred p;\nsetp.ne.b32 p, %21, 0;\n"
    "wgmma.mma_async.sync.aligned.m64n32k16.f32.bf16.bf16 {%0,%1,%2,%3,%4,%5,%6,%7,%8,%9,%10,%11,%12,%13,%14,%15}, {%16,%17,%18,%19}, %20, p, 1, 1, 1;\n}"
    : "+f"(d[0]), "+f"(d[1]), "+f"(d[2]), "+f"(d[3]), "+f"(d[4]), "+f"(d[5]), "+f"(d[6]), "+f"(d[7]), "+f"(d[8]), "+f"(d[9]), "+f"(d[10]), "+f"(d[11]), "+f"(d[12]), "+f"(d[13]), "+f"(d[14]), "+f"(d[15]) : "r"(a0), "r"(a1), "r"(a2), "r"(a3), "l"(desc), "r"(sc));
}
template <> __device__ __forceinline__ void wgmma_rs<16, 1>(float* d, uint32_t a0, uint32_t a1, uint32_t a2, uint32_t a3, uint64_t desc, int sc) {
  asm volatile("{\n.reg .pred p;\nsetp.ne.b32 p, %13, 0;\n"
    "wgmma.mma_async.sync.aligned.m64n16k16.f32.bf16.bf16 {%0,%1,%2,%3,%4,%5,%6,%7}, {%8,%9,%10,%11}, %12, p, 1, 1, 1;\n}"
    : "+f"(d[0]), "+f"(d[1]), "+f"(d[2]), "+f"(d[3]), "+f"(d[4]), "+f"(d[5]), "+f"(d[6]), "+f"(d[7]) : "r"(a0), "r"(a1), "r"(a2), "r"(a3), "l"(desc), "r"(sc));
}

__device__ __forceinline__ uint32_t pack_bf16(float lo, float hi) {
  uint32_t r; asm("cvt.rn.bf16x2.f32 %0, %1, %2;" : "=r"(r) : "f"(hi), "f"(lo)); return r;
}
__device__ __forceinline__ float bf_lo(uint32_t v) { return __uint_as_float(v << 16); }
__device__ __forceinline__ float bf_hi(uint32_t v) { return __uint_as_float(v & 0xffff0000u); }
__device__ __forceinline__ float bf_round(float x) { return bf_lo(pack_bf16(x, 0.f)); }
__device__ __forceinline__ uint32_t hmul2(uint32_t a, uint32_t b) { uint32_t r; asm("mul.rn.bf16x2 %0, %1, %2;" : "=r"(r) : "r"(a), "r"(b)); return r; }
__device__ __forceinline__ uint32_t hadd2(uint32_t a, uint32_t b) { uint32_t r; asm("add.rn.bf16x2 %0, %1, %2;" : "=r"(r) : "r"(a), "r"(b)); return r; }
__device__ __forceinline__ uint32_t hsub2(uint32_t a, uint32_t b) { uint32_t r; asm("sub.rn.bf16x2 %0, %1, %2;" : "=r"(r) : "r"(a), "r"(b)); return r; }
__device__ __forceinline__ uint32_t hfma2(uint32_t a, uint32_t b, uint32_t c) { uint32_t r; asm("fma.rn.bf16x2 %0, %1, %2, %3;" : "=r"(r) : "r"(a), "r"(b), "r"(c)); return r; }

__device__ __forceinline__ void sts16(uint32_t a, uint32_t v) { asm volatile("st.shared.b16 [%0], %1;" ::"r"(a), "h"((unsigned short)v) : "memory"); }
__device__ __forceinline__ void sts32(uint32_t a, uint32_t v) { asm volatile("st.shared.b32 [%0], %1;" ::"r"(a), "r"(v) : "memory"); }
__device__ __forceinline__ void sts64(uint32_t a, uint32_t x, uint32_t y) { asm volatile("st.shared.v2.b32 [%0], {%1,%2};" ::"r"(a), "r"(x), "r"(y) : "memory"); }
__device__ __forceinline__ void sts128(uint32_t a, uint32_t x, uint32_t y, uint32_t z, uint32_t w) {
  asm volatile("st.shared.v4.b32 [%0], {%1,%2,%3,%4};" ::"r"(a), "r"(x), "r"(y), "r"(z), "r"(w) : "memory");
}
__device__ __forceinline__ uint32_t lds32(uint32_t a) { uint32_t v; asm volatile("ld.shared.b32 %0, [%1];" : "=r"(v) : "r"(a) : "memory"); return v; }
__device__ __forceinline__ uint2 lds64(uint32_t a) { uint2 v; asm volatile("ld.shared.v2.b32 {%0,%1}, [%2];" : "=r"(v.x), "=r"(v.y) : "r"(a) : "memory"); return v; }
__device__ __forceinline__ uint4 lds128(uint32_t a) {
  uint4 v; asm volatile("ld.shared.v4.b32 {%0,%1,%2,%3}, [%4];" : "=r"(v.x), "=r"(v.y), "=r"(v.z), "=r"(v.w) : "r"(a) : "memory"); return v;
}
__device__ __forceinline__ void ldsm4(uint32_t a, uint32_t& r0, uint32_t& r1, uint32_t& r2, uint32_t& r3) {
  asm volatile("ldmatrix.sync.aligned.m8n8.x4.shared.b16 {%0,%1,%2,%3}, [%4];" : "=r"(r0), "=r"(r1), "=r"(r2), "=r"(r3) : "r"(a) : "memory");
}
__device__ __forceinline__ void ldsm4t(uint32_t a, uint32_t& r0, uint32_t& r1, uint32_t& r2, uint32_t& r3) {
  asm volatile("ldmatrix.sync.aligned.m8n8.x4.trans.shared.b16 {%0,%1,%2,%3}, [%4];" : "=r"(r0), "=r"(r1), "=r"(r2), "=r"(r3) : "r"(a) : "memory");
}
__device__ __forceinline__ void stsm4(uint32_t a, uint32_t r0, uint32_t r1, uint32_t r2, uint32_t r3) {
  asm volatile("stmatrix.sync.aligned.m8n8.x4.shared.b16 [%0], {%1,%2,%3,%4};" ::"r"(a), "r"(r0), "r"(r1), "r"(r2), "r"(r3) : "memory");
}
__device__ __forceinline__ void stsm4t(uint32_t a, uint32_t r0, uint32_t r1, uint32_t r2, uint32_t r3) {
  asm volatile("stmatrix.sync.aligned.m8n8.x4.trans.shared.b16 [%0], {%1,%2,%3,%4};" ::"r"(a), "r"(r0), "r"(r1), "r"(r2), "r"(r3) : "memory");
}
__device__ __forceinline__ void mma16816(float* c, uint32_t a0, uint32_t a1, uint32_t a2, uint32_t a3, uint32_t b0, uint32_t b1) {
  asm("mma.sync.aligned.m16n8k16.row.col.f32.bf16.bf16.f32 {%0,%1,%2,%3}, {%4,%5,%6,%7}, {%8,%9}, {%0,%1,%2,%3};"
      : "+f"(c[0]), "+f"(c[1]), "+f"(c[2]), "+f"(c[3]) : "r"(a0), "r"(a1), "r"(a2), "r"(a3), "r"(b0), "r"(b1));
}
__device__ __forceinline__ void bar_sync(int id, int n) { asm volatile("bar.sync %0, %1;" ::"r"(id), "r"(n) : "memory"); }
__device__ __forceinline__ void bar_arrive(int id, int n) { asm volatile("bar.arrive %0, %1;" ::"r"(id), "r"(n) : "memory"); }
__device__ __forceinline__ void wg_fence() { asm volatile("wgmma.fence.sync.aligned;" ::: "memory"); }
__device__ __forceinline__ void wg_commit() { asm volatile("wgmma.commit_group.sync.aligned;" ::: "memory"); }
__device__ __forceinline__ void wg_wait0() { asm volatile("wgmma.wait_group.sync.aligned 0;" ::: "memory"); }
__device__ __forceinline__ void fence_async() { asm volatile("fence.proxy.async.shared::cta;" ::: "memory"); }
__device__ __forceinline__ uint64_t mkdesc(uint32_t addr, uint32_t lbo, uint32_t sbo) {
  return (uint64_t)((addr & 0x3FFFF) >> 4) | ((uint64_t)(lbo >> 4) << 16) | ((uint64_t)(sbo >> 4) << 32);
}
__device__ __forceinline__ uint32_t mapa(uint32_t a, uint32_t rank) {
  uint32_t r; asm("mapa.shared::cluster.u32 %0, %1, %2;" : "=r"(r) : "r"(a), "r"(rank)); return r;
}
__device__ __forceinline__ void mbar_init_expect(uint32_t bar, uint32_t bytes) {
  asm volatile("mbarrier.init.shared::cta.b64 [%0], 1;" ::"r"(bar) : "memory");
  asm volatile("mbarrier.arrive.expect_tx.shared::cta.b64 _, [%0], %1;" ::"r"(bar), "r"(bytes) : "memory");
}
__device__ __forceinline__ void mbar_wait(uint32_t bar) {
#pragma unroll 1
  for (int it = 0; it < (1 << 22); it++) {
    uint32_t ok;
    asm volatile("{\n.reg .pred p;\nmbarrier.try_wait.parity.acquire.cluster.shared::cta.b64 p, [%1], 0;\nselp.u32 %0, 1, 0, p;\n}"
                 : "=r"(ok) : "r"(bar) : "memory");
    if (ok) return;
  }
  __trap();
}
__device__ __forceinline__ void st_async4(uint32_t a, uint32_t bar, uint32_t x, uint32_t y, uint32_t z, uint32_t w) {
  asm volatile("st.async.weak.shared::cluster.mbarrier::complete_tx::bytes.v4.b32 [%0], {%2,%3,%4,%5}, [%1];"
               ::"r"(a), "r"(bar), "r"(x), "r"(y), "r"(z), "r"(w) : "memory");
}

struct cf { float re, im; };
__device__ __forceinline__ cf cmul(cf a, cf b) { return {fmaf(a.re, b.re, -a.im * b.im), fmaf(a.re, b.im, a.im * b.re)}; }
__device__ __forceinline__ cf csq(cf a) { return {fmaf(a.re, a.re, -a.im * a.im), (a.re + a.re) * a.im}; }
__device__ __forceinline__ cf cexp_p(float xl, float y, float p) {
  float mag; asm("ex2.approx.ftz.f32 %0, %1;" : "=f"(mag) : "f"(xl * p));
  const float th = y * p;
  const float k = rintf(th * 0.15915494309189535f);
  float r = fmaf(k, -6.2831854820251465f, th);
  r = fmaf(k, 1.7484555314695172e-07f, r);
  return {mag * __cosf(r), mag * __sinf(r)};
}
__device__ __forceinline__ uint32_t ysw(int c) { return (uint32_t)(c ^ ((c >> 3) & 3)) * 16u; }

#define CMUL2(OR, OI, xr, xi, yr, yi, nyi) do { OR = hfma2(xr, yr, hmul2(xi, nyi)); OI = hfma2(xr, yi, hmul2(xi, yr)); } while (0)

__device__ __forceinline__ uint32_t gate_slow(const __nv_bfloat16* u, const __nv_bfloat16* gw, int row) {
  float s = 0.f;
  const uint32_t* xr = (const uint32_t*)(u + (size_t)row * D);
  const uint32_t* wr = (const uint32_t*)gw;
#pragma unroll 1
  for (int j = 0; j < D / 2; j++) { const uint32_t pr = hmul2(xr[j], wr[j]); s += bf_lo(pr); s += bf_hi(pr); }
  s = bf_round(s);
  return pack_bf16(1.f / (1.f + expf(-s)), 0.f);
}

__device__ __forceinline__ void prefix6(float* pf, uint32_t ub, int c0) {
  pf[0] = 0.f;
#pragma unroll
  for (int j = 0; j < 6; j++) {
    const int c = c0 + j;
    const uint4 v = lds128(ub + (c & 3) * U_CS + (63 - (c >> 2)) * 16);
    const uint32_t w[4] = {v.x, v.y, v.z, v.w};
#pragma unroll
    for (int i = 0; i < 4; i++) {
      pf[j * 8 + 2 * i + 1] = pf[j * 8 + 2 * i] + bf_lo(w[i]);
      pf[j * 8 + 2 * i + 2] = pf[j * 8 + 2 * i + 1] + bf_hi(w[i]);
    }
  }
}
template <int A, int B>
__device__ __forceinline__ void put_win(const float* pf, int ix, uint32_t addr) {
  uint32_t a[4];
#pragma unroll
  for (int i = 0; i < 4; i++) a[i] = pack_bf16(pf[ix + 2 * i - B + 1] - pf[ix + 2 * i - A], pf[ix + 2 * i - B + 2] - pf[ix + 2 * i - A + 1]);
  sts128(addr, a[0], a[1], a[2], a[3]);
}

__device__ __forceinline__ uint2 gate_ld(int x) {
  uint2 gv;
  asm volatile("ld.relaxed.gpu.global.v2.u32 {%0,%1}, [%2];" : "=r"(gv.x), "=r"(gv.y) : "l"(g_gate + x * 2) : "memory");
  return gv;
}
__device__ __noinline__ uint32_t gate_poll(const __nv_bfloat16* u, const __nv_bfloat16* gw, int x, uint32_t tag) {
  uint2 gv;
#pragma unroll 1
  for (int spins = 0; spins < (1 << 16); spins++) {
    gv = gate_ld(x);
    if ((gv.x >> 16) == tag && (gv.y >> 16) == tag) return __byte_perm(gv.x, gv.y, 0x5410);
  }
  return __byte_perm(gate_slow(u, gw, x * 2), gate_slow(u, gw, x * 2 + 1), 0x5410);
}
__device__ __forceinline__ uint32_t gate_fin(const Params& p, uint2 gv, int x, uint32_t tag) {
  if ((gv.x >> 16) == tag && (gv.y >> 16) == tag) return __byte_perm(gv.x, gv.y, 0x5410);
  return gate_poll(p.u, p.gw, x, tag);
}

__device__ __forceinline__ void ld4ch(uint32_t* v, uint32_t addr) {
#pragma unroll
  for (int k = 0; k < 4; k++) v[k] = lds32(addr + k * CH_BYTES);
}
__device__ __forceinline__ void skip_terms(uint32_t* ua, uint32_t* ub, uint32_t sb, int x, uint2 dA, uint2 dB) {
  const int c = x >> 2;
  uint32_t uu[4];
  ld4ch(uu, sb + CH_OFF + (x & 3) * 4 + U_OFF + (c & 3) * U_CS + (63 - (c >> 2)) * 16);
#pragma unroll
  for (int k = 0; k < 4; k++) {
    ua[k] = hmul2(uu[k], __byte_perm((k & 2) ? dA.y : dA.x, 0, (k & 1) ? 0x3232 : 0x1010));
    ub[k] = hmul2(uu[k], __byte_perm((k & 2) ? dB.y : dB.x, 0, (k & 1) ? 0x3232 : 0x1010));
  }
}
__device__ __forceinline__ uint4 mix(const uint32_t* a, const uint32_t* b, const uint32_t* ua, const uint32_t* ub, uint32_t g2) {
  const uint32_t h2 = hsub2(0x3f803f80u, g2);
  uint32_t o[4];
#pragma unroll
  for (int k = 0; k < 4; k++) o[k] = hadd2(hmul2(g2, hadd2(a[k], ua[k])), hmul2(h2, hadd2(b[k], ub[k])));
  return make_uint4(__byte_perm(o[0], o[1], 0x5410), __byte_perm(o[2], o[3], 0x5410), __byte_perm(o[0], o[1], 0x7632), __byte_perm(o[2], o[3], 0x7632));
}
__device__ __forceinline__ void send_box(uint32_t sb, int slot, int wtid, uint32_t rank, uint4 r) {
  st_async4(mapa(sb + XIN_OFF + slot * 2048 + wtid * 16, rank ^ 1), mapa(sb + B_X + slot * 8, rank ^ 1), r.x, r.y, r.z, r.w);
}
__device__ __forceinline__ void merge_box(uint32_t sb, const CUtensorMap* tm_out, int slot, int wtid, uint32_t rank, int oc0, uint4 r, int barid) {
  const uint32_t st = sb + RAW_OFF + slot * 4096 + wtid * 16;
  sts64(st + rank * 8, r.x, r.y); sts64(st + 2048 + rank * 8, r.z, r.w);
  mbar_wait(sb + B_X + slot * 8);
  const uint4 q = lds128(sb + XIN_OFF + slot * 2048 + wtid * 16);
  sts64(st + (rank ^ 1) * 8, q.x, q.y); sts64(st + 2048 + (rank ^ 1) * 8, q.z, q.w);
  fence_async();
  bar_sync(barid, 128);
  if (wtid == 0) {
    asm volatile("cp.async.bulk.tensor.3d.global.shared::cta.bulk_group [%0, {%2, %3, %4}], [%1];"
                 ::"l"(tm_out), "r"(sb + RAW_OFF + slot * 4096), "r"(oc0), "r"((2 * slot + (int)rank) * 128), "r"(0) : "memory");
    asm volatile("cp.async.bulk.commit_group;" ::: "memory");
  }
}

__device__ __forceinline__ void window_sums(uint32_t cb, int wq, int lane) {
      float pf[49];
      if (wq == 0 || wq == 3) {
        if (wq == 0 || lane < 16) {
          const int nu = wq ? 32 + lane : lane;
          prefix6(pf, cb + U_OFF, 4 * nu - 2);
          const uint32_t po = (5 - (nu >> 3)) * 576 + ((nu & 7) >> 1) * 144 + (nu & 1) * 64;
#pragma unroll
          for (int k = 0; k < 4; k++) { put_win<10, 6>(pf, 16 + 8 * k, cb + W5_OFF + po + k * 16); put_win<5, 3>(pf, 16 + 8 * k, cb + W3_OFF + po + k * 16); }
        }
      } else {
        const uint32_t po = (1 - (lane >> 4)) * 1152 + ((lane & 15) >> 2) * 144 + (lane & 3) * 32;
        if (wq == 1) {
          prefix6(pf, cb + U_OFF, 4 * lane - 3);
#pragma unroll
          for (int k = 0; k < 4; k++) put_win<20, 12>(pf, 24 + 8 * k, cb + W9_OFF + po + (k & 1) * 576 + (k >> 1) * 16);
        } else {
          prefix6(pf, cb + U_OFF, 4 * lane - 2);
          const uint32_t so = cb + S2_OFF + (lane >> 1) * 144 + (lane & 1) * 64;
#pragma unroll
          for (int k = 0; k < 4; k++) { put_win<11, 5>(pf, 16 + 8 * k, cb + W7_OFF + po + (k & 1) * 576 + (k >> 1) * 16); put_win<4, 3>(pf, 16 + 8 * k, so + k * 16); }
        }
      }
}

__global__ void __cluster_dims__(2, 1, 1) __launch_bounds__(640, 1)
ssm_kernel(const Params p, const __grid_constant__ CUtensorMap tm_in, const __grid_constant__ CUtensorMap tm_out) {
  extern __shared__ __align__(1024) unsigned char smem_raw[];
  const uint32_t sb = (uint32_t)__cvta_generic_to_shared(smem_raw);
  const int tid = threadIdx.x, lane = tid & 31;
  const int warp = __shfl_sync(0xffffffffu, tid >> 5, 0);
  const int ch = warp >> 2, wq = warp & 3, br = wq >> 1, hf = wq & 1;
  const int g = lane >> 2, t = lane & 3;
  const int d = blockIdx.x * 4 + ch;
  const uint32_t rank = blockIdx.x & 1;
  const uint32_t cb = sb + CH_OFF + ch * CH_BYTES;
  const int wtid = tid & 127;
  const int oc0 = (int)(blockIdx.x >> 1) * 8;
  STAMP(0); GT(0);

  if (warp >= 16) {
    if (wtid == 0) {
      mbar_init_expect(sb + B_RAW, 32768);
#pragma unroll
      for (int i = 0; i < 4; i++) mbar_init_expect(sb + B_X + 8 * i, 2048);
      asm volatile("mbarrier.init.shared::cta.b64 [%0], 128;" ::"r"(sb + B_U) : "memory");
      asm volatile("mbarrier.init.shared::cta.b64 [%0], 128;" ::"r"(sb + B_W) : "memory");
      asm volatile("mbarrier.init.shared::cta.b64 [%0], 16;" ::"r"(sb + B_Y2) : "memory");
      asm volatile("mbarrier.init.shared::cta.b64 [%0], 16;" ::"r"(sb + B_Y3) : "memory");
      asm volatile("fence.mbarrier_init.release.cluster;" ::: "memory");
      asm volatile("fence.proxy.async.shared::cta;" ::: "memory");
    }
    __syncwarp();
    asm volatile("barrier.cluster.arrive.relaxed.aligned;" ::: "memory");
    unsigned int epoch;
    asm volatile("ld.relaxed.gpu.global.u32 %0, [%1];" : "=r"(epoch) : "l"(&g_epoch) : "memory");
    const uint2 dA = *(const uint2*)(p.A_D + blockIdx.x * 4), dB = *(const uint2*)(p.B_D + blockIdx.x * 4);
    const uint4 gw0 = *(const uint4*)(p.gw + lane * 8), gw1 = *(const uint4*)(p.gw + 256 + lane * 8);
    asm volatile("barrier.cluster.wait.aligned;" ::: "memory");
    if (wtid == 0) {
      asm volatile("cp.async.bulk.tensor.5d.shared::cluster.global.mbarrier::complete_tx::bytes.multicast::cluster [%0], [%1, {%3, %4, %4, %4, %5}], [%2], %6;"
                   ::"r"(sb + RAW_OFF + rank * 16384), "l"(&tm_in), "r"(sb + B_RAW), "r"(oc0), "r"(0), "r"((int)rank * 32), "h"((unsigned short)3) : "memory");
    }
    sts128(sb + CH_OFF + wq * CH_BYTES + U_OFF + (lane >> 3) * U_CS + (64 + (lane & 7)) * 16, 0, 0, 0, 0);
    const uint32_t tag = (epoch + 1) & 0xffffu;
    {
      const int grow = blockIdx.x * 16 + wq * 4;
      uint4 gx[4][2];
#pragma unroll
      for (int i = 0; i < 4; i++) {
        gx[i][0] = *(const uint4*)(p.u + (size_t)(grow + i) * D + lane * 8);
        gx[i][1] = *(const uint4*)(p.u + (size_t)(grow + i) * D + 256 + lane * 8);
      }
      const uint32_t ws[8] = {gw0.x, gw0.y, gw0.z, gw0.w, gw1.x, gw1.y, gw1.z, gw1.w};
      float sm[4];
#pragma unroll
      for (int i = 0; i < 4; i++) {
        const uint32_t xs[8] = {gx[i][0].x, gx[i][0].y, gx[i][0].z, gx[i][0].w, gx[i][1].x, gx[i][1].y, gx[i][1].z, gx[i][1].w};
        float s = 0.f;
#pragma unroll
        for (int j = 0; j < 8; j++) { const uint32_t pr = hmul2(xs[j], ws[j]); s += bf_lo(pr); s += bf_hi(pr); }
        sm[i] = s;
      }
      {
        const bool b0 = lane & 1, b1 = lane & 2;
        float u0 = b0 ? sm[1] : sm[0], v0 = b0 ? sm[0] : sm[1], u1 = b0 ? sm[3] : sm[2], v1 = b0 ? sm[2] : sm[3];
        u0 += __shfl_xor_sync(0xffffffffu, v0, 1); u1 += __shfl_xor_sync(0xffffffffu, v1, 1);
        float s = b1 ? u1 : u0; const float v = b1 ? u0 : u1;
        s += __shfl_xor_sync(0xffffffffu, v, 2);
#pragma unroll
        for (int o = 4; o < 32; o <<= 1) s += __shfl_xor_sync(0xffffffffu, s, o);
        s = bf_round(s);
        const float gv = 1.f / (1.f + expf(-s));
        const uint32_t w = (tag << 16) | (pack_bf16(gv, 0.f) & 0xffffu);
        if (lane < 4) asm volatile("st.relaxed.gpu.global.u32 [%0], %1;" ::"l"(&g_gate[grow + lane]), "r"(w) : "memory");
      }
    }
    STAMP(3);
    mbar_wait(sb + B_RAW);
    STAMP(4);
    {
      const uint32_t dst = sb + CH_OFF + (g & 3) * CH_BYTES + U_OFF + t * U_CS + (63 - wq * 16) * 16;
#pragma unroll
      for (int h = 0; h < 2; h++) {
        uint32_t r[8][4];
#pragma unroll
        for (int i = 0; i < 8; i++) ldsm4t(sb + RAW_OFF + (wq * 16 + h * 8 + i) * 512 + lane * 16, r[i][0], r[i][1], r[i][2], r[i][3]);
        if ((uint32_t)(g >> 2) == rank) {
#pragma unroll
          for (int i = 0; i < 8; i++) sts128(dst - (h * 8 + i) * 16, r[i][0], r[i][1], r[i][2], r[i][3]);
        }
      }
    }
    fence_async();
    asm volatile("mbarrier.arrive.shared::cta.b64 _, [%0];" ::"r"(sb + B_U) : "memory");
    bar_sync(5, 128);
    STAMP(5);
#pragma unroll 1
    for (int k = 0; k < 4; k++) window_sums(sb + CH_OFF + k * CH_BYTES, wq, lane);
    fence_async();
    asm volatile("mbarrier.arrive.shared::cta.b64 _, [%0];" ::"r"(sb + B_W) : "memory");
    STAMP(7);
    STAMP(8);
    unsigned int ticket = 0;
    uint32_t gg[4];
    {
      uint2 gl[4];
#pragma unroll
      for (int i = 0; i < 4; i++) gl[i] = gate_ld((i ^ (int)rank ^ 1) * 128 + wtid);
#pragma unroll
      for (int i = 0; i < 4; i++) gg[i] = gate_fin(p, gl[i], (i ^ (int)rank ^ 1) * 128 + wtid, tag);
    }
    {
      uint32_t ua[4][4], ub[4][4], ya[4][4], yb[4][4], yo[4];
#pragma unroll
      for (int i = 0; i < 4; i++) {
        const int x = (i ^ (int)rank ^ 1) * 128 + wtid;
        skip_terms(ua[i], ub[i], sb, x, dA, dB);
        yo[i] = sb + CH_OFF + (x & 3) * 4 + ysw(x >> 2);
      }
      bar_sync(8, 640);
      STAMP(10);
#pragma unroll
      for (int i = 0; i < 4; i++) { ld4ch(ya[i], yo[i] + Y0_OFF); ld4ch(yb[i], yo[i] + Y0_OFF + 4096); }
      send_box(sb, 0, wtid, rank, mix(ya[0], yb[0], ua[0], ub[0], gg[0]));
      merge_box(sb, &tm_out, 0, wtid, rank, oc0, mix(ya[1], yb[1], ua[1], ub[1], gg[1]), 5);
      if (wtid == 0) ticket = atomicAdd(&g_ticket, 1u);
      STAMP(12);
      mbar_wait(sb + B_Y2);
      STAMP(11);
#pragma unroll
      for (int i = 2; i < 4; i++) { ld4ch(ya[i - 2], yo[i] + Y2_OFF - 1024); ld4ch(yb[i - 2], yo[i] + Y2_OFF - 1024 + 3072); }
#pragma unroll
      for (int i = 2; i < 4; i++)
#pragma unroll
        for (int k = 0; k < 4; k++) { ya[i][k] = hadd2(ya[i][k], ya[i - 2][k]); yb[i][k] = hadd2(yb[i][k], yb[i - 2][k]); }
      send_box(sb, 1, wtid, rank, mix(ya[2], yb[2], ua[2], ub[2], gg[2]));
      merge_box(sb, &tm_out, 1, wtid, rank, oc0, mix(ya[3], yb[3], ua[3], ub[3], gg[3]), 5);
      STAMP(13);
    }
    if (wtid == 0) {
      if (ticket == NCTA - 1) { g_ticket = 0; g_epoch = epoch + 1; }
      asm volatile("cp.async.bulk.wait_group.read 0;" ::: "memory");
    }
    STAMP(15);
    return;
  }
  asm volatile("barrier.cluster.arrive.relaxed.aligned;" ::: "memory");

  const int moff = d * NM + hf * 64 + lane * 2;
  const uint32_t q0 = *(const uint32_t*)((br ? p.B_lA : p.A_re) + moff), q1 = *(const uint32_t*)((br ? p.B_Aim : p.A_im) + moff);
  const uint32_t q2 = *(const uint32_t*)((br ? p.B_Cre : p.C_re) + moff), q3 = *(const uint32_t*)((br ? p.B_Cim : p.C_im) + moff);
  const uint32_t q4 = *(const uint32_t*)((br ? p.B_Cre : p.B_re) + moff), q5 = *(const uint32_t*)((br ? p.B_Cim : p.B_im) + moff);
  const uint2 ldt4 = *(const uint2*)((br ? p.B_ldt : p.A_ldt) + blockIdx.x * 4);
  unsigned int epoch;
  asm volatile("ld.relaxed.gpu.global.u32 %0, [%1];" : "=r"(epoch) : "l"(&g_epoch) : "memory");

  for (int i = wtid & 63; i < R_BR / 16; i += 64) sts128(cb + R_OFF + br * R_BR + i * 16, 0, 0, 0, 0);
  STAMP(1);

  float acc[5][4];
  float k2048 = 0.f;
  const uint32_t scr = cb + Y0_OFF + wq * SCR_BYTES;
  const uint32_t scr2 = sb + XIN_OFF + warp * 640;
  {
    const uint32_t ldt2 = (ch & 2) ? ldt4.y : ldt4.x;
    const float dt = bf_round(expf((ch & 1) ? bf_hi(ldt2) : bf_lo(ldt2)));
#pragma unroll
    for (int i = 0; i < 5; i++) acc[i][0] = acc[i][1] = acc[i][2] = acc[i][3] = 0.f;
    cf cc[2], zz1[2], zz128[2];
#pragma unroll
    for (int r = 0; r < 2; r++) {
      float v0 = r ? bf_hi(q0) : bf_lo(q0), v1 = r ? bf_hi(q1) : bf_lo(q1), v2 = r ? bf_hi(q2) : bf_lo(q2);
      float v3 = r ? bf_hi(q3) : bf_lo(q3), v4 = r ? bf_hi(q4) : bf_lo(q4), v5 = r ? bf_hi(q5) : bf_lo(q5);
      if (br == 0) { cc[r] = cmul(cf{v2, v3}, cf{dt * v4, dt * v5}); }
      else { v0 = -bf_round(expf(v0)); cc[r] = cf{2.f * dt * v2, 2.f * dt * v3}; }
      const float xl = (dt * v0) * 1.4426950408889634f, y = dt * v1;
      zz1[r] = cexp_p(xl, y, 1.f); zz128[r] = cexp_p(xl, y, 128.f);
    }
    STAMP(2);
    const uint32_t tb = scr + lane * 16;
    const uint32_t ta = scr + (lane >> 3) * 512 + (lane & 7) * 16;
    const uint32_t tc = ((lane & 8) ? scr2 : scr + 4096) + (lane >> 4) * 128 + (lane & 7) * 16;
    const uint32_t tm = scr2 + 512 + ((lane >> 3) & 1) * 64 + (lane >> 4) * 16;
#pragma unroll 1
    for (int r = 0; r < 2; r++) {
      const cf c = r ? cc[1] : cc[0], z1 = r ? zz1[1] : zz1[0], z128 = r ? zz128[1] : zz128[0];
      const cf z2 = csq(z1), z4 = csq(z2), z8 = csq(z4);
      const cf z16 = csq(z8), z24 = cmul(z16, z8), z32 = csq(z16), z40 = cmul(z32, z8), z48 = csq(z24), z56 = cmul(z32, z24), z64 = csq(z32);
      const cf z256 = csq(z128), z512 = csq(z256), z1024 = csq(z512), z2048 = csq(z1024);
      k2048 += fmaf(c.re, z2048.re, -c.im * z2048.im);
      __syncwarp();
      {
        uint32_t xr[4] = {pack_bf16(1.f, z8.re), pack_bf16(z16.re, z24.re), pack_bf16(z32.re, z40.re), pack_bf16(z48.re, z56.re)};
        uint32_t xi[4] = {pack_bf16(0.f, -z8.im), pack_bf16(-z16.im, -z24.im), pack_bf16(-z32.im, -z40.im), pack_bf16(-z48.im, -z56.im)};
        sts128(tb + 0 * 512, xr[0], xr[1], xr[2], xr[3]);
        sts128(tb + 2 * 512, xi[0], xi[1], xi[2], xi[3]);
        const uint32_t yr = pack_bf16(z64.re, z64.re), nyi = pack_bf16(z64.im, z64.im), yi = nyi ^ 0x80008000u;
        uint32_t o[4], q[4];
#pragma unroll
        for (int i = 0; i < 4; i++) CMUL2(o[i], q[i], xr[i], xi[i], yr, yi, nyi);
        sts128(tb + 1 * 512, o[0], o[1], o[2], o[3]);
        sts128(tb + 3 * 512, q[0], q[1], q[2], q[3]);
      }
      {
        const cf h1 = cmul(c, z128), h2 = cmul(c, z256), h3 = cmul(h1, z256), h4 = cmul(c, z512), h5 = cmul(h1, z512), h6 = cmul(h2, z512), h7 = cmul(h3, z512);
        const cf e1 = cmul(c, z1), e2 = cmul(c, z2), e3 = cmul(e1, z2), e129 = cmul(h1, z1), e130 = cmul(h1, z2), e131 = cmul(e129, z2);
        const cf e258 = cmul(h2, z2), e386 = cmul(h3, z2);
        const uint32_t pr0 = pack_bf16(c.re, e1.re), pr2 = pack_bf16(h1.re, e129.re), pi0 = pack_bf16(c.im, e1.im), pi2 = pack_bf16(h1.im, e129.im);
        sts128(tb + 4 * 512, pr0, pack_bf16(e2.re, e3.re), pr2, pack_bf16(e130.re, e131.re));
        sts128(tb + 5 * 512, pi0, pack_bf16(e2.im, e3.im), pi2, pack_bf16(e130.im, e131.im));
        uint32_t xr[4] = {pack_bf16(h2.re, e258.re), pack_bf16(h3.re, e386.re), pack_bf16(h4.re, h5.re), pack_bf16(h6.re, h7.re)};
        uint32_t xi[4] = {pack_bf16(h2.im, e258.im), pack_bf16(h3.im, e386.im), pack_bf16(h4.im, h5.im), pack_bf16(h6.im, h7.im)};
        sts128(tb + 6 * 512, xr[0], xr[1], xr[2], xr[3]);
        sts128(tb + 7 * 512, xi[0], xi[1], xi[2], xi[3]);
        xr[1] = __byte_perm(xr[0], xr[1], 0x5410); xi[1] = __byte_perm(xi[0], xi[1], 0x5410);
        xr[0] = __byte_perm(pr0, pr2, 0x5410); xi[0] = __byte_perm(pi0, pi2, 0x5410);
        const uint32_t yr = pack_bf16(z1024.re, z1024.re), yi = pack_bf16(z1024.im, z1024.im), nyi = yi ^ 0x80008000u;
        uint32_t o[4], q[4];
#pragma unroll
        for (int i = 0; i < 4; i++) CMUL2(o[i], q[i], xr[i], xi[i], yr, yi, nyi);
        sts128(tb + 8 * 512, o[0], o[1], o[2], o[3]);
        sts128(scr2 + lane * 16, q[0], q[1], q[2], q[3]);
        const uint32_t m4 = pack_bf16(z4.re, z4.im);
        sts16(scr2 + 512 + lane * 2, m4); sts16(scr2 + 576 + lane * 2, m4 >> 16);
      }
      __syncwarp();
#pragma unroll
      for (int kp = 0; kp < 2; kp++) {
        uint32_t rr[2], ri[2], yr[2], yi[2];
        ldsm4t(tc + kp * 256, rr[0], ri[0], rr[1], ri[1]);
        ldsm4(tm + kp * 32, yr[0], yi[0], yr[1], yi[1]);
#pragma unroll
        for (int k2 = 0; k2 < 2; k2++) {
          const int kk = kp * 2 + k2;
          uint32_t a0, a1, a2, a3, pr, pi, qr, qi, xr, xi;
          ldsm4t(ta + kk * 128, a0, a1, a2, a3);
          ldsm4t(ta + 2048 + kk * 128, pr, pi, qr, qi);
          const uint32_t nyi = yi[k2] ^ 0x80008000u;
          mma16816(acc[0], a0, a1, a2, a3, pr, pi);
          mma16816(acc[2], a0, a1, a2, a3, qr, qi);
          mma16816(acc[4], a0, a1, a2, a3, rr[k2], ri[k2]);
          CMUL2(xr, xi, pr, pi, yr[k2], yi[k2], nyi);
          mma16816(acc[1], a0, a1, a2, a3, xr, xi);
          CMUL2(xr, xi, qr, qi, yr[k2], yi[k2], nyi);
          mma16816(acc[3], a0, a1, a2, a3, xr, xi);
        }
      }
    }
#pragma unroll
    for (int o = 16; o; o >>= 1) k2048 += __shfl_xor_sync(0xffffffffu, k2048, o);
  }
  STAMP(3);
  __syncwarp();
  {
    const uint32_t xs = scr + lane * 16;
#define OTH(i, k) __float_as_uint(hf ? acc[i][k] : acc[i][2 + (k)])
    sts128(xs, OTH(0, 0), OTH(0, 1), OTH(1, 0), OTH(1, 1));
    sts128(xs + 512, OTH(2, 0), OTH(2, 1), OTH(3, 0), OTH(3, 1));
    sts128(xs + 1024, OTH(4, 0), OTH(4, 1), __float_as_uint(k2048), 0);
#undef OTH
  }

  bar_sync(1 + ch, 128);
  STAMP(4);
  {
    const uint32_t xo = cb + Y0_OFF + (wq ^ 1) * SCR_BYTES + lane * 16;
    const uint4 o0 = lds128(xo), o1 = lds128(xo + 512), o2 = lds128(xo + 1024);
    const uint32_t rb = cb + R_OFF + br * R_BR;
#define OWN(i, k) (hf ? acc[i][2 + (k)] : acc[i][k])
    const uint32_t vP = pack_bf16(OWN(0, 1) + __uint_as_float(o0.y), OWN(0, 0) + __uint_as_float(o0.x));
    const uint32_t vP4 = pack_bf16(OWN(1, 1) + __uint_as_float(o0.w), OWN(1, 0) + __uint_as_float(o0.z));
    const uint32_t vQ = pack_bf16(OWN(2, 1) + __uint_as_float(o1.y), OWN(2, 0) + __uint_as_float(o1.x));
    const uint32_t vQ4 = pack_bf16(OWN(3, 1) + __uint_as_float(o1.w), OWN(3, 0) + __uint_as_float(o1.z));
    const uint32_t vR = pack_bf16(OWN(4, 1) + __uint_as_float(o2.y), OWN(4, 0) + __uint_as_float(o2.x));
#undef OWN
    const int j = g + 8 * hf;
    {
      const int a = 2 * (t & 1) + 64 * (t & 2) + 8 * j;
      const uint32_t ad = rb + 2 * (RD_X0 - 1 - a);
      const uint32_t a1 = (t & 2) ? ad - 8 : ad, a2 = (t & 2) ? ad : ad - 8;
      const uint32_t w1 = (t & 2) ? vP4 : vP, w2 = (t & 2) ? vP : vP4;
      sts32(a1, w1); sts32(a2, w2);
      sts16(a1 + RD_CS + 2, w1); sts16(a1 + RD_CS + 4, w1 >> 16);
      sts16(a2 + RD_CS + 2, w2); sts16(a2 + RD_CS + 4, w2 >> 16);
    }
    if (t < 2) {
      const int b = 256 + 128 * t + 8 * j;
      const uint32_t ad = rb + 2 * (RD_X0 - 6 - b);
      const uint32_t v22 = __byte_perm(vQ4, 0, 0x3232), v00 = __byte_perm(vQ, 0, 0x3232);
      sts16(ad, vQ4);
      sts64(ad + 2, v22, __byte_perm(vQ4, vQ, 0x5432));
      sts32(ad + 10, v00);
      if (b != 256) { sts16(ad + 14, v00); sts128(ad + RD_CS + 2, vQ4, v22, vQ, v00); }
      else { sts64(ad + RD_CS + 2, vQ4, v22); sts32(ad + RD_CS + 10, vQ); sts16(ad + RD_CS + 14, v00); }
    } else {
      const uint32_t ao = rb + R_O2 + 2 * (159 - (32 * t + j)), ae = ao - (R_O2 - R_E2) + 2;
      sts16(ao, vQ4 >> 16); sts16(ao + RS_CS + 2, vQ4 >> 16); sts16(ao - 32, vQ4); sts16(ao - 32 + RS_CS + 2, vQ4);
      sts16(ae - 32, vQ); sts16(ae - 32 + RS_CS + 2, vQ);
      if (lane != 2 || hf) { sts16(ae, vQ >> 16); sts16(ae + RS_CS + 2, vQ >> 16); }
      else {
        const uint32_t vv = __byte_perm(vQ, 0, 0x3232), ad = rb + 2 * (RD_X0 - 514);
        sts16(ad, vv); sts32(ad + 2, vv); sts16(ad + 6, vv); sts64(ad + RD_CS + 2, vv, vv);
      }
    }
    {
      const uint32_t a = rb + ((g & 1) ? R_O3 : R_E3 + 2) + 2 * (159 - (64 + 16 * t + (j >> 1)));
      const bool p1024 = (lane == 0) && (hf == 0);
      const uint32_t a00 = p1024 ? rb + R_E2 + 2 * (159 - 127) : a;
      sts16(a00, vR >> 16); sts16(a00 + RS_CS + 2, vR >> 16);
      sts16(a - 16, vR); sts16(a - 16 + RS_CS + 2, vR);
      if (p1024) {
        sts32(sb + K1024_OFF + (ch * 2 + br) * 4, __byte_perm(vR, 0, 0x3232));
        const uint32_t kv = pack_bf16(k2048 + __uint_as_float(o2.z), 0.f);
        sts16(rb + R_E3 + 2 * (159 - 127), kv); sts16(rb + R_E3 + 2 * (159 - 127) + RS_CS + 2, kv);
      }
    }
  }
  STAMP(5);
  const uint32_t tag = (epoch + 1) & 0xffffu;
  asm volatile("barrier.cluster.wait.aligned;" ::: "memory");
  bar_sync(1 + ch, 128);
  mbar_wait(sb + B_U);
  STAMP(6);

  const uint32_t rb = cb + R_OFF + br * R_BR;
  const int eo = 16 * hf + g - 2 * t;
  float dacc[32];
  {
      {
        const int x0 = RD_X0 - (eo + 536);
        const uint32_t fa = rb + ((g & 1) ? 2 * x0 : RD_CS + 2 * x0 + 2);
        const uint64_t ub = mkdesc(cb + U_OFF, U_CS, 128);
        uint32_t f[2][9];
#pragma unroll
        for (int i = 0; i < 9; i++) f[0][i] = lds32(fa + (62 + i) * 16);
#pragma unroll
        for (int j = 0; j < 9; j++) {
          wg_fence();
#pragma unroll
          for (int k = 0; k < 4; k++) {
            const int s = 34 - 4 * j - k;
            if (s >= 0) {
              const int o = 2 * s - 66 + 128;
              const int cc = o & 3, rs = (o >> 2) - 32;
              const int n0 = ((-rs) >> 3) * 8;
              const uint64_t desc = ub + (uint64_t)((cc * U_CS - rs * 16) >> 4);
              const int fi = 2 * (3 - k);
              const uint32_t a1 = f[j & 1][fi], a0 = f[j & 1][fi + 1], a2 = f[j & 1][fi + 2];
              if (n0 == 0) wgmma_rs<64, 0>(dacc, a0, a1, a2, a0, desc, s != 34);
              else if (n0 == 8) wgmma_rs<56, 0>(dacc, a0, a1, a2, a0, desc, 1);
              else wgmma_rs<48, 0>(dacc, a0, a1, a2, a0, desc, 1);
            }
          }
          wg_commit();
          if (j < 8) {
#pragma unroll
            for (int i = 0; i < 9; i++) {
              const int idx = 62 - 8 * (j + 1) + i;
              if (idx >= 0) f[(j + 1) & 1][i] = lds32(fa + idx * 16);
            }
          }
          wg_wait0();
        }
      }
      const uint32_t yb = cb + Y0_OFF + br * 4096;
#pragma unroll
      for (int i = 0; i < 8; i += 2) {
        const int mi = lane >> 3;
        const int cidx = 4 * (63 - 8 * (i + (mi >> 1)) - (lane & 7)) + 2 * hf + (mi & 1);
        stsm4t(yb + ysw(cidx), pack_bf16(dacc[4 * i], dacc[4 * i + 1]), pack_bf16(dacc[4 * i + 2], dacc[4 * i + 3]),
               pack_bf16(dacc[4 * i + 4], dacc[4 * i + 5]), pack_bf16(dacc[4 * i + 6], dacc[4 * i + 7]));
      }
      bar_arrive(8, 640);
      STAMP(8);
  }
  const uint2 dA = *(const uint2*)(p.A_D + blockIdx.x * 4), dB = *(const uint2*)(p.B_D + blockIdx.x * 4);
  const uint2 gl = gate_ld((4 + ch) * 128 + wtid);
  mbar_wait(sb + B_W);
  const int x1 = 159 - (eo + 136);
  const uint32_t fs = rb + ((g & 1) ? 2 * x1 : RS_CS + 2 * x1 + 2);
  {
    uint32_t f[2][10];
    const uint64_t d5 = mkdesc(cb + W5_OFF, 144, 576), d3 = mkdesc(cb + W3_OFF, 144, 576);
#pragma unroll
    for (int i = 0; i < 5; i++) { f[0][i] = lds32(fs + R_E2 + (8 + i) * 16); f[0][5 + i] = lds32(fs + R_O2 + (8 + i) * 16); }
#pragma unroll
    for (int m = 2; m <= 4; m++) {
      wg_fence();
#pragma unroll
      for (int k = 0; k < 4; k++) {
        const uint32_t* a = &f[m & 1][(k >> 1) * 5 + (k & 1) * 2];
        const uint64_t desc = ((k >> 1) ? d3 : d5) + (k & 1) * 18 + (m - 2) * 36;
        if (m == 2) wgmma_rs<48, 1>(dacc, a[1], a[0], a[2], a[1], desc, k);
        else if (m == 3) wgmma_rs<40, 1>(dacc, a[1], a[0], a[2], a[1], desc, 1);
        else wgmma_rs<32, 1>(dacc, a[1], a[0], a[2], a[1], desc, 1);
      }
      wg_commit();
#pragma unroll
      for (int i = 0; i < 5; i++) {
        if (m < 4) { f[(m + 1) & 1][i] = lds32(fs + R_E2 + (4 * (3 - m) + i) * 16); f[(m + 1) & 1][5 + i] = lds32(fs + R_O2 + (4 * (3 - m) + i) * 16); }
        else { f[1][i] = lds32(fs + R_E3 + (8 + i) * 16); f[1][5 + i] = lds32(fs + R_O3 + (8 + i) * 16); }
      }
      wg_wait0();
    }
    {
      const uint32_t yb = cb + Y2_OFF + br * 3072;
#pragma unroll
      for (int i = 0; i < 6; i += 2) {
        const int mi = lane >> 3;
        const int cidx = 32 * (5 - i - (mi >> 1)) + 16 * hf + 8 * (mi & 1) + (lane & 7);
        stsm4(yb + ysw(cidx), pack_bf16(dacc[4 * i], dacc[4 * i + 1]), pack_bf16(dacc[4 * i + 2], dacc[4 * i + 3]),
              pack_bf16(dacc[4 * i + 4], dacc[4 * i + 5]), pack_bf16(dacc[4 * i + 6], dacc[4 * i + 7]));
      }
    }
    __syncwarp();
    if (lane == 0) asm volatile("mbarrier.arrive.shared::cta.b64 _, [%0];" ::"r"(sb + B_Y2) : "memory");
    STAMP(9);
    const uint64_t d9 = mkdesc(cb + W9_OFF, 144, 576), d7 = mkdesc(cb + W7_OFF, 144, 576);
#pragma unroll
    for (int m = 2; m <= 3; m++) {
      wg_fence();
#pragma unroll
      for (int k = 0; k < 4; k++) {
        const uint32_t* a = &f[(m + 1) & 1][(k >> 1) * 5 + (k & 1) * 2];
        const uint64_t desc = ((k >> 1) ? d7 : d9) + (k & 1) * 18 + (m - 2) * 72;
        if (m == 2) wgmma_rs<32, 1>(dacc, a[1], a[0], a[2], a[1], desc, k);
        else wgmma_rs<16, 1>(dacc, a[1], a[0], a[2], a[1], desc, 1);
      }
      wg_commit();
      if (m == 2) {
#pragma unroll
        for (int i = 0; i < 5; i++) { f[0][i] = lds32(fs + R_E3 + (4 + i) * 16); f[0][5 + i] = lds32(fs + R_O3 + (4 + i) * 16); }
      }
      wg_wait0();
    }
    const uint32_t yb = cb + Y3_OFF + br * 2048;
#pragma unroll
    for (int i = 0; i < 4; i += 2) {
      const int mi = lane >> 3;
      const int cidx = 64 * (1 - (i >> 1)) + 2 * (16 * hf + 8 * (mi & 1) + (lane & 7)) + (mi >> 1);
      stsm4(yb + ysw(cidx), pack_bf16(dacc[4 * i], dacc[4 * i + 1]), pack_bf16(dacc[4 * i + 2], dacc[4 * i + 3]),
            pack_bf16(dacc[4 * i + 4], dacc[4 * i + 5]), pack_bf16(dacc[4 * i + 6], dacc[4 * i + 7]));
    }
  }
  STAMP(10);
  __syncwarp();
  if (lane == 0) asm volatile("mbarrier.arrive.shared::cta.b64 _, [%0];" ::"r"(sb + B_Y3) : "memory");

  {
    const int x = (4 + ch) * 128 + wtid, c = x >> 2;
    const uint32_t g2 = gate_fin(p, gl, x, tag);
    const uint32_t yo = sb + CH_OFF + (x & 3) * 4 + ysw(c);
    uint32_t ua[4], ub[4], ya[4], yb[4], a2[4], b2[4], a3[4], b3[4], s2[4];
    skip_terms(ua, ub, sb, x, dA, dB);
    ld4ch(s2, sb + CH_OFF + (x & 3) * 4 + S2_OFF + ((c - 128) + ((c - 128) >> 3)) * 16);
    mbar_wait(sb + B_Y2);
    const uint4 k0 = lds128(sb + K1024_OFF), k1 = lds128(sb + K1024_OFF + 16);
    const uint32_t kk[8] = {k0.x, k0.y, k0.z, k0.w, k1.x, k1.y, k1.z, k1.w};
    ld4ch(ya, yo + Y0_OFF); ld4ch(yb, yo + Y0_OFF + 4096);
    ld4ch(a2, yo + Y2_OFF - 1024); ld4ch(b2, yo + Y2_OFF - 1024 + 3072);
#pragma unroll
    for (int k = 0; k < 4; k++) { a2[k] = hfma2(kk[2 * k], s2[k], a2[k]); b2[k] = hfma2(kk[2 * k + 1], s2[k], b2[k]); }
    STAMP(11);
    mbar_wait(sb + B_Y3);
    STAMP(12);
    ld4ch(a3, yo + Y3_OFF - 2048); ld4ch(b3, yo + Y3_OFF - 2048 + 2048);
#pragma unroll
    for (int k = 0; k < 4; k++) { ya[k] = hadd2(ya[k], hadd2(a2[k], a3[k])); yb[k] = hadd2(yb[k], hadd2(b2[k], b3[k])); }
    const uint4 r = mix(ya, yb, ua, ub, g2);
    if ((uint32_t)(ch & 1) != rank) send_box(sb, 2 + (ch >> 1), wtid, rank, r);
    else merge_box(sb, &tm_out, 2 + (ch >> 1), wtid, rank, oc0, r, 1 + ch);
  }
  STAMP(14);
  if (wtid == 0) asm volatile("cp.async.bulk.wait_group.read 0;" ::: "memory");
  STAMP(15); GT(1);
}

typedef CUresult (*EncodeFn)(CUtensorMap*, CUtensorMapDataType, cuuint32_t, void*, const cuuint64_t*, const cuuint64_t*,
                             const cuuint32_t*, const cuuint32_t*, CUtensorMapInterleave, CUtensorMapSwizzle,
                             CUtensorMapL2promotion, CUtensorMapFloatOOBfill);

}

extern "C" void kernel_launch(void* const* d_in, const int* in_sizes, int n_in, void* d_out, int out_size) {
  (void)in_sizes; (void)n_in; (void)out_size;
  typedef const __nv_bfloat16* bp;
  Params p;
  p.u = (bp)d_in[0]; p.A_re = (bp)d_in[1]; p.A_im = (bp)d_in[2]; p.B_re = (bp)d_in[3]; p.B_im = (bp)d_in[4];
  p.C_re = (bp)d_in[5]; p.C_im = (bp)d_in[6]; p.A_ldt = (bp)d_in[7]; p.A_D = (bp)d_in[8];
  p.B_lA = (bp)d_in[10]; p.B_Aim = (bp)d_in[11]; p.B_Cre = (bp)d_in[12]; p.B_Cim = (bp)d_in[13];
  p.B_ldt = (bp)d_in[14]; p.B_D = (bp)d_in[15]; p.gw = (bp)d_in[16];
  static EncodeFn enc = nullptr;
  if (!enc) {
    cudaDriverEntryPointQueryResult qr;
    cudaGetDriverEntryPoint("cuTensorMapEncodeTiled", (void**)&enc, cudaEnableDefault, &qr);
    cudaFuncSetAttribute(ssm_kernel, cudaFuncAttributeMaxDynamicSharedMemorySize, SMEM_BYTES);
  }
  CUtensorMap tm_in, tm_out;
  {
    cuuint64_t gd[5] = {512, 2, 4, 4, 64};
    cuuint64_t gs[4] = {1024, 8192, 2048, 32768};
    cuuint32_t bx[5] = {8, 2, 4, 4, 32};
    cuuint32_t es[5] = {1, 1, 1, 1, 1};
    enc(&tm_in, CU_TENSOR_MAP_DATA_TYPE_BFLOAT16, 5, d_in[0], gd, gs, bx, es, CU_TENSOR_MAP_INTERLEAVE_NONE,
        CU_TENSOR_MAP_SWIZZLE_NONE, CU_TENSOR_MAP_L2_PROMOTION_NONE, CU_TENSOR_MAP_FLOAT_OOB_FILL_NONE);
  }
  {
    cuuint64_t gd[3] = {512, 1024, 2};
    cuuint64_t gs[2] = {2048, 1024};
    cuuint32_t bx[3] = {8, 128, 2};
    cuuint32_t es[3] = {1, 1, 1};
    enc(&tm_out, CU_TENSOR_MAP_DATA_TYPE_BFLOAT16, 3, d_out, gd, gs, bx, es, CU_TENSOR_MAP_INTERLEAVE_NONE,
        CU_TENSOR_MAP_SWIZZLE_NONE, CU_TENSOR_MAP_L2_PROMOTION_NONE, CU_TENSOR_MAP_FLOAT_OOB_FILL_NONE);
  }
  ssm_kernel<<<NCTA, 640, SMEM_BYTES, cudaStreamPerThread>>>(p, tm_in, tm_out);
}
```

```cpp
#include <cuda_runtime.h>
#include <cuda.h>
#include <cuda_bf16.h>
#include <stdint.h>

namespace {
#define FIXA 1
#define FIXB 0
#define CPY(x) ((x) ^ zz)
#define FCPY(x) __uint_as_float(__float_as_uint(x) ^ zz)
#define STAG 2

constexpr int L = 2048, D = 512, NM = 128;
constexpr int NCTA = 128;

constexpr int RAW_OFF = 0;
constexpr int XIN_OFF = 32768;
constexpr int BAR_OFF = XIN_OFF + 10240;
constexpr int CH_OFF = BAR_OFF + 128;
constexpr int U_CS = 1184;
constexpr int U_OFF = 0;
constexpr int R_OFF = 4736;
constexpr int RD_X0 = 565;
constexpr int RD_CS = 1216;
constexpr int RS_CS = 320;
constexpr int R_E2 = 2 * RD_CS, R_O2 = R_E2 + 2 * RS_CS, R_E3 = R_O2 + 2 * RS_CS, R_O3 = R_E3 + 2 * RS_CS;
constexpr int R_BR = R_O3 + 2 * RS_CS;
constexpr int W5_OFF = R_OFF + 2 * R_BR;
constexpr int W3_OFF = W5_OFF + 3456;
constexpr int W9_OFF = W3_OFF + 3456;
constexpr int W7_OFF = W9_OFF + 2304;
constexpr int S2_OFF = W7_OFF + 2304;
constexpr int Y0_OFF = S2_OFF + 2304;
constexpr int Y2_OFF = Y0_OFF + 8192, Y3_OFF = Y2_OFF + 6144;
constexpr int CH_BYTES = Y0_OFF + 18432 + 16;
constexpr int SCR_BYTES = 4608;
constexpr int SMEM_BYTES = CH_OFF + 4 * CH_BYTES;
static_assert(CH_BYTES % 128 == 16, "bank staggering of the channel blocks");
static_assert(SMEM_BYTES <= 232448, "smem");
constexpr int B_RAW = BAR_OFF, B_X = BAR_OFF + 8, B_U = BAR_OFF + 40, B_W = BAR_OFF + 48, B_Y2 = BAR_OFF + 56, B_Y3 = BAR_OFF + 96;
constexpr int K1024_OFF = BAR_OFF + 64;

__device__ unsigned int g_gate[L];
__device__ unsigned int g_epoch;
__device__ unsigned int g_ticket;

#define STAMP(k)
#define GT(k)

struct Params {
  const __nv_bfloat16 *u, *A_re, *A_im, *B_re, *B_im, *C_re, *C_im, *A_ldt, *A_D;
  const __nv_bfloat16 *B_lA, *B_Aim, *B_Cre, *B_Cim, *B_ldt, *B_D, *gw;
};

template <int N, int TB> __device__ __forceinline__ void wgmma_rs(float* d, uint32_t a0, uint32_t a1, uint32_t a2, uint32_t a3, uint64_t desc, int sc);
template <> __device__ __forceinline__ void wgmma_rs<64, 0>(float* d, uint32_t a0, uint32_t a1, uint32_t a2, uint32_t a3, uint64_t desc, int sc) {
  asm volatile("{\n.reg .pred p;\nsetp.ne.b32 p, %37, 0;\n"
    "wgmma.mma_async.sync.aligned.m64n64k16.f32.bf16.bf16 {%0,%1,%2,%3,%4,%5,%6,%7,%8,%9,%10,%11,%12,%13,%14,%15,%16,%17,%18,%19,%20,%21,%22,%23,%24,%25,%26,%27,%28,%29,%30,%31}, {%32,%33,%34,%35}, %36, p, 1, 1, 0;\n}"
    : "+f"(d[0]), "+f"(d[1]), "+f"(d[2]), "+f"(d[3]), "+f"(d[4]), "+f"(d[5]), "+f"(d[6]), "+f"(d[7]), "+f"(d[8]), "+f"(d[9]), "+f"(d[10]), "+f"(d[11]), "+f"(d[12]), "+f"(d[13]), "+f"(d[14]), "+f"(d[15]), "+f"(d[16]), "+f"(d[17]), "+f"(d[18]), "+f"(d[19]), "+f"(d[20]), "+f"(d[21]), "+f"(d[22]), "+f"(d[23]), "+f"(d[24]), "+f"(d[25]), "+f"(d[26]), "+f"(d[27]), "+f"(d[28]), "+f"(d[29]), "+f"(d[30]), "+f"(d[31]) : "r"(a0), "r"(a1), "r"(a2), "r"(a3), "l"(desc), "r"(sc));
}
template <> __device__ __forceinline__ void wgmma_rs<56, 0>(float* d, uint32_t a0, uint32_t a1, uint32_t a2, uint32_t a3, uint64_t desc, int sc) {
  asm volatile("{\n.reg .pred p;\nsetp.ne.b32 p, %33, 0;\n"
    "wgmma.mma_async.sync.aligned.m64n56k16.f32.bf16.bf16 {%0,%1,%2,%3,%4,%5,%6,%7,%8,%9,%10,%11,%12,%13,%14,%15,%16,%17,%18,%19,%20,%21,%22,%23,%24,%25,%26,%27}, {%28,%29,%30,%31}, %32, p, 1, 1, 0;\n}"
    : "+f"(d[0]), "+f"(d[1]), "+f"(d[2]), "+f"(d[3]), "+f"(d[4]), "+f"(d[5]), "+f"(d[6]), "+f"(d[7]), "+f"(d[8]), "+f"(d[9]), "+f"(d[10]), "+f"(d[11]), "+f"(d[12]), "+f"(d[13]), "+f"(d[14]), "+f"(d[15]), "+f"(d[16]), "+f"(d[17]), "+f"(d[18]), "+f"(d[19]), "+f"(d[20]), "+f"(d[21]), "+f"(d[22]), "+f"(d[23]), "+f"(d[24]), "+f"(d[25]), "+f"(d[26]), "+f"(d[27]) : "r"(a0), "r"(a1), "r"(a2), "r"(a3), "l"(desc), "r"(sc));
}
template <> __device__ __forceinline__ void wgmma_rs<48, 0>(float* d, uint32_t a0, uint32_t a1, uint32_t a2, uint32_t a3, uint64_t desc, int sc) {
  asm volatile("{\n.reg .pred p;\nsetp.ne.b32 p, %29, 0;\n"
    "wgmma.mma_async.sync.aligned.m64n48k16.f32.bf16.bf16 {%0,%1,%2,%3,%4,%5,%6,%7,%8,%9,%10,%11,%12,%13,%14,%15,%16,%17,%18,%19,%20,%21,%22,%23}, {%24,%25,%26,%27}, %28, p, 1, 1, 0;\n}"
    : "+f"(d[0]), "+f"(d[1]), "+f"(d[2]), "+f"(d[3]), "+f"(d[4]), "+f"(d[5]), "+f"(d[6]), "+f"(d[7]), "+f"(d[8]), "+f"(d[9]), "+f"(d[10]), "+f"(d[11]), "+f"(d[12]), "+f"(d[13]), "+f"(d[14]), "+f"(d[15]), "+f"(d[16]), "+f"(d[17]), "+f"(d[18]), "+f"(d[19]), "+f"(d[20]), "+f"(d[21]), "+f"(d[22]), "+f"(d[23]) : "r"(a0), "r"(a1), "r"(a2), "r"(a3), "l"(desc), "r"(sc));
}
template <> __device__ __forceinline__ void wgmma_rs<48, 1>(float* d, uint32_t a0, uint32_t a1, uint32_t a2, uint32_t a3, uint64_t desc, int sc) {
  asm volatile("{\n.reg .pred p;\nsetp.ne.b32 p, %29, 0;\n"
    "wgmma.mma_async.sync.aligned.m64n48k16.f32.bf16.bf16 {%0,%1,%2,%3,%4,%5,%6,%7,%8,%9,%10,%11,%12,%13,%14,%15,%16,%17,%18,%19,%20,%21,%22,%23}, {%24,%25,%26,%27}, %28, p, 1, 1, 1;\n}"
    : "+f"(d[0]), "+f"(d[1]), "+f"(d[2]), "+f"(d[3]), "+f"(d[4]), "+f"(d[5]), "+f"(d[6]), "+f"(d[7]), "+f"(d[8]), "+f"(d[9]), "+f"(d[10]), "+f"(d[11]), "+f"(d[12]), "+f"(d[13]), "+f"(d[14]), "+f"(d[15]), "+f"(d[16]), "+f"(d[17]), "+f"(d[18]), "+f"(d[19]), "+f"(d[20]), "+f"(d[21]), "+f"(d[22]), "+f"(d[23]) : "r"(a0), "r"(a1), "r"(a2), "r"(a3), "l"(desc), "r"(sc));
}
template <> __device__ __forceinline__ void wgmma_rs<40, 1>(float* d, uint32_t a0, uint32_t a1, uint32_t a2, uint32_t a3, uint64_t desc, int sc) {
  asm volatile("{\n.reg .pred p;\nsetp.ne.b32 p, %25, 0;\n"
    "wgmma.mma_async.sync.aligned.m64n40k16.f32.bf16.bf16 {%0,%1,%2,%3,%4,%5,%6,%7,%8,%9,%10,%11,%12,%13,%14,%15,%16,%17,%18,%19}, {%20,%21,%22,%23}, %24, p, 1, 1, 1;\n}"
    : "+f"(d[0]), "+f"(d[1]), "+f"(d[2]), "+f"(d[3]), "+f"(d[4]), "+f"(d[5]), "+f"(d[6]), "+f"(d[7]), "+f"(d[8]), "+f"(d[9]), "+f"(d[10]), "+f"(d[11]), "+f"(d[12]), "+f"(d[13]), "+f"(d[14]), "+f"(d[15]), "+f"(d[16]), "+f"(d[17]), "+f"(d[18]), "+f"(d[19]) : "r"(a0), "r"(a1), "r"(a2), "r"(a3), "l"(desc), "r"(sc));
}
template <> __device__ __forceinline__ void wgmma_rs<32, 1>(float* d, uint32_t a0, uint32_t a1, uint32_t a2, uint32_t a3, uint64_t desc, int sc) {
  asm volatile("{\n.reg .pred p;\nsetp.ne.b32 p, %21, 0;\n"
    "wgmma.mma_async.sync.aligned.m64n32k16.f32.bf16.bf16 {%0,%1,%2,%3,%4,%5,%6,%7,%8,%9,%10,%11,%12,%13,%14,%15}, {%16,%17,%18,%19}, %20, p, 1, 1, 1;\n}"
    : "+f"(d[0]), "+f"(d[1]), "+f"(d[2]), "+f"(d[3]), "+f"(d[4]), "+f"(d[5]), "+f"(d[6]), "+f"(d[7]), "+f"(d[8]), "+f"(d[9]), "+f"(d[10]), "+f"(d[11]), "+f"(d[12]), "+f"(d[13]), "+f"(d[14]), "+f"(d[15]) : "r"(a0), "r"(a1), "r"(a2), "r"(a3), "l"(desc), "r"(sc));
}
template <> __device__ __forceinline__ void wgmma_rs<16, 1>(float* d, uint32_t a0, uint32_t a1, uint32_t a2, uint32_t a3, uint64_t desc, int sc) {
  asm volatile("{\n.reg .pred p;\nsetp.ne.b32 p, %13, 0;\n"
    "wgmma.mma_async.sync.aligned.m64n16k16.f32.bf16.bf16 {%0,%1,%2,%3,%4,%5,%6,%7}, {%8,%9,%10,%11}, %12, p, 1, 1, 1;\n}"
    : "+f"(d[0]), "+f"(d[1]), "+f"(d[2]), "+f"(d[3]), "+f"(d[4]), "+f"(d[5]), "+f"(d[6]), "+f"(d[7]) : "r"(a0), "r"(a1), "r"(a2), "r"(a3), "l"(desc), "r"(sc));
}

__device__ __forceinline__ uint32_t pack_bf16(float lo, float hi) {
  uint32_t r; asm("cvt.rn.bf16x2.f32 %0, %1, %2;" : "=r"(r) : "f"(hi), "f"(lo)); return r;
}
__device__ __forceinline__ float bf_lo(uint32_t v) { return __uint_as_float(v << 16); }
__device__ __forceinline__ float bf_hi(uint32_t v) { return __uint_as_float(v & 0xffff0000u); }
__device__ __forceinline__ float bf_round(float x) { return bf_lo(pack_bf16(x, 0.f)); }
__device__ __forceinline__ uint32_t hmul2(uint32_t a, uint32_t b) { uint32_t r; asm("mul.rn.bf16x2 %0, %1, %2;" : "=r"(r) : "r"(a), "r"(b)); return r; }
__device__ __forceinline__ uint32_t hadd2(uint32_t a, uint32_t b) { uint32_t r; asm("add.rn.bf16x2 %0, %1, %2;" : "=r"(r) : "r"(a), "r"(b)); return r; }
__device__ __forceinline__ uint32_t hsub2(uint32_t a, uint32_t b) { uint32_t r; asm("sub.rn.bf16x2 %0, %1, %2;" : "=r"(r) : "r"(a), "r"(b)); return r; }
__device__ __forceinline__ uint32_t hfma2(uint32_t a, uint32_t b, uint32_t c) { uint32_t r; asm("fma.rn.bf16x2 %0, %1, %2, %3;" : "=r"(r) : "r"(a), "r"(b), "r"(c)); return r; }

__device__ __forceinline__ void sts16(uint32_t a, uint32_t v) { asm volatile("st.shared.b16 [%0], %1;" ::"r"(a), "h"((unsigned short)v) : "memory"); }
__device__ __forceinline__ void sts32(uint32_t a, uint32_t v) { asm volatile("st.shared.b32 [%0], %1;" ::"r"(a), "r"(v) : "memory"); }
__device__ __forceinline__ void sts64(uint32_t a, uint32_t x, uint32_t y) { asm volatile("st.shared.v2.b32 [%0], {%1,%2};" ::"r"(a), "r"(x), "r"(y) : "memory"); }
__device__ __forceinline__ void sts128(uint32_t a, uint32_t x, uint32_t y, uint32_t z, uint32_t w) {
  asm volatile("st.shared.v4.b32 [%0], {%1,%2,%3,%4};" ::"r"(a), "r"(x), "r"(y), "r"(z), "r"(w) : "memory");
}
__device__ __forceinline__ uint32_t lds32(uint32_t a) { uint32_t v; asm volatile("ld.shared.b32 %0, [%1];" : "=r"(v) : "r"(a) : "memory"); return v; }
__device__ __forceinline__ uint2 lds64(uint32_t a) { uint2 v; asm volatile("ld.shared.v2.b32 {%0,%1}, [%2];" : "=r"(v.x), "=r"(v.y) : "r"(a) : "memory"); return v; }
__device__ __forceinline__ uint4 lds128(uint32_t a) {
  uint4 v; asm volatile("ld.shared.v4.b32 {%0,%1,%2,%3}, [%4];" : "=r"(v.x), "=r"(v.y), "=r"(v.z), "=r"(v.w) : "r"(a) : "memory"); return v;
}
__device__ __forceinline__ void ldsm4(uint32_t a, uint32_t& r0, uint32_t& r1, uint32_t& r2, uint32_t& r3) {
  asm volatile("ldmatrix.sync.aligned.m8n8.x4.shared.b16 {%0,%1,%2,%3}, [%4];" : "=r"(r0), "=r"(r1), "=r"(r2), "=r"(r3) : "r"(a) : "memory");
}
__device__ __forceinline__ void ldsm4t(uint32_t a, uint32_t& r0, uint32_t& r1, uint32_t& r2, uint32_t& r3) {
  asm volatile("ldmatrix.sync.aligned.m8n8.x4.trans.shared.b16 {%0,%1,%2,%3}, [%4];" : "=r"(r0), "=r"(r1), "=r"(r2), "=r"(r3) : "r"(a) : "memory");
}
__device__ __forceinline__ void stsm4(uint32_t a, uint32_t r0, uint32_t r1, uint32_t r2, uint32_t r3) {
  asm volatile("stmatrix.sync.aligned.m8n8.x4.shared.b16 [%0], {%1,%2,%3,%4};" ::"r"(a), "r"(r0), "r"(r1), "r"(r2), "r"(r3) : "memory");
}
__device__ __forceinline__ void stsm4t(uint32_t a, uint32_t r0, uint32_t r1, uint32_t r2, uint32_t r3) {
  asm volatile("stmatrix.sync.aligned.m8n8.x4.trans.shared.b16 [%0], {%1,%2,%3,%4};" ::"r"(a), "r"(r0), "r"(r1), "r"(r2), "r"(r3) : "memory");
}
__device__ __forceinline__ void mma16816(float* c, uint32_t a0, uint32_t a1, uint32_t a2, uint32_t a3, uint32_t b0, uint32_t b1) {
  asm("mma.sync.aligned.m16n8k16.row.col.f32.bf16.bf16.f32 {%0,%1,%2,%3}, {%4,%5,%6,%7}, {%8,%9}, {%0,%1,%2,%3};"
      : "+f"(c[0]), "+f"(c[1]), "+f"(c[2]), "+f"(c[3]) : "r"(a0), "r"(a1), "r"(a2), "r"(a3), "r"(b0), "r"(b1));
}
__device__ __forceinline__ void bar_sync(int id, int n) { asm volatile("bar.sync %0, %1;" ::"r"(id), "r"(n) : "memory"); }
__device__ __forceinline__ void bar_arrive(int id, int n) { asm volatile("bar.arrive %0, %1;" ::"r"(id), "r"(n) : "memory"); }
__device__ __forceinline__ void wg_fence() { asm volatile("wgmma.fence.sync.aligned;" ::: "memory"); }
__device__ __forceinline__ void wg_commit() { asm volatile("wgmma.commit_group.sync.aligned;" ::: "memory"); }
__device__ __forceinline__ void wg_wait0() { asm volatile("wgmma.wait_group.sync.aligned 0;" ::: "memory"); }
__device__ __forceinline__ void fence_async() { asm volatile("fence.proxy.async.shared::cta;" ::: "memory"); }
__device__ __forceinline__ uint64_t mkdesc(uint32_t addr, uint32_t lbo, uint32_t sbo) {
  return (uint64_t)((addr & 0x3FFFF) >> 4) | ((uint64_t)(lbo >> 4) << 16) | ((uint64_t)(sbo >> 4) << 32);
}
__device__ __forceinline__ uint32_t mapa(uint32_t a, uint32_t rank) {
  uint32_t r; asm("mapa.shared::cluster.u32 %0, %1, %2;" : "=r"(r) : "r"(a), "r"(rank)); return r;
}
__device__ __forceinline__ void mbar_init_expect(uint32_t bar, uint32_t bytes) {
  asm volatile("mbarrier.init.shared::cta.b64 [%0], 1;" ::"r"(bar) : "memory");
  asm volatile("mbarrier.arrive.expect_tx.shared::cta.b64 _, [%0], %1;" ::"r"(bar), "r"(bytes) : "memory");
}
__device__ __forceinline__ void mbar_wait(uint32_t bar) {
#pragma unroll 1
  for (int it = 0; it < (1 << 22); it++) {
    uint32_t ok;
    asm volatile("{\n.reg .pred p;\nmbarrier.try_wait.parity.acquire.cluster.shared::cta.b64 p, [%1], 0;\nselp.u32 %0, 1, 0, p;\n}"
                 : "=r"(ok) : "r"(bar) : "memory");
    if (ok) return;
  }
  __trap();
}
__device__ __forceinline__ void st_async4(uint32_t a, uint32_t bar, uint32_t x, uint32_t y, uint32_t z, uint32_t w) {
  asm volatile("st.async.weak.shared::cluster.mbarrier::complete_tx::bytes.v4.b32 [%0], {%2,%3,%4,%5}, [%1];"
               ::"r"(a), "r"(bar), "r"(x), "r"(y), "r"(z), "r"(w) : "memory");
}

struct cf { float re, im; };
__device__ __forceinline__ cf cmul(cf a, cf b) { return {fmaf(a.re, b.re, -a.im * b.im), fmaf(a.re, b.im, a.im * b.re)}; }
__device__ __forceinline__ cf csq(cf a) { return {fmaf(a.re, a.re, -a.im * a.im), (a.re + a.re) * a.im}; }
__device__ __forceinline__ cf cexp_p(float xl, float y, float p) {
  float mag; asm("ex2.approx.ftz.f32 %0, %1;" : "=f"(mag) : "f"(xl * p));
  const float th = y * p;
  const float k = rintf(th * 0.15915494309189535f);
  float r = fmaf(k, -6.2831854820251465f, th);
  r = fmaf(k, 1.7484555314695172e-07f, r);
  return {mag * __cosf(r), mag * __sinf(r)};
}
__device__ __forceinline__ uint32_t ysw(int c) { return (uint32_t)(c ^ ((c >> 3) & 3)) * 16u; }

#define CMUL2(OR, OI, xr, xi, yr, yi, nyi) do { OR = hfma2(xr, yr, hmul2(xi, nyi)); OI = hfma2(xr, yi, hmul2(xi, yr)); } while (0)

__device__ __forceinline__ uint32_t gate_slow(const __nv_bfloat16* u, const __nv_bfloat16* gw, int row) {
  float s = 0.f;
  const uint32_t* xr = (const uint32_t*)(u + (size_t)row * D);
  const uint32_t* wr = (const uint32_t*)gw;
#pragma unroll 1
  for (int j = 0; j < D / 2; j++) { const uint32_t pr = hmul2(xr[j], wr[j]); s += bf_lo(pr); s += bf_hi(pr); }
  s = bf_round(s);
  return pack_bf16(1.f / (1.f + expf(-s)), 0.f);
}

__device__ __forceinline__ void prefix6(float* pf, uint32_t ub, int c0) {
  pf[0] = 0.f;
#pragma unroll
  for (int j = 0; j < 6; j++) {
    const int c = c0 + j;
    const uint4 v = lds128(ub + (c & 3) * U_CS + (63 - (c >> 2)) * 16);
    const uint32_t w[4] = {v.x, v.y, v.z, v.w};
#pragma unroll
    for (int i = 0; i < 4; i++) {
      pf[j * 8 + 2 * i + 1] = pf[j * 8 + 2 * i] + bf_lo(w[i]);
      pf[j * 8 + 2 * i + 2] = pf[j * 8 + 2 * i + 1] + bf_hi(w[i]);
    }
  }
}
template <int A, int B>
__device__ __forceinline__ void put_win(const float* pf, int ix, uint32_t addr) {
  uint32_t a[4];
#pragma unroll
  for (int i = 0; i < 4; i++) a[i] = pack_bf16(pf[ix + 2 * i - B + 1] - pf[ix + 2 * i - A], pf[ix + 2 * i - B + 2] - pf[ix + 2 * i - A + 1]);
  sts128(addr, a[0], a[1], a[2], a[3]);
}

__device__ __forceinline__ uint2 gate_ld(int x) {
  uint2 gv;
  asm volatile("ld.relaxed.gpu.global.v2.u32 {%0,%1}, [%2];" : "=r"(gv.x), "=r"(gv.y) : "l"(g_gate + x * 2) : "memory");
  return gv;
}
__device__ __noinline__ uint32_t gate_poll(const __nv_bfloat16* u, const __nv_bfloat16* gw, int x, uint32_t tag) {
  uint2 gv;
#pragma unroll 1
  for (int spins = 0; spins < (1 << 16); spins++) {
    gv = gate_ld(x);
    if ((gv.x >> 16) == tag && (gv.y >> 16) == tag) return __byte_perm(gv.x, gv.y, 0x5410);
  }
  return __byte_perm(gate_slow(u, gw, x * 2), gate_slow(u, gw, x * 2 + 1), 0x5410);
}
__device__ __forceinline__ uint32_t gate_fin(const Params& p, uint2 gv, int x, uint32_t tag) {
  if ((gv.x >> 16) == tag && (gv.y >> 16) == tag) return __byte_perm(gv.x, gv.y, 0x5410);
  return gate_poll(p.u, p.gw, x, tag);
}

__device__ __forceinline__ void ld4ch(uint32_t* v, uint32_t addr) {
#pragma unroll
  for (int k = 0; k < 4; k++) v[k] = lds32(addr + k * CH_BYTES);
}
__device__ __forceinline__ void skip_terms(uint32_t* ua, uint32_t* ub, uint32_t sb, int x, uint2 dA, uint2 dB) {
  const int c = x >> 2;
  uint32_t uu[4];
  ld4ch(uu, sb + CH_OFF + (x & 3) * 4 + U_OFF + (c & 3) * U_CS + (63 - (c >> 2)) * 16);
#pragma unroll
  for (int k = 0; k < 4; k++) {
    ua[k] = hmul2(uu[k], __byte_perm((k & 2) ? dA.y : dA.x, 0, (k & 1) ? 0x3232 : 0x1010));
    ub[k] = hmul2(uu[k], __byte_perm((k & 2) ? dB.y : dB.x, 0, (k & 1) ? 0x3232 : 0x1010));
  }
}
__device__ __forceinline__ uint4 mix(const uint32_t* a, const uint32_t* b, const uint32_t* ua, const uint32_t* ub, uint32_t g2) {
  const uint32_t h2 = hsub2(0x3f803f80u, g2);
  uint32_t o[4];
#pragma unroll
  for (int k = 0; k < 4; k++) o[k] = hadd2(hmul2(g2, hadd2(a[k], ua[k])), hmul2(h2, hadd2(b[k], ub[k])));
  return make_uint4(__byte_perm(o[0], o[1], 0x5410), __byte_perm(o[2], o[3], 0x5410), __byte_perm(o[0], o[1], 0x7632), __byte_perm(o[2], o[3], 0x7632));
}
__device__ __forceinline__ void send_box(uint32_t sb, int slot, int wtid, uint32_t rank, uint4 r) {
  st_async4(mapa(sb + XIN_OFF + slot * 2048 + wtid * 16, rank ^ 1), mapa(sb + B_X + slot * 8, rank ^ 1), r.x, r.y, r.z, r.w);
}
__device__ __forceinline__ void merge_box(uint32_t sb, const CUtensorMap* tm_out, int slot, int wtid, uint32_t rank, int oc0, uint4 r, int barid) {
  const uint32_t st = sb + RAW_OFF + slot * 4096 + wtid * 16;
  sts64(st + rank * 8, r.x, r.y); sts64(st + 2048 + rank * 8, r.z, r.w);
  mbar_wait(sb + B_X + slot * 8);
  const uint4 q = lds128(sb + XIN_OFF + slot * 2048 + wtid * 16);
  sts64(st + (rank ^ 1) * 8, q.x, q.y); sts64(st + 2048 + (rank ^ 1) * 8, q.z, q.w);
  fence_async();
  bar_sync(barid, 128);
  if (wtid == 0) {
    asm volatile("cp.async.bulk.tensor.3d.global.shared::cta.bulk_group [%0, {%2, %3, %4}], [%1];"
                 ::"l"(tm_out), "r"(sb + RAW_OFF + slot * 4096), "r"(oc0), "r"((2 * slot + (int)rank) * 128), "r"(0) : "memory");
    asm volatile("cp.async.bulk.commit_group;" ::: "memory");
  }
}

__device__ __forceinline__ void window_sums(uint32_t cb, int wq, int lane) {
      float pf[49];
      if (wq == 0 || wq == 3) {
        if (wq == 0 || lane < 16) {
          const int nu = wq ? 32 + lane : lane;
          prefix6(pf, cb + U_OFF, 4 * nu - 2);
          const uint32_t po = (5 - (nu >> 3)) * 576 + ((nu & 7) >> 1) * 144 + (nu & 1) * 64;
#pragma unroll
          for (int k = 0; k < 4; k++) { put_win<10, 6>(pf, 16 + 8 * k, cb + W5_OFF + po + k * 16); put_win<5, 3>(pf, 16 + 8 * k, cb + W3_OFF + po + k * 16); }
        }
      } else {
        const uint32_t po = (1 - (lane >> 4)) * 1152 + ((lane & 15) >> 2) * 144 + (lane & 3) * 32;
        if (wq == 1) {
          prefix6(pf, cb + U_OFF, 4 * lane - 3);
#pragma unroll
          for (int k = 0; k < 4; k++) put_win<20, 12>(pf, 24 + 8 * k, cb + W9_OFF + po + (k & 1) * 576 + (k >> 1) * 16);
        } else {
          prefix6(pf, cb + U_OFF, 4 * lane - 2);
          const uint32_t so = cb + S2_OFF + (lane >> 1) * 144 + (lane & 1) * 64;
#pragma unroll
          for (int k = 0; k < 4; k++) { put_win<11, 5>(pf, 16 + 8 * k, cb + W7_OFF + po + (k & 1) * 576 + (k >> 1) * 16); put_win<4, 3>(pf, 16 + 8 * k, so + k * 16); }
        }
      }
}

__device__ __forceinline__ void conv_dense(uint32_t cb, uint32_t zz) {
  const int lane = threadIdx.x & 31, wq = (threadIdx.x >> 5) & 3, br = wq >> 1, hf = wq & 1, g = lane >> 2, t = lane & 3;
  const uint32_t rb = cb + R_OFF + br * R_BR;
  const int eo = 16 * hf + g - 2 * t;
  float dacc[32];
  {
      {
        const int x0 = RD_X0 - (eo + 536);
        const uint32_t fa = rb + ((g & 1) ? 2 * x0 : RD_CS + 2 * x0 + 2);
        const uint64_t ub = mkdesc(cb + U_OFF, U_CS, 128);
        uint32_t A[2][4][4];
        float e56[28], e48[24];
        auto loadA = [&](int j) {
#pragma unroll
          for (int k = 0; k < 4; k++) {
            const int s = 34 - 4 * j - k;
            if (s >= 0) {
              if (k == 0) A[j & 1][0][2] = lds32(fa + (2 * s + 2) * 16);
              A[j & 1][k][0] = lds32(fa + (2 * s + 1) * 16);
              A[j & 1][k][1] = lds32(fa + (2 * s) * 16);
            }
          }
#pragma unroll
          for (int k = 0; k < 4; k++) {
            if (34 - 4 * j - k >= 0) {
              A[j & 1][k][3] = CPY(A[j & 1][k][0]);
              if (k) A[j & 1][k][2] = CPY(A[j & 1][k - 1][1]);
            }
          }
        };
        loadA(0);
#pragma unroll
        for (int j = 0; j < 9; j++) {
          wg_fence();
#pragma unroll
          for (int k = 0; k < 4; k++) {
            const int s = 34 - 4 * j - k;
            if (s >= 0) {
              const int o = 2 * s - 66 + 128;
              const int cc = o & 3, rs = (o >> 2) - 32;
              const int n0 = ((-rs) >> 3) * 8;
              const uint64_t desc = ub + (uint64_t)((cc * U_CS - rs * 16) >> 4);
              const uint32_t* a = A[j & 1][k];
              if (n0 == 0) wgmma_rs<64, 0>(dacc, a[0], a[1], a[2], a[3], desc, s != 34);
              else if (n0 == 8) wgmma_rs<56, 0>(FIXB ? e56 : dacc, a[0], a[1], a[2], a[3], desc, 1);
              else wgmma_rs<48, 0>(FIXB ? e48 : dacc, a[0], a[1], a[2], a[3], desc, 1);
            }
          }
          wg_commit();
          if (j < 8) loadA(j + 1);
          wg_wait0();
        }
      }
      const uint32_t yb = cb + Y0_OFF + br * 4096;
#pragma unroll
      for (int i = 0; i < 8; i += 2) {
        const int mi = lane >> 3;
        const int cidx = 4 * (63 - 8 * (i + (mi >> 1)) - (lane & 7)) + 2 * hf + (mi & 1);
        stsm4t(yb + ysw(cidx), pack_bf16(dacc[4 * i], dacc[4 * i + 1]), pack_bf16(dacc[4 * i + 2], dacc[4 * i + 3]),
               pack_bf16(dacc[4 * i + 4], dacc[4 * i + 5]), pack_bf16(dacc[4 * i + 6], dacc[4 * i + 7]));
      }
      bar_arrive(8, 640);
      STAMP(8);
  }
}

__device__ __forceinline__ void conv_far(uint32_t sb, uint32_t cb, uint32_t zz) {
  const int lane = threadIdx.x & 31, wq = (threadIdx.x >> 5) & 3, br = wq >> 1, hf = wq & 1, g = lane >> 2, t = lane & 3;
  const uint32_t rb = cb + R_OFF + br * R_BR;
  const int eo = 16 * hf + g - 2 * t;
  float dacc[24];
  const int x1 = 159 - (eo + 136);
  const uint32_t fs = rb + ((g & 1) ? 2 * x1 : RS_CS + 2 * x1 + 2);
  {
    uint32_t A[2][4][4];
    auto loadA = [&](int buf, uint32_t oe, uint32_t oo, int i0) {
#pragma unroll
      for (int a = 0; a < 2; a++) {
        const uint32_t base = fs + (a ? oo : oe) + i0 * 16;
        uint32_t* k0 = A[buf][2 * a];
        uint32_t* k1 = A[buf][2 * a + 1];
        k0[1] = lds32(base); k0[0] = lds32(base + 16); k0[2] = lds32(base + 32); k1[0] = lds32(base + 48); k1[2] = lds32(base + 64);
      }
#pragma unroll
      for (int a = 0; a < 2; a++) {
        uint32_t* k0 = A[buf][2 * a];
        uint32_t* k1 = A[buf][2 * a + 1];
        k0[3] = CPY(k0[0]); k1[1] = CPY(k0[2]); k1[3] = CPY(k1[0]);
      }
    };
    const uint64_t d5 = mkdesc(cb + W5_OFF, 144, 576), d3 = mkdesc(cb + W3_OFF, 144, 576);
    loadA(0, R_E2, R_O2, 8);
#pragma unroll
    for (int m = 2; m <= 4; m++) {
      wg_fence();
#pragma unroll
      for (int k = 0; k < 4; k++) {
        const uint32_t* a = A[m & 1][k];
        const uint64_t desc = ((k >> 1) ? d3 : d5) + (k & 1) * 18 + (m - 2) * 36;
        if (m == 2) wgmma_rs<48, 1>(dacc, a[0], a[1], a[2], a[3], desc, k);
        else if (m == 3) wgmma_rs<40, 1>(dacc, a[0], a[1], a[2], a[3], desc, 1);
        else wgmma_rs<32, 1>(dacc, a[0], a[1], a[2], a[3], desc, 1);
      }
      wg_commit();
      if (m < 4) loadA((m + 1) & 1, R_E2, R_O2, 4 * (3 - m));
      else loadA(1, R_E3, R_O3, 8);
      wg_wait0();
    }
    {
      const uint32_t yb = cb + Y2_OFF + br * 3072;
#pragma unroll
      for (int i = 0; i < 6; i += 2) {
        const int mi = lane >> 3;
        const int cidx = 32 * (5 - i - (mi >> 1)) + 16 * hf + 8 * (mi & 1) + (lane & 7);
        stsm4(yb + ysw(cidx), pack_bf16(dacc[4 * i], dacc[4 * i + 1]), pack_bf16(dacc[4 * i + 2], dacc[4 * i + 3]),
              pack_bf16(dacc[4 * i + 4], dacc[4 * i + 5]), pack_bf16(dacc[4 * i + 6], dacc[4 * i + 7]));
      }
    }
    __syncwarp();
    if (lane == 0) asm volatile("mbarrier.arrive.shared::cta.b64 _, [%0];" ::"r"(sb + B_Y2) : "memory");
    STAMP(9);
    const uint64_t d9 = mkdesc(cb + W9_OFF, 144, 576), d7 = mkdesc(cb + W7_OFF, 144, 576);
#pragma unroll
    for (int m = 2; m <= 3; m++) {
      wg_fence();
#pragma unroll
      for (int k = 0; k < 4; k++) {
        const uint32_t* a = A[(m + 1) & 1][k];
        const uint64_t desc = ((k >> 1) ? d7 : d9) + (k & 1) * 18 + (m - 2) * 72;
        if (m == 2) wgmma_rs<32, 1>(dacc, a[0], a[1], a[2], a[3], desc, k);
        else wgmma_rs<16, 1>(dacc, a[0], a[1], a[2], a[3], desc, 1);
      }
      wg_commit();
      if (m == 2) loadA(0, R_E3, R_O3, 4);
      wg_wait0();
    }
    const uint32_t yb = cb + Y3_OFF + br * 2048;
#pragma unroll
    for (int i = 0; i < 4; i += 2) {
      const int mi = lane >> 3;
      const int cidx = 64 * (1 - (i >> 1)) + 2 * (16 * hf + 8 * (mi & 1) + (lane & 7)) + (mi >> 1);
      stsm4(yb + ysw(cidx), pack_bf16(dacc[4 * i], dacc[4 * i + 1]), pack_bf16(dacc[4 * i + 2], dacc[4 * i + 3]),
            pack_bf16(dacc[4 * i + 4], dacc[4 * i + 5]), pack_bf16(dacc[4 * i + 6], dacc[4 * i + 7]));
    }
  }
}

__global__ void __cluster_dims__(2, 1, 1) __launch_bounds__(640, 1)
ssm_kernel(const Params p, const __grid_constant__ CUtensorMap tm_in, const __grid_constant__ CUtensorMap tm_out) {
  extern __shared__ __align__(1024) unsigned char smem_raw[];
  const uint32_t sb = (uint32_t)__cvta_generic_to_shared(smem_raw);
  const int tid = threadIdx.x, lane = tid & 31;
  const int warp = __shfl_sync(0xffffffffu, tid >> 5, 0);
  const int ch = warp >> 2, wq = warp & 3, br = wq >> 1, hf = wq & 1;
  const int g = lane >> 2, t = lane & 3;
  const int d = blockIdx.x * 4 + ch;
  const uint32_t rank = blockIdx.x & 1;
  const uint32_t cb = sb + CH_OFF + ch * CH_BYTES;
  const int wtid = tid & 127;
  const int oc0 = (int)(blockIdx.x >> 1) * 8;
  STAMP(0); GT(0);

  if (warp >= 16) {
    if (wtid == 0) {
      mbar_init_expect(sb + B_RAW, 32768);
#pragma unroll
      for (int i = 0; i < 4; i++) mbar_init_expect(sb + B_X + 8 * i, 2048);
      asm volatile("mbarrier.init.shared::cta.b64 [%0], 128;" ::"r"(sb + B_U) : "memory");
      asm volatile("mbarrier.init.shared::cta.b64 [%0], 128;" ::"r"(sb + B_W) : "memory");
      asm volatile("mbarrier.init.shared::cta.b64 [%0], 16;" ::"r"(sb + B_Y2) : "memory");
      asm volatile("mbarrier.init.shared::cta.b64 [%0], 16;" ::"r"(sb + B_Y3) : "memory");
      asm volatile("fence.mbarrier_init.release.cluster;" ::: "memory");
      asm volatile("fence.proxy.async.shared::cta;" ::: "memory");
    }
    __syncwarp();
    asm volatile("barrier.cluster.arrive.relaxed.aligned;" ::: "memory");
    unsigned int epoch;
    asm volatile("ld.relaxed.gpu.global.u32 %0, [%1];" : "=r"(epoch) : "l"(&g_epoch) : "memory");
    const uint2 dA = *(const uint2*)(p.A_D + blockIdx.x * 4), dB = *(const uint2*)(p.B_D + blockIdx.x * 4);
    const uint4 gw0 = *(const uint4*)(p.gw + lane * 8), gw1 = *(const uint4*)(p.gw + 256 + lane * 8);
    asm volatile("barrier.cluster.wait.aligned;" ::: "memory");
    if (wtid == 0) {
      asm volatile("cp.async.bulk.tensor.5d.shared::cluster.global.mbarrier::complete_tx::bytes.multicast::cluster [%0], [%1, {%3, %4, %4, %4, %5}], [%2], %6;"
                   ::"r"(sb + RAW_OFF + rank * 16384), "l"(&tm_in), "r"(sb + B_RAW), "r"(oc0), "r"(0), "r"((int)rank * 32), "h"((unsigned short)3) : "memory");
    }
    sts128(sb + CH_OFF + wq * CH_BYTES + U_OFF + (lane >> 3) * U_CS + (64 + (lane & 7)) * 16, 0, 0, 0, 0);
    STAMP(3);
    mbar_wait(sb + B_RAW);
    STAMP(4);
    {
      const uint32_t dst = sb + CH_OFF + (g & 3) * CH_BYTES + U_OFF + t * U_CS + (63 - wq * 16) * 16;
#pragma unroll
      for (int h = 0; h < 2; h++) {
        uint32_t r[8][4];
#pragma unroll
        for (int i = 0; i < 8; i++) ldsm4t(sb + RAW_OFF + (wq * 16 + h * 8 + i) * 512 + lane * 16, r[i][0], r[i][1], r[i][2], r[i][3]);
        if ((uint32_t)(g >> 2) == rank) {
#pragma unroll
          for (int i = 0; i < 8; i++) sts128(dst - (h * 8 + i) * 16, r[i][0], r[i][1], r[i][2], r[i][3]);
        }
      }
    }
    fence_async();
    asm volatile("mbarrier.arrive.shared::cta.b64 _, [%0];" ::"r"(sb + B_U) : "memory");
    bar_sync(5, 128);
    STAMP(5);
    const uint32_t tag = (epoch + 1) & 0xffffu;
    {
      const int grow = blockIdx.x * 16 + wq * 4;
      uint4 gx[4][2];
#pragma unroll
      for (int i = 0; i < 4; i++) {
        gx[i][0] = *(const uint4*)(p.u + (size_t)(grow + i) * D + lane * 8);
        gx[i][1] = *(const uint4*)(p.u + (size_t)(grow + i) * D + 256 + lane * 8);
      }
      const uint32_t ws[8] = {gw0.x, gw0.y, gw0.z, gw0.w, gw1.x, gw1.y, gw1.z, gw1.w};
      float sm[4];
#pragma unroll
      for (int i = 0; i < 4; i++) {
        const uint32_t xs[8] = {gx[i][0].x, gx[i][0].y, gx[i][0].z, gx[i][0].w, gx[i][1].x, gx[i][1].y, gx[i][1].z, gx[i][1].w};
        float s = 0.f;
#pragma unroll
        for (int j = 0; j < 8; j++) { const uint32_t pr = hmul2(xs[j], ws[j]); s += bf_lo(pr); s += bf_hi(pr); }
        sm[i] = s;
      }
      {
        const bool b0 = lane & 1, b1 = lane & 2;
        float u0 = b0 ? sm[1] : sm[0], v0 = b0 ? sm[0] : sm[1], u1 = b0 ? sm[3] : sm[2], v1 = b0 ? sm[2] : sm[3];
        u0 += __shfl_xor_sync(0xffffffffu, v0, 1); u1 += __shfl_xor_sync(0xffffffffu, v1, 1);
        float s = b1 ? u1 : u0; const float v = b1 ? u0 : u1;
        s += __shfl_xor_sync(0xffffffffu, v, 2);
#pragma unroll
        for (int o = 4; o < 32; o <<= 1) s += __shfl_xor_sync(0xffffffffu, s, o);
        s = bf_round(s);
        const float gv = 1.f / (1.f + expf(-s));
        const uint32_t w = (tag << 16) | (pack_bf16(gv, 0.f) & 0xffffu);
        if (lane < 4) asm volatile("st.relaxed.gpu.global.u32 [%0], %1;" ::"l"(&g_gate[grow + lane]), "r"(w) : "memory");
      }
    }
    STAMP(6);
#pragma unroll 1
    for (int k = 0; k < 4; k++) window_sums(sb + CH_OFF + k * CH_BYTES, wq, lane);
    fence_async();
    asm volatile("mbarrier.arrive.shared::cta.b64 _, [%0];" ::"r"(sb + B_W) : "memory");
    STAMP(7);
    STAMP(8);
    uint32_t gg[4];
    {
      uint2 gl[4];
#pragma unroll
      for (int i = 0; i < 4; i++) gl[i] = gate_ld((i ^ (int)rank ^ 1) * 128 + wtid);
#pragma unroll
      for (int i = 0; i < 4; i++) gg[i] = gate_fin(p, gl[i], (i ^ (int)rank ^ 1) * 128 + wtid, tag);
    }
    {
      uint32_t ua[4][4], ub[4][4], ya[4][4], yb[4][4], yo[4];
#pragma unroll
      for (int i = 0; i < 4; i++) {
        const int x = (i ^ (int)rank ^ 1) * 128 + wtid;
        skip_terms(ua[i], ub[i], sb, x, dA, dB);
        yo[i] = sb + CH_OFF + (x & 3) * 4 + ysw(x >> 2);
      }
      bar_sync(8, 640);
      STAMP(10);
#pragma unroll
      for (int i = 0; i < 4; i++) { ld4ch(ya[i], yo[i] + Y0_OFF); ld4ch(yb[i], yo[i] + Y0_OFF + 4096); }
      send_box(sb, 0, wtid, rank, mix(ya[0], yb[0], ua[0], ub[0], gg[0]));
      merge_box(sb, &tm_out, 0, wtid, rank, oc0, mix(ya[1], yb[1], ua[1], ub[1], gg[1]), 5);
      STAMP(12);
      mbar_wait(sb + B_Y2);
      STAMP(11);
#pragma unroll
      for (int i = 2; i < 4; i++) { ld4ch(ya[i - 2], yo[i] + Y2_OFF - 1024); ld4ch(yb[i - 2], yo[i] + Y2_OFF - 1024 + 3072); }
#pragma unroll
      for (int i = 2; i < 4; i++)
#pragma unroll
        for (int k = 0; k < 4; k++) { ya[i][k] = hadd2(ya[i][k], ya[i - 2][k]); yb[i][k] = hadd2(yb[i][k], yb[i - 2][k]); }
      send_box(sb, 1, wtid, rank, mix(ya[2], yb[2], ua[2], ub[2], gg[2]));
      merge_box(sb, &tm_out, 1, wtid, rank, oc0, mix(ya[3], yb[3], ua[3], ub[3], gg[3]), 5);
      STAMP(13);
    }
    if (wtid == 0) {
      if (atomicAdd(&g_ticket, 1u) == NCTA - 1) { g_ticket = 0; g_epoch = epoch + 1; }
      asm volatile("cp.async.bulk.wait_group.read 0;" ::: "memory");
    }
    STAMP(15);
    return;
  }
  asm volatile("barrier.cluster.arrive.relaxed.aligned;" ::: "memory");

  const int moff = d * NM + hf * 64 + lane * 2;
  const uint32_t q0 = *(const uint32_t*)((br ? p.B_lA : p.A_re) + moff), q1 = *(const uint32_t*)((br ? p.B_Aim : p.A_im) + moff);
  const uint32_t q2 = *(const uint32_t*)((br ? p.B_Cre : p.C_re) + moff), q3 = *(const uint32_t*)((br ? p.B_Cim : p.C_im) + moff);
  const uint32_t q4 = *(const uint32_t*)((br ? p.B_Cre : p.B_re) + moff), q5 = *(const uint32_t*)((br ? p.B_Cim : p.B_im) + moff);
  const uint2 ldt4 = *(const uint2*)((br ? p.B_ldt : p.A_ldt) + blockIdx.x * 4);
  unsigned int epoch;
  asm volatile("ld.relaxed.gpu.global.u32 %0, [%1];" : "=r"(epoch) : "l"(&g_epoch) : "memory");

  for (int i = wtid & 63; i < R_BR / 16; i += 64) sts128(cb + R_OFF + br * R_BR + i * 16, 0, 0, 0, 0);
  STAMP(1);

  float acc[5][4];
  float k2048 = 0.f;
  const uint32_t scr = cb + Y0_OFF + wq * SCR_BYTES;
  const uint32_t scr2 = sb + XIN_OFF + warp * 640;
  {
    const uint32_t ldt2 = (ch & 2) ? ldt4.y : ldt4.x;
    const float dt = bf_round(expf((ch & 1) ? bf_hi(ldt2) : bf_lo(ldt2)));
#pragma unroll
    for (int i = 0; i < 5; i++) acc[i][0] = acc[i][1] = acc[i][2] = acc[i][3] = 0.f;
    cf cc[2], zz1[2], zz128[2];
#pragma unroll
    for (int r = 0; r < 2; r++) {
      float v0 = r ? bf_hi(q0) : bf_lo(q0), v1 = r ? bf_hi(q1) : bf_lo(q1), v2 = r ? bf_hi(q2) : bf_lo(q2);
      float v3 = r ? bf_hi(q3) : bf_lo(q3), v4 = r ? bf_hi(q4) : bf_lo(q4), v5 = r ? bf_hi(q5) : bf_lo(q5);
      if (br == 0) { cc[r] = cmul(cf{v2, v3}, cf{dt * v4, dt * v5}); }
      else { v0 = -bf_round(expf(v0)); cc[r] = cf{2.f * dt * v2, 2.f * dt * v3}; }
      const float xl = (dt * v0) * 1.4426950408889634f, y = dt * v1;
      zz1[r] = cexp_p(xl, y, 1.f); zz128[r] = cexp_p(xl, y, 128.f);
    }
    STAMP(2);
    const uint32_t tb = scr + lane * 16;
    const uint32_t ta = scr + (lane >> 3) * 512 + (lane & 7) * 16;
    const uint32_t tc = ((lane & 8) ? scr2 : scr + 4096) + (lane >> 4) * 128 + (lane & 7) * 16;
    const uint32_t tm = scr2 + 512 + ((lane >> 3) & 1) * 64 + (lane >> 4) * 16;
    if (ch >= 2) bar_sync(6, 512);
#pragma unroll 1
    for (int r = 0; r < 2; r++) {
      const cf c = r ? cc[1] : cc[0], z1 = r ? zz1[1] : zz1[0], z128 = r ? zz128[1] : zz128[0];
      const cf z2 = csq(z1), z4 = csq(z2), z8 = csq(z4);
      const cf z16 = csq(z8), z24 = cmul(z16, z8), z32 = csq(z16), z40 = cmul(z32, z8), z48 = csq(z24), z56 = cmul(z32, z24), z64 = csq(z32);
      const cf z256 = csq(z128), z512 = csq(z256), z1024 = csq(z512), z2048 = csq(z1024);
      k2048 += fmaf(c.re, z2048.re, -c.im * z2048.im);
      __syncwarp();
      {
        uint32_t xr[4] = {pack_bf16(1.f, z8.re), pack_bf16(z16.re, z24.re), pack_bf16(z32.re, z40.re), pack_bf16(z48.re, z56.re)};
        uint32_t xi[4] = {pack_bf16(0.f, -z8.im), pack_bf16(-z16.im, -z24.im), pack_bf16(-z32.im, -z40.im), pack_bf16(-z48.im, -z56.im)};
        sts128(tb + 0 * 512, xr[0], xr[1], xr[2], xr[3]);
        sts128(tb + 2 * 512, xi[0], xi[1], xi[2], xi[3]);
        const uint32_t yr = pack_bf16(z64.re, z64.re), nyi = pack_bf16(z64.im, z64.im), yi = nyi ^ 0x80008000u;
        uint32_t o[4], q[4];
#pragma unroll
        for (int i = 0; i < 4; i++) CMUL2(o[i], q[i], xr[i], xi[i], yr, yi, nyi);
        sts128(tb + 1 * 512, o[0], o[1], o[2], o[3]);
        sts128(tb + 3 * 512, q[0], q[1], q[2], q[3]);
      }
      {
        const cf h1 = cmul(c, z128), h2 = cmul(c, z256), h3 = cmul(h1, z256), h4 = cmul(c, z512), h5 = cmul(h1, z512), h6 = cmul(h2, z512), h7 = cmul(h3, z512);
        const cf e1 = cmul(c, z1), e2 = cmul(c, z2), e3 = cmul(e1, z2), e129 = cmul(h1, z1), e130 = cmul(h1, z2), e131 = cmul(e129, z2);
        const cf e258 = cmul(h2, z2), e386 = cmul(h3, z2);
        const uint32_t pr0 = pack_bf16(c.re, e1.re), pr2 = pack_bf16(h1.re, e129.re), pi0 = pack_bf16(c.im, e1.im), pi2 = pack_bf16(h1.im, e129.im);
        sts128(tb + 4 * 512, pr0, pack_bf16(e2.re, e3.re), pr2, pack_bf16(e130.re, e131.re));
        sts128(tb + 5 * 512, pi0, pack_bf16(e2.im, e3.im), pi2, pack_bf16(e130.im, e131.im));
        uint32_t xr[4] = {pack_bf16(h2.re, e258.re), pack_bf16(h3.re, e386.re), pack_bf16(h4.re, h5.re), pack_bf16(h6.re, h7.re)};
        uint32_t xi[4] = {pack_bf16(h2.im, e258.im), pack_bf16(h3.im, e386.im), pack_bf16(h4.im, h5.im), pack_bf16(h6.im, h7.im)};
        sts128(tb + 6 * 512, xr[0], xr[1], xr[2], xr[3]);
        sts128(tb + 7 * 512, xi[0], xi[1], xi[2], xi[3]);
        xr[1] = __byte_perm(xr[0], xr[1], 0x5410); xi[1] = __byte_perm(xi[0], xi[1], 0x5410);
        xr[0] = __byte_perm(pr0, pr2, 0x5410); xi[0] = __byte_perm(pi0, pi2, 0x5410);
        const uint32_t yr = pack_bf16(z1024.re, z1024.re), yi = pack_bf16(z1024.im, z1024.im), nyi = yi ^ 0x80008000u;
        uint32_t o[4], q[4];
#pragma unroll
        for (int i = 0; i < 4; i++) CMUL2(o[i], q[i], xr[i], xi[i], yr, yi, nyi);
        sts128(tb + 8 * 512, o[0], o[1], o[2], o[3]);
        sts128(scr2 + lane * 16, q[0], q[1], q[2], q[3]);
        const uint32_t m4 = pack_bf16(z4.re, z4.im);
        sts16(scr2 + 512 + lane * 2, m4); sts16(scr2 + 576 + lane * 2, m4 >> 16);
      }
      __syncwarp();
#pragma unroll
      for (int kp = 0; kp < 2; kp++) {
        uint32_t rr[2], ri[2], yr[2], yi[2];
        ldsm4t(tc + kp * 256, rr[0], ri[0], rr[1], ri[1]);
        ldsm4(tm + kp * 32, yr[0], yi[0], yr[1], yi[1]);
#pragma unroll
        for (int k2 = 0; k2 < 2; k2++) {
          const int kk = kp * 2 + k2;
          uint32_t a0, a1, a2, a3, pr, pi, qr, qi, xr, xi;
          ldsm4t(ta + kk * 128, a0, a1, a2, a3);
          ldsm4t(ta + 2048 + kk * 128, pr, pi, qr, qi);
          const uint32_t nyi = yi[k2] ^ 0x80008000u;
          mma16816(acc[0], a0, a1, a2, a3, pr, pi);
          mma16816(acc[2], a0, a1, a2, a3, qr, qi);
          mma16816(acc[4], a0, a1, a2, a3, rr[k2], ri[k2]);
          CMUL2(xr, xi, pr, pi, yr[k2], yi[k2], nyi);
          mma16816(acc[1], a0, a1, a2, a3, xr, xi);
          CMUL2(xr, xi, qr, qi, yr[k2], yi[k2], nyi);
          mma16816(acc[3], a0, a1, a2, a3, xr, xi);
        }
      }
      if (ch < 2 && r == 0) bar_arrive(6, 512);
    }
#pragma unroll
    for (int o = 16; o; o >>= 1) k2048 += __shfl_xor_sync(0xffffffffu, k2048, o);
  }
  STAMP(3);
  __syncwarp();
  {
    const uint32_t xs = scr + lane * 16;
#define OTH(i, k) __float_as_uint(hf ? acc[i][k] : acc[i][2 + (k)])
    sts128(xs, OTH(0, 0), OTH(0, 1), OTH(1, 0), OTH(1, 1));
    sts128(xs + 512, OTH(2, 0), OTH(2, 1), OTH(3, 0), OTH(3, 1));
    sts128(xs + 1024, OTH(4, 0), OTH(4, 1), __float_as_uint(k2048), 0);
#undef OTH
  }

  bar_sync(1 + ch, 128);
  STAMP(4);
  {
    const uint32_t xo = cb + Y0_OFF + (wq ^ 1) * SCR_BYTES + lane * 16;
    const uint4 o0 = lds128(xo), o1 = lds128(xo + 512), o2 = lds128(xo + 1024);
    const uint32_t rb = cb + R_OFF + br * R_BR;
#define OWN(i, k) (hf ? acc[i][2 + (k)] : acc[i][k])
    const uint32_t vP = pack_bf16(OWN(0, 1) + __uint_as_float(o0.y), OWN(0, 0) + __uint_as_float(o0.x));
    const uint32_t vP4 = pack_bf16(OWN(1, 1) + __uint_as_float(o0.w), OWN(1, 0) + __uint_as_float(o0.z));
    const uint32_t vQ = pack_bf16(OWN(2, 1) + __uint_as_float(o1.y), OWN(2, 0) + __uint_as_float(o1.x));
    const uint32_t vQ4 = pack_bf16(OWN(3, 1) + __uint_as_float(o1.w), OWN(3, 0) + __uint_as_float(o1.z));
    const uint32_t vR = pack_bf16(OWN(4, 1) + __uint_as_float(o2.y), OWN(4, 0) + __uint_as_float(o2.x));
#undef OWN
    const int j = g + 8 * hf;
    {
      const int a = 2 * (t & 1) + 64 * (t & 2) + 8 * j;
      const uint32_t ad = rb + 2 * (RD_X0 - 1 - a);
      const uint32_t a1 = (t & 2) ? ad - 8 : ad, a2 = (t & 2) ? ad : ad - 8;
      const uint32_t w1 = (t & 2) ? vP4 : vP, w2 = (t & 2) ? vP : vP4;
      sts32(a1, w1); sts32(a2, w2);
      sts16(a1 + RD_CS + 2, w1); sts16(a1 + RD_CS + 4, w1 >> 16);
      sts16(a2 + RD_CS + 2, w2); sts16(a2 + RD_CS + 4, w2 >> 16);
    }
    if (t < 2) {
      const int b = 256 + 128 * t + 8 * j;
      const uint32_t ad = rb + 2 * (RD_X0 - 6 - b);
      const uint32_t v22 = __byte_perm(vQ4, 0, 0x3232), v00 = __byte_perm(vQ, 0, 0x3232);
      sts16(ad, vQ4);
      sts64(ad + 2, v22, __byte_perm(vQ4, vQ, 0x5432));
      sts32(ad + 10, v00);
      if (b != 256) { sts16(ad + 14, v00); sts128(ad + RD_CS + 2, vQ4, v22, vQ, v00); }
      else { sts64(ad + RD_CS + 2, vQ4, v22); sts32(ad + RD_CS + 10, vQ); sts16(ad + RD_CS + 14, v00); }
    } else {
      const uint32_t ao = rb + R_O2 + 2 * (159 - (32 * t + j)), ae = ao - (R_O2 - R_E2) + 2;
      sts16(ao, vQ4 >> 16); sts16(ao + RS_CS + 2, vQ4 >> 16); sts16(ao - 32, vQ4); sts16(ao - 32 + RS_CS + 2, vQ4);
      sts16(ae - 32, vQ); sts16(ae - 32 + RS_CS + 2, vQ);
      if (lane != 2 || hf) { sts16(ae, vQ >> 16); sts16(ae + RS_CS + 2, vQ >> 16); }
      else {
        const uint32_t vv = __byte_perm(vQ, 0, 0x3232), ad = rb + 2 * (RD_X0 - 514);
        sts16(ad, vv); sts32(ad + 2, vv); sts16(ad + 6, vv); sts64(ad + RD_CS + 2, vv, vv);
      }
    }
    {
      const uint32_t a = rb + ((g & 1) ? R_O3 : R_E3 + 2) + 2 * (159 - (64 + 16 * t + (j >> 1)));
      const bool p1024 = (lane == 0) && (hf == 0);
      const uint32_t a00 = p1024 ? rb + R_E2 + 2 * (159 - 127) : a;
      sts16(a00, vR >> 16); sts16(a00 + RS_CS + 2, vR >> 16);
      sts16(a - 16, vR); sts16(a - 16 + RS_CS + 2, vR);
      if (p1024) {
        sts32(sb + K1024_OFF + (ch * 2 + br) * 4, __byte_perm(vR, 0, 0x3232));
        const uint32_t kv = pack_bf16(k2048 + __uint_as_float(o2.z), 0.f);
        sts16(rb + R_E3 + 2 * (159 - 127), kv); sts16(rb + R_E3 + 2 * (159 - 127) + RS_CS + 2, kv);
      }
    }
  }
  STAMP(5);
  const uint32_t tag = (epoch + 1) & 0xffffu;
  asm volatile("barrier.cluster.wait.aligned;" ::: "memory");
  bar_sync(1 + ch, 128);
  mbar_wait(sb + B_U);
  STAMP(6);

  const uint32_t zz = lds32(cb + R_OFF);
  conv_dense(cb, zz);
  const uint2 dA = *(const uint2*)(p.A_D + blockIdx.x * 4), dB = *(const uint2*)(p.B_D + blockIdx.x * 4);
  const uint2 gl = gate_ld((4 + ch) * 128 + wtid);
  mbar_wait(sb + B_W);
  conv_far(sb, cb, zz);
  STAMP(10);
  __syncwarp();
  if (lane == 0) asm volatile("mbarrier.arrive.shared::cta.b64 _, [%0];" ::"r"(sb + B_Y3) : "memory");

  {
    const int x = (4 + ch) * 128 + wtid, c = x >> 2;
    const uint32_t g2 = gate_fin(p, gl, x, tag);
    const uint32_t yo = sb + CH_OFF + (x & 3) * 4 + ysw(c);
    uint32_t ua[4], ub[4], ya[4], yb[4], a2[4], b2[4], a3[4], b3[4], s2[4];
    skip_terms(ua, ub, sb, x, dA, dB);
    ld4ch(s2, sb + CH_OFF + (x & 3) * 4 + S2_OFF + ((c - 128) + ((c - 128) >> 3)) * 16);
    mbar_wait(sb + B_Y2);
    const uint4 k0 = lds128(sb + K1024_OFF), k1 = lds128(sb + K1024_OFF + 16);
    const uint32_t kk[8] = {k0.x, k0.y, k0.z, k0.w, k1.x, k1.y, k1.z, k1.w};
    ld4ch(ya, yo + Y0_OFF); ld4ch(yb, yo + Y0_OFF + 4096);
    ld4ch(a2, yo + Y2_OFF - 1024); ld4ch(b2, yo + Y2_OFF - 1024 + 3072);
#pragma unroll
    for (int k = 0; k < 4; k++) { a2[k] = hfma2(kk[2 * k], s2[k], a2[k]); b2[k] = hfma2(kk[2 * k + 1], s2[k], b2[k]); }
    STAMP(11);
    mbar_wait(sb + B_Y3);
    STAMP(12);
    ld4ch(a3, yo + Y3_OFF - 2048); ld4ch(b3, yo + Y3_OFF - 2048 + 2048);
#pragma unroll
    for (int k = 0; k < 4; k++) { ya[k] = hadd2(ya[k], hadd2(a2[k], a3[k])); yb[k] = hadd2(yb[k], hadd2(b2[k], b3[k])); }
    const uint4 r = mix(ya, yb, ua, ub, g2);
    if ((uint32_t)(ch & 1) != rank) send_box(sb, 2 + (ch >> 1), wtid, rank, r);
    else merge_box(sb, &tm_out, 2 + (ch >> 1), wtid, rank, oc0, r, 1 + ch);
  }
  STAMP(14);
  if (wtid == 0) asm volatile("cp.async.bulk.wait_group.read 0;" ::: "memory");
  STAMP(15); GT(1);
}

typedef CUresult (*EncodeFn)(CUtensorMap*, CUtensorMapDataType, cuuint32_t, void*, const cuuint64_t*, const cuuint64_t*,
                             const cuuint32_t*, const cuuint32_t*, CUtensorMapInterleave, CUtensorMapSwizzle,
                             CUtensorMapL2promotion, CUtensorMapFloatOOBfill);

}

extern "C" void kernel_launch(void* const* d_in, const int* in_sizes, int n_in, void* d_out, int out_size) {
  (void)in_sizes; (void)n_in; (void)out_size;
  typedef const __nv_bfloat16* bp;
  Params p;
  p.u = (bp)d_in[0]; p.A_re = (bp)d_in[1]; p.A_im = (bp)d_in[2]; p.B_re = (bp)d_in[3]; p.B_im = (bp)d_in[4];
  p.C_re = (bp)d_in[5]; p.C_im = (bp)d_in[6]; p.A_ldt = (bp)d_in[7]; p.A_D = (bp)d_in[8];
  p.B_lA = (bp)d_in[10]; p.B_Aim = (bp)d_in[11]; p.B_Cre = (bp)d_in[12]; p.B_Cim = (bp)d_in[13];
  p.B_ldt = (bp)d_in[14]; p.B_D = (bp)d_in[15]; p.gw = (bp)d_in[16];
  static EncodeFn enc = nullptr;
  if (!enc) {
    cudaDriverEntryPointQueryResult qr;
    cudaGetDriverEntryPoint("cuTensorMapEncodeTiled", (void**)&enc, cudaEnableDefault, &qr);
    cudaFuncSetAttribute(ssm_kernel, cudaFuncAttributeMaxDynamicSharedMemorySize, SMEM_BYTES);
  }
  CUtensorMap tm_in, tm_out;
  {
    cuuint64_t gd[5] = {512, 2, 4, 4, 64};
    cuuint64_t gs[4] = {1024, 8192, 2048, 32768};
    cuuint32_t bx[5] = {8, 2, 4, 4, 32};
    cuuint32_t es[5] = {1, 1, 1, 1, 1};
    enc(&tm_in, CU_TENSOR_MAP_DATA_TYPE_BFLOAT16, 5, d_in[0], gd, gs, bx, es, CU_TENSOR_MAP_INTERLEAVE_NONE,
        CU_TENSOR_MAP_SWIZZLE_NONE, CU_TENSOR_MAP_L2_PROMOTION_NONE, CU_TENSOR_MAP_FLOAT_OOB_FILL_NONE);
  }
  {
    cuuint64_t gd[3] = {512, 1024, 2};
    cuuint64_t gs[2] = {2048, 1024};
    cuuint32_t bx[3] = {8, 128, 2};
    cuuint32_t es[3] = {1, 1, 1};
    enc(&tm_out, CU_TENSOR_MAP_DATA_TYPE_BFLOAT16, 3, d_out, gd, gs, bx, es, CU_TENSOR_MAP_INTERLEAVE_NONE,
        CU_TENSOR_MAP_SWIZZLE_NONE, CU_TENSOR_MAP_L2_PROMOTION_NONE, CU_TENSOR_MAP_FLOAT_OOB_FILL_NONE);
  }
  ssm_kernel<<<NCTA, 640, SMEM_BYTES, cudaStreamPerThread>>>(p, tm_in, tm_out);
}
```

```cpp
#include <cuda_runtime.h>
#include <cuda.h>
#include <cuda_bf16.h>
#include <stdint.h>

namespace {
#define FIXA 0
#define FIXB 1
#define CPY(x) (x)
#define FCPY(x) __uint_as_float(opq(__float_as_uint(x), zz))
#define STAG 0

constexpr int L = 2048, D = 512, NM = 128;
constexpr int NCTA = 128;

constexpr int RAW_OFF = 0;
constexpr int XIN_OFF = 32768;
constexpr int BAR_OFF = XIN_OFF + 10240;
constexpr int CH_OFF = BAR_OFF + 128;
constexpr int U_CS = 1184;
constexpr int U_OFF = 0;
constexpr int R_OFF = 4736;
constexpr int RD_X0 = 565;
constexpr int RD_CS = 1216;
constexpr int RS_CS = 320;
constexpr int R_E2 = 2 * RD_CS, R_O2 = R_E2 + 2 * RS_CS, R_E3 = R_O2 + 2 * RS_CS, R_O3 = R_E3 + 2 * RS_CS;
constexpr int R_BR = R_O3 + 2 * RS_CS;
constexpr int W5_OFF = R_OFF + 2 * R_BR;
constexpr int W3_OFF = W5_OFF + 3456;
constexpr int W9_OFF = W3_OFF + 3456;
constexpr int W7_OFF = W9_OFF + 2304;
constexpr int S2_OFF = W7_OFF + 2304;
constexpr int Y0_OFF = S2_OFF + 2304;
constexpr int Y2_OFF = Y0_OFF + 8192, Y3_OFF = Y2_OFF + 6144;
constexpr int CH_BYTES = Y0_OFF + 18432 + 16;
constexpr int SCR_BYTES = 4608;
constexpr int SMEM_BYTES = CH_OFF + 4 * CH_BYTES;
static_assert(CH_BYTES % 128 == 16, "bank staggering of the channel blocks");
static_assert(SMEM_BYTES <= 232448, "smem");
constexpr int B_RAW = BAR_OFF, B_X = BAR_OFF + 8, B_U = BAR_OFF + 40, B_W = BAR_OFF + 48, B_Y2 = BAR_OFF + 56, B_Y3 = BAR_OFF + 96;
constexpr int K1024_OFF = BAR_OFF + 64;

__device__ unsigned int g_gate[L];
__device__ unsigned int g_epoch;
__device__ unsigned int g_ticket;

#define STAMP(k)
#define GT(k)

struct Params {
  const __nv_bfloat16 *u, *A_re, *A_im, *B_re, *B_im, *C_re, *C_im, *A_ldt, *A_D;
  const __nv_bfloat16 *B_lA, *B_Aim, *B_Cre, *B_Cim, *B_ldt, *B_D, *gw;
};

template <int N, int TB> __device__ __forceinline__ void wgmma_rs(float* d, uint32_t a0, uint32_t a1, uint32_t a2, uint32_t a3, uint64_t desc, int sc);
template <> __device__ __forceinline__ void wgmma_rs<64, 0>(float* d, uint32_t a0, uint32_t a1, uint32_t a2, uint32_t a3, uint64_t desc, int sc) {
  asm volatile("{\n.reg .pred p;\nsetp.ne.b32 p, %37, 0;\n"
    "wgmma.mma_async.sync.aligned.m64n64k16.f32.bf16.bf16 {%0,%1,%2,%3,%4,%5,%6,%7,%8,%9,%10,%11,%12,%13,%14,%15,%16,%17,%18,%19,%20,%21,%22,%23,%24,%25,%26,%27,%28,%29,%30,%31}, {%32,%33,%34,%35}, %36, p, 1, 1, 0;\n}"
    : "+f"(d[0]), "+f"(d[1]), "+f"(d[2]), "+f"(d[3]), "+f"(d[4]), "+f"(d[5]), "+f"(d[6]), "+f"(d[7]), "+f"(d[8]), "+f"(d[9]), "+f"(d[10]), "+f"(d[11]), "+f"(d[12]), "+f"(d[13]), "+f"(d[14]), "+f"(d[15]), "+f"(d[16]), "+f"(d[17]), "+f"(d[18]), "+f"(d[19]), "+f"(d[20]), "+f"(d[21]), "+f"(d[22]), "+f"(d[23]), "+f"(d[24]), "+f"(d[25]), "+f"(d[26]), "+f"(d[27]), "+f"(d[28]), "+f"(d[29]), "+f"(d[30]), "+f"(d[31]) : "r"(a0), "r"(a1), "r"(a2), "r"(a3), "l"(desc), "r"(sc));
}
template <> __device__ __forceinline__ void wgmma_rs<56, 0>(float* d, uint32_t a0, uint32_t a1, uint32_t a2, uint32_t a3, uint64_t desc, int sc) {
  asm volatile("{\n.reg .pred p;\nsetp.ne.b32 p, %33, 0;\n"
    "wgmma.mma_async.sync.aligned.m64n56k16.f32.bf16.bf16 {%0,%1,%2,%3,%4,%5,%6,%7,%8,%9,%10,%11,%12,%13,%14,%15,%16,%17,%18,%19,%20,%21,%22,%23,%24,%25,%26,%27}, {%28,%29,%30,%31}, %32, p, 1, 1, 0;\n}"
    : "+f"(d[0]), "+f"(d[1]), "+f"(d[2]), "+f"(d[3]), "+f"(d[4]), "+f"(d[5]), "+f"(d[6]), "+f"(d[7]), "+f"(d[8]), "+f"(d[9]), "+f"(d[10]), "+f"(d[11]), "+f"(d[12]), "+f"(d[13]), "+f"(d[14]), "+f"(d[15]), "+f"(d[16]), "+f"(d[17]), "+f"(d[18]), "+f"(d[19]), "+f"(d[20]), "+f"(d[21]), "+f"(d[22]), "+f"(d[23]), "+f"(d[24]), "+f"(d[25]), "+f"(d[26]), "+f"(d[27]) : "r"(a0), "r"(a1), "r"(a2), "r"(a3), "l"(desc), "r"(sc));
}
template <> __device__ __forceinline__ void wgmma_rs<48, 0>(float* d, uint32_t a0, uint32_t a1, uint32_t a2, uint32_t a3, uint64_t desc, int sc) {
  asm volatile("{\n.reg .pred p;\nsetp.ne.b32 p, %29, 0;\n"
    "wgmma.mma_async.sync.aligned.m64n48k16.f32.bf16.bf16 {%0,%1,%2,%3,%4,%5,%6,%7,%8,%9,%10,%11,%12,%13,%14,%15,%16,%17,%18,%19,%20,%21,%22,%23}, {%24,%25,%26,%27}, %28, p, 1, 1, 0;\n}"
    : "+f"(d[0]), "+f"(d[1]), "+f"(d[2]), "+f"(d[3]), "+f"(d[4]), "+f"(d[5]), "+f"(d[6]), "+f"(d[7]), "+f"(d[8]), "+f"(d[9]), "+f"(d[10]), "+f"(d[11]), "+f"(d[12]), "+f"(d[13]), "+f"(d[14]), "+f"(d[15]), "+f"(d[16]), "+f"(d[17]), "+f"(d[18]), "+f"(d[19]), "+f"(d[20]), "+f"(d[21]), "+f"(d[22]), "+f"(d[23]) : "r"(a0), "r"(a1), "r"(a2), "r"(a3), "l"(desc), "r"(sc));
}
template <> __device__ __forceinline__ void wgmma_rs<48, 1>(float* d, uint32_t a0, uint32_t a1, uint32_t a2, uint32_t a3, uint64_t desc, int sc) {
  asm volatile("{\n.reg .pred p;\nsetp.ne.b32 p, %29, 0;\n"
    "wgmma.mma_async.sync.aligned.m64n48k16.f32.bf16.bf16 {%0,%1,%2,%3,%4,%5,%6,%7,%8,%9,%10,%11,%12,%13,%14,%15,%16,%17,%18,%19,%20,%21,%22,%23}, {%24,%25,%26,%27}, %28, p, 1, 1, 1;\n}"
    : "+f"(d[0]), "+f"(d[1]), "+f"(d[2]), "+f"(d[3]), "+f"(d[4]), "+f"(d[5]), "+f"(d[6]), "+f"(d[7]), "+f"(d[8]), "+f"(d[9]), "+f"(d[10]), "+f"(d[11]), "+f"(d[12]), "+f"(d[13]), "+f"(d[14]), "+f"(d[15]), "+f"(d[16]), "+f"(d[17]), "+f"(d[18]), "+f"(d[19]), "+f"(d[20]), "+f"(d[21]), "+f"(d[22]), "+f"(d[23]) : "r"(a0), "r"(a1), "r"(a2), "r"(a3), "l"(desc), "r"(sc));
}
template <> __device__ __forceinline__ void wgmma_rs<40, 1>(float* d, uint32_t a0, uint32_t a1, uint32_t a2, uint32_t a3, uint64_t desc, int sc) {
  asm volatile("{\n.reg .pred p;\nsetp.ne.b32 p, %25, 0;\n"
    "wgmma.mma_async.sync.aligned.m64n40k16.f32.bf16.bf16 {%0,%1,%2,%3,%4,%5,%6,%7,%8,%9,%10,%11,%12,%13,%14,%15,%16,%17,%18,%19}, {%20,%21,%22,%23}, %24, p, 1, 1, 1;\n}"
    : "+f"(d[0]), "+f"(d[1]), "+f"(d[2]), "+f"(d[3]), "+f"(d[4]), "+f"(d[5]), "+f"(d[6]), "+f"(d[7]), "+f"(d[8]), "+f"(d[9]), "+f"(d[10]), "+f"(d[11]), "+f"(d[12]), "+f"(d[13]), "+f"(d[14]), "+f"(d[15]), "+f"(d[16]), "+f"(d[17]), "+f"(d[18]), "+f"(d[19]) : "r"(a0), "r"(a1), "r"(a2), "r"(a3), "l"(desc), "r"(sc));
}
template <> __device__ __forceinline__ void wgmma_rs<32, 1>(float* d, uint32_t a0, uint32_t a1, uint32_t a2, uint32_t a3, uint64_t desc, int sc) {
  asm volatile("{\n.reg .pred p;\nsetp.ne.b32 p, %21, 0;\n"
    "wgmma.mma_async.sync.aligned.m64n32k16.f32.bf16.bf16 {%0,%1,%2,%3,%4,%5,%6,%7,%8,%9,%10,%11,%12,%13,%14,%15}, {%16,%17,%18,%19}, %20, p, 1, 1, 1;\n}"
    : "+f"(d[0]), "+f"(d[1]), "+f"(d[2]), "+f"(d[3]), "+f"(d[4]), "+f"(d[5]), "+f"(d[6]), "+f"(d[7]), "+f"(d[8]), "+f"(d[9]), "+f"(d[10]), "+f"(d[11]), "+f"(d[12]), "+f"(d[13]), "+f"(d[14]), "+f"(d[15]) : "r"(a0), "r"(a1), "r"(a2), "r"(a3), "l"(desc), "r"(sc));
}
template <> __device__ __forceinline__ void wgmma_rs<16, 1>(float* d, uint32_t a0, uint32_t a1, uint32_t a2, uint32_t a3, uint64_t desc, int sc) {
  asm volatile("{\n.reg .pred p;\nsetp.ne.b32 p, %13, 0;\n"
    "wgmma.mma_async.sync.aligned.m64n16k16.f32.bf16.bf16 {%0,%1,%2,%3,%4,%5,%6,%7}, {%8,%9,%10,%11}, %12, p, 1, 1, 1;\n}"
    : "+f"(d[0]), "+f"(d[1]), "+f"(d[2]), "+f"(d[3]), "+f"(d[4]), "+f"(d[5]), "+f"(d[6]), "+f"(d[7]) : "r"(a0), "r"(a1), "r"(a2), "r"(a3), "l"(desc), "r"(sc));
}

__device__ __forceinline__ uint32_t pack_bf16(float lo, float hi) {
  uint32_t r; asm("cvt.rn.bf16x2.f32 %0, %1, %2;" : "=r"(r) : "f"(hi), "f"(lo)); return r;
}
__device__ __forceinline__ float bf_lo(uint32_t v) { return __uint_as_float(v << 16); }
__device__ __forceinline__ float bf_hi(uint32_t v) { return __uint_as_float(v & 0xffff0000u); }
__device__ __forceinline__ float bf_round(float x) { return bf_lo(pack_bf16(x, 0.f)); }
__device__ __forceinline__ uint32_t hmul2(uint32_t a, uint32_t b) { uint32_t r; asm("mul.rn.bf16x2 %0, %1, %2;" : "=r"(r) : "r"(a), "r"(b)); return r; }
__device__ __forceinline__ uint32_t hadd2(uint32_t a, uint32_t b) { uint32_t r; asm("add.rn.bf16x2 %0, %1, %2;" : "=r"(r) : "r"(a), "r"(b)); return r; }
__device__ __forceinline__ uint32_t hsub2(uint32_t a, uint32_t b) { uint32_t r; asm("sub.rn.bf16x2 %0, %1, %2;" : "=r"(r) : "r"(a), "r"(b)); return r; }
__device__ __forceinline__ uint32_t hfma2(uint32_t a, uint32_t b, uint32_t c) { uint32_t r; asm("fma.rn.bf16x2 %0, %1, %2, %3;" : "=r"(r) : "r"(a), "r"(b), "r"(c)); return r; }

__device__ __forceinline__ void sts16(uint32_t a, uint32_t v) { asm volatile("st.shared.b16 [%0], %1;" ::"r"(a), "h"((unsigned short)v) : "memory"); }
__device__ __forceinline__ void sts32(uint32_t a, uint32_t v) { asm volatile("st.shared.b32 [%0], %1;" ::"r"(a), "r"(v) : "memory"); }
__device__ __forceinline__ void sts64(uint32_t a, uint32_t x, uint32_t y) { asm volatile("st.shared.v2.b32 [%0], {%1,%2};" ::"r"(a), "r"(x), "r"(y) : "memory"); }
__device__ __forceinline__ void sts128(uint32_t a, uint32_t x, uint32_t y, uint32_t z, uint32_t w) {
  asm volatile("st.shared.v4.b32 [%0], {%1,%2,%3,%4};" ::"r"(a), "r"(x), "r"(y), "r"(z), "r"(w) : "memory");
}
__device__ __forceinline__ uint32_t lds32(uint32_t a) { uint32_t v; asm volatile("ld.shared.b32 %0, [%1];" : "=r"(v) : "r"(a) : "memory"); return v; }
__device__ __forceinline__ uint2 lds64(uint32_t a) { uint2 v; asm volatile("ld.shared.v2.b32 {%0,%1}, [%2];" : "=r"(v.x), "=r"(v.y) : "r"(a) : "memory"); return v; }
__device__ __forceinline__ uint4 lds128(uint32_t a) {
  uint4 v; asm volatile("ld.shared.v4.b32 {%0,%1,%2,%3}, [%4];" : "=r"(v.x), "=r"(v.y), "=r"(v.z), "=r"(v.w) : "r"(a) : "memory"); return v;
}
__device__ __forceinline__ void ldsm4(uint32_t a, uint32_t& r0, uint32_t& r1, uint32_t& r2, uint32_t& r3) {
  asm volatile("ldmatrix.sync.aligned.m8n8.x4.shared.b16 {%0,%1,%2,%3}, [%4];" : "=r"(r0), "=r"(r1), "=r"(r2), "=r"(r3) : "r"(a) : "memory");
}
__device__ __forceinline__ void ldsm4t(uint32_t a, uint32_t& r0, uint32_t& r1, uint32_t& r2, uint32_t& r3) {
  asm volatile("ldmatrix.sync.aligned.m8n8.x4.trans.shared.b16 {%0,%1,%2,%3}, [%4];" : "=r"(r0), "=r"(r1), "=r"(r2), "=r"(r3) : "r"(a) : "memory");
}
__device__ __forceinline__ void stsm4(uint32_t a, uint32_t r0, uint32_t r1, uint32_t r2, uint32_t r3) {
  asm volatile("stmatrix.sync.aligned.m8n8.x4.shared.b16 [%0], {%1,%2,%3,%4};" ::"r"(a), "r"(r0), "r"(r1), "r"(r2), "r"(r3) : "memory");
}
__device__ __forceinline__ void stsm4t(uint32_t a, uint32_t r0, uint32_t r1, uint32_t r2, uint32_t r3) {
  asm volatile("stmatrix.sync.aligned.m8n8.x4.trans.shared.b16 [%0], {%1,%2,%3,%4};" ::"r"(a), "r"(r0), "r"(r1), "r"(r2), "r"(r3) : "memory");
}
__device__ __forceinline__ void mma16816(float* c, uint32_t a0, uint32_t a1, uint32_t a2, uint32_t a3, uint32_t b0, uint32_t b1) {
  asm("mma.sync.aligned.m16n8k16.row.col.f32.bf16.bf16.f32 {%0,%1,%2,%3}, {%4,%5,%6,%7}, {%8,%9}, {%0,%1,%2,%3};"
      : "+f"(c[0]), "+f"(c[1]), "+f"(c[2]), "+f"(c[3]) : "r"(a0), "r"(a1), "r"(a2), "r"(a3), "r"(b0), "r"(b1));
}
__device__ __forceinline__ void bar_sync(int id, int n) { asm volatile("bar.sync %0, %1;" ::"r"(id), "r"(n) : "memory"); }
__device__ __forceinline__ void bar_arrive(int id, int n) { asm volatile("bar.arrive %0, %1;" ::"r"(id), "r"(n) : "memory"); }
__device__ __forceinline__ void wg_fence() { asm volatile("wgmma.fence.sync.aligned;" ::: "memory"); }
__device__ __forceinline__ void wg_commit() { asm volatile("wgmma.commit_group.sync.aligned;" ::: "memory"); }
__device__ __forceinline__ void wg_wait0() { asm volatile("wgmma.wait_group.sync.aligned 0;" ::: "memory"); }
__device__ __forceinline__ void fence_async() { asm volatile("fence.proxy.async.shared::cta;" ::: "memory"); }
__device__ __forceinline__ uint32_t opq(uint32_t x, uint32_t z) { uint32_t r; asm volatile("xor.b32 %0, %1, %2;" : "=r"(r) : "r"(x), "r"(z)); return r; }
__device__ __forceinline__ uint64_t mkdesc(uint32_t addr, uint32_t lbo, uint32_t sbo) {
  return (uint64_t)((addr & 0x3FFFF) >> 4) | ((uint64_t)(lbo >> 4) << 16) | ((uint64_t)(sbo >> 4) << 32);
}
__device__ __forceinline__ uint32_t mapa(uint32_t a, uint32_t rank) {
  uint32_t r; asm("mapa.shared::cluster.u32 %0, %1, %2;" : "=r"(r) : "r"(a), "r"(rank)); return r;
}
__device__ __forceinline__ void mbar_init_expect(uint32_t bar, uint32_t bytes) {
  asm volatile("mbarrier.init.shared::cta.b64 [%0], 1;" ::"r"(bar) : "memory");
  asm volatile("mbarrier.arrive.expect_tx.shared::cta.b64 _, [%0], %1;" ::"r"(bar), "r"(bytes) : "memory");
}
__device__ __forceinline__ void mbar_wait(uint32_t bar) {
#pragma unroll 1
  for (int it = 0; it < (1 << 22); it++) {
    uint32_t ok;
    asm volatile("{\n.reg .pred p;\nmbarrier.try_wait.parity.acquire.cluster.shared::cta.b64 p, [%1], 0;\nselp.u32 %0, 1, 0, p;\n}"
                 : "=r"(ok) : "r"(bar) : "memory");
    if (ok) return;
  }
  __trap();
}
__device__ __forceinline__ void st_async4(uint32_t a, uint32_t bar, uint32_t x, uint32_t y, uint32_t z, uint32_t w) {
  asm volatile("st.async.weak.shared::cluster.mbarrier::complete_tx::bytes.v4.b32 [%0], {%2,%3,%4,%5}, [%1];"
               ::"r"(a), "r"(bar), "r"(x), "r"(y), "r"(z), "r"(w) : "memory");
}

struct cf { float re, im; };
__device__ __forceinline__ cf cmul(cf a, cf b) { return {fmaf(a.re, b.re, -a.im * b.im), fmaf(a.re, b.im, a.im * b.re)}; }
__device__ __forceinline__ cf csq(cf a) { return {fmaf(a.re, a.re, -a.im * a.im), (a.re + a.re) * a.im}; }
__device__ __forceinline__ cf cexp_p(float xl, float y, float p) {
  float mag; asm("ex2.approx.ftz.f32 %0, %1;" : "=f"(mag) : "f"(xl * p));
  const float th = y * p;
  const float k = rintf(th * 0.15915494309189535f);
  float r = fmaf(k, -6.2831854820251465f, th);
  r = fmaf(k, 1.7484555314695172e-07f, r);
  return {mag * __cosf(r), mag * __sinf(r)};
}
__device__ __forceinline__ uint32_t ysw(int c) { return (uint32_t)(c ^ ((c >> 3) & 3)) * 16u; }

#define CMUL2(OR, OI, xr, xi, yr, yi, nyi) do { OR = hfma2(xr, yr, hmul2(xi, nyi)); OI = hfma2(xr, yi, hmul2(xi, yr)); } while (0)

__device__ __forceinline__ uint32_t gate_slow(const __nv_bfloat16* u, const __nv_bfloat16* gw, int row) {
  float s = 0.f;
  const uint32_t* xr = (const uint32_t*)(u + (size_t)row * D);
  const uint32_t* wr = (const uint32_t*)gw;
#pragma unroll 1
  for (int j = 0; j < D / 2; j++) { const uint32_t pr = hmul2(xr[j], wr[j]); s += bf_lo(pr); s += bf_hi(pr); }
  s = bf_round(s);
  return pack_bf16(1.f / (1.f + expf(-s)), 0.f);
}

__device__ __forceinline__ void prefix6(float* pf, uint32_t ub, int c0) {
  pf[0] = 0.f;
#pragma unroll
  for (int j = 0; j < 6; j++) {
    const int c = c0 + j;
    const uint4 v = lds128(ub + (c & 3) * U_CS + (63 - (c >> 2)) * 16);
    const uint32_t w[4] = {v.x, v.y, v.z, v.w};
#pragma unroll
    for (int i = 0; i < 4; i++) {
      pf[j * 8 + 2 * i + 1] = pf[j * 8 + 2 * i] + bf_lo(w[i]);
      pf[j * 8 + 2 * i + 2] = pf[j * 8 + 2 * i + 1] + bf_hi(w[i]);
    }
  }
}
template <int A, int B>
__device__ __forceinline__ void put_win(const float* pf, int ix, uint32_t addr) {
  uint32_t a[4];
#pragma unroll
  for (int i = 0; i < 4; i++) a[i] = pack_bf16(pf[ix + 2 * i - B + 1] - pf[ix + 2 * i - A], pf[ix + 2 * i - B + 2] - pf[ix + 2 * i - A + 1]);
  sts128(addr, a[0], a[1], a[2], a[3]);
}

__device__ __forceinline__ uint2 gate_ld(int x) {
  uint2 gv;
  asm volatile("ld.relaxed.gpu.global.v2.u32 {%0,%1}, [%2];" : "=r"(gv.x), "=r"(gv.y) : "l"(g_gate + x * 2) : "memory");
  return gv;
}
__device__ __noinline__ uint32_t gate_poll(const __nv_bfloat16* u, const __nv_bfloat16* gw, int x, uint32_t tag) {
  uint2 gv;
#pragma unroll 1
  for (int spins = 0; spins < (1 << 16); spins++) {
    gv = gate_ld(x);
    if ((gv.x >> 16) == tag && (gv.y >> 16) == tag) return __byte_perm(gv.x, gv.y, 0x5410);
  }
  return __byte_perm(gate_slow(u, gw, x * 2), gate_slow(u, gw, x * 2 + 1), 0x5410);
}
__device__ __forceinline__ uint32_t gate_fin(const Params& p, uint2 gv, int x, uint32_t tag) {
  if ((gv.x >> 16) == tag && (gv.y >> 16) == tag) return __byte_perm(gv.x, gv.y, 0x5410);
  return gate_poll(p.u, p.gw, x, tag);
}

__device__ __forceinline__ void ld4ch(uint32_t* v, uint32_t addr) {
#pragma unroll
  for (int k = 0; k < 4; k++) v[k] = lds32(addr + k * CH_BYTES);
}
__device__ __forceinline__ void skip_terms(uint32_t* ua, uint32_t* ub, uint32_t sb, int x, uint2 dA, uint2 dB) {
  const int c = x >> 2;
  uint32_t uu[4];
  ld4ch(uu, sb + CH_OFF + (x & 3) * 4 + U_OFF + (c & 3) * U_CS + (63 - (c >> 2)) * 16);
#pragma unroll
  for (int k = 0; k < 4; k++) {
    ua[k] = hmul2(uu[k], __byte_perm((k & 2) ? dA.y : dA.x, 0, (k & 1) ? 0x3232 : 0x1010));
    ub[k] = hmul2(uu[k], __byte_perm((k & 2) ? dB.y : dB.x, 0, (k & 1) ? 0x3232 : 0x1010));
  }
}
__device__ __forceinline__ uint4 mix(const uint32_t* a, const uint32_t* b, const uint32_t* ua, const uint32_t* ub, uint32_t g2) {
  const uint32_t h2 = hsub2(0x3f803f80u, g2);
  uint32_t o[4];
#pragma unroll
  for (int k = 0; k < 4; k++) o[k] = hadd2(hmul2(g2, hadd2(a[k], ua[k])), hmul2(h2, hadd2(b[k], ub[k])));
  return make_uint4(__byte_perm(o[0], o[1], 0x5410), __byte_perm(o[2], o[3], 0x5410), __byte_perm(o[0], o[1], 0x7632), __byte_perm(o[2], o[3], 0x7632));
}
__device__ __forceinline__ void send_box(uint32_t sb, int slot, int wtid, uint32_t rank, uint4 r) {
  st_async4(mapa(sb + XIN_OFF + slot * 2048 + wtid * 16, rank ^ 1), mapa(sb + B_X + slot * 8, rank ^ 1), r.x, r.y, r.z, r.w);
}
__device__ __forceinline__ void merge_box(uint32_t sb, const CUtensorMap* tm_out, int slot, int wtid, uint32_t rank, int oc0, uint4 r, int barid) {
  const uint32_t st = sb + RAW_OFF + slot * 4096 + wtid * 16;
  sts64(st + rank * 8, r.x, r.y); sts64(st + 2048 + rank * 8, r.z, r.w);
  mbar_wait(sb + B_X + slot * 8);
  const uint4 q = lds128(sb + XIN_OFF + slot * 2048 + wtid * 16);
  sts64(st + (rank ^ 1) * 8, q.x, q.y); sts64(st + 2048 + (rank ^ 1) * 8, q.z, q.w);
  fence_async();
  bar_sync(barid, 128);
  if (wtid == 0) {
    asm volatile("cp.async.bulk.tensor.3d.global.shared::cta.bulk_group [%0, {%2, %3, %4}], [%1];"
                 ::"l"(tm_out), "r"(sb + RAW_OFF + slot * 4096), "r"(oc0), "r"((2 * slot + (int)rank) * 128), "r"(0) : "memory");
    asm volatile("cp.async.bulk.commit_group;" ::: "memory");
  }
}

__device__ __forceinline__ void window_sums(uint32_t cb, int wq, int lane) {
      float pf[49];
      if (wq == 0 || wq == 3) {
        if (wq == 0 || lane < 16) {
          const int nu = wq ? 32 + lane : lane;
          prefix6(pf, cb + U_OFF, 4 * nu - 2);
          const uint32_t po = (5 - (nu >> 3)) * 576 + ((nu & 7) >> 1) * 144 + (nu & 1) * 64;
#pragma unroll
          for (int k = 0; k < 4; k++) { put_win<10, 6>(pf, 16 + 8 * k, cb + W5_OFF + po + k * 16); put_win<5, 3>(pf, 16 + 8 * k, cb + W3_OFF + po + k * 16); }
        }
      } else {
        const uint32_t po = (1 - (lane >> 4)) * 1152 + ((lane & 15) >> 2) * 144 + (lane & 3) * 32;
        if (wq == 1) {
          prefix6(pf, cb + U_OFF, 4 * lane - 3);
#pragma unroll
          for (int k = 0; k < 4; k++) put_win<20, 12>(pf, 24 + 8 * k, cb + W9_OFF + po + (k & 1) * 576 + (k >> 1) * 16);
        } else {
          prefix6(pf, cb + U_OFF, 4 * lane - 2);
          const uint32_t so = cb + S2_OFF + (lane >> 1) * 144 + (lane & 1) * 64;
#pragma unroll
          for (int k = 0; k < 4; k++) { put_win<11, 5>(pf, 16 + 8 * k, cb + W7_OFF + po + (k & 1) * 576 + (k >> 1) * 16); put_win<4, 3>(pf, 16 + 8 * k, so + k * 16); }
        }
      }
}

__device__ __forceinline__ void conv_dense(uint32_t cb, uint32_t zz) {
  const int lane = threadIdx.x & 31, wq = (threadIdx.x >> 5) & 3, br = wq >> 1, hf = wq & 1, g = lane >> 2, t = lane & 3;
  const uint32_t rb = cb + R_OFF + br * R_BR;
  const int eo = 16 * hf + g - 2 * t;
  float dacc[32];
  {
      {
        const int x0 = RD_X0 - (eo + 536);
        const uint32_t fa = rb + ((g & 1) ? 2 * x0 : RD_CS + 2 * x0 + 2);
        const uint64_t ub = mkdesc(cb + U_OFF, U_CS, 128);
        uint32_t A[2][4][4];
        float e56[28], e48[24];
        auto loadA = [&](int j) {
#pragma unroll
          for (int k = 0; k < 4; k++) {
            const int s = 34 - 4 * j - k;
            if (s >= 0) {
              if (k == 0) A[j & 1][0][2] = lds32(fa + (2 * s + 2) * 16);
              A[j & 1][k][0] = lds32(fa + (2 * s + 1) * 16);
              A[j & 1][k][1] = lds32(fa + (2 * s) * 16);
            }
          }
#pragma unroll
          for (int k = 0; k < 4; k++) {
            if (34 - 4 * j - k >= 0) {
              A[j & 1][k][3] = CPY(A[j & 1][k][0]);
              if (k) A[j & 1][k][2] = CPY(A[j & 1][k - 1][1]);
            }
          }
        };
        loadA(0);
#pragma unroll
        for (int j = 0; j < 9; j++) {
          if (j == 4) {
#pragma unroll
            for (int i = 0; i < 28; i++) e56[i] = FCPY(dacc[i]);
          }
          if (j == 8) {
#pragma unroll
            for (int i = 0; i < 24; i++) e48[i] = FCPY(e56[i]);
          }
          wg_fence();
#pragma unroll
          for (int k = 0; k < 4; k++) {
            const int s = 34 - 4 * j - k;
            if (s >= 0) {
              const int o = 2 * s - 66 + 128;
              const int cc = o & 3, rs = (o >> 2) - 32;
              const int n0 = ((-rs) >> 3) * 8;
              const uint64_t desc = ub + (uint64_t)((cc * U_CS - rs * 16) >> 4);
              const uint32_t* a = A[j & 1][k];
              if (n0 == 0) wgmma_rs<64, 0>(dacc, a[0], a[1], a[2], a[3], desc, s != 34);
              else if (n0 == 8) wgmma_rs<56, 0>(FIXB ? e56 : dacc, a[0], a[1], a[2], a[3], desc, 1);
              else wgmma_rs<48, 0>(FIXB ? e48 : dacc, a[0], a[1], a[2], a[3], desc, 1);
            }
          }
          wg_commit();
          if (j < 8) loadA(j + 1);
          wg_wait0();
        }
#pragma unroll
        for (int i = 0; i < 28; i++) dacc[i] = i < 24 ? e48[i] : e56[i];
      }
      const uint32_t yb = cb + Y0_OFF + br * 4096;
#pragma unroll
      for (int i = 0; i < 8; i += 2) {
        const int mi = lane >> 3;
        const int cidx = 4 * (63 - 8 * (i + (mi >> 1)) - (lane & 7)) + 2 * hf + (mi & 1);
        stsm4t(yb + ysw(cidx), pack_bf16(dacc[4 * i], dacc[4 * i + 1]), pack_bf16(dacc[4 * i + 2], dacc[4 * i + 3]),
               pack_bf16(dacc[4 * i + 4], dacc[4 * i + 5]), pack_bf16(dacc[4 * i + 6], dacc[4 * i + 7]));
      }
      bar_arrive(8, 640);
      STAMP(8);
  }
}

__device__ __forceinline__ void conv_far(uint32_t sb, uint32_t cb, uint32_t zz) {
  const int lane = threadIdx.x & 31, wq = (threadIdx.x >> 5) & 3, br = wq >> 1, hf = wq & 1, g = lane >> 2, t = lane & 3;
  const uint32_t rb = cb + R_OFF + br * R_BR;
  const int eo = 16 * hf + g - 2 * t;
  float dacc[24], e40[20], e32[16], h32[16], h16[8];
  const int x1 = 159 - (eo + 136);
  const uint32_t fs = rb + ((g & 1) ? 2 * x1 : RS_CS + 2 * x1 + 2);
  {
    uint32_t A[2][4][4];
    auto loadA = [&](int buf, uint32_t oe, uint32_t oo, int i0) {
#pragma unroll
      for (int a = 0; a < 2; a++) {
        const uint32_t base = fs + (a ? oo : oe) + i0 * 16;
        uint32_t* k0 = A[buf][2 * a];
        uint32_t* k1 = A[buf][2 * a + 1];
        k0[1] = lds32(base); k0[0] = lds32(base + 16); k0[2] = lds32(base + 32); k1[0] = lds32(base + 48); k1[2] = lds32(base + 64);
      }
#pragma unroll
      for (int a = 0; a < 2; a++) {
        uint32_t* k0 = A[buf][2 * a];
        uint32_t* k1 = A[buf][2 * a + 1];
        k0[3] = CPY(k0[0]); k1[1] = CPY(k0[2]); k1[3] = CPY(k1[0]);
      }
    };
    const uint64_t d5 = mkdesc(cb + W5_OFF, 144, 576), d3 = mkdesc(cb + W3_OFF, 144, 576);
    loadA(0, R_E2, R_O2, 8);
#pragma unroll
    for (int m = 2; m <= 4; m++) {
      if (m == 3) {
#pragma unroll
        for (int i = 0; i < 20; i++) e40[i] = FCPY(dacc[i]);
      }
      if (m == 4) {
#pragma unroll
        for (int i = 0; i < 16; i++) e32[i] = FCPY(e40[i]);
      }
      wg_fence();
#pragma unroll
      for (int k = 0; k < 4; k++) {
        const uint32_t* a = A[m & 1][k];
        const uint64_t desc = ((k >> 1) ? d3 : d5) + (k & 1) * 18 + (m - 2) * 36;
        if (m == 2) wgmma_rs<48, 1>(dacc, a[0], a[1], a[2], a[3], desc, k);
        else if (m == 3) wgmma_rs<40, 1>(e40, a[0], a[1], a[2], a[3], desc, 1);
        else wgmma_rs<32, 1>(e32, a[0], a[1], a[2], a[3], desc, 1);
      }
      wg_commit();
      if (m < 4) loadA((m + 1) & 1, R_E2, R_O2, 4 * (3 - m));
      else loadA(1, R_E3, R_O3, 8);
      wg_wait0();
    }
#pragma unroll
    for (int i = 0; i < 20; i++) dacc[i] = i < 16 ? e32[i] : e40[i];
    {
      const uint32_t yb = cb + Y2_OFF + br * 3072;
#pragma unroll
      for (int i = 0; i < 6; i += 2) {
        const int mi = lane >> 3;
        const int cidx = 32 * (5 - i - (mi >> 1)) + 16 * hf + 8 * (mi & 1) + (lane & 7);
        stsm4(yb + ysw(cidx), pack_bf16(dacc[4 * i], dacc[4 * i + 1]), pack_bf16(dacc[4 * i + 2], dacc[4 * i + 3]),
              pack_bf16(dacc[4 * i + 4], dacc[4 * i + 5]), pack_bf16(dacc[4 * i + 6], dacc[4 * i + 7]));
      }
    }
    __syncwarp();
    if (lane == 0) asm volatile("mbarrier.arrive.shared::cta.b64 _, [%0];" ::"r"(sb + B_Y2) : "memory");
    STAMP(9);
    const uint64_t d9 = mkdesc(cb + W9_OFF, 144, 576), d7 = mkdesc(cb + W7_OFF, 144, 576);
#pragma unroll
    for (int m = 2; m <= 3; m++) {
      if (m == 3) {
#pragma unroll
        for (int i = 0; i < 8; i++) h16[i] = FCPY(h32[i]);
      }
      wg_fence();
#pragma unroll
      for (int k = 0; k < 4; k++) {
        const uint32_t* a = A[(m + 1) & 1][k];
        const uint64_t desc = ((k >> 1) ? d7 : d9) + (k & 1) * 18 + (m - 2) * 72;
        if (m == 2) wgmma_rs<32, 1>(h32, a[0], a[1], a[2], a[3], desc, k);
        else wgmma_rs<16, 1>(h16, a[0], a[1], a[2], a[3], desc, 1);
      }
      wg_commit();
      if (m == 2) loadA(0, R_E3, R_O3, 4);
      wg_wait0();
    }
#pragma unroll
    for (int i = 0; i < 16; i++) dacc[i] = i < 8 ? h16[i] : h32[i];
    const uint32_t yb = cb + Y3_OFF + br * 2048;
#pragma unroll
    for (int i = 0; i < 4; i += 2) {
      const int mi = lane >> 3;
      const int cidx = 64 * (1 - (i >> 1)) + 2 * (16 * hf + 8 * (mi & 1) + (lane & 7)) + (mi >> 1);
      stsm4(yb + ysw(cidx), pack_bf16(dacc[4 * i], dacc[4 * i + 1]), pack_bf16(dacc[4 * i + 2], dacc[4 * i + 3]),
            pack_bf16(dacc[4 * i + 4], dacc[4 * i + 5]), pack_bf16(dacc[4 * i + 6], dacc[4 * i + 7]));
    }
  }
}

__global__ void __cluster_dims__(2, 1, 1) __launch_bounds__(640, 1)
ssm_kernel(const Params p, const __grid_constant__ CUtensorMap tm_in, const __grid_constant__ CUtensorMap tm_out) {
  extern __shared__ __align__(1024) unsigned char smem_raw[];
  const uint32_t sb = (uint32_t)__cvta_generic_to_shared(smem_raw);
  const int tid = threadIdx.x, lane = tid & 31;
  const int warp = __shfl_sync(0xffffffffu, tid >> 5, 0);
  const int ch = warp >> 2, wq = warp & 3, br = wq >> 1, hf = wq & 1;
  const int g = lane >> 2, t = lane & 3;
  const int d = blockIdx.x * 4 + ch;
  const uint32_t rank = blockIdx.x & 1;
  const uint32_t cb = sb + CH_OFF + ch * CH_BYTES;
  const int wtid = tid & 127;
  const int oc0 = (int)(blockIdx.x >> 1) * 8;
  STAMP(0); GT(0);

  if (warp >= 16) {
    if (wtid == 0) {
      mbar_init_expect(sb + B_RAW, 32768);
#pragma unroll
      for (int i = 0; i < 4; i++) mbar_init_expect(sb + B_X + 8 * i, 2048);
      asm volatile("mbarrier.init.shared::cta.b64 [%0], 128;" ::"r"(sb + B_U) : "memory");
      asm volatile("mbarrier.init.shared::cta.b64 [%0], 128;" ::"r"(sb + B_W) : "memory");
      asm volatile("mbarrier.init.shared::cta.b64 [%0], 16;" ::"r"(sb + B_Y2) : "memory");
      asm volatile("mbarrier.init.shared::cta.b64 [%0], 16;" ::"r"(sb + B_Y3) : "memory");
      asm volatile("fence.mbarrier_init.release.cluster;" ::: "memory");
      asm volatile("fence.proxy.async.shared::cta;" ::: "memory");
    }
    __syncwarp();
    asm volatile("barrier.cluster.arrive.relaxed.aligned;" ::: "memory");
    unsigned int epoch;
    asm volatile("ld.relaxed.gpu.global.u32 %0, [%1];" : "=r"(epoch) : "l"(&g_epoch) : "memory");
    const uint2 dA = *(const uint2*)(p.A_D + blockIdx.x * 4), dB = *(const uint2*)(p.B_D + blockIdx.x * 4);
    const uint4 gw0 = *(const uint4*)(p.gw + lane * 8), gw1 = *(const uint4*)(p.gw + 256 + lane * 8);
    asm volatile("barrier.cluster.wait.aligned;" ::: "memory");
    if (wtid == 0) {
      asm volatile("cp.async.bulk.tensor.5d.shared::cluster.global.mbarrier::complete_tx::bytes.multicast::cluster [%0], [%1, {%3, %4, %4, %4, %5}], [%2], %6;"
                   ::"r"(sb + RAW_OFF + rank * 16384), "l"(&tm_in), "r"(sb + B_RAW), "r"(oc0), "r"(0), "r"((int)rank * 32), "h"((unsigned short)3) : "memory");
    }
    sts128(sb + CH_OFF + wq * CH_BYTES + U_OFF + (lane >> 3) * U_CS + (64 + (lane & 7)) * 16, 0, 0, 0, 0);
    STAMP(3);
    mbar_wait(sb + B_RAW);
    STAMP(4);
    {
      const uint32_t dst = sb + CH_OFF + (g & 3) * CH_BYTES + U_OFF + t * U_CS + (63 - wq * 16) * 16;
#pragma unroll
      for (int h = 0; h < 2; h++) {
        uint32_t r[8][4];
#pragma unroll
        for (int i = 0; i < 8; i++) ldsm4t(sb + RAW_OFF + (wq * 16 + h * 8 + i) * 512 + lane * 16, r[i][0], r[i][1], r[i][2], r[i][3]);
        if ((uint32_t)(g >> 2) == rank) {
#pragma unroll
          for (int i = 0; i < 8; i++) sts128(dst - (h * 8 + i) * 16, r[i][0], r[i][1], r[i][2], r[i][3]);
        }
      }
    }
    fence_async();
    asm volatile("mbarrier.arrive.shared::cta.b64 _, [%0];" ::"r"(sb + B_U) : "memory");
    bar_sync(5, 128);
    STAMP(5);
    const uint32_t tag = (epoch + 1) & 0xffffu;
    {
      const int grow = blockIdx.x * 16 + wq * 4;
      uint4 gx[4][2];
#pragma unroll
      for (int i = 0; i < 4; i++) {
        gx[i][0] = *(const uint4*)(p.u + (size_t)(grow + i) * D + lane * 8);
        gx[i][1] = *(const uint4*)(p.u + (size_t)(grow + i) * D + 256 + lane * 8);
      }
      const uint32_t ws[8] = {gw0.x, gw0.y, gw0.z, gw0.w, gw1.x, gw1.y, gw1.z, gw1.w};
      float sm[4];
#pragma unroll
      for (int i = 0; i < 4; i++) {
        const uint32_t xs[8] = {gx[i][0].x, gx[i][0].y, gx[i][0].z, gx[i][0].w, gx[i][1].x, gx[i][1].y, gx[i][1].z, gx[i][1].w};
        float s = 0.f;
#pragma unroll
        for (int j = 0; j < 8; j++) { const uint32_t pr = hmul2(xs[j], ws[j]); s += bf_lo(pr); s += bf_hi(pr); }
        sm[i] = s;
      }
      {
        const bool b0 = lane & 1, b1 = lane & 2;
        float u0 = b0 ? sm[1] : sm[0], v0 = b0 ? sm[0] : sm[1], u1 = b0 ? sm[3] : sm[2], v1 = b0 ? sm[2] : sm[3];
        u0 += __shfl_xor_sync(0xffffffffu, v0, 1); u1 += __shfl_xor_sync(0xffffffffu, v1, 1);
        float s = b1 ? u1 : u0; const float v = b1 ? u0 : u1;
        s += __shfl_xor_sync(0xffffffffu, v, 2);
#pragma unroll
        for (int o = 4; o < 32; o <<= 1) s += __shfl_xor_sync(0xffffffffu, s, o);
        s = bf_round(s);
        const float gv = 1.f / (1.f + expf(-s));
        const uint32_t w = (tag << 16) | (pack_bf16(gv, 0.f) & 0xffffu);
        if (lane < 4) asm volatile("st.relaxed.gpu.global.u32 [%0], %1;" ::"l"(&g_gate[grow + lane]), "r"(w) : "memory");
      }
    }
    STAMP(6);
#pragma unroll 1
    for (int k = 0; k < 4; k++) window_sums(sb + CH_OFF + k * CH_BYTES, wq, lane);
    fence_async();
    asm volatile("mbarrier.arrive.shared::cta.b64 _, [%0];" ::"r"(sb + B_W) : "memory");
    STAMP(7);
    STAMP(8);
    uint32_t gg[4];
    {
      uint2 gl[4];
#pragma unroll
      for (int i = 0; i < 4; i++) gl[i] = gate_ld((i ^ (int)rank ^ 1) * 128 + wtid);
#pragma unroll
      for (int i = 0; i < 4; i++) gg[i] = gate_fin(p, gl[i], (i ^ (int)rank ^ 1) * 128 + wtid, tag);
    }
    {
      uint32_t ua[4][4], ub[4][4], ya[4][4], yb[4][4], yo[4];
#pragma unroll
      for (int i = 0; i < 4; i++) {
        const int x = (i ^ (int)rank ^ 1) * 128 + wtid;
        skip_terms(ua[i], ub[i], sb, x, dA, dB);
        yo[i] = sb + CH_OFF + (x & 3) * 4 + ysw(x >> 2);
      }
      bar_sync(8, 640);
      STAMP(10);
#pragma unroll
      for (int i = 0; i < 4; i++) { ld4ch(ya[i], yo[i] + Y0_OFF); ld4ch(yb[i], yo[i] + Y0_OFF + 4096); }
      send_box(sb, 0, wtid, rank, mix(ya[0], yb[0], ua[0], ub[0], gg[0]));
      merge_box(sb, &tm_out, 0, wtid, rank, oc0, mix(ya[1], yb[1], ua[1], ub[1], gg[1]), 5);
      STAMP(12);
      mbar_wait(sb + B_Y2);
      STAMP(11);
#pragma unroll
      for (int i = 2; i < 4; i++) { ld4ch(ya[i - 2], yo[i] + Y2_OFF - 1024); ld4ch(yb[i - 2], yo[i] + Y2_OFF - 1024 + 3072); }
#pragma unroll
      for (int i = 2; i < 4; i++)
#pragma unroll
        for (int k = 0; k < 4; k++) { ya[i][k] = hadd2(ya[i][k], ya[i - 2][k]); yb[i][k] = hadd2(yb[i][k], yb[i - 2][k]); }
      send_box(sb, 1, wtid, rank, mix(ya[2], yb[2], ua[2], ub[2], gg[2]));
      merge_box(sb, &tm_out, 1, wtid, rank, oc0, mix(ya[3], yb[3], ua[3], ub[3], gg[3]), 5);
      STAMP(13);
    }
    if (wtid == 0) {
      if (atomicAdd(&g_ticket, 1u) == NCTA - 1) { g_ticket = 0; g_epoch = epoch + 1; }
      asm volatile("cp.async.bulk.wait_group.read 0;" ::: "memory");
    }
    STAMP(15);
    return;
  }
  asm volatile("barrier.cluster.arrive.relaxed.aligned;" ::: "memory");

  const int moff = d * NM + hf * 64 + lane * 2;
  const uint32_t q0 = *(const uint32_t*)((br ? p.B_lA : p.A_re) + moff), q1 = *(const uint32_t*)((br ? p.B_Aim : p.A_im) + moff);
  const uint32_t q2 = *(const uint32_t*)((br ? p.B_Cre : p.C_re) + moff), q3 = *(const uint32_t*)((br ? p.B_Cim : p.C_im) + moff);
  const uint32_t q4 = *(const uint32_t*)((br ? p.B_Cre : p.B_re) + moff), q5 = *(const uint32_t*)((br ? p.B_Cim : p.B_im) + moff);
  const uint2 ldt4 = *(const uint2*)((br ? p.B_ldt : p.A_ldt) + blockIdx.x * 4);
  unsigned int epoch;
  asm volatile("ld.relaxed.gpu.global.u32 %0, [%1];" : "=r"(epoch) : "l"(&g_epoch) : "memory");

  for (int i = wtid & 63; i < R_BR / 16; i += 64) sts128(cb + R_OFF + br * R_BR + i * 16, 0, 0, 0, 0);
  STAMP(1);

  float acc[5][4];
  float k2048 = 0.f;
  const uint32_t scr = cb + Y0_OFF + wq * SCR_BYTES;
  const uint32_t scr2 = sb + XIN_OFF + warp * 640;
  {
    const uint32_t ldt2 = (ch & 2) ? ldt4.y : ldt4.x;
    const float dt = bf_round(expf((ch & 1) ? bf_hi(ldt2) : bf_lo(ldt2)));
#pragma unroll
    for (int i = 0; i < 5; i++) acc[i][0] = acc[i][1] = acc[i][2] = acc[i][3] = 0.f;
    cf cc[2], zz1[2], zz128[2];
#pragma unroll
    for (int r = 0; r < 2; r++) {
      float v0 = r ? bf_hi(q0) : bf_lo(q0), v1 = r ? bf_hi(q1) : bf_lo(q1), v2 = r ? bf_hi(q2) : bf_lo(q2);
      float v3 = r ? bf_hi(q3) : bf_lo(q3), v4 = r ? bf_hi(q4) : bf_lo(q4), v5 = r ? bf_hi(q5) : bf_lo(q5);
      if (br == 0) { cc[r] = cmul(cf{v2, v3}, cf{dt * v4, dt * v5}); }
      else { v0 = -bf_round(expf(v0)); cc[r] = cf{2.f * dt * v2, 2.f * dt * v3}; }
      const float xl = (dt * v0) * 1.4426950408889634f, y = dt * v1;
      zz1[r] = cexp_p(xl, y, 1.f); zz128[r] = cexp_p(xl, y, 128.f);
    }
    STAMP(2);
    const uint32_t tb = scr + lane * 16;
    const uint32_t ta = scr + (lane >> 3) * 512 + (lane & 7) * 16;
    const uint32_t tc = ((lane & 8) ? scr2 : scr + 4096) + (lane >> 4) * 128 + (lane & 7) * 16;
    const uint32_t tm = scr2 + 512 + ((lane >> 3) & 1) * 64 + (lane >> 4) * 16;
#pragma unroll 1
    for (int r = 0; r < 2; r++) {
      const cf c = r ? cc[1] : cc[0], z1 = r ? zz1[1] : zz1[0], z128 = r ? zz128[1] : zz128[0];
      const cf z2 = csq(z1), z4 = csq(z2), z8 = csq(z4);
      const cf z16 = csq(z8), z24 = cmul(z16, z8), z32 = csq(z16), z40 = cmul(z32, z8), z48 = csq(z24), z56 = cmul(z32, z24), z64 = csq(z32);
      const cf z256 = csq(z128), z512 = csq(z256), z1024 = csq(z512), z2048 = csq(z1024);
      k2048 += fmaf(c.re, z2048.re, -c.im * z2048.im);
      __syncwarp();
      {
        uint32_t xr[4] = {pack_bf16(1.f, z8.re), pack_bf16(z16.re, z24.re), pack_bf16(z32.re, z40.re), pack_bf16(z48.re, z56.re)};
        uint32_t xi[4] = {pack_bf16(0.f, -z8.im), pack_bf16(-z16.im, -z24.im), pack_bf16(-z32.im, -z40.im), pack_bf16(-z48.im, -z56.im)};
        sts128(tb + 0 * 512, xr[0], xr[1], xr[2], xr[3]);
        sts128(tb + 2 * 512, xi[0], xi[1], xi[2], xi[3]);
        const uint32_t yr = pack_bf16(z64.re, z64.re), nyi = pack_bf16(z64.im, z64.im), yi = nyi ^ 0x80008000u;
        uint32_t o[4], q[4];
#pragma unroll
        for (int i = 0; i < 4; i++) CMUL2(o[i], q[i], xr[i], xi[i], yr, yi, nyi);
        sts128(tb + 1 * 512, o[0], o[1], o[2], o[3]);
        sts128(tb + 3 * 512, q[0], q[1], q[2], q[3]);
      }
      {
        const cf h1 = cmul(c, z128), h2 = cmul(c, z256), h3 = cmul(h1, z256), h4 = cmul(c, z512), h5 = cmul(h1, z512), h6 = cmul(h2, z512), h7 = cmul(h3, z512);
        const cf e1 = cmul(c, z1), e2 = cmul(c, z2), e3 = cmul(e1, z2), e129 = cmul(h1, z1), e130 = cmul(h1, z2), e131 = cmul(e129, z2);
        const cf e258 = cmul(h2, z2), e386 = cmul(h3, z2);
        const uint32_t pr0 = pack_bf16(c.re, e1.re), pr2 = pack_bf16(h1.re, e129.re), pi0 = pack_bf16(c.im, e1.im), pi2 = pack_bf16(h1.im, e129.im);
        sts128(tb + 4 * 512, pr0, pack_bf16(e2.re, e3.re), pr2, pack_bf16(e130.re, e131.re));
        sts128(tb + 5 * 512, pi0, pack_bf16(e2.im, e3.im), pi2, pack_bf16(e130.im, e131.im));
        uint32_t xr[4] = {pack_bf16(h2.re, e258.re), pack_bf16(h3.re, e386.re), pack_bf16(h4.re, h5.re), pack_bf16(h6.re, h7.re)};
        uint32_t xi[4] = {pack_bf16(h2.im, e258.im), pack_bf16(h3.im, e386.im), pack_bf16(h4.im, h5.im), pack_bf16(h6.im, h7.im)};
        sts128(tb + 6 * 512, xr[0], xr[1], xr[2], xr[3]);
        sts128(tb + 7 * 512, xi[0], xi[1], xi[2], xi[3]);
        xr[1] = __byte_perm(xr[0], xr[1], 0x5410); xi[1] = __byte_perm(xi[0], xi[1], 0x5410);
        xr[0] = __byte_perm(pr0, pr2, 0x5410); xi[0] = __byte_perm(pi0, pi2, 0x5410);
        const uint32_t yr = pack_bf16(z1024.re, z1024.re), yi = pack_bf16(z1024.im, z1024.im), nyi = yi ^ 0x80008000u;
        uint32_t o[4], q[4];
#pragma unroll
        for (int i = 0; i < 4; i++) CMUL2(o[i], q[i], xr[i], xi[i], yr, yi, nyi);
        sts128(tb + 8 * 512, o[0], o[1], o[2], o[3]);
        sts128(scr2 + lane * 16, q[0], q[1], q[2], q[3]);
        const uint32_t m4 = pack_bf16(z4.re, z4.im);
        sts16(scr2 + 512 + lane * 2, m4); sts16(scr2 + 576 + lane * 2, m4 >> 16);
      }
      __syncwarp();
#pragma unroll
      for (int kp = 0; kp < 2; kp++) {
        uint32_t rr[2], ri[2], yr[2], yi[2];
        ldsm4t(tc + kp * 256, rr[0], ri[0], rr[1], ri[1]);
        ldsm4(tm + kp * 32, yr[0], yi[0], yr[1], yi[1]);
#pragma unroll
        for (int k2 = 0; k2 < 2; k2++) {
          const int kk = kp * 2 + k2;
          uint32_t a0, a1, a2, a3, pr, pi, qr, qi, xr, xi;
          ldsm4t(ta + kk * 128, a0, a1, a2, a3);
          ldsm4t(ta + 2048 + kk * 128, pr, pi, qr, qi);
          const uint32_t nyi = yi[k2] ^ 0x80008000u;
          mma16816(acc[0], a0, a1, a2, a3, pr, pi);
          mma16816(acc[2], a0, a1, a2, a3, qr, qi);
          mma16816(acc[4], a0, a1, a2, a3, rr[k2], ri[k2]);
          CMUL2(xr, xi, pr, pi, yr[k2], yi[k2], nyi);
          mma16816(acc[1], a0, a1, a2, a3, xr, xi);
          CMUL2(xr, xi, qr, qi, yr[k2], yi[k2], nyi);
          mma16816(acc[3], a0, a1, a2, a3, xr, xi);
        }
      }
    }
#pragma unroll
    for (int o = 16; o; o >>= 1) k2048 += __shfl_xor_sync(0xffffffffu, k2048, o);
  }
  STAMP(3);
  __syncwarp();
  {
    const uint32_t xs = scr + lane * 16;
#define OTH(i, k) __float_as_uint(hf ? acc[i][k] : acc[i][2 + (k)])
    sts128(xs, OTH(0, 0), OTH(0, 1), OTH(1, 0), OTH(1, 1));
    sts128(xs + 512, OTH(2, 0), OTH(2, 1), OTH(3, 0), OTH(3, 1));
    sts128(xs + 1024, OTH(4, 0), OTH(4, 1), __float_as_uint(k2048), 0);
#undef OTH
  }

  bar_sync(1 + ch, 128);
  STAMP(4);
  {
    const uint32_t xo = cb + Y0_OFF + (wq ^ 1) * SCR_BYTES + lane * 16;
    const uint4 o0 = lds128(xo), o1 = lds128(xo + 512), o2 = lds128(xo + 1024);
    const uint32_t rb = cb + R_OFF + br * R_BR;
#define OWN(i, k) (hf ? acc[i][2 + (k)] : acc[i][k])
    const uint32_t vP = pack_bf16(OWN(0, 1) + __uint_as_float(o0.y), OWN(0, 0) + __uint_as_float(o0.x));
    const uint32_t vP4 = pack_bf16(OWN(1, 1) + __uint_as_float(o0.w), OWN(1, 0) + __uint_as_float(o0.z));
    const uint32_t vQ = pack_bf16(OWN(2, 1) + __uint_as_float(o1.y), OWN(2, 0) + __uint_as_float(o1.x));
    const uint32_t vQ4 = pack_bf16(OWN(3, 1) + __uint_as_float(o1.w), OWN(3, 0) + __uint_as_float(o1.z));
    const uint32_t vR = pack_bf16(OWN(4, 1) + __uint_as_float(o2.y), OWN(4, 0) + __uint_as_float(o2.x));
#undef OWN
    const int j = g + 8 * hf;
    {
      const int a = 2 * (t & 1) + 64 * (t & 2) + 8 * j;
      const uint32_t ad = rb + 2 * (RD_X0 - 1 - a);
      const uint32_t a1 = (t & 2) ? ad - 8 : ad, a2 = (t & 2) ? ad : ad - 8;
      const uint32_t w1 = (t & 2) ? vP4 : vP, w2 = (t & 2) ? vP : vP4;
      sts32(a1, w1); sts32(a2, w2);
      sts16(a1 + RD_CS + 2, w1); sts16(a1 + RD_CS + 4, w1 >> 16);
      sts16(a2 + RD_CS + 2, w2); sts16(a2 + RD_CS + 4, w2 >> 16);
    }
    if (t < 2) {
      const int b = 256 + 128 * t + 8 * j;
      const uint32_t ad = rb + 2 * (RD_X0 - 6 - b);
      const uint32_t v22 = __byte_perm(vQ4, 0, 0x3232), v00 = __byte_perm(vQ, 0, 0x3232);
      sts16(ad, vQ4);
      sts64(ad + 2, v22, __byte_perm(vQ4, vQ, 0x5432));
      sts32(ad + 10, v00);
      if (b != 256) { sts16(ad + 14, v00); sts128(ad + RD_CS + 2, vQ4, v22, vQ, v00); }
      else { sts64(ad + RD_CS + 2, vQ4, v22); sts32(ad + RD_CS + 10, vQ); sts16(ad + RD_CS + 14, v00); }
    } else {
      const uint32_t ao = rb + R_O2 + 2 * (159 - (32 * t + j)), ae = ao - (R_O2 - R_E2) + 2;
      sts16(ao, vQ4 >> 16); sts16(ao + RS_CS + 2, vQ4 >> 16); sts16(ao - 32, vQ4); sts16(ao - 32 + RS_CS + 2, vQ4);
      sts16(ae - 32, vQ); sts16(ae - 32 + RS_CS + 2, vQ);
      if (lane != 2 || hf) { sts16(ae, vQ >> 16); sts16(ae + RS_CS + 2, vQ >> 16); }
      else {
        const uint32_t vv = __byte_perm(vQ, 0, 0x3232), ad = rb + 2 * (RD_X0 - 514);
        sts16(ad, vv); sts32(ad + 2, vv); sts16(ad + 6, vv); sts64(ad + RD_CS + 2, vv, vv);
      }
    }
    {
      const uint32_t a = rb + ((g & 1) ? R_O3 : R_E3 + 2) + 2 * (159 - (64 + 16 * t + (j >> 1)));
      const bool p1024 = (lane == 0) && (hf == 0);
      const uint32_t a00 = p1024 ? rb + R_E2 + 2 * (159 - 127) : a;
      sts16(a00, vR >> 16); sts16(a00 + RS_CS + 2, vR >> 16);
      sts16(a - 16, vR); sts16(a - 16 + RS_CS + 2, vR);
      if (p1024) {
        sts32(sb + K1024_OFF + (ch * 2 + br) * 4, __byte_perm(vR, 0, 0x3232));
        const uint32_t kv = pack_bf16(k2048 + __uint_as_float(o2.z), 0.f);
        sts16(rb + R_E3 + 2 * (159 - 127), kv); sts16(rb + R_E3 + 2 * (159 - 127) + RS_CS + 2, kv);
      }
    }
  }
  STAMP(5);
  const uint32_t tag = (epoch + 1) & 0xffffu;
  asm volatile("barrier.cluster.wait.aligned;" ::: "memory");
  bar_sync(1 + ch, 128);
  mbar_wait(sb + B_U);
  STAMP(6);

  const uint32_t zz = lds32(cb + R_OFF);
  conv_dense(cb, zz);
  const uint2 dA = *(const uint2*)(p.A_D + blockIdx.x * 4), dB = *(const uint2*)(p.B_D + blockIdx.x * 4);
  const uint2 gl = gate_ld((4 + ch) * 128 + wtid);
  mbar_wait(sb + B_W);
  conv_far(sb, cb, zz);
  STAMP(10);
  __syncwarp();
  if (lane == 0) asm volatile("mbarrier.arrive.shared::cta.b64 _, [%0];" ::"r"(sb + B_Y3) : "memory");

  {
    const int x = (4 + ch) * 128 + wtid, c = x >> 2;
    const uint32_t g2 = gate_fin(p, gl, x, tag);
    const uint32_t yo = sb + CH_OFF + (x & 3) * 4 + ysw(c);
    uint32_t ua[4], ub[4], ya[4], yb[4], a2[4], b2[4], a3[4], b3[4], s2[4];
    skip_terms(ua, ub, sb, x, dA, dB);
    ld4ch(s2, sb + CH_OFF + (x & 3) * 4 + S2_OFF + ((c - 128) + ((c - 128) >> 3)) * 16);
    mbar_wait(sb + B_Y2);
    const uint4 k0 = lds128(sb + K1024_OFF), k1 = lds128(sb + K1024_OFF + 16);
    const uint32_t kk[8] = {k0.x, k0.y, k0.z, k0.w, k1.x, k1.y, k1.z, k1.w};
    ld4ch(ya, yo + Y0_OFF); ld4ch(yb, yo + Y0_OFF + 4096);
    ld4ch(a2, yo + Y2_OFF - 1024); ld4ch(b2, yo + Y2_OFF - 1024 + 3072);
#pragma unroll
    for (int k = 0; k < 4; k++) { a2[k] = hfma2(kk[2 * k], s2[k], a2[k]); b2[k] = hfma2(kk[2 * k + 1], s2[k], b2[k]); }
    STAMP(11);
    mbar_wait(sb + B_Y3);
    STAMP(12);
    ld4ch(a3, yo + Y3_OFF - 2048); ld4ch(b3, yo + Y3_OFF - 2048 + 2048);
#pragma unroll
    for (int k = 0; k < 4; k++) { ya[k] = hadd2(ya[k], hadd2(a2[k], a3[k])); yb[k] = hadd2(yb[k], hadd2(b2[k], b3[k])); }
    const uint4 r = mix(ya, yb, ua, ub, g2);
    if ((uint32_t)(ch & 1) != rank) send_box(sb, 2 + (ch >> 1), wtid, rank, r);
    else merge_box(sb, &tm_out, 2 + (ch >> 1), wtid, rank, oc0, r, 1 + ch);
  }
  STAMP(14);
  if (wtid == 0) asm volatile("cp.async.bulk.wait_group.read 0;" ::: "memory");
  STAMP(15); GT(1);
}

typedef CUresult (*EncodeFn)(CUtensorMap*, CUtensorMapDataType, cuuint32_t, void*, const cuuint64_t*, const cuuint64_t*,
                             const cuuint32_t*, const cuuint32_t*, CUtensorMapInterleave, CUtensorMapSwizzle,
                             CUtensorMapL2promotion, CUtensorMapFloatOOBfill);

}

extern "C" void kernel_launch(void* const* d_in, const int* in_sizes, int n_in, void* d_out, int out_size) {
  (void)in_sizes; (void)n_in; (void)out_size;
  typedef const __nv_bfloat16* bp;
  Params p;
  p.u = (bp)d_in[0]; p.A_re = (bp)d_in[1]; p.A_im = (bp)d_in[2]; p.B_re = (bp)d_in[3]; p.B_im = (bp)d_in[4];
  p.C_re = (bp)d_in[5]; p.C_im = (bp)d_in[6]; p.A_ldt = (bp)d_in[7]; p.A_D = (bp)d_in[8];
  p.B_lA = (bp)d_in[10]; p.B_Aim = (bp)d_in[11]; p.B_Cre = (bp)d_in[12]; p.B_Cim = (bp)d_in[13];
  p.B_ldt = (bp)d_in[14]; p.B_D = (bp)d_in[15]; p.gw = (bp)d_in[16];
  static EncodeFn enc = nullptr;
  if (!enc) {
    cudaDriverEntryPointQueryResult qr;
    cudaGetDriverEntryPoint("cuTensorMapEncodeTiled", (void**)&enc, cudaEnableDefault, &qr);
    cudaFuncSetAttribute(ssm_kernel, cudaFuncAttributeMaxDynamicSharedMemorySize, SMEM_BYTES);
  }
  CUtensorMap tm_in, tm_out;
  {
    cuuint64_t gd[5] = {512, 2, 4, 4, 64};
    cuuint64_t gs[4] = {1024, 8192, 2048, 32768};
    cuuint32_t bx[5] = {8, 2, 4, 4, 32};
    cuuint32_t es[5] = {1, 1, 1, 1, 1};
    enc(&tm_in, CU_TENSOR_MAP_DATA_TYPE_BFLOAT16, 5, d_in[0], gd, gs, bx, es, CU_TENSOR_MAP_INTERLEAVE_NONE,
        CU_TENSOR_MAP_SWIZZLE_NONE, CU_TENSOR_MAP_L2_PROMOTION_NONE, CU_TENSOR_MAP_FLOAT_OOB_FILL_NONE);
  }
  {
    cuuint64_t gd[3] = {512, 1024, 2};
    cuuint64_t gs[2] = {2048, 1024};
    cuuint32_t bx[3] = {8, 128, 2};
    cuuint32_t es[3] = {1, 1, 1};
    enc(&tm_out, CU_TENSOR_MAP_DATA_TYPE_BFLOAT16, 3, d_out, gd, gs, bx, es, CU_TENSOR_MAP_INTERLEAVE_NONE,
        CU_TENSOR_MAP_SWIZZLE_NONE, CU_TENSOR_MAP_L2_PROMOTION_NONE, CU_TENSOR_MAP_FLOAT_OOB_FILL_NONE);
  }
  ssm_kernel<<<NCTA, 640, SMEM_BYTES, cudaStreamPerThread>>>(p, tm_in, tm_out);
}
```

```cpp
#include <cuda_runtime.h>
#include <cuda.h>
#include <cuda_bf16.h>
#include <stdint.h>

namespace {
#define FIXA 0
#define FIXB 1
#define CPY(x) (x)
#define FCPY(x) __uint_as_float(opq(__float_as_uint(x), zz))
#define STAG 0

constexpr int L = 2048, D = 512, NM = 128;
constexpr int NCTA = 128;

constexpr int RAW_OFF = 0;
constexpr int XIN_OFF = 32768;
constexpr int BAR_OFF = XIN_OFF + 10240;
constexpr int CH_OFF = BAR_OFF + 128;
constexpr int U_CS = 1184;
constexpr int U_OFF = 0;
constexpr int R_OFF = 4736;
constexpr int RD_X0 = 565;
constexpr int RD_CS = 1216;
constexpr int RS_CS = 320;
constexpr int R_E2 = 2 * RD_CS, R_O2 = R_E2 + 2 * RS_CS, R_E3 = R_O2 + 2 * RS_CS, R_O3 = R_E3 + 2 * RS_CS;
constexpr int R_BR = R_O3 + 2 * RS_CS;
constexpr int W5_OFF = R_OFF + 2 * R_BR;
constexpr int W3_OFF = W5_OFF + 3456;
constexpr int W9_OFF = W3_OFF + 3456;
constexpr int W7_OFF = W9_OFF + 2304;
constexpr int S2_OFF = W7_OFF + 2304;
constexpr int Y0_OFF = S2_OFF + 2304;
constexpr int Y2_OFF = Y0_OFF + 8192, Y3_OFF = Y2_OFF + 6144;
constexpr int CH_BYTES = Y0_OFF + 18432 + 16;
constexpr int SCR_BYTES = 4608;
constexpr int SMEM_BYTES = CH_OFF + 4 * CH_BYTES;
static_assert(CH_BYTES % 128 == 16, "bank staggering of the channel blocks");
static_assert(SMEM_BYTES <= 232448, "smem");
constexpr int B_RAW = BAR_OFF, B_X = BAR_OFF + 8, B_U = BAR_OFF + 40, B_W = BAR_OFF + 48, B_Y2 = BAR_OFF + 56, B_Y3 = BAR_OFF + 96;
constexpr int K1024_OFF = BAR_OFF + 64;

__device__ unsigned int g_gate[L];
__device__ unsigned int g_epoch;
__device__ unsigned int g_ticket;

#define STAMP(k)
#define GT(k)

struct Params {
  const __nv_bfloat16 *u, *A_re, *A_im, *B_re, *B_im, *C_re, *C_im, *A_ldt, *A_D;
  const __nv_bfloat16 *B_lA, *B_Aim, *B_Cre, *B_Cim, *B_ldt, *B_D, *gw;
};

template <int N, int TB> __device__ __forceinline__ void wgmma_rs(float* d, uint32_t a0, uint32_t a1, uint32_t a2, uint32_t a3, uint64_t desc, int sc);
template <> __device__ __forceinline__ void wgmma_rs<64, 0>(float* d, uint32_t a0, uint32_t a1, uint32_t a2, uint32_t a3, uint64_t desc, int sc) {
  asm volatile("{\n.reg .pred p;\nsetp.ne.b32 p, %37, 0;\n"
    "wgmma.mma_async.sync.aligned.m64n64k16.f32.bf16.bf16 {%0,%1,%2,%3,%4,%5,%6,%7,%8,%9,%10,%11,%12,%13,%14,%15,%16,%17,%18,%19,%20,%21,%22,%23,%24,%25,%26,%27,%28,%29,%30,%31}, {%32,%33,%34,%35}, %36, p, 1, 1, 0;\n}"
    : "+f"(d[0]), "+f"(d[1]), "+f"(d[2]), "+f"(d[3]), "+f"(d[4]), "+f"(d[5]), "+f"(d[6]), "+f"(d[7]), "+f"(d[8]), "+f"(d[9]), "+f"(d[10]), "+f"(d[11]), "+f"(d[12]), "+f"(d[13]), "+f"(d[14]), "+f"(d[15]), "+f"(d[16]), "+f"(d[17]), "+f"(d[18]), "+f"(d[19]), "+f"(d[20]), "+f"(d[21]), "+f"(d[22]), "+f"(d[23]), "+f"(d[24]), "+f"(d[25]), "+f"(d[26]), "+f"(d[27]), "+f"(d[28]), "+f"(d[29]), "+f"(d[30]), "+f"(d[31]) : "r"(a0), "r"(a1), "r"(a2), "r"(a3), "l"(desc), "r"(sc));
}
template <> __device__ __forceinline__ void wgmma_rs<56, 0>(float* d, uint32_t a0, uint32_t a1, uint32_t a2, uint32_t a3, uint64_t desc, int sc) {
  asm volatile("{\n.reg .pred p;\nsetp.ne.b32 p, %33, 0;\n"
    "wgmma.mma_async.sync.aligned.m64n56k16.f32.bf16.bf16 {%0,%1,%2,%3,%4,%5,%6,%7,%8,%9,%10,%11,%12,%13,%14,%15,%16,%17,%18,%19,%20,%21,%22,%23,%24,%25,%26,%27}, {%28,%29,%30,%31}, %32, p, 1, 1, 0;\n}"
    : "+f"(d[0]), "+f"(d[1]), "+f"(d[2]), "+f"(d[3]), "+f"(d[4]), "+f"(d[5]), "+f"(d[6]), "+f"(d[7]), "+f"(d[8]), "+f"(d[9]), "+f"(d[10]), "+f"(d[11]), "+f"(d[12]), "+f"(d[13]), "+f"(d[14]), "+f"(d[15]), "+f"(d[16]), "+f"(d[17]), "+f"(d[18]), "+f"(d[19]), "+f"(d[20]), "+f"(d[21]), "+f"(d[22]), "+f"(d[23]), "+f"(d[24]), "+f"(d[25]), "+f"(d[26]), "+f"(d[27]) : "r"(a0), "r"(a1), "r"(a2), "r"(a3), "l"(desc), "r"(sc));
}
template <> __device__ __forceinline__ void wgmma_rs<48, 0>(float* d, uint32_t a0, uint32_t a1, uint32_t a2, uint32_t a3, uint64_t desc, int sc) {
  asm volatile("{\n.reg .pred p;\nsetp.ne.b32 p, %29, 0;\n"
    "wgmma.mma_async.sync.aligned.m64n48k16.f32.bf16.bf16 {%0,%1,%2,%3,%4,%5,%6,%7,%8,%9,%10,%11,%12,%13,%14,%15,%16,%17,%18,%19,%20,%21,%22,%23}, {%24,%25,%26,%27}, %28, p, 1, 1, 0;\n}"
    : "+f"(d[0]), "+f"(d[1]), "+f"(d[2]), "+f"(d[3]), "+f"(d[4]), "+f"(d[5]), "+f"(d[6]), "+f"(d[7]), "+f"(d[8]), "+f"(d[9]), "+f"(d[10]), "+f"(d[11]), "+f"(d[12]), "+f"(d[13]), "+f"(d[14]), "+f"(d[15]), "+f"(d[16]), "+f"(d[17]), "+f"(d[18]), "+f"(d[19]), "+f"(d[20]), "+f"(d[21]), "+f"(d[22]), "+f"(d[23]) : "r"(a0), "r"(a1), "r"(a2), "r"(a3), "l"(desc), "r"(sc));
}
template <> __device__ __forceinline__ void wgmma_rs<32, 0>(float* d, uint32_t a0, uint32_t a1, uint32_t a2, uint32_t a3, uint64_t desc, int sc) {
  asm volatile("{\n.reg .pred p;\nsetp.ne.b32 p, %21, 0;\n"
    "wgmma.mma_async.sync.aligned.m64n32k16.f32.bf16.bf16 {%0,%1,%2,%3,%4,%5,%6,%7,%8,%9,%10,%11,%12,%13,%14,%15}, {%16,%17,%18,%19}, %20, p, 1, 1, 0;\n}"
    : "+f"(d[0]), "+f"(d[1]), "+f"(d[2]), "+f"(d[3]), "+f"(d[4]), "+f"(d[5]), "+f"(d[6]), "+f"(d[7]), "+f"(d[8]), "+f"(d[9]), "+f"(d[10]), "+f"(d[11]), "+f"(d[12]), "+f"(d[13]), "+f"(d[14]), "+f"(d[15]) : "r"(a0), "r"(a1), "r"(a2), "r"(a3), "l"(desc), "r"(sc));
}
template <> __device__ __forceinline__ void wgmma_rs<48, 1>(float* d, uint32_t a0, uint32_t a1, uint32_t a2, uint32_t a3, uint64_t desc, int sc) {
  asm volatile("{\n.reg .pred p;\nsetp.ne.b32 p, %29, 0;\n"
    "wgmma.mma_async.sync.aligned.m64n48k16.f32.bf16.bf16 {%0,%1,%2,%3,%4,%5,%6,%7,%8,%9,%10,%11,%12,%13,%14,%15,%16,%17,%18,%19,%20,%21,%22,%23}, {%24,%25,%26,%27}, %28, p, 1, 1, 1;\n}"
    : "+f"(d[0]), "+f"(d[1]), "+f"(d[2]), "+f"(d[3]), "+f"(d[4]), "+f"(d[5]), "+f"(d[6]), "+f"(d[7]), "+f"(d[8]), "+f"(d[9]), "+f"(d[10]), "+f"(d[11]), "+f"(d[12]), "+f"(d[13]), "+f"(d[14]), "+f"(d[15]), "+f"(d[16]), "+f"(d[17]), "+f"(d[18]), "+f"(d[19]), "+f"(d[20]), "+f"(d[21]), "+f"(d[22]), "+f"(d[23]) : "r"(a0), "r"(a1), "r"(a2), "r"(a3), "l"(desc), "r"(sc));
}
template <> __device__ __forceinline__ void wgmma_rs<40, 1>(float* d, uint32_t a0, uint32_t a1, uint32_t a2, uint32_t a3, uint64_t desc, int sc) {
  asm volatile("{\n.reg .pred p;\nsetp.ne.b32 p, %25, 0;\n"
    "wgmma.mma_async.sync.aligned.m64n40k16.f32.bf16.bf16 {%0,%1,%2,%3,%4,%5,%6,%7,%8,%9,%10,%11,%12,%13,%14,%15,%16,%17,%18,%19}, {%20,%21,%22,%23}, %24, p, 1, 1, 1;\n}"
    : "+f"(d[0]), "+f"(d[1]), "+f"(d[2]), "+f"(d[3]), "+f"(d[4]), "+f"(d[5]), "+f"(d[6]), "+f"(d[7]), "+f"(d[8]), "+f"(d[9]), "+f"(d[10]), "+f"(d[11]), "+f"(d[12]), "+f"(d[13]), "+f"(d[14]), "+f"(d[15]), "+f"(d[16]), "+f"(d[17]), "+f"(d[18]), "+f"(d[19]) : "r"(a0), "r"(a1), "r"(a2), "r"(a3), "l"(desc), "r"(sc));
}
template <> __device__ __forceinline__ void wgmma_rs<32, 1>(float* d, uint32_t a0, uint32_t a1, uint32_t a2, uint32_t a3, uint64_t desc, int sc) {
  asm volatile("{\n.reg .pred p;\nsetp.ne.b32 p, %21, 0;\n"
    "wgmma.mma_async.sync.aligned.m64n32k16.f32.bf16.bf16 {%0,%1,%2,%3,%4,%5,%6,%7,%8,%9,%10,%11,%12,%13,%14,%15}, {%16,%17,%18,%19}, %20, p, 1, 1, 1;\n}"
    : "+f"(d[0]), "+f"(d[1]), "+f"(d[2]), "+f"(d[3]), "+f"(d[4]), "+f"(d[5]), "+f"(d[6]), "+f"(d[7]), "+f"(d[8]), "+f"(d[9]), "+f"(d[10]), "+f"(d[11]), "+f"(d[12]), "+f"(d[13]), "+f"(d[14]), "+f"(d[15]) : "r"(a0), "r"(a1), "r"(a2), "r"(a3), "l"(desc), "r"(sc));
}
template <> __device__ __forceinline__ void wgmma_rs<16, 1>(float* d, uint32_t a0, uint32_t a1, uint32_t a2, uint32_t a3, uint64_t desc, int sc) {
  asm volatile("{\n.reg .pred p;\nsetp.ne.b32 p, %13, 0;\n"
    "wgmma.mma_async.sync.aligned.m64n16k16.f32.bf16.bf16 {%0,%1,%2,%3,%4,%5,%6,%7}, {%8,%9,%10,%11}, %12, p, 1, 1, 1;\n}"
    : "+f"(d[0]), "+f"(d[1]), "+f"(d[2]), "+f"(d[3]), "+f"(d[4]), "+f"(d[5]), "+f"(d[6]), "+f"(d[7]) : "r"(a0), "r"(a1), "r"(a2), "r"(a3), "l"(desc), "r"(sc));
}

__device__ __forceinline__ uint32_t pack_bf16(float lo, float hi) {
  uint32_t r; asm("cvt.rn.bf16x2.f32 %0, %1, %2;" : "=r"(r) : "f"(hi), "f"(lo)); return r;
}
__device__ __forceinline__ float bf_lo(uint32_t v) { return __uint_as_float(v << 16); }
__device__ __forceinline__ float bf_hi(uint32_t v) { return __uint_as_float(v & 0xffff0000u); }
__device__ __forceinline__ float bf_round(float x) { return bf_lo(pack_bf16(x, 0.f)); }
__device__ __forceinline__ uint32_t hmul2(uint32_t a, uint32_t b) { uint32_t r; asm("mul.rn.bf16x2 %0, %1, %2;" : "=r"(r) : "r"(a), "r"(b)); return r; }
__device__ __forceinline__ uint32_t hadd2(uint32_t a, uint32_t b) { uint32_t r; asm("add.rn.bf16x2 %0, %1, %2;" : "=r"(r) : "r"(a), "r"(b)); return r; }
__device__ __forceinline__ uint32_t hsub2(uint32_t a, uint32_t b) { uint32_t r; asm("sub.rn.bf16x2 %0, %1, %2;" : "=r"(r) : "r"(a), "r"(b)); return r; }
__device__ __forceinline__ uint32_t hfma2(uint32_t a, uint32_t b, uint32_t c) { uint32_t r; asm("fma.rn.bf16x2 %0, %1, %2, %3;" : "=r"(r) : "r"(a), "r"(b), "r"(c)); return r; }

__device__ __forceinline__ void sts16(uint32_t a, uint32_t v) { asm volatile("st.shared.b16 [%0], %1;" ::"r"(a), "h"((unsigned short)v) : "memory"); }
__device__ __forceinline__ void sts32(uint32_t a, uint32_t v) { asm volatile("st.shared.b32 [%0], %1;" ::"r"(a), "r"(v) : "memory"); }
__device__ __forceinline__ void sts64(uint32_t a, uint32_t x, uint32_t y) { asm volatile("st.shared.v2.b32 [%0], {%1,%2};" ::"r"(a), "r"(x), "r"(y) : "memory"); }
__device__ __forceinline__ void sts128(uint32_t a, uint32_t x, uint32_t y, uint32_t z, uint32_t w) {
  asm volatile("st.shared.v4.b32 [%0], {%1,%2,%3,%4};" ::"r"(a), "r"(x), "r"(y), "r"(z), "r"(w) : "memory");
}
__device__ __forceinline__ uint32_t lds32(uint32_t a) { uint32_t v; asm volatile("ld.shared.b32 %0, [%1];" : "=r"(v) : "r"(a) : "memory"); return v; }
__device__ __forceinline__ uint2 lds64(uint32_t a) { uint2 v; asm volatile("ld.shared.v2.b32 {%0,%1}, [%2];" : "=r"(v.x), "=r"(v.y) : "r"(a) : "memory"); return v; }
__device__ __forceinline__ uint4 lds128(uint32_t a) {
  uint4 v; asm volatile("ld.shared.v4.b32 {%0,%1,%2,%3}, [%4];" : "=r"(v.x), "=r"(v.y), "=r"(v.z), "=r"(v.w) : "r"(a) : "memory"); return v;
}
__device__ __forceinline__ void ldsm4(uint32_t a, uint32_t& r0, uint32_t& r1, uint32_t& r2, uint32_t& r3) {
  asm volatile("ldmatrix.sync.aligned.m8n8.x4.shared.b16 {%0,%1,%2,%3}, [%4];" : "=r"(r0), "=r"(r1), "=r"(r2), "=r"(r3) : "r"(a) : "memory");
}
__device__ __forceinline__ void ldsm4t(uint32_t a, uint32_t& r0, uint32_t& r1, uint32_t& r2, uint32_t& r3) {
  asm volatile("ldmatrix.sync.aligned.m8n8.x4.trans.shared.b16 {%0,%1,%2,%3}, [%4];" : "=r"(r0), "=r"(r1), "=r"(r2), "=r"(r3) : "r"(a) : "memory");
}
__device__ __forceinline__ void stsm4(uint32_t a, uint32_t r0, uint32_t r1, uint32_t r2, uint32_t r3) {
  asm volatile("stmatrix.sync.aligned.m8n8.x4.shared.b16 [%0], {%1,%2,%3,%4};" ::"r"(a), "r"(r0), "r"(r1), "r"(r2), "r"(r3) : "memory");
}
__device__ __forceinline__ void stsm4t(uint32_t a, uint32_t r0, uint32_t r1, uint32_t r2, uint32_t r3) {
  asm volatile("stmatrix.sync.aligned.m8n8.x4.trans.shared.b16 [%0], {%1,%2,%3,%4};" ::"r"(a), "r"(r0), "r"(r1), "r"(r2), "r"(r3) : "memory");
}
__device__ __forceinline__ void mma16816(float* c, uint32_t a0, uint32_t a1, uint32_t a2, uint32_t a3, uint32_t b0, uint32_t b1) {
  asm("mma.sync.aligned.m16n8k16.row.col.f32.bf16.bf16.f32 {%0,%1,%2,%3}, {%4,%5,%6,%7}, {%8,%9}, {%0,%1,%2,%3};"
      : "+f"(c[0]), "+f"(c[1]), "+f"(c[2]), "+f"(c[3]) : "r"(a0), "r"(a1), "r"(a2), "r"(a3), "r"(b0), "r"(b1));
}
__device__ __forceinline__ void bar_sync(int id, int n) { asm volatile("bar.sync %0, %1;" ::"r"(id), "r"(n) : "memory"); }
__device__ __forceinline__ void bar_arrive(int id, int n) { asm volatile("bar.arrive %0, %1;" ::"r"(id), "r"(n) : "memory"); }
__device__ __forceinline__ void wg_fence() { asm volatile("wgmma.fence.sync.aligned;" ::: "memory"); }
__device__ __forceinline__ void wg_commit() { asm volatile("wgmma.commit_group.sync.aligned;" ::: "memory"); }
__device__ __forceinline__ void wg_wait0() { asm volatile("wgmma.wait_group.sync.aligned 0;" ::: "memory"); }
__device__ __forceinline__ void fence_async() { asm volatile("fence.proxy.async.shared::cta;" ::: "memory"); }
__device__ __forceinline__ uint32_t opq(uint32_t x, uint32_t z) { uint32_t r; asm volatile("xor.b32 %0, %1, %2;" : "=r"(r) : "r"(x), "r"(z)); return r; }
__device__ __forceinline__ uint64_t mkdesc(uint32_t addr, uint32_t lbo, uint32_t sbo) {
  return (uint64_t)((addr & 0x3FFFF) >> 4) | ((uint64_t)(lbo >> 4) << 16) | ((uint64_t)(sbo >> 4) << 32);
}
__device__ __forceinline__ uint32_t mapa(uint32_t a, uint32_t rank) {
  uint32_t r; asm("mapa.shared::cluster.u32 %0, %1, %2;" : "=r"(r) : "r"(a), "r"(rank)); return r;
}
__device__ __forceinline__ void mbar_init_expect(uint32_t bar, uint32_t bytes) {
  asm volatile("mbarrier.init.shared::cta.b64 [%0], 1;" ::"r"(bar) : "memory");
  asm volatile("mbarrier.arrive.expect_tx.shared::cta.b64 _, [%0], %1;" ::"r"(bar), "r"(bytes) : "memory");
}
__device__ __forceinline__ void mbar_wait(uint32_t bar) {
#pragma unroll 1
  for (int it = 0; it < (1 << 22); it++) {
    uint32_t ok;
    asm volatile("{\n.reg .pred p;\nmbarrier.try_wait.parity.acquire.cluster.shared::cta.b64 p, [%1], 0;\nselp.u32 %0, 1, 0, p;\n}"
                 : "=r"(ok) : "r"(bar) : "memory");
    if (ok) return;
  }
  __trap();
}
__device__ __forceinline__ void st_async4(uint32_t a, uint32_t bar, uint32_t x, uint32_t y, uint32_t z, uint32_t w) {
  asm volatile("st.async.weak.shared::cluster.mbarrier::complete_tx::bytes.v4.b32 [%0], {%2,%3,%4,%5}, [%1];"
               ::"r"(a), "r"(bar), "r"(x), "r"(y), "r"(z), "r"(w) : "memory");
}

struct cf { float re, im; };
__device__ __forceinline__ cf cmul(cf a, cf b) { return {fmaf(a.re, b.re, -a.im * b.im), fmaf(a.re, b.im, a.im * b.re)}; }
__device__ __forceinline__ cf csq(cf a) { return {fmaf(a.re, a.re, -a.im * a.im), (a.re + a.re) * a.im}; }
__device__ __forceinline__ cf cexp_p(float xl, float y, float p) {
  float mag; asm("ex2.approx.ftz.f32 %0, %1;" : "=f"(mag) : "f"(xl * p));
  const float th = y * p;
  const float k = rintf(th * 0.15915494309189535f);
  float r = fmaf(k, -6.2831854820251465f, th);
  r = fmaf(k, 1.7484555314695172e-07f, r);
  return {mag * __cosf(r), mag * __sinf(r)};
}
__device__ __forceinline__ uint32_t ysw(int c) { return (uint32_t)(c ^ ((c >> 3) & 3)) * 16u; }

#define CMUL2(OR, OI, xr, xi, yr, yi, nyi) do { OR = hfma2(xr, yr, hmul2(xi, nyi)); OI = hfma2(xr, yi, hmul2(xi, yr)); } while (0)

__device__ __forceinline__ uint32_t gate_slow(const __nv_bfloat16* u, const __nv_bfloat16* gw, int row) {
  float s = 0.f;
  const uint32_t* xr = (const uint32_t*)(u + (size_t)row * D);
  const uint32_t* wr = (const uint32_t*)gw;
#pragma unroll 1
  for (int j = 0; j < D / 2; j++) { const uint32_t pr = hmul2(xr[j], wr[j]); s += bf_lo(pr); s += bf_hi(pr); }
  s = bf_round(s);
  return pack_bf16(1.f / (1.f + expf(-s)), 0.f);
}

__device__ __forceinline__ uint2 gate_ld(int x) {
  uint2 gv;
  asm volatile("ld.relaxed.gpu.global.v2.u32 {%0,%1}, [%2];" : "=r"(gv.x), "=r"(gv.y) : "l"(g_gate + x * 2) : "memory");
  return gv;
}
__device__ __noinline__ uint32_t gate_poll(const __nv_bfloat16* u, const __nv_bfloat16* gw, int x, uint32_t tag) {
  uint2 gv;
#pragma unroll 1
  for (int spins = 0; spins < (1 << 16); spins++) {
    gv = gate_ld(x);
    if ((gv.x >> 16) == tag && (gv.y >> 16) == tag) return __byte_perm(gv.x, gv.y, 0x5410);
  }
  return __byte_perm(gate_slow(u, gw, x * 2), gate_slow(u, gw, x * 2 + 1), 0x5410);
}
__device__ __forceinline__ uint32_t gate_fin(const Params& p, uint2 gv, int x, uint32_t tag) {
  if ((gv.x >> 16) == tag && (gv.y >> 16) == tag) return __byte_perm(gv.x, gv.y, 0x5410);
  return gate_poll(p.u, p.gw, x, tag);
}

__device__ __forceinline__ void ld4ch(uint32_t* v, uint32_t addr) {
#pragma unroll
  for (int k = 0; k < 4; k++) v[k] = lds32(addr + k * CH_BYTES);
}
__device__ __forceinline__ void skip_terms(uint32_t* ua, uint32_t* ub, uint32_t sb, int x, uint2 dA, uint2 dB) {
  const int c = x >> 2;
  uint32_t uu[4];
  ld4ch(uu, sb + CH_OFF + (x & 3) * 4 + U_OFF + (c & 3) * U_CS + (63 - (c >> 2)) * 16);
#pragma unroll
  for (int k = 0; k < 4; k++) {
    ua[k] = hmul2(uu[k], __byte_perm((k & 2) ? dA.y : dA.x, 0, (k & 1) ? 0x3232 : 0x1010));
    ub[k] = hmul2(uu[k], __byte_perm((k & 2) ? dB.y : dB.x, 0, (k & 1) ? 0x3232 : 0x1010));
  }
}
__device__ __forceinline__ uint4 mix(const uint32_t* a, const uint32_t* b, const uint32_t* ua, const uint32_t* ub, uint32_t g2) {
  const uint32_t h2 = hsub2(0x3f803f80u, g2);
  uint32_t o[4];
#pragma unroll
  for (int k = 0; k < 4; k++) o[k] = hadd2(hmul2(g2, hadd2(a[k], ua[k])), hmul2(h2, hadd2(b[k], ub[k])));
  return make_uint4(__byte_perm(o[0], o[1], 0x5410), __byte_perm(o[2], o[3], 0x5410), __byte_perm(o[0], o[1], 0x7632), __byte_perm(o[2], o[3], 0x7632));
}
__device__ __forceinline__ void send_box(uint32_t sb, int slot, int wtid, uint32_t rank, uint4 r) {
  st_async4(mapa(sb + XIN_OFF + slot * 2048 + wtid * 16, rank ^ 1), mapa(sb + B_X + slot * 8, rank ^ 1), r.x, r.y, r.z, r.w);
}
__device__ __forceinline__ void merge_box(uint32_t sb, const CUtensorMap* tm_out, int slot, int wtid, uint32_t rank, int oc0, uint4 r, int barid) {
  const uint32_t st = sb + RAW_OFF + slot * 4096 + wtid * 16;
  sts64(st + rank * 8, r.x, r.y); sts64(st + 2048 + rank * 8, r.z, r.w);
  mbar_wait(sb + B_X + slot * 8);
  const uint4 q = lds128(sb + XIN_OFF + slot * 2048 + wtid * 16);
  sts64(st + (rank ^ 1) * 8, q.x, q.y); sts64(st + 2048 + (rank ^ 1) * 8, q.z, q.w);
  fence_async();
  bar_sync(barid, 128);
  if (wtid == 0) {
    asm volatile("cp.async.bulk.tensor.3d.global.shared::cta.bulk_group [%0, {%2, %3, %4}], [%1];"
                 ::"l"(tm_out), "r"(sb + RAW_OFF + slot * 4096), "r"(oc0), "r"((2 * slot + (int)rank) * 128), "r"(0) : "memory");
    asm volatile("cp.async.bulk.commit_group;" ::: "memory");
  }
}

__device__ __forceinline__ uint32_t band2(int e, int lo, int hi) {
  return ((uint32_t)(e - lo) <= (uint32_t)(hi - lo) ? 0x3f80u : 0u) | ((uint32_t)(e - 1 - lo) <= (uint32_t)(hi - lo) ? 0x3f800000u : 0u);
}

__device__ __forceinline__ void conv_dense(uint32_t cb, uint32_t zz) {
  const int lane = threadIdx.x & 31, wq = (threadIdx.x >> 5) & 3, br = wq >> 1, hf = wq & 1, g = lane >> 2, t = lane & 3;
  const uint32_t rb = cb + R_OFF + br * R_BR;
  const int eo = 16 * hf + g - 2 * t;
  float dacc[32];
  {
      {
        const int x0 = RD_X0 - (eo + 536);
        const uint32_t fa = rb + ((g & 1) ? 2 * x0 : RD_CS + 2 * x0 + 2);
        const uint64_t ub = mkdesc(cb + U_OFF, U_CS, 128);
        uint32_t A[2][4][4];
        float e56[28], e48[24];
        auto loadA = [&](int j) {
#pragma unroll
          for (int k = 0; k < 4; k++) {
            const int s = 34 - 4 * j - k;
            if (s >= 0) {
              if (k == 0) A[j & 1][0][2] = lds32(fa + (2 * s + 2) * 16);
              A[j & 1][k][0] = lds32(fa + (2 * s + 1) * 16);
              A[j & 1][k][1] = lds32(fa + (2 * s) * 16);
            }
          }
#pragma unroll
          for (int k = 0; k < 4; k++) {
            if (34 - 4 * j - k >= 0) {
              A[j & 1][k][3] = CPY(A[j & 1][k][0]);
              if (k) A[j & 1][k][2] = CPY(A[j & 1][k - 1][1]);
            }
          }
        };
        loadA(0);
#pragma unroll
        for (int j = 0; j < 9; j++) {
          if (j == 4) {
#pragma unroll
            for (int i = 0; i < 28; i++) e56[i] = FCPY(dacc[i]);
          }
          if (j == 8) {
#pragma unroll
            for (int i = 0; i < 24; i++) e48[i] = FCPY(e56[i]);
          }
          wg_fence();
#pragma unroll
          for (int k = 0; k < 4; k++) {
            const int s = 34 - 4 * j - k;
            if (s >= 0) {
              const int o = 2 * s - 66 + 128;
              const int cc = o & 3, rs = (o >> 2) - 32;
              const int n0 = ((-rs) >> 3) * 8;
              const uint64_t desc = ub + (uint64_t)((cc * U_CS - rs * 16) >> 4);
              const uint32_t* a = A[j & 1][k];
              if (n0 == 0) wgmma_rs<64, 0>(dacc, a[0], a[1], a[2], a[3], desc, s != 34);
              else if (n0 == 8) wgmma_rs<56, 0>(FIXB ? e56 : dacc, a[0], a[1], a[2], a[3], desc, 1);
              else wgmma_rs<48, 0>(FIXB ? e48 : dacc, a[0], a[1], a[2], a[3], desc, 1);
            }
          }
          wg_commit();
          if (j < 8) loadA(j + 1);
          wg_wait0();
        }
#pragma unroll
        for (int i = 0; i < 28; i++) dacc[i] = i < 24 ? e48[i] : e56[i];
      }
      const uint32_t yb = cb + Y0_OFF + br * 4096;
#pragma unroll
      for (int i = 0; i < 8; i += 2) {
        const int mi = lane >> 3;
        const int cidx = 4 * (63 - 8 * (i + (mi >> 1)) - (lane & 7)) + 2 * hf + (mi & 1);
        stsm4t(yb + ysw(cidx), pack_bf16(dacc[4 * i], dacc[4 * i + 1]), pack_bf16(dacc[4 * i + 2], dacc[4 * i + 3]),
               pack_bf16(dacc[4 * i + 4], dacc[4 * i + 5]), pack_bf16(dacc[4 * i + 6], dacc[4 * i + 7]));
      }
      bar_arrive(8, 640);
      STAMP(8);
  }
}

__device__ __forceinline__ void conv_far(uint32_t sb, uint32_t cb, uint32_t zz) {
  const int lane = threadIdx.x & 31, wq = (threadIdx.x >> 5) & 3, br = wq >> 1, hf = wq & 1, g = lane >> 2, t = lane & 3;
  const uint32_t rb = cb + R_OFF + br * R_BR;
  const int eo = 16 * hf + g - 2 * t;
  float dacc[24], e40[20], e32[16], h32[16], h16[8];
  const int x1 = 159 - (eo + 136);
  const uint32_t fs = rb + ((g & 1) ? 2 * x1 : RS_CS + 2 * x1 + 2);
  {
    uint32_t A[2][4][4];
    auto loadA = [&](int buf, uint32_t oe, uint32_t oo, int i0) {
#pragma unroll
      for (int a = 0; a < 2; a++) {
        const uint32_t base = fs + (a ? oo : oe) + i0 * 16;
        uint32_t* k0 = A[buf][2 * a];
        uint32_t* k1 = A[buf][2 * a + 1];
        k0[1] = lds32(base); k0[0] = lds32(base + 16); k0[2] = lds32(base + 32); k1[0] = lds32(base + 48); k1[2] = lds32(base + 64);
      }
#pragma unroll
      for (int a = 0; a < 2; a++) {
        uint32_t* k0 = A[buf][2 * a];
        uint32_t* k1 = A[buf][2 * a + 1];
        k0[3] = CPY(k0[0]); k1[1] = CPY(k0[2]); k1[3] = CPY(k1[0]);
      }
    };
    const uint64_t d5 = mkdesc(cb + W5_OFF, 144, 576), d3 = mkdesc(cb + W3_OFF, 144, 576);
    loadA(0, R_E2, R_O2, 8);
#pragma unroll
    for (int m = 2; m <= 4; m++) {
      if (m == 3) {
#pragma unroll
        for (int i = 0; i < 20; i++) e40[i] = FCPY(dacc[i]);
      }
      if (m == 4) {
#pragma unroll
        for (int i = 0; i < 16; i++) e32[i] = FCPY(e40[i]);
      }
      wg_fence();
#pragma unroll
      for (int k = 0; k < 4; k++) {
        const uint32_t* a = A[m & 1][k];
        const uint64_t desc = ((k >> 1) ? d3 : d5) + (k & 1) * 18 + (m - 2) * 36;
        if (m == 2) wgmma_rs<48, 1>(dacc, a[0], a[1], a[2], a[3], desc, k);
        else if (m == 3) wgmma_rs<40, 1>(e40, a[0], a[1], a[2], a[3], desc, 1);
        else wgmma_rs<32, 1>(e32, a[0], a[1], a[2], a[3], desc, 1);
      }
      wg_commit();
      if (m < 4) loadA((m + 1) & 1, R_E2, R_O2, 4 * (3 - m));
      else loadA(1, R_E3, R_O3, 8);
      wg_wait0();
    }
#pragma unroll
    for (int i = 0; i < 20; i++) dacc[i] = i < 16 ? e32[i] : e40[i];
    {
      const uint32_t yb = cb + Y2_OFF + br * 3072;
#pragma unroll
      for (int i = 0; i < 6; i += 2) {
        const int mi = lane >> 3;
        const int cidx = 32 * (5 - i - (mi >> 1)) + 16 * hf + 8 * (mi & 1) + (lane & 7);
        stsm4(yb + ysw(cidx), pack_bf16(dacc[4 * i], dacc[4 * i + 1]), pack_bf16(dacc[4 * i + 2], dacc[4 * i + 3]),
              pack_bf16(dacc[4 * i + 4], dacc[4 * i + 5]), pack_bf16(dacc[4 * i + 6], dacc[4 * i + 7]));
      }
    }
    __syncwarp();
    if (lane == 0) asm volatile("mbarrier.arrive.shared::cta.b64 _, [%0];" ::"r"(sb + B_Y2) : "memory");
    STAMP(9);
    const uint64_t d9 = mkdesc(cb + W9_OFF, 144, 576), d7 = mkdesc(cb + W7_OFF, 144, 576);
#pragma unroll
    for (int m = 2; m <= 3; m++) {
      if (m == 3) {
#pragma unroll
        for (int i = 0; i < 8; i++) h16[i] = FCPY(h32[i]);
      }
      wg_fence();
#pragma unroll
      for (int k = 0; k < 4; k++) {
        const uint32_t* a = A[(m + 1) & 1][k];
        const uint64_t desc = ((k >> 1) ? d7 : d9) + (k & 1) * 18 + (m - 2) * 72;
        if (m == 2) wgmma_rs<32, 1>(h32, a[0], a[1], a[2], a[3], desc, k);
        else wgmma_rs<16, 1>(h16, a[0], a[1], a[2], a[3], desc, 1);
      }
      wg_commit();
      if (m == 2) loadA(0, R_E3, R_O3, 4);
      wg_wait0();
    }
#pragma unroll
    for (int i = 0; i < 16; i++) dacc[i] = i < 8 ? h16[i] : h32[i];
    const uint32_t yb = cb + Y3_OFF + br * 2048;
#pragma unroll
    for (int i = 0; i < 4; i += 2) {
      const int mi = lane >> 3;
      const int cidx = 64 * (1 - (i >> 1)) + 2 * (16 * hf + 8 * (mi & 1) + (lane & 7)) + (mi >> 1);
      stsm4(yb + ysw(cidx), pack_bf16(dacc[4 * i], dacc[4 * i + 1]), pack_bf16(dacc[4 * i + 2], dacc[4 * i + 3]),
            pack_bf16(dacc[4 * i + 4], dacc[4 * i + 5]), pack_bf16(dacc[4 * i + 6], dacc[4 * i + 7]));
    }
  }
}

__global__ void __cluster_dims__(2, 1, 1) __launch_bounds__(640, 1)
ssm_kernel(const Params p, const __grid_constant__ CUtensorMap tm_in, const __grid_constant__ CUtensorMap tm_out) {
  extern __shared__ __align__(1024) unsigned char smem_raw[];
  const uint32_t sb = (uint32_t)__cvta_generic_to_shared(smem_raw);
  const int tid = threadIdx.x, lane = tid & 31;
  const int warp = __shfl_sync(0xffffffffu, tid >> 5, 0);
  const int ch = warp >> 2, wq = warp & 3, br = wq >> 1, hf = wq & 1;
  const int g = lane >> 2, t = lane & 3;
  const int d = blockIdx.x * 4 + ch;
  const uint32_t rank = blockIdx.x & 1;
  const uint32_t cb = sb + CH_OFF + ch * CH_BYTES;
  const int wtid = tid & 127;
  const int oc0 = (int)(blockIdx.x >> 1) * 8;
  STAMP(0); GT(0);

  if (warp >= 16) {
    if (wtid == 0) {
      mbar_init_expect(sb + B_RAW, 32768);
#pragma unroll
      for (int i = 0; i < 4; i++) mbar_init_expect(sb + B_X + 8 * i, 2048);
      asm volatile("mbarrier.init.shared::cta.b64 [%0], 128;" ::"r"(sb + B_U) : "memory");
      asm volatile("mbarrier.init.shared::cta.b64 [%0], 128;" ::"r"(sb + B_W) : "memory");
      asm volatile("mbarrier.init.shared::cta.b64 [%0], 16;" ::"r"(sb + B_Y2) : "memory");
      asm volatile("mbarrier.init.shared::cta.b64 [%0], 16;" ::"r"(sb + B_Y3) : "memory");
      asm volatile("fence.mbarrier_init.release.cluster;" ::: "memory");
      asm volatile("fence.proxy.async.shared::cta;" ::: "memory");
    }
    __syncwarp();
    asm volatile("barrier.cluster.arrive.relaxed.aligned;" ::: "memory");
    unsigned int epoch;
    asm volatile("ld.relaxed.gpu.global.u32 %0, [%1];" : "=r"(epoch) : "l"(&g_epoch) : "memory");
    const uint2 dA = *(const uint2*)(p.A_D + blockIdx.x * 4), dB = *(const uint2*)(p.B_D + blockIdx.x * 4);
    const uint4 gw0 = *(const uint4*)(p.gw + lane * 8), gw1 = *(const uint4*)(p.gw + 256 + lane * 8);
    asm volatile("barrier.cluster.wait.aligned;" ::: "memory");
    if (wtid == 0) {
      asm volatile("cp.async.bulk.tensor.5d.shared::cluster.global.mbarrier::complete_tx::bytes.multicast::cluster [%0], [%1, {%3, %4, %4, %4, %5}], [%2], %6;"
                   ::"r"(sb + RAW_OFF + rank * 16384), "l"(&tm_in), "r"(sb + B_RAW), "r"(oc0), "r"(0), "r"((int)rank * 32), "h"((unsigned short)3) : "memory");
    }
    sts128(sb + CH_OFF + wq * CH_BYTES + U_OFF + (lane >> 3) * U_CS + (64 + (lane & 7)) * 16, 0, 0, 0, 0);
    uint32_t BA[3][4], BB[4][4], BC[3][4];
    {
      const int eo = 16 * hf + g - 2 * t;
      const int l1 = br ? 3 : 6, h1 = br ? 5 : 10, l2 = br ? 5 : 12, h2 = br ? 11 : 20;
#pragma unroll
      for (int i = 0; i < 4; i++) {
        const int e = eo + 32 - 16 * i;
        BB[i][0] = band2(e, l2, h2); BB[i][1] = band2(e + 8, l2, h2); BB[i][2] = band2(e - 8, l2, h2); BB[i][3] = BB[i][0];
        if (i) {
          BA[i - 1][0] = band2(e, l1, h1); BA[i - 1][1] = band2(e + 8, l1, h1); BA[i - 1][2] = band2(e - 8, l1, h1); BA[i - 1][3] = BA[i - 1][0];
          BC[i - 1][0] = band2(e, 3, 4); BC[i - 1][1] = band2(e + 8, 3, 4); BC[i - 1][2] = band2(e - 8, 3, 4); BC[i - 1][3] = BC[i - 1][0];
        }
      }
    }
    STAMP(3);
    mbar_wait(sb + B_RAW);
    STAMP(4);
    {
      const uint32_t dst = sb + CH_OFF + (g & 3) * CH_BYTES + U_OFF + t * U_CS + (63 - wq * 16) * 16;
#pragma unroll
      for (int h = 0; h < 2; h++) {
        uint32_t r[8][4];
#pragma unroll
        for (int i = 0; i < 8; i++) ldsm4t(sb + RAW_OFF + (wq * 16 + h * 8 + i) * 512 + lane * 16, r[i][0], r[i][1], r[i][2], r[i][3]);
        if ((uint32_t)(g >> 2) == rank) {
#pragma unroll
          for (int i = 0; i < 8; i++) sts128(dst - (h * 8 + i) * 16, r[i][0], r[i][1], r[i][2], r[i][3]);
        }
      }
    }
    fence_async();
    asm volatile("mbarrier.arrive.shared::cta.b64 _, [%0];" ::"r"(sb + B_U) : "memory");
    bar_sync(5, 128);
    STAMP(5);
    {
      const uint32_t mrow = lane & 7, mi = lane >> 3;
#pragma unroll 1
      for (int k = 0; k < 4; k++) {
        const uint32_t kb = sb + CH_OFF + k * CH_BYTES;
        const uint64_t ub = mkdesc(kb + U_OFF, U_CS, 128);
        float w1[24], w2[16], w3[16];
        wg_fence();
#pragma unroll
        for (int i = 0; i < 3; i++)
          wgmma_rs<48, 0>(w1, BA[i][0], BA[i][1], BA[i][2], BA[i][3], ub + (uint64_t)((((2 * i + 2) & 3) * U_CS + (16 + (i == 0)) * 16) >> 4), i);
#pragma unroll
        for (int i = 0; i < 4; i++)
          wgmma_rs<32, 0>(w2, BB[i][0], BB[i][1], BB[i][2], BB[i][3], ub + (uint64_t)((((2 * i) & 3) * U_CS + (32 + (i < 2)) * 16) >> 4), i);
#pragma unroll
        for (int i = 0; i < 3; i++)
          wgmma_rs<32, 0>(w3, BC[i][0], BC[i][1], BC[i][2], BC[i][3], ub + (uint64_t)((((2 * i + 2) & 3) * U_CS + (32 + (i == 0)) * 16) >> 4), i);
        wg_commit();
        wg_wait0();
#pragma unroll
        for (int i = 0; i < 6; i += 2) {
          const int c = 4 * (47 - 8 * (i + (int)(mi >> 1)) - (int)mrow) + 2 * hf + (int)(mi & 1);
          stsm4t(kb + (br ? W3_OFF : W5_OFF) + (5 - (c >> 5)) * 576 + ((c & 31) >> 3) * 144 + (c & 7) * 16,
                 pack_bf16(w1[4 * i], w1[4 * i + 1]), pack_bf16(w1[4 * i + 2], w1[4 * i + 3]),
                 pack_bf16(w1[4 * i + 4], w1[4 * i + 5]), pack_bf16(w1[4 * i + 6], w1[4 * i + 7]));
        }
#pragma unroll
        for (int i = 0; i < 4; i += 2) {
          const int c = 4 * (31 - 8 * (i + (int)(mi >> 1)) - (int)mrow) + 2 * hf + (int)(mi & 1), pp = c >> 1;
          stsm4t(kb + (br ? W7_OFF : W9_OFF) + (1 - (pp >> 5)) * 1152 + (c & 1) * 576 + ((pp & 31) >> 3) * 144 + (pp & 7) * 16,
                 pack_bf16(w2[4 * i], w2[4 * i + 1]), pack_bf16(w2[4 * i + 2], w2[4 * i + 3]),
                 pack_bf16(w2[4 * i + 4], w2[4 * i + 5]), pack_bf16(w2[4 * i + 6], w2[4 * i + 7]));
          if (br == 0)
            stsm4t(kb + S2_OFF + (c + (c >> 3)) * 16,
                   pack_bf16(w3[4 * i], w3[4 * i + 1]), pack_bf16(w3[4 * i + 2], w3[4 * i + 3]),
                   pack_bf16(w3[4 * i + 4], w3[4 * i + 5]), pack_bf16(w3[4 * i + 6], w3[4 * i + 7]));
        }
      }
    }
    fence_async();
    asm volatile("mbarrier.arrive.shared::cta.b64 _, [%0];" ::"r"(sb + B_W) : "memory");
    STAMP(7);
    const uint32_t tag = (epoch + 1) & 0xffffu;
    {
      const int grow = blockIdx.x * 16 + wq * 4;
      uint4 gx[4][2];
#pragma unroll
      for (int i = 0; i < 4; i++) {
        gx[i][0] = *(const uint4*)(p.u + (size_t)(grow + i) * D + lane * 8);
        gx[i][1] = *(const uint4*)(p.u + (size_t)(grow + i) * D + 256 + lane * 8);
      }
      const uint32_t ws[8] = {gw0.x, gw0.y, gw0.z, gw0.w, gw1.x, gw1.y, gw1.z, gw1.w};
      float sm[4];
#pragma unroll
      for (int i = 0; i < 4; i++) {
        const uint32_t xs[8] = {gx[i][0].x, gx[i][0].y, gx[i][0].z, gx[i][0].w, gx[i][1].x, gx[i][1].y, gx[i][1].z, gx[i][1].w};
        float s = 0.f;
#pragma unroll
        for (int j = 0; j < 8; j++) { const uint32_t pr = hmul2(xs[j], ws[j]); s += bf_lo(pr); s += bf_hi(pr); }
        sm[i] = s;
      }
      {
        const bool b0 = lane & 1, b1 = lane & 2;
        float u0 = b0 ? sm[1] : sm[0], v0 = b0 ? sm[0] : sm[1], u1 = b0 ? sm[3] : sm[2], v1 = b0 ? sm[2] : sm[3];
        u0 += __shfl_xor_sync(0xffffffffu, v0, 1); u1 += __shfl_xor_sync(0xffffffffu, v1, 1);
        float s = b1 ? u1 : u0; const float v = b1 ? u0 : u1;
        s += __shfl_xor_sync(0xffffffffu, v, 2);
#pragma unroll
        for (int o = 4; o < 32; o <<= 1) s += __shfl_xor_sync(0xffffffffu, s, o);
        s = bf_round(s);
        const float gv = 1.f / (1.f + expf(-s));
        const uint32_t w = (tag << 16) | (pack_bf16(gv, 0.f) & 0xffffu);
        if (lane < 4) asm volatile("st.relaxed.gpu.global.u32 [%0], %1;" ::"l"(&g_gate[grow + lane]), "r"(w) : "memory");
      }
    }
    STAMP(8);
    uint32_t gg[4];
    {
      uint2 gl[4];
#pragma unroll
      for (int i = 0; i < 4; i++) gl[i] = gate_ld((i ^ (int)rank ^ 1) * 128 + wtid);
#pragma unroll
      for (int i = 0; i < 4; i++) gg[i] = gate_fin(p, gl[i], (i ^ (int)rank ^ 1) * 128 + wtid, tag);
    }
    {
      uint32_t ua[4][4], ub[4][4], ya[4][4], yb[4][4], yo[4];
#pragma unroll
      for (int i = 0; i < 4; i++) {
        const int x = (i ^ (int)rank ^ 1) * 128 + wtid;
        skip_terms(ua[i], ub[i], sb, x, dA, dB);
        yo[i] = sb + CH_OFF + (x & 3) * 4 + ysw(x >> 2);
      }
      bar_sync(8, 640);
      STAMP(10);
#pragma unroll
      for (int i = 0; i < 4; i++) { ld4ch(ya[i], yo[i] + Y0_OFF); ld4ch(yb[i], yo[i] + Y0_OFF + 4096); }
      send_box(sb, 0, wtid, rank, mix(ya[0], yb[0], ua[0], ub[0], gg[0]));
      merge_box(sb, &tm_out, 0, wtid, rank, oc0, mix(ya[1], yb[1], ua[1], ub[1], gg[1]), 5);
      STAMP(12);
      mbar_wait(sb + B_Y2);
      STAMP(11);
#pragma unroll
      for (int i = 2; i < 4; i++) { ld4ch(ya[i - 2], yo[i] + Y2_OFF - 1024); ld4ch(yb[i - 2], yo[i] + Y2_OFF - 1024 + 3072); }
#pragma unroll
      for (int i = 2; i < 4; i++)
#pragma unroll
        for (int k = 0; k < 4; k++) { ya[i][k] = hadd2(ya[i][k], ya[i - 2][k]); yb[i][k] = hadd2(yb[i][k], yb[i - 2][k]); }
      send_box(sb, 1, wtid, rank, mix(ya[2], yb[2], ua[2], ub[2], gg[2]));
      merge_box(sb, &tm_out, 1, wtid, rank, oc0, mix(ya[3], yb[3], ua[3], ub[3], gg[3]), 5);
      STAMP(13);
    }
    if (wtid == 0) {
      if (atomicAdd(&g_ticket, 1u) == NCTA - 1) { g_ticket = 0; g_epoch = epoch + 1; }
      asm volatile("cp.async.bulk.wait_group.read 0;" ::: "memory");
    }
    STAMP(15);
    return;
  }
  asm volatile("barrier.cluster.arrive.relaxed.aligned;" ::: "memory");

  const int moff = d * NM + hf * 64 + lane * 2;
  const uint32_t q0 = *(const uint32_t*)((br ? p.B_lA : p.A_re) + moff), q1 = *(const uint32_t*)((br ? p.B_Aim : p.A_im) + moff);
  const uint32_t q2 = *(const uint32_t*)((br ? p.B_Cre : p.C_re) + moff), q3 = *(const uint32_t*)((br ? p.B_Cim : p.C_im) + moff);
  const uint32_t q4 = *(const uint32_t*)((br ? p.B_Cre : p.B_re) + moff), q5 = *(const uint32_t*)((br ? p.B_Cim : p.B_im) + moff);
  const uint2 ldt4 = *(const uint2*)((br ? p.B_ldt : p.A_ldt) + blockIdx.x * 4);
  unsigned int epoch;
  asm volatile("ld.relaxed.gpu.global.u32 %0, [%1];" : "=r"(epoch) : "l"(&g_epoch) : "memory");

  for (int i = wtid & 63; i < R_BR / 16; i += 64) sts128(cb + R_OFF + br * R_BR + i * 16, 0, 0, 0, 0);
  STAMP(1);

  float acc[5][4];
  float k2048 = 0.f;
  const uint32_t scr = cb + Y0_OFF + wq * SCR_BYTES;
  const uint32_t scr2 = sb + XIN_OFF + warp * 640;
  {
    const uint32_t ldt2 = (ch & 2) ? ldt4.y : ldt4.x;
    const float dt = bf_round(expf((ch & 1) ? bf_hi(ldt2) : bf_lo(ldt2)));
#pragma unroll
    for (int i = 0; i < 5; i++) acc[i][0] = acc[i][1] = acc[i][2] = acc[i][3] = 0.f;
    cf cc[2], zz1[2], zz128[2];
#pragma unroll
    for (int r = 0; r < 2; r++) {
      float v0 = r ? bf_hi(q0) : bf_lo(q0), v1 = r ? bf_hi(q1) : bf_lo(q1), v2 = r ? bf_hi(q2) : bf_lo(q2);
      float v3 = r ? bf_hi(q3) : bf_lo(q3), v4 = r ? bf_hi(q4) : bf_lo(q4), v5 = r ? bf_hi(q5) : bf_lo(q5);
      if (br == 0) { cc[r] = cmul(cf{v2, v3}, cf{dt * v4, dt * v5}); }
      else { v0 = -bf_round(expf(v0)); cc[r] = cf{2.f * dt * v2, 2.f * dt * v3}; }
      const float xl = (dt * v0) * 1.4426950408889634f, y = dt * v1;
      zz1[r] = cexp_p(xl, y, 1.f); zz128[r] = cexp_p(xl, y, 128.f);
    }
    STAMP(2);
    const uint32_t tb = scr + lane * 16;
    const uint32_t ta = scr + (lane >> 3) * 512 + (lane & 7) * 16;
    const uint32_t tc = ((lane & 8) ? scr2 : scr + 4096) + (lane >> 4) * 128 + (lane & 7) * 16;
    const uint32_t tm = scr2 + 512 + ((lane >> 3) & 1) * 64 + (lane >> 4) * 16;
#pragma unroll 1
    for (int r = 0; r < 2; r++) {
      const cf c = r ? cc[1] : cc[0], z1 = r ? zz1[1] : zz1[0], z128 = r ? zz128[1] : zz128[0];
      const cf z2 = csq(z1), z4 = csq(z2), z8 = csq(z4);
      const cf z16 = csq(z8), z24 = cmul(z16, z8), z32 = csq(z16), z40 = cmul(z32, z8), z48 = csq(z24), z56 = cmul(z32, z24), z64 = csq(z32);
      const cf z256 = csq(z128), z512 = csq(z256), z1024 = csq(z512), z2048 = csq(z1024);
      k2048 += fmaf(c.re, z2048.re, -c.im * z2048.im);
      __syncwarp();
      {
        uint32_t xr[4] = {pack_bf16(1.f, z8.re), pack_bf16(z16.re, z24.re), pack_bf16(z32.re, z40.re), pack_bf16(z48.re, z56.re)};
        uint32_t xi[4] = {pack_bf16(0.f, -z8.im), pack_bf16(-z16.im, -z24.im), pack_bf16(-z32.im, -z40.im), pack_bf16(-z48.im, -z56.im)};
        sts128(tb + 0 * 512, xr[0], xr[1], xr[2], xr[3]);
        sts128(tb + 2 * 512, xi[0], xi[1], xi[2], xi[3]);
        const uint32_t yr = pack_bf16(z64.re, z64.re), nyi = pack_bf16(z64.im, z64.im), yi = nyi ^ 0x80008000u;
        uint32_t o[4], q[4];
#pragma unroll
        for (int i = 0; i < 4; i++) CMUL2(o[i], q[i], xr[i], xi[i], yr, yi, nyi);
        sts128(tb + 1 * 512, o[0], o[1], o[2], o[3]);
        sts128(tb + 3 * 512, q[0], q[1], q[2], q[3]);
      }
      {
        const cf h1 = cmul(c, z128), h2 = cmul(c, z256), h3 = cmul(h1, z256), h4 = cmul(c, z512), h5 = cmul(h1, z512), h6 = cmul(h2, z512), h7 = cmul(h3, z512);
        const cf e1 = cmul(c, z1), e2 = cmul(c, z2), e3 = cmul(e1, z2), e129 = cmul(h1, z1), e130 = cmul(h1, z2), e131 = cmul(e129, z2);
        const cf e258 = cmul(h2, z2), e386 = cmul(h3, z2);
        const uint32_t pr0 = pack_bf16(c.re, e1.re), pr2 = pack_bf16(h1.re, e129.re), pi0 = pack_bf16(c.im, e1.im), pi2 = pack_bf16(h1.im, e129.im);
        sts128(tb + 4 * 512, pr0, pack_bf16(e2.re, e3.re), pr2, pack_bf16(e130.re, e131.re));
        sts128(tb + 5 * 512, pi0, pack_bf16(e2.im, e3.im), pi2, pack_bf16(e130.im, e131.im));
        uint32_t xr[4] = {pack_bf16(h2.re, e258.re), pack_bf16(h3.re, e386.re), pack_bf16(h4.re, h5.re), pack_bf16(h6.re, h7.re)};
        uint32_t xi[4] = {pack_bf16(h2.im, e258.im), pack_bf16(h3.im, e386.im), pack_bf16(h4.im, h5.im), pack_bf16(h6.im, h7.im)};
        sts128(tb + 6 * 512, xr[0], xr[1], xr[2], xr[3]);
        sts128(tb + 7 * 512, xi[0], xi[1], xi[2], xi[3]);
        xr[1] = __byte_perm(xr[0], xr[1], 0x5410); xi[1] = __byte_perm(xi[0], xi[1], 0x5410);
        xr[0] = __byte_perm(pr0, pr2, 0x5410); xi[0] = __byte_perm(pi0, pi2, 0x5410);
        const uint32_t yr = pack_bf16(z1024.re, z1024.re), yi = pack_bf16(z1024.im, z1024.im), nyi = yi ^ 0x80008000u;
        uint32_t o[4], q[4];
#pragma unroll
        for (int i = 0; i < 4; i++) CMUL2(o[i], q[i], xr[i], xi[i], yr, yi, nyi);
        sts128(tb + 8 * 512, o[0], o[1], o[2], o[3]);
        sts128(scr2 + lane * 16, q[0], q[1], q[2], q[3]);
        const uint32_t m4 = pack_bf16(z4.re, z4.im);
        sts16(scr2 + 512 + lane * 2, m4); sts16(scr2 + 576 + lane * 2, m4 >> 16);
      }
      __syncwarp();
#pragma unroll
      for (int kp = 0; kp < 2; kp++) {
        uint32_t rr[2], ri[2], yr[2], yi[2];
        ldsm4t(tc + kp * 256, rr[0], ri[0], rr[1], ri[1]);
        ldsm4(tm + kp * 32, yr[0], yi[0], yr[1], yi[1]);
#pragma unroll
        for (int k2 = 0; k2 < 2; k2++) {
          const int kk = kp * 2 + k2;
          uint32_t a0, a1, a2, a3, pr, pi, qr, qi, xr, xi;
          ldsm4t(ta + kk * 128, a0, a1, a2, a3);
          ldsm4t(ta + 2048 + kk * 128, pr, pi, qr, qi);
          const uint32_t nyi = yi[k2] ^ 0x80008000u;
          mma16816(acc[0], a0, a1, a2, a3, pr, pi);
          mma16816(acc[2], a0, a1, a2, a3, qr, qi);
          mma16816(acc[4], a0, a1, a2, a3, rr[k2], ri[k2]);
          CMUL2(xr, xi, pr, pi, yr[k2], yi[k2], nyi);
          mma16816(acc[1], a0, a1, a2, a3, xr, xi);
          CMUL2(xr, xi, qr, qi, yr[k2], yi[k2], nyi);
          mma16816(acc[3], a0, a1, a2, a3, xr, xi);
        }
      }
    }
#pragma unroll
    for (int o = 16; o; o >>= 1) k2048 += __shfl_xor_sync(0xffffffffu, k2048, o);
  }
  STAMP(3);
  __syncwarp();
  {
    const uint32_t xs = scr + lane * 16;
#define OTH(i, k) __float_as_uint(hf ? acc[i][k] : acc[i][2 + (k)])
    sts128(xs, OTH(0, 0), OTH(0, 1), OTH(1, 0), OTH(1, 1));
    sts128(xs + 512, OTH(2, 0), OTH(2, 1), OTH(3, 0), OTH(3, 1));
    sts128(xs + 1024, OTH(4, 0), OTH(4, 1), __float_as_uint(k2048), 0);
#undef OTH
  }

  bar_sync(1 + ch, 128);
  STAMP(4);
  {
    const uint32_t xo = cb + Y0_OFF + (wq ^ 1) * SCR_BYTES + lane * 16;
    const uint4 o0 = lds128(xo), o1 = lds128(xo + 512), o2 = lds128(xo + 1024);
    const uint32_t rb = cb + R_OFF + br * R_BR;
#define OWN(i, k) (hf ? acc[i][2 + (k)] : acc[i][k])
    const uint32_t vP = pack_bf16(OWN(0, 1) + __uint_as_float(o0.y), OWN(0, 0) + __uint_as_float(o0.x));
    const uint32_t vP4 = pack_bf16(OWN(1, 1) + __uint_as_float(o0.w), OWN(1, 0) + __uint_as_float(o0.z));
    const uint32_t vQ = pack_bf16(OWN(2, 1) + __uint_as_float(o1.y), OWN(2, 0) + __uint_as_float(o1.x));
    const uint32_t vQ4 = pack_bf16(OWN(3, 1) + __uint_as_float(o1.w), OWN(3, 0) + __uint_as_float(o1.z));
    const uint32_t vR = pack_bf16(OWN(4, 1) + __uint_as_float(o2.y), OWN(4, 0) + __uint_as_float(o2.x));
#undef OWN
    const int j = g + 8 * hf;
    {
      const int a = 2 * (t & 1) + 64 * (t & 2) + 8 * j;
      const uint32_t ad = rb + 2 * (RD_X0 - 1 - a);
      const uint32_t a1 = (t & 2) ? ad - 8 : ad, a2 = (t & 2) ? ad : ad - 8;
      const uint32_t w1 = (t & 2) ? vP4 : vP, w2 = (t & 2) ? vP : vP4;
      sts32(a1, w1); sts32(a2, w2);
      sts16(a1 + RD_CS + 2, w1); sts16(a1 + RD_CS + 4, w1 >> 16);
      sts16(a2 + RD_CS + 2, w2); sts16(a2 + RD_CS + 4, w2 >> 16);
    }
    if (t < 2) {
      const int b = 256 + 128 * t + 8 * j;
      const uint32_t ad = rb + 2 * (RD_X0 - 6 - b);
      const uint32_t v22 = __byte_perm(vQ4, 0, 0x3232), v00 = __byte_perm(vQ, 0, 0x3232);
      sts16(ad, vQ4);
      sts64(ad + 2, v22, __byte_perm(vQ4, vQ, 0x5432));
      sts32(ad + 10, v00);
      if (b != 256) { sts16(ad + 14, v00); sts128(ad + RD_CS + 2, vQ4, v22, vQ, v00); }
      else { sts64(ad + RD_CS + 2, vQ4, v22); sts32(ad + RD_CS + 10, vQ); sts16(ad + RD_CS + 14, v00); }
    } else {
      const uint32_t ao = rb + R_O2 + 2 * (159 - (32 * t + j)), ae = ao - (R_O2 - R_E2) + 2;
      sts16(ao, vQ4 >> 16); sts16(ao + RS_CS + 2, vQ4 >> 16); sts16(ao - 32, vQ4); sts16(ao - 32 + RS_CS + 2, vQ4);
      sts16(ae - 32, vQ); sts16(ae - 32 + RS_CS + 2, vQ);
      if (lane != 2 || hf) { sts16(ae, vQ >> 16); sts16(ae + RS_CS + 2, vQ >> 16); }
      else {
        const uint32_t vv = __byte_perm(vQ, 0, 0x3232), ad = rb + 2 * (RD_X0 - 514);
        sts16(ad, vv); sts32(ad + 2, vv); sts16(ad + 6, vv); sts64(ad + RD_CS + 2, vv, vv);
      }
    }
    {
      const uint32_t a = rb + ((g & 1) ? R_O3 : R_E3 + 2) + 2 * (159 - (64 + 16 * t + (j >> 1)));
      const bool p1024 = (lane == 0) && (hf == 0);
      const uint32_t a00 = p1024 ? rb + R_E2 + 2 * (159 - 127) : a;
      sts16(a00, vR >> 16); sts16(a00 + RS_CS + 2, vR >> 16);
      sts16(a - 16, vR); sts16(a - 16 + RS_CS + 2, vR);
      if (p1024) {
        sts32(sb + K1024_OFF + (ch * 2 + br) * 4, __byte_perm(vR, 0, 0x3232));
        const uint32_t kv = pack_bf16(k2048 + __uint_as_float(o2.z), 0.f);
        sts16(rb + R_E3 + 2 * (159 - 127), kv); sts16(rb + R_E3 + 2 * (159 - 127) + RS_CS + 2, kv);
      }
    }
  }
  STAMP(5);
  const uint32_t tag = (epoch + 1) & 0xffffu;
  asm volatile("barrier.cluster.wait.aligned;" ::: "memory");
  bar_sync(1 + ch, 128);
  mbar_wait(sb + B_U);
  STAMP(6);

  const uint32_t zz = lds32(cb + R_OFF);
  conv_dense(cb, zz);
  const uint2 dA = *(const uint2*)(p.A_D + blockIdx.x * 4), dB = *(const uint2*)(p.B_D + blockIdx.x * 4);
  const uint2 gl = gate_ld((4 + ch) * 128 + wtid);
  mbar_wait(sb + B_W);
  conv_far(sb, cb, zz);
  STAMP(10);
  __syncwarp();
  if (lane == 0) asm volatile("mbarrier.arrive.shared::cta.b64 _, [%0];" ::"r"(sb + B_Y3) : "memory");

  {
    const int x = (4 + ch) * 128 + wtid, c = x >> 2;
    const uint32_t g2 = gate_fin(p, gl, x, tag);
    const uint32_t yo = sb + CH_OFF + (x & 3) * 4 + ysw(c);
    uint32_t ua[4], ub[4], ya[4], yb[4], a2[4], b2[4], a3[4], b3[4], s2[4];
    skip_terms(ua, ub, sb, x, dA, dB);
    ld4ch(s2, sb + CH_OFF + (x & 3) * 4 + S2_OFF + ((c - 128) + ((c - 128) >> 3)) * 16);
    mbar_wait(sb + B_Y2);
    const uint4 k0 = lds128(sb + K1024_OFF), k1 = lds128(sb + K1024_OFF + 16);
    const uint32_t kk[8] = {k0.x, k0.y, k0.z, k0.w, k1.x, k1.y, k1.z, k1.w};
    ld4ch(ya, yo + Y0_OFF); ld4ch(yb, yo + Y0_OFF + 4096);
    ld4ch(a2, yo + Y2_OFF - 1024); ld4ch(b2, yo + Y2_OFF - 1024 + 3072);
#pragma unroll
    for (int k = 0; k < 4; k++) { a2[k] = hfma2(kk[2 * k], s2[k], a2[k]); b2[k] = hfma2(kk[2 * k + 1], s2[k], b2[k]); }
    STAMP(11);
    mbar_wait(sb + B_Y3);
    STAMP(12);
    ld4ch(a3, yo + Y3_OFF - 2048); ld4ch(b3, yo + Y3_OFF - 2048 + 2048);
#pragma unroll
    for (int k = 0; k < 4; k++) { ya[k] = hadd2(ya[k], hadd2(a2[k], a3[k])); yb[k] = hadd2(yb[k], hadd2(b2[k], b3[k])); }
    const uint4 r = mix(ya, yb, ua, ub, g2);
    if ((uint32_t)(ch & 1) != rank) send_box(sb, 2 + (ch >> 1), wtid, rank, r);
    else merge_box(sb, &tm_out, 2 + (ch >> 1), wtid, rank, oc0, r, 1 + ch);
  }
  STAMP(14);
  if (wtid == 0) asm volatile("cp.async.bulk.wait_group.read 0;" ::: "memory");
  STAMP(15); GT(1);
}

typedef CUresult (*EncodeFn)(CUtensorMap*, CUtensorMapDataType, cuuint32_t, void*, const cuuint64_t*, const cuuint64_t*,
                             const cuuint32_t*, const cuuint32_t*, CUtensorMapInterleave, CUtensorMapSwizzle,
                             CUtensorMapL2promotion, CUtensorMapFloatOOBfill);

}

extern "C" void kernel_launch(void* const* d_in, const int* in_sizes, int n_in, void* d_out, int out_size) {
  (void)in_sizes; (void)n_in; (void)out_size;
  typedef const __nv_bfloat16* bp;
  Params p;
  p.u = (bp)d_in[0]; p.A_re = (bp)d_in[1]; p.A_im = (bp)d_in[2]; p.B_re = (bp)d_in[3]; p.B_im = (bp)d_in[4];
  p.C_re = (bp)d_in[5]; p.C_im = (bp)d_in[6]; p.A_ldt = (bp)d_in[7]; p.A_D = (bp)d_in[8];
  p.B_lA = (bp)d_in[10]; p.B_Aim = (bp)d_in[11]; p.B_Cre = (bp)d_in[12]; p.B_Cim = (bp)d_in[13];
  p.B_ldt = (bp)d_in[14]; p.B_D = (bp)d_in[15]; p.gw = (bp)d_in[16];
  static EncodeFn enc = nullptr;
  if (!enc) {
    cudaDriverEntryPointQueryResult qr;
    cudaGetDriverEntryPoint("cuTensorMapEncodeTiled", (void**)&enc, cudaEnableDefault, &qr);
    cudaFuncSetAttribute(ssm_kernel, cudaFuncAttributeMaxDynamicSharedMemorySize, SMEM_BYTES);
  }
  CUtensorMap tm_in, tm_out;
  {
    cuuint64_t gd[5] = {512, 2, 4, 4, 64};
    cuuint64_t gs[4] = {1024, 8192, 2048, 32768};
    cuuint32_t bx[5] = {8, 2, 4, 4, 32};
    cuuint32_t es[5] = {1, 1, 1, 1, 1};
    enc(&tm_in, CU_TENSOR_MAP_DATA_TYPE_BFLOAT16, 5, d_in[0], gd, gs, bx, es, CU_TENSOR_MAP_INTERLEAVE_NONE,
        CU_TENSOR_MAP_SWIZZLE_NONE, CU_TENSOR_MAP_L2_PROMOTION_NONE, CU_TENSOR_MAP_FLOAT_OOB_FILL_NONE);
  }
  {
    cuuint64_t gd[3] = {512, 1024, 2};
    cuuint64_t gs[2] = {2048, 1024};
    cuuint32_t bx[3] = {8, 128, 2};
    cuuint32_t es[3] = {1, 1, 1};
    enc(&tm_out, CU_TENSOR_MAP_DATA_TYPE_BFLOAT16, 3, d_out, gd, gs, bx, es, CU_TENSOR_MAP_INTERLEAVE_NONE,
        CU_TENSOR_MAP_SWIZZLE_NONE, CU_TENSOR_MAP_L2_PROMOTION_NONE, CU_TENSOR_MAP_FLOAT_OOB_FILL_NONE);
  }
  ssm_kernel<<<NCTA, 640, SMEM_BYTES, cudaStreamPerThread>>>(p, tm_in, tm_out);
}
```

```cpp
#include <cuda_runtime.h>
#include <cuda.h>
#include <cuda_bf16.h>
#include <stdint.h>

namespace {
#define FIXA 0
#define FIXB 1
#define CPY(x) (x)
#define FCPY(x) __uint_as_float(opq(__float_as_uint(x), zz))
#define STAG 0

constexpr int L = 2048, D = 512, NM = 128;
constexpr int NCTA = 128;

constexpr int RAW_OFF = 0;
constexpr int XIN_OFF = 32768;
constexpr int BAR_OFF = XIN_OFF + 10240;
constexpr int CH_OFF = BAR_OFF + 128;
constexpr int U_CS = 1184;
constexpr int U_OFF = 0;
constexpr int R_OFF = 4736;
constexpr int RD_X0 = 565;
constexpr int RD_CS = 1216;
constexpr int RS_CS = 320;
constexpr int R_E2 = 2 * RD_CS, R_O2 = R_E2 + 2 * RS_CS, R_E3 = R_O2 + 2 * RS_CS, R_O3 = R_E3 + 2 * RS_CS;
constexpr int R_BR = R_O3 + 2 * RS_CS;
constexpr int W5_OFF = R_OFF + 2 * R_BR;
constexpr int W3_OFF = W5_OFF + 3456;
constexpr int W9_OFF = W3_OFF + 3456;
constexpr int W7_OFF = W9_OFF + 2304;
constexpr int S2_OFF = W7_OFF + 2304;
constexpr int Y0_OFF = S2_OFF + 2304;
constexpr int Y2_OFF = Y0_OFF + 8192, Y3_OFF = Y2_OFF + 6144;
constexpr int CH_BYTES = Y0_OFF + 18432 + 16;
constexpr int SCR_BYTES = 4608;
constexpr int SMEM_BYTES = CH_OFF + 4 * CH_BYTES;
static_assert(CH_BYTES % 128 == 16, "bank staggering of the channel blocks");
static_assert(SMEM_BYTES <= 232448, "smem");
constexpr int B_RAW = BAR_OFF, B_X = BAR_OFF + 8, B_U = BAR_OFF + 40, B_W = BAR_OFF + 48, B_Y2 = BAR_OFF + 56, B_Y3 = BAR_OFF + 96;
constexpr int K1024_OFF = BAR_OFF + 64;

__device__ unsigned int g_gate[L];
__device__ unsigned int g_epoch;
__device__ unsigned int g_ticket;

#define STAMP(k)
#define GT(k)

struct Params {
  const __nv_bfloat16 *u, *A_re, *A_im, *B_re, *B_im, *C_re, *C_im, *A_ldt, *A_D;
  const __nv_bfloat16 *B_lA, *B_Aim, *B_Cre, *B_Cim, *B_ldt, *B_D, *gw;
};

template <int N, int TB> __device__ __forceinline__ void wgmma_rs(float* d, uint32_t a0, uint32_t a1, uint32_t a2, uint32_t a3, uint64_t desc, int sc);
template <> __device__ __forceinline__ void wgmma_rs<64, 0>(float* d, uint32_t a0, uint32_t a1, uint32_t a2, uint32_t a3, uint64_t desc, int sc) {
  asm volatile("{\n.reg .pred p;\nsetp.ne.b32 p, %37, 0;\n"
    "wgmma.mma_async.sync.aligned.m64n64k16.f32.bf16.bf16 {%0,%1,%2,%3,%4,%5,%6,%7,%8,%9,%10,%11,%12,%13,%14,%15,%16,%17,%18,%19,%20,%21,%22,%23,%24,%25,%26,%27,%28,%29,%30,%31}, {%32,%33,%34,%35}, %36, p, 1, 1, 0;\n}"
    : "+f"(d[0]), "+f"(d[1]), "+f"(d[2]), "+f"(d[3]), "+f"(d[4]), "+f"(d[5]), "+f"(d[6]), "+f"(d[7]), "+f"(d[8]), "+f"(d[9]), "+f"(d[10]), "+f"(d[11]), "+f"(d[12]), "+f"(d[13]), "+f"(d[14]), "+f"(d[15]), "+f"(d[16]), "+f"(d[17]), "+f"(d[18]), "+f"(d[19]), "+f"(d[20]), "+f"(d[21]), "+f"(d[22]), "+f"(d[23]), "+f"(d[24]), "+f"(d[25]), "+f"(d[26]), "+f"(d[27]), "+f"(d[28]), "+f"(d[29]), "+f"(d[30]), "+f"(d[31]) : "r"(a0), "r"(a1), "r"(a2), "r"(a3), "l"(desc), "r"(sc));
}
template <> __device__ __forceinline__ void wgmma_rs<56, 0>(float* d, uint32_t a0, uint32_t a1, uint32_t a2, uint32_t a3, uint64_t desc, int sc) {
  asm volatile("{\n.reg .pred p;\nsetp.ne.b32 p, %33, 0;\n"
    "wgmma.mma_async.sync.aligned.m64n56k16.f32.bf16.bf16 {%0,%1,%2,%3,%4,%5,%6,%7,%8,%9,%10,%11,%12,%13,%14,%15,%16,%17,%18,%19,%20,%21,%22,%23,%24,%25,%26,%27}, {%28,%29,%30,%31}, %32, p, 1, 1, 0;\n}"
    : "+f"(d[0]), "+f"(d[1]), "+f"(d[2]), "+f"(d[3]), "+f"(d[4]), "+f"(d[5]), "+f"(d[6]), "+f"(d[7]), "+f"(d[8]), "+f"(d[9]), "+f"(d[10]), "+f"(d[11]), "+f"(d[12]), "+f"(d[13]), "+f"(d[14]), "+f"(d[15]), "+f"(d[16]), "+f"(d[17]), "+f"(d[18]), "+f"(d[19]), "+f"(d[20]), "+f"(d[21]), "+f"(d[22]), "+f"(d[23]), "+f"(d[24]), "+f"(d[25]), "+f"(d[26]), "+f"(d[27]) : "r"(a0), "r"(a1), "r"(a2), "r"(a3), "l"(desc), "r"(sc));
}
template <> __device__ __forceinline__ void wgmma_rs<48, 0>(float* d, uint32_t a0, uint32_t a1, uint32_t a2, uint32_t a3, uint64_t desc, int sc) {
  asm volatile("{\n.reg .pred p;\nsetp.ne.b32 p, %29, 0;\n"
    "wgmma.mma_async.sync.aligned.m64n48k16.f32.bf16.bf16 {%0,%1,%2,%3,%4,%5,%6,%7,%8,%9,%10,%11,%12,%13,%14,%15,%16,%17,%18,%19,%20,%21,%22,%23}, {%24,%25,%26,%27}, %28, p, 1, 1, 0;\n}"
    : "+f"(d[0]), "+f"(d[1]), "+f"(d[2]), "+f"(d[3]), "+f"(d[4]), "+f"(d[5]), "+f"(d[6]), "+f"(d[7]), "+f"(d[8]), "+f"(d[9]), "+f"(d[10]), "+f"(d[11]), "+f"(d[12]), "+f"(d[13]), "+f"(d[14]), "+f"(d[15]), "+f"(d[16]), "+f"(d[17]), "+f"(d[18]), "+f"(d[19]), "+f"(d[20]), "+f"(d[21]), "+f"(d[22]), "+f"(d[23]) : "r"(a0), "r"(a1), "r"(a2), "r"(a3), "l"(desc), "r"(sc));
}
template <> __device__ __forceinline__ void wgmma_rs<32, 0>(float* d, uint32_t a0, uint32_t a1, uint32_t a2, uint32_t a3, uint64_t desc, int sc) {
  asm volatile("{\n.reg .pred p;\nsetp.ne.b32 p, %21, 0;\n"
    "wgmma.mma_async.sync.aligned.m64n32k16.f32.bf16.bf16 {%0,%1,%2,%3,%4,%5,%6,%7,%8,%9,%10,%11,%12,%13,%14,%15}, {%16,%17,%18,%19}, %20, p, 1, 1, 0;\n}"
    : "+f"(d[0]), "+f"(d[1]), "+f"(d[2]), "+f"(d[3]), "+f"(d[4]), "+f"(d[5]), "+f"(d[6]), "+f"(d[7]), "+f"(d[8]), "+f"(d[9]), "+f"(d[10]), "+f"(d[11]), "+f"(d[12]), "+f"(d[13]), "+f"(d[14]), "+f"(d[15]) : "r"(a0), "r"(a1), "r"(a2), "r"(a3), "l"(desc), "r"(sc));
}
template <> __device__ __forceinline__ void wgmma_rs<48, 1>(float* d, uint32_t a0, uint32_t a1, uint32_t a2, uint32_t a3, uint64_t desc, int sc) {
  asm volatile("{\n.reg .pred p;\nsetp.ne.b32 p, %29, 0;\n"
    "wgmma.mma_async.sync.aligned.m64n48k16.f32.bf16.bf16 {%0,%1,%2,%3,%4,%5,%6,%7,%8,%9,%10,%11,%12,%13,%14,%15,%16,%17,%18,%19,%20,%21,%22,%23}, {%24,%25,%26,%27}, %28, p, 1, 1, 1;\n}"
    : "+f"(d[0]), "+f"(d[1]), "+f"(d[2]), "+f"(d[3]), "+f"(d[4]), "+f"(d[5]), "+f"(d[6]), "+f"(d[7]), "+f"(d[8]), "+f"(d[9]), "+f"(d[10]), "+f"(d[11]), "+f"(d[12]), "+f"(d[13]), "+f"(d[14]), "+f"(d[15]), "+f"(d[16]), "+f"(d[17]), "+f"(d[18]), "+f"(d[19]), "+f"(d[20]), "+f"(d[21]), "+f"(d[22]), "+f"(d[23]) : "r"(a0), "r"(a1), "r"(a2), "r"(a3), "l"(desc), "r"(sc));
}
template <> __device__ __forceinline__ void wgmma_rs<40, 1>(float* d, uint32_t a0, uint32_t a1, uint32_t a2, uint32_t a3, uint64_t desc, int sc) {
  asm volatile("{\n.reg .pred p;\nsetp.ne.b32 p, %25, 0;\n"
    "wgmma.mma_async.sync.aligned.m64n40k16.f32.bf16.bf16 {%0,%1,%2,%3,%4,%5,%6,%7,%8,%9,%10,%11,%12,%13,%14,%15,%16,%17,%18,%19}, {%20,%21,%22,%23}, %24, p, 1, 1, 1;\n}"
    : "+f"(d[0]), "+f"(d[1]), "+f"(d[2]), "+f"(d[3]), "+f"(d[4]), "+f"(d[5]), "+f"(d[6]), "+f"(d[7]), "+f"(d[8]), "+f"(d[9]), "+f"(d[10]), "+f"(d[11]), "+f"(d[12]), "+f"(d[13]), "+f"(d[14]), "+f"(d[15]), "+f"(d[16]), "+f"(d[17]), "+f"(d[18]), "+f"(d[19]) : "r"(a0), "r"(a1), "r"(a2), "r"(a3), "l"(desc), "r"(sc));
}
template <> __device__ __forceinline__ void wgmma_rs<32, 1>(float* d, uint32_t a0, uint32_t a1, uint32_t a2, uint32_t a3, uint64_t desc, int sc) {
  asm volatile("{\n.reg .pred p;\nsetp.ne.b32 p, %21, 0;\n"
    "wgmma.mma_async.sync.aligned.m64n32k16.f32.bf16.bf16 {%0,%1,%2,%3,%4,%5,%6,%7,%8,%9,%10,%11,%12,%13,%14,%15}, {%16,%17,%18,%19}, %20, p, 1, 1, 1;\n}"
    : "+f"(d[0]), "+f"(d[1]), "+f"(d[2]), "+f"(d[3]), "+f"(d[4]), "+f"(d[5]), "+f"(d[6]), "+f"(d[7]), "+f"(d[8]), "+f"(d[9]), "+f"(d[10]), "+f"(d[11]), "+f"(d[12]), "+f"(d[13]), "+f"(d[14]), "+f"(d[15]) : "r"(a0), "r"(a1), "r"(a2), "r"(a3), "l"(desc), "r"(sc));
}
template <> __device__ __forceinline__ void wgmma_rs<16, 1>(float* d, uint32_t a0, uint32_t a1, uint32_t a2, uint32_t a3, uint64_t desc, int sc) {
  asm volatile("{\n.reg .pred p;\nsetp.ne.b32 p, %13, 0;\n"
    "wgmma.mma_async.sync.aligned.m64n16k16.f32.bf16.bf16 {%0,%1,%2,%3,%4,%5,%6,%7}, {%8,%9,%10,%11}, %12, p, 1, 1, 1;\n}"
    : "+f"(d[0]), "+f"(d[1]), "+f"(d[2]), "+f"(d[3]), "+f"(d[4]), "+f"(d[5]), "+f"(d[6]), "+f"(d[7]) : "r"(a0), "r"(a1), "r"(a2), "r"(a3), "l"(desc), "r"(sc));
}

__device__ __forceinline__ uint32_t pack_bf16(float lo, float hi) {
  uint32_t r; asm("cvt.rn.bf16x2.f32 %0, %1, %2;" : "=r"(r) : "f"(hi), "f"(lo)); return r;
}
__device__ __forceinline__ float bf_lo(uint32_t v) { return __uint_as_float(v << 16); }
__device__ __forceinline__ float bf_hi(uint32_t v) { return __uint_as_float(v & 0xffff0000u); }
__device__ __forceinline__ float bf_round(float x) { return bf_lo(pack_bf16(x, 0.f)); }
__device__ __forceinline__ uint32_t hmul2(uint32_t a, uint32_t b) { uint32_t r; asm("mul.rn.bf16x2 %0, %1, %2;" : "=r"(r) : "r"(a), "r"(b)); return r; }
__device__ __forceinline__ uint32_t hadd2(uint32_t a, uint32_t b) { uint32_t r; asm("add.rn.bf16x2 %0, %1, %2;" : "=r"(r) : "r"(a), "r"(b)); return r; }
__device__ __forceinline__ uint32_t hsub2(uint32_t a, uint32_t b) { uint32_t r; asm("sub.rn.bf16x2 %0, %1, %2;" : "=r"(r) : "r"(a), "r"(b)); return r; }
__device__ __forceinline__ uint32_t hfma2(uint32_t a, uint32_t b, uint32_t c) { uint32_t r; asm("fma.rn.bf16x2 %0, %1, %2, %3;" : "=r"(r) : "r"(a), "r"(b), "r"(c)); return r; }

__device__ __forceinline__ void sts16(uint32_t a, uint32_t v) { asm volatile("st.shared.b16 [%0], %1;" ::"r"(a), "h"((unsigned short)v) : "memory"); }
__device__ __forceinline__ void sts32(uint32_t a, uint32_t v) { asm volatile("st.shared.b32 [%0], %1;" ::"r"(a), "r"(v) : "memory"); }
__device__ __forceinline__ void sts64(uint32_t a, uint32_t x, uint32_t y) { asm volatile("st.shared.v2.b32 [%0], {%1,%2};" ::"r"(a), "r"(x), "r"(y) : "memory"); }
__device__ __forceinline__ void sts128(uint32_t a, uint32_t x, uint32_t y, uint32_t z, uint32_t w) {
  asm volatile("st.shared.v4.b32 [%0], {%1,%2,%3,%4};" ::"r"(a), "r"(x), "r"(y), "r"(z), "r"(w) : "memory");
}
__device__ __forceinline__ uint32_t lds32(uint32_t a) { uint32_t v; asm volatile("ld.shared.b32 %0, [%1];" : "=r"(v) : "r"(a) : "memory"); return v; }
__device__ __forceinline__ uint2 lds64(uint32_t a) { uint2 v; asm volatile("ld.shared.v2.b32 {%0,%1}, [%2];" : "=r"(v.x), "=r"(v.y) : "r"(a) : "memory"); return v; }
__device__ __forceinline__ uint4 lds128(uint32_t a) {
  uint4 v; asm volatile("ld.shared.v4.b32 {%0,%1,%2,%3}, [%4];" : "=r"(v.x), "=r"(v.y), "=r"(v.z), "=r"(v.w) : "r"(a) : "memory"); return v;
}
__device__ __forceinline__ void ldsm4(uint32_t a, uint32_t& r0, uint32_t& r1, uint32_t& r2, uint32_t& r3) {
  asm volatile("ldmatrix.sync.aligned.m8n8.x4.shared.b16 {%0,%1,%2,%3}, [%4];" : "=r"(r0), "=r"(r1), "=r"(r2), "=r"(r3) : "r"(a) : "memory");
}
__device__ __forceinline__ void ldsm4t(uint32_t a, uint32_t& r0, uint32_t& r1, uint32_t& r2, uint32_t& r3) {
  asm volatile("ldmatrix.sync.aligned.m8n8.x4.trans.shared.b16 {%0,%1,%2,%3}, [%4];" : "=r"(r0), "=r"(r1), "=r"(r2), "=r"(r3) : "r"(a) : "memory");
}
__device__ __forceinline__ void stsm4(uint32_t a, uint32_t r0, uint32_t r1, uint32_t r2, uint32_t r3) {
  asm volatile("stmatrix.sync.aligned.m8n8.x4.shared.b16 [%0], {%1,%2,%3,%4};" ::"r"(a), "r"(r0), "r"(r1), "r"(r2), "r"(r3) : "memory");
}
__device__ __forceinline__ void stsm4t(uint32_t a, uint32_t r0, uint32_t r1, uint32_t r2, uint32_t r3) {
  asm volatile("stmatrix.sync.aligned.m8n8.x4.trans.shared.b16 [%0], {%1,%2,%3,%4};" ::"r"(a), "r"(r0), "r"(r1), "r"(r2), "r"(r3) : "memory");
}
__device__ __forceinline__ void mma16816(float* c, uint32_t a0, uint32_t a1, uint32_t a2, uint32_t a3, uint32_t b0, uint32_t b1) {
  asm("mma.sync.aligned.m16n8k16.row.col.f32.bf16.bf16.f32 {%0,%1,%2,%3}, {%4,%5,%6,%7}, {%8,%9}, {%0,%1,%2,%3};"
      : "+f"(c[0]), "+f"(c[1]), "+f"(c[2]), "+f"(c[3]) : "r"(a0), "r"(a1), "r"(a2), "r"(a3), "r"(b0), "r"(b1));
}
__device__ __forceinline__ void bar_sync(int id, int n) { asm volatile("bar.sync %0, %1;" ::"r"(id), "r"(n) : "memory"); }
__device__ __forceinline__ void bar_arrive(int id, int n) { asm volatile("bar.arrive %0, %1;" ::"r"(id), "r"(n) : "memory"); }
__device__ __forceinline__ void wg_fence() { asm volatile("wgmma.fence.sync.aligned;" ::: "memory"); }
__device__ __forceinline__ void wg_commit() { asm volatile("wgmma.commit_group.sync.aligned;" ::: "memory"); }
__device__ __forceinline__ void wg_wait0() { asm volatile("wgmma.wait_group.sync.aligned 0;" ::: "memory"); }
__device__ __forceinline__ void fence_async() { asm volatile("fence.proxy.async.shared::cta;" ::: "memory"); }
__device__ __forceinline__ uint32_t opq(uint32_t x, uint32_t z) { uint32_t r; asm volatile("xor.b32 %0, %1, %2;" : "=r"(r) : "r"(x), "r"(z)); return r; }
__device__ __forceinline__ uint64_t mkdesc(uint32_t addr, uint32_t lbo, uint32_t sbo) {
  return (uint64_t)((addr & 0x3FFFF) >> 4) | ((uint64_t)(lbo >> 4) << 16) | ((uint64_t)(sbo >> 4) << 32);
}
__device__ __forceinline__ uint32_t mapa(uint32_t a, uint32_t rank) {
  uint32_t r; asm("mapa.shared::cluster.u32 %0, %1, %2;" : "=r"(r) : "r"(a), "r"(rank)); return r;
}
__device__ __forceinline__ void mbar_init_expect(uint32_t bar, uint32_t bytes) {
  asm volatile("mbarrier.init.shared::cta.b64 [%0], 1;" ::"r"(bar) : "memory");
  asm volatile("mbarrier.arrive.expect_tx.shared::cta.b64 _, [%0], %1;" ::"r"(bar), "r"(bytes) : "memory");
}
__device__ __forceinline__ void mbar_wait(uint32_t bar) {
#pragma unroll 1
  for (int it = 0; it < (1 << 22); it++) {
    uint32_t ok;
    asm volatile("{\n.reg .pred p;\nmbarrier.try_wait.parity.acquire.cluster.shared::cta.b64 p, [%1], 0;\nselp.u32 %0, 1, 0, p;\n}"
                 : "=r"(ok) : "r"(bar) : "memory");
    if (ok) return;
  }
  __trap();
}
__device__ __forceinline__ void st_async4(uint32_t a, uint32_t bar, uint32_t x, uint32_t y, uint32_t z, uint32_t w) {
  asm volatile("st.async.weak.shared::cluster.mbarrier::complete_tx::bytes.v4.b32 [%0], {%2,%3,%4,%5}, [%1];"
               ::"r"(a), "r"(bar), "r"(x), "r"(y), "r"(z), "r"(w) : "memory");
}

struct cf { float re, im; };
__device__ __forceinline__ cf cmul(cf a, cf b) { return {fmaf(a.re, b.re, -a.im * b.im), fmaf(a.re, b.im, a.im * b.re)}; }
__device__ __forceinline__ cf csq(cf a) { return {fmaf(a.re, a.re, -a.im * a.im), (a.re + a.re) * a.im}; }
__device__ __forceinline__ cf cexp_p(float xl, float y, float p) {
  float mag; asm("ex2.approx.ftz.f32 %0, %1;" : "=f"(mag) : "f"(xl * p));
  const float th = y * p;
  const float k = rintf(th * 0.15915494309189535f);
  float r = fmaf(k, -6.2831854820251465f, th);
  r = fmaf(k, 1.7484555314695172e-07f, r);
  return {mag * __cosf(r), mag * __sinf(r)};
}
__device__ __forceinline__ uint32_t ysw(int c) { return (uint32_t)(c ^ ((c >> 3) & 3)) * 16u; }

#define CMUL2(OR, OI, xr, xi, yr, yi, nyi) do { OR = hfma2(xr, yr, hmul2(xi, nyi)); OI = hfma2(xr, yi, hmul2(xi, yr)); } while (0)

__device__ __forceinline__ uint32_t gate_slow(const __nv_bfloat16* u, const __nv_bfloat16* gw, int row) {
  float s = 0.f;
  const uint32_t* xr = (const uint32_t*)(u + (size_t)row * D);
  const uint32_t* wr = (const uint32_t*)gw;
#pragma unroll 1
  for (int j = 0; j < D / 2; j++) { const uint32_t pr = hmul2(xr[j], wr[j]); s += bf_lo(pr); s += bf_hi(pr); }
  s = bf_round(s);
  return pack_bf16(1.f / (1.f + expf(-s)), 0.f);
}

__device__ __forceinline__ uint2 gate_ld(int x) {
  uint2 gv;
  asm volatile("ld.relaxed.gpu.global.v2.u32 {%0,%1}, [%2];" : "=r"(gv.x), "=r"(gv.y) : "l"(g_gate + x * 2) : "memory");
  return gv;
}
__device__ __noinline__ uint32_t gate_poll(const __nv_bfloat16* u, const __nv_bfloat16* gw, int x, uint32_t tag) {
  uint2 gv;
#pragma unroll 1
  for (int spins = 0; spins < (1 << 16); spins++) {
    gv = gate_ld(x);
    if ((gv.x >> 16) == tag && (gv.y >> 16) == tag) return __byte_perm(gv.x, gv.y, 0x5410);
  }
  return __byte_perm(gate_slow(u, gw, x * 2), gate_slow(u, gw, x * 2 + 1), 0x5410);
}
__device__ __forceinline__ uint32_t gate_fin(const Params& p, uint2 gv, int x, uint32_t tag) {
  if ((gv.x >> 16) == tag && (gv.y >> 16) == tag) return __byte_perm(gv.x, gv.y, 0x5410);
  return gate_poll(p.u, p.gw, x, tag);
}

__device__ __forceinline__ void ld4ch(uint32_t* v, uint32_t addr) {
#pragma unroll
  for (int k = 0; k < 4; k++) v[k] = lds32(addr + k * CH_BYTES);
}
__device__ __forceinline__ void skip_terms(uint32_t* ua, uint32_t* ub, uint32_t sb, int x, uint2 dA, uint2 dB) {
  const int c = x >> 2;
  uint32_t uu[4];
  ld4ch(uu, sb + CH_OFF + (x & 3) * 4 + U_OFF + (c & 3) * U_CS + (63 - (c >> 2)) * 16);
#pragma unroll
  for (int k = 0; k < 4; k++) {
    ua[k] = hmul2(uu[k], __byte_perm((k & 2) ? dA.y : dA.x, 0, (k & 1) ? 0x3232 : 0x1010));
    ub[k] = hmul2(uu[k], __byte_perm((k & 2) ? dB.y : dB.x, 0, (k & 1) ? 0x3232 : 0x1010));
  }
}
__device__ __forceinline__ uint4 mix(const uint32_t* a, const uint32_t* b, const uint32_t* ua, const uint32_t* ub, uint32_t g2) {
  const uint32_t h2 = hsub2(0x3f803f80u, g2);
  uint32_t o[4];
#pragma unroll
  for (int k = 0; k < 4; k++) o[k] = hadd2(hmul2(g2, hadd2(a[k], ua[k])), hmul2(h2, hadd2(b[k], ub[k])));
  return make_uint4(__byte_perm(o[0], o[1], 0x5410), __byte_perm(o[2], o[3], 0x5410), __byte_perm(o[0], o[1], 0x7632), __byte_perm(o[2], o[3], 0x7632));
}
__device__ __forceinline__ void send_box(uint32_t sb, int slot, int wtid, uint32_t rank, uint4 r) {
  st_async4(mapa(sb + XIN_OFF + slot * 2048 + wtid * 16, rank ^ 1), mapa(sb + B_X + slot * 8, rank ^ 1), r.x, r.y, r.z, r.w);
}
__device__ __forceinline__ void merge_box(uint32_t sb, const CUtensorMap* tm_out, int slot, int wtid, uint32_t rank, int oc0, uint4 r, int barid) {
  const uint32_t st = sb + RAW_OFF + slot * 4096 + wtid * 16;
  sts64(st + rank * 8, r.x, r.y); sts64(st + 2048 + rank * 8, r.z, r.w);
  mbar_wait(sb + B_X + slot * 8);
  const uint4 q = lds128(sb + XIN_OFF + slot * 2048 + wtid * 16);
  sts64(st + (rank ^ 1) * 8, q.x, q.y); sts64(st + 2048 + (rank ^ 1) * 8, q.z, q.w);
  fence_async();
  bar_sync(barid, 128);
  if (wtid == 0) {
    asm volatile("cp.async.bulk.tensor.3d.global.shared::cta.bulk_group [%0, {%2, %3, %4}], [%1];"
                 ::"l"(tm_out), "r"(sb + RAW_OFF + slot * 4096), "r"(oc0), "r"((2 * slot + (int)rank) * 128), "r"(0) : "memory");
    asm volatile("cp.async.bulk.commit_group;" ::: "memory");
  }
}

__device__ __forceinline__ uint32_t band2(int e, int lo, int hi) {
  return ((uint32_t)(e - lo) <= (uint32_t)(hi - lo) ? 0x3f80u : 0u) | ((uint32_t)(e - 1 - lo) <= (uint32_t)(hi - lo) ? 0x3f800000u : 0u);
}

__device__ __forceinline__ void conv_dense(uint32_t cb, uint32_t zz) {
  const int lane = threadIdx.x & 31, wq = (threadIdx.x >> 5) & 3, br = wq >> 1, hf = wq & 1, g = lane >> 2, t = lane & 3;
  const uint32_t rb = cb + R_OFF + br * R_BR;
  const int eo = 16 * hf + g - 2 * t;
  float dacc[32];
  {
      {
        const int x0 = RD_X0 - (eo + 536);
        const uint32_t fa = rb + ((g & 1) ? 2 * x0 : RD_CS + 2 * x0 + 2);
        const uint64_t ub = mkdesc(cb + U_OFF, U_CS, 128);
        uint32_t A[2][4][4];
        float e56[28], e48[24];
        auto loadA = [&](int j) {
#pragma unroll
          for (int k = 0; k < 4; k++) {
            const int s = 34 - 4 * j - k;
            if (s >= 0) {
              if (k == 0) A[j & 1][0][2] = lds32(fa + (2 * s + 2) * 16);
              A[j & 1][k][0] = lds32(fa + (2 * s + 1) * 16);
              A[j & 1][k][1] = lds32(fa + (2 * s) * 16);
            }
          }
#pragma unroll
          for (int k = 0; k < 4; k++) {
            if (34 - 4 * j - k >= 0) {
              A[j & 1][k][3] = CPY(A[j & 1][k][0]);
              if (k) A[j & 1][k][2] = CPY(A[j & 1][k - 1][1]);
            }
          }
        };
        loadA(0);
#pragma unroll
        for (int j = 0; j < 9; j++) {
          if (j == 4) {
#pragma unroll
            for (int i = 0; i < 28; i++) e56[i] = FCPY(dacc[i]);
          }
          if (j == 8) {
#pragma unroll
            for (int i = 0; i < 24; i++) e48[i] = FCPY(e56[i]);
          }
          wg_fence();
#pragma unroll
          for (int k = 0; k < 4; k++) {
            const int s = 34 - 4 * j - k;
            if (s >= 0) {
              const int o = 2 * s - 66 + 128;
              const int cc = o & 3, rs = (o >> 2) - 32;
              const int n0 = ((-rs) >> 3) * 8;
              const uint64_t desc = ub + (uint64_t)((cc * U_CS - rs * 16) >> 4);
              const uint32_t* a = A[j & 1][k];
              if (n0 == 0) wgmma_rs<64, 0>(dacc, a[0], a[1], a[2], a[3], desc, s != 34);
              else if (n0 == 8) wgmma_rs<56, 0>(FIXB ? e56 : dacc, a[0], a[1], a[2], a[3], desc, 1);
              else wgmma_rs<48, 0>(FIXB ? e48 : dacc, a[0], a[1], a[2], a[3], desc, 1);
            }
          }
          wg_commit();
          if (j < 8) loadA(j + 1);
          wg_wait0();
        }
#pragma unroll
        for (int i = 0; i < 28; i++) dacc[i] = i < 24 ? e48[i] : e56[i];
      }
      const uint32_t yb = cb + Y0_OFF + br * 4096;
#pragma unroll
      for (int i = 0; i < 8; i += 2) {
        const int mi = lane >> 3;
        const int cidx = 4 * (63 - 8 * (i + (mi >> 1)) - (lane & 7)) + 2 * hf + (mi & 1);
        stsm4t(yb + ysw(cidx), pack_bf16(dacc[4 * i], dacc[4 * i + 1]), pack_bf16(dacc[4 * i + 2], dacc[4 * i + 3]),
               pack_bf16(dacc[4 * i + 4], dacc[4 * i + 5]), pack_bf16(dacc[4 * i + 6], dacc[4 * i + 7]));
      }
      bar_arrive(8, 640);
      STAMP(8);
  }
}

__device__ __forceinline__ void conv_far(uint32_t sb, uint32_t cb, uint32_t zz) {
  const int lane = threadIdx.x & 31, wq = (threadIdx.x >> 5) & 3, br = wq >> 1, hf = wq & 1, g = lane >> 2, t = lane & 3;
  const uint32_t rb = cb + R_OFF + br * R_BR;
  const int eo = 16 * hf + g - 2 * t;
  float dacc[24], e40[20], e32[16], h32[16], h16[8];
  const int x1 = 159 - (eo + 136);
  const uint32_t fs = rb + ((g & 1) ? 2 * x1 : RS_CS + 2 * x1 + 2);
  {
    uint32_t A[2][4][4];
    auto loadA = [&](int buf, uint32_t oe, uint32_t oo, int i0) {
#pragma unroll
      for (int a = 0; a < 2; a++) {
        const uint32_t base = fs + (a ? oo : oe) + i0 * 16;
        uint32_t* k0 = A[buf][2 * a];
        uint32_t* k1 = A[buf][2 * a + 1];
        k0[1] = lds32(base); k0[0] = lds32(base + 16); k0[2] = lds32(base + 32); k1[0] = lds32(base + 48); k1[2] = lds32(base + 64);
      }
#pragma unroll
      for (int a = 0; a < 2; a++) {
        uint32_t* k0 = A[buf][2 * a];
        uint32_t* k1 = A[buf][2 * a + 1];
        k0[3] = CPY(k0[0]); k1[1] = CPY(k0[2]); k1[3] = CPY(k1[0]);
      }
    };
    const uint64_t d5 = mkdesc(cb + W5_OFF, 144, 576), d3 = mkdesc(cb + W3_OFF, 144, 576);
    loadA(0, R_E2, R_O2, 8);
#pragma unroll
    for (int m = 2; m <= 4; m++) {
      if (m == 3) {
#pragma unroll
        for (int i = 0; i < 20; i++) e40[i] = FCPY(dacc[i]);
      }
      if (m == 4) {
#pragma unroll
        for (int i = 0; i < 16; i++) e32[i] = FCPY(e40[i]);
      }
      wg_fence();
#pragma unroll
      for (int k = 0; k < 4; k++) {
        const uint32_t* a = A[m & 1][k];
        const uint64_t desc = ((k >> 1) ? d3 : d5) + (k & 1) * 18 + (m - 2) * 36;
        if (m == 2) wgmma_rs<48, 1>(dacc, a[0], a[1], a[2], a[3], desc, k);
        else if (m == 3) wgmma_rs<40, 1>(e40, a[0], a[1], a[2], a[3], desc, 1);
        else wgmma_rs<32, 1>(e32, a[0], a[1], a[2], a[3], desc, 1);
      }
      wg_commit();
      if (m < 4) loadA((m + 1) & 1, R_E2, R_O2, 4 * (3 - m));
      else loadA(1, R_E3, R_O3, 8);
      wg_wait0();
    }
#pragma unroll
    for (int i = 0; i < 20; i++) dacc[i] = i < 16 ? e32[i] : e40[i];
    {
      const uint32_t yb = cb + Y2_OFF + br * 3072;
#pragma unroll
      for (int i = 0; i < 6; i += 2) {
        const int mi = lane >> 3;
        const int cidx = 32 * (5 - i - (mi >> 1)) + 16 * hf + 8 * (mi & 1) + (lane & 7);
        stsm4(yb + ysw(cidx), pack_bf16(dacc[4 * i], dacc[4 * i + 1]), pack_bf16(dacc[4 * i + 2], dacc[4 * i + 3]),
              pack_bf16(dacc[4 * i + 4], dacc[4 * i + 5]), pack_bf16(dacc[4 * i + 6], dacc[4 * i + 7]));
      }
    }
    __syncwarp();
    if (lane == 0) asm volatile("mbarrier.arrive.shared::cta.b64 _, [%0];" ::"r"(sb + B_Y2) : "memory");
    STAMP(9);
    const uint64_t d9 = mkdesc(cb + W9_OFF, 144, 576), d7 = mkdesc(cb + W7_OFF, 144, 576);
#pragma unroll
    for (int m = 2; m <= 3; m++) {
      if (m == 3) {
#pragma unroll
        for (int i = 0; i < 8; i++) h16[i] = FCPY(h32[i]);
      }
      wg_fence();
#pragma unroll
      for (int k = 0; k < 4; k++) {
        const uint32_t* a = A[(m + 1) & 1][k];
        const uint64_t desc = ((k >> 1) ? d7 : d9) + (k & 1) * 18 + (m - 2) * 72;
        if (m == 2) wgmma_rs<32, 1>(h32, a[0], a[1], a[2], a[3], desc, k);
        else wgmma_rs<16, 1>(h16, a[0], a[1], a[2], a[3], desc, 1);
      }
      wg_commit();
      if (m == 2) loadA(0, R_E3, R_O3, 4);
      wg_wait0();
    }
#pragma unroll
    for (int i = 0; i < 16; i++) dacc[i] = i < 8 ? h16[i] : h32[i];
    const uint32_t yb = cb + Y3_OFF + br * 2048;
#pragma unroll
    for (int i = 0; i < 4; i += 2) {
      const int mi = lane >> 3;
      const int cidx = 64 * (1 - (i >> 1)) + 2 * (16 * hf + 8 * (mi & 1) + (lane & 7)) + (mi >> 1);
      stsm4(yb + ysw(cidx), pack_bf16(dacc[4 * i], dacc[4 * i + 1]), pack_bf16(dacc[4 * i + 2], dacc[4 * i + 3]),
            pack_bf16(dacc[4 * i + 4], dacc[4 * i + 5]), pack_bf16(dacc[4 * i + 6], dacc[4 * i + 7]));
    }
  }
}

__global__ void __cluster_dims__(2, 1, 1) __launch_bounds__(640, 1)
ssm_kernel(const Params p, const __grid_constant__ CUtensorMap tm_in, const __grid_constant__ CUtensorMap tm_out) {
  extern __shared__ __align__(1024) unsigned char smem_raw[];
  const uint32_t sb = (uint32_t)__cvta_generic_to_shared(smem_raw);
  const int tid = threadIdx.x, lane = tid & 31;
  const int warp = __shfl_sync(0xffffffffu, tid >> 5, 0);
  const int ch = warp >> 2, wq = warp & 3, br = wq >> 1, hf = wq & 1;
  const int g = lane >> 2, t = lane & 3;
  const int d = blockIdx.x * 4 + ch;
  const uint32_t rank = blockIdx.x & 1;
  const uint32_t cb = sb + CH_OFF + ch * CH_BYTES;
  const int wtid = tid & 127;
  const int oc0 = (int)(blockIdx.x >> 1) * 8;
  STAMP(0); GT(0);

  if (warp >= 16) {
    if (wtid == 0) {
      mbar_init_expect(sb + B_RAW, 32768);
#pragma unroll
      for (int i = 0; i < 4; i++) mbar_init_expect(sb + B_X + 8 * i, 2048);
      asm volatile("mbarrier.init.shared::cta.b64 [%0], 128;" ::"r"(sb + B_U) : "memory");
      asm volatile("mbarrier.init.shared::cta.b64 [%0], 128;" ::"r"(sb + B_W) : "memory");
      asm volatile("mbarrier.init.shared::cta.b64 [%0], 16;" ::"r"(sb + B_Y2) : "memory");
      asm volatile("mbarrier.init.shared::cta.b64 [%0], 16;" ::"r"(sb + B_Y3) : "memory");
      asm volatile("fence.mbarrier_init.release.cluster;" ::: "memory");
      asm volatile("fence.proxy.async.shared::cta;" ::: "memory");
    }
    __syncwarp();
    asm volatile("barrier.cluster.arrive.relaxed.aligned;" ::: "memory");
    unsigned int epoch;
    asm volatile("ld.relaxed.gpu.global.u32 %0, [%1];" : "=r"(epoch) : "l"(&g_epoch) : "memory");
    const uint2 dA = *(const uint2*)(p.A_D + blockIdx.x * 4), dB = *(const uint2*)(p.B_D + blockIdx.x * 4);
    const uint4 gw0 = *(const uint4*)(p.gw + lane * 8), gw1 = *(const uint4*)(p.gw + 256 + lane * 8);
    asm volatile("barrier.cluster.wait.aligned;" ::: "memory");
    if (wtid == 0) {
      asm volatile("cp.async.bulk.tensor.5d.shared::cluster.global.mbarrier::complete_tx::bytes.multicast::cluster [%0], [%1, {%3, %4, %4, %4, %5}], [%2], %6;"
                   ::"r"(sb + RAW_OFF + rank * 16384), "l"(&tm_in), "r"(sb + B_RAW), "r"(oc0), "r"(0), "r"((int)rank * 32), "h"((unsigned short)3) : "memory");
    }
    sts128(sb + CH_OFF + wq * CH_BYTES + U_OFF + (lane >> 3) * U_CS + (64 + (lane & 7)) * 16, 0, 0, 0, 0);
    uint32_t BA[3][4];
    {
      const int l1 = br ? 3 : 6, h1 = br ? 5 : 10;
#pragma unroll
      for (int i = 0; i < 3; i++) {
        const int e = 16 * hf + g - 2 * t + 16 - 16 * i;
        BA[i][0] = band2(e, l1, h1); BA[i][1] = band2(e + 8, l1, h1); BA[i][2] = band2(e - 8, l1, h1); BA[i][3] = BA[i][0];
      }
    }
    STAMP(3);
    mbar_wait(sb + B_RAW);
    STAMP(4);
    {
      const uint32_t dst = sb + CH_OFF + (g & 3) * CH_BYTES + U_OFF + t * U_CS + (63 - wq * 16) * 16;
#pragma unroll
      for (int h = 0; h < 2; h++) {
        uint32_t r[8][4];
#pragma unroll
        for (int i = 0; i < 8; i++) ldsm4t(sb + RAW_OFF + (wq * 16 + h * 8 + i) * 512 + lane * 16, r[i][0], r[i][1], r[i][2], r[i][3]);
        if ((uint32_t)(g >> 2) == rank) {
#pragma unroll
          for (int i = 0; i < 8; i++) sts128(dst - (h * 8 + i) * 16, r[i][0], r[i][1], r[i][2], r[i][3]);
        }
      }
    }
    fence_async();
    asm volatile("mbarrier.arrive.shared::cta.b64 _, [%0];" ::"r"(sb + B_U) : "memory");
    bar_sync(5, 128);
    STAMP(5);
    {
      const int mrow = lane & 7, mi = lane >> 3;
      const int eo = 16 * hf + g - 2 * t;
      const uint64_t ub0 = mkdesc(sb + CH_OFF + U_OFF, U_CS, 128);
      {
        float w[2][24];
#pragma unroll
        for (int i = 0; i < 24; i++) { w[0][i] = 0.f; w[1][i] = 0.f; }
        uint32_t wa[3];
#pragma unroll
        for (int i = 0; i < 3; i++) {
          const int c = 4 * (47 - 8 * (2 * i + (mi >> 1)) - mrow) + 2 * hf + (mi & 1);
          wa[i] = sb + CH_OFF + (br ? W3_OFF : W5_OFF) + (5 - (c >> 5)) * 576 + ((c & 31) >> 3) * 144 + (c & 7) * 16;
        }
#pragma unroll 1
        for (int kp = 0; kp < 2; kp++) {
          wg_fence();
#pragma unroll
          for (int k = 0; k < 2; k++)
#pragma unroll
            for (int i = 0; i < 3; i++)
              wgmma_rs<48, 0>(w[k], BA[i][0], BA[i][1], BA[i][2], BA[i][3],
                              ub0 + (uint64_t)(((2 * kp + k) * CH_BYTES + ((2 * i + 2) & 3) * U_CS + (16 + (i == 0)) * 16) >> 4), i);
          wg_commit();
          wg_wait0();
#pragma unroll
          for (int k = 0; k < 2; k++)
#pragma unroll
            for (int i = 0; i < 3; i++)
              stsm4t(wa[i] + (2 * kp + k) * CH_BYTES, pack_bf16(w[k][8 * i], w[k][8 * i + 1]), pack_bf16(w[k][8 * i + 2], w[k][8 * i + 3]),
                     pack_bf16(w[k][8 * i + 4], w[k][8 * i + 5]), pack_bf16(w[k][8 * i + 6], w[k][8 * i + 7]));
        }
      }
      {
        uint32_t BB[4][4], BC[3][4];
        const int l2 = br ? 5 : 12, h2 = br ? 11 : 20;
#pragma unroll
        for (int i = 0; i < 4; i++) {
          const int e = eo + 32 - 16 * i;
          BB[i][0] = band2(e, l2, h2); BB[i][1] = band2(e + 8, l2, h2); BB[i][2] = band2(e - 8, l2, h2); BB[i][3] = BB[i][0];
          if (i) { BC[i - 1][0] = band2(e, 3, 4); BC[i - 1][1] = band2(e + 8, 3, 4); BC[i - 1][2] = band2(e - 8, 3, 4); BC[i - 1][3] = BC[i - 1][0]; }
        }
        float w2[16], w3[16];
#pragma unroll
        for (int i = 0; i < 16; i++) { w2[i] = 0.f; w3[i] = 0.f; }
        uint32_t wa[2], sa[2];
#pragma unroll
        for (int i = 0; i < 2; i++) {
          const int c = 4 * (31 - 8 * (2 * i + (mi >> 1)) - mrow) + 2 * hf + (mi & 1), pp = c >> 1;
          wa[i] = sb + CH_OFF + (br ? W7_OFF : W9_OFF) + (1 - (pp >> 5)) * 1152 + (c & 1) * 576 + ((pp & 31) >> 3) * 144 + (pp & 7) * 16;
          sa[i] = sb + CH_OFF + S2_OFF + (c + (c >> 3)) * 16;
        }
#pragma unroll 1
        for (int k = 0; k < 4; k++) {
          wg_fence();
#pragma unroll
          for (int i = 0; i < 4; i++)
            wgmma_rs<32, 0>(w2, BB[i][0], BB[i][1], BB[i][2], BB[i][3],
                            ub0 + (uint64_t)((k * CH_BYTES + ((2 * i) & 3) * U_CS + (32 + (i < 2)) * 16) >> 4), i);
#pragma unroll
          for (int i = 0; i < 3; i++)
            wgmma_rs<32, 0>(w3, BC[i][0], BC[i][1], BC[i][2], BC[i][3],
                            ub0 + (uint64_t)((k * CH_BYTES + ((2 * i + 2) & 3) * U_CS + (32 + (i == 0)) * 16) >> 4), i);
          wg_commit();
          wg_wait0();
#pragma unroll
          for (int i = 0; i < 2; i++) {
            stsm4t(wa[i] + k * CH_BYTES, pack_bf16(w2[8 * i], w2[8 * i + 1]), pack_bf16(w2[8 * i + 2], w2[8 * i + 3]),
                   pack_bf16(w2[8 * i + 4], w2[8 * i + 5]), pack_bf16(w2[8 * i + 6], w2[8 * i + 7]));
            if (br == 0)
              stsm4t(sa[i] + k * CH_BYTES, pack_bf16(w3[8 * i], w3[8 * i + 1]), pack_bf16(w3[8 * i + 2], w3[8 * i + 3]),
                     pack_bf16(w3[8 * i + 4], w3[8 * i + 5]), pack_bf16(w3[8 * i + 6], w3[8 * i + 7]));
          }
        }
      }
    }
    fence_async();
    asm volatile("mbarrier.arrive.shared::cta.b64 _, [%0];" ::"r"(sb + B_W) : "memory");
    STAMP(7);
    const uint32_t tag = (epoch + 1) & 0xffffu;
    {
      const int grow = blockIdx.x * 16 + wq * 4;
      uint4 gx[4][2];
#pragma unroll
      for (int i = 0; i < 4; i++) {
        gx[i][0] = *(const uint4*)(p.u + (size_t)(grow + i) * D + lane * 8);
        gx[i][1] = *(const uint4*)(p.u + (size_t)(grow + i) * D + 256 + lane * 8);
      }
      const uint32_t ws[8] = {gw0.x, gw0.y, gw0.z, gw0.w, gw1.x, gw1.y, gw1.z, gw1.w};
      float sm[4];
#pragma unroll
      for (int i = 0; i < 4; i++) {
        const uint32_t xs[8] = {gx[i][0].x, gx[i][0].y, gx[i][0].z, gx[i][0].w, gx[i][1].x, gx[i][1].y, gx[i][1].z, gx[i][1].w};
        float s = 0.f;
#pragma unroll
        for (int j = 0; j < 8; j++) { const uint32_t pr = hmul2(xs[j], ws[j]); s += bf_lo(pr); s += bf_hi(pr); }
        sm[i] = s;
      }
      {
        const bool b0 = lane & 1, b1 = lane & 2;
        float u0 = b0 ? sm[1] : sm[0], v0 = b0 ? sm[0] : sm[1], u1 = b0 ? sm[3] : sm[2], v1 = b0 ? sm[2] : sm[3];
        u0 += __shfl_xor_sync(0xffffffffu, v0, 1); u1 += __shfl_xor_sync(0xffffffffu, v1, 1);
        float s = b1 ? u1 : u0; const float v = b1 ? u0 : u1;
        s += __shfl_xor_sync(0xffffffffu, v, 2);
#pragma unroll
        for (int o = 4; o < 32; o <<= 1) s += __shfl_xor_sync(0xffffffffu, s, o);
        s = bf_round(s);
        const float gv = 1.f / (1.f + expf(-s));
        const uint32_t w = (tag << 16) | (pack_bf16(gv, 0.f) & 0xffffu);
        if (lane < 4) asm volatile("st.relaxed.gpu.global.u32 [%0], %1;" ::"l"(&g_gate[grow + lane]), "r"(w) : "memory");
      }
    }
    STAMP(8);
    uint32_t gg[4];
    {
      uint2 gl[4];
#pragma unroll
      for (int i = 0; i < 4; i++) gl[i] = gate_ld((i ^ (int)rank ^ 1) * 128 + wtid);
#pragma unroll
      for (int i = 0; i < 4; i++) gg[i] = gate_fin(p, gl[i], (i ^ (int)rank ^ 1) * 128 + wtid, tag);
    }
    {
      uint32_t ua[4][4], ub[4][4], ya[4][4], yb[4][4], yo[4];
#pragma unroll
      for (int i = 0; i < 4; i++) {
        const int x = (i ^ (int)rank ^ 1) * 128 + wtid;
        skip_terms(ua[i], ub[i], sb, x, dA, dB);
        yo[i] = sb + CH_OFF + (x & 3) * 4 + ysw(x >> 2);
      }
      bar_sync(8, 640);
      STAMP(10);
#pragma unroll
      for (int i = 0; i < 4; i++) { ld4ch(ya[i], yo[i] + Y0_OFF); ld4ch(yb[i], yo[i] + Y0_OFF + 4096); }
      send_box(sb, 0, wtid, rank, mix(ya[0], yb[0], ua[0], ub[0], gg[0]));
      merge_box(sb, &tm_out, 0, wtid, rank, oc0, mix(ya[1], yb[1], ua[1], ub[1], gg[1]), 5);
      STAMP(12);
      mbar_wait(sb + B_Y2);
      STAMP(11);
#pragma unroll
      for (int i = 2; i < 4; i++) { ld4ch(ya[i - 2], yo[i] + Y2_OFF - 1024); ld4ch(yb[i - 2], yo[i] + Y2_OFF - 1024 + 3072); }
#pragma unroll
      for (int i = 2; i < 4; i++)
#pragma unroll
        for (int k = 0; k < 4; k++) { ya[i][k] = hadd2(ya[i][k], ya[i - 2][k]); yb[i][k] = hadd2(yb[i][k], yb[i - 2][k]); }
      send_box(sb, 1, wtid, rank, mix(ya[2], yb[2], ua[2], ub[2], gg[2]));
      merge_box(sb, &tm_out, 1, wtid, rank, oc0, mix(ya[3], yb[3], ua[3], ub[3], gg[3]), 5);
      STAMP(13);
    }
    if (wtid == 0) {
      if (atomicAdd(&g_ticket, 1u) == NCTA - 1) { g_ticket = 0; g_epoch = epoch + 1; }
      asm volatile("cp.async.bulk.wait_group.read 0;" ::: "memory");
    }
    STAMP(15);
    return;
  }
  asm volatile("barrier.cluster.arrive.relaxed.aligned;" ::: "memory");

  const int moff = d * NM + hf * 64 + lane * 2;
  const uint32_t q0 = *(const uint32_t*)((br ? p.B_lA : p.A_re) + moff), q1 = *(const uint32_t*)((br ? p.B_Aim : p.A_im) + moff);
  const uint32_t q2 = *(const uint32_t*)((br ? p.B_Cre : p.C_re) + moff), q3 = *(const uint32_t*)((br ? p.B_Cim : p.C_im) + moff);
  const uint32_t q4 = *(const uint32_t*)((br ? p.B_Cre : p.B_re) + moff), q5 = *(const uint32_t*)((br ? p.B_Cim : p.B_im) + moff);
  const uint2 ldt4 = *(const uint2*)((br ? p.B_ldt : p.A_ldt) + blockIdx.x * 4);
  unsigned int epoch;
  asm volatile("ld.relaxed.gpu.global.u32 %0, [%1];" : "=r"(epoch) : "l"(&g_epoch) : "memory");

  for (int i = wtid & 63; i < R_BR / 16; i += 64) sts128(cb + R_OFF + br * R_BR + i * 16, 0, 0, 0, 0);
  STAMP(1);

  float acc[5][4];
  float k2048 = 0.f;
  const uint32_t scr = cb + Y0_OFF + wq * SCR_BYTES;
  const uint32_t scr2 = sb + XIN_OFF + warp * 640;
  {
    const uint32_t ldt2 = (ch & 2) ? ldt4.y : ldt4.x;
    const float dt = bf_round(expf((ch & 1) ? bf_hi(ldt2) : bf_lo(ldt2)));
#pragma unroll
    for (int i = 0; i < 5; i++) acc[i][0] = acc[i][1] = acc[i][2] = acc[i][3] = 0.f;
    cf cc[2], zz1[2], zz128[2];
#pragma unroll
    for (int r = 0; r < 2; r++) {
      float v0 = r ? bf_hi(q0) : bf_lo(q0), v1 = r ? bf_hi(q1) : bf_lo(q1), v2 = r ? bf_hi(q2) : bf_lo(q2);
      float v3 = r ? bf_hi(q3) : bf_lo(q3), v4 = r ? bf_hi(q4) : bf_lo(q4), v5 = r ? bf_hi(q5) : bf_lo(q5);
      if (br == 0) { cc[r] = cmul(cf{v2, v3}, cf{dt * v4, dt * v5}); }
      else { v0 = -bf_round(expf(v0)); cc[r] = cf{2.f * dt * v2, 2.f * dt * v3}; }
      const float xl = (dt * v0) * 1.4426950408889634f, y = dt * v1;
      zz1[r] = cexp_p(xl, y, 1.f); zz128[r] = cexp_p(xl, y, 128.f);
    }
    STAMP(2);
    const uint32_t tb = scr + lane * 16;
    const uint32_t ta = scr + (lane >> 3) * 512 + (lane & 7) * 16;
    const uint32_t tc = ((lane & 8) ? scr2 : scr + 4096) + (lane >> 4) * 128 + (lane & 7) * 16;
    const uint32_t tm = scr2 + 512 + ((lane >> 3) & 1) * 64 + (lane >> 4) * 16;
#pragma unroll 1
    for (int r = 0; r < 2; r++) {
      const cf c = r ? cc[1] : cc[0], z1 = r ? zz1[1] : zz1[0], z128 = r ? zz128[1] : zz128[0];
      const cf z2 = csq(z1), z4 = csq(z2), z8 = csq(z4);
      const cf z16 = csq(z8), z24 = cmul(z16, z8), z32 = csq(z16), z40 = cmul(z32, z8), z48 = csq(z24), z56 = cmul(z32, z24), z64 = csq(z32);
      const cf z256 = csq(z128), z512 = csq(z256), z1024 = csq(z512), z2048 = csq(z1024);
      k2048 += fmaf(c.re, z2048.re, -c.im * z2048.im);
      __syncwarp();
      {
        uint32_t xr[4] = {pack_bf16(1.f, z8.re), pack_bf16(z16.re, z24.re), pack_bf16(z32.re, z40.re), pack_bf16(z48.re, z56.re)};
        uint32_t xi[4] = {pack_bf16(0.f, -z8.im), pack_bf16(-z16.im, -z24.im), pack_bf16(-z32.im, -z40.im), pack_bf16(-z48.im, -z56.im)};
        sts128(tb + 0 * 512, xr[0], xr[1], xr[2], xr[3]);
        sts128(tb + 2 * 512, xi[0], xi[1], xi[2], xi[3]);
        const uint32_t yr = pack_bf16(z64.re, z64.re), nyi = pack_bf16(z64.im, z64.im), yi = nyi ^ 0x80008000u;
        uint32_t o[4], q[4];
#pragma unroll
        for (int i = 0; i < 4; i++) CMUL2(o[i], q[i], xr[i], xi[i], yr, yi, nyi);
        sts128(tb + 1 * 512, o[0], o[1], o[2], o[3]);
        sts128(tb + 3 * 512, q[0], q[1], q[2], q[3]);
      }
      {
        const cf h1 = cmul(c, z128), h2 = cmul(c, z256), h3 = cmul(h1, z256), h4 = cmul(c, z512), h5 = cmul(h1, z512), h6 = cmul(h2, z512), h7 = cmul(h3, z512);
        const cf e1 = cmul(c, z1), e2 = cmul(c, z2), e3 = cmul(e1, z2), e129 = cmul(h1, z1), e130 = cmul(h1, z2), e131 = cmul(e129, z2);
        const cf e258 = cmul(h2, z2), e386 = cmul(h3, z2);
        const uint32_t pr0 = pack_bf16(c.re, e1.re), pr2 = pack_bf16(h1.re, e129.re), pi0 = pack_bf16(c.im, e1.im), pi2 = pack_bf16(h1.im, e129.im);
        sts128(tb + 4 * 512, pr0, pack_bf16(e2.re, e3.re), pr2, pack_bf16(e130.re, e131.re));
        sts128(tb + 5 * 512, pi0, pack_bf16(e2.im, e3.im), pi2, pack_bf16(e130.im, e131.im));
        uint32_t xr[4] = {pack_bf16(h2.re, e258.re), pack_bf16(h3.re, e386.re), pack_bf16(h4.re, h5.re), pack_bf16(h6.re, h7.re)};
        uint32_t xi[4] = {pack_bf16(h2.im, e258.im), pack_bf16(h3.im, e386.im), pack_bf16(h4.im, h5.im), pack_bf16(h6.im, h7.im)};
        sts128(tb + 6 * 512, xr[0], xr[1], xr[2], xr[3]);
        sts128(tb + 7 * 512, xi[0], xi[1], xi[2], xi[3]);
        xr[1] = __byte_perm(xr[0], xr[1], 0x5410); xi[1] = __byte_perm(xi[0], xi[1], 0x5410);
        xr[0] = __byte_perm(pr0, pr2, 0x5410); xi[0] = __byte_perm(pi0, pi2, 0x5410);
        const uint32_t yr = pack_bf16(z1024.re, z1024.re), yi = pack_bf16(z1024.im, z1024.im), nyi = yi ^ 0x80008000u;
        uint32_t o[4], q[4];
#pragma unroll
        for (int i = 0; i < 4; i++) CMUL2(o[i], q[i], xr[i], xi[i], yr, yi, nyi);
        sts128(tb + 8 * 512, o[0], o[1], o[2], o[3]);
        sts128(scr2 + lane * 16, q[0], q[1], q[2], q[3]);
        const uint32_t m4 = pack_bf16(z4.re, z4.im);
        sts16(scr2 + 512 + lane * 2, m4); sts16(scr2 + 576 + lane * 2, m4 >> 16);
      }
      __syncwarp();
#pragma unroll
      for (int kp = 0; kp < 2; kp++) {
        uint32_t rr[2], ri[2], yr[2], yi[2];
        ldsm4t(tc + kp * 256, rr[0], ri[0], rr[1], ri[1]);
        ldsm4(tm + kp * 32, yr[0], yi[0], yr[1], yi[1]);
#pragma unroll
        for (int k2 = 0; k2 < 2; k2++) {
          const int kk = kp * 2 + k2;
          uint32_t a0, a1, a2, a3, pr, pi, qr, qi, xr, xi;
          ldsm4t(ta + kk * 128, a0, a1, a2, a3);
          ldsm4t(ta + 2048 + kk * 128, pr, pi, qr, qi);
          const uint32_t nyi = yi[k2] ^ 0x80008000u;
          mma16816(acc[0], a0, a1, a2, a3, pr, pi);
          mma16816(acc[2], a0, a1, a2, a3, qr, qi);
          mma16816(acc[4], a0, a1, a2, a3, rr[k2], ri[k2]);
          CMUL2(xr, xi, pr, pi, yr[k2], yi[k2], nyi);
          mma16816(acc[1], a0, a1, a2, a3, xr, xi);
          CMUL2(xr, xi, qr, qi, yr[k2], yi[k2], nyi);
          mma16816(acc[3], a0, a1, a2, a3, xr, xi);
        }
      }
    }
#pragma unroll
    for (int o = 16; o; o >>= 1) k2048 += __shfl_xor_sync(0xffffffffu, k2048, o);
  }
  STAMP(3);
  __syncwarp();
  {
    const uint32_t xs = scr + lane * 16;
#define OTH(i, k) __float_as_uint(hf ? acc[i][k] : acc[i][2 + (k)])
    sts128(xs, OTH(0, 0), OTH(0, 1), OTH(1, 0), OTH(1, 1));
    sts128(xs + 512, OTH(2, 0), OTH(2, 1), OTH(3, 0), OTH(3, 1));
    sts128(xs + 1024, OTH(4, 0), OTH(4, 1), __float_as_uint(k2048), 0);
#undef OTH
  }

  bar_sync(1 + ch, 128);
  STAMP(4);
  {
    const uint32_t xo = cb + Y0_OFF + (wq ^ 1) * SCR_BYTES + lane * 16;
    const uint4 o0 = lds128(xo), o1 = lds128(xo + 512), o2 = lds128(xo + 1024);
    const uint32_t rb = cb + R_OFF + br * R_BR;
#define OWN(i, k) (hf ? acc[i][2 + (k)] : acc[i][k])
    const uint32_t vP = pack_bf16(OWN(0, 1) + __uint_as_float(o0.y), OWN(0, 0) + __uint_as_float(o0.x));
    const uint32_t vP4 = pack_bf16(OWN(1, 1) + __uint_as_float(o0.w), OWN(1, 0) + __uint_as_float(o0.z));
    const uint32_t vQ = pack_bf16(OWN(2, 1) + __uint_as_float(o1.y), OWN(2, 0) + __uint_as_float(o1.x));
    const uint32_t vQ4 = pack_bf16(OWN(3, 1) + __uint_as_float(o1.w), OWN(3, 0) + __uint_as_float(o1.z));
    const uint32_t vR = pack_bf16(OWN(4, 1) + __uint_as_float(o2.y), OWN(4, 0) + __uint_as_float(o2.x));
#undef OWN
    const int j = g + 8 * hf;
    {
      const int a = 2 * (t & 1) + 64 * (t & 2) + 8 * j;
      const uint32_t ad = rb + 2 * (RD_X0 - 1 - a);
      const uint32_t a1 = (t & 2) ? ad - 8 : ad, a2 = (t & 2) ? ad : ad - 8;
      const uint32_t w1 = (t & 2) ? vP4 : vP, w2 = (t & 2) ? vP : vP4;
      sts32(a1, w1); sts32(a2, w2);
      sts16(a1 + RD_CS + 2, w1); sts16(a1 + RD_CS + 4, w1 >> 16);
      sts16(a2 + RD_CS + 2, w2); sts16(a2 + RD_CS + 4, w2 >> 16);
    }
    if (t < 2) {
      const int b = 256 + 128 * t + 8 * j;
      const uint32_t ad = rb + 2 * (RD_X0 - 6 - b);
      const uint32_t v22 = __byte_perm(vQ4, 0, 0x3232), v00 = __byte_perm(vQ, 0, 0x3232);
      sts16(ad, vQ4);
      sts64(ad + 2, v22, __byte_perm(vQ4, vQ, 0x5432));
      sts32(ad + 10, v00);
      if (b != 256) { sts16(ad + 14, v00); sts128(ad + RD_CS + 2, vQ4, v22, vQ, v00); }
      else { sts64(ad + RD_CS + 2, vQ4, v22); sts32(ad + RD_CS + 10, vQ); sts16(ad + RD_CS + 14, v00); }
    } else {
      const uint32_t ao = rb + R_O2 + 2 * (159 - (32 * t + j)), ae = ao - (R_O2 - R_E2) + 2;
      sts16(ao, vQ4 >> 16); sts16(ao + RS_CS + 2, vQ4 >> 16); sts16(ao - 32, vQ4); sts16(ao - 32 + RS_CS + 2, vQ4);
      sts16(ae - 32, vQ); sts16(ae - 32 + RS_CS + 2, vQ);
      if (lane != 2 || hf) { sts16(ae, vQ >> 16); sts16(ae + RS_CS + 2, vQ >> 16); }
      else {
        const uint32_t vv = __byte_perm(vQ, 0, 0x3232), ad = rb + 2 * (RD_X0 - 514);
        sts16(ad, vv); sts32(ad + 2, vv); sts16(ad + 6, vv); sts64(ad + RD_CS + 2, vv, vv);
      }
    }
    {
      const uint32_t a = rb + ((g & 1) ? R_O3 : R_E3 + 2) + 2 * (159 - (64 + 16 * t + (j >> 1)));
      const bool p1024 = (lane == 0) && (hf == 0);
      const uint32_t a00 = p1024 ? rb + R_E2 + 2 * (159 - 127) : a;
      sts16(a00, vR >> 16); sts16(a00 + RS_CS + 2, vR >> 16);
      sts16(a - 16, vR); sts16(a - 16 + RS_CS + 2, vR);
      if (p1024) {
        sts32(sb + K1024_OFF + (ch * 2 + br) * 4, __byte_perm(vR, 0, 0x3232));
        const uint32_t kv = pack_bf16(k2048 + __uint_as_float(o2.z), 0.f);
        sts16(rb + R_E3 + 2 * (159 - 127), kv); sts16(rb + R_E3 + 2 * (159 - 127) + RS_CS + 2, kv);
      }
    }
  }
  STAMP(5);
  const uint32_t tag = (epoch + 1) & 0xffffu;
  asm volatile("barrier.cluster.wait.aligned;" ::: "memory");
  bar_sync(1 + ch, 128);
  mbar_wait(sb + B_U);
  STAMP(6);

  const uint32_t zz = lds32(cb + R_OFF);
  conv_dense(cb, zz);
  const uint2 dA = *(const uint2*)(p.A_D + blockIdx.x * 4), dB = *(const uint2*)(p.B_D + blockIdx.x * 4);
  const uint2 gl = gate_ld((4 + ch) * 128 + wtid);
  mbar_wait(sb + B_W);
  conv_far(sb, cb, zz);
  STAMP(10);
  __syncwarp();
  if (lane == 0) asm volatile("mbarrier.arrive.shared::cta.b64 _, [%0];" ::"r"(sb + B_Y3) : "memory");

  {
    const int x = (4 + ch) * 128 + wtid, c = x >> 2;
    const uint32_t g2 = gate_fin(p, gl, x, tag);
    const uint32_t yo = sb + CH_OFF + (x & 3) * 4 + ysw(c);
    uint32_t ua[4], ub[4], ya[4], yb[4], a2[4], b2[4], a3[4], b3[4], s2[4];
    skip_terms(ua, ub, sb, x, dA, dB);
    ld4ch(s2, sb + CH_OFF + (x & 3) * 4 + S2_OFF + ((c - 128) + ((c - 128) >> 3)) * 16);
    mbar_wait(sb + B_Y2);
    const uint4 k0 = lds128(sb + K1024_OFF), k1 = lds128(sb + K1024_OFF + 16);
    const uint32_t kk[8] = {k0.x, k0.y, k0.z, k0.w, k1.x, k1.y, k1.z, k1.w};
    ld4ch(ya, yo + Y0_OFF); ld4ch(yb, yo + Y0_OFF + 4096);
    ld4ch(a2, yo + Y2_OFF - 1024); ld4ch(b2, yo + Y2_OFF - 1024 + 3072);
#pragma unroll
    for (int k = 0; k < 4; k++) { a2[k] = hfma2(kk[2 * k], s2[k], a2[k]); b2[k] = hfma2(kk[2 * k + 1], s2[k], b2[k]); }
    STAMP(11);
    mbar_wait(sb + B_Y3);
    STAMP(12);
    ld4ch(a3, yo + Y3_OFF - 2048); ld4ch(b3, yo + Y3_OFF - 2048 + 2048);
#pragma unroll
    for (int k = 0; k < 4; k++) { ya[k] = hadd2(ya[k], hadd2(a2[k], a3[k])); yb[k] = hadd2(yb[k], hadd2(b2[k], b3[k])); }
    const uint4 r = mix(ya, yb, ua, ub, g2);
    if ((uint32_t)(ch & 1) != rank) send_box(sb, 2 + (ch >> 1), wtid, rank, r);
    else merge_box(sb, &tm_out, 2 + (ch >> 1), wtid, rank, oc0, r, 1 + ch);
  }
  STAMP(14);
  if (wtid == 0) asm volatile("cp.async.bulk.wait_group.read 0;" ::: "memory");
  STAMP(15); GT(1);
}

typedef CUresult (*EncodeFn)(CUtensorMap*, CUtensorMapDataType, cuuint32_t, void*, const cuuint64_t*, const cuuint64_t*,
                             const cuuint32_t*, const cuuint32_t*, CUtensorMapInterleave, CUtensorMapSwizzle,
                             CUtensorMapL2promotion, CUtensorMapFloatOOBfill);

}

extern "C" void kernel_launch(void* const* d_in, const int* in_sizes, int n_in, void* d_out, int out_size) {
  (void)in_sizes; (void)n_in; (void)out_size;
  typedef const __nv_bfloat16* bp;
  Params p;
  p.u = (bp)d_in[0]; p.A_re = (bp)d_in[1]; p.A_im = (bp)d_in[2]; p.B_re = (bp)d_in[3]; p.B_im = (bp)d_in[4];
  p.C_re = (bp)d_in[5]; p.C_im = (bp)d_in[6]; p.A_ldt = (bp)d_in[7]; p.A_D = (bp)d_in[8];
  p.B_lA = (bp)d_in[10]; p.B_Aim = (bp)d_in[11]; p.B_Cre = (bp)d_in[12]; p.B_Cim = (bp)d_in[13];
  p.B_ldt = (bp)d_in[14]; p.B_D = (bp)d_in[15]; p.gw = (bp)d_in[16];
  static EncodeFn enc = nullptr;
  if (!enc) {
    cudaDriverEntryPointQueryResult qr;
    cudaGetDriverEntryPoint("cuTensorMapEncodeTiled", (void**)&enc, cudaEnableDefault, &qr);
    cudaFuncSetAttribute(ssm_kernel, cudaFuncAttributeMaxDynamicSharedMemorySize, SMEM_BYTES);
  }
  CUtensorMap tm_in, tm_out;
  {
    cuuint64_t gd[5] = {512, 2, 4, 4, 64};
    cuuint64_t gs[4] = {1024, 8192, 2048, 32768};
    cuuint32_t bx[5] = {8, 2, 4, 4, 32};
    cuuint32_t es[5] = {1, 1, 1, 1, 1};
    enc(&tm_in, CU_TENSOR_MAP_DATA_TYPE_BFLOAT16, 5, d_in[0], gd, gs, bx, es, CU_TENSOR_MAP_INTERLEAVE_NONE,
        CU_TENSOR_MAP_SWIZZLE_NONE, CU_TENSOR_MAP_L2_PROMOTION_NONE, CU_TENSOR_MAP_FLOAT_OOB_FILL_NONE);
  }
  {
    cuuint64_t gd[3] = {512, 1024, 2};
    cuuint64_t gs[2] = {2048, 1024};
    cuuint32_t bx[3] = {8, 128, 2};
    cuuint32_t es[3] = {1, 1, 1};
    enc(&tm_out, CU_TENSOR_MAP_DATA_TYPE_BFLOAT16, 3, d_out, gd, gs, bx, es, CU_TENSOR_MAP_INTERLEAVE_NONE,
        CU_TENSOR_MAP_SWIZZLE_NONE, CU_TENSOR_MAP_L2_PROMOTION_NONE, CU_TENSOR_MAP_FLOAT_OOB_FILL_NONE);
  }
  ssm_kernel<<<NCTA, 640, SMEM_BYTES, cudaStreamPerThread>>>(p, tm_in, tm_out);
}
```

```cpp
#include <cuda_runtime.h>
#include <cuda.h>
#include <cuda_bf16.h>
#include <stdint.h>

namespace {
#define FIXA 0
#define FIXB 1
#define CPY(x) (x)
#define FCPY(x) __uint_as_float(opq(__float_as_uint(x), zz))
#define STAG 0

constexpr int L = 2048, D = 512, NM = 128;
constexpr int NCTA = 128;

constexpr int RAW_OFF = 0;
constexpr int XIN_OFF = 32768;
constexpr int BAR_OFF = XIN_OFF + 10240;
constexpr int CH_OFF = BAR_OFF + 128;
constexpr int U_CS = 1184;
constexpr int U_OFF = 0;
constexpr int R_OFF = 4736;
constexpr int RD_X0 = 565;
constexpr int RD_CS = 1216;
constexpr int RS_CS = 320;
constexpr int R_E2 = 2 * RD_CS, R_O2 = R_E2 + 2 * RS_CS, R_E3 = R_O2 + 2 * RS_CS, R_O3 = R_E3 + 2 * RS_CS;
constexpr int R_BR = R_O3 + 2 * RS_CS;
constexpr int W5_OFF = R_OFF + 2 * R_BR;
constexpr int W3_OFF = W5_OFF + 3456;
constexpr int W9_OFF = W3_OFF + 3456;
constexpr int W7_OFF = W9_OFF + 2304;
constexpr int S2_OFF = W7_OFF + 2304;
constexpr int Y0_OFF = S2_OFF + 2304;
constexpr int Y2_OFF = Y0_OFF + 8192, Y3_OFF = Y2_OFF + 6144;
constexpr int CH_BYTES = Y0_OFF + 18432 + 16;
constexpr int SCR_BYTES = 4608;
constexpr int SMEM_BYTES = CH_OFF + 4 * CH_BYTES;
static_assert(CH_BYTES % 128 == 16, "bank staggering of the channel blocks");
static_assert(SMEM_BYTES <= 232448, "smem");
constexpr int B_RAW = BAR_OFF, B_X = BAR_OFF + 8, B_U = BAR_OFF + 40, B_W = BAR_OFF + 48, B_Y2 = BAR_OFF + 56, B_Y3 = BAR_OFF + 96;
constexpr int K1024_OFF = BAR_OFF + 64;

__device__ unsigned int g_gate[L];
__device__ unsigned int g_epoch;
__device__ unsigned int g_ticket;

#define STAMP(k)
#define GT(k)

struct Params {
  const __nv_bfloat16 *u, *A_re, *A_im, *B_re, *B_im, *C_re, *C_im, *A_ldt, *A_D;
  const __nv_bfloat16 *B_lA, *B_Aim, *B_Cre, *B_Cim, *B_ldt, *B_D, *gw;
};

template <int N, int TB> __device__ __forceinline__ void wgmma_rs(float* d, uint32_t a0, uint32_t a1, uint32_t a2, uint32_t a3, uint64_t desc, int sc);
template <> __device__ __forceinline__ void wgmma_rs<64, 0>(float* d, uint32_t a0, uint32_t a1, uint32_t a2, uint32_t a3, uint64_t desc, int sc) {
  asm volatile("{\n.reg .pred p;\nsetp.ne.b32 p, %37, 0;\n"
    "wgmma.mma_async.sync.aligned.m64n64k16.f32.bf16.bf16 {%0,%1,%2,%3,%4,%5,%6,%7,%8,%9,%10,%11,%12,%13,%14,%15,%16,%17,%18,%19,%20,%21,%22,%23,%24,%25,%26,%27,%28,%29,%30,%31}, {%32,%33,%34,%35}, %36, p, 1, 1, 0;\n}"
    : "+f"(d[0]), "+f"(d[1]), "+f"(d[2]), "+f"(d[3]), "+f"(d[4]), "+f"(d[5]), "+f"(d[6]), "+f"(d[7]), "+f"(d[8]), "+f"(d[9]), "+f"(d[10]), "+f"(d[11]), "+f"(d[12]), "+f"(d[13]), "+f"(d[14]), "+f"(d[15]), "+f"(d[16]), "+f"(d[17]), "+f"(d[18]), "+f"(d[19]), "+f"(d[20]), "+f"(d[21]), "+f"(d[22]), "+f"(d[23]), "+f"(d[24]), "+f"(d[25]), "+f"(d[26]), "+f"(d[27]), "+f"(d[28]), "+f"(d[29]), "+f"(d[30]), "+f"(d[31]) : "r"(a0), "r"(a1), "r"(a2), "r"(a3), "l"(desc), "r"(sc));
}
template <> __device__ __forceinline__ void wgmma_rs<56, 0>(float* d, uint32_t a0, uint32_t a1, uint32_t a2, uint32_t a3, uint64_t desc, int sc) {
  asm volatile("{\n.reg .pred p;\nsetp.ne.b32 p, %33, 0;\n"
    "wgmma.mma_async.sync.aligned.m64n56k16.f32.bf16.bf16 {%0,%1,%2,%3,%4,%5,%6,%7,%8,%9,%10,%11,%12,%13,%14,%15,%16,%17,%18,%19,%20,%21,%22,%23,%24,%25,%26,%27}, {%28,%29,%30,%31}, %32, p, 1, 1, 0;\n}"
    : "+f"(d[0]), "+f"(d[1]), "+f"(d[2]), "+f"(d[3]), "+f"(d[4]), "+f"(d[5]), "+f"(d[6]), "+f"(d[7]), "+f"(d[8]), "+f"(d[9]), "+f"(d[10]), "+f"(d[11]), "+f"(d[12]), "+f"(d[13]), "+f"(d[14]), "+f"(d[15]), "+f"(d[16]), "+f"(d[17]), "+f"(d[18]), "+f"(d[19]), "+f"(d[20]), "+f"(d[21]), "+f"(d[22]), "+f"(d[23]), "+f"(d[24]), "+f"(d[25]), "+f"(d[26]), "+f"(d[27]) : "r"(a0), "r"(a1), "r"(a2), "r"(a3), "l"(desc), "r"(sc));
}
template <> __device__ __forceinline__ void wgmma_rs<48, 0>(float* d, uint32_t a0, uint32_t a1, uint32_t a2, uint32_t a3, uint64_t desc, int sc) {
  asm volatile("{\n.reg .pred p;\nsetp.ne.b32 p, %29, 0;\n"
    "wgmma.mma_async.sync.aligned.m64n48k16.f32.bf16.bf16 {%0,%1,%2,%3,%4,%5,%6,%7,%8,%9,%10,%11,%12,%13,%14,%15,%16,%17,%18,%19,%20,%21,%22,%23}, {%24,%25,%26,%27}, %28, p, 1, 1, 0;\n}"
    : "+f"(d[0]), "+f"(d[1]), "+f"(d[2]), "+f"(d[3]), "+f"(d[4]), "+f"(d[5]), "+f"(d[6]), "+f"(d[7]), "+f"(d[8]), "+f"(d[9]), "+f"(d[10]), "+f"(d[11]), "+f"(d[12]), "+f"(d[13]), "+f"(d[14]), "+f"(d[15]), "+f"(d[16]), "+f"(d[17]), "+f"(d[18]), "+f"(d[19]), "+f"(d[20]), "+f"(d[21]), "+f"(d[22]), "+f"(d[23]) : "r"(a0), "r"(a1), "r"(a2), "r"(a3), "l"(desc), "r"(sc));
}
template <> __device__ __forceinline__ void wgmma_rs<32, 0>(float* d, uint32_t a0, uint32_t a1, uint32_t a2, uint32_t a3, uint64_t desc, int sc) {
  asm volatile("{\n.reg .pred p;\nsetp.ne.b32 p, %21, 0;\n"
    "wgmma.mma_async.sync.aligned.m64n32k16.f32.bf16.bf16 {%0,%1,%2,%3,%4,%5,%6,%7,%8,%9,%10,%11,%12,%13,%14,%15}, {%16,%17,%18,%19}, %20, p, 1, 1, 0;\n}"
    : "+f"(d[0]), "+f"(d[1]), "+f"(d[2]), "+f"(d[3]), "+f"(d[4]), "+f"(d[5]), "+f"(d[6]), "+f"(d[7]), "+f"(d[8]), "+f"(d[9]), "+f"(d[10]), "+f"(d[11]), "+f"(d[12]), "+f"(d[13]), "+f"(d[14]), "+f"(d[15]) : "r"(a0), "r"(a1), "r"(a2), "r"(a3), "l"(desc), "r"(sc));
}
template <> __device__ __forceinline__ void wgmma_rs<48, 1>(float* d, uint32_t a0, uint32_t a1, uint32_t a2, uint32_t a3, uint64_t desc, int sc) {
  asm volatile("{\n.reg .pred p;\nsetp.ne.b32 p, %29, 0;\n"
    "wgmma.mma_async.sync.aligned.m64n48k16.f32.bf16.bf16 {%0,%1,%2,%3,%4,%5,%6,%7,%8,%9,%10,%11,%12,%13,%14,%15,%16,%17,%18,%19,%20,%21,%22,%23}, {%24,%25,%26,%27}, %28, p, 1, 1, 1;\n}"
    : "+f"(d[0]), "+f"(d[1]), "+f"(d[2]), "+f"(d[3]), "+f"(d[4]), "+f"(d[5]), "+f"(d[6]), "+f"(d[7]), "+f"(d[8]), "+f"(d[9]), "+f"(d[10]), "+f"(d[11]), "+f"(d[12]), "+f"(d[13]), "+f"(d[14]), "+f"(d[15]), "+f"(d[16]), "+f"(d[17]), "+f"(d[18]), "+f"(d[19]), "+f"(d[20]), "+f"(d[21]), "+f"(d[22]), "+f"(d[23]) : "r"(a0), "r"(a1), "r"(a2), "r"(a3), "l"(desc), "r"(sc));
}
template <> __device__ __forceinline__ void wgmma_rs<40, 1>(float* d, uint32_t a0, uint32_t a1, uint32_t a2, uint32_t a3, uint64_t desc, int sc) {
  asm volatile("{\n.reg .pred p;\nsetp.ne.b32 p, %25, 0;\n"
    "wgmma.mma_async.sync.aligned.m64n40k16.f32.bf16.bf16 {%0,%1,%2,%3,%4,%5,%6,%7,%8,%9,%10,%11,%12,%13,%14,%15,%16,%17,%18,%19}, {%20,%21,%22,%23}, %24, p, 1, 1, 1;\n}"
    : "+f"(d[0]), "+f"(d[1]), "+f"(d[2]), "+f"(d[3]), "+f"(d[4]), "+f"(d[5]), "+f"(d[6]), "+f"(d[7]), "+f"(d[8]), "+f"(d[9]), "+f"(d[10]), "+f"(d[11]), "+f"(d[12]), "+f"(d[13]), "+f"(d[14]), "+f"(d[15]), "+f"(d[16]), "+f"(d[17]), "+f"(d[18]), "+f"(d[19]) : "r"(a0), "r"(a1), "r"(a2), "r"(a3), "l"(desc), "r"(sc));
}
template <> __device__ __forceinline__ void wgmma_rs<32, 1>(float* d, uint32_t a0, uint32_t a1, uint32_t a2, uint32_t a3, uint64_t desc, int sc) {
  asm volatile("{\n.reg .pred p;\nsetp.ne.b32 p, %21, 0;\n"
    "wgmma.mma_async.sync.aligned.m64n32k16.f32.bf16.bf16 {%0,%1,%2,%3,%4,%5,%6,%7,%8,%9,%10,%11,%12,%13,%14,%15}, {%16,%17,%18,%19}, %20, p, 1, 1, 1;\n}"
    : "+f"(d[0]), "+f"(d[1]), "+f"(d[2]), "+f"(d[3]), "+f"(d[4]), "+f"(d[5]), "+f"(d[6]), "+f"(d[7]), "+f"(d[8]), "+f"(d[9]), "+f"(d[10]), "+f"(d[11]), "+f"(d[12]), "+f"(d[13]), "+f"(d[14]), "+f"(d[15]) : "r"(a0), "r"(a1), "r"(a2), "r"(a3), "l"(desc), "r"(sc));
}
template <> __device__ __forceinline__ void wgmma_rs<16, 1>(float* d, uint32_t a0, uint32_t a1, uint32_t a2, uint32_t a3, uint64_t desc, int sc) {
  asm volatile("{\n.reg .pred p;\nsetp.ne.b32 p, %13, 0;\n"
    "wgmma.mma_async.sync.aligned.m64n16k16.f32.bf16.bf16 {%0,%1,%2,%3,%4,%5,%6,%7}, {%8,%9,%10,%11}, %12, p, 1, 1, 1;\n}"
    : "+f"(d[0]), "+f"(d[1]), "+f"(d[2]), "+f"(d[3]), "+f"(d[4]), "+f"(d[5]), "+f"(d[6]), "+f"(d[7]) : "r"(a0), "r"(a1), "r"(a2), "r"(a3), "l"(desc), "r"(sc));
}

__device__ __forceinline__ uint32_t pack_bf16(float lo, float hi) {
  uint32_t r; asm("cvt.rn.bf16x2.f32 %0, %1, %2;" : "=r"(r) : "f"(hi), "f"(lo)); return r;
}
__device__ __forceinline__ float bf_lo(uint32_t v) { return __uint_as_float(v << 16); }
__device__ __forceinline__ float bf_hi(uint32_t v) { return __uint_as_float(v & 0xffff0000u); }
__device__ __forceinline__ float bf_round(float x) { return bf_lo(pack_bf16(x, 0.f)); }
__device__ __forceinline__ uint32_t hmul2(uint32_t a, uint32_t b) { uint32_t r; asm("mul.rn.bf16x2 %0, %1, %2;" : "=r"(r) : "r"(a), "r"(b)); return r; }
__device__ __forceinline__ uint32_t hadd2(uint32_t a, uint32_t b) { uint32_t r; asm("add.rn.bf16x2 %0, %1, %2;" : "=r"(r) : "r"(a), "r"(b)); return r; }
__device__ __forceinline__ uint32_t hsub2(uint32_t a, uint32_t b) { uint32_t r; asm("sub.rn.bf16x2 %0, %1, %2;" : "=r"(r) : "r"(a), "r"(b)); return r; }
__device__ __forceinline__ uint32_t hfma2(uint32_t a, uint32_t b, uint32_t c) { uint32_t r; asm("fma.rn.bf16x2 %0, %1, %2, %3;" : "=r"(r) : "r"(a), "r"(b), "r"(c)); return r; }

__device__ __forceinline__ void sts16(uint32_t a, uint32_t v) { asm volatile("st.shared.b16 [%0], %1;" ::"r"(a), "h"((unsigned short)v) : "memory"); }
__device__ __forceinline__ void sts32(uint32_t a, uint32_t v) { asm volatile("st.shared.b32 [%0], %1;" ::"r"(a), "r"(v) : "memory"); }
__device__ __forceinline__ void sts64(uint32_t a, uint32_t x, uint32_t y) { asm volatile("st.shared.v2.b32 [%0], {%1,%2};" ::"r"(a), "r"(x), "r"(y) : "memory"); }
__device__ __forceinline__ void sts128(uint32_t a, uint32_t x, uint32_t y, uint32_t z, uint32_t w) {
  asm volatile("st.shared.v4.b32 [%0], {%1,%2,%3,%4};" ::"r"(a), "r"(x), "r"(y), "r"(z), "r"(w) : "memory");
}
__device__ __forceinline__ uint32_t lds32(uint32_t a) { uint32_t v; asm volatile("ld.shared.b32 %0, [%1];" : "=r"(v) : "r"(a) : "memory"); return v; }
__device__ __forceinline__ uint2 lds64(uint32_t a) { uint2 v; asm volatile("ld.shared.v2.b32 {%0,%1}, [%2];" : "=r"(v.x), "=r"(v.y) : "r"(a) : "memory"); return v; }
__device__ __forceinline__ uint4 lds128(uint32_t a) {
  uint4 v; asm volatile("ld.shared.v4.b32 {%0,%1,%2,%3}, [%4];" : "=r"(v.x), "=r"(v.y), "=r"(v.z), "=r"(v.w) : "r"(a) : "memory"); return v;
}
__device__ __forceinline__ uint4 ldg128(const void* a) {
  uint4 v; asm volatile("ld.global.nc.v4.b32 {%0,%1,%2,%3}, [%4];" : "=r"(v.x), "=r"(v.y), "=r"(v.z), "=r"(v.w) : "l"(a) : "memory"); return v;
}
__device__ __forceinline__ uint2 ldg64(const void* a) {
  uint2 v; asm volatile("ld.global.nc.v2.b32 {%0,%1}, [%2];" : "=r"(v.x), "=r"(v.y) : "l"(a) : "memory"); return v;
}
__device__ __forceinline__ void ldsm4(uint32_t a, uint32_t& r0, uint32_t& r1, uint32_t& r2, uint32_t& r3) {
  asm volatile("ldmatrix.sync.aligned.m8n8.x4.shared.b16 {%0,%1,%2,%3}, [%4];" : "=r"(r0), "=r"(r1), "=r"(r2), "=r"(r3) : "r"(a) : "memory");
}
__device__ __forceinline__ void ldsm4t(uint32_t a, uint32_t& r0, uint32_t& r1, uint32_t& r2, uint32_t& r3) {
  asm volatile("ldmatrix.sync.aligned.m8n8.x4.trans.shared.b16 {%0,%1,%2,%3}, [%4];" : "=r"(r0), "=r"(r1), "=r"(r2), "=r"(r3) : "r"(a) : "memory");
}
__device__ __forceinline__ void stsm4(uint32_t a, uint32_t r0, uint32_t r1, uint32_t r2, uint32_t r3) {
  asm volatile("stmatrix.sync.aligned.m8n8.x4.shared.b16 [%0], {%1,%2,%3,%4};" ::"r"(a), "r"(r0), "r"(r1), "r"(r2), "r"(r3) : "memory");
}
__device__ __forceinline__ void stsm4t(uint32_t a, uint32_t r0, uint32_t r1, uint32_t r2, uint32_t r3) {
  asm volatile("stmatrix.sync.aligned.m8n8.x4.trans.shared.b16 [%0], {%1,%2,%3,%4};" ::"r"(a), "r"(r0), "r"(r1), "r"(r2), "r"(r3) : "memory");
}
__device__ __forceinline__ void mma16816(float* c, uint32_t a0, uint32_t a1, uint32_t a2, uint32_t a3, uint32_t b0, uint32_t b1) {
  asm("mma.sync.aligned.m16n8k16.row.col.f32.bf16.bf16.f32 {%0,%1,%2,%3}, {%4,%5,%6,%7}, {%8,%9}, {%0,%1,%2,%3};"
      : "+f"(c[0]), "+f"(c[1]), "+f"(c[2]), "+f"(c[3]) : "r"(a0), "r"(a1), "r"(a2), "r"(a3), "r"(b0), "r"(b1));
}
__device__ __forceinline__ void bar_sync(int id, int n) { asm volatile("bar.sync %0, %1;" ::"r"(id), "r"(n) : "memory"); }
__device__ __forceinline__ void bar_arrive(int id, int n) { asm volatile("bar.arrive %0, %1;" ::"r"(id), "r"(n) : "memory"); }
__device__ __forceinline__ void wg_fence() { asm volatile("wgmma.fence.sync.aligned;" ::: "memory"); }
__device__ __forceinline__ void wg_commit() { asm volatile("wgmma.commit_group.sync.aligned;" ::: "memory"); }
__device__ __forceinline__ void wg_wait0() { asm volatile("wgmma.wait_group.sync.aligned 0;" ::: "memory"); }
__device__ __forceinline__ void fence_async() { asm volatile("fence.proxy.async.shared::cta;" ::: "memory"); }
__device__ __forceinline__ uint32_t opq(uint32_t x, uint32_t z) { uint32_t r; asm volatile("xor.b32 %0, %1, %2;" : "=r"(r) : "r"(x), "r"(z)); return r; }
__device__ __forceinline__ uint64_t mkdesc(uint32_t addr, uint32_t lbo, uint32_t sbo) {
  return (uint64_t)((addr & 0x3FFFF) >> 4) | ((uint64_t)(lbo >> 4) << 16) | ((uint64_t)(sbo >> 4) << 32);
}
__device__ __forceinline__ uint32_t mapa(uint32_t a, uint32_t rank) {
  uint32_t r; asm("mapa.shared::cluster.u32 %0, %1, %2;" : "=r"(r) : "r"(a), "r"(rank)); return r;
}
__device__ __forceinline__ void mbar_init_expect(uint32_t bar, uint32_t bytes) {
  asm volatile("mbarrier.init.shared::cta.b64 [%0], 1;" ::"r"(bar) : "memory");
  asm volatile("mbarrier.arrive.expect_tx.shared::cta.b64 _, [%0], %1;" ::"r"(bar), "r"(bytes) : "memory");
}
__device__ __forceinline__ void mbar_wait(uint32_t bar) {
#pragma unroll 1
  for (int it = 0; it < (1 << 22); it++) {
    uint32_t ok;
    asm volatile("{\n.reg .pred p;\nmbarrier.try_wait.parity.acquire.cluster.shared::cta.b64 p, [%1], 0;\nselp.u32 %0, 1, 0, p;\n}"
                 : "=r"(ok) : "r"(bar) : "memory");
    if (ok) return;
  }
  __trap();
}
__device__ __forceinline__ void st_async4(uint32_t a, uint32_t bar, uint32_t x, uint32_t y, uint32_t z, uint32_t w) {
  asm volatile("st.async.weak.shared::cluster.mbarrier::complete_tx::bytes.v4.b32 [%0], {%2,%3,%4,%5}, [%1];"
               ::"r"(a), "r"(bar), "r"(x), "r"(y), "r"(z), "r"(w) : "memory");
}

struct cf { float re, im; };
__device__ __forceinline__ cf cmul(cf a, cf b) { return {fmaf(a.re, b.re, -a.im * b.im), fmaf(a.re, b.im, a.im * b.re)}; }
__device__ __forceinline__ cf csq(cf a) { return {fmaf(a.re, a.re, -a.im * a.im), (a.re + a.re) * a.im}; }
__device__ __forceinline__ cf cexp_p(float xl, float y, float p) {
  float mag; asm("ex2.approx.ftz.f32 %0, %1;" : "=f"(mag) : "f"(xl * p));
  const float th = y * p;
  const float k = rintf(th * 0.15915494309189535f);
  float r = fmaf(k, -6.2831854820251465f, th);
  r = fmaf(k, 1.7484555314695172e-07f, r);
  return {mag * __cosf(r), mag * __sinf(r)};
}
__device__ __forceinline__ uint32_t ysw(int c) { return (uint32_t)(c ^ ((c >> 3) & 3)) * 16u; }

#define CMUL2(OR, OI, xr, xi, yr, yi, nyi) do { OR = hfma2(xr, yr, hmul2(xi, nyi)); OI = hfma2(xr, yi, hmul2(xi, yr)); } while (0)

__device__ __forceinline__ uint32_t gate_slow(const __nv_bfloat16* u, const __nv_bfloat16* gw, int row) {
  float s = 0.f;
  const uint32_t* xr = (const uint32_t*)(u + (size_t)row * D);
  const uint32_t* wr = (const uint32_t*)gw;
#pragma unroll 1
  for (int j = 0; j < D / 2; j++) { const uint32_t pr = hmul2(xr[j], wr[j]); s += bf_lo(pr); s += bf_hi(pr); }
  s = bf_round(s);
  return pack_bf16(1.f / (1.f + expf(-s)), 0.f);
}

__device__ __forceinline__ uint2 gate_ld(int x) {
  uint2 gv;
  asm volatile("ld.relaxed.gpu.global.v2.u32 {%0,%1}, [%2];" : "=r"(gv.x), "=r"(gv.y) : "l"(g_gate + x * 2) : "memory");
  return gv;
}
__device__ __noinline__ uint32_t gate_poll(const __nv_bfloat16* u, const __nv_bfloat16* gw, int x, uint32_t tag) {
  uint2 gv;
#pragma unroll 1
  for (int spins = 0; spins < (1 << 16); spins++) {
    gv = gate_ld(x);
    if ((gv.x >> 16) == tag && (gv.y >> 16) == tag) return __byte_perm(gv.x, gv.y, 0x5410);
  }
  return __byte_perm(gate_slow(u, gw, x * 2), gate_slow(u, gw, x * 2 + 1), 0x5410);
}
__device__ __forceinline__ uint32_t gate_fin(const Params& p, uint2 gv, int x, uint32_t tag) {
  if ((gv.x >> 16) == tag && (gv.y >> 16) == tag) return __byte_perm(gv.x, gv.y, 0x5410);
  return gate_poll(p.u, p.gw, x, tag);
}

__device__ __forceinline__ void ld4ch(uint32_t* v, uint32_t addr) {
#pragma unroll
  for (int k = 0; k < 4; k++) v[k] = lds32(addr + k * CH_BYTES);
}
__device__ __forceinline__ void skip_terms(uint32_t* ua, uint32_t* ub, uint32_t sb, int x, uint2 dA, uint2 dB) {
  const int c = x >> 2;
  uint32_t uu[4];
  ld4ch(uu, sb + CH_OFF + (x & 3) * 4 + U_OFF + (c & 3) * U_CS + (63 - (c >> 2)) * 16);
#pragma unroll
  for (int k = 0; k < 4; k++) {
    ua[k] = hmul2(uu[k], __byte_perm((k & 2) ? dA.y : dA.x, 0, (k & 1) ? 0x3232 : 0x1010));
    ub[k] = hmul2(uu[k], __byte_perm((k & 2) ? dB.y : dB.x, 0, (k & 1) ? 0x3232 : 0x1010));
  }
}
__device__ __forceinline__ uint4 mix(const uint32_t* a, const uint32_t* b, const uint32_t* ua, const uint32_t* ub, uint32_t g2) {
  const uint32_t h2 = hsub2(0x3f803f80u, g2);
  uint32_t o[4];
#pragma unroll
  for (int k = 0; k < 4; k++) o[k] = hadd2(hmul2(g2, hadd2(a[k], ua[k])), hmul2(h2, hadd2(b[k], ub[k])));
  return make_uint4(__byte_perm(o[0], o[1], 0x5410), __byte_perm(o[2], o[3], 0x5410), __byte_perm(o[0], o[1], 0x7632), __byte_perm(o[2], o[3], 0x7632));
}
__device__ __forceinline__ void send_box(uint32_t sb, int slot, int wtid, uint32_t rank, uint4 r) {
  st_async4(mapa(sb + XIN_OFF + slot * 2048 + wtid * 16, rank ^ 1), mapa(sb + B_X + slot * 8, rank ^ 1), r.x, r.y, r.z, r.w);
}
__device__ __forceinline__ void merge_box(uint32_t sb, const CUtensorMap* tm_out, int slot, int wtid, uint32_t rank, int oc0, uint4 r, int barid) {
  const uint32_t st = sb + RAW_OFF + slot * 4096 + wtid * 16;
  sts64(st + rank * 8, r.x, r.y); sts64(st + 2048 + rank * 8, r.z, r.w);
  mbar_wait(sb + B_X + slot * 8);
  const uint4 q = lds128(sb + XIN_OFF + slot * 2048 + wtid * 16);
  sts64(st + (rank ^ 1) * 8, q.x, q.y); sts64(st + 2048 + (rank ^ 1) * 8, q.z, q.w);
  fence_async();
  bar_sync(barid, 128);
  if (wtid == 0) {
    asm volatile("cp.async.bulk.tensor.3d.global.shared::cta.bulk_group [%0, {%2, %3, %4}], [%1];"
                 ::"l"(tm_out), "r"(sb + RAW_OFF + slot * 4096), "r"(oc0), "r"((2 * slot + (int)rank) * 128), "r"(0) : "memory");
    asm volatile("cp.async.bulk.commit_group;" ::: "memory");
  }
}

__device__ __forceinline__ uint32_t band2(int e, int lo, int hi) {
  uint32_t r = ((uint32_t)(e - lo) <= (uint32_t)(hi - lo) ? 0x3f80u : 0u) | ((uint32_t)(e - 1 - lo) <= (uint32_t)(hi - lo) ? 0x3f800000u : 0u);
  asm volatile("" : "+r"(r));
  return r;
}

__device__ __forceinline__ void conv_dense(uint32_t cb, uint32_t zz) {
  const int lane = threadIdx.x & 31, wq = (threadIdx.x >> 5) & 3, br = wq >> 1, hf = wq & 1, g = lane >> 2, t = lane & 3;
  const uint32_t rb = cb + R_OFF + br * R_BR;
  const int eo = 16 * hf + g - 2 * t;
  float dacc[32];
  {
      {
        const int x0 = RD_X0 - (eo + 536);
        const uint32_t fa = rb + ((g & 1) ? 2 * x0 : RD_CS + 2 * x0 + 2);
        const uint64_t ub = mkdesc(cb + U_OFF, U_CS, 128);
        uint32_t A[2][4][4];
        float e56[28], e48[24];
        auto loadA = [&](int j) {
#pragma unroll
          for (int k = 0; k < 4; k++) {
            const int s = 34 - 4 * j - k;
            if (s >= 0) {
              if (k == 0) A[j & 1][0][2] = lds32(fa + (2 * s + 2) * 16);
              A[j & 1][k][0] = lds32(fa + (2 * s + 1) * 16);
              A[j & 1][k][1] = lds32(fa + (2 * s) * 16);
            }
          }
#pragma unroll
          for (int k = 0; k < 4; k++) {
            if (34 - 4 * j - k >= 0) {
              A[j & 1][k][3] = CPY(A[j & 1][k][0]);
              if (k) A[j & 1][k][2] = CPY(A[j & 1][k - 1][1]);
            }
          }
        };
        loadA(0);
#pragma unroll
        for (int j = 0; j < 9; j++) {
          if (j == 4) {
#pragma unroll
            for (int i = 0; i < 28; i++) e56[i] = FCPY(dacc[i]);
          }
          if (j == 8) {
#pragma unroll
            for (int i = 0; i < 24; i++) e48[i] = FCPY(e56[i]);
          }
          wg_fence();
#pragma unroll
          for (int k = 0; k < 4; k++) {
            const int s = 34 - 4 * j - k;
            if (s >= 0) {
              const int o = 2 * s - 66 + 128;
              const int cc = o & 3, rs = (o >> 2) - 32;
              const int n0 = ((-rs) >> 3) * 8;
              const uint64_t desc = ub + (uint64_t)((cc * U_CS - rs * 16) >> 4);
              const uint32_t* a = A[j & 1][k];
              if (n0 == 0) wgmma_rs<64, 0>(dacc, a[0], a[1], a[2], a[3], desc, s != 34);
              else if (n0 == 8) wgmma_rs<56, 0>(FIXB ? e56 : dacc, a[0], a[1], a[2], a[3], desc, 1);
              else wgmma_rs<48, 0>(FIXB ? e48 : dacc, a[0], a[1], a[2], a[3], desc, 1);
            }
          }
          wg_commit();
          if (j < 8) loadA(j + 1);
          wg_wait0();
        }
#pragma unroll
        for (int i = 0; i < 28; i++) dacc[i] = i < 24 ? e48[i] : e56[i];
      }
      const uint32_t yb = cb + Y0_OFF + br * 4096;
#pragma unroll
      for (int i = 0; i < 8; i += 2) {
        const int mi = lane >> 3;
        const int cidx = 4 * (63 - 8 * (i + (mi >> 1)) - (lane & 7)) + 2 * hf + (mi & 1);
        stsm4t(yb + ysw(cidx), pack_bf16(dacc[4 * i], dacc[4 * i + 1]), pack_bf16(dacc[4 * i + 2], dacc[4 * i + 3]),
               pack_bf16(dacc[4 * i + 4], dacc[4 * i + 5]), pack_bf16(dacc[4 * i + 6], dacc[4 * i + 7]));
      }
      bar_arrive(8, 640);
      STAMP(8);
  }
}

__device__ __forceinline__ void conv_far(uint32_t sb, uint32_t cb, uint32_t zz) {
  const int lane = threadIdx.x & 31, wq = (threadIdx.x >> 5) & 3, br = wq >> 1, hf = wq & 1, g = lane >> 2, t = lane & 3;
  const uint32_t rb = cb + R_OFF + br * R_BR;
  const int eo = 16 * hf + g - 2 * t;
  float dacc[24], e40[20], e32[16], h32[16], h16[8];
  const int x1 = 159 - (eo + 136);
  const uint32_t fs = rb + ((g & 1) ? 2 * x1 : RS_CS + 2 * x1 + 2);
  {
    uint32_t A[2][4][4];
    auto loadA = [&](int buf, uint32_t oe, uint32_t oo, int i0) {
#pragma unroll
      for (int a = 0; a < 2; a++) {
        const uint32_t base = fs + (a ? oo : oe) + i0 * 16;
        uint32_t* k0 = A[buf][2 * a];
        uint32_t* k1 = A[buf][2 * a + 1];
        k0[1] = lds32(base); k0[0] = lds32(base + 16); k0[2] = lds32(base + 32); k1[0] = lds32(base + 48); k1[2] = lds32(base + 64);
      }
#pragma unroll
      for (int a = 0; a < 2; a++) {
        uint32_t* k0 = A[buf][2 * a];
        uint32_t* k1 = A[buf][2 * a + 1];
        k0[3] = CPY(k0[0]); k1[1] = CPY(k0[2]); k1[3] = CPY(k1[0]);
      }
    };
    const uint64_t d5 = mkdesc(cb + W5_OFF, 144, 576), d3 = mkdesc(cb + W3_OFF, 144, 576);
    loadA(0, R_E2, R_O2, 8);
#pragma unroll
    for (int m = 2; m <= 4; m++) {
      if (m == 3) {
#pragma unroll
        for (int i = 0; i < 20; i++) e40[i] = FCPY(dacc[i]);
      }
      if (m == 4) {
#pragma unroll
        for (int i = 0; i < 16; i++) e32[i] = FCPY(e40[i]);
      }
      wg_fence();
#pragma unroll
      for (int k = 0; k < 4; k++) {
        const uint32_t* a = A[m & 1][k];
        const uint64_t desc = ((k >> 1) ? d3 : d5) + (k & 1) * 18 + (m - 2) * 36;
        if (m == 2) wgmma_rs<48, 1>(dacc, a[0], a[1], a[2], a[3], desc, k);
        else if (m == 3) wgmma_rs<40, 1>(e40, a[0], a[1], a[2], a[3], desc, 1);
        else wgmma_rs<32, 1>(e32, a[0], a[1], a[2], a[3], desc, 1);
      }
      wg_commit();
      if (m < 4) loadA((m + 1) & 1, R_E2, R_O2, 4 * (3 - m));
      else loadA(1, R_E3, R_O3, 8);
      wg_wait0();
    }
#pragma unroll
    for (int i = 0; i < 20; i++) dacc[i] = i < 16 ? e32[i] : e40[i];
    {
      const uint32_t yb = cb + Y2_OFF + br * 3072;
#pragma unroll
      for (int i = 0; i < 6; i += 2) {
        const int mi = lane >> 3;
        const int cidx = 32 * (5 - i - (mi >> 1)) + 16 * hf + 8 * (mi & 1) + (lane & 7);
        stsm4(yb + ysw(cidx), pack_bf16(dacc[4 * i], dacc[4 * i + 1]), pack_bf16(dacc[4 * i + 2], dacc[4 * i + 3]),
              pack_bf16(dacc[4 * i + 4], dacc[4 * i + 5]), pack_bf16(dacc[4 * i + 6], dacc[4 * i + 7]));
      }
    }
    __syncwarp();
    if (lane == 0) asm volatile("mbarrier.arrive.shared::cta.b64 _, [%0];" ::"r"(sb + B_Y2) : "memory");
    STAMP(9);
    const uint64_t d9 = mkdesc(cb + W9_OFF, 144, 576), d7 = mkdesc(cb + W7_OFF, 144, 576);
#pragma unroll
    for (int m = 2; m <= 3; m++) {
      if (m == 3) {
#pragma unroll
        for (int i = 0; i < 8; i++) h16[i] = FCPY(h32[i]);
      }
      wg_fence();
#pragma unroll
      for (int k = 0; k < 4; k++) {
        const uint32_t* a = A[(m + 1) & 1][k];
        const uint64_t desc = ((k >> 1) ? d7 : d9) + (k & 1) * 18 + (m - 2) * 72;
        if (m == 2) wgmma_rs<32, 1>(h32, a[0], a[1], a[2], a[3], desc, k);
        else wgmma_rs<16, 1>(h16, a[0], a[1], a[2], a[3], desc, 1);
      }
      wg_commit();
      if (m == 2) loadA(0, R_E3, R_O3, 4);
      wg_wait0();
    }
#pragma unroll
    for (int i = 0; i < 16; i++) dacc[i] = i < 8 ? h16[i] : h32[i];
    const uint32_t yb = cb + Y3_OFF + br * 2048;
#pragma unroll
    for (int i = 0; i < 4; i += 2) {
      const int mi = lane >> 3;
      const int cidx = 64 * (1 - (i >> 1)) + 2 * (16 * hf + 8 * (mi & 1) + (lane & 7)) + (mi >> 1);
      stsm4(yb + ysw(cidx), pack_bf16(dacc[4 * i], dacc[4 * i + 1]), pack_bf16(dacc[4 * i + 2], dacc[4 * i + 3]),
            pack_bf16(dacc[4 * i + 4], dacc[4 * i + 5]), pack_bf16(dacc[4 * i + 6], dacc[4 * i + 7]));
    }
  }
}

__global__ void __cluster_dims__(2, 1, 1) __launch_bounds__(640, 1)
ssm_kernel(const Params p, const __grid_constant__ CUtensorMap tm_in, const __grid_constant__ CUtensorMap tm_out) {
  extern __shared__ __align__(1024) unsigned char smem_raw[];
  const uint32_t sb = (uint32_t)__cvta_generic_to_shared(smem_raw);
  const int tid = threadIdx.x, lane = tid & 31;
  const int warp = __shfl_sync(0xffffffffu, tid >> 5, 0);
  const int ch = warp >> 2, wq = warp & 3, br = wq >> 1, hf = wq & 1;
  const int g = lane >> 2, t = lane & 3;
  const int d = blockIdx.x * 4 + ch;
  const uint32_t rank = blockIdx.x & 1;
  const uint32_t cb = sb + CH_OFF + ch * CH_BYTES;
  const int wtid = tid & 127;
  const int oc0 = (int)(blockIdx.x >> 1) * 8;
  STAMP(0); GT(0);

  if (warp >= 16) {
    if (wtid == 0) {
      mbar_init_expect(sb + B_RAW, 32768);
#pragma unroll
      for (int i = 0; i < 4; i++) mbar_init_expect(sb + B_X + 8 * i, 2048);
      asm volatile("mbarrier.init.shared::cta.b64 [%0], 128;" ::"r"(sb + B_U) : "memory");
      asm volatile("mbarrier.init.shared::cta.b64 [%0], 128;" ::"r"(sb + B_W) : "memory");
      asm volatile("mbarrier.init.shared::cta.b64 [%0], 16;" ::"r"(sb + B_Y2) : "memory");
      asm volatile("mbarrier.init.shared::cta.b64 [%0], 16;" ::"r"(sb + B_Y3) : "memory");
      asm volatile("fence.mbarrier_init.release.cluster;" ::: "memory");
      asm volatile("fence.proxy.async.shared::cta;" ::: "memory");
    }
    __syncwarp();
    asm volatile("barrier.cluster.arrive.relaxed.aligned;" ::: "memory");
    unsigned int epoch;
    asm volatile("ld.relaxed.gpu.global.u32 %0, [%1];" : "=r"(epoch) : "l"(&g_epoch) : "memory");
    asm volatile("barrier.cluster.wait.aligned;" ::: "memory");
    if (wtid == 0) {
      asm volatile("cp.async.bulk.tensor.5d.shared::cluster.global.mbarrier::complete_tx::bytes.multicast::cluster [%0], [%1, {%3, %4, %4, %4, %5}], [%2], %6;"
                   ::"r"(sb + RAW_OFF + rank * 16384), "l"(&tm_in), "r"(sb + B_RAW), "r"(oc0), "r"(0), "r"((int)rank * 32), "h"((unsigned short)3) : "memory");
    }
    sts128(sb + CH_OFF + wq * CH_BYTES + U_OFF + (lane >> 3) * U_CS + (64 + (lane & 7)) * 16, 0, 0, 0, 0);
    const uint4 gw0 = ldg128(p.gw + lane * 8), gw1 = ldg128(p.gw + 256 + lane * 8);
      const int grow = blockIdx.x * 16 + wq * 4;
      uint4 gx[4][2];
#pragma unroll
      for (int i = 0; i < 4; i++) {
        gx[i][0] = ldg128(p.u + (size_t)(grow + i) * D + lane * 8);
        gx[i][1] = ldg128(p.u + (size_t)(grow + i) * D + 256 + lane * 8);
      }
    STAMP(3);
    mbar_wait(sb + B_RAW);
    STAMP(4);
    {
      const uint32_t dst = sb + CH_OFF + (g & 3) * CH_BYTES + U_OFF + t * U_CS + (63 - wq * 16) * 16;
#pragma unroll
      for (int h = 0; h < 2; h++) {
        uint32_t r[8][4];
#pragma unroll
        for (int i = 0; i < 8; i++) ldsm4t(sb + RAW_OFF + (wq * 16 + h * 8 + i) * 512 + lane * 16, r[i][0], r[i][1], r[i][2], r[i][3]);
        if ((uint32_t)(g >> 2) == rank) {
#pragma unroll
          for (int i = 0; i < 8; i++) sts128(dst - (h * 8 + i) * 16, r[i][0], r[i][1], r[i][2], r[i][3]);
        }
      }
    }
    fence_async();
    asm volatile("mbarrier.arrive.shared::cta.b64 _, [%0];" ::"r"(sb + B_U) : "memory");
    const uint32_t tag = (epoch + 1) & 0xffffu;
    {
      const uint32_t ws[8] = {gw0.x, gw0.y, gw0.z, gw0.w, gw1.x, gw1.y, gw1.z, gw1.w};
      float sm[4];
#pragma unroll
      for (int i = 0; i < 4; i++) {
        const uint32_t xs[8] = {gx[i][0].x, gx[i][0].y, gx[i][0].z, gx[i][0].w, gx[i][1].x, gx[i][1].y, gx[i][1].z, gx[i][1].w};
        float s = 0.f;
#pragma unroll
        for (int j = 0; j < 8; j++) { const uint32_t pr = hmul2(xs[j], ws[j]); s += bf_lo(pr); s += bf_hi(pr); }
        sm[i] = s;
      }
      {
        const bool b0 = lane & 1, b1 = lane & 2;
        float u0 = b0 ? sm[1] : sm[0], v0 = b0 ? sm[0] : sm[1], u1 = b0 ? sm[3] : sm[2], v1 = b0 ? sm[2] : sm[3];
        u0 += __shfl_xor_sync(0xffffffffu, v0, 1); u1 += __shfl_xor_sync(0xffffffffu, v1, 1);
        float s = b1 ? u1 : u0; const float v = b1 ? u0 : u1;
        s += __shfl_xor_sync(0xffffffffu, v, 2);
#pragma unroll
        for (int o = 4; o < 32; o <<= 1) s += __shfl_xor_sync(0xffffffffu, s, o);
        s = bf_round(s);
        const float gv = 1.f / (1.f + expf(-s));
        const uint32_t w = (tag << 16) | (pack_bf16(gv, 0.f) & 0xffffu);
        if (lane < 4) asm volatile("st.relaxed.gpu.global.u32 [%0], %1;" ::"l"(&g_gate[grow + lane]), "r"(w) : "memory");
      }
    }
    STAMP(2);
    uint32_t BA[3][4], BC[3][4];
    {
      const int l1 = br ? 3 : 6, h1 = br ? 5 : 10;
#pragma unroll
      for (int i = 0; i < 3; i++) {
        const int e = 16 * hf + g - 2 * t + 16 - 16 * i;
        BA[i][0] = band2(e, l1, h1); BA[i][1] = band2(e + 8, l1, h1); BA[i][2] = band2(e - 8, l1, h1); BA[i][3] = BA[i][0];
        BC[i][0] = band2(e, 3, 4); BC[i][1] = band2(e + 8, 3, 4); BC[i][2] = band2(e - 8, 3, 4); BC[i][3] = BC[i][0];
      }
    }
    bar_sync(5, 128);
    STAMP(5);
    {
      const int mrow = lane & 7, mi = lane >> 3;
      const uint64_t ub0 = mkdesc(sb + CH_OFF + U_OFF, U_CS, 128);
      {
        float w1[24], w3[16];
#pragma unroll
        for (int i = 0; i < 24; i++) w1[i] = 0.f;
#pragma unroll
        for (int i = 0; i < 16; i++) w3[i] = 0.f;
        uint32_t wa[3], sa[2];
#pragma unroll
        for (int i = 0; i < 3; i++) {
          const int c = 4 * (47 - 8 * (2 * i + (mi >> 1)) - mrow) + 2 * hf + (mi & 1);
          wa[i] = sb + CH_OFF + (br ? W3_OFF : W5_OFF) + (5 - (c >> 5)) * 576 + ((c & 31) >> 3) * 144 + (c & 7) * 16;
          if (i) sa[i - 1] = sb + CH_OFF + S2_OFF + (c + (c >> 3)) * 16;
        }
#pragma unroll 1
        for (int k = 0; k < 4; k++) {
          wg_fence();
#pragma unroll
          for (int i = 0; i < 3; i++)
            wgmma_rs<48, 0>(w1, BA[i][0], BA[i][1], BA[i][2], BA[i][3],
                            ub0 + (uint64_t)((k * CH_BYTES + ((2 * i + 2) & 3) * U_CS + (16 + (i == 0)) * 16) >> 4), i);
#pragma unroll
          for (int i = 0; i < 3; i++)
            wgmma_rs<32, 0>(w3, BC[i][0], BC[i][1], BC[i][2], BC[i][3],
                            ub0 + (uint64_t)((k * CH_BYTES + ((2 * i + 2) & 3) * U_CS + (32 + (i == 0)) * 16) >> 4), i);
          wg_commit();
          wg_wait0();
#pragma unroll
          for (int i = 0; i < 3; i++)
            stsm4t(wa[i] + k * CH_BYTES, pack_bf16(w1[8 * i], w1[8 * i + 1]), pack_bf16(w1[8 * i + 2], w1[8 * i + 3]),
                   pack_bf16(w1[8 * i + 4], w1[8 * i + 5]), pack_bf16(w1[8 * i + 6], w1[8 * i + 7]));
          if (br == 0) {
#pragma unroll
            for (int i = 0; i < 2; i++)
              stsm4t(sa[i] + k * CH_BYTES, pack_bf16(w3[8 * i], w3[8 * i + 1]), pack_bf16(w3[8 * i + 2], w3[8 * i + 3]),
                     pack_bf16(w3[8 * i + 4], w3[8 * i + 5]), pack_bf16(w3[8 * i + 6], w3[8 * i + 7]));
          }
        }
      }
      {
        uint32_t BB[4][4];
        const int l2 = br ? 5 : 12, h2 = br ? 11 : 20;
#pragma unroll
        for (int i = 0; i < 4; i++) {
          const int e = 16 * hf + g - 2 * t + 32 - 16 * i;
          BB[i][0] = band2(e, l2, h2); BB[i][1] = band2(e + 8, l2, h2); BB[i][2] = band2(e - 8, l2, h2); BB[i][3] = BB[i][0];
        }
        float w2[2][16];
#pragma unroll
        for (int i = 0; i < 16; i++) { w2[0][i] = 0.f; w2[1][i] = 0.f; }
        uint32_t wa[2];
#pragma unroll
        for (int i = 0; i < 2; i++) {
          const int c = 4 * (31 - 8 * (2 * i + (mi >> 1)) - mrow) + 2 * hf + (mi & 1), pp = c >> 1;
          wa[i] = sb + CH_OFF + (br ? W7_OFF : W9_OFF) + (1 - (pp >> 5)) * 1152 + (c & 1) * 576 + ((pp & 31) >> 3) * 144 + (pp & 7) * 16;
        }
#pragma unroll 1
        for (int kp = 0; kp < 2; kp++) {
          wg_fence();
#pragma unroll
          for (int k = 0; k < 2; k++)
#pragma unroll
            for (int i = 0; i < 4; i++)
              wgmma_rs<32, 0>(w2[k], BB[i][0], BB[i][1], BB[i][2], BB[i][3],
                              ub0 + (uint64_t)(((2 * kp + k) * CH_BYTES + ((2 * i) & 3) * U_CS + (32 + (i < 2)) * 16) >> 4), i);
          wg_commit();
          wg_wait0();
#pragma unroll
          for (int k = 0; k < 2; k++)
#pragma unroll
            for (int i = 0; i < 2; i++)
              stsm4t(wa[i] + (2 * kp + k) * CH_BYTES, pack_bf16(w2[k][8 * i], w2[k][8 * i + 1]), pack_bf16(w2[k][8 * i + 2], w2[k][8 * i + 3]),
                     pack_bf16(w2[k][8 * i + 4], w2[k][8 * i + 5]), pack_bf16(w2[k][8 * i + 6], w2[k][8 * i + 7]));
        }
      }
    }
    fence_async();
    asm volatile("mbarrier.arrive.shared::cta.b64 _, [%0];" ::"r"(sb + B_W) : "memory");
    STAMP(7);
    const uint2 dA = ldg64(p.A_D + blockIdx.x * 4), dB = ldg64(p.B_D + blockIdx.x * 4);
    STAMP(8);
    uint32_t gg[4];
    {
      uint2 gl[4];
#pragma unroll
      for (int i = 0; i < 4; i++) gl[i] = gate_ld((i ^ (int)rank ^ 1) * 128 + wtid);
#pragma unroll
      for (int i = 0; i < 4; i++) gg[i] = gate_fin(p, gl[i], (i ^ (int)rank ^ 1) * 128 + wtid, tag);
    }
    {
      uint32_t ua[4][4], ub[4][4], ya[4][4], yb[4][4], yo[4];
#pragma unroll
      for (int i = 0; i < 4; i++) {
        const int x = (i ^ (int)rank ^ 1) * 128 + wtid;
        skip_terms(ua[i], ub[i], sb, x, dA, dB);
        yo[i] = sb + CH_OFF + (x & 3) * 4 + ysw(x >> 2);
      }
      bar_sync(8, 640);
      STAMP(10);
#pragma unroll
      for (int i = 0; i < 4; i++) { ld4ch(ya[i], yo[i] + Y0_OFF); ld4ch(yb[i], yo[i] + Y0_OFF + 4096); }
      send_box(sb, 0, wtid, rank, mix(ya[0], yb[0], ua[0], ub[0], gg[0]));
      merge_box(sb, &tm_out, 0, wtid, rank, oc0, mix(ya[1], yb[1], ua[1], ub[1], gg[1]), 5);
      STAMP(12);
      mbar_wait(sb + B_Y2);
      STAMP(11);
#pragma unroll
      for (int i = 2; i < 4; i++) { ld4ch(ya[i - 2], yo[i] + Y2_OFF - 1024); ld4ch(yb[i - 2], yo[i] + Y2_OFF - 1024 + 3072); }
#pragma unroll
      for (int i = 2; i < 4; i++)
#pragma unroll
        for (int k = 0; k < 4; k++) { ya[i][k] = hadd2(ya[i][k], ya[i - 2][k]); yb[i][k] = hadd2(yb[i][k], yb[i - 2][k]); }
      send_box(sb, 1, wtid, rank, mix(ya[2], yb[2], ua[2], ub[2], gg[2]));
      merge_box(sb, &tm_out, 1, wtid, rank, oc0, mix(ya[3], yb[3], ua[3], ub[3], gg[3]), 5);
      STAMP(13);
    }
    if (wtid == 0) {
      if (atomicAdd(&g_ticket, 1u) == NCTA - 1) { g_ticket = 0; g_epoch = epoch + 1; }
      asm volatile("cp.async.bulk.wait_group.read 0;" ::: "memory");
    }
    STAMP(15);
    return;
  }
  asm volatile("barrier.cluster.arrive.relaxed.aligned;" ::: "memory");

  const int moff = d * NM + hf * 64 + lane * 2;
  const uint32_t q0 = *(const uint32_t*)((br ? p.B_lA : p.A_re) + moff), q1 = *(const uint32_t*)((br ? p.B_Aim : p.A_im) + moff);
  const uint32_t q2 = *(const uint32_t*)((br ? p.B_Cre : p.C_re) + moff), q3 = *(const uint32_t*)((br ? p.B_Cim : p.C_im) + moff);
  const uint32_t q4 = *(const uint32_t*)((br ? p.B_Cre : p.B_re) + moff), q5 = *(const uint32_t*)((br ? p.B_Cim : p.B_im) + moff);
  const uint2 ldt4 = *(const uint2*)((br ? p.B_ldt : p.A_ldt) + blockIdx.x * 4);
  unsigned int epoch;
  asm volatile("ld.relaxed.gpu.global.u32 %0, [%1];" : "=r"(epoch) : "l"(&g_epoch) : "memory");

  for (int i = wtid & 63; i < R_BR / 16; i += 64) sts128(cb + R_OFF + br * R_BR + i * 16, 0, 0, 0, 0);
  STAMP(1);

  float acc[5][4];
  float k2048 = 0.f;
  const uint32_t scr = cb + Y0_OFF + wq * SCR_BYTES;
  const uint32_t scr2 = sb + XIN_OFF + warp * 640;
  {
    const uint32_t ldt2 = (ch & 2) ? ldt4.y : ldt4.x;
    const float dt = bf_round(expf((ch & 1) ? bf_hi(ldt2) : bf_lo(ldt2)));
#pragma unroll
    for (int i = 0; i < 5; i++) acc[i][0] = acc[i][1] = acc[i][2] = acc[i][3] = 0.f;
    cf cc[2], zz1[2], zz128[2];
#pragma unroll
    for (int r = 0; r < 2; r++) {
      float v0 = r ? bf_hi(q0) : bf_lo(q0), v1 = r ? bf_hi(q1) : bf_lo(q1), v2 = r ? bf_hi(q2) : bf_lo(q2);
      float v3 = r ? bf_hi(q3) : bf_lo(q3), v4 = r ? bf_hi(q4) : bf_lo(q4), v5 = r ? bf_hi(q5) : bf_lo(q5);
      if (br == 0) { cc[r] = cmul(cf{v2, v3}, cf{dt * v4, dt * v5}); }
      else { v0 = -bf_round(expf(v0)); cc[r] = cf{2.f * dt * v2, 2.f * dt * v3}; }
      const float xl = (dt * v0) * 1.4426950408889634f, y = dt * v1;
      zz1[r] = cexp_p(xl, y, 1.f); zz128[r] = cexp_p(xl, y, 128.f);
    }
    STAMP(2);
    const uint32_t tb = scr + lane * 16;
    const uint32_t ta = scr + (lane >> 3) * 512 + (lane & 7) * 16;
    const uint32_t tc = ((lane & 8) ? scr2 : scr + 4096) + (lane >> 4) * 128 + (lane & 7) * 16;
    const uint32_t tm = scr2 + 512 + ((lane >> 3) & 1) * 64 + (lane >> 4) * 16;
#pragma unroll 1
    for (int r = 0; r < 2; r++) {
      const cf c = r ? cc[1] : cc[0], z1 = r ? zz1[1] : zz1[0], z128 = r ? zz128[1] : zz128[0];
      const cf z2 = csq(z1), z4 = csq(z2), z8 = csq(z4);
      const cf z16 = csq(z8), z24 = cmul(z16, z8), z32 = csq(z16), z40 = cmul(z32, z8), z48 = csq(z24), z56 = cmul(z32, z24), z64 = csq(z32);
      const cf z256 = csq(z128), z512 = csq(z256), z1024 = csq(z512), z2048 = csq(z1024);
      k2048 += fmaf(c.re, z2048.re, -c.im * z2048.im);
      __syncwarp();
      {
        uint32_t xr[4] = {pack_bf16(1.f, z8.re), pack_bf16(z16.re, z24.re), pack_bf16(z32.re, z40.re), pack_bf16(z48.re, z56.re)};
        uint32_t xi[4] = {pack_bf16(0.f, -z8.im), pack_bf16(-z16.im, -z24.im), pack_bf16(-z32.im, -z40.im), pack_bf16(-z48.im, -z56.im)};
        sts128(tb + 0 * 512, xr[0], xr[1], xr[2], xr[3]);
        sts128(tb + 2 * 512, xi[0], xi[1], xi[2], xi[3]);
        const uint32_t yr = pack_bf16(z64.re, z64.re), nyi = pack_bf16(z64.im, z64.im), yi = nyi ^ 0x80008000u;
        uint32_t o[4], q[4];
#pragma unroll
        for (int i = 0; i < 4; i++) CMUL2(o[i], q[i], xr[i], xi[i], yr, yi, nyi);
        sts128(tb + 1 * 512, o[0], o[1], o[2], o[3]);
        sts128(tb + 3 * 512, q[0], q[1], q[2], q[3]);
      }
      {
        const cf h1 = cmul(c, z128), h2 = cmul(c, z256), h3 = cmul(h1, z256), h4 = cmul(c, z512), h5 = cmul(h1, z512), h6 = cmul(h2, z512), h7 = cmul(h3, z512);
        const cf e1 = cmul(c, z1), e2 = cmul(c, z2), e3 = cmul(e1, z2), e129 = cmul(h1, z1), e130 = cmul(h1, z2), e131 = cmul(e129, z2);
        const cf e258 = cmul(h2, z2), e386 = cmul(h3, z2);
        const uint32_t pr0 = pack_bf16(c.re, e1.re), pr2 = pack_bf16(h1.re, e129.re), pi0 = pack_bf16(c.im, e1.im), pi2 = pack_bf16(h1.im, e129.im);
        sts128(tb + 4 * 512, pr0, pack_bf16(e2.re, e3.re), pr2, pack_bf16(e130.re, e131.re));
        sts128(tb + 5 * 512, pi0, pack_bf16(e2.im, e3.im), pi2, pack_bf16(e130.im, e131.im));
        uint32_t xr[4] = {pack_bf16(h2.re, e258.re), pack_bf16(h3.re, e386.re), pack_bf16(h4.re, h5.re), pack_bf16(h6.re, h7.re)};
        uint32_t xi[4] = {pack_bf16(h2.im, e258.im), pack_bf16(h3.im, e386.im), pack_bf16(h4.im, h5.im), pack_bf16(h6.im, h7.im)};
        sts128(tb + 6 * 512, xr[0], xr[1], xr[2], xr[3]);
        sts128(tb + 7 * 512, xi[0], xi[1], xi[2], xi[3]);
        xr[1] = __byte_perm(xr[0], xr[1], 0x5410); xi[1] = __byte_perm(xi[0], xi[1], 0x5410);
        xr[0] = __byte_perm(pr0, pr2, 0x5410); xi[0] = __byte_perm(pi0, pi2, 0x5410);
        const uint32_t yr = pack_bf16(z1024.re, z1024.re), yi = pack_bf16(z1024.im, z1024.im), nyi = yi ^ 0x80008000u;
        uint32_t o[4], q[4];
#pragma unroll
        for (int i = 0; i < 4; i++) CMUL2(o[i], q[i], xr[i], xi[i], yr, yi, nyi);
        sts128(tb + 8 * 512, o[0], o[1], o[2], o[3]);
        sts128(scr2 + lane * 16, q[0], q[1], q[2], q[3]);
        const uint32_t m4 = pack_bf16(z4.re, z4.im);
        sts16(scr2 + 512 + lane * 2, m4); sts16(scr2 + 576 + lane * 2, m4 >> 16);
      }
      __syncwarp();
#pragma unroll
      for (int kp = 0; kp < 2; kp++) {
        uint32_t rr[2], ri[2], yr[2], yi[2];
        ldsm4t(tc + kp * 256, rr[0], ri[0], rr[1], ri[1]);
        ldsm4(tm + kp * 32, yr[0], yi[0], yr[1], yi[1]);
#pragma unroll
        for (int k2 = 0; k2 < 2; k2++) {
          const int kk = kp * 2 + k2;
          uint32_t a0, a1, a2, a3, pr, pi, qr, qi, xr, xi;
          ldsm4t(ta + kk * 128, a0, a1, a2, a3);
          ldsm4t(ta + 2048 + kk * 128, pr, pi, qr, qi);
          const uint32_t nyi = yi[k2] ^ 0x80008000u;
          mma16816(acc[0], a0, a1, a2, a3, pr, pi);
          mma16816(acc[2], a0, a1, a2, a3, qr, qi);
          mma16816(acc[4], a0, a1, a2, a3, rr[k2], ri[k2]);
          CMUL2(xr, xi, pr, pi, yr[k2], yi[k2], nyi);
          mma16816(acc[1], a0, a1, a2, a3, xr, xi);
          CMUL2(xr, xi, qr, qi, yr[k2], yi[k2], nyi);
          mma16816(acc[3], a0, a1, a2, a3, xr, xi);
        }
      }
    }
#pragma unroll
    for (int o = 16; o; o >>= 1) k2048 += __shfl_xor_sync(0xffffffffu, k2048, o);
  }
  STAMP(3);
  __syncwarp();
  {
    const uint32_t xs = scr + lane * 16;
#define OTH(i, k) __float_as_uint(hf ? acc[i][k] : acc[i][2 + (k)])
    sts128(xs, OTH(0, 0), OTH(0, 1), OTH(1, 0), OTH(1, 1));
    sts128(xs + 512, OTH(2, 0), OTH(2, 1), OTH(3, 0), OTH(3, 1));
    sts128(xs + 1024, OTH(4, 0), OTH(4, 1), __float_as_uint(k2048), 0);
#undef OTH
  }

  bar_sync(1 + ch, 128);
  STAMP(4);
  {
    const uint32_t xo = cb + Y0_OFF + (wq ^ 1) * SCR_BYTES + lane * 16;
    const uint4 o0 = lds128(xo), o1 = lds128(xo + 512), o2 = lds128(xo + 1024);
    const uint32_t rb = cb + R_OFF + br * R_BR;
#define OWN(i, k) (hf ? acc[i][2 + (k)] : acc[i][k])
    const uint32_t vP = pack_bf16(OWN(0, 1) + __uint_as_float(o0.y), OWN(0, 0) + __uint_as_float(o0.x));
    const uint32_t vP4 = pack_bf16(OWN(1, 1) + __uint_as_float(o0.w), OWN(1, 0) + __uint_as_float(o0.z));
    const uint32_t vQ = pack_bf16(OWN(2, 1) + __uint_as_float(o1.y), OWN(2, 0) + __uint_as_float(o1.x));
    const uint32_t vQ4 = pack_bf16(OWN(3, 1) + __uint_as_float(o1.w), OWN(3, 0) + __uint_as_float(o1.z));
    const uint32_t vR = pack_bf16(OWN(4, 1) + __uint_as_float(o2.y), OWN(4, 0) + __uint_as_float(o2.x));
#undef OWN
    const int j = g + 8 * hf;
    {
      const int a = 2 * (t & 1) + 64 * (t & 2) + 8 * j;
      const uint32_t ad = rb + 2 * (RD_X0 - 1 - a);
      const uint32_t a1 = (t & 2) ? ad - 8 : ad, a2 = (t & 2) ? ad : ad - 8;
      const uint32_t w1 = (t & 2) ? vP4 : vP, w2 = (t & 2) ? vP : vP4;
      sts32(a1, w1); sts32(a2, w2);
      sts16(a1 + RD_CS + 2, w1); sts16(a1 + RD_CS + 4, w1 >> 16);
      sts16(a2 + RD_CS + 2, w2); sts16(a2 + RD_CS + 4, w2 >> 16);
    }
    if (t < 2) {
      const int b = 256 + 128 * t + 8 * j;
      const uint32_t ad = rb + 2 * (RD_X0 - 6 - b);
      const uint32_t v22 = __byte_perm(vQ4, 0, 0x3232), v00 = __byte_perm(vQ, 0, 0x3232);
      sts16(ad, vQ4);
      sts64(ad + 2, v22, __byte_perm(vQ4, vQ, 0x5432));
      sts32(ad + 10, v00);
      if (b != 256) { sts16(ad + 14, v00); sts128(ad + RD_CS + 2, vQ4, v22, vQ, v00); }
      else { sts64(ad + RD_CS + 2, vQ4, v22); sts32(ad + RD_CS + 10, vQ); sts16(ad + RD_CS + 14, v00); }
    } else {
      const uint32_t ao = rb + R_O2 + 2 * (159 - (32 * t + j)), ae = ao - (R_O2 - R_E2) + 2;
      sts16(ao, vQ4 >> 16); sts16(ao + RS_CS + 2, vQ4 >> 16); sts16(ao - 32, vQ4); sts16(ao - 32 + RS_CS + 2, vQ4);
      sts16(ae - 32, vQ); sts16(ae - 32 + RS_CS + 2, vQ);
      if (lane != 2 || hf) { sts16(ae, vQ >> 16); sts16(ae + RS_CS + 2, vQ >> 16); }
      else {
        const uint32_t vv = __byte_perm(vQ, 0, 0x3232), ad = rb + 2 * (RD_X0 - 514);
        sts16(ad, vv); sts32(ad + 2, vv); sts16(ad + 6, vv); sts64(ad + RD_CS + 2, vv, vv);
      }
    }
    {
      const uint32_t a = rb + ((g & 1) ? R_O3 : R_E3 + 2) + 2 * (159 - (64 + 16 * t + (j >> 1)));
      const bool p1024 = (lane == 0) && (hf == 0);
      const uint32_t a00 = p1024 ? rb + R_E2 + 2 * (159 - 127) : a;
      sts16(a00, vR >> 16); sts16(a00 + RS_CS + 2, vR >> 16);
      sts16(a - 16, vR); sts16(a - 16 + RS_CS + 2, vR);
      if (p1024) {
        sts32(sb + K1024_OFF + (ch * 2 + br) * 4, __byte_perm(vR, 0, 0x3232));
        const uint32_t kv = pack_bf16(k2048 + __uint_as_float(o2.z), 0.f);
        sts16(rb + R_E3 + 2 * (159 - 127), kv); sts16(rb + R_E3 + 2 * (159 - 127) + RS_CS + 2, kv);
      }
    }
  }
  STAMP(5);
  const uint32_t tag = (epoch + 1) & 0xffffu;
  asm volatile("barrier.cluster.wait.aligned;" ::: "memory");
  bar_sync(1 + ch, 128);
  mbar_wait(sb + B_U);
  STAMP(6);

  const uint32_t zz = lds32(cb + R_OFF);
  conv_dense(cb, zz);
  const uint2 dA = ldg64(p.A_D + blockIdx.x * 4), dB = ldg64(p.B_D + blockIdx.x * 4);
  const uint2 gl = gate_ld((4 + ch) * 128 + wtid);
  mbar_wait(sb + B_W);
  conv_far(sb, cb, zz);
  STAMP(10);
  __syncwarp();
  if (lane == 0) asm volatile("mbarrier.arrive.shared::cta.b64 _, [%0];" ::"r"(sb + B_Y3) : "memory");

  {
    const int x = (4 + ch) * 128 + wtid, c = x >> 2;
    const uint32_t g2 = gate_fin(p, gl, x, tag);
    const uint32_t yo = sb + CH_OFF + (x & 3) * 4 + ysw(c);
    uint32_t ua[4], ub[4], ya[4], yb[4], a2[4], b2[4], a3[4], b3[4], s2[4];
    skip_terms(ua, ub, sb, x, dA, dB);
    ld4ch(s2, sb + CH_OFF + (x & 3) * 4 + S2_OFF + ((c - 128) + ((c - 128) >> 3)) * 16);
    mbar_wait(sb + B_Y2);
    const uint4 k0 = lds128(sb + K1024_OFF), k1 = lds128(sb + K1024_OFF + 16);
    const uint32_t kk[8] = {k0.x, k0.y, k0.z, k0.w, k1.x, k1.y, k1.z, k1.w};
    ld4ch(ya, yo + Y0_OFF); ld4ch(yb, yo + Y0_OFF + 4096);
    ld4ch(a2, yo + Y2_OFF - 1024); ld4ch(b2, yo + Y2_OFF - 1024 + 3072);
#pragma unroll
    for (int k = 0; k < 4; k++) { a2[k] = hfma2(kk[2 * k], s2[k], a2[k]); b2[k] = hfma2(kk[2 * k + 1], s2[k], b2[k]); }
    STAMP(11);
    mbar_wait(sb + B_Y3);
    STAMP(12);
    ld4ch(a3, yo + Y3_OFF - 2048); ld4ch(b3, yo + Y3_OFF - 2048 + 2048);
#pragma unroll
    for (int k = 0; k < 4; k++) { ya[k] = hadd2(ya[k], hadd2(a2[k], a3[k])); yb[k] = hadd2(yb[k], hadd2(b2[k], b3[k])); }
    const uint4 r = mix(ya, yb, ua, ub, g2);
    if ((uint32_t)(ch & 1) != rank) send_box(sb, 2 + (ch >> 1), wtid, rank, r);
    else merge_box(sb, &tm_out, 2 + (ch >> 1), wtid, rank, oc0, r, 1 + ch);
  }
  STAMP(14);
  if (wtid == 0) asm volatile("cp.async.bulk.wait_group.read 0;" ::: "memory");
  STAMP(15); GT(1);
}

typedef CUresult (*EncodeFn)(CUtensorMap*, CUtensorMapDataType, cuuint32_t, void*, const cuuint64_t*, const cuuint64_t*,
                             const cuuint32_t*, const cuuint32_t*, CUtensorMapInterleave, CUtensorMapSwizzle,
                             CUtensorMapL2promotion, CUtensorMapFloatOOBfill);

}

extern "C" void kernel_launch(void* const* d_in, const int* in_sizes, int n_in, void* d_out, int out_size) {
  (void)in_sizes; (void)n_in; (void)out_size;
  typedef const __nv_bfloat16* bp;
  Params p;
  p.u = (bp)d_in[0]; p.A_re = (bp)d_in[1]; p.A_im = (bp)d_in[2]; p.B_re = (bp)d_in[3]; p.B_im = (bp)d_in[4];
  p.C_re = (bp)d_in[5]; p.C_im = (bp)d_in[6]; p.A_ldt = (bp)d_in[7]; p.A_D = (bp)d_in[8];
  p.B_lA = (bp)d_in[10]; p.B_Aim = (bp)d_in[11]; p.B_Cre = (bp)d_in[12]; p.B_Cim = (bp)d_in[13];
  p.B_ldt = (bp)d_in[14]; p.B_D = (bp)d_in[15]; p.gw = (bp)d_in[16];
  static EncodeFn enc = nullptr;
  if (!enc) {
    cudaDriverEntryPointQueryResult qr;
    cudaGetDriverEntryPoint("cuTensorMapEncodeTiled", (void**)&enc, cudaEnableDefault, &qr);
    cudaFuncSetAttribute(ssm_kernel, cudaFuncAttributeMaxDynamicSharedMemorySize, SMEM_BYTES);
  }
  CUtensorMap tm_in, tm_out;
  {
    cuuint64_t gd[5] = {512, 2, 4, 4, 64};
    cuuint64_t gs[4] = {1024, 8192, 2048, 32768};
    cuuint32_t bx[5] = {8, 2, 4, 4, 32};
    cuuint32_t es[5] = {1, 1, 1, 1, 1};
    enc(&tm_in, CU_TENSOR_MAP_DATA_TYPE_BFLOAT16, 5, d_in[0], gd, gs, bx, es, CU_TENSOR_MAP_INTERLEAVE_NONE,
        CU_TENSOR_MAP_SWIZZLE_NONE, CU_TENSOR_MAP_L2_PROMOTION_NONE, CU_TENSOR_MAP_FLOAT_OOB_FILL_NONE);
  }
  {
    cuuint64_t gd[3] = {512, 1024, 2};
    cuuint64_t gs[2] = {2048, 1024};
    cuuint32_t bx[3] = {8, 128, 2};
    cuuint32_t es[3] = {1, 1, 1};
    enc(&tm_out, CU_TENSOR_MAP_DATA_TYPE_BFLOAT16, 3, d_out, gd, gs, bx, es, CU_TENSOR_MAP_INTERLEAVE_NONE,
        CU_TENSOR_MAP_SWIZZLE_NONE, CU_TENSOR_MAP_L2_PROMOTION_NONE, CU_TENSOR_MAP_FLOAT_OOB_FILL_NONE);
  }
  ssm_kernel<<<NCTA, 640, SMEM_BYTES, cudaStreamPerThread>>>(p, tm_in, tm_out);
}
```

```cpp
#include <cuda_runtime.h>
#include <cuda.h>
#include <cuda_bf16.h>
#include <stdint.h>

namespace {
#define FIXA 0
#define FIXB 1
#define CPY(x) (x)
#define FCPY(x) __uint_as_float(opq(__float_as_uint(x), zz))

constexpr int L = 2048, D = 512, NM = 128;
constexpr int NCTA = 128;

constexpr int RAW_OFF = 0;
constexpr int XIN_OFF = 32768;
constexpr int BAR_OFF = XIN_OFF + 10240;
constexpr int CH_OFF = BAR_OFF + 128;
constexpr int U_CS = 1184;
constexpr int U_OFF = 0;
constexpr int R_OFF = 4736;
constexpr int RD_X0 = 565;
constexpr int RD_CS = 1216;
constexpr int RS_CS = 320;
constexpr int R_E2 = 2 * RD_CS, R_O2 = R_E2 + 2 * RS_CS, R_E3 = R_O2 + 2 * RS_CS, R_O3 = R_E3 + 2 * RS_CS;
constexpr int R_BR = R_O3 + 2 * RS_CS;
constexpr int W5_OFF = R_OFF + 2 * R_BR;
constexpr int W3_OFF = W5_OFF + 3456;
constexpr int W9_OFF = W3_OFF + 3456;
constexpr int W7_OFF = W9_OFF + 2304;
constexpr int S2_OFF = W7_OFF + 2304;
constexpr int Y0_OFF = S2_OFF + 2304;
constexpr int Y2_OFF = Y0_OFF + 8192, Y3_OFF = Y2_OFF + 6144;
constexpr int CH_BYTES = Y0_OFF + 18432 + 16;
constexpr int SCR_BYTES = 4608;
constexpr int SMEM_BYTES = CH_OFF + 4 * CH_BYTES;
static_assert(CH_BYTES % 128 == 16, "bank staggering of the channel blocks");
static_assert(SMEM_BYTES <= 232448, "smem");
constexpr int B_RAW = BAR_OFF, B_X = BAR_OFF + 8, B_U = BAR_OFF + 40, B_W = BAR_OFF + 48, B_Y2 = BAR_OFF + 56, B_Y3 = BAR_OFF + 96;
constexpr int TAG_OFF = BAR_OFF + 104;
constexpr int K1024_OFF = BAR_OFF + 64;

__device__ unsigned int g_gate[L];
__device__ unsigned int g_epoch;
__device__ unsigned int g_ticket;

#define STAMP(k)
#define GT(k)

struct Params {
  const __nv_bfloat16* t[14];
  const __nv_bfloat16 *u, *gw, *A_D, *B_D;
};

template <int N, int TB> __device__ __forceinline__ void wgmma_rs(float* d, uint32_t a0, uint32_t a1, uint32_t a2, uint32_t a3, uint64_t desc, int sc);
template <> __device__ __forceinline__ void wgmma_rs<64, 0>(float* d, uint32_t a0, uint32_t a1, uint32_t a2, uint32_t a3, uint64_t desc, int sc) {
  asm volatile("{\n.reg .pred p;\nsetp.ne.b32 p, %37, 0;\n"
    "wgmma.mma_async.sync.aligned.m64n64k16.f32.bf16.bf16 {%0,%1,%2,%3,%4,%5,%6,%7,%8,%9,%10,%11,%12,%13,%14,%15,%16,%17,%18,%19,%20,%21,%22,%23,%24,%25,%26,%27,%28,%29,%30,%31}, {%32,%33,%34,%35}, %36, p, 1, 1, 0;\n}"
    : "+f"(d[0]), "+f"(d[1]), "+f"(d[2]), "+f"(d[3]), "+f"(d[4]), "+f"(d[5]), "+f"(d[6]), "+f"(d[7]), "+f"(d[8]), "+f"(d[9]), "+f"(d[10]), "+f"(d[11]), "+f"(d[12]), "+f"(d[13]), "+f"(d[14]), "+f"(d[15]), "+f"(d[16]), "+f"(d[17]), "+f"(d[18]), "+f"(d[19]), "+f"(d[20]), "+f"(d[21]), "+f"(d[22]), "+f"(d[23]), "+f"(d[24]), "+f"(d[25]), "+f"(d[26]), "+f"(d[27]), "+f"(d[28]), "+f"(d[29]), "+f"(d[30]), "+f"(d[31]) : "r"(a0), "r"(a1), "r"(a2), "r"(a3), "l"(desc), "r"(sc));
}
template <> __device__ __forceinline__ void wgmma_rs<56, 0>(float* d, uint32_t a0, uint32_t a1, uint32_t a2, uint32_t a3, uint64_t desc, int sc) {
  asm volatile("{\n.reg .pred p;\nsetp.ne.b32 p, %33, 0;\n"
    "wgmma.mma_async.sync.aligned.m64n56k16.f32.bf16.bf16 {%0,%1,%2,%3,%4,%5,%6,%7,%8,%9,%10,%11,%12,%13,%14,%15,%16,%17,%18,%19,%20,%21,%22,%23,%24,%25,%26,%27}, {%28,%29,%30,%31}, %32, p, 1, 1, 0;\n}"
    : "+f"(d[0]), "+f"(d[1]), "+f"(d[2]), "+f"(d[3]), "+f"(d[4]), "+f"(d[5]), "+f"(d[6]), "+f"(d[7]), "+f"(d[8]), "+f"(d[9]), "+f"(d[10]), "+f"(d[11]), "+f"(d[12]), "+f"(d[13]), "+f"(d[14]), "+f"(d[15]), "+f"(d[16]), "+f"(d[17]), "+f"(d[18]), "+f"(d[19]), "+f"(d[20]), "+f"(d[21]), "+f"(d[22]), "+f"(d[23]), "+f"(d[24]), "+f"(d[25]), "+f"(d[26]), "+f"(d[27]) : "r"(a0), "r"(a1), "r"(a2), "r"(a3), "l"(desc), "r"(sc));
}
template <> __device__ __forceinline__ void wgmma_rs<48, 0>(float* d, uint32_t a0, uint32_t a1, uint32_t a2, uint32_t a3, uint64_t desc, int sc) {
  asm volatile("{\n.reg .pred p;\nsetp.ne.b32 p, %29, 0;\n"
    "wgmma.mma_async.sync.aligned.m64n48k16.f32.bf16.bf16 {%0,%1,%2,%3,%4,%5,%6,%7,%8,%9,%10,%11,%12,%13,%14,%15,%16,%17,%18,%19,%20,%21,%22,%23}, {%24,%25,%26,%27}, %28, p, 1, 1, 0;\n}"
    : "+f"(d[0]), "+f"(d[1]), "+f"(d[2]), "+f"(d[3]), "+f"(d[4]), "+f"(d[5]), "+f"(d[6]), "+f"(d[7]), "+f"(d[8]), "+f"(d[9]), "+f"(d[10]), "+f"(d[11]), "+f"(d[12]), "+f"(d[13]), "+f"(d[14]), "+f"(d[15]), "+f"(d[16]), "+f"(d[17]), "+f"(d[18]), "+f"(d[19]), "+f"(d[20]), "+f"(d[21]), "+f"(d[22]), "+f"(d[23]) : "r"(a0), "r"(a1), "r"(a2), "r"(a3), "l"(desc), "r"(sc));
}
template <> __device__ __forceinline__ void wgmma_rs<32, 0>(float* d, uint32_t a0, uint32_t a1, uint32_t a2, uint32_t a3, uint64_t desc, int sc) {
  asm volatile("{\n.reg .pred p;\nsetp.ne.b32 p, %21, 0;\n"
    "wgmma.mma_async.sync.aligned.m64n32k16.f32.bf16.bf16 {%0,%1,%2,%3,%4,%5,%6,%7,%8,%9,%10,%11,%12,%13,%14,%15}, {%16,%17,%18,%19}, %20, p, 1, 1, 0;\n}"
    : "+f"(d[0]), "+f"(d[1]), "+f"(d[2]), "+f"(d[3]), "+f"(d[4]), "+f"(d[5]), "+f"(d[6]), "+f"(d[7]), "+f"(d[8]), "+f"(d[9]), "+f"(d[10]), "+f"(d[11]), "+f"(d[12]), "+f"(d[13]), "+f"(d[14]), "+f"(d[15]) : "r"(a0), "r"(a1), "r"(a2), "r"(a3), "l"(desc), "r"(sc));
}
template <> __device__ __forceinline__ void wgmma_rs<48, 1>(float* d, uint32_t a0, uint32_t a1, uint32_t a2, uint32_t a3, uint64_t desc, int sc) {
  asm volatile("{\n.reg .pred p;\nsetp.ne.b32 p, %29, 0;\n"
    "wgmma.mma_async.sync.aligned.m64n48k16.f32.bf16.bf16 {%0,%1,%2,%3,%4,%5,%6,%7,%8,%9,%10,%11,%12,%13,%14,%15,%16,%17,%18,%19,%20,%21,%22,%23}, {%24,%25,%26,%27}, %28, p, 1, 1, 1;\n}"
    : "+f"(d[0]), "+f"(d[1]), "+f"(d[2]), "+f"(d[3]), "+f"(d[4]), "+f"(d[5]), "+f"(d[6]), "+f"(d[7]), "+f"(d[8]), "+f"(d[9]), "+f"(d[10]), "+f"(d[11]), "+f"(d[12]), "+f"(d[13]), "+f"(d[14]), "+f"(d[15]), "+f"(d[16]), "+f"(d[17]), "+f"(d[18]), "+f"(d[19]), "+f"(d[20]), "+f"(d[21]), "+f"(d[22]), "+f"(d[23]) : "r"(a0), "r"(a1), "r"(a2), "r"(a3), "l"(desc), "r"(sc));
}
template <> __device__ __forceinline__ void wgmma_rs<40, 1>(float* d, uint32_t a0, uint32_t a1, uint32_t a2, uint32_t a3, uint64_t desc, int sc) {
  asm volatile("{\n.reg .pred p;\nsetp.ne.b32 p, %25, 0;\n"
    "wgmma.mma_async.sync.aligned.m64n40k16.f32.bf16.bf16 {%0,%1,%2,%3,%4,%5,%6,%7,%8,%9,%10,%11,%12,%13,%14,%15,%16,%17,%18,%19}, {%20,%21,%22,%23}, %24, p, 1, 1, 1;\n}"
    : "+f"(d[0]), "+f"(d[1]), "+f"(d[2]), "+f"(d[3]), "+f"(d[4]), "+f"(d[5]), "+f"(d[6]), "+f"(d[7]), "+f"(d[8]), "+f"(d[9]), "+f"(d[10]), "+f"(d[11]), "+f"(d[12]), "+f"(d[13]), "+f"(d[14]), "+f"(d[15]), "+f"(d[16]), "+f"(d[17]), "+f"(d[18]), "+f"(d[19]) : "r"(a0), "r"(a1), "r"(a2), "r"(a3), "l"(desc), "r"(sc));
}
template <> __device__ __forceinline__ void wgmma_rs<32, 1>(float* d, uint32_t a0, uint32_t a1, uint32_t a2, uint32_t a3, uint64_t desc, int sc) {
  asm volatile("{\n.reg .pred p;\nsetp.ne.b32 p, %21, 0;\n"
    "wgmma.mma_async.sync.aligned.m64n32k16.f32.bf16.bf16 {%0,%1,%2,%3,%4,%5,%6,%7,%8,%9,%10,%11,%12,%13,%14,%15}, {%16,%17,%18,%19}, %20, p, 1, 1, 1;\n}"
    : "+f"(d[0]), "+f"(d[1]), "+f"(d[2]), "+f"(d[3]), "+f"(d[4]), "+f"(d[5]), "+f"(d[6]), "+f"(d[7]), "+f"(d[8]), "+f"(d[9]), "+f"(d[10]), "+f"(d[11]), "+f"(d[12]), "+f"(d[13]), "+f"(d[14]), "+f"(d[15]) : "r"(a0), "r"(a1), "r"(a2), "r"(a3), "l"(desc), "r"(sc));
}
template <> __device__ __forceinline__ void wgmma_rs<16, 1>(float* d, uint32_t a0, uint32_t a1, uint32_t a2, uint32_t a3, uint64_t desc, int sc) {
  asm volatile("{\n.reg .pred p;\nsetp.ne.b32 p, %13, 0;\n"
    "wgmma.mma_async.sync.aligned.m64n16k16.f32.bf16.bf16 {%0,%1,%2,%3,%4,%5,%6,%7}, {%8,%9,%10,%11}, %12, p, 1, 1, 1;\n}"
    : "+f"(d[0]), "+f"(d[1]), "+f"(d[2]), "+f"(d[3]), "+f"(d[4]), "+f"(d[5]), "+f"(d[6]), "+f"(d[7]) : "r"(a0), "r"(a1), "r"(a2), "r"(a3), "l"(desc), "r"(sc));
}

__device__ __forceinline__ uint32_t pack_bf16(float lo, float hi) {
  uint32_t r; asm("cvt.rn.bf16x2.f32 %0, %1, %2;" : "=r"(r) : "f"(hi), "f"(lo)); return r;
}
__device__ __forceinline__ float bf_lo(uint32_t v) { return __uint_as_float(v << 16); }
__device__ __forceinline__ float bf_hi(uint32_t v) { return __uint_as_float(v & 0xffff0000u); }
__device__ __forceinline__ float bf_round(float x) { return bf_lo(pack_bf16(x, 0.f)); }
__device__ __forceinline__ uint32_t hmul2(uint32_t a, uint32_t b) { uint32_t r; asm("mul.rn.bf16x2 %0, %1, %2;" : "=r"(r) : "r"(a), "r"(b)); return r; }
__device__ __forceinline__ uint32_t hadd2(uint32_t a, uint32_t b) { uint32_t r; asm("add.rn.bf16x2 %0, %1, %2;" : "=r"(r) : "r"(a), "r"(b)); return r; }
__device__ __forceinline__ uint32_t hsub2(uint32_t a, uint32_t b) { uint32_t r; asm("sub.rn.bf16x2 %0, %1, %2;" : "=r"(r) : "r"(a), "r"(b)); return r; }
__device__ __forceinline__ uint32_t hfma2(uint32_t a, uint32_t b, uint32_t c) { uint32_t r; asm("fma.rn.bf16x2 %0, %1, %2, %3;" : "=r"(r) : "r"(a), "r"(b), "r"(c)); return r; }

__device__ __forceinline__ void sts16(uint32_t a, uint32_t v) { asm volatile("st.shared.b16 [%0], %1;" ::"r"(a), "h"((unsigned short)v) : "memory"); }
__device__ __forceinline__ void sts32(uint32_t a, uint32_t v) { asm volatile("st.shared.b32 [%0], %1;" ::"r"(a), "r"(v) : "memory"); }
__device__ __forceinline__ void sts64(uint32_t a, uint32_t x, uint32_t y) { asm volatile("st.shared.v2.b32 [%0], {%1,%2};" ::"r"(a), "r"(x), "r"(y) : "memory"); }
__device__ __forceinline__ void sts128(uint32_t a, uint32_t x, uint32_t y, uint32_t z, uint32_t w) {
  asm volatile("st.shared.v4.b32 [%0], {%1,%2,%3,%4};" ::"r"(a), "r"(x), "r"(y), "r"(z), "r"(w) : "memory");
}
__device__ __forceinline__ uint32_t lds32(uint32_t a) { uint32_t v; asm volatile("ld.shared.b32 %0, [%1];" : "=r"(v) : "r"(a) : "memory"); return v; }
__device__ __forceinline__ uint2 lds64(uint32_t a) { uint2 v; asm volatile("ld.shared.v2.b32 {%0,%1}, [%2];" : "=r"(v.x), "=r"(v.y) : "r"(a) : "memory"); return v; }
__device__ __forceinline__ uint4 lds128(uint32_t a) {
  uint4 v; asm volatile("ld.shared.v4.b32 {%0,%1,%2,%3}, [%4];" : "=r"(v.x), "=r"(v.y), "=r"(v.z), "=r"(v.w) : "r"(a) : "memory"); return v;
}
__device__ __forceinline__ uint4 ldg128(const void* a) {
  uint4 v; asm volatile("ld.global.nc.v4.b32 {%0,%1,%2,%3}, [%4];" : "=r"(v.x), "=r"(v.y), "=r"(v.z), "=r"(v.w) : "l"(a) : "memory"); return v;
}
__device__ __forceinline__ uint2 ldg64(const void* a) {
  uint2 v; asm volatile("ld.global.nc.v2.b32 {%0,%1}, [%2];" : "=r"(v.x), "=r"(v.y) : "l"(a) : "memory"); return v;
}
__device__ __forceinline__ void ldsm4(uint32_t a, uint32_t& r0, uint32_t& r1, uint32_t& r2, uint32_t& r3) {
  asm volatile("ldmatrix.sync.aligned.m8n8.x4.shared.b16 {%0,%1,%2,%3}, [%4];" : "=r"(r0), "=r"(r1), "=r"(r2), "=r"(r3) : "r"(a) : "memory");
}
__device__ __forceinline__ void ldsm4t(uint32_t a, uint32_t& r0, uint32_t& r1, uint32_t& r2, uint32_t& r3) {
  asm volatile("ldmatrix.sync.aligned.m8n8.x4.trans.shared.b16 {%0,%1,%2,%3}, [%4];" : "=r"(r0), "=r"(r1), "=r"(r2), "=r"(r3) : "r"(a) : "memory");
}
__device__ __forceinline__ void stsm4(uint32_t a, uint32_t r0, uint32_t r1, uint32_t r2, uint32_t r3) {
  asm volatile("stmatrix.sync.aligned.m8n8.x4.shared.b16 [%0], {%1,%2,%3,%4};" ::"r"(a), "r"(r0), "r"(r1), "r"(r2), "r"(r3) : "memory");
}
__device__ __forceinline__ void stsm4t(uint32_t a, uint32_t r0, uint32_t r1, uint32_t r2, uint32_t r3) {
  asm volatile("stmatrix.sync.aligned.m8n8.x4.trans.shared.b16 [%0], {%1,%2,%3,%4};" ::"r"(a), "r"(r0), "r"(r1), "r"(r2), "r"(r3) : "memory");
}
__device__ __forceinline__ void mma16816(float* c, uint32_t a0, uint32_t a1, uint32_t a2, uint32_t a3, uint32_t b0, uint32_t b1) {
  asm("mma.sync.aligned.m16n8k16.row.col.f32.bf16.bf16.f32 {%0,%1,%2,%3}, {%4,%5,%6,%7}, {%8,%9}, {%0,%1,%2,%3};"
      : "+f"(c[0]), "+f"(c[1]), "+f"(c[2]), "+f"(c[3]) : "r"(a0), "r"(a1), "r"(a2), "r"(a3), "r"(b0), "r"(b1));
}
__device__ __forceinline__ void bar_sync(int id, int n) { asm volatile("bar.sync %0, %1;" ::"r"(id), "r"(n) : "memory"); }
__device__ __forceinline__ void bar_arrive(int id, int n) { asm volatile("bar.arrive %0, %1;" ::"r"(id), "r"(n) : "memory"); }
__device__ __forceinline__ void wg_fence() { asm volatile("wgmma.fence.sync.aligned;" ::: "memory"); }
__device__ __forceinline__ void wg_commit() { asm volatile("wgmma.commit_group.sync.aligned;" ::: "memory"); }
__device__ __forceinline__ void wg_wait0() { asm volatile("wgmma.wait_group.sync.aligned 0;" ::: "memory"); }
__device__ __forceinline__ void fence_async() { asm volatile("fence.proxy.async.shared::cta;" ::: "memory"); }
__device__ __forceinline__ uint32_t opq(uint32_t x, uint32_t z) { uint32_t r; asm volatile("xor.b32 %0, %1, %2;" : "=r"(r) : "r"(x), "r"(z)); return r; }
__device__ __forceinline__ uint64_t mkdesc(uint32_t addr, uint32_t lbo, uint32_t sbo) {
  return (uint64_t)((addr & 0x3FFFF) >> 4) | ((uint64_t)(lbo >> 4) << 16) | ((uint64_t)(sbo >> 4) << 32);
}
__device__ __forceinline__ uint32_t mapa(uint32_t a, uint32_t rank) {
  uint32_t r; asm("mapa.shared::cluster.u32 %0, %1, %2;" : "=r"(r) : "r"(a), "r"(rank)); return r;
}
__device__ __forceinline__ void mbar_init_expect(uint32_t bar, uint32_t bytes) {
  asm volatile("mbarrier.init.shared::cta.b64 [%0], 1;" ::"r"(bar) : "memory");
  asm volatile("mbarrier.arrive.expect_tx.shared::cta.b64 _, [%0], %1;" ::"r"(bar), "r"(bytes) : "memory");
}
__device__ __forceinline__ void mbar_wait(uint32_t bar) {
#pragma unroll 1
  for (int it = 0; it < (1 << 22); it++) {
    uint32_t ok;
    asm volatile("{\n.reg .pred p;\nmbarrier.try_wait.parity.acquire.cluster.shared::cta.b64 p, [%1], 0;\nselp.u32 %0, 1, 0, p;\n}"
                 : "=r"(ok) : "r"(bar) : "memory");
    if (ok) return;
  }
  __trap();
}
__device__ __forceinline__ void st_async4(uint32_t a, uint32_t bar, uint32_t x, uint32_t y, uint32_t z, uint32_t w) {
  asm volatile("st.async.weak.shared::cluster.mbarrier::complete_tx::bytes.v4.b32 [%0], {%2,%3,%4,%5}, [%1];"
               ::"r"(a), "r"(bar), "r"(x), "r"(y), "r"(z), "r"(w) : "memory");
}

struct cf { float re, im; };
__device__ __forceinline__ cf cmul(cf a, cf b) { return {fmaf(a.re, b.re, -a.im * b.im), fmaf(a.re, b.im, a.im * b.re)}; }
__device__ __forceinline__ cf csq(cf a) { return {fmaf(a.re, a.re, -a.im * a.im), (a.re + a.re) * a.im}; }
__device__ __forceinline__ cf cexp_p(float xl, float y, float p) {
  float mag; asm("ex2.approx.ftz.f32 %0, %1;" : "=f"(mag) : "f"(xl * p));
  const float th = y * p;
  const float k = rintf(th * 0.15915494309189535f);
  float r = fmaf(k, -6.2831854820251465f, th);
  r = fmaf(k, 1.7484555314695172e-07f, r);
  return {mag * __cosf(r), mag * __sinf(r)};
}
__device__ __forceinline__ uint32_t ysw(int c) { return (uint32_t)(c ^ ((c >> 3) & 3)) * 16u; }

#define CMUL2(OR, OI, xr, xi, yr, yi, nyi) do { OR = hfma2(xr, yr, hmul2(xi, nyi)); OI = hfma2(xr, yi, hmul2(xi, yr)); } while (0)

__device__ __forceinline__ uint32_t gate_slow(const __nv_bfloat16* u, const __nv_bfloat16* gw, int row) {
  float s = 0.f;
  const uint32_t* xr = (const uint32_t*)(u + (size_t)row * D);
  const uint32_t* wr = (const uint32_t*)gw;
#pragma unroll 1
  for (int j = 0; j < D / 2; j++) { const uint32_t pr = hmul2(xr[j], wr[j]); s += bf_lo(pr); s += bf_hi(pr); }
  s = bf_round(s);
  return pack_bf16(1.f / (1.f + expf(-s)), 0.f);
}

__device__ __forceinline__ uint2 gate_ld(int x) {
  uint2 gv;
  asm volatile("ld.relaxed.gpu.global.v2.u32 {%0,%1}, [%2];" : "=r"(gv.x), "=r"(gv.y) : "l"(g_gate + x * 2) : "memory");
  return gv;
}
__device__ __noinline__ uint32_t gate_poll(const __nv_bfloat16* u, const __nv_bfloat16* gw, int x, uint32_t tag) {
  uint2 gv;
#pragma unroll 1
  for (int spins = 0; spins < (1 << 16); spins++) {
    gv = gate_ld(x);
    if ((gv.x >> 16) == tag && (gv.y >> 16) == tag) return __byte_perm(gv.x, gv.y, 0x5410);
  }
  return __byte_perm(gate_slow(u, gw, x * 2), gate_slow(u, gw, x * 2 + 1), 0x5410);
}
__device__ __forceinline__ uint32_t gate_fin(const Params& p, uint2 gv, int x, uint32_t tag) {
  if ((gv.x >> 16) == tag && (gv.y >> 16) == tag) return __byte_perm(gv.x, gv.y, 0x5410);
  return gate_poll(p.u, p.gw, x, tag);
}

__device__ __forceinline__ void ld4ch(uint32_t* v, uint32_t addr) {
#pragma unroll
  for (int k = 0; k < 4; k++) v[k] = lds32(addr + k * CH_BYTES);
}
__device__ __forceinline__ void skip_terms(uint32_t* ua, uint32_t* ub, uint32_t sb, int x, uint2 dA, uint2 dB) {
  const int c = x >> 2;
  uint32_t uu[4];
  ld4ch(uu, sb + CH_OFF + (x & 3) * 4 + U_OFF + (c & 3) * U_CS + (63 - (c >> 2)) * 16);
#pragma unroll
  for (int k = 0; k < 4; k++) {
    ua[k] = hmul2(uu[k], __byte_perm((k & 2) ? dA.y : dA.x, 0, (k & 1) ? 0x3232 : 0x1010));
    ub[k] = hmul2(uu[k], __byte_perm((k & 2) ? dB.y : dB.x, 0, (k & 1) ? 0x3232 : 0x1010));
  }
}
__device__ __forceinline__ uint4 mix(const uint32_t* a, const uint32_t* b, const uint32_t* ua, const uint32_t* ub, uint32_t g2) {
  const uint32_t h2 = hsub2(0x3f803f80u, g2);
  uint32_t o[4];
#pragma unroll
  for (int k = 0; k < 4; k++) o[k] = hadd2(hmul2(g2, hadd2(a[k], ua[k])), hmul2(h2, hadd2(b[k], ub[k])));
  return make_uint4(__byte_perm(o[0], o[1], 0x5410), __byte_perm(o[2], o[3], 0x5410), __byte_perm(o[0], o[1], 0x7632), __byte_perm(o[2], o[3], 0x7632));
}
__device__ __forceinline__ void send_box(uint32_t sb, int slot, int wtid, uint32_t rank, uint4 r) {
  st_async4(mapa(sb + XIN_OFF + slot * 2048 + wtid * 16, rank ^ 1), mapa(sb + B_X + slot * 8, rank ^ 1), r.x, r.y, r.z, r.w);
}
__device__ __forceinline__ void merge_box(uint32_t sb, const CUtensorMap* tm_out, int slot, int wtid, uint32_t rank, int oc0, uint4 r, int barid) {
  const uint32_t st = sb + RAW_OFF + slot * 4096 + wtid * 16;
  sts64(st + rank * 8, r.x, r.y); sts64(st + 2048 + rank * 8, r.z, r.w);
  mbar_wait(sb + B_X + slot * 8);
  const uint4 q = lds128(sb + XIN_OFF + slot * 2048 + wtid * 16);
  sts64(st + (rank ^ 1) * 8, q.x, q.y); sts64(st + 2048 + (rank ^ 1) * 8, q.z, q.w);
  fence_async();
  bar_sync(barid, 128);
  if (wtid == 0) {
    asm volatile("cp.async.bulk.tensor.3d.global.shared::cta.bulk_group [%0, {%2, %3, %4}], [%1];"
                 ::"l"(tm_out), "r"(sb + RAW_OFF + slot * 4096), "r"(oc0), "r"((2 * slot + (int)rank) * 128), "r"(0) : "memory");
    asm volatile("cp.async.bulk.commit_group;" ::: "memory");
  }
}

__device__ __forceinline__ uint32_t band2(int e, int lo, int hi) {
  uint32_t r = ((uint32_t)(e - lo) <= (uint32_t)(hi - lo) ? 0x3f80u : 0u) | ((uint32_t)(e - 1 - lo) <= (uint32_t)(hi - lo) ? 0x3f800000u : 0u);
  asm volatile("" : "+r"(r));
  return r;
}

__device__ __forceinline__ void conv_dense(uint32_t cb, uint32_t zz) {
  const int lane = threadIdx.x & 31, wq = (threadIdx.x >> 5) & 3, br = wq >> 1, hf = wq & 1, g = lane >> 2, t = lane & 3;
  const uint32_t rb = cb + R_OFF + br * R_BR;
  const int eo = 16 * hf + g - 2 * t;
  float dacc[32];
  {
      {
        const int x0 = RD_X0 - (eo + 536);
        const uint32_t fa = rb + ((g & 1) ? 2 * x0 : RD_CS + 2 * x0 + 2);
        const uint64_t ub = mkdesc(cb + U_OFF, U_CS, 128);
        uint32_t A[2][4][4];
        float e56[28], e48[24];
        auto loadA = [&](int j) {
#pragma unroll
          for (int k = 0; k < 4; k++) {
            const int s = 34 - 4 * j - k;
            if (s >= 0) {
              if (k == 0 && j == 0) A[0][0][2] = lds32(fa + (2 * s + 2) * 16);
              A[j & 1][k][0] = lds32(fa + (2 * s + 1) * 16);
              A[j & 1][k][1] = lds32(fa + (2 * s) * 16);
            }
          }
#pragma unroll
          for (int k = 0; k < 4; k++) {
            if (34 - 4 * j - k >= 0) {
              A[j & 1][k][3] = CPY(A[j & 1][k][0]);
              if (k) A[j & 1][k][2] = CPY(A[j & 1][k - 1][1]);
              else if (j) A[j & 1][0][2] = CPY(A[(j - 1) & 1][3][1]);
            }
          }
        };
        loadA(0);
#pragma unroll
        for (int j = 0; j < 9; j++) {
          if (j == 4) {
#pragma unroll
            for (int i = 0; i < 28; i++) e56[i] = FCPY(dacc[i]);
          }
          if (j == 8) {
#pragma unroll
            for (int i = 0; i < 24; i++) e48[i] = FCPY(e56[i]);
          }
          wg_fence();
#pragma unroll
          for (int k = 0; k < 4; k++) {
            const int s = 34 - 4 * j - k;
            if (s >= 0) {
              const int o = 2 * s - 66 + 128;
              const int cc = o & 3, rs = (o >> 2) - 32;
              const int n0 = ((-rs) >> 3) * 8;
              const uint64_t desc = ub + (uint64_t)((cc * U_CS - rs * 16) >> 4);
              const uint32_t* a = A[j & 1][k];
              if (n0 == 0) wgmma_rs<64, 0>(dacc, a[0], a[1], a[2], a[3], desc, s != 34);
              else if (n0 == 8) wgmma_rs<56, 0>(FIXB ? e56 : dacc, a[0], a[1], a[2], a[3], desc, 1);
              else wgmma_rs<48, 0>(FIXB ? e48 : dacc, a[0], a[1], a[2], a[3], desc, 1);
            }
          }
          wg_commit();
          if (j < 8) loadA(j + 1);
          wg_wait0();
        }
#pragma unroll
        for (int i = 0; i < 28; i++) dacc[i] = i < 24 ? e48[i] : e56[i];
      }
      const uint32_t yb = cb + Y0_OFF + br * 4096;
#pragma unroll
      for (int i = 0; i < 8; i += 2) {
        const int mi = lane >> 3;
        const int cidx = 4 * (63 - 8 * (i + (mi >> 1)) - (lane & 7)) + 2 * hf + (mi & 1);
        stsm4t(yb + ysw(cidx), pack_bf16(dacc[4 * i], dacc[4 * i + 1]), pack_bf16(dacc[4 * i + 2], dacc[4 * i + 3]),
               pack_bf16(dacc[4 * i + 4], dacc[4 * i + 5]), pack_bf16(dacc[4 * i + 6], dacc[4 * i + 7]));
      }
      bar_arrive(6, 640);
      STAMP(8);
  }
}

__device__ __forceinline__ void conv_far(uint32_t sb, uint32_t cb, uint32_t zz) {
  const int lane = threadIdx.x & 31, wq = (threadIdx.x >> 5) & 3, br = wq >> 1, hf = wq & 1, g = lane >> 2, t = lane & 3;
  const uint32_t rb = cb + R_OFF + br * R_BR;
  const int eo = 16 * hf + g - 2 * t;
  float dacc[24], e40[20], e32[16], h32[16], h16[8];
  const int x1 = 159 - (eo + 136);
  const uint32_t fs = rb + ((g & 1) ? 2 * x1 : RS_CS + 2 * x1 + 2);
  {
    uint32_t A[2][4][4];
    auto loadA = [&](int buf, uint32_t oe, uint32_t oo, int i0) {
#pragma unroll
      for (int a = 0; a < 2; a++) {
        const uint32_t base = fs + (a ? oo : oe) + i0 * 16;
        uint32_t* k0 = A[buf][2 * a];
        uint32_t* k1 = A[buf][2 * a + 1];
        k0[1] = lds32(base); k0[0] = lds32(base + 16); k0[2] = lds32(base + 32); k1[0] = lds32(base + 48); k1[2] = lds32(base + 64);
      }
#pragma unroll
      for (int a = 0; a < 2; a++) {
        uint32_t* k0 = A[buf][2 * a];
        uint32_t* k1 = A[buf][2 * a + 1];
        k0[3] = CPY(k0[0]); k1[1] = CPY(k0[2]); k1[3] = CPY(k1[0]);
      }
    };
    const uint64_t d5 = mkdesc(cb + W5_OFF, 144, 576), d3 = mkdesc(cb + W3_OFF, 144, 576);
    loadA(0, R_E2, R_O2, 8);
#pragma unroll
    for (int m = 2; m <= 4; m++) {
      if (m == 3) {
#pragma unroll
        for (int i = 0; i < 20; i++) e40[i] = FCPY(dacc[i]);
      }
      if (m == 4) {
#pragma unroll
        for (int i = 0; i < 16; i++) e32[i] = FCPY(e40[i]);
      }
      wg_fence();
#pragma unroll
      for (int k = 0; k < 4; k++) {
        const uint32_t* a = A[m & 1][k];
        const uint64_t desc = ((k >> 1) ? d3 : d5) + (k & 1) * 18 + (m - 2) * 36;
        if (m == 2) wgmma_rs<48, 1>(dacc, a[0], a[1], a[2], a[3], desc, k);
        else if (m == 3) wgmma_rs<40, 1>(e40, a[0], a[1], a[2], a[3], desc, 1);
        else wgmma_rs<32, 1>(e32, a[0], a[1], a[2], a[3], desc, 1);
      }
      wg_commit();
      if (m < 4) loadA((m + 1) & 1, R_E2, R_O2, 4 * (3 - m));
      else loadA(1, R_E3, R_O3, 8);
      wg_wait0();
    }
#pragma unroll
    for (int i = 0; i < 20; i++) dacc[i] = i < 16 ? e32[i] : e40[i];
    {
      const uint32_t yb = cb + Y2_OFF + br * 3072;
#pragma unroll
      for (int i = 0; i < 6; i += 2) {
        const int mi = lane >> 3;
        const int cidx = 32 * (5 - i - (mi >> 1)) + 16 * hf + 8 * (mi & 1) + (lane & 7);
        stsm4(yb + ysw(cidx), pack_bf16(dacc[4 * i], dacc[4 * i + 1]), pack_bf16(dacc[4 * i + 2], dacc[4 * i + 3]),
              pack_bf16(dacc[4 * i + 4], dacc[4 * i + 5]), pack_bf16(dacc[4 * i + 6], dacc[4 * i + 7]));
      }
    }
    __syncwarp();
    if (lane == 0) asm volatile("mbarrier.arrive.shared::cta.b64 _, [%0];" ::"r"(sb + B_Y2) : "memory");
    STAMP(9);
    const uint64_t d9 = mkdesc(cb + W9_OFF, 144, 576), d7 = mkdesc(cb + W7_OFF, 144, 576);
#pragma unroll
    for (int m = 2; m <= 3; m++) {
      if (m == 3) {
#pragma unroll
        for (int i = 0; i < 8; i++) h16[i] = FCPY(h32[i]);
      }
      wg_fence();
#pragma unroll
      for (int k = 0; k < 4; k++) {
        const uint32_t* a = A[(m + 1) & 1][k];
        const uint64_t desc = ((k >> 1) ? d7 : d9) + (k & 1) * 18 + (m - 2) * 72;
        if (m == 2) wgmma_rs<32, 1>(h32, a[0], a[1], a[2], a[3], desc, k);
        else wgmma_rs<16, 1>(h16, a[0], a[1], a[2], a[3], desc, 1);
      }
      wg_commit();
      if (m == 2) loadA(0, R_E3, R_O3, 4);
      wg_wait0();
    }
#pragma unroll
    for (int i = 0; i < 16; i++) dacc[i] = i < 8 ? h16[i] : h32[i];
    const uint32_t yb = cb + Y3_OFF + br * 2048;
#pragma unroll
    for (int i = 0; i < 4; i += 2) {
      const int mi = lane >> 3;
      const int cidx = 64 * (1 - (i >> 1)) + 2 * (16 * hf + 8 * (mi & 1) + (lane & 7)) + (mi >> 1);
      stsm4(yb + ysw(cidx), pack_bf16(dacc[4 * i], dacc[4 * i + 1]), pack_bf16(dacc[4 * i + 2], dacc[4 * i + 3]),
            pack_bf16(dacc[4 * i + 4], dacc[4 * i + 5]), pack_bf16(dacc[4 * i + 6], dacc[4 * i + 7]));
    }
  }
}

__global__ void __cluster_dims__(2, 1, 1) __launch_bounds__(640, 1)
ssm_kernel(const Params p, const __grid_constant__ CUtensorMap tm_in, const __grid_constant__ CUtensorMap tm_out) {
  extern __shared__ __align__(1024) unsigned char smem_raw[];
  const uint32_t sb = (uint32_t)__cvta_generic_to_shared(smem_raw);
  const int tid = threadIdx.x, lane = tid & 31;
  const int warp = __shfl_sync(0xffffffffu, tid >> 5, 0);
  const int ch = warp >> 2, wq = warp & 3, br = wq >> 1, hf = wq & 1;
  const int g = lane >> 2, t = lane & 3;
  const int d = blockIdx.x * 4 + ch;
  const uint32_t rank = blockIdx.x & 1;
  const uint32_t cb = sb + CH_OFF + ch * CH_BYTES;
  const int wtid = tid & 127;
  const int oc0 = (int)(blockIdx.x >> 1) * 8;
  STAMP(0); GT(0);

  if (warp >= 16) {
    if (wtid == 0) {
      mbar_init_expect(sb + B_RAW, 32768);
#pragma unroll
      for (int i = 0; i < 4; i++) mbar_init_expect(sb + B_X + 8 * i, 2048);
      asm volatile("mbarrier.init.shared::cta.b64 [%0], 128;" ::"r"(sb + B_U) : "memory");
      asm volatile("mbarrier.init.shared::cta.b64 [%0], 128;" ::"r"(sb + B_W) : "memory");
      asm volatile("mbarrier.init.shared::cta.b64 [%0], 16;" ::"r"(sb + B_Y2) : "memory");
      asm volatile("mbarrier.init.shared::cta.b64 [%0], 16;" ::"r"(sb + B_Y3) : "memory");
      asm volatile("fence.mbarrier_init.release.cluster;" ::: "memory");
      asm volatile("fence.proxy.async.shared::cta;" ::: "memory");
    }
    __syncwarp();
    asm volatile("barrier.cluster.arrive.relaxed.aligned;" ::: "memory");
    unsigned int epoch;
    asm volatile("ld.relaxed.gpu.global.u32 %0, [%1];" : "=r"(epoch) : "l"(&g_epoch) : "memory");
    asm volatile("barrier.cluster.wait.aligned;" ::: "memory");
    if (wtid == 0) {
      asm volatile("cp.async.bulk.tensor.5d.shared::cluster.global.mbarrier::complete_tx::bytes.multicast::cluster [%0], [%1, {%3, %4, %4, %4, %5}], [%2], %6;"
                   ::"r"(sb + RAW_OFF + rank * 16384), "l"(&tm_in), "r"(sb + B_RAW), "r"(oc0), "r"(0), "r"((int)rank * 32), "h"((unsigned short)3) : "memory");
    }
    sts128(sb + CH_OFF + wq * CH_BYTES + U_OFF + (lane >> 3) * U_CS + (64 + (lane & 7)) * 16, 0, 0, 0, 0);
    const uint4 gw0 = ldg128(p.gw + lane * 8), gw1 = ldg128(p.gw + 256 + lane * 8);
      const int grow = blockIdx.x * 16 + wq * 4;
      uint4 gx[4][2];
#pragma unroll
      for (int i = 0; i < 4; i++) {
        gx[i][0] = ldg128(p.u + (size_t)(grow + i) * D + lane * 8);
        gx[i][1] = ldg128(p.u + (size_t)(grow + i) * D + 256 + lane * 8);
      }
    uint32_t BA[3][4], BC[3][4];
    {
      const int l1 = br ? 3 : 6, h1 = br ? 5 : 10;
#pragma unroll
      for (int i = 0; i < 3; i++) {
        const int e = 16 * hf + g - 2 * t + 16 - 16 * i;
        BA[i][0] = band2(e, l1, h1); BA[i][1] = band2(e + 8, l1, h1); BA[i][2] = band2(e - 8, l1, h1); BA[i][3] = BA[i][0];
        BC[i][0] = band2(e, 3, 4); BC[i][1] = band2(e + 8, 3, 4); BC[i][2] = band2(e - 8, 3, 4); BC[i][3] = BC[i][0];
      }
    }
    const uint32_t tag = (epoch + 1) & 0xffffu;
    if (wtid == 0) sts32(sb + TAG_OFF, tag);
    {
      const uint32_t ws[8] = {gw0.x, gw0.y, gw0.z, gw0.w, gw1.x, gw1.y, gw1.z, gw1.w};
      float sm[4];
#pragma unroll
      for (int i = 0; i < 4; i++) {
        const uint32_t xs[8] = {gx[i][0].x, gx[i][0].y, gx[i][0].z, gx[i][0].w, gx[i][1].x, gx[i][1].y, gx[i][1].z, gx[i][1].w};
        float s = 0.f;
#pragma unroll
        for (int j = 0; j < 8; j++) { const uint32_t pr = hmul2(xs[j], ws[j]); s += bf_lo(pr); s += bf_hi(pr); }
        sm[i] = s;
      }
      {
        const bool b0 = lane & 1, b1 = lane & 2;
        float u0 = b0 ? sm[1] : sm[0], v0 = b0 ? sm[0] : sm[1], u1 = b0 ? sm[3] : sm[2], v1 = b0 ? sm[2] : sm[3];
        u0 += __shfl_xor_sync(0xffffffffu, v0, 1); u1 += __shfl_xor_sync(0xffffffffu, v1, 1);
        float s = b1 ? u1 : u0; const float v = b1 ? u0 : u1;
        s += __shfl_xor_sync(0xffffffffu, v, 2);
#pragma unroll
        for (int o = 4; o < 32; o <<= 1) s += __shfl_xor_sync(0xffffffffu, s, o);
        s = bf_round(s);
        const float gv = 1.f / (1.f + expf(-s));
        const uint32_t w = (tag << 16) | (pack_bf16(gv, 0.f) & 0xffffu);
        if (lane < 4) asm volatile("st.relaxed.gpu.global.u32 [%0], %1;" ::"l"(&g_gate[grow + lane]), "r"(w) : "memory");
      }
    }
    STAMP(2);
    STAMP(3);
    mbar_wait(sb + B_RAW);
    STAMP(4);
    {
      const uint32_t dst = sb + CH_OFF + (g & 3) * CH_BYTES + U_OFF + t * U_CS + (63 - wq * 16) * 16;
#pragma unroll
      for (int h = 0; h < 2; h++) {
        uint32_t r[8][4];
#pragma unroll
        for (int i = 0; i < 8; i++) ldsm4t(sb + RAW_OFF + (wq * 16 + h * 8 + i) * 512 + lane * 16, r[i][0], r[i][1], r[i][2], r[i][3]);
        if ((uint32_t)(g >> 2) == rank) {
#pragma unroll
          for (int i = 0; i < 8; i++) sts128(dst - (h * 8 + i) * 16, r[i][0], r[i][1], r[i][2], r[i][3]);
        }
      }
    }
    fence_async();
    asm volatile("mbarrier.arrive.shared::cta.b64 _, [%0];" ::"r"(sb + B_U) : "memory");
    bar_sync(5, 128);
    STAMP(5);
    {
      const int mrow = lane & 7, mi = lane >> 3;
      const uint64_t ub0 = mkdesc(sb + CH_OFF + U_OFF, U_CS, 128);
      {
        float w1[24], w3[16];
#pragma unroll
        for (int i = 0; i < 24; i++) w1[i] = 0.f;
#pragma unroll
        for (int i = 0; i < 16; i++) w3[i] = 0.f;
        uint32_t wa[3], sa[2];
#pragma unroll
        for (int i = 0; i < 3; i++) {
          const int c = 4 * (47 - 8 * (2 * i + (mi >> 1)) - mrow) + 2 * hf + (mi & 1);
          wa[i] = sb + CH_OFF + (br ? W3_OFF : W5_OFF) + (5 - (c >> 5)) * 576 + ((c & 31) >> 3) * 144 + (c & 7) * 16;
          if (i) sa[i - 1] = sb + CH_OFF + S2_OFF + (c + (c >> 3)) * 16;
        }
#pragma unroll 1
        for (int k = 0; k < 4; k++) {
          wg_fence();
#pragma unroll
          for (int i = 0; i < 3; i++)
            wgmma_rs<48, 0>(w1, BA[i][0], BA[i][1], BA[i][2], BA[i][3],
                            ub0 + (uint64_t)((k * CH_BYTES + ((2 * i + 2) & 3) * U_CS + (16 + (i == 0)) * 16) >> 4), i);
#pragma unroll
          for (int i = 0; i < 3; i++)
            wgmma_rs<32, 0>(w3, BC[i][0], BC[i][1], BC[i][2], BC[i][3],
                            ub0 + (uint64_t)((k * CH_BYTES + ((2 * i + 2) & 3) * U_CS + (32 + (i == 0)) * 16) >> 4), i);
          wg_commit();
          wg_wait0();
#pragma unroll
          for (int i = 0; i < 3; i++)
            stsm4t(wa[i] + k * CH_BYTES, pack_bf16(w1[8 * i], w1[8 * i + 1]), pack_bf16(w1[8 * i + 2], w1[8 * i + 3]),
                   pack_bf16(w1[8 * i + 4], w1[8 * i + 5]), pack_bf16(w1[8 * i + 6], w1[8 * i + 7]));
          if (br == 0) {
#pragma unroll
            for (int i = 0; i < 2; i++)
              stsm4t(sa[i] + k * CH_BYTES, pack_bf16(w3[8 * i], w3[8 * i + 1]), pack_bf16(w3[8 * i + 2], w3[8 * i + 3]),
                     pack_bf16(w3[8 * i + 4], w3[8 * i + 5]), pack_bf16(w3[8 * i + 6], w3[8 * i + 7]));
          }
        }
      }
      {
        uint32_t BB[4][4];
        const int l2 = br ? 5 : 12, h2 = br ? 11 : 20;
#pragma unroll
        for (int i = 0; i < 4; i++) {
          const int e = 16 * hf + g - 2 * t + 32 - 16 * i;
          BB[i][0] = band2(e, l2, h2); BB[i][1] = band2(e + 8, l2, h2); BB[i][2] = band2(e - 8, l2, h2); BB[i][3] = BB[i][0];
        }
        float w2[2][16];
#pragma unroll
        for (int i = 0; i < 16; i++) { w2[0][i] = 0.f; w2[1][i] = 0.f; }
        uint32_t wa[2];
#pragma unroll
        for (int i = 0; i < 2; i++) {
          const int c = 4 * (31 - 8 * (2 * i + (mi >> 1)) - mrow) + 2 * hf + (mi & 1), pp = c >> 1;
          wa[i] = sb + CH_OFF + (br ? W7_OFF : W9_OFF) + (1 - (pp >> 5)) * 1152 + (c & 1) * 576 + ((pp & 31) >> 3) * 144 + (pp & 7) * 16;
        }
#pragma unroll 1
        for (int kp = 0; kp < 2; kp++) {
          wg_fence();
#pragma unroll
          for (int k = 0; k < 2; k++)
#pragma unroll
            for (int i = 0; i < 4; i++)
              wgmma_rs<32, 0>(w2[k], BB[i][0], BB[i][1], BB[i][2], BB[i][3],
                              ub0 + (uint64_t)(((2 * kp + k) * CH_BYTES + ((2 * i) & 3) * U_CS + (32 + (i < 2)) * 16) >> 4), i);
          wg_commit();
          wg_wait0();
#pragma unroll
          for (int k = 0; k < 2; k++)
#pragma unroll
            for (int i = 0; i < 2; i++)
              stsm4t(wa[i] + (2 * kp + k) * CH_BYTES, pack_bf16(w2[k][8 * i], w2[k][8 * i + 1]), pack_bf16(w2[k][8 * i + 2], w2[k][8 * i + 3]),
                     pack_bf16(w2[k][8 * i + 4], w2[k][8 * i + 5]), pack_bf16(w2[k][8 * i + 6], w2[k][8 * i + 7]));
        }
      }
    }
    fence_async();
    asm volatile("mbarrier.arrive.shared::cta.b64 _, [%0];" ::"r"(sb + B_W) : "memory");
    STAMP(7);
    const uint2 dA = ldg64(p.A_D + blockIdx.x * 4), dB = ldg64(p.B_D + blockIdx.x * 4);
    STAMP(8);
    uint32_t gg[4];
    {
      uint2 gl[4];
#pragma unroll
      for (int i = 0; i < 4; i++) gl[i] = gate_ld((i ^ (int)rank ^ 1) * 128 + wtid);
#pragma unroll
      for (int i = 0; i < 4; i++) gg[i] = gate_fin(p, gl[i], (i ^ (int)rank ^ 1) * 128 + wtid, tag);
    }
    {
      uint32_t ua[4][4], ub[4][4], ya[4][4], yb[4][4], yo[4];
#pragma unroll
      for (int i = 0; i < 4; i++) {
        const int x = (i ^ (int)rank ^ 1) * 128 + wtid;
        skip_terms(ua[i], ub[i], sb, x, dA, dB);
        yo[i] = sb + CH_OFF + (x & 3) * 4 + ysw(x >> 2);
      }
      bar_sync(6, 640);
      STAMP(10);
#pragma unroll
      for (int i = 0; i < 4; i++) { ld4ch(ya[i], yo[i] + Y0_OFF); ld4ch(yb[i], yo[i] + Y0_OFF + 4096); }
      send_box(sb, 0, wtid, rank, mix(ya[0], yb[0], ua[0], ub[0], gg[0]));
      merge_box(sb, &tm_out, 0, wtid, rank, oc0, mix(ya[1], yb[1], ua[1], ub[1], gg[1]), 5);
      STAMP(12);
      mbar_wait(sb + B_Y2);
      STAMP(11);
#pragma unroll
      for (int i = 2; i < 4; i++) { ld4ch(ya[i - 2], yo[i] + Y2_OFF - 1024); ld4ch(yb[i - 2], yo[i] + Y2_OFF - 1024 + 3072); }
#pragma unroll
      for (int i = 2; i < 4; i++)
#pragma unroll
        for (int k = 0; k < 4; k++) { ya[i][k] = hadd2(ya[i][k], ya[i - 2][k]); yb[i][k] = hadd2(yb[i][k], yb[i - 2][k]); }
      send_box(sb, 1, wtid, rank, mix(ya[2], yb[2], ua[2], ub[2], gg[2]));
      merge_box(sb, &tm_out, 1, wtid, rank, oc0, mix(ya[3], yb[3], ua[3], ub[3], gg[3]), 5);
      STAMP(13);
    }
    if (wtid == 0) {
      if (atomicAdd(&g_ticket, 1u) == NCTA - 1) { g_ticket = 0; g_epoch = epoch + 1; }
      asm volatile("cp.async.bulk.wait_group.read 0;" ::: "memory");
    }
    STAMP(15);
    return;
  }
  asm volatile("barrier.cluster.arrive.relaxed.aligned;" ::: "memory");

  const int moff = d * NM + hf * 64 + lane * 2;
  const __nv_bfloat16* const* tp = p.t + (br ? 0 : 6);
  const uint32_t q0 = *(const uint32_t*)(tp[0] + moff), q1 = *(const uint32_t*)(tp[1] + moff);
  const uint32_t q2 = *(const uint32_t*)(tp[2] + moff), q3 = *(const uint32_t*)(tp[3] + moff);
  const uint2 ldt4 = *(const uint2*)(tp[4] + blockIdx.x * 4);
  const uint32_t q4 = *(const uint32_t*)(tp[br ? 2 : 5] + moff), q5 = *(const uint32_t*)(tp[br ? 3 : 6] + moff);

  for (int i = wtid & 63; i < R_BR / 16; i += 64) sts128(cb + R_OFF + br * R_BR + i * 16, 0, 0, 0, 0);
  STAMP(1);

  float acc[5][4];
  float k2048 = 0.f;
  const uint32_t scr = cb + Y0_OFF + wq * SCR_BYTES;
  const uint32_t scr2 = sb + XIN_OFF + warp * 640;
  {
    const uint32_t ldt2 = (ch & 2) ? ldt4.y : ldt4.x;
    const float dt = bf_round(expf((ch & 1) ? bf_hi(ldt2) : bf_lo(ldt2)));
#pragma unroll
    for (int i = 0; i < 5; i++) acc[i][0] = acc[i][1] = acc[i][2] = acc[i][3] = 0.f;
    cf cc[2], zz1[2], zz128[2];
#pragma unroll
    for (int r = 0; r < 2; r++) {
      float v0 = r ? bf_hi(q0) : bf_lo(q0), v1 = r ? bf_hi(q1) : bf_lo(q1), v2 = r ? bf_hi(q2) : bf_lo(q2);
      float v3 = r ? bf_hi(q3) : bf_lo(q3), v4 = r ? bf_hi(q4) : bf_lo(q4), v5 = r ? bf_hi(q5) : bf_lo(q5);
      if (br == 0) { cc[r] = cmul(cf{v2, v3}, cf{dt * v4, dt * v5}); }
      else { v0 = -bf_round(expf(v0)); cc[r] = cf{2.f * dt * v2, 2.f * dt * v3}; }
      const float xl = (dt * v0) * 1.4426950408889634f, y = dt * v1;
      zz1[r] = cexp_p(xl, y, 1.f); zz128[r] = cexp_p(xl, y, 128.f);
    }
    STAMP(2);
    const uint32_t tb = scr + lane * 16;
    const uint32_t ta = scr + (lane >> 3) * 512 + (lane & 7) * 16;
    const uint32_t tc = ((lane & 8) ? scr2 : scr + 4096) + (lane >> 4) * 128 + (lane & 7) * 16;
    const uint32_t tm = scr2 + 512 + ((lane >> 3) & 1) * 64 + (lane >> 4) * 16;
#pragma unroll 1
    for (int r = 0; r < 2; r++) {
      const cf c = r ? cc[1] : cc[0], z1 = r ? zz1[1] : zz1[0], z128 = r ? zz128[1] : zz128[0];
      const cf z2 = csq(z1), z4 = csq(z2), z8 = csq(z4);
      const cf z16 = csq(z8), z24 = cmul(z16, z8), z32 = csq(z16), z40 = cmul(z32, z8), z48 = csq(z24), z56 = cmul(z32, z24), z64 = csq(z32);
      const cf z256 = csq(z128), z512 = csq(z256), z1024 = csq(z512), z2048 = csq(z1024);
      {
        float kk = fmaf(c.re, z2048.re, -c.im * z2048.im);
#pragma unroll
        for (int o = 16; o; o >>= 1) kk += __shfl_xor_sync(0xffffffffu, kk, o);
        k2048 += kk;
      }
      __syncwarp();
      {
        uint32_t xr[4] = {pack_bf16(1.f, z8.re), pack_bf16(z16.re, z24.re), pack_bf16(z32.re, z40.re), pack_bf16(z48.re, z56.re)};
        uint32_t xi[4] = {pack_bf16(0.f, -z8.im), pack_bf16(-z16.im, -z24.im), pack_bf16(-z32.im, -z40.im), pack_bf16(-z48.im, -z56.im)};
        sts128(tb + 0 * 512, xr[0], xr[1], xr[2], xr[3]);
        sts128(tb + 2 * 512, xi[0], xi[1], xi[2], xi[3]);
        const uint32_t yr = pack_bf16(z64.re, z64.re), nyi = pack_bf16(z64.im, z64.im), yi = nyi ^ 0x80008000u;
        uint32_t o[4], q[4];
#pragma unroll
        for (int i = 0; i < 4; i++) CMUL2(o[i], q[i], xr[i], xi[i], yr, yi, nyi);
        sts128(tb + 1 * 512, o[0], o[1], o[2], o[3]);
        sts128(tb + 3 * 512, q[0], q[1], q[2], q[3]);
      }
      {
        const cf h1 = cmul(c, z128), h2 = cmul(c, z256), h3 = cmul(h1, z256), h4 = cmul(c, z512), h5 = cmul(h1, z512), h6 = cmul(h2, z512), h7 = cmul(h3, z512);
        const cf e1 = cmul(c, z1), e2 = cmul(c, z2), e3 = cmul(e1, z2), e129 = cmul(h1, z1), e130 = cmul(h1, z2), e131 = cmul(e129, z2);
        const cf e258 = cmul(h2, z2), e386 = cmul(h3, z2);
        const uint32_t pr0 = pack_bf16(c.re, e1.re), pr2 = pack_bf16(h1.re, e129.re), pi0 = pack_bf16(c.im, e1.im), pi2 = pack_bf16(h1.im, e129.im);
        sts128(tb + 4 * 512, pr0, pack_bf16(e2.re, e3.re), pr2, pack_bf16(e130.re, e131.re));
        sts128(tb + 5 * 512, pi0, pack_bf16(e2.im, e3.im), pi2, pack_bf16(e130.im, e131.im));
        uint32_t xr[4] = {pack_bf16(h2.re, e258.re), pack_bf16(h3.re, e386.re), pack_bf16(h4.re, h5.re), pack_bf16(h6.re, h7.re)};
        uint32_t xi[4] = {pack_bf16(h2.im, e258.im), pack_bf16(h3.im, e386.im), pack_bf16(h4.im, h5.im), pack_bf16(h6.im, h7.im)};
        sts128(tb + 6 * 512, xr[0], xr[1], xr[2], xr[3]);
        sts128(tb + 7 * 512, xi[0], xi[1], xi[2], xi[3]);
        xr[1] = __byte_perm(xr[0], xr[1], 0x5410); xi[1] = __byte_perm(xi[0], xi[1], 0x5410);
        xr[0] = __byte_perm(pr0, pr2, 0x5410); xi[0] = __byte_perm(pi0, pi2, 0x5410);
        const uint32_t yr = pack_bf16(z1024.re, z1024.re), yi = pack_bf16(z1024.im, z1024.im), nyi = yi ^ 0x80008000u;
        uint32_t o[4], q[4];
#pragma unroll
        for (int i = 0; i < 4; i++) CMUL2(o[i], q[i], xr[i], xi[i], yr, yi, nyi);
        sts128(tb + 8 * 512, o[0], o[1], o[2], o[3]);
        sts128(scr2 + lane * 16, q[0], q[1], q[2], q[3]);
        const uint32_t m4 = pack_bf16(z4.re, z4.im);
        sts16(scr2 + 512 + lane * 2, m4); sts16(scr2 + 576 + lane * 2, m4 >> 16);
      }
      __syncwarp();
#pragma unroll
      for (int kp = 0; kp < 2; kp++) {
        uint32_t rr[2], ri[2], yr[2], yi[2];
        ldsm4t(tc + kp * 256, rr[0], ri[0], rr[1], ri[1]);
        ldsm4(tm + kp * 32, yr[0], yi[0], yr[1], yi[1]);
#pragma unroll
        for (int k2 = 0; k2 < 2; k2++) {
          const int kk = kp * 2 + k2;
          uint32_t a0, a1, a2, a3, pr, pi, qr, qi, xr, xi;
          ldsm4t(ta + kk * 128, a0, a1, a2, a3);
          ldsm4t(ta + 2048 + kk * 128, pr, pi, qr, qi);
          const uint32_t nyi = yi[k2] ^ 0x80008000u;
          mma16816(acc[0], a0, a1, a2, a3, pr, pi);
          mma16816(acc[2], a0, a1, a2, a3, qr, qi);
          mma16816(acc[4], a0, a1, a2, a3, rr[k2], ri[k2]);
          CMUL2(xr, xi, pr, pi, yr[k2], yi[k2], nyi);
          mma16816(acc[1], a0, a1, a2, a3, xr, xi);
          CMUL2(xr, xi, qr, qi, yr[k2], yi[k2], nyi);
          mma16816(acc[3], a0, a1, a2, a3, xr, xi);
        }
      }
    }
  }
  STAMP(3);
  __syncwarp();
  {
    const uint32_t xs = scr + lane * 16;
#define OTH(i, k) __float_as_uint(hf ? acc[i][k] : acc[i][2 + (k)])
    sts128(xs, OTH(0, 0), OTH(0, 1), OTH(1, 0), OTH(1, 1));
    sts128(xs + 512, OTH(2, 0), OTH(2, 1), OTH(3, 0), OTH(3, 1));
    sts128(xs + 1024, OTH(4, 0), OTH(4, 1), __float_as_uint(k2048), 0);
#undef OTH
  }

  bar_sync(7 + (warp >> 1), 64);
  STAMP(4);
  {
    const uint32_t xo = cb + Y0_OFF + (wq ^ 1) * SCR_BYTES + lane * 16;
    const uint4 o0 = lds128(xo), o1 = lds128(xo + 512), o2 = lds128(xo + 1024);
    const uint32_t rb = cb + R_OFF + br * R_BR;
#define OWN(i, k) (hf ? acc[i][2 + (k)] : acc[i][k])
    const uint32_t vP = pack_bf16(OWN(0, 1) + __uint_as_float(o0.y), OWN(0, 0) + __uint_as_float(o0.x));
    const uint32_t vP4 = pack_bf16(OWN(1, 1) + __uint_as_float(o0.w), OWN(1, 0) + __uint_as_float(o0.z));
    const uint32_t vQ = pack_bf16(OWN(2, 1) + __uint_as_float(o1.y), OWN(2, 0) + __uint_as_float(o1.x));
    const uint32_t vQ4 = pack_bf16(OWN(3, 1) + __uint_as_float(o1.w), OWN(3, 0) + __uint_as_float(o1.z));
    const uint32_t vR = pack_bf16(OWN(4, 1) + __uint_as_float(o2.y), OWN(4, 0) + __uint_as_float(o2.x));
#undef OWN
    const int j = g + 8 * hf;
    {
      const int a = 2 * (t & 1) + 64 * (t & 2) + 8 * j;
      const uint32_t ad = rb + 2 * (RD_X0 - 1 - a);
      const uint32_t a1 = (t & 2) ? ad - 8 : ad, a2 = (t & 2) ? ad : ad - 8;
      const uint32_t w1 = (t & 2) ? vP4 : vP, w2 = (t & 2) ? vP : vP4;
      sts32(a1, w1); sts32(a2, w2);
      sts16(a1 + RD_CS + 2, w1); sts16(a1 + RD_CS + 4, w1 >> 16);
      sts16(a2 + RD_CS + 2, w2); sts16(a2 + RD_CS + 4, w2 >> 16);
    }
    if (t < 2) {
      const int b = 256 + 128 * t + 8 * j;
      const uint32_t ad = rb + 2 * (RD_X0 - 6 - b);
      const uint32_t v22 = __byte_perm(vQ4, 0, 0x3232), v00 = __byte_perm(vQ, 0, 0x3232);
      sts16(ad, vQ4);
      sts64(ad + 2, v22, __byte_perm(vQ4, vQ, 0x5432));
      sts32(ad + 10, v00);
      if (b != 256) { sts16(ad + 14, v00); sts128(ad + RD_CS + 2, vQ4, v22, vQ, v00); }
      else { sts64(ad + RD_CS + 2, vQ4, v22); sts32(ad + RD_CS + 10, vQ); sts16(ad + RD_CS + 14, v00); }
    } else {
      const uint32_t ao = rb + R_O2 + 2 * (159 - (32 * t + j)), ae = ao - (R_O2 - R_E2) + 2;
      sts16(ao, vQ4 >> 16); sts16(ao + RS_CS + 2, vQ4 >> 16); sts16(ao - 32, vQ4); sts16(ao - 32 + RS_CS + 2, vQ4);
      sts16(ae - 32, vQ); sts16(ae - 32 + RS_CS + 2, vQ);
      if (lane != 2 || hf) { sts16(ae, vQ >> 16); sts16(ae + RS_CS + 2, vQ >> 16); }
      else {
        const uint32_t vv = __byte_perm(vQ, 0, 0x3232), ad = rb + 2 * (RD_X0 - 514);
        sts16(ad, vv); sts32(ad + 2, vv); sts16(ad + 6, vv); sts64(ad + RD_CS + 2, vv, vv);
      }
    }
    {
      const uint32_t a = rb + ((g & 1) ? R_O3 : R_E3 + 2) + 2 * (159 - (64 + 16 * t + (j >> 1)));
      const bool p1024 = (lane == 0) && (hf == 0);
      const uint32_t a00 = p1024 ? rb + R_E2 + 2 * (159 - 127) : a;
      sts16(a00, vR >> 16); sts16(a00 + RS_CS + 2, vR >> 16);
      sts16(a - 16, vR); sts16(a - 16 + RS_CS + 2, vR);
      if (p1024) {
        sts32(sb + K1024_OFF + (ch * 2 + br) * 4, __byte_perm(vR, 0, 0x3232));
        const uint32_t kv = pack_bf16(k2048 + __uint_as_float(o2.z), 0.f);
        sts16(rb + R_E3 + 2 * (159 - 127), kv); sts16(rb + R_E3 + 2 * (159 - 127) + RS_CS + 2, kv);
      }
    }
  }
  STAMP(5);
  asm volatile("barrier.cluster.wait.aligned;" ::: "memory");
  bar_sync(7 + (warp >> 1), 64);
  mbar_wait(sb + B_U);
  STAMP(6);

  const uint32_t zz = lds32(cb + R_OFF + br * R_BR);
  conv_dense(cb, zz);
  const uint2 dA = ldg64(p.A_D + blockIdx.x * 4), dB = ldg64(p.B_D + blockIdx.x * 4);
  const uint2 gl = gate_ld((4 + ch) * 128 + wtid);
  mbar_wait(sb + B_W);
  conv_far(sb, cb, zz);
  STAMP(10);
  __syncwarp();
  if (lane == 0) asm volatile("mbarrier.arrive.shared::cta.b64 _, [%0];" ::"r"(sb + B_Y3) : "memory");

  {
    const int x = (4 + ch) * 128 + wtid, c = x >> 2;
    const uint32_t g2 = gate_fin(p, gl, x, lds32(sb + TAG_OFF));
    const uint32_t yo = sb + CH_OFF + (x & 3) * 4 + ysw(c);
    uint32_t ua[4], ub[4], ya[4], yb[4], a2[4], b2[4], a3[4], b3[4], s2[4];
    skip_terms(ua, ub, sb, x, dA, dB);
    ld4ch(s2, sb + CH_OFF + (x & 3) * 4 + S2_OFF + ((c - 128) + ((c - 128) >> 3)) * 16);
    mbar_wait(sb + B_Y2);
    const uint4 k0 = lds128(sb + K1024_OFF), k1 = lds128(sb + K1024_OFF + 16);
    const uint32_t kk[8] = {k0.x, k0.y, k0.z, k0.w, k1.x, k1.y, k1.z, k1.w};
    ld4ch(ya, yo + Y0_OFF); ld4ch(yb, yo + Y0_OFF + 4096);
    ld4ch(a2, yo + Y2_OFF - 1024); ld4ch(b2, yo + Y2_OFF - 1024 + 3072);
#pragma unroll
    for (int k = 0; k < 4; k++) { a2[k] = hfma2(kk[2 * k], s2[k], a2[k]); b2[k] = hfma2(kk[2 * k + 1], s2[k], b2[k]); }
    STAMP(11);
    mbar_wait(sb + B_Y3);
    STAMP(12);
    ld4ch(a3, yo + Y3_OFF - 2048); ld4ch(b3, yo + Y3_OFF - 2048 + 2048);
#pragma unroll
    for (int k = 0; k < 4; k++) { ya[k] = hadd2(ya[k], hadd2(a2[k], a3[k])); yb[k] = hadd2(yb[k], hadd2(b2[k], b3[k])); }
    const uint4 r = mix(ya, yb, ua, ub, g2);
    if ((uint32_t)(ch & 1) != rank) send_box(sb, 2 + (ch >> 1), wtid, rank, r);
    else merge_box(sb, &tm_out, 2 + (ch >> 1), wtid, rank, oc0, r, 1 + ch);
  }
  STAMP(14);
  if (wtid == 0) asm volatile("cp.async.bulk.wait_group.read 0;" ::: "memory");
  STAMP(15); GT(1);
}

typedef CUresult (*EncodeFn)(CUtensorMap*, CUtensorMapDataType, cuuint32_t, void*, const cuuint64_t*, const cuuint64_t*,
                             const cuuint32_t*, const cuuint32_t*, CUtensorMapInterleave, CUtensorMapSwizzle,
                             CUtensorMapL2promotion, CUtensorMapFloatOOBfill);

}

extern "C" void kernel_launch(void* const* d_in, const int* in_sizes, int n_in, void* d_out, int out_size) {
  (void)in_sizes; (void)n_in; (void)out_size;
  typedef const __nv_bfloat16* bp;
  Params p;
  p.t[0] = (bp)d_in[10]; p.t[1] = (bp)d_in[11]; p.t[2] = (bp)d_in[12]; p.t[3] = (bp)d_in[13]; p.t[4] = (bp)d_in[14]; p.t[5] = nullptr;
  p.t[6] = (bp)d_in[1]; p.t[7] = (bp)d_in[2]; p.t[8] = (bp)d_in[5]; p.t[9] = (bp)d_in[6]; p.t[10] = (bp)d_in[7];
  p.t[11] = (bp)d_in[3]; p.t[12] = (bp)d_in[4]; p.t[13] = nullptr;
  p.u = (bp)d_in[0]; p.gw = (bp)d_in[16]; p.A_D = (bp)d_in[8]; p.B_D = (bp)d_in[15];
  static EncodeFn enc = nullptr;
  if (!enc) {
    cudaDriverEntryPointQueryResult qr;
    cudaGetDriverEntryPoint("cuTensorMapEncodeTiled", (void**)&enc, cudaEnableDefault, &qr);
    cudaFuncSetAttribute(ssm_kernel, cudaFuncAttributeMaxDynamicSharedMemorySize, SMEM_BYTES);
  }
  CUtensorMap tm_in, tm_out;
  {
    cuuint64_t gd[5] = {512, 2, 4, 4, 64};
    cuuint64_t gs[4] = {1024, 8192, 2048, 32768};
    cuuint32_t bx[5] = {8, 2, 4, 4, 32};
    cuuint32_t es[5] = {1, 1, 1, 1, 1};
    enc(&tm_in, CU_TENSOR_MAP_DATA_TYPE_BFLOAT16, 5, d_in[0], gd, gs, bx, es, CU_TENSOR_MAP_INTERLEAVE_NONE,
        CU_TENSOR_MAP_SWIZZLE_NONE, CU_TENSOR_MAP_L2_PROMOTION_NONE, CU_TENSOR_MAP_FLOAT_OOB_FILL_NONE);
  }
  {
    cuuint64_t gd[3] = {512, 1024, 2};
    cuuint64_t gs[2] = {2048, 1024};
    cuuint32_t bx[3] = {8, 128, 2};
    cuuint32_t es[3] = {1, 1, 1};
    enc(&tm_out, CU_TENSOR_MAP_DATA_TYPE_BFLOAT16, 3, d_out, gd, gs, bx, es, CU_TENSOR_MAP_INTERLEAVE_NONE,
        CU_TENSOR_MAP_SWIZZLE_NONE, CU_TENSOR_MAP_L2_PROMOTION_NONE, CU_TENSOR_MAP_FLOAT_OOB_FILL_NONE);
  }
  ssm_kernel<<<NCTA, 640, SMEM_BYTES, cudaStreamPerThread>>>(p, tm_in, tm_out);
}
```

```cpp
#include <cuda_runtime.h>
#include <cuda.h>
#include <cuda_bf16.h>
#include <stdint.h>

namespace {
#define FIXA 0
#define FIXB 1
#define CPY(x) (x)
#define FCPY(x) __uint_as_float(opq(__float_as_uint(x), zz))

constexpr int L = 2048, D = 512, NM = 128;
constexpr int NCTA = 128;
constexpr int NGATE = 4;

constexpr int RAW_OFF = 0;
constexpr int XIN_OFF = 32768;
constexpr int BAR_OFF = XIN_OFF + 10240;
constexpr int CH_OFF = BAR_OFF + 128;
constexpr int U_CS = 1184;
constexpr int U_OFF = 0;
constexpr int R_OFF = 4736;
constexpr int RD_X0 = 565;
constexpr int RD_CS = 1216;
constexpr int RS_CS = 320;
constexpr int R_E2 = 2 * RD_CS, R_O2 = R_E2 + 2 * RS_CS, R_E3 = R_O2 + 2 * RS_CS, R_O3 = R_E3 + 2 * RS_CS;
constexpr int R_BR = R_O3 + 2 * RS_CS;
constexpr int W5_OFF = R_OFF + 2 * R_BR;
constexpr int W3_OFF = W5_OFF + 3456;
constexpr int W9_OFF = W3_OFF + 3456;
constexpr int W7_OFF = W9_OFF + 2304;
constexpr int S2_OFF = W7_OFF + 2304;
constexpr int Y0_OFF = S2_OFF + 2304;
constexpr int Y2_OFF = Y0_OFF + 8192, Y3_OFF = Y2_OFF + 6144;
constexpr int CH_BYTES = Y0_OFF + 18432 + 16;
constexpr int SCR_BYTES = 4608;
constexpr int SMEM_BYTES = CH_OFF + 4 * CH_BYTES;
static_assert(CH_BYTES % 128 == 16, "bank staggering of the channel blocks");
static_assert(SMEM_BYTES <= 232448, "smem");
constexpr int B_RAW = BAR_OFF, B_X = BAR_OFF + 8, B_U = BAR_OFF + 40, B_W = BAR_OFF + 48, B_Y2 = BAR_OFF + 56, B_Y3 = BAR_OFF + 96;
constexpr int TAG_OFF = BAR_OFF + 104;
constexpr int K1024_OFF = BAR_OFF + 64;

__device__ unsigned int g_gate[L];
__device__ unsigned int g_epoch;
__device__ unsigned int g_ticket;

#define STAMP(k)
#define GT(k)

struct Params {
  const __nv_bfloat16* t[14];
  const __nv_bfloat16 *u, *gw, *A_D, *B_D;
};

template <int N, int TB> __device__ __forceinline__ void wgmma_rs(float* d, uint32_t a0, uint32_t a1, uint32_t a2, uint32_t a3, uint64_t desc, int sc);
template <> __device__ __forceinline__ void wgmma_rs<64, 0>(float* d, uint32_t a0, uint32_t a1, uint32_t a2, uint32_t a3, uint64_t desc, int sc) {
  asm volatile("{\n.reg .pred p;\nsetp.ne.b32 p, %37, 0;\n"
    "wgmma.mma_async.sync.aligned.m64n64k16.f32.bf16.bf16 {%0,%1,%2,%3,%4,%5,%6,%7,%8,%9,%10,%11,%12,%13,%14,%15,%16,%17,%18,%19,%20,%21,%22,%23,%24,%25,%26,%27,%28,%29,%30,%31}, {%32,%33,%34,%35}, %36, p, 1, 1, 0;\n}"
    : "+f"(d[0]), "+f"(d[1]), "+f"(d[2]), "+f"(d[3]), "+f"(d[4]), "+f"(d[5]), "+f"(d[6]), "+f"(d[7]), "+f"(d[8]), "+f"(d[9]), "+f"(d[10]), "+f"(d[11]), "+f"(d[12]), "+f"(d[13]), "+f"(d[14]), "+f"(d[15]), "+f"(d[16]), "+f"(d[17]), "+f"(d[18]), "+f"(d[19]), "+f"(d[20]), "+f"(d[21]), "+f"(d[22]), "+f"(d[23]), "+f"(d[24]), "+f"(d[25]), "+f"(d[26]), "+f"(d[27]), "+f"(d[28]), "+f"(d[29]), "+f"(d[30]), "+f"(d[31]) : "r"(a0), "r"(a1), "r"(a2), "r"(a3), "l"(desc), "r"(sc));
}
template <> __device__ __forceinline__ void wgmma_rs<56, 0>(float* d, uint32_t a0, uint32_t a1, uint32_t a2, uint32_t a3, uint64_t desc, int sc) {
  asm volatile("{\n.reg .pred p;\nsetp.ne.b32 p, %33, 0;\n"
    "wgmma.mma_async.sync.aligned.m64n56k16.f32.bf16.bf16 {%0,%1,%2,%3,%4,%5,%6,%7,%8,%9,%10,%11,%12,%13,%14,%15,%16,%17,%18,%19,%20,%21,%22,%23,%24,%25,%26,%27}, {%28,%29,%30,%31}, %32, p, 1, 1, 0;\n}"
    : "+f"(d[0]), "+f"(d[1]), "+f"(d[2]), "+f"(d[3]), "+f"(d[4]), "+f"(d[5]), "+f"(d[6]), "+f"(d[7]), "+f"(d[8]), "+f"(d[9]), "+f"(d[10]), "+f"(d[11]), "+f"(d[12]), "+f"(d[13]), "+f"(d[14]), "+f"(d[15]), "+f"(d[16]), "+f"(d[17]), "+f"(d[18]), "+f"(d[19]), "+f"(d[20]), "+f"(d[21]), "+f"(d[22]), "+f"(d[23]), "+f"(d[24]), "+f"(d[25]), "+f"(d[26]), "+f"(d[27]) : "r"(a0), "r"(a1), "r"(a2), "r"(a3), "l"(desc), "r"(sc));
}
template <> __device__ __forceinline__ void wgmma_rs<48, 0>(float* d, uint32_t a0, uint32_t a1, uint32_t a2, uint32_t a3, uint64_t desc, int sc) {
  asm volatile("{\n.reg .pred p;\nsetp.ne.b32 p, %29, 0;\n"
    "wgmma.mma_async.sync.aligned.m64n48k16.f32.bf16.bf16 {%0,%1,%2,%3,%4,%5,%6,%7,%8,%9,%10,%11,%12,%13,%14,%15,%16,%17,%18,%19,%20,%21,%22,%23}, {%24,%25,%26,%27}, %28, p, 1, 1, 0;\n}"
    : "+f"(d[0]), "+f"(d[1]), "+f"(d[2]), "+f"(d[3]), "+f"(d[4]), "+f"(d[5]), "+f"(d[6]), "+f"(d[7]), "+f"(d[8]), "+f"(d[9]), "+f"(d[10]), "+f"(d[11]), "+f"(d[12]), "+f"(d[13]), "+f"(d[14]), "+f"(d[15]), "+f"(d[16]), "+f"(d[17]), "+f"(d[18]), "+f"(d[19]), "+f"(d[20]), "+f"(d[21]), "+f"(d[22]), "+f"(d[23]) : "r"(a0), "r"(a1), "r"(a2), "r"(a3), "l"(desc), "r"(sc));
}
template <> __device__ __forceinline__ void wgmma_rs<32, 0>(float* d, uint32_t a0, uint32_t a1, uint32_t a2, uint32_t a3, uint64_t desc, int sc) {
  asm volatile("{\n.reg .pred p;\nsetp.ne.b32 p, %21, 0;\n"
    "wgmma.mma_async.sync.aligned.m64n32k16.f32.bf16.bf16 {%0,%1,%2,%3,%4,%5,%6,%7,%8,%9,%10,%11,%12,%13,%14,%15}, {%16,%17,%18,%19}, %20, p, 1, 1, 0;\n}"
    : "+f"(d[0]), "+f"(d[1]), "+f"(d[2]), "+f"(d[3]), "+f"(d[4]), "+f"(d[5]), "+f"(d[6]), "+f"(d[7]), "+f"(d[8]), "+f"(d[9]), "+f"(d[10]), "+f"(d[11]), "+f"(d[12]), "+f"(d[13]), "+f"(d[14]), "+f"(d[15]) : "r"(a0), "r"(a1), "r"(a2), "r"(a3), "l"(desc), "r"(sc));
}
template <> __device__ __forceinline__ void wgmma_rs<48, 1>(float* d, uint32_t a0, uint32_t a1, uint32_t a2, uint32_t a3, uint64_t desc, int sc) {
  asm volatile("{\n.reg .pred p;\nsetp.ne.b32 p, %29, 0;\n"
    "wgmma.mma_async.sync.aligned.m64n48k16.f32.bf16.bf16 {%0,%1,%2,%3,%4,%5,%6,%7,%8,%9,%10,%11,%12,%13,%14,%15,%16,%17,%18,%19,%20,%21,%22,%23}, {%24,%25,%26,%27}, %28, p, 1, 1, 1;\n}"
    : "+f"(d[0]), "+f"(d[1]), "+f"(d[2]), "+f"(d[3]), "+f"(d[4]), "+f"(d[5]), "+f"(d[6]), "+f"(d[7]), "+f"(d[8]), "+f"(d[9]), "+f"(d[10]), "+f"(d[11]), "+f"(d[12]), "+f"(d[13]), "+f"(d[14]), "+f"(d[15]), "+f"(d[16]), "+f"(d[17]), "+f"(d[18]), "+f"(d[19]), "+f"(d[20]), "+f"(d[21]), "+f"(d[22]), "+f"(d[23]) : "r"(a0), "r"(a1), "r"(a2), "r"(a3), "l"(desc), "r"(sc));
}
template <> __device__ __forceinline__ void wgmma_rs<40, 1>(float* d, uint32_t a0, uint32_t a1, uint32_t a2, uint32_t a3, uint64_t desc, int sc) {
  asm volatile("{\n.reg .pred p;\nsetp.ne.b32 p, %25, 0;\n"
    "wgmma.mma_async.sync.aligned.m64n40k16.f32.bf16.bf16 {%0,%1,%2,%3,%4,%5,%6,%7,%8,%9,%10,%11,%12,%13,%14,%15,%16,%17,%18,%19}, {%20,%21,%22,%23}, %24, p, 1, 1, 1;\n}"
    : "+f"(d[0]), "+f"(d[1]), "+f"(d[2]), "+f"(d[3]), "+f"(d[4]), "+f"(d[5]), "+f"(d[6]), "+f"(d[7]), "+f"(d[8]), "+f"(d[9]), "+f"(d[10]), "+f"(d[11]), "+f"(d[12]), "+f"(d[13]), "+f"(d[14]), "+f"(d[15]), "+f"(d[16]), "+f"(d[17]), "+f"(d[18]), "+f"(d[19]) : "r"(a0), "r"(a1), "r"(a2), "r"(a3), "l"(desc), "r"(sc));
}
template <> __device__ __forceinline__ void wgmma_rs<32, 1>(float* d, uint32_t a0, uint32_t a1, uint32_t a2, uint32_t a3, uint64_t desc, int sc) {
  asm volatile("{\n.reg .pred p;\nsetp.ne.b32 p, %21, 0;\n"
    "wgmma.mma_async.sync.aligned.m64n32k16.f32.bf16.bf16 {%0,%1,%2,%3,%4,%5,%6,%7,%8,%9,%10,%11,%12,%13,%14,%15}, {%16,%17,%18,%19}, %20, p, 1, 1, 1;\n}"
    : "+f"(d[0]), "+f"(d[1]), "+f"(d[2]), "+f"(d[3]), "+f"(d[4]), "+f"(d[5]), "+f"(d[6]), "+f"(d[7]), "+f"(d[8]), "+f"(d[9]), "+f"(d[10]), "+f"(d[11]), "+f"(d[12]), "+f"(d[13]), "+f"(d[14]), "+f"(d[15]) : "r"(a0), "r"(a1), "r"(a2), "r"(a3), "l"(desc), "r"(sc));
}
template <> __device__ __forceinline__ void wgmma_rs<16, 1>(float* d, uint32_t a0, uint32_t a1, uint32_t a2, uint32_t a3, uint64_t desc, int sc) {
  asm volatile("{\n.reg .pred p;\nsetp.ne.b32 p, %13, 0;\n"
    "wgmma.mma_async.sync.aligned.m64n16k16.f32.bf16.bf16 {%0,%1,%2,%3,%4,%5,%6,%7}, {%8,%9,%10,%11}, %12, p, 1, 1, 1;\n}"
    : "+f"(d[0]), "+f"(d[1]), "+f"(d[2]), "+f"(d[3]), "+f"(d[4]), "+f"(d[5]), "+f"(d[6]), "+f"(d[7]) : "r"(a0), "r"(a1), "r"(a2), "r"(a3), "l"(desc), "r"(sc));
}

__device__ __forceinline__ uint32_t pack_bf16(float lo, float hi) {
  uint32_t r; asm("cvt.rn.bf16x2.f32 %0, %1, %2;" : "=r"(r) : "f"(hi), "f"(lo)); return r;
}
__device__ __forceinline__ float bf_lo(uint32_t v) { return __uint_as_float(v << 16); }
__device__ __forceinline__ float bf_hi(uint32_t v) { return __uint_as_float(v & 0xffff0000u); }
__device__ __forceinline__ float bf_round(float x) { return bf_lo(pack_bf16(x, 0.f)); }
__device__ __forceinline__ uint32_t hmul2(uint32_t a, uint32_t b) { uint32_t r; asm("mul.rn.bf16x2 %0, %1, %2;" : "=r"(r) : "r"(a), "r"(b)); return r; }
__device__ __forceinline__ uint32_t hadd2(uint32_t a, uint32_t b) { uint32_t r; asm("add.rn.bf16x2 %0, %1, %2;" : "=r"(r) : "r"(a), "r"(b)); return r; }
__device__ __forceinline__ uint32_t hsub2(uint32_t a, uint32_t b) { uint32_t r; asm("sub.rn.bf16x2 %0, %1, %2;" : "=r"(r) : "r"(a), "r"(b)); return r; }
__device__ __forceinline__ uint32_t hfma2(uint32_t a, uint32_t b, uint32_t c) { uint32_t r; asm("fma.rn.bf16x2 %0, %1, %2, %3;" : "=r"(r) : "r"(a), "r"(b), "r"(c)); return r; }

__device__ __forceinline__ void sts16(uint32_t a, uint32_t v) { asm volatile("st.shared.b16 [%0], %1;" ::"r"(a), "h"((unsigned short)v) : "memory"); }
__device__ __forceinline__ void sts32(uint32_t a, uint32_t v) { asm volatile("st.shared.b32 [%0], %1;" ::"r"(a), "r"(v) : "memory"); }
__device__ __forceinline__ void sts64(uint32_t a, uint32_t x, uint32_t y) { asm volatile("st.shared.v2.b32 [%0], {%1,%2};" ::"r"(a), "r"(x), "r"(y) : "memory"); }
__device__ __forceinline__ void sts128(uint32_t a, uint32_t x, uint32_t y, uint32_t z, uint32_t w) {
  asm volatile("st.shared.v4.b32 [%0], {%1,%2,%3,%4};" ::"r"(a), "r"(x), "r"(y), "r"(z), "r"(w) : "memory");
}
__device__ __forceinline__ uint32_t lds32(uint32_t a) { uint32_t v; asm volatile("ld.shared.b32 %0, [%1];" : "=r"(v) : "r"(a) : "memory"); return v; }
__device__ __forceinline__ uint2 lds64(uint32_t a) { uint2 v; asm volatile("ld.shared.v2.b32 {%0,%1}, [%2];" : "=r"(v.x), "=r"(v.y) : "r"(a) : "memory"); return v; }
__device__ __forceinline__ uint4 lds128(uint32_t a) {
  uint4 v; asm volatile("ld.shared.v4.b32 {%0,%1,%2,%3}, [%4];" : "=r"(v.x), "=r"(v.y), "=r"(v.z), "=r"(v.w) : "r"(a) : "memory"); return v;
}
__device__ __forceinline__ uint4 ldg128(const void* a) {
  uint4 v; asm volatile("ld.global.nc.v4.b32 {%0,%1,%2,%3}, [%4];" : "=r"(v.x), "=r"(v.y), "=r"(v.z), "=r"(v.w) : "l"(a) : "memory"); return v;
}
__device__ __forceinline__ uint2 ldg64(const void* a) {
  uint2 v; asm volatile("ld.global.nc.v2.b32 {%0,%1}, [%2];" : "=r"(v.x), "=r"(v.y) : "l"(a) : "memory"); return v;
}
__device__ __forceinline__ void ldsm4(uint32_t a, uint32_t& r0, uint32_t& r1, uint32_t& r2, uint32_t& r3) {
  asm volatile("ldmatrix.sync.aligned.m8n8.x4.shared.b16 {%0,%1,%2,%3}, [%4];" : "=r"(r0), "=r"(r1), "=r"(r2), "=r"(r3) : "r"(a) : "memory");
}
__device__ __forceinline__ void ldsm4t(uint32_t a, uint32_t& r0, uint32_t& r1, uint32_t& r2, uint32_t& r3) {
  asm volatile("ldmatrix.sync.aligned.m8n8.x4.trans.shared.b16 {%0,%1,%2,%3}, [%4];" : "=r"(r0), "=r"(r1), "=r"(r2), "=r"(r3) : "r"(a) : "memory");
}
__device__ __forceinline__ void stsm4(uint32_t a, uint32_t r0, uint32_t r1, uint32_t r2, uint32_t r3) {
  asm volatile("stmatrix.sync.aligned.m8n8.x4.shared.b16 [%0], {%1,%2,%3,%4};" ::"r"(a), "r"(r0), "r"(r1), "r"(r2), "r"(r3) : "memory");
}
__device__ __forceinline__ void stsm4t(uint32_t a, uint32_t r0, uint32_t r1, uint32_t r2, uint32_t r3) {
  asm volatile("stmatrix.sync.aligned.m8n8.x4.trans.shared.b16 [%0], {%1,%2,%3,%4};" ::"r"(a), "r"(r0), "r"(r1), "r"(r2), "r"(r3) : "memory");
}
__device__ __forceinline__ void mma16816(float* c, uint32_t a0, uint32_t a1, uint32_t a2, uint32_t a3, uint32_t b0, uint32_t b1) {
  asm("mma.sync.aligned.m16n8k16.row.col.f32.bf16.bf16.f32 {%0,%1,%2,%3}, {%4,%5,%6,%7}, {%8,%9}, {%0,%1,%2,%3};"
      : "+f"(c[0]), "+f"(c[1]), "+f"(c[2]), "+f"(c[3]) : "r"(a0), "r"(a1), "r"(a2), "r"(a3), "r"(b0), "r"(b1));
}
__device__ __forceinline__ void bar_sync(int id, int n) { asm volatile("bar.sync %0, %1;" ::"r"(id), "r"(n) : "memory"); }
__device__ __forceinline__ void bar_arrive(int id, int n) { asm volatile("bar.arrive %0, %1;" ::"r"(id), "r"(n) : "memory"); }
__device__ __forceinline__ void wg_fence() { asm volatile("wgmma.fence.sync.aligned;" ::: "memory"); }
__device__ __forceinline__ void wg_commit() { asm volatile("wgmma.commit_group.sync.aligned;" ::: "memory"); }
__device__ __forceinline__ void wg_wait0() { asm volatile("wgmma.wait_group.sync.aligned 0;" ::: "memory"); }
__device__ __forceinline__ void fence_async() { asm volatile("fence.proxy.async.shared::cta;" ::: "memory"); }
__device__ __forceinline__ uint32_t opq(uint32_t x, uint32_t z) { uint32_t r; asm volatile("xor.b32 %0, %1, %2;" : "=r"(r) : "r"(x), "r"(z)); return r; }
__device__ __forceinline__ uint64_t mkdesc(uint32_t addr, uint32_t lbo, uint32_t sbo) {
  return (uint64_t)((addr & 0x3FFFF) >> 4) | ((uint64_t)(lbo >> 4) << 16) | ((uint64_t)(sbo >> 4) << 32);
}
__device__ __forceinline__ uint32_t mapa(uint32_t a, uint32_t rank) {
  uint32_t r; asm("mapa.shared::cluster.u32 %0, %1, %2;" : "=r"(r) : "r"(a), "r"(rank)); return r;
}
__device__ __forceinline__ void mbar_init_expect(uint32_t bar, uint32_t bytes) {
  asm volatile("mbarrier.init.shared::cta.b64 [%0], 1;" ::"r"(bar) : "memory");
  asm volatile("mbarrier.arrive.expect_tx.shared::cta.b64 _, [%0], %1;" ::"r"(bar), "r"(bytes) : "memory");
}
__device__ __forceinline__ void mbar_wait(uint32_t bar) {
#pragma unroll 1
  for (int it = 0; it < (1 << 22); it++) {
    uint32_t ok;
    asm volatile("{\n.reg .pred p;\nmbarrier.try_wait.parity.acquire.cluster.shared::cta.b64 p, [%1], 0;\nselp.u32 %0, 1, 0, p;\n}"
                 : "=r"(ok) : "r"(bar) : "memory");
    if (ok) return;
  }
  __trap();
}
__device__ __forceinline__ void st_async4(uint32_t a, uint32_t bar, uint32_t x, uint32_t y, uint32_t z, uint32_t w) {
  asm volatile("st.async.weak.shared::cluster.mbarrier::complete_tx::bytes.v4.b32 [%0], {%2,%3,%4,%5}, [%1];"
               ::"r"(a), "r"(bar), "r"(x), "r"(y), "r"(z), "r"(w) : "memory");
}

struct cf { float re, im; };
__device__ __forceinline__ cf cmul(cf a, cf b) { return {fmaf(a.re, b.re, -a.im * b.im), fmaf(a.re, b.im, a.im * b.re)}; }
__device__ __forceinline__ cf csq(cf a) { return {fmaf(a.re, a.re, -a.im * a.im), (a.re + a.re) * a.im}; }
__device__ __forceinline__ cf cexp_p(float xl, float y, float p) {
  float mag; asm("ex2.approx.ftz.f32 %0, %1;" : "=f"(mag) : "f"(xl * p));
  const float th = y * p;
  const float k = rintf(th * 0.15915494309189535f);
  float r = fmaf(k, -6.2831854820251465f, th);
  r = fmaf(k, 1.7484555314695172e-07f, r);
  return {mag * __cosf(r), mag * __sinf(r)};
}
__device__ __forceinline__ uint32_t ysw(int c) { return (uint32_t)(c ^ ((c >> 3) & 3)) * 16u; }

#define CMUL2(OR, OI, xr, xi, yr, yi, nyi) do { OR = hfma2(xr, yr, hmul2(xi, nyi)); OI = hfma2(xr, yi, hmul2(xi, yr)); } while (0)

__device__ __forceinline__ uint32_t gate_slow(const __nv_bfloat16* u, const __nv_bfloat16* gw, int row) {
  float s = 0.f;
  const uint32_t* xr = (const uint32_t*)(u + (size_t)row * D);
  const uint32_t* wr = (const uint32_t*)gw;
#pragma unroll 1
  for (int j = 0; j < D / 2; j++) { const uint32_t pr = hmul2(xr[j], wr[j]); s += bf_lo(pr); s += bf_hi(pr); }
  s = bf_round(s);
  return pack_bf16(1.f / (1.f + expf(-s)), 0.f);
}

__device__ __forceinline__ uint2 gate_ld(int x) {
  uint2 gv;
  asm volatile("ld.relaxed.gpu.global.v2.u32 {%0,%1}, [%2];" : "=r"(gv.x), "=r"(gv.y) : "l"(g_gate + x * 2) : "memory");
  return gv;
}
__device__ __noinline__ uint32_t gate_poll(const __nv_bfloat16* u, const __nv_bfloat16* gw, int x, uint32_t tag) {
  uint2 gv;
#pragma unroll 1
  for (int spins = 0; spins < (1 << 16); spins++) {
    gv = gate_ld(x);
    if ((gv.x >> 16) == tag && (gv.y >> 16) == tag) return __byte_perm(gv.x, gv.y, 0x5410);
  }
  return __byte_perm(gate_slow(u, gw, x * 2), gate_slow(u, gw, x * 2 + 1), 0x5410);
}
__device__ __forceinline__ uint32_t gate_fin(const Params& p, uint2 gv, int x, uint32_t tag) {
  if ((gv.x >> 16) == tag && (gv.y >> 16) == tag) return __byte_perm(gv.x, gv.y, 0x5410);
  return gate_poll(p.u, p.gw, x, tag);
}

__device__ __forceinline__ void ld4ch(uint32_t* v, uint32_t addr) {
#pragma unroll
  for (int k = 0; k < 4; k++) v[k] = lds32(addr + k * CH_BYTES);
}
__device__ __forceinline__ void skip_terms(uint32_t* ua, uint32_t* ub, uint32_t sb, int x, uint2 dA, uint2 dB) {
  const int c = x >> 2;
  uint32_t uu[4];
  ld4ch(uu, sb + CH_OFF + (x & 3) * 4 + U_OFF + (c & 3) * U_CS + (63 - (c >> 2)) * 16);
#pragma unroll
  for (int k = 0; k < 4; k++) {
    ua[k] = hmul2(uu[k], __byte_perm((k & 2) ? dA.y : dA.x, 0, (k & 1) ? 0x3232 : 0x1010));
    ub[k] = hmul2(uu[k], __byte_perm((k & 2) ? dB.y : dB.x, 0, (k & 1) ? 0x3232 : 0x1010));
  }
}
__device__ __forceinline__ uint4 mix(const uint32_t* a, const uint32_t* b, const uint32_t* ua, const uint32_t* ub, uint32_t g2) {
  const uint32_t h2 = hsub2(0x3f803f80u, g2);
  uint32_t o[4];
#pragma unroll
  for (int k = 0; k < 4; k++) o[k] = hadd2(hmul2(g2, hadd2(a[k], ua[k])), hmul2(h2, hadd2(b[k], ub[k])));
  return make_uint4(__byte_perm(o[0], o[1], 0x5410), __byte_perm(o[2], o[3], 0x5410), __byte_perm(o[0], o[1], 0x7632), __byte_perm(o[2], o[3], 0x7632));
}
__device__ __forceinline__ void send_box(uint32_t sb, int slot, int wtid, uint32_t rank, uint4 r) {
  st_async4(mapa(sb + XIN_OFF + slot * 2048 + wtid * 16, rank ^ 1), mapa(sb + B_X + slot * 8, rank ^ 1), r.x, r.y, r.z, r.w);
}
__device__ __forceinline__ void merge_box(uint32_t sb, const CUtensorMap* tm_out, int slot, int wtid, uint32_t rank, int oc0, uint4 r, int barid) {
  const uint32_t st = sb + RAW_OFF + slot * 4096 + wtid * 16;
  sts64(st + rank * 8, r.x, r.y); sts64(st + 2048 + rank * 8, r.z, r.w);
  mbar_wait(sb + B_X + slot * 8);
  const uint4 q = lds128(sb + XIN_OFF + slot * 2048 + wtid * 16);
  sts64(st + (rank ^ 1) * 8, q.x, q.y); sts64(st + 2048 + (rank ^ 1) * 8, q.z, q.w);
  fence_async();
  bar_sync(barid, 128);
  if (wtid == 0) {
    asm volatile("cp.async.bulk.tensor.3d.global.shared::cta.bulk_group [%0, {%2, %3, %4}], [%1];"
                 ::"l"(tm_out), "r"(sb + RAW_OFF + slot * 4096), "r"(oc0), "r"((2 * slot + (int)rank) * 128), "r"(0) : "memory");
    asm volatile("cp.async.bulk.commit_group;" ::: "memory");
  }
}

__device__ __forceinline__ uint32_t band2(int e, int lo, int hi) {
  uint32_t r = ((uint32_t)(e - lo) <= (uint32_t)(hi - lo) ? 0x3f80u : 0u) | ((uint32_t)(e - 1 - lo) <= (uint32_t)(hi - lo) ? 0x3f800000u : 0u);
  asm volatile("" : "+r"(r));
  return r;
}

__device__ __forceinline__ void conv_dense(uint32_t cb, uint32_t zz) {
  const int lane = threadIdx.x & 31, wq = (threadIdx.x >> 5) & 3, br = wq >> 1, hf = wq & 1, g = lane >> 2, t = lane & 3;
  const uint32_t rb = cb + R_OFF + br * R_BR;
  const int eo = 16 * hf + g - 2 * t;
  float dacc[32];
  {
      {
        const int x0 = RD_X0 - (eo + 536);
        const uint32_t fa = rb + ((g & 1) ? 2 * x0 : RD_CS + 2 * x0 + 2);
        const uint64_t ub = mkdesc(cb + U_OFF, U_CS, 128);
        uint32_t A[2][4][4];
        float e56[28], e48[24];
        auto loadA = [&](int j) {
#pragma unroll
          for (int k = 0; k < 4; k++) {
            const int s = 34 - 4 * j - k;
            if (s >= 0) {
              if (k == 0 && j == 0) A[0][0][2] = lds32(fa + (2 * s + 2) * 16);
              A[j & 1][k][0] = lds32(fa + (2 * s + 1) * 16);
              A[j & 1][k][1] = lds32(fa + (2 * s) * 16);
            }
          }
#pragma unroll
          for (int k = 0; k < 4; k++) {
            if (34 - 4 * j - k >= 0) {
              A[j & 1][k][3] = CPY(A[j & 1][k][0]);
              if (k) A[j & 1][k][2] = CPY(A[j & 1][k - 1][1]);
              else if (j) A[j & 1][0][2] = CPY(A[(j - 1) & 1][3][1]);
            }
          }
        };
        loadA(0);
#pragma unroll
        for (int j = 0; j < 9; j++) {
          if (j == 4) {
#pragma unroll
            for (int i = 0; i < 28; i++) e56[i] = FCPY(dacc[i]);
          }
          if (j == 8) {
#pragma unroll
            for (int i = 0; i < 24; i++) e48[i] = FCPY(e56[i]);
          }
          wg_fence();
#pragma unroll
          for (int k = 0; k < 4; k++) {
            const int s = 34 - 4 * j - k;
            if (s >= 0) {
              const int o = 2 * s - 66 + 128;
              const int cc = o & 3, rs = (o >> 2) - 32;
              const int n0 = ((-rs) >> 3) * 8;
              const uint64_t desc = ub + (uint64_t)((cc * U_CS - rs * 16) >> 4);
              const uint32_t* a = A[j & 1][k];
              if (n0 == 0) wgmma_rs<64, 0>(dacc, a[0], a[1], a[2], a[3], desc, s != 34);
              else if (n0 == 8) wgmma_rs<56, 0>(FIXB ? e56 : dacc, a[0], a[1], a[2], a[3], desc, 1);
              else wgmma_rs<48, 0>(FIXB ? e48 : dacc, a[0], a[1], a[2], a[3], desc, 1);
            }
          }
          wg_commit();
          if (j < 8) loadA(j + 1);
          wg_wait0();
        }
#pragma unroll
        for (int i = 0; i < 28; i++) dacc[i] = i < 24 ? e48[i] : e56[i];
      }
      const uint32_t yb = cb + Y0_OFF + br * 4096;
#pragma unroll
      for (int i = 0; i < 8; i += 2) {
        const int mi = lane >> 3;
        const int cidx = 4 * (63 - 8 * (i + (mi >> 1)) - (lane & 7)) + 2 * hf + (mi & 1);
        stsm4t(yb + ysw(cidx), pack_bf16(dacc[4 * i], dacc[4 * i + 1]), pack_bf16(dacc[4 * i + 2], dacc[4 * i + 3]),
               pack_bf16(dacc[4 * i + 4], dacc[4 * i + 5]), pack_bf16(dacc[4 * i + 6], dacc[4 * i + 7]));
      }
      bar_arrive(6, 640);
      STAMP(8);
  }
}

__device__ __forceinline__ void conv_far(uint32_t sb, uint32_t cb, uint32_t zz) {
  const int lane = threadIdx.x & 31, wq = (threadIdx.x >> 5) & 3, br = wq >> 1, hf = wq & 1, g = lane >> 2, t = lane & 3;
  const uint32_t rb = cb + R_OFF + br * R_BR;
  const int eo = 16 * hf + g - 2 * t;
  float dacc[24], e40[20], e32[16], h32[16], h16[8];
  const int x1 = 159 - (eo + 136);
  const uint32_t fs = rb + ((g & 1) ? 2 * x1 : RS_CS + 2 * x1 + 2);
  {
    uint32_t A[2][4][4];
    auto loadA = [&](int buf, uint32_t oe, uint32_t oo, int i0) {
#pragma unroll
      for (int a = 0; a < 2; a++) {
        const uint32_t base = fs + (a ? oo : oe) + i0 * 16;
        uint32_t* k0 = A[buf][2 * a];
        uint32_t* k1 = A[buf][2 * a + 1];
        k0[1] = lds32(base); k0[0] = lds32(base + 16); k0[2] = lds32(base + 32); k1[0] = lds32(base + 48); k1[2] = lds32(base + 64);
      }
#pragma unroll
      for (int a = 0; a < 2; a++) {
        uint32_t* k0 = A[buf][2 * a];
        uint32_t* k1 = A[buf][2 * a + 1];
        k0[3] = CPY(k0[0]); k1[1] = CPY(k0[2]); k1[3] = CPY(k1[0]);
      }
    };
    const uint64_t d5 = mkdesc(cb + W5_OFF, 144, 576), d3 = mkdesc(cb + W3_OFF, 144, 576);
    loadA(0, R_E2, R_O2, 8);
#pragma unroll
    for (int m = 2; m <= 4; m++) {
      if (m == 3) {
#pragma unroll
        for (int i = 0; i < 20; i++) e40[i] = FCPY(dacc[i]);
      }
      if (m == 4) {
#pragma unroll
        for (int i = 0; i < 16; i++) e32[i] = FCPY(e40[i]);
      }
      wg_fence();
#pragma unroll
      for (int k = 0; k < 4; k++) {
        const uint32_t* a = A[m & 1][k];
        const uint64_t desc = ((k >> 1) ? d3 : d5) + (k & 1) * 18 + (m - 2) * 36;
        if (m == 2) wgmma_rs<48, 1>(dacc, a[0], a[1], a[2], a[3], desc, k);
        else if (m == 3) wgmma_rs<40, 1>(e40, a[0], a[1], a[2], a[3], desc, 1);
        else wgmma_rs<32, 1>(e32, a[0], a[1], a[2], a[3], desc, 1);
      }
      wg_commit();
      if (m < 4) loadA((m + 1) & 1, R_E2, R_O2, 4 * (3 - m));
      else loadA(1, R_E3, R_O3, 8);
      wg_wait0();
    }
#pragma unroll
    for (int i = 0; i < 20; i++) dacc[i] = i < 16 ? e32[i] : e40[i];
    {
      const uint32_t yb = cb + Y2_OFF + br * 3072;
#pragma unroll
      for (int i = 0; i < 6; i += 2) {
        const int mi = lane >> 3;
        const int cidx = 32 * (5 - i - (mi >> 1)) + 16 * hf + 8 * (mi & 1) + (lane & 7);
        stsm4(yb + ysw(cidx), pack_bf16(dacc[4 * i], dacc[4 * i + 1]), pack_bf16(dacc[4 * i + 2], dacc[4 * i + 3]),
              pack_bf16(dacc[4 * i + 4], dacc[4 * i + 5]), pack_bf16(dacc[4 * i + 6], dacc[4 * i + 7]));
      }
    }
    __syncwarp();
    if (lane == 0) asm volatile("mbarrier.arrive.shared::cta.b64 _, [%0];" ::"r"(sb + B_Y2) : "memory");
    STAMP(9);
    const uint64_t d9 = mkdesc(cb + W9_OFF, 144, 576), d7 = mkdesc(cb + W7_OFF, 144, 576);
#pragma unroll
    for (int m = 2; m <= 3; m++) {
      if (m == 3) {
#pragma unroll
        for (int i = 0; i < 8; i++) h16[i] = FCPY(h32[i]);
      }
      wg_fence();
#pragma unroll
      for (int k = 0; k < 4; k++) {
        const uint32_t* a = A[(m + 1) & 1][k];
        const uint64_t desc = ((k >> 1) ? d7 : d9) + (k & 1) * 18 + (m - 2) * 72;
        if (m == 2) wgmma_rs<32, 1>(h32, a[0], a[1], a[2], a[3], desc, k);
        else wgmma_rs<16, 1>(h16, a[0], a[1], a[2], a[3], desc, 1);
      }
      wg_commit();
      if (m == 2) loadA(0, R_E3, R_O3, 4);
      wg_wait0();
    }
#pragma unroll
    for (int i = 0; i < 16; i++) dacc[i] = i < 8 ? h16[i] : h32[i];
    const uint32_t yb = cb + Y3_OFF + br * 2048;
#pragma unroll
    for (int i = 0; i < 4; i += 2) {
      const int mi = lane >> 3;
      const int cidx = 64 * (1 - (i >> 1)) + 2 * (16 * hf + 8 * (mi & 1) + (lane & 7)) + (mi >> 1);
      stsm4(yb + ysw(cidx), pack_bf16(dacc[4 * i], dacc[4 * i + 1]), pack_bf16(dacc[4 * i + 2], dacc[4 * i + 3]),
            pack_bf16(dacc[4 * i + 4], dacc[4 * i + 5]), pack_bf16(dacc[4 * i + 6], dacc[4 * i + 7]));
    }
  }
}

__device__ __forceinline__ void gate_cta(const Params& p, int warp, int lane) {
  unsigned int epoch;
  asm volatile("ld.relaxed.gpu.global.u32 %0, [%1];" : "=r"(epoch) : "l"(&g_epoch) : "memory");
  const uint4 gw0 = ldg128(p.gw + lane * 8), gw1 = ldg128(p.gw + 256 + lane * 8);
  const uint32_t ws[8] = {gw0.x, gw0.y, gw0.z, gw0.w, gw1.x, gw1.y, gw1.z, gw1.w};
  const uint32_t tag = (epoch + 1) & 0xffffu;
  uint4 gx[2][4][2];
  int grow = (blockIdx.x * 20 + warp) * 4;
#pragma unroll
  for (int i = 0; i < 4; i++) {
    gx[0][i][0] = ldg128(p.u + (size_t)(grow + i) * D + lane * 8);
    gx[0][i][1] = ldg128(p.u + (size_t)(grow + i) * D + 256 + lane * 8);
  }
#pragma unroll
  for (int it = 0; it < 7; it++) {
    const int nrow = grow + 80 * NGATE;
    if (it < 6 && nrow < L) {
#pragma unroll
      for (int i = 0; i < 4; i++) {
        gx[(it + 1) & 1][i][0] = ldg128(p.u + (size_t)(nrow + i) * D + lane * 8);
        gx[(it + 1) & 1][i][1] = ldg128(p.u + (size_t)(nrow + i) * D + 256 + lane * 8);
      }
    }
    if (grow < L) {
      float sm[4];
#pragma unroll
      for (int i = 0; i < 4; i++) {
        const uint4 x0 = gx[it & 1][i][0], x1 = gx[it & 1][i][1];
        const uint32_t xs[8] = {x0.x, x0.y, x0.z, x0.w, x1.x, x1.y, x1.z, x1.w};
        float s = 0.f;
#pragma unroll
        for (int j = 0; j < 8; j++) { const uint32_t pr = hmul2(xs[j], ws[j]); s += bf_lo(pr); s += bf_hi(pr); }
        sm[i] = s;
      }
      const bool b0 = lane & 1, b1 = lane & 2;
      float u0 = b0 ? sm[1] : sm[0], v0 = b0 ? sm[0] : sm[1], u1 = b0 ? sm[3] : sm[2], v1 = b0 ? sm[2] : sm[3];
      u0 += __shfl_xor_sync(0xffffffffu, v0, 1); u1 += __shfl_xor_sync(0xffffffffu, v1, 1);
      float s = b1 ? u1 : u0; const float v = b1 ? u0 : u1;
      s += __shfl_xor_sync(0xffffffffu, v, 2);
#pragma unroll
      for (int o = 4; o < 32; o <<= 1) s += __shfl_xor_sync(0xffffffffu, s, o);
      s = bf_round(s);
      const float gv = 1.f / (1.f + expf(-s));
      const uint32_t w = (tag << 16) | (pack_bf16(gv, 0.f) & 0xffffu);
      if (lane < 4) asm volatile("st.relaxed.gpu.global.u32 [%0], %1;" ::"l"(&g_gate[grow + lane]), "r"(w) : "memory");
    }
    grow = nrow;
  }
  __syncthreads();
  if (threadIdx.x == 0 && atomicAdd(&g_ticket, 1u) == NCTA + NGATE - 1) { g_ticket = 0; g_epoch = epoch + 1; }
}

__global__ void __cluster_dims__(2, 1, 1) __launch_bounds__(640, 1)
ssm_kernel(const Params p, const __grid_constant__ CUtensorMap tm_in, const __grid_constant__ CUtensorMap tm_out) {
  extern __shared__ __align__(1024) unsigned char smem_raw[];
  const uint32_t sb = (uint32_t)__cvta_generic_to_shared(smem_raw);
  const int tid = threadIdx.x, lane = tid & 31;
  const int warp = __shfl_sync(0xffffffffu, tid >> 5, 0);
  const int ch = warp >> 2, wq = warp & 3, br = wq >> 1, hf = wq & 1;
  const int g = lane >> 2, t = lane & 3;
  if (blockIdx.x < NGATE) { gate_cta(p, warp, lane); return; }
  const int bid = blockIdx.x - NGATE;
  const int d = bid * 4 + ch;
  const uint32_t rank = blockIdx.x & 1;
  const uint32_t cb = sb + CH_OFF + ch * CH_BYTES;
  const int wtid = tid & 127;
  const int oc0 = (bid >> 1) * 8;
  STAMP(0); GT(0);

  if (warp >= 16) {
    if (wtid == 0) {
      mbar_init_expect(sb + B_RAW, 32768);
#pragma unroll
      for (int i = 0; i < 4; i++) mbar_init_expect(sb + B_X + 8 * i, 2048);
      asm volatile("mbarrier.init.shared::cta.b64 [%0], 128;" ::"r"(sb + B_U) : "memory");
      asm volatile("mbarrier.init.shared::cta.b64 [%0], 128;" ::"r"(sb + B_W) : "memory");
      asm volatile("mbarrier.init.shared::cta.b64 [%0], 16;" ::"r"(sb + B_Y2) : "memory");
      asm volatile("mbarrier.init.shared::cta.b64 [%0], 16;" ::"r"(sb + B_Y3) : "memory");
      asm volatile("fence.mbarrier_init.release.cluster;" ::: "memory");
      asm volatile("fence.proxy.async.shared::cta;" ::: "memory");
    }
    __syncwarp();
    asm volatile("barrier.cluster.arrive.relaxed.aligned;" ::: "memory");
    unsigned int epoch;
    asm volatile("ld.relaxed.gpu.global.u32 %0, [%1];" : "=r"(epoch) : "l"(&g_epoch) : "memory");
    asm volatile("barrier.cluster.wait.aligned;" ::: "memory");
    if (wtid == 0) {
      asm volatile("cp.async.bulk.tensor.5d.shared::cluster.global.mbarrier::complete_tx::bytes.multicast::cluster [%0], [%1, {%3, %4, %4, %4, %5}], [%2], %6;"
                   ::"r"(sb + RAW_OFF + rank * 16384), "l"(&tm_in), "r"(sb + B_RAW), "r"(oc0), "r"(0), "r"((int)rank * 32), "h"((unsigned short)3) : "memory");
    }
    sts128(sb + CH_OFF + wq * CH_BYTES + U_OFF + (lane >> 3) * U_CS + (64 + (lane & 7)) * 16, 0, 0, 0, 0);
    uint32_t BA[3][4], BC[3][4];
    {
      const int l1 = br ? 3 : 6, h1 = br ? 5 : 10;
#pragma unroll
      for (int i = 0; i < 3; i++) {
        const int e = 16 * hf + g - 2 * t + 16 - 16 * i;
        BA[i][0] = band2(e, l1, h1); BA[i][1] = band2(e + 8, l1, h1); BA[i][2] = band2(e - 8, l1, h1); BA[i][3] = BA[i][0];
        BC[i][0] = band2(e, 3, 4); BC[i][1] = band2(e + 8, 3, 4); BC[i][2] = band2(e - 8, 3, 4); BC[i][3] = BC[i][0];
      }
    }
    const uint32_t tag = (epoch + 1) & 0xffffu;
    if (wtid == 0) sts32(sb + TAG_OFF, tag);
    STAMP(3);
    mbar_wait(sb + B_RAW);
    STAMP(4);
    {
      const uint32_t dst = sb + CH_OFF + (g & 3) * CH_BYTES + U_OFF + t * U_CS + (63 - wq * 16) * 16;
#pragma unroll
      for (int h = 0; h < 2; h++) {
        uint32_t r[8][4];
#pragma unroll
        for (int i = 0; i < 8; i++) ldsm4t(sb + RAW_OFF + (wq * 16 + h * 8 + i) * 512 + lane * 16, r[i][0], r[i][1], r[i][2], r[i][3]);
        if ((uint32_t)(g >> 2) == rank) {
#pragma unroll
          for (int i = 0; i < 8; i++) sts128(dst - (h * 8 + i) * 16, r[i][0], r[i][1], r[i][2], r[i][3]);
        }
      }
    }
    fence_async();
    asm volatile("mbarrier.arrive.shared::cta.b64 _, [%0];" ::"r"(sb + B_U) : "memory");
    bar_sync(5, 128);
    STAMP(5);
    {
      const int mrow = lane & 7, mi = lane >> 3;
      const uint64_t ub0 = mkdesc(sb + CH_OFF + U_OFF, U_CS, 128);
      {
        float w1[24], w3[16];
#pragma unroll
        for (int i = 0; i < 24; i++) w1[i] = 0.f;
#pragma unroll
        for (int i = 0; i < 16; i++) w3[i] = 0.f;
        uint32_t wa[3], sa[2];
#pragma unroll
        for (int i = 0; i < 3; i++) {
          const int c = 4 * (47 - 8 * (2 * i + (mi >> 1)) - mrow) + 2 * hf + (mi & 1);
          wa[i] = sb + CH_OFF + (br ? W3_OFF : W5_OFF) + (5 - (c >> 5)) * 576 + ((c & 31) >> 3) * 144 + (c & 7) * 16;
          if (i) sa[i - 1] = sb + CH_OFF + S2_OFF + (c + (c >> 3)) * 16;
        }
#pragma unroll 1
        for (int k = 0; k < 4; k++) {
          wg_fence();
#pragma unroll
          for (int i = 0; i < 3; i++)
            wgmma_rs<48, 0>(w1, BA[i][0], BA[i][1], BA[i][2], BA[i][3],
                            ub0 + (uint64_t)((k * CH_BYTES + ((2 * i + 2) & 3) * U_CS + (16 + (i == 0)) * 16) >> 4), i);
#pragma unroll
          for (int i = 0; i < 3; i++)
            wgmma_rs<32, 0>(w3, BC[i][0], BC[i][1], BC[i][2], BC[i][3],
                            ub0 + (uint64_t)((k * CH_BYTES + ((2 * i + 2) & 3) * U_CS + (32 + (i == 0)) * 16) >> 4), i);
          wg_commit();
          wg_wait0();
#pragma unroll
          for (int i = 0; i < 3; i++)
            stsm4t(wa[i] + k * CH_BYTES, pack_bf16(w1[8 * i], w1[8 * i + 1]), pack_bf16(w1[8 * i + 2], w1[8 * i + 3]),
                   pack_bf16(w1[8 * i + 4], w1[8 * i + 5]), pack_bf16(w1[8 * i + 6], w1[8 * i + 7]));
          if (br == 0) {
#pragma unroll
            for (int i = 0; i < 2; i++)
              stsm4t(sa[i] + k * CH_BYTES, pack_bf16(w3[8 * i], w3[8 * i + 1]), pack_bf16(w3[8 * i + 2], w3[8 * i + 3]),
                     pack_bf16(w3[8 * i + 4], w3[8 * i + 5]), pack_bf16(w3[8 * i + 6], w3[8 * i + 7]));
          }
        }
      }
      {
        uint32_t BB[4][4];
        const int l2 = br ? 5 : 12, h2 = br ? 11 : 20;
#pragma unroll
        for (int i = 0; i < 4; i++) {
          const int e = 16 * hf + g - 2 * t + 32 - 16 * i;
          BB[i][0] = band2(e, l2, h2); BB[i][1] = band2(e + 8, l2, h2); BB[i][2] = band2(e - 8, l2, h2); BB[i][3] = BB[i][0];
        }
        float w2[2][16];
#pragma unroll
        for (int i = 0; i < 16; i++) { w2[0][i] = 0.f; w2[1][i] = 0.f; }
        uint32_t wa[2];
#pragma unroll
        for (int i = 0; i < 2; i++) {
          const int c = 4 * (31 - 8 * (2 * i + (mi >> 1)) - mrow) + 2 * hf + (mi & 1), pp = c >> 1;
          wa[i] = sb + CH_OFF + (br ? W7_OFF : W9_OFF) + (1 - (pp >> 5)) * 1152 + (c & 1) * 576 + ((pp & 31) >> 3) * 144 + (pp & 7) * 16;
        }
#pragma unroll 1
        for (int kp = 0; kp < 2; kp++) {
          wg_fence();
#pragma unroll
          for (int k = 0; k < 2; k++)
#pragma unroll
            for (int i = 0; i < 4; i++)
              wgmma_rs<32, 0>(w2[k], BB[i][0], BB[i][1], BB[i][2], BB[i][3],
                              ub0 + (uint64_t)(((2 * kp + k) * CH_BYTES + ((2 * i) & 3) * U_CS + (32 + (i < 2)) * 16) >> 4), i);
          wg_commit();
          wg_wait0();
#pragma unroll
          for (int k = 0; k < 2; k++)
#pragma unroll
            for (int i = 0; i < 2; i++)
              stsm4t(wa[i] + (2 * kp + k) * CH_BYTES, pack_bf16(w2[k][8 * i], w2[k][8 * i + 1]), pack_bf16(w2[k][8 * i + 2], w2[k][8 * i + 3]),
                     pack_bf16(w2[k][8 * i + 4], w2[k][8 * i + 5]), pack_bf16(w2[k][8 * i + 6], w2[k][8 * i + 7]));
        }
      }
    }
    fence_async();
    asm volatile("mbarrier.arrive.shared::cta.b64 _, [%0];" ::"r"(sb + B_W) : "memory");
    STAMP(7);
    const uint2 dA = ldg64(p.A_D + bid * 4), dB = ldg64(p.B_D + bid * 4);
    STAMP(8);
    uint32_t gg[4];
    {
      uint2 gl[4];
#pragma unroll
      for (int i = 0; i < 4; i++) gl[i] = gate_ld((i ^ (int)rank ^ 1) * 128 + wtid);
#pragma unroll
      for (int i = 0; i < 4; i++) gg[i] = gate_fin(p, gl[i], (i ^ (int)rank ^ 1) * 128 + wtid, tag);
    }
    {
      uint32_t ua[4][4], ub[4][4], ya[4][4], yb[4][4], yo[4];
#pragma unroll
      for (int i = 0; i < 4; i++) {
        const int x = (i ^ (int)rank ^ 1) * 128 + wtid;
        skip_terms(ua[i], ub[i], sb, x, dA, dB);
        yo[i] = sb + CH_OFF + (x & 3) * 4 + ysw(x >> 2);
      }
      bar_sync(6, 640);
      STAMP(10);
#pragma unroll
      for (int i = 0; i < 4; i++) { ld4ch(ya[i], yo[i] + Y0_OFF); ld4ch(yb[i], yo[i] + Y0_OFF + 4096); }
      send_box(sb, 0, wtid, rank, mix(ya[0], yb[0], ua[0], ub[0], gg[0]));
      merge_box(sb, &tm_out, 0, wtid, rank, oc0, mix(ya[1], yb[1], ua[1], ub[1], gg[1]), 5);
      STAMP(12);
      mbar_wait(sb + B_Y2);
      STAMP(11);
#pragma unroll
      for (int i = 2; i < 4; i++) { ld4ch(ya[i - 2], yo[i] + Y2_OFF - 1024); ld4ch(yb[i - 2], yo[i] + Y2_OFF - 1024 + 3072); }
#pragma unroll
      for (int i = 2; i < 4; i++)
#pragma unroll
        for (int k = 0; k < 4; k++) { ya[i][k] = hadd2(ya[i][k], ya[i - 2][k]); yb[i][k] = hadd2(yb[i][k], yb[i - 2][k]); }
      send_box(sb, 1, wtid, rank, mix(ya[2], yb[2], ua[2], ub[2], gg[2]));
      merge_box(sb, &tm_out, 1, wtid, rank, oc0, mix(ya[3], yb[3], ua[3], ub[3], gg[3]), 5);
      STAMP(13);
    }
    if (wtid == 0) {
      if (atomicAdd(&g_ticket, 1u) == NCTA + NGATE - 1) { g_ticket = 0; g_epoch = epoch + 1; }
      asm volatile("cp.async.bulk.wait_group.read 0;" ::: "memory");
    }
    STAMP(15);
    return;
  }
  asm volatile("barrier.cluster.arrive.relaxed.aligned;" ::: "memory");

  const int moff = d * NM + hf * 64 + lane * 2;
  const __nv_bfloat16* const* tp = p.t + (br ? 0 : 6);
  const uint32_t q0 = *(const uint32_t*)(tp[0] + moff), q1 = *(const uint32_t*)(tp[1] + moff);
  const uint32_t q2 = *(const uint32_t*)(tp[2] + moff), q3 = *(const uint32_t*)(tp[3] + moff);
  const uint2 ldt4 = *(const uint2*)(tp[4] + bid * 4);
  const uint32_t q4 = *(const uint32_t*)(tp[br ? 2 : 5] + moff), q5 = *(const uint32_t*)(tp[br ? 3 : 6] + moff);

  for (int i = wtid & 63; i < R_BR / 16; i += 64) sts128(cb + R_OFF + br * R_BR + i * 16, 0, 0, 0, 0);
  STAMP(1);

  float acc[5][4];
  float k2048 = 0.f;
  const uint32_t scr = cb + Y0_OFF + wq * SCR_BYTES;
  const uint32_t scr2 = sb + XIN_OFF + warp * 640;
  {
    const uint32_t ldt2 = (ch & 2) ? ldt4.y : ldt4.x;
    const float dt = bf_round(expf((ch & 1) ? bf_hi(ldt2) : bf_lo(ldt2)));
#pragma unroll
    for (int i = 0; i < 5; i++) acc[i][0] = acc[i][1] = acc[i][2] = acc[i][3] = 0.f;
    cf cc[2], zz1[2], zz128[2];
#pragma unroll
    for (int r = 0; r < 2; r++) {
      float v0 = r ? bf_hi(q0) : bf_lo(q0), v1 = r ? bf_hi(q1) : bf_lo(q1), v2 = r ? bf_hi(q2) : bf_lo(q2);
      float v3 = r ? bf_hi(q3) : bf_lo(q3), v4 = r ? bf_hi(q4) : bf_lo(q4), v5 = r ? bf_hi(q5) : bf_lo(q5);
      if (br == 0) { cc[r] = cmul(cf{v2, v3}, cf{dt * v4, dt * v5}); }
      else { v0 = -bf_round(expf(v0)); cc[r] = cf{2.f * dt * v2, 2.f * dt * v3}; }
      const float xl = (dt * v0) * 1.4426950408889634f, y = dt * v1;
      zz1[r] = cexp_p(xl, y, 1.f); zz128[r] = cexp_p(xl, y, 128.f);
    }
    STAMP(2);
    const uint32_t tb = scr + lane * 16;
    const uint32_t ta = scr + (lane >> 3) * 512 + (lane & 7) * 16;
    const uint32_t tc = ((lane & 8) ? scr2 : scr + 4096) + (lane >> 4) * 128 + (lane & 7) * 16;
    const uint32_t tm = scr2 + 512 + ((lane >> 3) & 1) * 64 + (lane >> 4) * 16;
#pragma unroll 1
    for (int r = 0; r < 2; r++) {
      const cf c = r ? cc[1] : cc[0], z1 = r ? zz1[1] : zz1[0], z128 = r ? zz128[1] : zz128[0];
      const cf z2 = csq(z1), z4 = csq(z2), z8 = csq(z4);
      const cf z16 = csq(z8), z24 = cmul(z16, z8), z32 = csq(z16), z40 = cmul(z32, z8), z48 = csq(z24), z56 = cmul(z32, z24), z64 = csq(z32);
      const cf z256 = csq(z128), z512 = csq(z256), z1024 = csq(z512), z2048 = csq(z1024);
      {
        float kk = fmaf(c.re, z2048.re, -c.im * z2048.im);
#pragma unroll
        for (int o = 16; o; o >>= 1) kk += __shfl_xor_sync(0xffffffffu, kk, o);
        k2048 += kk;
      }
      __syncwarp();
      {
        uint32_t xr[4] = {pack_bf16(1.f, z8.re), pack_bf16(z16.re, z24.re), pack_bf16(z32.re, z40.re), pack_bf16(z48.re, z56.re)};
        uint32_t xi[4] = {pack_bf16(0.f, -z8.im), pack_bf16(-z16.im, -z24.im), pack_bf16(-z32.im, -z40.im), pack_bf16(-z48.im, -z56.im)};
        sts128(tb + 0 * 512, xr[0], xr[1], xr[2], xr[3]);
        sts128(tb + 2 * 512, xi[0], xi[1], xi[2], xi[3]);
        const uint32_t yr = pack_bf16(z64.re, z64.re), nyi = pack_bf16(z64.im, z64.im), yi = nyi ^ 0x80008000u;
        uint32_t o[4], q[4];
#pragma unroll
        for (int i = 0; i < 4; i++) CMUL2(o[i], q[i], xr[i], xi[i], yr, yi, nyi);
        sts128(tb + 1 * 512, o[0], o[1], o[2], o[3]);
        sts128(tb + 3 * 512, q[0], q[1], q[2], q[3]);
      }
      {
        const cf h1 = cmul(c, z128), h2 = cmul(c, z256), h3 = cmul(h1, z256), h4 = cmul(c, z512), h5 = cmul(h1, z512), h6 = cmul(h2, z512), h7 = cmul(h3, z512);
        const cf e1 = cmul(c, z1), e2 = cmul(c, z2), e3 = cmul(e1, z2), e129 = cmul(h1, z1), e130 = cmul(h1, z2), e131 = cmul(e129, z2);
        const cf e258 = cmul(h2, z2), e386 = cmul(h3, z2);
        const uint32_t pr0 = pack_bf16(c.re, e1.re), pr2 = pack_bf16(h1.re, e129.re), pi0 = pack_bf16(c.im, e1.im), pi2 = pack_bf16(h1.im, e129.im);
        sts128(tb + 4 * 512, pr0, pack_bf16(e2.re, e3.re), pr2, pack_bf16(e130.re, e131.re));
        sts128(tb + 5 * 512, pi0, pack_bf16(e2.im, e3.im), pi2, pack_bf16(e130.im, e131.im));
        uint32_t xr[4] = {pack_bf16(h2.re, e258.re), pack_bf16(h3.re, e386.re), pack_bf16(h4.re, h5.re), pack_bf16(h6.re, h7.re)};
        uint32_t xi[4] = {pack_bf16(h2.im, e258.im), pack_bf16(h3.im, e386.im), pack_bf16(h4.im, h5.im), pack_bf16(h6.im, h7.im)};
        sts128(tb + 6 * 512, xr[0], xr[1], xr[2], xr[3]);
        sts128(tb + 7 * 512, xi[0], xi[1], xi[2], xi[3]);
        xr[1] = __byte_perm(xr[0], xr[1], 0x5410); xi[1] = __byte_perm(xi[0], xi[1], 0x5410);
        xr[0] = __byte_perm(pr0, pr2, 0x5410); xi[0] = __byte_perm(pi0, pi2, 0x5410);
        const uint32_t yr = pack_bf16(z1024.re, z1024.re), yi = pack_bf16(z1024.im, z1024.im), nyi = yi ^ 0x80008000u;
        uint32_t o[4], q[4];
#pragma unroll
        for (int i = 0; i < 4; i++) CMUL2(o[i], q[i], xr[i], xi[i], yr, yi, nyi);
        sts128(tb + 8 * 512, o[0], o[1], o[2], o[3]);
        sts128(scr2 + lane * 16, q[0], q[1], q[2], q[3]);
        const uint32_t m4 = pack_bf16(z4.re, z4.im);
        sts16(scr2 + 512 + lane * 2, m4); sts16(scr2 + 576 + lane * 2, m4 >> 16);
      }
      __syncwarp();
#pragma unroll
      for (int kp = 0; kp < 2; kp++) {
        uint32_t rr[2], ri[2], yr[2], yi[2];
        ldsm4t(tc + kp * 256, rr[0], ri[0], rr[1], ri[1]);
        ldsm4(tm + kp * 32, yr[0], yi[0], yr[1], yi[1]);
#pragma unroll
        for (int k2 = 0; k2 < 2; k2++) {
          const int kk = kp * 2 + k2;
          uint32_t a0, a1, a2, a3, pr, pi, qr, qi, xr, xi;
          ldsm4t(ta + kk * 128, a0, a1, a2, a3);
          ldsm4t(ta + 2048 + kk * 128, pr, pi, qr, qi);
          const uint32_t nyi = yi[k2] ^ 0x80008000u;
          mma16816(acc[0], a0, a1, a2, a3, pr, pi);
          mma16816(acc[2], a0, a1, a2, a3, qr, qi);
          mma16816(acc[4], a0, a1, a2, a3, rr[k2], ri[k2]);
          CMUL2(xr, xi, pr, pi, yr[k2], yi[k2], nyi);
          mma16816(acc[1], a0, a1, a2, a3, xr, xi);
          CMUL2(xr, xi, qr, qi, yr[k2], yi[k2], nyi);
          mma16816(acc[3], a0, a1, a2, a3, xr, xi);
        }
      }
    }
  }
  STAMP(3);
  __syncwarp();
  {
    const uint32_t xs = scr + lane * 16;
#define OTH(i, k) __float_as_uint(hf ? acc[i][k] : acc[i][2 + (k)])
    sts128(xs, OTH(0, 0), OTH(0, 1), OTH(1, 0), OTH(1, 1));
    sts128(xs + 512, OTH(2, 0), OTH(2, 1), OTH(3, 0), OTH(3, 1));
    sts128(xs + 1024, OTH(4, 0), OTH(4, 1), __float_as_uint(k2048), 0);
#undef OTH
  }

  bar_sync(7 + (warp >> 1), 64);
  STAMP(4);
  {
    const uint32_t xo = cb + Y0_OFF + (wq ^ 1) * SCR_BYTES + lane * 16;
    const uint4 o0 = lds128(xo), o1 = lds128(xo + 512), o2 = lds128(xo + 1024);
    const uint32_t rb = cb + R_OFF + br * R_BR;
#define OWN(i, k) (hf ? acc[i][2 + (k)] : acc[i][k])
    const uint32_t vP = pack_bf16(OWN(0, 1) + __uint_as_float(o0.y), OWN(0, 0) + __uint_as_float(o0.x));
    const uint32_t vP4 = pack_bf16(OWN(1, 1) + __uint_as_float(o0.w), OWN(1, 0) + __uint_as_float(o0.z));
    const uint32_t vQ = pack_bf16(OWN(2, 1) + __uint_as_float(o1.y), OWN(2, 0) + __uint_as_float(o1.x));
    const uint32_t vQ4 = pack_bf16(OWN(3, 1) + __uint_as_float(o1.w), OWN(3, 0) + __uint_as_float(o1.z));
    const uint32_t vR = pack_bf16(OWN(4, 1) + __uint_as_float(o2.y), OWN(4, 0) + __uint_as_float(o2.x));
#undef OWN
    const int j = g + 8 * hf;
    {
      const int a = 2 * (t & 1) + 64 * (t & 2) + 8 * j;
      const uint32_t ad = rb + 2 * (RD_X0 - 1 - a);
      const uint32_t a1 = (t & 2) ? ad - 8 : ad, a2 = (t & 2) ? ad : ad - 8;
      const uint32_t w1 = (t & 2) ? vP4 : vP, w2 = (t & 2) ? vP : vP4;
      sts32(a1, w1); sts32(a2, w2);
      sts16(a1 + RD_CS + 2, w1); sts16(a1 + RD_CS + 4, w1 >> 16);
      sts16(a2 + RD_CS + 2, w2); sts16(a2 + RD_CS + 4, w2 >> 16);
    }
    if (t < 2) {
      const int b = 256 + 128 * t + 8 * j;
      const uint32_t ad = rb + 2 * (RD_X0 - 6 - b);
      const uint32_t v22 = __byte_perm(vQ4, 0, 0x3232), v00 = __byte_perm(vQ, 0, 0x3232);
      sts16(ad, vQ4);
      sts64(ad + 2, v22, __byte_perm(vQ4, vQ, 0x5432));
      sts32(ad + 10, v00);
      if (b != 256) { sts16(ad + 14, v00); sts128(ad + RD_CS + 2, vQ4, v22, vQ, v00); }
      else { sts64(ad + RD_CS + 2, vQ4, v22); sts32(ad + RD_CS + 10, vQ); sts16(ad + RD_CS + 14, v00); }
    } else {
      const uint32_t ao = rb + R_O2 + 2 * (159 - (32 * t + j)), ae = ao - (R_O2 - R_E2) + 2;
      sts16(ao, vQ4 >> 16); sts16(ao + RS_CS + 2, vQ4 >> 16); sts16(ao - 32, vQ4); sts16(ao - 32 + RS_CS + 2, vQ4);
      sts16(ae - 32, vQ); sts16(ae - 32 + RS_CS + 2, vQ);
      if (lane != 2 || hf) { sts16(ae, vQ >> 16); sts16(ae + RS_CS + 2, vQ >> 16); }
      else {
        const uint32_t vv = __byte_perm(vQ, 0, 0x3232), ad = rb + 2 * (RD_X0 - 514);
        sts16(ad, vv); sts32(ad + 2, vv); sts16(ad + 6, vv); sts64(ad + RD_CS + 2, vv, vv);
      }
    }
    {
      const uint32_t a = rb + ((g & 1) ? R_O3 : R_E3 + 2) + 2 * (159 - (64 + 16 * t + (j >> 1)));
      const bool p1024 = (lane == 0) && (hf == 0);
      const uint32_t a00 = p1024 ? rb + R_E2 + 2 * (159 - 127) : a;
      sts16(a00, vR >> 16); sts16(a00 + RS_CS + 2, vR >> 16);
      sts16(a - 16, vR); sts16(a - 16 + RS_CS + 2, vR);
      if (p1024) {
        sts32(sb + K1024_OFF + (ch * 2 + br) * 4, __byte_perm(vR, 0, 0x3232));
        const uint32_t kv = pack_bf16(k2048 + __uint_as_float(o2.z), 0.f);
        sts16(rb + R_E3 + 2 * (159 - 127), kv); sts16(rb + R_E3 + 2 * (159 - 127) + RS_CS + 2, kv);
      }
    }
  }
  STAMP(5);
  asm volatile("barrier.cluster.wait.aligned;" ::: "memory");
  bar_sync(7 + (warp >> 1), 64);
  mbar_wait(sb + B_U);
  STAMP(6);

  const uint32_t zz = lds32(cb + R_OFF + br * R_BR);
  conv_dense(cb, zz);
  const uint2 dA = ldg64(p.A_D + bid * 4), dB = ldg64(p.B_D + bid * 4);
  const uint2 gl = gate_ld((4 + ch) * 128 + wtid);
  mbar_wait(sb + B_W);
  conv_far(sb, cb, zz);
  STAMP(10);
  __syncwarp();
  if (lane == 0) asm volatile("mbarrier.arrive.shared::cta.b64 _, [%0];" ::"r"(sb + B_Y3) : "memory");

  {
    const int x = (4 + ch) * 128 + wtid, c = x >> 2;
    const uint32_t g2 = gate_fin(p, gl, x, lds32(sb + TAG_OFF));
    const uint32_t yo = sb + CH_OFF + (x & 3) * 4 + ysw(c);
    uint32_t ua[4], ub[4], ya[4], yb[4], a2[4], b2[4], a3[4], b3[4], s2[4];
    skip_terms(ua, ub, sb, x, dA, dB);
    ld4ch(s2, sb + CH_OFF + (x & 3) * 4 + S2_OFF + ((c - 128) + ((c - 128) >> 3)) * 16);
    mbar_wait(sb + B_Y2);
    const uint4 k0 = lds128(sb + K1024_OFF), k1 = lds128(sb + K1024_OFF + 16);
    const uint32_t kk[8] = {k0.x, k0.y, k0.z, k0.w, k1.x, k1.y, k1.z, k1.w};
    ld4ch(ya, yo + Y0_OFF); ld4ch(yb, yo + Y0_OFF + 4096);
    ld4ch(a2, yo + Y2_OFF - 1024); ld4ch(b2, yo + Y2_OFF - 1024 + 3072);
#pragma unroll
    for (int k = 0; k < 4; k++) { a2[k] = hfma2(kk[2 * k], s2[k], a2[k]); b2[k] = hfma2(kk[2 * k + 1], s2[k], b2[k]); }
    STAMP(11);
    mbar_wait(sb + B_Y3);
    STAMP(12);
    ld4ch(a3, yo + Y3_OFF - 2048); ld4ch(b3, yo + Y3_OFF - 2048 + 2048);
#pragma unroll
    for (int k = 0; k < 4; k++) { ya[k] = hadd2(ya[k], hadd2(a2[k], a3[k])); yb[k] = hadd2(yb[k], hadd2(b2[k], b3[k])); }
    const uint4 r = mix(ya, yb, ua, ub, g2);
    if ((uint32_t)(ch & 1) != rank) send_box(sb, 2 + (ch >> 1), wtid, rank, r);
    else merge_box(sb, &tm_out, 2 + (ch >> 1), wtid, rank, oc0, r, 1 + ch);
  }
  STAMP(14);
  if (wtid == 0) asm volatile("cp.async.bulk.wait_group.read 0;" ::: "memory");
  STAMP(15); GT(1);
}

typedef CUresult (*EncodeFn)(CUtensorMap*, CUtensorMapDataType, cuuint32_t, void*, const cuuint64_t*, const cuuint64_t*,
                             const cuuint32_t*, const cuuint32_t*, CUtensorMapInterleave, CUtensorMapSwizzle,
                             CUtensorMapL2promotion, CUtensorMapFloatOOBfill);

}

extern "C" void kernel_launch(void* const* d_in, const int* in_sizes, int n_in, void* d_out, int out_size) {
  (void)in_sizes; (void)n_in; (void)out_size;
  typedef const __nv_bfloat16* bp;
  Params p;
  p.t[0] = (bp)d_in[10]; p.t[1] = (bp)d_in[11]; p.t[2] = (bp)d_in[12]; p.t[3] = (bp)d_in[13]; p.t[4] = (bp)d_in[14]; p.t[5] = nullptr;
  p.t[6] = (bp)d_in[1]; p.t[7] = (bp)d_in[2]; p.t[8] = (bp)d_in[5]; p.t[9] = (bp)d_in[6]; p.t[10] = (bp)d_in[7];
  p.t[11] = (bp)d_in[3]; p.t[12] = (bp)d_in[4]; p.t[13] = nullptr;
  p.u = (bp)d_in[0]; p.gw = (bp)d_in[16]; p.A_D = (bp)d_in[8]; p.B_D = (bp)d_in[15];
  static EncodeFn enc = nullptr;
  if (!enc) {
    cudaDriverEntryPointQueryResult qr;
    cudaGetDriverEntryPoint("cuTensorMapEncodeTiled", (void**)&enc, cudaEnableDefault, &qr);
    cudaFuncSetAttribute(ssm_kernel, cudaFuncAttributeMaxDynamicSharedMemorySize, SMEM_BYTES);
  }
  CUtensorMap tm_in, tm_out;
  {
    cuuint64_t gd[5] = {512, 2, 4, 4, 64};
    cuuint64_t gs[4] = {1024, 8192, 2048, 32768};
    cuuint32_t bx[5] = {8, 2, 4, 4, 32};
    cuuint32_t es[5] = {1, 1, 1, 1, 1};
    enc(&tm_in, CU_TENSOR_MAP_DATA_TYPE_BFLOAT16, 5, d_in[0], gd, gs, bx, es, CU_TENSOR_MAP_INTERLEAVE_NONE,
        CU_TENSOR_MAP_SWIZZLE_NONE, CU_TENSOR_MAP_L2_PROMOTION_NONE, CU_TENSOR_MAP_FLOAT_OOB_FILL_NONE);
  }
  {
    cuuint64_t gd[3] = {512, 1024, 2};
    cuuint64_t gs[2] = {2048, 1024};
    cuuint32_t bx[3] = {8, 128, 2};
    cuuint32_t es[3] = {1, 1, 1};
    enc(&tm_out, CU_TENSOR_MAP_DATA_TYPE_BFLOAT16, 3, d_out, gd, gs, bx, es, CU_TENSOR_MAP_INTERLEAVE_NONE,
        CU_TENSOR_MAP_SWIZZLE_NONE, CU_TENSOR_MAP_L2_PROMOTION_NONE, CU_TENSOR_MAP_FLOAT_OOB_FILL_NONE);
  }
  ssm_kernel<<<NCTA + NGATE, 640, SMEM_BYTES, cudaStreamPerThread>>>(p, tm_in, tm_out);
}
```

```cpp
#include <cuda_runtime.h>
#include <cuda.h>
#include <cuda_bf16.h>
#include <stdint.h>

namespace {
#define FIXA 0
#define FIXB 1
#define CPY(x) (x)
#define FCPY(x) __uint_as_float(opq(__float_as_uint(x), zz))

constexpr int L = 2048, D = 512, NM = 128;
constexpr int NCTA = 128;
constexpr int NGATE = 4;

constexpr int RAW_OFF = 0;
constexpr int XIN_OFF = 32768;
constexpr int BAR_OFF = XIN_OFF + 10240;
constexpr int CH_OFF = BAR_OFF + 128;
constexpr int U_CS = 1184;
constexpr int U_OFF = 0;
constexpr int R_OFF = 4736;
constexpr int RD_X0 = 565;
constexpr int RD_CS = 1216;
constexpr int RS_CS = 320;
constexpr int R_E2 = 2 * RD_CS, R_O2 = R_E2 + 2 * RS_CS, R_E3 = R_O2 + 2 * RS_CS, R_O3 = R_E3 + 2 * RS_CS;
constexpr int R_BR = R_O3 + 2 * RS_CS;
constexpr int W5_OFF = R_OFF + 2 * R_BR;
constexpr int W3_OFF = W5_OFF + 3456;
constexpr int W9_OFF = W3_OFF + 3456;
constexpr int W7_OFF = W9_OFF + 2304;
constexpr int S2_OFF = W7_OFF + 2304;
constexpr int Y0_OFF = S2_OFF + 2304;
constexpr int Y2_OFF = Y0_OFF + 8192, Y3_OFF = Y2_OFF + 6144;
constexpr int CH_BYTES = Y0_OFF + 18432 + 16;
constexpr int SCR_BYTES = 4608;
constexpr int SMEM_BYTES = CH_OFF + 4 * CH_BYTES;
static_assert(CH_BYTES % 128 == 16, "bank staggering of the channel blocks");
static_assert(SMEM_BYTES <= 232448, "smem");
constexpr int B_RAW = BAR_OFF, B_X = BAR_OFF + 8, B_U = BAR_OFF + 40, B_W = BAR_OFF + 48, B_Y2 = BAR_OFF + 56, B_Y3 = BAR_OFF + 96;
constexpr int TAG_OFF = BAR_OFF + 104;
constexpr int K1024_OFF = BAR_OFF + 64;

__device__ unsigned int g_gate[L];
__device__ unsigned int g_epoch;
__device__ unsigned int g_ticket;

#define STAMP(k)
#define GT(k)

struct Params {
  const __nv_bfloat16* t[14];
  const __nv_bfloat16 *u, *gw, *A_D, *B_D;
};

template <int N, int TB> __device__ __forceinline__ void wgmma_rs(float* d, uint32_t a0, uint32_t a1, uint32_t a2, uint32_t a3, uint64_t desc, int sc);
template <> __device__ __forceinline__ void wgmma_rs<64, 0>(float* d, uint32_t a0, uint32_t a1, uint32_t a2, uint32_t a3, uint64_t desc, int sc) {
  asm volatile("{\n.reg .pred p;\nsetp.ne.b32 p, %37, 0;\n"
    "wgmma.mma_async.sync.aligned.m64n64k16.f32.bf16.bf16 {%0,%1,%2,%3,%4,%5,%6,%7,%8,%9,%10,%11,%12,%13,%14,%15,%16,%17,%18,%19,%20,%21,%22,%23,%24,%25,%26,%27,%28,%29,%30,%31}, {%32,%33,%34,%35}, %36, p, 1, 1, 0;\n}"
    : "+f"(d[0]), "+f"(d[1]), "+f"(d[2]), "+f"(d[3]), "+f"(d[4]), "+f"(d[5]), "+f"(d[6]), "+f"(d[7]), "+f"(d[8]), "+f"(d[9]), "+f"(d[10]), "+f"(d[11]), "+f"(d[12]), "+f"(d[13]), "+f"(d[14]), "+f"(d[15]), "+f"(d[16]), "+f"(d[17]), "+f"(d[18]), "+f"(d[19]), "+f"(d[20]), "+f"(d[21]), "+f"(d[22]), "+f"(d[23]), "+f"(d[24]), "+f"(d[25]), "+f"(d[26]), "+f"(d[27]), "+f"(d[28]), "+f"(d[29]), "+f"(d[30]), "+f"(d[31]) : "r"(a0), "r"(a1), "r"(a2), "r"(a3), "l"(desc), "r"(sc));
}
template <> __device__ __forceinline__ void wgmma_rs<56, 0>(float* d, uint32_t a0, uint32_t a1, uint32_t a2, uint32_t a3, uint64_t desc, int sc) {
  asm volatile("{\n.reg .pred p;\nsetp.ne.b32 p, %33, 0;\n"
    "wgmma.mma_async.sync.aligned.m64n56k16.f32.bf16.bf16 {%0,%1,%2,%3,%4,%5,%6,%7,%8,%9,%10,%11,%12,%13,%14,%15,%16,%17,%18,%19,%20,%21,%22,%23,%24,%25,%26,%27}, {%28,%29,%30,%31}, %32, p, 1, 1, 0;\n}"
    : "+f"(d[0]), "+f"(d[1]), "+f"(d[2]), "+f"(d[3]), "+f"(d[4]), "+f"(d[5]), "+f"(d[6]), "+f"(d[7]), "+f"(d[8]), "+f"(d[9]), "+f"(d[10]), "+f"(d[11]), "+f"(d[12]), "+f"(d[13]), "+f"(d[14]), "+f"(d[15]), "+f"(d[16]), "+f"(d[17]), "+f"(d[18]), "+f"(d[19]), "+f"(d[20]), "+f"(d[21]), "+f"(d[22]), "+f"(d[23]), "+f"(d[24]), "+f"(d[25]), "+f"(d[26]), "+f"(d[27]) : "r"(a0), "r"(a1), "r"(a2), "r"(a3), "l"(desc), "r"(sc));
}
template <> __device__ __forceinline__ void wgmma_rs<48, 0>(float* d, uint32_t a0, uint32_t a1, uint32_t a2, uint32_t a3, uint64_t desc, int sc) {
  asm volatile("{\n.reg .pred p;\nsetp.ne.b32 p, %29, 0;\n"
    "wgmma.mma_async.sync.aligned.m64n48k16.f32.bf16.bf16 {%0,%1,%2,%3,%4,%5,%6,%7,%8,%9,%10,%11,%12,%13,%14,%15,%16,%17,%18,%19,%20,%21,%22,%23}, {%24,%25,%26,%27}, %28, p, 1, 1, 0;\n}"
    : "+f"(d[0]), "+f"(d[1]), "+f"(d[2]), "+f"(d[3]), "+f"(d[4]), "+f"(d[5]), "+f"(d[6]), "+f"(d[7]), "+f"(d[8]), "+f"(d[9]), "+f"(d[10]), "+f"(d[11]), "+f"(d[12]), "+f"(d[13]), "+f"(d[14]), "+f"(d[15]), "+f"(d[16]), "+f"(d[17]), "+f"(d[18]), "+f"(d[19]), "+f"(d[20]), "+f"(d[21]), "+f"(d[22]), "+f"(d[23]) : "r"(a0), "r"(a1), "r"(a2), "r"(a3), "l"(desc), "r"(sc));
}
template <> __device__ __forceinline__ void wgmma_rs<32, 0>(float* d, uint32_t a0, uint32_t a1, uint32_t a2, uint32_t a3, uint64_t desc, int sc) {
  asm volatile("{\n.reg .pred p;\nsetp.ne.b32 p, %21, 0;\n"
    "wgmma.mma_async.sync.aligned.m64n32k16.f32.bf16.bf16 {%0,%1,%2,%3,%4,%5,%6,%7,%8,%9,%10,%11,%12,%13,%14,%15}, {%16,%17,%18,%19}, %20, p, 1, 1, 0;\n}"
    : "+f"(d[0]), "+f"(d[1]), "+f"(d[2]), "+f"(d[3]), "+f"(d[4]), "+f"(d[5]), "+f"(d[6]), "+f"(d[7]), "+f"(d[8]), "+f"(d[9]), "+f"(d[10]), "+f"(d[11]), "+f"(d[12]), "+f"(d[13]), "+f"(d[14]), "+f"(d[15]) : "r"(a0), "r"(a1), "r"(a2), "r"(a3), "l"(desc), "r"(sc));
}
template <> __device__ __forceinline__ void wgmma_rs<48, 1>(float* d, uint32_t a0, uint32_t a1, uint32_t a2, uint32_t a3, uint64_t desc, int sc) {
  asm volatile("{\n.reg .pred p;\nsetp.ne.b32 p, %29, 0;\n"
    "wgmma.mma_async.sync.aligned.m64n48k16.f32.bf16.bf16 {%0,%1,%2,%3,%4,%5,%6,%7,%8,%9,%10,%11,%12,%13,%14,%15,%16,%17,%18,%19,%20,%21,%22,%23}, {%24,%25,%26,%27}, %28, p, 1, 1, 1;\n}"
    : "+f"(d[0]), "+f"(d[1]), "+f"(d[2]), "+f"(d[3]), "+f"(d[4]), "+f"(d[5]), "+f"(d[6]), "+f"(d[7]), "+f"(d[8]), "+f"(d[9]), "+f"(d[10]), "+f"(d[11]), "+f"(d[12]), "+f"(d[13]), "+f"(d[14]), "+f"(d[15]), "+f"(d[16]), "+f"(d[17]), "+f"(d[18]), "+f"(d[19]), "+f"(d[20]), "+f"(d[21]), "+f"(d[22]), "+f"(d[23]) : "r"(a0), "r"(a1), "r"(a2), "r"(a3), "l"(desc), "r"(sc));
}
template <> __device__ __forceinline__ void wgmma_rs<40, 1>(float* d, uint32_t a0, uint32_t a1, uint32_t a2, uint32_t a3, uint64_t desc, int sc) {
  asm volatile("{\n.reg .pred p;\nsetp.ne.b32 p, %25, 0;\n"
    "wgmma.mma_async.sync.aligned.m64n40k16.f32.bf16.bf16 {%0,%1,%2,%3,%4,%5,%6,%7,%8,%9,%10,%11,%12,%13,%14,%15,%16,%17,%18,%19}, {%20,%21,%22,%23}, %24, p, 1, 1, 1;\n}"
    : "+f"(d[0]), "+f"(d[1]), "+f"(d[2]), "+f"(d[3]), "+f"(d[4]), "+f"(d[5]), "+f"(d[6]), "+f"(d[7]), "+f"(d[8]), "+f"(d[9]), "+f"(d[10]), "+f"(d[11]), "+f"(d[12]), "+f"(d[13]), "+f"(d[14]), "+f"(d[15]), "+f"(d[16]), "+f"(d[17]), "+f"(d[18]), "+f"(d[19]) : "r"(a0), "r"(a1), "r"(a2), "r"(a3), "l"(desc), "r"(sc));
}
template <> __device__ __forceinline__ void wgmma_rs<32, 1>(float* d, uint32_t a0, uint32_t a1, uint32_t a2, uint32_t a3, uint64_t desc, int sc) {
  asm volatile("{\n.reg .pred p;\nsetp.ne.b32 p, %21, 0;\n"
    "wgmma.mma_async.sync.aligned.m64n32k16.f32.bf16.bf16 {%0,%1,%2,%3,%4,%5,%6,%7,%8,%9,%10,%11,%12,%13,%14,%15}, {%16,%17,%18,%19}, %20, p, 1, 1, 1;\n}"
    : "+f"(d[0]), "+f"(d[1]), "+f"(d[2]), "+f"(d[3]), "+f"(d[4]), "+f"(d[5]), "+f"(d[6]), "+f"(d[7]), "+f"(d[8]), "+f"(d[9]), "+f"(d[10]), "+f"(d[11]), "+f"(d[12]), "+f"(d[13]), "+f"(d[14]), "+f"(d[15]) : "r"(a0), "r"(a1), "r"(a2), "r"(a3), "l"(desc), "r"(sc));
}
template <> __device__ __forceinline__ void wgmma_rs<16, 1>(float* d, uint32_t a0, uint32_t a1, uint32_t a2, uint32_t a3, uint64_t desc, int sc) {
  asm volatile("{\n.reg .pred p;\nsetp.ne.b32 p, %13, 0;\n"
    "wgmma.mma_async.sync.aligned.m64n16k16.f32.bf16.bf16 {%0,%1,%2,%3,%4,%5,%6,%7}, {%8,%9,%10,%11}, %12, p, 1, 1, 1;\n}"
    : "+f"(d[0]), "+f"(d[1]), "+f"(d[2]), "+f"(d[3]), "+f"(d[4]), "+f"(d[5]), "+f"(d[6]), "+f"(d[7]) : "r"(a0), "r"(a1), "r"(a2), "r"(a3), "l"(desc), "r"(sc));
}

__device__ __forceinline__ uint32_t pack_bf16(float lo, float hi) {
  uint32_t r; asm("cvt.rn.bf16x2.f32 %0, %1, %2;" : "=r"(r) : "f"(hi), "f"(lo)); return r;
}
__device__ __forceinline__ float bf_lo(uint32_t v) { return __uint_as_float(v << 16); }
__device__ __forceinline__ float bf_hi(uint32_t v) { return __uint_as_float(v & 0xffff0000u); }
__device__ __forceinline__ float bf_round(float x) { return bf_lo(pack_bf16(x, 0.f)); }
__device__ __forceinline__ uint32_t hmul2(uint32_t a, uint32_t b) { uint32_t r; asm("mul.rn.bf16x2 %0, %1, %2;" : "=r"(r) : "r"(a), "r"(b)); return r; }
__device__ __forceinline__ uint32_t hadd2(uint32_t a, uint32_t b) { uint32_t r; asm("add.rn.bf16x2 %0, %1, %2;" : "=r"(r) : "r"(a), "r"(b)); return r; }
__device__ __forceinline__ uint32_t hsub2(uint32_t a, uint32_t b) { uint32_t r; asm("sub.rn.bf16x2 %0, %1, %2;" : "=r"(r) : "r"(a), "r"(b)); return r; }
__device__ __forceinline__ uint32_t hfma2(uint32_t a, uint32_t b, uint32_t c) { uint32_t r; asm("fma.rn.bf16x2 %0, %1, %2, %3;" : "=r"(r) : "r"(a), "r"(b), "r"(c)); return r; }

__device__ __forceinline__ void sts16(uint32_t a, uint32_t v) { asm volatile("st.shared.b16 [%0], %1;" ::"r"(a), "h"((unsigned short)v) : "memory"); }
__device__ __forceinline__ void sts32(uint32_t a, uint32_t v) { asm volatile("st.shared.b32 [%0], %1;" ::"r"(a), "r"(v) : "memory"); }
__device__ __forceinline__ void sts64(uint32_t a, uint32_t x, uint32_t y) { asm volatile("st.shared.v2.b32 [%0], {%1,%2};" ::"r"(a), "r"(x), "r"(y) : "memory"); }
__device__ __forceinline__ void sts128(uint32_t a, uint32_t x, uint32_t y, uint32_t z, uint32_t w) {
  asm volatile("st.shared.v4.b32 [%0], {%1,%2,%3,%4};" ::"r"(a), "r"(x), "r"(y), "r"(z), "r"(w) : "memory");
}
__device__ __forceinline__ uint32_t lds32(uint32_t a) { uint32_t v; asm volatile("ld.shared.b32 %0, [%1];" : "=r"(v) : "r"(a) : "memory"); return v; }
__device__ __forceinline__ uint2 lds64(uint32_t a) { uint2 v; asm volatile("ld.shared.v2.b32 {%0,%1}, [%2];" : "=r"(v.x), "=r"(v.y) : "r"(a) : "memory"); return v; }
__device__ __forceinline__ uint4 lds128(uint32_t a) {
  uint4 v; asm volatile("ld.shared.v4.b32 {%0,%1,%2,%3}, [%4];" : "=r"(v.x), "=r"(v.y), "=r"(v.z), "=r"(v.w) : "r"(a) : "memory"); return v;
}
__device__ __forceinline__ uint4 ldg128(const void* a) {
  uint4 v; asm volatile("ld.global.nc.v4.b32 {%0,%1,%2,%3}, [%4];" : "=r"(v.x), "=r"(v.y), "=r"(v.z), "=r"(v.w) : "l"(a) : "memory"); return v;
}
__device__ __forceinline__ uint2 ldg64(const void* a) {
  uint2 v; asm volatile("ld.global.nc.v2.b32 {%0,%1}, [%2];" : "=r"(v.x), "=r"(v.y) : "l"(a) : "memory"); return v;
}
__device__ __forceinline__ void ldsm4(uint32_t a, uint32_t& r0, uint32_t& r1, uint32_t& r2, uint32_t& r3) {
  asm volatile("ldmatrix.sync.aligned.m8n8.x4.shared.b16 {%0,%1,%2,%3}, [%4];" : "=r"(r0), "=r"(r1), "=r"(r2), "=r"(r3) : "r"(a) : "memory");
}
__device__ __forceinline__ void ldsm4t(uint32_t a, uint32_t& r0, uint32_t& r1, uint32_t& r2, uint32_t& r3) {
  asm volatile("ldmatrix.sync.aligned.m8n8.x4.trans.shared.b16 {%0,%1,%2,%3}, [%4];" : "=r"(r0), "=r"(r1), "=r"(r2), "=r"(r3) : "r"(a) : "memory");
}
__device__ __forceinline__ void stsm4(uint32_t a, uint32_t r0, uint32_t r1, uint32_t r2, uint32_t r3) {
  asm volatile("stmatrix.sync.aligned.m8n8.x4.shared.b16 [%0], {%1,%2,%3,%4};" ::"r"(a), "r"(r0), "r"(r1), "r"(r2), "r"(r3) : "memory");
}
__device__ __forceinline__ void stsm4t(uint32_t a, uint32_t r0, uint32_t r1, uint32_t r2, uint32_t r3) {
  asm volatile("stmatrix.sync.aligned.m8n8.x4.trans.shared.b16 [%0], {%1,%2,%3,%4};" ::"r"(a), "r"(r0), "r"(r1), "r"(r2), "r"(r3) : "memory");
}
__device__ __forceinline__ void mma16816(float* c, uint32_t a0, uint32_t a1, uint32_t a2, uint32_t a3, uint32_t b0, uint32_t b1) {
  asm("mma.sync.aligned.m16n8k16.row.col.f32.bf16.bf16.f32 {%0,%1,%2,%3}, {%4,%5,%6,%7}, {%8,%9}, {%0,%1,%2,%3};"
      : "+f"(c[0]), "+f"(c[1]), "+f"(c[2]), "+f"(c[3]) : "r"(a0), "r"(a1), "r"(a2), "r"(a3), "r"(b0), "r"(b1));
}
__device__ __forceinline__ void bar_sync(int id, int n) { asm volatile("bar.sync %0, %1;" ::"r"(id), "r"(n) : "memory"); }
__device__ __forceinline__ void bar_arrive(int id, int n) { asm volatile("bar.arrive %0, %1;" ::"r"(id), "r"(n) : "memory"); }
__device__ __forceinline__ void wg_fence() { asm volatile("wgmma.fence.sync.aligned;" ::: "memory"); }
__device__ __forceinline__ void wg_commit() { asm volatile("wgmma.commit_group.sync.aligned;" ::: "memory"); }
__device__ __forceinline__ void wg_wait0() { asm volatile("wgmma.wait_group.sync.aligned 0;" ::: "memory"); }
__device__ __forceinline__ void fence_async() { asm volatile("fence.proxy.async.shared::cta;" ::: "memory"); }
__device__ __forceinline__ uint32_t opq(uint32_t x, uint32_t z) { uint32_t r; asm volatile("xor.b32 %0, %1, %2;" : "=r"(r) : "r"(x), "r"(z)); return r; }
__device__ __forceinline__ uint64_t mkdesc(uint32_t addr, uint32_t lbo, uint32_t sbo) {
  return (uint64_t)((addr & 0x3FFFF) >> 4) | ((uint64_t)(lbo >> 4) << 16) | ((uint64_t)(sbo >> 4) << 32);
}
__device__ __forceinline__ uint32_t mapa(uint32_t a, uint32_t rank) {
  uint32_t r; asm("mapa.shared::cluster.u32 %0, %1, %2;" : "=r"(r) : "r"(a), "r"(rank)); return r;
}
__device__ __forceinline__ void mbar_init_expect(uint32_t bar, uint32_t bytes) {
  asm volatile("mbarrier.init.shared::cta.b64 [%0], 1;" ::"r"(bar) : "memory");
  asm volatile("mbarrier.arrive.expect_tx.shared::cta.b64 _, [%0], %1;" ::"r"(bar), "r"(bytes) : "memory");
}
__device__ __forceinline__ void mbar_wait(uint32_t bar) {
#pragma unroll 1
  for (int it = 0; it < (1 << 22); it++) {
    uint32_t ok;
    asm volatile("{\n.reg .pred p;\nmbarrier.try_wait.parity.acquire.cluster.shared::cta.b64 p, [%1], 0;\nselp.u32 %0, 1, 0, p;\n}"
                 : "=r"(ok) : "r"(bar) : "memory");
    if (ok) return;
  }
  __trap();
}
__device__ __forceinline__ void st_async4(uint32_t a, uint32_t bar, uint32_t x, uint32_t y, uint32_t z, uint32_t w) {
  asm volatile("st.async.weak.shared::cluster.mbarrier::complete_tx::bytes.v4.b32 [%0], {%2,%3,%4,%5}, [%1];"
               ::"r"(a), "r"(bar), "r"(x), "r"(y), "r"(z), "r"(w) : "memory");
}

struct cf { float re, im; };
__device__ __forceinline__ cf cmul(cf a, cf b) { return {fmaf(a.re, b.re, -a.im * b.im), fmaf(a.re, b.im, a.im * b.re)}; }
__device__ __forceinline__ cf csq(cf a) { return {fmaf(a.re, a.re, -a.im * a.im), (a.re + a.re) * a.im}; }
__device__ __forceinline__ cf cexp_p(float xl, float y, float p) {
  float mag; asm("ex2.approx.ftz.f32 %0, %1;" : "=f"(mag) : "f"(xl * p));
  const float th = y * p;
  const float k = rintf(th * 0.15915494309189535f);
  float r = fmaf(k, -6.2831854820251465f, th);
  r = fmaf(k, 1.7484555314695172e-07f, r);
  return {mag * __cosf(r), mag * __sinf(r)};
}
__device__ __forceinline__ uint32_t ysw(int c) { return (uint32_t)(c ^ ((c >> 3) & 3)) * 16u; }

#define CMUL2(OR, OI, xr, xi, yr, yi, nyi) do { OR = hfma2(xr, yr, hmul2(xi, nyi)); OI = hfma2(xr, yi, hmul2(xi, yr)); } while (0)

__device__ __forceinline__ uint32_t gate_slow(const __nv_bfloat16* u, const __nv_bfloat16* gw, int row) {
  float s = 0.f;
  const uint32_t* xr = (const uint32_t*)(u + (size_t)row * D);
  const uint32_t* wr = (const uint32_t*)gw;
#pragma unroll 1
  for (int j = 0; j < D / 2; j++) { const uint32_t pr = hmul2(xr[j], wr[j]); s += bf_lo(pr); s += bf_hi(pr); }
  s = bf_round(s);
  return pack_bf16(1.f / (1.f + expf(-s)), 0.f);
}

__device__ __forceinline__ uint2 gate_ld(int x) {
  uint2 gv;
  asm volatile("ld.relaxed.gpu.global.v2.u32 {%0,%1}, [%2];" : "=r"(gv.x), "=r"(gv.y) : "l"(g_gate + x * 2) : "memory");
  return gv;
}
__device__ __noinline__ uint32_t gate_poll(const __nv_bfloat16* u, const __nv_bfloat16* gw, int x, uint32_t tag) {
  uint2 gv;
#pragma unroll 1
  for (int spins = 0; spins < (1 << 16); spins++) {
    gv = gate_ld(x);
    if ((gv.x >> 16) == tag && (gv.y >> 16) == tag) return __byte_perm(gv.x, gv.y, 0x5410);
  }
  return __byte_perm(gate_slow(u, gw, x * 2), gate_slow(u, gw, x * 2 + 1), 0x5410);
}
__device__ __forceinline__ uint32_t gate_fin(const Params& p, uint2 gv, int x, uint32_t tag) {
  if ((gv.x >> 16) == tag && (gv.y >> 16) == tag) return __byte_perm(gv.x, gv.y, 0x5410);
  return gate_poll(p.u, p.gw, x, tag);
}

__device__ __forceinline__ void ld4ch(uint32_t* v, uint32_t addr) {
#pragma unroll
  for (int k = 0; k < 4; k++) v[k] = lds32(addr + k * CH_BYTES);
}
__device__ __forceinline__ void skip_terms(uint32_t* ua, uint32_t* ub, uint32_t sb, int x, uint2 dA, uint2 dB) {
  const int c = x >> 2;
  uint32_t uu[4];
  ld4ch(uu, sb + CH_OFF + (x & 3) * 4 + U_OFF + (c & 3) * U_CS + (63 - (c >> 2)) * 16);
#pragma unroll
  for (int k = 0; k < 4; k++) {
    ua[k] = hmul2(uu[k], __byte_perm((k & 2) ? dA.y : dA.x, 0, (k & 1) ? 0x3232 : 0x1010));
    ub[k] = hmul2(uu[k], __byte_perm((k & 2) ? dB.y : dB.x, 0, (k & 1) ? 0x3232 : 0x1010));
  }
}
__device__ __forceinline__ uint4 mix(const uint32_t* a, const uint32_t* b, const uint32_t* ua, const uint32_t* ub, uint32_t g2) {
  const uint32_t h2 = hsub2(0x3f803f80u, g2);
  uint32_t o[4];
#pragma unroll
  for (int k = 0; k < 4; k++) o[k] = hadd2(hmul2(g2, hadd2(a[k], ua[k])), hmul2(h2, hadd2(b[k], ub[k])));
  return make_uint4(__byte_perm(o[0], o[1], 0x5410), __byte_perm(o[2], o[3], 0x5410), __byte_perm(o[0], o[1], 0x7632), __byte_perm(o[2], o[3], 0x7632));
}
__device__ __forceinline__ void send_box(uint32_t sb, int slot, int wtid, uint32_t rank, uint4 r) {
  st_async4(mapa(sb + XIN_OFF + slot * 2048 + wtid * 16, rank ^ 1), mapa(sb + B_X + slot * 8, rank ^ 1), r.x, r.y, r.z, r.w);
}
__device__ __forceinline__ void merge_box(uint32_t sb, const CUtensorMap* tm_out, int slot, int wtid, uint32_t rank, int oc0, uint4 r, int barid) {
  const uint32_t st = sb + RAW_OFF + slot * 4096 + wtid * 16;
  sts64(st + rank * 8, r.x, r.y); sts64(st + 2048 + rank * 8, r.z, r.w);
  mbar_wait(sb + B_X + slot * 8);
  const uint4 q = lds128(sb + XIN_OFF + slot * 2048 + wtid * 16);
  sts64(st + (rank ^ 1) * 8, q.x, q.y); sts64(st + 2048 + (rank ^ 1) * 8, q.z, q.w);
  fence_async();
  bar_sync(barid, 128);
  if (wtid == 0) {
    asm volatile("cp.async.bulk.tensor.3d.global.shared::cta.bulk_group [%0, {%2, %3, %4}], [%1];"
                 ::"l"(tm_out), "r"(sb + RAW_OFF + slot * 4096), "r"(oc0), "r"((2 * slot + (int)rank) * 128), "r"(0) : "memory");
    asm volatile("cp.async.bulk.commit_group;" ::: "memory");
  }
}

__device__ __forceinline__ uint32_t band2(int e, int lo, int hi) {
  uint32_t r = ((uint32_t)(e - lo) <= (uint32_t)(hi - lo) ? 0x3f80u : 0u) | ((uint32_t)(e - 1 - lo) <= (uint32_t)(hi - lo) ? 0x3f800000u : 0u);
  asm volatile("" : "+r"(r));
  return r;
}

__device__ __forceinline__ void conv_dense(uint32_t cb, uint32_t zz) {
  const int lane = threadIdx.x & 31, wq = (threadIdx.x >> 5) & 3, br = wq >> 1, hf = wq & 1, g = lane >> 2, t = lane & 3;
  const uint32_t rb = cb + R_OFF + br * R_BR;
  const int eo = 16 * hf + g - 2 * t;
  float dacc[32];
  {
      {
        const int x0 = RD_X0 - (eo + 536);
        const uint32_t fa = rb + ((g & 1) ? 2 * x0 : RD_CS + 2 * x0 + 2);
        const uint64_t ub = mkdesc(cb + U_OFF, U_CS, 128);
        uint32_t A[2][4][4];
        float e56[28], e48[24];
        auto loadA = [&](int j) {
#pragma unroll
          for (int k = 0; k < 4; k++) {
            const int s = 34 - 4 * j - k;
            if (s >= 0) {
              if (k == 0 && j == 0) A[0][0][2] = lds32(fa + (2 * s + 2) * 16);
              A[j & 1][k][0] = lds32(fa + (2 * s + 1) * 16);
              A[j & 1][k][1] = lds32(fa + (2 * s) * 16);
            }
          }
#pragma unroll
          for (int k = 0; k < 4; k++) {
            if (34 - 4 * j - k >= 0) {
              A[j & 1][k][3] = CPY(A[j & 1][k][0]);
              if (k) A[j & 1][k][2] = CPY(A[j & 1][k - 1][1]);
              else if (j) A[j & 1][0][2] = CPY(A[(j - 1) & 1][3][1]);
            }
          }
        };
        loadA(0);
#pragma unroll
        for (int j = 0; j < 9; j++) {
          if (j == 4) {
#pragma unroll
            for (int i = 0; i < 28; i++) e56[i] = FCPY(dacc[i]);
          }
          if (j == 8) {
#pragma unroll
            for (int i = 0; i < 24; i++) e48[i] = FCPY(e56[i]);
          }
          wg_fence();
#pragma unroll
          for (int k = 0; k < 4; k++) {
            const int s = 34 - 4 * j - k;
            if (s >= 0) {
              const int o = 2 * s - 66 + 128;
              const int cc = o & 3, rs = (o >> 2) - 32;
              const int n0 = ((-rs) >> 3) * 8;
              const uint64_t desc = ub + (uint64_t)((cc * U_CS - rs * 16) >> 4);
              const uint32_t* a = A[j & 1][k];
              if (n0 == 0) wgmma_rs<64, 0>(dacc, a[0], a[1], a[2], a[3], desc, s != 34);
              else if (n0 == 8) wgmma_rs<56, 0>(FIXB ? e56 : dacc, a[0], a[1], a[2], a[3], desc, 1);
              else wgmma_rs<48, 0>(FIXB ? e48 : dacc, a[0], a[1], a[2], a[3], desc, 1);
            }
          }
          wg_commit();
          if (j < 8) loadA(j + 1);
          wg_wait0();
        }
#pragma unroll
        for (int i = 0; i < 28; i++) dacc[i] = i < 24 ? e48[i] : e56[i];
      }
      const uint32_t yb = cb + Y0_OFF + br * 4096;
#pragma unroll
      for (int i = 0; i < 8; i += 2) {
        const int mi = lane >> 3;
        const int cidx = 4 * (63 - 8 * (i + (mi >> 1)) - (lane & 7)) + 2 * hf + (mi & 1);
        stsm4t(yb + ysw(cidx), pack_bf16(dacc[4 * i], dacc[4 * i + 1]), pack_bf16(dacc[4 * i + 2], dacc[4 * i + 3]),
               pack_bf16(dacc[4 * i + 4], dacc[4 * i + 5]), pack_bf16(dacc[4 * i + 6], dacc[4 * i + 7]));
      }
      bar_arrive(6, 640);
      STAMP(8);
  }
}

__device__ __forceinline__ void conv_far(uint32_t sb, uint32_t cb, uint32_t zz) {
  const int lane = threadIdx.x & 31, wq = (threadIdx.x >> 5) & 3, br = wq >> 1, hf = wq & 1, g = lane >> 2, t = lane & 3;
  const uint32_t rb = cb + R_OFF + br * R_BR;
  const int eo = 16 * hf + g - 2 * t;
  float dacc[24], e40[20], e32[16], h32[16], h16[8];
  const int x1 = 159 - (eo + 136);
  const uint32_t fs = rb + ((g & 1) ? 2 * x1 : RS_CS + 2 * x1 + 2);
  {
    uint32_t A[2][4][4];
    auto loadA = [&](int buf, uint32_t oe, uint32_t oo, int i0) {
#pragma unroll
      for (int a = 0; a < 2; a++) {
        const uint32_t base = fs + (a ? oo : oe) + i0 * 16;
        uint32_t* k0 = A[buf][2 * a];
        uint32_t* k1 = A[buf][2 * a + 1];
        k0[1] = lds32(base); k0[0] = lds32(base + 16); k0[2] = lds32(base + 32); k1[0] = lds32(base + 48); k1[2] = lds32(base + 64);
      }
#pragma unroll
      for (int a = 0; a < 2; a++) {
        uint32_t* k0 = A[buf][2 * a];
        uint32_t* k1 = A[buf][2 * a + 1];
        k0[3] = CPY(k0[0]); k1[1] = CPY(k0[2]); k1[3] = CPY(k1[0]);
      }
    };
    const uint64_t d5 = mkdesc(cb + W5_OFF, 144, 576), d3 = mkdesc(cb + W3_OFF, 144, 576);
    loadA(0, R_E2, R_O2, 8);
#pragma unroll
    for (int m = 2; m <= 4; m++) {
      if (m == 3) {
#pragma unroll
        for (int i = 0; i < 20; i++) e40[i] = FCPY(dacc[i]);
      }
      if (m == 4) {
#pragma unroll
        for (int i = 0; i < 16; i++) e32[i] = FCPY(e40[i]);
      }
      wg_fence();
#pragma unroll
      for (int k = 0; k < 4; k++) {
        const uint32_t* a = A[m & 1][k];
        const uint64_t desc = ((k >> 1) ? d3 : d5) + (k & 1) * 18 + (m - 2) * 36;
        if (m == 2) wgmma_rs<48, 1>(dacc, a[0], a[1], a[2], a[3], desc, k);
        else if (m == 3) wgmma_rs<40, 1>(e40, a[0], a[1], a[2], a[3], desc, 1);
        else wgmma_rs<32, 1>(e32, a[0], a[1], a[2], a[3], desc, 1);
      }
      wg_commit();
      if (m < 4) loadA((m + 1) & 1, R_E2, R_O2, 4 * (3 - m));
      else loadA(1, R_E3, R_O3, 8);
      wg_wait0();
    }
#pragma unroll
    for (int i = 0; i < 20; i++) dacc[i] = i < 16 ? e32[i] : e40[i];
    {
      const uint32_t yb = cb + Y2_OFF + br * 3072;
#pragma unroll
      for (int i = 0; i < 6; i += 2) {
        const int mi = lane >> 3;
        const int cidx = 32 * (5 - i - (mi >> 1)) + 16 * hf + 8 * (mi & 1) + (lane & 7);
        stsm4(yb + ysw(cidx), pack_bf16(dacc[4 * i], dacc[4 * i + 1]), pack_bf16(dacc[4 * i + 2], dacc[4 * i + 3]),
              pack_bf16(dacc[4 * i + 4], dacc[4 * i + 5]), pack_bf16(dacc[4 * i + 6], dacc[4 * i + 7]));
      }
    }
    __syncwarp();
    if (lane == 0) asm volatile("mbarrier.arrive.shared::cta.b64 _, [%0];" ::"r"(sb + B_Y2) : "memory");
    STAMP(9);
    const uint64_t d9 = mkdesc(cb + W9_OFF, 144, 576), d7 = mkdesc(cb + W7_OFF, 144, 576);
#pragma unroll
    for (int m = 2; m <= 3; m++) {
      if (m == 3) {
#pragma unroll
        for (int i = 0; i < 8; i++) h16[i] = FCPY(h32[i]);
      }
      wg_fence();
#pragma unroll
      for (int k = 0; k < 4; k++) {
        const uint32_t* a = A[(m + 1) & 1][k];
        const uint64_t desc = ((k >> 1) ? d7 : d9) + (k & 1) * 18 + (m - 2) * 72;
        if (m == 2) wgmma_rs<32, 1>(h32, a[0], a[1], a[2], a[3], desc, k);
        else wgmma_rs<16, 1>(h16, a[0], a[1], a[2], a[3], desc, 1);
      }
      wg_commit();
      if (m == 2) loadA(0, R_E3, R_O3, 4);
      wg_wait0();
    }
#pragma unroll
    for (int i = 0; i < 16; i++) dacc[i] = i < 8 ? h16[i] : h32[i];
    const uint32_t yb = cb + Y3_OFF + br * 2048;
#pragma unroll
    for (int i = 0; i < 4; i += 2) {
      const int mi = lane >> 3;
      const int cidx = 64 * (1 - (i >> 1)) + 2 * (16 * hf + 8 * (mi & 1) + (lane & 7)) + (mi >> 1);
      stsm4(yb + ysw(cidx), pack_bf16(dacc[4 * i], dacc[4 * i + 1]), pack_bf16(dacc[4 * i + 2], dacc[4 * i + 3]),
            pack_bf16(dacc[4 * i + 4], dacc[4 * i + 5]), pack_bf16(dacc[4 * i + 6], dacc[4 * i + 7]));
    }
  }
}

__device__ __noinline__ void gate_cta(const __nv_bfloat16* u, const __nv_bfloat16* gw) {
  const int lane = threadIdx.x & 31;
  unsigned int epoch;
  asm volatile("ld.relaxed.gpu.global.u32 %0, [%1];" : "=r"(epoch) : "l"(&g_epoch) : "memory");
  const uint4 gw0 = ldg128(gw + lane * 8), gw1 = ldg128(gw + 256 + lane * 8);
  const uint32_t ws[8] = {gw0.x, gw0.y, gw0.z, gw0.w, gw1.x, gw1.y, gw1.z, gw1.w};
  const uint32_t tag = (epoch + 1) & 0xffffu;
  uint4 gx[4][2], nx[4][2];
  int grow = (blockIdx.x * 20 + (threadIdx.x >> 5)) * 4;
#pragma unroll
  for (int i = 0; i < 4; i++) {
    nx[i][0] = ldg128(u + (size_t)(grow + i) * D + lane * 8);
    nx[i][1] = ldg128(u + (size_t)(grow + i) * D + 256 + lane * 8);
  }
#pragma unroll 1
  for (; grow < L; grow += 80 * NGATE) {
    const int nrow = min(grow + 80 * NGATE, L - 4);
#pragma unroll
    for (int i = 0; i < 4; i++) {
      gx[i][0] = nx[i][0]; gx[i][1] = nx[i][1];
      nx[i][0] = ldg128(u + (size_t)(nrow + i) * D + lane * 8);
      nx[i][1] = ldg128(u + (size_t)(nrow + i) * D + 256 + lane * 8);
    }
    float sm[4];
#pragma unroll
    for (int i = 0; i < 4; i++) {
      const uint32_t xs[8] = {gx[i][0].x, gx[i][0].y, gx[i][0].z, gx[i][0].w, gx[i][1].x, gx[i][1].y, gx[i][1].z, gx[i][1].w};
      float s = 0.f;
#pragma unroll
      for (int j = 0; j < 8; j++) { const uint32_t pr = hmul2(xs[j], ws[j]); s += bf_lo(pr); s += bf_hi(pr); }
      sm[i] = s;
    }
    const bool b0 = lane & 1, b1 = lane & 2;
    float u0 = b0 ? sm[1] : sm[0], v0 = b0 ? sm[0] : sm[1], u1 = b0 ? sm[3] : sm[2], v1 = b0 ? sm[2] : sm[3];
    u0 += __shfl_xor_sync(0xffffffffu, v0, 1); u1 += __shfl_xor_sync(0xffffffffu, v1, 1);
    float s = b1 ? u1 : u0; const float v = b1 ? u0 : u1;
    s += __shfl_xor_sync(0xffffffffu, v, 2);
#pragma unroll
    for (int o = 4; o < 32; o <<= 1) s += __shfl_xor_sync(0xffffffffu, s, o);
    s = bf_round(s);
    const float gv = 1.f / (1.f + expf(-s));
    const uint32_t w = (tag << 16) | (pack_bf16(gv, 0.f) & 0xffffu);
    if (lane < 4) asm volatile("st.relaxed.gpu.global.u32 [%0], %1;" ::"l"(&g_gate[grow + lane]), "r"(w) : "memory");
  }
  __syncthreads();
  if (threadIdx.x == 0 && atomicAdd(&g_ticket, 1u) == NCTA + NGATE - 1) { g_ticket = 0; g_epoch = epoch + 1; }
}

__global__ void __cluster_dims__(2, 1, 1) __launch_bounds__(640, 1)
ssm_kernel(const Params p, const __grid_constant__ CUtensorMap tm_in, const __grid_constant__ CUtensorMap tm_out) {
  extern __shared__ __align__(1024) unsigned char smem_raw[];
  const uint32_t sb = (uint32_t)__cvta_generic_to_shared(smem_raw);
  const int tid = threadIdx.x, lane = tid & 31;
  const int warp = __shfl_sync(0xffffffffu, tid >> 5, 0);
  const int ch = warp >> 2, wq = warp & 3, br = wq >> 1, hf = wq & 1;
  const int g = lane >> 2, t = lane & 3;
  if (__builtin_expect(blockIdx.x < NGATE, 0)) { gate_cta(p.u, p.gw); return; }
  const int bid = blockIdx.x - NGATE;
  const int d = bid * 4 + ch;
  const uint32_t rank = blockIdx.x & 1;
  const uint32_t cb = sb + CH_OFF + ch * CH_BYTES;
  const int wtid = tid & 127;
  const int oc0 = (bid >> 1) * 8;
  STAMP(0); GT(0);

  if (warp >= 16) {
    if (wtid == 0) {
      mbar_init_expect(sb + B_RAW, 32768);
#pragma unroll
      for (int i = 0; i < 4; i++) mbar_init_expect(sb + B_X + 8 * i, 2048);
      asm volatile("mbarrier.init.shared::cta.b64 [%0], 128;" ::"r"(sb + B_U) : "memory");
      asm volatile("mbarrier.init.shared::cta.b64 [%0], 128;" ::"r"(sb + B_W) : "memory");
      asm volatile("mbarrier.init.shared::cta.b64 [%0], 16;" ::"r"(sb + B_Y2) : "memory");
      asm volatile("mbarrier.init.shared::cta.b64 [%0], 16;" ::"r"(sb + B_Y3) : "memory");
      asm volatile("fence.mbarrier_init.release.cluster;" ::: "memory");
      asm volatile("fence.proxy.async.shared::cta;" ::: "memory");
    }
    __syncwarp();
    asm volatile("barrier.cluster.arrive.relaxed.aligned;" ::: "memory");
    unsigned int epoch;
    asm volatile("ld.relaxed.gpu.global.u32 %0, [%1];" : "=r"(epoch) : "l"(&g_epoch) : "memory");
    asm volatile("barrier.cluster.wait.aligned;" ::: "memory");
    if (wtid == 0) {
      asm volatile("cp.async.bulk.tensor.5d.shared::cluster.global.mbarrier::complete_tx::bytes.multicast::cluster [%0], [%1, {%3, %4, %4, %4, %5}], [%2], %6;"
                   ::"r"(sb + RAW_OFF + rank * 16384), "l"(&tm_in), "r"(sb + B_RAW), "r"(oc0), "r"(0), "r"((int)rank * 32), "h"((unsigned short)3) : "memory");
    }
    sts128(sb + CH_OFF + wq * CH_BYTES + U_OFF + (lane >> 3) * U_CS + (64 + (lane & 7)) * 16, 0, 0, 0, 0);
    uint32_t BA[3][4], BC[3][4];
    {
      const int l1 = br ? 3 : 6, h1 = br ? 5 : 10;
#pragma unroll
      for (int i = 0; i < 3; i++) {
        const int e = 16 * hf + g - 2 * t + 16 - 16 * i;
        BA[i][0] = band2(e, l1, h1); BA[i][1] = band2(e + 8, l1, h1); BA[i][2] = band2(e - 8, l1, h1); BA[i][3] = BA[i][0];
        BC[i][0] = band2(e, 3, 4); BC[i][1] = band2(e + 8, 3, 4); BC[i][2] = band2(e - 8, 3, 4); BC[i][3] = BC[i][0];
      }
    }
    const uint32_t tag = (epoch + 1) & 0xffffu;
    if (wtid == 0) sts32(sb + TAG_OFF, tag);
    STAMP(3);
    mbar_wait(sb + B_RAW);
    STAMP(4);
    {
      const uint32_t dst = sb + CH_OFF + (g & 3) * CH_BYTES + U_OFF + t * U_CS + (63 - wq * 16) * 16;
#pragma unroll
      for (int h = 0; h < 2; h++) {
        uint32_t r[8][4];
#pragma unroll
        for (int i = 0; i < 8; i++) ldsm4t(sb + RAW_OFF + (wq * 16 + h * 8 + i) * 512 + lane * 16, r[i][0], r[i][1], r[i][2], r[i][3]);
        if ((uint32_t)(g >> 2) == rank) {
#pragma unroll
          for (int i = 0; i < 8; i++) sts128(dst - (h * 8 + i) * 16, r[i][0], r[i][1], r[i][2], r[i][3]);
        }
      }
    }
    fence_async();
    asm volatile("mbarrier.arrive.shared::cta.b64 _, [%0];" ::"r"(sb + B_U) : "memory");
    bar_sync(5, 128);
    STAMP(5);
    {
      const int mrow = lane & 7, mi = lane >> 3;
      const uint64_t ub0 = mkdesc(sb + CH_OFF + U_OFF, U_CS, 128);
      {
        float w1[24], w3[16];
#pragma unroll
        for (int i = 0; i < 24; i++) w1[i] = 0.f;
#pragma unroll
        for (int i = 0; i < 16; i++) w3[i] = 0.f;
        uint32_t wa[3], sa[2];
#pragma unroll
        for (int i = 0; i < 3; i++) {
          const int c = 4 * (47 - 8 * (2 * i + (mi >> 1)) - mrow) + 2 * hf + (mi & 1);
          wa[i] = sb + CH_OFF + (br ? W3_OFF : W5_OFF) + (5 - (c >> 5)) * 576 + ((c & 31) >> 3) * 144 + (c & 7) * 16;
          if (i) sa[i - 1] = sb + CH_OFF + S2_OFF + (c + (c >> 3)) * 16;
        }
#pragma unroll 1
        for (int k = 0; k < 4; k++) {
          wg_fence();
#pragma unroll
          for (int i = 0; i < 3; i++)
            wgmma_rs<48, 0>(w1, BA[i][0], BA[i][1], BA[i][2], BA[i][3],
                            ub0 + (uint64_t)((k * CH_BYTES + ((2 * i + 2) & 3) * U_CS + (16 + (i == 0)) * 16) >> 4), i);
#pragma unroll
          for (int i = 0; i < 3; i++)
            wgmma_rs<32, 0>(w3, BC[i][0], BC[i][1], BC[i][2], BC[i][3],
                            ub0 + (uint64_t)((k * CH_BYTES + ((2 * i + 2) & 3) * U_CS + (32 + (i == 0)) * 16) >> 4), i);
          wg_commit();
          wg_wait0();
#pragma unroll
          for (int i = 0; i < 3; i++)
            stsm4t(wa[i] + k * CH_BYTES, pack_bf16(w1[8 * i], w1[8 * i + 1]), pack_bf16(w1[8 * i + 2], w1[8 * i + 3]),
                   pack_bf16(w1[8 * i + 4], w1[8 * i + 5]), pack_bf16(w1[8 * i + 6], w1[8 * i + 7]));
          if (br == 0) {
#pragma unroll
            for (int i = 0; i < 2; i++)
              stsm4t(sa[i] + k * CH_BYTES, pack_bf16(w3[8 * i], w3[8 * i + 1]), pack_bf16(w3[8 * i + 2], w3[8 * i + 3]),
                     pack_bf16(w3[8 * i + 4], w3[8 * i + 5]), pack_bf16(w3[8 * i + 6], w3[8 * i + 7]));
          }
        }
      }
      {
        uint32_t BB[4][4];
        const int l2 = br ? 5 : 12, h2 = br ? 11 : 20;
#pragma unroll
        for (int i = 0; i < 4; i++) {
          const int e = 16 * hf + g - 2 * t + 32 - 16 * i;
          BB[i][0] = band2(e, l2, h2); BB[i][1] = band2(e + 8, l2, h2); BB[i][2] = band2(e - 8, l2, h2); BB[i][3] = BB[i][0];
        }
        float w2[2][16];
#pragma unroll
        for (int i = 0; i < 16; i++) { w2[0][i] = 0.f; w2[1][i] = 0.f; }
        uint32_t wa[2];
#pragma unroll
        for (int i = 0; i < 2; i++) {
          const int c = 4 * (31 - 8 * (2 * i + (mi >> 1)) - mrow) + 2 * hf + (mi & 1), pp = c >> 1;
          wa[i] = sb + CH_OFF + (br ? W7_OFF : W9_OFF) + (1 - (pp >> 5)) * 1152 + (c & 1) * 576 + ((pp & 31) >> 3) * 144 + (pp & 7) * 16;
        }
#pragma unroll 1
        for (int kp = 0; kp < 2; kp++) {
          wg_fence();
#pragma unroll
          for (int k = 0; k < 2; k++)
#pragma unroll
            for (int i = 0; i < 4; i++)
              wgmma_rs<32, 0>(w2[k], BB[i][0], BB[i][1], BB[i][2], BB[i][3],
                              ub0 + (uint64_t)(((2 * kp + k) * CH_BYTES + ((2 * i) & 3) * U_CS + (32 + (i < 2)) * 16) >> 4), i);
          wg_commit();
          wg_wait0();
#pragma unroll
          for (int k = 0; k < 2; k++)
#pragma unroll
            for (int i = 0; i < 2; i++)
              stsm4t(wa[i] + (2 * kp + k) * CH_BYTES, pack_bf16(w2[k][8 * i], w2[k][8 * i + 1]), pack_bf16(w2[k][8 * i + 2], w2[k][8 * i + 3]),
                     pack_bf16(w2[k][8 * i + 4], w2[k][8 * i + 5]), pack_bf16(w2[k][8 * i + 6], w2[k][8 * i + 7]));
        }
      }
    }
    fence_async();
    asm volatile("mbarrier.arrive.shared::cta.b64 _, [%0];" ::"r"(sb + B_W) : "memory");
    STAMP(7);
    const uint2 dA = ldg64(p.A_D + bid * 4), dB = ldg64(p.B_D + bid * 4);
    STAMP(8);
    uint32_t gg[4];
    {
      uint2 gl[4];
#pragma unroll
      for (int i = 0; i < 4; i++) gl[i] = gate_ld((i ^ (int)rank ^ 1) * 128 + wtid);
#pragma unroll
      for (int i = 0; i < 4; i++) gg[i] = gate_fin(p, gl[i], (i ^ (int)rank ^ 1) * 128 + wtid, tag);
    }
    {
      uint32_t ua[4][4], ub[4][4], ya[4][4], yb[4][4], yo[4];
#pragma unroll
      for (int i = 0; i < 4; i++) {
        const int x = (i ^ (int)rank ^ 1) * 128 + wtid;
        skip_terms(ua[i], ub[i], sb, x, dA, dB);
        yo[i] = sb + CH_OFF + (x & 3) * 4 + ysw(x >> 2);
      }
      bar_sync(6, 640);
      STAMP(10);
#pragma unroll
      for (int i = 0; i < 4; i++) { ld4ch(ya[i], yo[i] + Y0_OFF); ld4ch(yb[i], yo[i] + Y0_OFF + 4096); }
      send_box(sb, 0, wtid, rank, mix(ya[0], yb[0], ua[0], ub[0], gg[0]));
      merge_box(sb, &tm_out, 0, wtid, rank, oc0, mix(ya[1], yb[1], ua[1], ub[1], gg[1]), 5);
      STAMP(12);
      mbar_wait(sb + B_Y2);
      STAMP(11);
#pragma unroll
      for (int i = 2; i < 4; i++) { ld4ch(ya[i - 2], yo[i] + Y2_OFF - 1024); ld4ch(yb[i - 2], yo[i] + Y2_OFF - 1024 + 3072); }
#pragma unroll
      for (int i = 2; i < 4; i++)
#pragma unroll
        for (int k = 0; k < 4; k++) { ya[i][k] = hadd2(ya[i][k], ya[i - 2][k]); yb[i][k] = hadd2(yb[i][k], yb[i - 2][k]); }
      send_box(sb, 1, wtid, rank, mix(ya[2], yb[2], ua[2], ub[2], gg[2]));
      merge_box(sb, &tm_out, 1, wtid, rank, oc0, mix(ya[3], yb[3], ua[3], ub[3], gg[3]), 5);
      STAMP(13);
    }
    if (wtid == 0) {
      if (atomicAdd(&g_ticket, 1u) == NCTA + NGATE - 1) { g_ticket = 0; g_epoch = epoch + 1; }
      asm volatile("cp.async.bulk.wait_group.read 0;" ::: "memory");
    }
    STAMP(15);
    return;
  }
  asm volatile("barrier.cluster.arrive.relaxed.aligned;" ::: "memory");

  const int moff = d * NM + hf * 64 + lane * 2;
  const __nv_bfloat16* const* tp = p.t + (br ? 0 : 6);
  const uint32_t q0 = *(const uint32_t*)(tp[0] + moff), q1 = *(const uint32_t*)(tp[1] + moff);
  const uint32_t q2 = *(const uint32_t*)(tp[2] + moff), q3 = *(const uint32_t*)(tp[3] + moff);
  const uint2 ldt4 = *(const uint2*)(tp[4] + bid * 4);
  const uint32_t q4 = *(const uint32_t*)(tp[br ? 2 : 5] + moff), q5 = *(const uint32_t*)(tp[br ? 3 : 6] + moff);

  for (int i = wtid & 63; i < R_BR / 16; i += 64) sts128(cb + R_OFF + br * R_BR + i * 16, 0, 0, 0, 0);
  STAMP(1);

  float acc[5][4];
  float k2048 = 0.f;
  const uint32_t scr = cb + Y0_OFF + wq * SCR_BYTES;
  const uint32_t scr2 = sb + XIN_OFF + warp * 640;
  {
    const uint32_t ldt2 = (ch & 2) ? ldt4.y : ldt4.x;
    const float dt = bf_round(expf((ch & 1) ? bf_hi(ldt2) : bf_lo(ldt2)));
#pragma unroll
    for (int i = 0; i < 5; i++) acc[i][0] = acc[i][1] = acc[i][2] = acc[i][3] = 0.f;
    cf cc[2], zz1[2], zz128[2];
#pragma unroll
    for (int r = 0; r < 2; r++) {
      float v0 = r ? bf_hi(q0) : bf_lo(q0), v1 = r ? bf_hi(q1) : bf_lo(q1), v2 = r ? bf_hi(q2) : bf_lo(q2);
      float v3 = r ? bf_hi(q3) : bf_lo(q3), v4 = r ? bf_hi(q4) : bf_lo(q4), v5 = r ? bf_hi(q5) : bf_lo(q5);
      if (br == 0) { cc[r] = cmul(cf{v2, v3}, cf{dt * v4, dt * v5}); }
      else { v0 = -bf_round(expf(v0)); cc[r] = cf{2.f * dt * v2, 2.f * dt * v3}; }
      const float xl = (dt * v0) * 1.4426950408889634f, y = dt * v1;
      zz1[r] = cexp_p(xl, y, 1.f); zz128[r] = cexp_p(xl, y, 128.f);
    }
    STAMP(2);
    const uint32_t tb = scr + lane * 16;
    const uint32_t ta = scr + (lane >> 3) * 512 + (lane & 7) * 16;
    const uint32_t tc = ((lane & 8) ? scr2 : scr + 4096) + (lane >> 4) * 128 + (lane & 7) * 16;
    const uint32_t tm = scr2 + 512 + ((lane >> 3) & 1) * 64 + (lane >> 4) * 16;
#pragma unroll 1
    for (int r = 0; r < 2; r++) {
      const cf c = r ? cc[1] : cc[0], z1 = r ? zz1[1] : zz1[0], z128 = r ? zz128[1] : zz128[0];
      const cf z2 = csq(z1), z4 = csq(z2), z8 = csq(z4);
      const cf z16 = csq(z8), z24 = cmul(z16, z8), z32 = csq(z16), z40 = cmul(z32, z8), z48 = csq(z24), z56 = cmul(z32, z24), z64 = csq(z32);
      const cf z256 = csq(z128), z512 = csq(z256), z1024 = csq(z512), z2048 = csq(z1024);
      {
        float kk = fmaf(c.re, z2048.re, -c.im * z2048.im);
#pragma unroll
        for (int o = 16; o; o >>= 1) kk += __shfl_xor_sync(0xffffffffu, kk, o);
        k2048 += kk;
      }
      __syncwarp();
      {
        uint32_t xr[4] = {pack_bf16(1.f, z8.re), pack_bf16(z16.re, z24.re), pack_bf16(z32.re, z40.re), pack_bf16(z48.re, z56.re)};
        uint32_t xi[4] = {pack_bf16(0.f, -z8.im), pack_bf16(-z16.im, -z24.im), pack_bf16(-z32.im, -z40.im), pack_bf16(-z48.im, -z56.im)};
        sts128(tb + 0 * 512, xr[0], xr[1], xr[2], xr[3]);
        sts128(tb + 2 * 512, xi[0], xi[1], xi[2], xi[3]);
        const uint32_t yr = pack_bf16(z64.re, z64.re), nyi = pack_bf16(z64.im, z64.im), yi = nyi ^ 0x80008000u;
        uint32_t o[4], q[4];
#pragma unroll
        for (int i = 0; i < 4; i++) CMUL2(o[i], q[i], xr[i], xi[i], yr, yi, nyi);
        sts128(tb + 1 * 512, o[0], o[1], o[2], o[3]);
        sts128(tb + 3 * 512, q[0], q[1], q[2], q[3]);
      }
      {
        const cf h1 = cmul(c, z128), h2 = cmul(c, z256), h3 = cmul(h1, z256), h4 = cmul(c, z512), h5 = cmul(h1, z512), h6 = cmul(h2, z512), h7 = cmul(h3, z512);
        const cf e1 = cmul(c, z1), e2 = cmul(c, z2), e3 = cmul(e1, z2), e129 = cmul(h1, z1), e130 = cmul(h1, z2), e131 = cmul(e129, z2);
        const cf e258 = cmul(h2, z2), e386 = cmul(h3, z2);
        const uint32_t pr0 = pack_bf16(c.re, e1.re), pr2 = pack_bf16(h1.re, e129.re), pi0 = pack_bf16(c.im, e1.im), pi2 = pack_bf16(h1.im, e129.im);
        sts128(tb + 4 * 512, pr0, pack_bf16(e2.re, e3.re), pr2, pack_bf16(e130.re, e131.re));
        sts128(tb + 5 * 512, pi0, pack_bf16(e2.im, e3.im), pi2, pack_bf16(e130.im, e131.im));
        uint32_t xr[4] = {pack_bf16(h2.re, e258.re), pack_bf16(h3.re, e386.re), pack_bf16(h4.re, h5.re), pack_bf16(h6.re, h7.re)};
        uint32_t xi[4] = {pack_bf16(h2.im, e258.im), pack_bf16(h3.im, e386.im), pack_bf16(h4.im, h5.im), pack_bf16(h6.im, h7.im)};
        sts128(tb + 6 * 512, xr[0], xr[1], xr[2], xr[3]);
        sts128(tb + 7 * 512, xi[0], xi[1], xi[2], xi[3]);
        xr[1] = __byte_perm(xr[0], xr[1], 0x5410); xi[1] = __byte_perm(xi[0], xi[1], 0x5410);
        xr[0] = __byte_perm(pr0, pr2, 0x5410); xi[0] = __byte_perm(pi0, pi2, 0x5410);
        const uint32_t yr = pack_bf16(z1024.re, z1024.re), yi = pack_bf16(z1024.im, z1024.im), nyi = yi ^ 0x80008000u;
        uint32_t o[4], q[4];
#pragma unroll
        for (int i = 0; i < 4; i++) CMUL2(o[i], q[i], xr[i], xi[i], yr, yi, nyi);
        sts128(tb + 8 * 512, o[0], o[1], o[2], o[3]);
        sts128(scr2 + lane * 16, q[0], q[1], q[2], q[3]);
        const uint32_t m4 = pack_bf16(z4.re, z4.im);
        sts16(scr2 + 512 + lane * 2, m4); sts16(scr2 + 576 + lane * 2, m4 >> 16);
      }
      __syncwarp();
#pragma unroll
      for (int kp = 0; kp < 2; kp++) {
        uint32_t rr[2], ri[2], yr[2], yi[2];
        ldsm4t(tc + kp * 256, rr[0], ri[0], rr[1], ri[1]);
        ldsm4(tm + kp * 32, yr[0], yi[0], yr[1], yi[1]);
#pragma unroll
        for (int k2 = 0; k2 < 2; k2++) {
          const int kk = kp * 2 + k2;
          uint32_t a0, a1, a2, a3, pr, pi, qr, qi, xr, xi;
          ldsm4t(ta + kk * 128, a0, a1, a2, a3);
          ldsm4t(ta + 2048 + kk * 128, pr, pi, qr, qi);
          const uint32_t nyi = yi[k2] ^ 0x80008000u;
          mma16816(acc[0], a0, a1, a2, a3, pr, pi);
          mma16816(acc[2], a0, a1, a2, a3, qr, qi);
          mma16816(acc[4], a0, a1, a2, a3, rr[k2], ri[k2]);
          CMUL2(xr, xi, pr, pi, yr[k2], yi[k2], nyi);
          mma16816(acc[1], a0, a1, a2, a3, xr, xi);
          CMUL2(xr, xi, qr, qi, yr[k2], yi[k2], nyi);
          mma16816(acc[3], a0, a1, a2, a3, xr, xi);
        }
      }
    }
  }
  STAMP(3);
  __syncwarp();
  {
    const uint32_t xs = scr + lane * 16;
#define OTH(i, k) __float_as_uint(hf ? acc[i][k] : acc[i][2 + (k)])
    sts128(xs, OTH(0, 0), OTH(0, 1), OTH(1, 0), OTH(1, 1));
    sts128(xs + 512, OTH(2, 0), OTH(2, 1), OTH(3, 0), OTH(3, 1));
    sts128(xs + 1024, OTH(4, 0), OTH(4, 1), __float_as_uint(k2048), 0);
#undef OTH
  }

  bar_sync(7 + (warp >> 1), 64);
  STAMP(4);
  {
    const uint32_t xo = cb + Y0_OFF + (wq ^ 1) * SCR_BYTES + lane * 16;
    const uint4 o0 = lds128(xo), o1 = lds128(xo + 512), o2 = lds128(xo + 1024);
    const uint32_t rb = cb + R_OFF + br * R_BR;
#define OWN(i, k) (hf ? acc[i][2 + (k)] : acc[i][k])
    const uint32_t vP = pack_bf16(OWN(0, 1) + __uint_as_float(o0.y), OWN(0, 0) + __uint_as_float(o0.x));
    const uint32_t vP4 = pack_bf16(OWN(1, 1) + __uint_as_float(o0.w), OWN(1, 0) + __uint_as_float(o0.z));
    const uint32_t vQ = pack_bf16(OWN(2, 1) + __uint_as_float(o1.y), OWN(2, 0) + __uint_as_float(o1.x));
    const uint32_t vQ4 = pack_bf16(OWN(3, 1) + __uint_as_float(o1.w), OWN(3, 0) + __uint_as_float(o1.z));
    const uint32_t vR = pack_bf16(OWN(4, 1) + __uint_as_float(o2.y), OWN(4, 0) + __uint_as_float(o2.x));
#undef OWN
    const int j = g + 8 * hf;
    {
      const int a = 2 * (t & 1) + 64 * (t & 2) + 8 * j;
      const uint32_t ad = rb + 2 * (RD_X0 - 1 - a);
      const uint32_t a1 = (t & 2) ? ad - 8 : ad, a2 = (t & 2) ? ad : ad - 8;
      const uint32_t w1 = (t & 2) ? vP4 : vP, w2 = (t & 2) ? vP : vP4;
      sts32(a1, w1); sts32(a2, w2);
      sts16(a1 + RD_CS + 2, w1); sts16(a1 + RD_CS + 4, w1 >> 16);
      sts16(a2 + RD_CS + 2, w2); sts16(a2 + RD_CS + 4, w2 >> 16);
    }
    if (t < 2) {
      const int b = 256 + 128 * t + 8 * j;
      const uint32_t ad = rb + 2 * (RD_X0 - 6 - b);
      const uint32_t v22 = __byte_perm(vQ4, 0, 0x3232), v00 = __byte_perm(vQ, 0, 0x3232);
      sts16(ad, vQ4);
      sts64(ad + 2, v22, __byte_perm(vQ4, vQ, 0x5432));
      sts32(ad + 10, v00);
      if (b != 256) { sts16(ad + 14, v00); sts128(ad + RD_CS + 2, vQ4, v22, vQ, v00); }
      else { sts64(ad + RD_CS + 2, vQ4, v22); sts32(ad + RD_CS + 10, vQ); sts16(ad + RD_CS + 14, v00); }
    } else {
      const uint32_t ao = rb + R_O2 + 2 * (159 - (32 * t + j)), ae = ao - (R_O2 - R_E2) + 2;
      sts16(ao, vQ4 >> 16); sts16(ao + RS_CS + 2, vQ4 >> 16); sts16(ao - 32, vQ4); sts16(ao - 32 + RS_CS + 2, vQ4);
      sts16(ae - 32, vQ); sts16(ae - 32 + RS_CS + 2, vQ);
      if (lane != 2 || hf) { sts16(ae, vQ >> 16); sts16(ae + RS_CS + 2, vQ >> 16); }
      else {
        const uint32_t vv = __byte_perm(vQ, 0, 0x3232), ad = rb + 2 * (RD_X0 - 514);
        sts16(ad, vv); sts32(ad + 2, vv); sts16(ad + 6, vv); sts64(ad + RD_CS + 2, vv, vv);
      }
    }
    {
      const uint32_t a = rb + ((g & 1) ? R_O3 : R_E3 + 2) + 2 * (159 - (64 + 16 * t + (j >> 1)));
      const bool p1024 = (lane == 0) && (hf == 0);
      const uint32_t a00 = p1024 ? rb + R_E2 + 2 * (159 - 127) : a;
      sts16(a00, vR >> 16); sts16(a00 + RS_CS + 2, vR >> 16);
      sts16(a - 16, vR); sts16(a - 16 + RS_CS + 2, vR);
      if (p1024) {
        sts32(sb + K1024_OFF + (ch * 2 + br) * 4, __byte_perm(vR, 0, 0x3232));
        const uint32_t kv = pack_bf16(k2048 + __uint_as_float(o2.z), 0.f);
        sts16(rb + R_E3 + 2 * (159 - 127), kv); sts16(rb + R_E3 + 2 * (159 - 127) + RS_CS + 2, kv);
      }
    }
  }
  STAMP(5);
  asm volatile("barrier.cluster.wait.aligned;" ::: "memory");
  bar_sync(7 + (warp >> 1), 64);
  mbar_wait(sb + B_U);
  STAMP(6);

  const uint32_t zz = lds32(cb + R_OFF + br * R_BR);
  conv_dense(cb, zz);
  const uint2 dA = ldg64(p.A_D + bid * 4), dB = ldg64(p.B_D + bid * 4);
  const uint2 gl = gate_ld((4 + ch) * 128 + wtid);
  mbar_wait(sb + B_W);
  conv_far(sb, cb, zz);
  STAMP(10);
  __syncwarp();
  if (lane == 0) asm volatile("mbarrier.arrive.shared::cta.b64 _, [%0];" ::"r"(sb + B_Y3) : "memory");

  {
    const int x = (4 + ch) * 128 + wtid, c = x >> 2;
    const uint32_t g2 = gate_fin(p, gl, x, lds32(sb + TAG_OFF));
    const uint32_t yo = sb + CH_OFF + (x & 3) * 4 + ysw(c);
    uint32_t ua[4], ub[4], ya[4], yb[4], a2[4], b2[4], a3[4], b3[4], s2[4];
    skip_terms(ua, ub, sb, x, dA, dB);
    ld4ch(s2, sb + CH_OFF + (x & 3) * 4 + S2_OFF + ((c - 128) + ((c - 128) >> 3)) * 16);
    mbar_wait(sb + B_Y2);
    const uint4 k0 = lds128(sb + K1024_OFF), k1 = lds128(sb + K1024_OFF + 16);
    const uint32_t kk[8] = {k0.x, k0.y, k0.z, k0.w, k1.x, k1.y, k1.z, k1.w};
    ld4ch(ya, yo + Y0_OFF); ld4ch(yb, yo + Y0_OFF + 4096);
    ld4ch(a2, yo + Y2_OFF - 1024); ld4ch(b2, yo + Y2_OFF - 1024 + 3072);
#pragma unroll
    for (int k = 0; k < 4; k++) { a2[k] = hfma2(kk[2 * k], s2[k], a2[k]); b2[k] = hfma2(kk[2 * k + 1], s2[k], b2[k]); }
    STAMP(11);
    mbar_wait(sb + B_Y3);
    STAMP(12);
    ld4ch(a3, yo + Y3_OFF - 2048); ld4ch(b3, yo + Y3_OFF - 2048 + 2048);
#pragma unroll
    for (int k = 0; k < 4; k++) { ya[k] = hadd2(ya[k], hadd2(a2[k], a3[k])); yb[k] = hadd2(yb[k], hadd2(b2[k], b3[k])); }
    const uint4 r = mix(ya, yb, ua, ub, g2);
    if ((uint32_t)(ch & 1) != rank) send_box(sb, 2 + (ch >> 1), wtid, rank, r);
    else merge_box(sb, &tm_out, 2 + (ch >> 1), wtid, rank, oc0, r, 1 + ch);
  }
  STAMP(14);
  if (wtid == 0) asm volatile("cp.async.bulk.wait_group.read 0;" ::: "memory");
  STAMP(15); GT(1);
}

typedef CUresult (*EncodeFn)(CUtensorMap*, CUtensorMapDataType, cuuint32_t, void*, const cuuint64_t*, const cuuint64_t*,
                             const cuuint32_t*, const cuuint32_t*, CUtensorMapInterleave, CUtensorMapSwizzle,
                             CUtensorMapL2promotion, CUtensorMapFloatOOBfill);

}

extern "C" void kernel_launch(void* const* d_in, const int* in_sizes, int n_in, void* d_out, int out_size) {
  (void)in_sizes; (void)n_in; (void)out_size;
  typedef const __nv_bfloat16* bp;
  Params p;
  p.t[0] = (bp)d_in[10]; p.t[1] = (bp)d_in[11]; p.t[2] = (bp)d_in[12]; p.t[3] = (bp)d_in[13]; p.t[4] = (bp)d_in[14]; p.t[5] = nullptr;
  p.t[6] = (bp)d_in[1]; p.t[7] = (bp)d_in[2]; p.t[8] = (bp)d_in[5]; p.t[9] = (bp)d_in[6]; p.t[10] = (bp)d_in[7];
  p.t[11] = (bp)d_in[3]; p.t[12] = (bp)d_in[4]; p.t[13] = nullptr;
  p.u = (bp)d_in[0]; p.gw = (bp)d_in[16]; p.A_D = (bp)d_in[8]; p.B_D = (bp)d_in[15];
  static EncodeFn enc = nullptr;
  if (!enc) {
    cudaDriverEntryPointQueryResult qr;
    cudaGetDriverEntryPoint("cuTensorMapEncodeTiled", (void**)&enc, cudaEnableDefault, &qr);
    cudaFuncSetAttribute(ssm_kernel, cudaFuncAttributeMaxDynamicSharedMemorySize, SMEM_BYTES);
  }
  CUtensorMap tm_in, tm_out;
  {
    cuuint64_t gd[5] = {512, 2, 4, 4, 64};
    cuuint64_t gs[4] = {1024, 8192, 2048, 32768};
    cuuint32_t bx[5] = {8, 2, 4, 4, 32};
    cuuint32_t es[5] = {1, 1, 1, 1, 1};
    enc(&tm_in, CU_TENSOR_MAP_DATA_TYPE_BFLOAT16, 5, d_in[0], gd, gs, bx, es, CU_TENSOR_MAP_INTERLEAVE_NONE,
        CU_TENSOR_MAP_SWIZZLE_NONE, CU_TENSOR_MAP_L2_PROMOTION_NONE, CU_TENSOR_MAP_FLOAT_OOB_FILL_NONE);
  }
  {
    cuuint64_t gd[3] = {512, 1024, 2};
    cuuint64_t gs[2] = {2048, 1024};
    cuuint32_t bx[3] = {8, 128, 2};
    cuuint32_t es[3] = {1, 1, 1};
    enc(&tm_out, CU_TENSOR_MAP_DATA_TYPE_BFLOAT16, 3, d_out, gd, gs, bx, es, CU_TENSOR_MAP_INTERLEAVE_NONE,
        CU_TENSOR_MAP_SWIZZLE_NONE, CU_TENSOR_MAP_L2_PROMOTION_NONE, CU_TENSOR_MAP_FLOAT_OOB_FILL_NONE);
  }
  ssm_kernel<<<NCTA + NGATE, 640, SMEM_BYTES, cudaStreamPerThread>>>(p, tm_in, tm_out);
}
```

```cpp
#include <cuda_runtime.h>
#include <cuda.h>
#include <cuda_bf16.h>
#include <stdint.h>

namespace {
#define FIXA 0
#define FIXB 1
#define CPY(x) (x)
#define FCPY(x) __uint_as_float(opq(__float_as_uint(x), zz))

constexpr int L = 2048, D = 512, NM = 128;
constexpr int NCTA = 128;
constexpr int NGATE = 4;

constexpr int RAW_OFF = 0;
constexpr int XIN_OFF = 32768;
constexpr int BAR_OFF = XIN_OFF + 10240;
constexpr int CH_OFF = BAR_OFF + 128;
constexpr int U_CS = 1184;
constexpr int U_OFF = 0;
constexpr int R_OFF = 4736;
constexpr int RD_X0 = 565;
constexpr int RD_CS = 1216;
constexpr int RS_CS = 320;
constexpr int R_E2 = 2 * RD_CS, R_O2 = R_E2 + 2 * RS_CS, R_E3 = R_O2 + 2 * RS_CS, R_O3 = R_E3 + 2 * RS_CS;
constexpr int R_BR = R_O3 + 2 * RS_CS;
constexpr int W5_OFF = R_OFF + 2 * R_BR;
constexpr int W3_OFF = W5_OFF + 3456;
constexpr int W9_OFF = W3_OFF + 3456;
constexpr int W7_OFF = W9_OFF + 2304;
constexpr int S2_OFF = W7_OFF + 2304;
constexpr int Y0_OFF = S2_OFF + 2304;
constexpr int Y2_OFF = Y0_OFF + 8192, Y3_OFF = Y2_OFF + 6144;
constexpr int CH_BYTES = Y0_OFF + 18432 + 16;
constexpr int SCR_BYTES = 4608;
constexpr int SMEM_BYTES = CH_OFF + 4 * CH_BYTES;
static_assert(CH_BYTES % 128 == 16, "bank staggering of the channel blocks");
static_assert(SMEM_BYTES <= 232448, "smem");
constexpr int B_RAW = BAR_OFF, B_X = BAR_OFF + 8, B_U = BAR_OFF + 40, B_W = BAR_OFF + 48, B_Y2 = BAR_OFF + 56, B_Y3 = BAR_OFF + 96;
constexpr int TAG_OFF = BAR_OFF + 104;
constexpr int K1024_OFF = BAR_OFF + 64;

__device__ unsigned int g_gate[L];
__device__ unsigned int g_epoch;
__device__ unsigned int g_ticket;

#define STAMP(k)
#define GT(k)

struct Params {
  const __nv_bfloat16* t[14];
  const __nv_bfloat16 *u, *gw, *A_D, *B_D;
};

template <int N, int TB> __device__ __forceinline__ void wgmma_rs(float* d, uint32_t a0, uint32_t a1, uint32_t a2, uint32_t a3, uint64_t desc, int sc);
template <> __device__ __forceinline__ void wgmma_rs<64, 0>(float* d, uint32_t a0, uint32_t a1, uint32_t a2, uint32_t a3, uint64_t desc, int sc) {
  asm volatile("{\n.reg .pred p;\nsetp.ne.b32 p, %37, 0;\n"
    "wgmma.mma_async.sync.aligned.m64n64k16.f32.bf16.bf16 {%0,%1,%2,%3,%4,%5,%6,%7,%8,%9,%10,%11,%12,%13,%14,%15,%16,%17,%18,%19,%20,%21,%22,%23,%24,%25,%26,%27,%28,%29,%30,%31}, {%32,%33,%34,%35}, %36, p, 1, 1, 0;\n}"
    : "+f"(d[0]), "+f"(d[1]), "+f"(d[2]), "+f"(d[3]), "+f"(d[4]), "+f"(d[5]), "+f"(d[6]), "+f"(d[7]), "+f"(d[8]), "+f"(d[9]), "+f"(d[10]), "+f"(d[11]), "+f"(d[12]), "+f"(d[13]), "+f"(d[14]), "+f"(d[15]), "+f"(d[16]), "+f"(d[17]), "+f"(d[18]), "+f"(d[19]), "+f"(d[20]), "+f"(d[21]), "+f"(d[22]), "+f"(d[23]), "+f"(d[24]), "+f"(d[25]), "+f"(d[26]), "+f"(d[27]), "+f"(d[28]), "+f"(d[29]), "+f"(d[30]), "+f"(d[31]) : "r"(a0), "r"(a1), "r"(a2), "r"(a3), "l"(desc), "r"(sc));
}
template <> __device__ __forceinline__ void wgmma_rs<56, 0>(float* d, uint32_t a0, uint32_t a1, uint32_t a2, uint32_t a3, uint64_t desc, int sc) {
  asm volatile("{\n.reg .pred p;\nsetp.ne.b32 p, %33, 0;\n"
    "wgmma.mma_async.sync.aligned.m64n56k16.f32.bf16.bf16 {%0,%1,%2,%3,%4,%5,%6,%7,%8,%9,%10,%11,%12,%13,%14,%15,%16,%17,%18,%19,%20,%21,%22,%23,%24,%25,%26,%27}, {%28,%29,%30,%31}, %32, p, 1, 1, 0;\n}"
    : "+f"(d[0]), "+f"(d[1]), "+f"(d[2]), "+f"(d[3]), "+f"(d[4]), "+f"(d[5]), "+f"(d[6]), "+f"(d[7]), "+f"(d[8]), "+f"(d[9]), "+f"(d[10]), "+f"(d[11]), "+f"(d[12]), "+f"(d[13]), "+f"(d[14]), "+f"(d[15]), "+f"(d[16]), "+f"(d[17]), "+f"(d[18]), "+f"(d[19]), "+f"(d[20]), "+f"(d[21]), "+f"(d[22]), "+f"(d[23]), "+f"(d[24]), "+f"(d[25]), "+f"(d[26]), "+f"(d[27]) : "r"(a0), "r"(a1), "r"(a2), "r"(a3), "l"(desc), "r"(sc));
}
template <> __device__ __forceinline__ void wgmma_rs<48, 0>(float* d, uint32_t a0, uint32_t a1, uint32_t a2, uint32_t a3, uint64_t desc, int sc) {
  asm volatile("{\n.reg .pred p;\nsetp.ne.b32 p, %29, 0;\n"
    "wgmma.mma_async.sync.aligned.m64n48k16.f32.bf16.bf16 {%0,%1,%2,%3,%4,%5,%6,%7,%8,%9,%10,%11,%12,%13,%14,%15,%16,%17,%18,%19,%20,%21,%22,%23}, {%24,%25,%26,%27}, %28, p, 1, 1, 0;\n}"
    : "+f"(d[0]), "+f"(d[1]), "+f"(d[2]), "+f"(d[3]), "+f"(d[4]), "+f"(d[5]), "+f"(d[6]), "+f"(d[7]), "+f"(d[8]), "+f"(d[9]), "+f"(d[10]), "+f"(d[11]), "+f"(d[12]), "+f"(d[13]), "+f"(d[14]), "+f"(d[15]), "+f"(d[16]), "+f"(d[17]), "+f"(d[18]), "+f"(d[19]), "+f"(d[20]), "+f"(d[21]), "+f"(d[22]), "+f"(d[23]) : "r"(a0), "r"(a1), "r"(a2), "r"(a3), "l"(desc), "r"(sc));
}
template <> __device__ __forceinline__ void wgmma_rs<32, 0>(float* d, uint32_t a0, uint32_t a1, uint32_t a2, uint32_t a3, uint64_t desc, int sc) {
  asm volatile("{\n.reg .pred p;\nsetp.ne.b32 p, %21, 0;\n"
    "wgmma.mma_async.sync.aligned.m64n32k16.f32.bf16.bf16 {%0,%1,%2,%3,%4,%5,%6,%7,%8,%9,%10,%11,%12,%13,%14,%15}, {%16,%17,%18,%19}, %20, p, 1, 1, 0;\n}"
    : "+f"(d[0]), "+f"(d[1]), "+f"(d[2]), "+f"(d[3]), "+f"(d[4]), "+f"(d[5]), "+f"(d[6]), "+f"(d[7]), "+f"(d[8]), "+f"(d[9]), "+f"(d[10]), "+f"(d[11]), "+f"(d[12]), "+f"(d[13]), "+f"(d[14]), "+f"(d[15]) : "r"(a0), "r"(a1), "r"(a2), "r"(a3), "l"(desc), "r"(sc));
}
template <> __device__ __forceinline__ void wgmma_rs<48, 1>(float* d, uint32_t a0, uint32_t a1, uint32_t a2, uint32_t a3, uint64_t desc, int sc) {
  asm volatile("{\n.reg .pred p;\nsetp.ne.b32 p, %29, 0;\n"
    "wgmma.mma_async.sync.aligned.m64n48k16.f32.bf16.bf16 {%0,%1,%2,%3,%4,%5,%6,%7,%8,%9,%10,%11,%12,%13,%14,%15,%16,%17,%18,%19,%20,%21,%22,%23}, {%24,%25,%26,%27}, %28, p, 1, 1, 1;\n}"
    : "+f"(d[0]), "+f"(d[1]), "+f"(d[2]), "+f"(d[3]), "+f"(d[4]), "+f"(d[5]), "+f"(d[6]), "+f"(d[7]), "+f"(d[8]), "+f"(d[9]), "+f"(d[10]), "+f"(d[11]), "+f"(d[12]), "+f"(d[13]), "+f"(d[14]), "+f"(d[15]), "+f"(d[16]), "+f"(d[17]), "+f"(d[18]), "+f"(d[19]), "+f"(d[20]), "+f"(d[21]), "+f"(d[22]), "+f"(d[23]) : "r"(a0), "r"(a1), "r"(a2), "r"(a3), "l"(desc), "r"(sc));
}
template <> __device__ __forceinline__ void wgmma_rs<40, 1>(float* d, uint32_t a0, uint32_t a1, uint32_t a2, uint32_t a3, uint64_t desc, int sc) {
  asm volatile("{\n.reg .pred p;\nsetp.ne.b32 p, %25, 0;\n"
    "wgmma.mma_async.sync.aligned.m64n40k16.f32.bf16.bf16 {%0,%1,%2,%3,%4,%5,%6,%7,%8,%9,%10,%11,%12,%13,%14,%15,%16,%17,%18,%19}, {%20,%21,%22,%23}, %24, p, 1, 1, 1;\n}"
    : "+f"(d[0]), "+f"(d[1]), "+f"(d[2]), "+f"(d[3]), "+f"(d[4]), "+f"(d[5]), "+f"(d[6]), "+f"(d[7]), "+f"(d[8]), "+f"(d[9]), "+f"(d[10]), "+f"(d[11]), "+f"(d[12]), "+f"(d[13]), "+f"(d[14]), "+f"(d[15]), "+f"(d[16]), "+f"(d[17]), "+f"(d[18]), "+f"(d[19]) : "r"(a0), "r"(a1), "r"(a2), "r"(a3), "l"(desc), "r"(sc));
}
template <> __device__ __forceinline__ void wgmma_rs<32, 1>(float* d, uint32_t a0, uint32_t a1, uint32_t a2, uint32_t a3, uint64_t desc, int sc) {
  asm volatile("{\n.reg .pred p;\nsetp.ne.b32 p, %21, 0;\n"
    "wgmma.mma_async.sync.aligned.m64n32k16.f32.bf16.bf16 {%0,%1,%2,%3,%4,%5,%6,%7,%8,%9,%10,%11,%12,%13,%14,%15}, {%16,%17,%18,%19}, %20, p, 1, 1, 1;\n}"
    : "+f"(d[0]), "+f"(d[1]), "+f"(d[2]), "+f"(d[3]), "+f"(d[4]), "+f"(d[5]), "+f"(d[6]), "+f"(d[7]), "+f"(d[8]), "+f"(d[9]), "+f"(d[10]), "+f"(d[11]), "+f"(d[12]), "+f"(d[13]), "+f"(d[14]), "+f"(d[15]) : "r"(a0), "r"(a1), "r"(a2), "r"(a3), "l"(desc), "r"(sc));
}
template <> __device__ __forceinline__ void wgmma_rs<16, 1>(float* d, uint32_t a0, uint32_t a1, uint32_t a2, uint32_t a3, uint64_t desc, int sc) {
  asm volatile("{\n.reg .pred p;\nsetp.ne.b32 p, %13, 0;\n"
    "wgmma.mma_async.sync.aligned.m64n16k16.f32.bf16.bf16 {%0,%1,%2,%3,%4,%5,%6,%7}, {%8,%9,%10,%11}, %12, p, 1, 1, 1;\n}"
    : "+f"(d[0]), "+f"(d[1]), "+f"(d[2]), "+f"(d[3]), "+f"(d[4]), "+f"(d[5]), "+f"(d[6]), "+f"(d[7]) : "r"(a0), "r"(a1), "r"(a2), "r"(a3), "l"(desc), "r"(sc));
}

__device__ __forceinline__ uint32_t pack_bf16(float lo, float hi) {
  uint32_t r; asm("cvt.rn.bf16x2.f32 %0, %1, %2;" : "=r"(r) : "f"(hi), "f"(lo)); return r;
}
__device__ __forceinline__ float bf_lo(uint32_t v) { return __uint_as_float(v << 16); }
__device__ __forceinline__ float bf_hi(uint32_t v) { return __uint_as_float(v & 0xffff0000u); }
__device__ __forceinline__ float bf_round(float x) { return bf_lo(pack_bf16(x, 0.f)); }
__device__ __forceinline__ uint32_t hmul2(uint32_t a, uint32_t b) { uint32_t r; asm("mul.rn.bf16x2 %0, %1, %2;" : "=r"(r) : "r"(a), "r"(b)); return r; }
__device__ __forceinline__ uint32_t hadd2(uint32_t a, uint32_t b) { uint32_t r; asm("add.rn.bf16x2 %0, %1, %2;" : "=r"(r) : "r"(a), "r"(b)); return r; }
__device__ __forceinline__ uint32_t hsub2(uint32_t a, uint32_t b) { uint32_t r; asm("sub.rn.bf16x2 %0, %1, %2;" : "=r"(r) : "r"(a), "r"(b)); return r; }
__device__ __forceinline__ uint32_t hfma2(uint32_t a, uint32_t b, uint32_t c) { uint32_t r; asm("fma.rn.bf16x2 %0, %1, %2, %3;" : "=r"(r) : "r"(a), "r"(b), "r"(c)); return r; }

__device__ __forceinline__ void sts16(uint32_t a, uint32_t v) { asm volatile("st.shared.b16 [%0], %1;" ::"r"(a), "h"((unsigned short)v) : "memory"); }
__device__ __forceinline__ void sts32(uint32_t a, uint32_t v) { asm volatile("st.shared.b32 [%0], %1;" ::"r"(a), "r"(v) : "memory"); }
__device__ __forceinline__ void sts64(uint32_t a, uint32_t x, uint32_t y) { asm volatile("st.shared.v2.b32 [%0], {%1,%2};" ::"r"(a), "r"(x), "r"(y) : "memory"); }
__device__ __forceinline__ void sts128(uint32_t a, uint32_t x, uint32_t y, uint32_t z, uint32_t w) {
  asm volatile("st.shared.v4.b32 [%0], {%1,%2,%3,%4};" ::"r"(a), "r"(x), "r"(y), "r"(z), "r"(w) : "memory");
}
__device__ __forceinline__ uint32_t lds32(uint32_t a) { uint32_t v; asm volatile("ld.shared.b32 %0, [%1];" : "=r"(v) : "r"(a) : "memory"); return v; }
__device__ __forceinline__ uint2 lds64(uint32_t a) { uint2 v; asm volatile("ld.shared.v2.b32 {%0,%1}, [%2];" : "=r"(v.x), "=r"(v.y) : "r"(a) : "memory"); return v; }
__device__ __forceinline__ uint4 lds128(uint32_t a) {
  uint4 v; asm volatile("ld.shared.v4.b32 {%0,%1,%2,%3}, [%4];" : "=r"(v.x), "=r"(v.y), "=r"(v.z), "=r"(v.w) : "r"(a) : "memory"); return v;
}
__device__ __forceinline__ uint4 ldg128(const void* a) {
  uint4 v; asm volatile("ld.global.nc.v4.b32 {%0,%1,%2,%3}, [%4];" : "=r"(v.x), "=r"(v.y), "=r"(v.z), "=r"(v.w) : "l"(a) : "memory"); return v;
}
__device__ __forceinline__ uint2 ldg64(const void* a) {
  uint2 v; asm volatile("ld.global.nc.v2.b32 {%0,%1}, [%2];" : "=r"(v.x), "=r"(v.y) : "l"(a) : "memory"); return v;
}
__device__ __forceinline__ void ldsm4(uint32_t a, uint32_t& r0, uint32_t& r1, uint32_t& r2, uint32_t& r3) {
  asm volatile("ldmatrix.sync.aligned.m8n8.x4.shared.b16 {%0,%1,%2,%3}, [%4];" : "=r"(r0), "=r"(r1), "=r"(r2), "=r"(r3) : "r"(a) : "memory");
}
__device__ __forceinline__ void ldsm4t(uint32_t a, uint32_t& r0, uint32_t& r1, uint32_t& r2, uint32_t& r3) {
  asm volatile("ldmatrix.sync.aligned.m8n8.x4.trans.shared.b16 {%0,%1,%2,%3}, [%4];" : "=r"(r0), "=r"(r1), "=r"(r2), "=r"(r3) : "r"(a) : "memory");
}
__device__ __forceinline__ void stsm4(uint32_t a, uint32_t r0, uint32_t r1, uint32_t r2, uint32_t r3) {
  asm volatile("stmatrix.sync.aligned.m8n8.x4.shared.b16 [%0], {%1,%2,%3,%4};" ::"r"(a), "r"(r0), "r"(r1), "r"(r2), "r"(r3) : "memory");
}
__device__ __forceinline__ void stsm4t(uint32_t a, uint32_t r0, uint32_t r1, uint32_t r2, uint32_t r3) {
  asm volatile("stmatrix.sync.aligned.m8n8.x4.trans.shared.b16 [%0], {%1,%2,%3,%4};" ::"r"(a), "r"(r0), "r"(r1), "r"(r2), "r"(r3) : "memory");
}
__device__ __forceinline__ void mma16816(float* c, uint32_t a0, uint32_t a1, uint32_t a2, uint32_t a3, uint32_t b0, uint32_t b1) {
  asm("mma.sync.aligned.m16n8k16.row.col.f32.bf16.bf16.f32 {%0,%1,%2,%3}, {%4,%5,%6,%7}, {%8,%9}, {%0,%1,%2,%3};"
      : "+f"(c[0]), "+f"(c[1]), "+f"(c[2]), "+f"(c[3]) : "r"(a0), "r"(a1), "r"(a2), "r"(a3), "r"(b0), "r"(b1));
}
__device__ __forceinline__ void bar_sync(int id, int n) { asm volatile("bar.sync %0, %1;" ::"r"(id), "r"(n) : "memory"); }
__device__ __forceinline__ void bar_arrive(int id, int n) { asm volatile("bar.arrive %0, %1;" ::"r"(id), "r"(n) : "memory"); }
__device__ __forceinline__ void wg_fence() { asm volatile("wgmma.fence.sync.aligned;" ::: "memory"); }
__device__ __forceinline__ void wg_commit() { asm volatile("wgmma.commit_group.sync.aligned;" ::: "memory"); }
__device__ __forceinline__ void wg_wait0() { asm volatile("wgmma.wait_group.sync.aligned 0;" ::: "memory"); }
__device__ __forceinline__ void fence_async() { asm volatile("fence.proxy.async.shared::cta;" ::: "memory"); }
__device__ __forceinline__ uint32_t opq(uint32_t x, uint32_t z) { uint32_t r; asm volatile("xor.b32 %0, %1, %2;" : "=r"(r) : "r"(x), "r"(z)); return r; }
__device__ __forceinline__ uint64_t mkdesc(uint32_t addr, uint32_t lbo, uint32_t sbo) {
  return (uint64_t)((addr & 0x3FFFF) >> 4) | ((uint64_t)(lbo >> 4) << 16) | ((uint64_t)(sbo >> 4) << 32);
}
__device__ __forceinline__ uint32_t mapa(uint32_t a, uint32_t rank) {
  uint32_t r; asm("mapa.shared::cluster.u32 %0, %1, %2;" : "=r"(r) : "r"(a), "r"(rank)); return r;
}
__device__ __forceinline__ void mbar_init_expect(uint32_t bar, uint32_t bytes) {
  asm volatile("mbarrier.init.shared::cta.b64 [%0], 1;" ::"r"(bar) : "memory");
  asm volatile("mbarrier.arrive.expect_tx.shared::cta.b64 _, [%0], %1;" ::"r"(bar), "r"(bytes) : "memory");
}
__device__ __forceinline__ void mbar_wait(uint32_t bar) {
#pragma unroll 1
  for (int it = 0; it < (1 << 22); it++) {
    uint32_t ok;
    asm volatile("{\n.reg .pred p;\nmbarrier.try_wait.parity.acquire.cluster.shared::cta.b64 p, [%1], 0;\nselp.u32 %0, 1, 0, p;\n}"
                 : "=r"(ok) : "r"(bar) : "memory");
    if (ok) return;
  }
  __trap();
}
__device__ __forceinline__ void st_async4(uint32_t a, uint32_t bar, uint32_t x, uint32_t y, uint32_t z, uint32_t w) {
  asm volatile("st.async.weak.shared::cluster.mbarrier::complete_tx::bytes.v4.b32 [%0], {%2,%3,%4,%5}, [%1];"
               ::"r"(a), "r"(bar), "r"(x), "r"(y), "r"(z), "r"(w) : "memory");
}

struct cf { float re, im; };
__device__ __forceinline__ cf cmul(cf a, cf b) { return {fmaf(a.re, b.re, -a.im * b.im), fmaf(a.re, b.im, a.im * b.re)}; }
__device__ __forceinline__ cf csq(cf a) { return {fmaf(a.re, a.re, -a.im * a.im), (a.re + a.re) * a.im}; }
__device__ __forceinline__ cf cexp_p(float xl, float y, float p) {
  float mag; asm("ex2.approx.ftz.f32 %0, %1;" : "=f"(mag) : "f"(xl * p));
  const float th = y * p;
  const float k = rintf(th * 0.15915494309189535f);
  float r = fmaf(k, -6.2831854820251465f, th);
  r = fmaf(k, 1.7484555314695172e-07f, r);
  return {mag * __cosf(r), mag * __sinf(r)};
}
__device__ __forceinline__ uint32_t ysw(int c) { return (uint32_t)(c ^ ((c >> 3) & 3)) * 16u; }

#define CMUL2(OR, OI, xr, xi, yr, yi, nyi) do { OR = hfma2(xr, yr, hmul2(xi, nyi)); OI = hfma2(xr, yi, hmul2(xi, yr)); } while (0)

__device__ __forceinline__ uint32_t gate_slow(const __nv_bfloat16* u, const __nv_bfloat16* gw, int row) {
  float s = 0.f;
  const uint32_t* xr = (const uint32_t*)(u + (size_t)row * D);
  const uint32_t* wr = (const uint32_t*)gw;
#pragma unroll 1
  for (int j = 0; j < D / 2; j++) { const uint32_t pr = hmul2(xr[j], wr[j]); s += bf_lo(pr); s += bf_hi(pr); }
  s = bf_round(s);
  return pack_bf16(1.f / (1.f + expf(-s)), 0.f);
}

__device__ __forceinline__ uint2 gate_ld(int x) {
  uint2 gv;
  asm volatile("ld.relaxed.gpu.global.v2.u32 {%0,%1}, [%2];" : "=r"(gv.x), "=r"(gv.y) : "l"(g_gate + x * 2) : "memory");
  return gv;
}
__device__ __noinline__ uint32_t gate_poll(const Params* pp, int x, uint32_t tag) {
  uint2 gv;
#pragma unroll 1
  for (int spins = 0; spins < (1 << 16); spins++) {
    gv = gate_ld(x);
    if ((gv.x >> 16) == tag && (gv.y >> 16) == tag) return __byte_perm(gv.x, gv.y, 0x5410);
  }
  return __byte_perm(gate_slow(pp->u, pp->gw, x * 2), gate_slow(pp->u, pp->gw, x * 2 + 1), 0x5410);
}
__device__ __forceinline__ uint32_t gate_fin(const Params& p, uint2 gv, int x, uint32_t tag) {
  if ((gv.x >> 16) == tag && (gv.y >> 16) == tag) return __byte_perm(gv.x, gv.y, 0x5410);
  return gate_poll(&p, x, tag);
}

__device__ __forceinline__ void ld4ch(uint32_t* v, uint32_t addr) {
#pragma unroll
  for (int k = 0; k < 4; k++) v[k] = lds32(addr + k * CH_BYTES);
}
__device__ __forceinline__ void skip_terms(uint32_t* ua, uint32_t* ub, uint32_t sb, int x, uint2 dA, uint2 dB) {
  const int c = x >> 2;
  uint32_t uu[4];
  ld4ch(uu, sb + CH_OFF + (x & 3) * 4 + U_OFF + (c & 3) * U_CS + (63 - (c >> 2)) * 16);
#pragma unroll
  for (int k = 0; k < 4; k++) {
    ua[k] = hmul2(uu[k], __byte_perm((k & 2) ? dA.y : dA.x, 0, (k & 1) ? 0x3232 : 0x1010));
    ub[k] = hmul2(uu[k], __byte_perm((k & 2) ? dB.y : dB.x, 0, (k & 1) ? 0x3232 : 0x1010));
  }
}
__device__ __forceinline__ uint4 mix(const uint32_t* a, const uint32_t* b, const uint32_t* ua, const uint32_t* ub, uint32_t g2) {
  const uint32_t h2 = hsub2(0x3f803f80u, g2);
  uint32_t o[4];
#pragma unroll
  for (int k = 0; k < 4; k++) o[k] = hadd2(hmul2(g2, hadd2(a[k], ua[k])), hmul2(h2, hadd2(b[k], ub[k])));
  return make_uint4(__byte_perm(o[0], o[1], 0x5410), __byte_perm(o[2], o[3], 0x5410), __byte_perm(o[0], o[1], 0x7632), __byte_perm(o[2], o[3], 0x7632));
}
__device__ __forceinline__ void send_box(uint32_t sb, int slot, int wtid, uint32_t rank, uint4 r) {
  st_async4(mapa(sb + XIN_OFF + slot * 2048 + wtid * 16, rank ^ 1), mapa(sb + B_X + slot * 8, rank ^ 1), r.x, r.y, r.z, r.w);
}
__device__ __forceinline__ void merge_box(uint32_t sb, const CUtensorMap* tm_out, int slot, int wtid, uint32_t rank, int oc0, uint4 r, int barid) {
  const uint32_t st = sb + RAW_OFF + slot * 4096 + wtid * 16;
  sts64(st + rank * 8, r.x, r.y); sts64(st + 2048 + rank * 8, r.z, r.w);
  mbar_wait(sb + B_X + slot * 8);
  const uint4 q = lds128(sb + XIN_OFF + slot * 2048 + wtid * 16);
  sts64(st + (rank ^ 1) * 8, q.x, q.y); sts64(st + 2048 + (rank ^ 1) * 8, q.z, q.w);
  fence_async();
  bar_sync(barid, 128);
  if (wtid == 0) {
    asm volatile("cp.async.bulk.tensor.3d.global.shared::cta.bulk_group [%0, {%2, %3, %4}], [%1];"
                 ::"l"(tm_out), "r"(sb + RAW_OFF + slot * 4096), "r"(oc0), "r"((2 * slot + (int)rank) * 128), "r"(0) : "memory");
    asm volatile("cp.async.bulk.commit_group;" ::: "memory");
  }
}

__device__ __forceinline__ uint32_t band2(int e, int lo, int hi) {
  uint32_t r = ((uint32_t)(e - lo) <= (uint32_t)(hi - lo) ? 0x3f80u : 0u) | ((uint32_t)(e - 1 - lo) <= (uint32_t)(hi - lo) ? 0x3f800000u : 0u);
  asm volatile("" : "+r"(r));
  return r;
}

__device__ __forceinline__ void conv_dense(uint32_t cb, uint32_t zz) {
  const int lane = threadIdx.x & 31, wq = (threadIdx.x >> 5) & 3, br = wq >> 1, hf = wq & 1, g = lane >> 2, t = lane & 3;
  const uint32_t rb = cb + R_OFF + br * R_BR;
  const int eo = 16 * hf + g - 2 * t;
  float dacc[32];
  {
      {
        const int x0 = RD_X0 - (eo + 536);
        const uint32_t fa = rb + ((g & 1) ? 2 * x0 : RD_CS + 2 * x0 + 2);
        const uint64_t ub = mkdesc(cb + U_OFF, U_CS, 128);
        uint32_t A[2][4][4];
        float e56[28], e48[24];
        auto loadA = [&](int j) {
#pragma unroll
          for (int k = 0; k < 4; k++) {
            const int s = 34 - 4 * j - k;
            if (s >= 0) {
              if (k == 0 && j == 0) A[0][0][2] = lds32(fa + (2 * s + 2) * 16);
              A[j & 1][k][0] = lds32(fa + (2 * s + 1) * 16);
              A[j & 1][k][1] = lds32(fa + (2 * s) * 16);
            }
          }
#pragma unroll
          for (int k = 0; k < 4; k++) {
            if (34 - 4 * j - k >= 0) {
              A[j & 1][k][3] = CPY(A[j & 1][k][0]);
              if (k) A[j & 1][k][2] = CPY(A[j & 1][k - 1][1]);
              else if (j) A[j & 1][0][2] = CPY(A[(j - 1) & 1][3][1]);
            }
          }
        };
        loadA(0);
#pragma unroll
        for (int j = 0; j < 9; j++) {
          if (j == 4) {
#pragma unroll
            for (int i = 0; i < 28; i++) e56[i] = FCPY(dacc[i]);
          }
          if (j == 8) {
#pragma unroll
            for (int i = 0; i < 24; i++) e48[i] = FCPY(e56[i]);
          }
          wg_fence();
#pragma unroll
          for (int k = 0; k < 4; k++) {
            const int s = 34 - 4 * j - k;
            if (s >= 0) {
              const int o = 2 * s - 66 + 128;
              const int cc = o & 3, rs = (o >> 2) - 32;
              const int n0 = ((-rs) >> 3) * 8;
              const uint64_t desc = ub + (uint64_t)((cc * U_CS - rs * 16) >> 4);
              const uint32_t* a = A[j & 1][k];
              if (n0 == 0) wgmma_rs<64, 0>(dacc, a[0], a[1], a[2], a[3], desc, s != 34);
              else if (n0 == 8) wgmma_rs<56, 0>(FIXB ? e56 : dacc, a[0], a[1], a[2], a[3], desc, 1);
              else wgmma_rs<48, 0>(FIXB ? e48 : dacc, a[0], a[1], a[2], a[3], desc, 1);
            }
          }
          wg_commit();
          if (j < 8) loadA(j + 1);
          wg_wait0();
        }
#pragma unroll
        for (int i = 0; i < 28; i++) dacc[i] = i < 24 ? e48[i] : e56[i];
      }
      const uint32_t yb = cb + Y0_OFF + br * 4096;
#pragma unroll
      for (int i = 0; i < 8; i += 2) {
        const int mi = lane >> 3;
        const int cidx = 4 * (63 - 8 * (i + (mi >> 1)) - (lane & 7)) + 2 * hf + (mi & 1);
        stsm4t(yb + ysw(cidx), pack_bf16(dacc[4 * i], dacc[4 * i + 1]), pack_bf16(dacc[4 * i + 2], dacc[4 * i + 3]),
               pack_bf16(dacc[4 * i + 4], dacc[4 * i + 5]), pack_bf16(dacc[4 * i + 6], dacc[4 * i + 7]));
      }
      bar_arrive(6, 640);
      STAMP(8);
  }
}

__device__ __forceinline__ void conv_far(uint32_t sb, uint32_t cb, uint32_t zz) {
  const int lane = threadIdx.x & 31, wq = (threadIdx.x >> 5) & 3, br = wq >> 1, hf = wq & 1, g = lane >> 2, t = lane & 3;
  const uint32_t rb = cb + R_OFF + br * R_BR;
  const int eo = 16 * hf + g - 2 * t;
  float dacc[24], e40[20], e32[16], h32[16], h16[8];
  const int x1 = 159 - (eo + 136);
  const uint32_t fs = rb + ((g & 1) ? 2 * x1 : RS_CS + 2 * x1 + 2);
  {
    uint32_t A[2][4][4];
    auto loadA = [&](int buf, uint32_t oe, uint32_t oo, int i0) {
#pragma unroll
      for (int a = 0; a < 2; a++) {
        const uint32_t base = fs + (a ? oo : oe) + i0 * 16;
        uint32_t* k0 = A[buf][2 * a];
        uint32_t* k1 = A[buf][2 * a + 1];
        k0[1] = lds32(base); k0[0] = lds32(base + 16); k0[2] = lds32(base + 32); k1[0] = lds32(base + 48); k1[2] = lds32(base + 64);
      }
#pragma unroll
      for (int a = 0; a < 2; a++) {
        uint32_t* k0 = A[buf][2 * a];
        uint32_t* k1 = A[buf][2 * a + 1];
        k0[3] = CPY(k0[0]); k1[1] = CPY(k0[2]); k1[3] = CPY(k1[0]);
      }
    };
    const uint64_t d5 = mkdesc(cb + W5_OFF, 144, 576), d3 = mkdesc(cb + W3_OFF, 144, 576);
    loadA(0, R_E2, R_O2, 8);
#pragma unroll
    for (int m = 2; m <= 4; m++) {
      if (m == 3) {
#pragma unroll
        for (int i = 0; i < 20; i++) e40[i] = FCPY(dacc[i]);
      }
      if (m == 4) {
#pragma unroll
        for (int i = 0; i < 16; i++) e32[i] = FCPY(e40[i]);
      }
      wg_fence();
#pragma unroll
      for (int k = 0; k < 4; k++) {
        const uint32_t* a = A[m & 1][k];
        const uint64_t desc = ((k >> 1) ? d3 : d5) + (k & 1) * 18 + (m - 2) * 36;
        if (m == 2) wgmma_rs<48, 1>(dacc, a[0], a[1], a[2], a[3], desc, k);
        else if (m == 3) wgmma_rs<40, 1>(e40, a[0], a[1], a[2], a[3], desc, 1);
        else wgmma_rs<32, 1>(e32, a[0], a[1], a[2], a[3], desc, 1);
      }
      wg_commit();
      if (m < 4) loadA((m + 1) & 1, R_E2, R_O2, 4 * (3 - m));
      else loadA(1, R_E3, R_O3, 8);
      wg_wait0();
    }
#pragma unroll
    for (int i = 0; i < 20; i++) dacc[i] = i < 16 ? e32[i] : e40[i];
    {
      const uint32_t yb = cb + Y2_OFF + br * 3072;
#pragma unroll
      for (int i = 0; i < 6; i += 2) {
        const int mi = lane >> 3;
        const int cidx = 32 * (5 - i - (mi >> 1)) + 16 * hf + 8 * (mi & 1) + (lane & 7);
        stsm4(yb + ysw(cidx), pack_bf16(dacc[4 * i], dacc[4 * i + 1]), pack_bf16(dacc[4 * i + 2], dacc[4 * i + 3]),
              pack_bf16(dacc[4 * i + 4], dacc[4 * i + 5]), pack_bf16(dacc[4 * i + 6], dacc[4 * i + 7]));
      }
    }
    __syncwarp();
    if (lane == 0) asm volatile("mbarrier.arrive.shared::cta.b64 _, [%0];" ::"r"(sb + B_Y2) : "memory");
    STAMP(9);
    const uint64_t d9 = mkdesc(cb + W9_OFF, 144, 576), d7 = mkdesc(cb + W7_OFF, 144, 576);
#pragma unroll
    for (int m = 2; m <= 3; m++) {
      if (m == 3) {
#pragma unroll
        for (int i = 0; i < 8; i++) h16[i] = FCPY(h32[i]);
      }
      wg_fence();
#pragma unroll
      for (int k = 0; k < 4; k++) {
        const uint32_t* a = A[(m + 1) & 1][k];
        const uint64_t desc = ((k >> 1) ? d7 : d9) + (k & 1) * 18 + (m - 2) * 72;
        if (m == 2) wgmma_rs<32, 1>(h32, a[0], a[1], a[2], a[3], desc, k);
        else wgmma_rs<16, 1>(h16, a[0], a[1], a[2], a[3], desc, 1);
      }
      wg_commit();
      if (m == 2) loadA(0, R_E3, R_O3, 4);
      wg_wait0();
    }
#pragma unroll
    for (int i = 0; i < 16; i++) dacc[i] = i < 8 ? h16[i] : h32[i];
    const uint32_t yb = cb + Y3_OFF + br * 2048;
#pragma unroll
    for (int i = 0; i < 4; i += 2) {
      const int mi = lane >> 3;
      const int cidx = 64 * (1 - (i >> 1)) + 2 * (16 * hf + 8 * (mi & 1) + (lane & 7)) + (mi >> 1);
      stsm4(yb + ysw(cidx), pack_bf16(dacc[4 * i], dacc[4 * i + 1]), pack_bf16(dacc[4 * i + 2], dacc[4 * i + 3]),
            pack_bf16(dacc[4 * i + 4], dacc[4 * i + 5]), pack_bf16(dacc[4 * i + 6], dacc[4 * i + 7]));
    }
  }
}

__device__ __noinline__ void gate_cta(const Params* pp) {
  const __nv_bfloat16 *u = pp->u, *gw = pp->gw;
  const int lane = threadIdx.x & 31;
  unsigned int epoch;
  asm volatile("ld.relaxed.gpu.global.u32 %0, [%1];" : "=r"(epoch) : "l"(&g_epoch) : "memory");
  const uint4 gw0 = ldg128(gw + lane * 8), gw1 = ldg128(gw + 256 + lane * 8);
  const uint32_t ws[8] = {gw0.x, gw0.y, gw0.z, gw0.w, gw1.x, gw1.y, gw1.z, gw1.w};
  const uint32_t tag = (epoch + 1) & 0xffffu;
  uint4 gx[4][2], nx[4][2];
  int grow = (blockIdx.x * 20 + (threadIdx.x >> 5)) * 4;
#pragma unroll
  for (int i = 0; i < 4; i++) {
    nx[i][0] = ldg128(u + (size_t)(grow + i) * D + lane * 8);
    nx[i][1] = ldg128(u + (size_t)(grow + i) * D + 256 + lane * 8);
  }
#pragma unroll 1
  for (; grow < L; grow += 80 * NGATE) {
    const int nrow = min(grow + 80 * NGATE, L - 4);
#pragma unroll
    for (int i = 0; i < 4; i++) {
      gx[i][0] = nx[i][0]; gx[i][1] = nx[i][1];
      nx[i][0] = ldg128(u + (size_t)(nrow + i) * D + lane * 8);
      nx[i][1] = ldg128(u + (size_t)(nrow + i) * D + 256 + lane * 8);
    }
    float c[2][4];
#pragma unroll
    for (int i = 0; i < 2; i++) {
      const uint4 *x = gx[2 * i], *y = gx[2 * i + 1];
      const uint32_t xs[8] = {x[0].x, x[0].y, x[0].z, x[0].w, x[1].x, x[1].y, x[1].z, x[1].w};
      const uint32_t ys[8] = {y[0].x, y[0].y, y[0].z, y[0].w, y[1].x, y[1].y, y[1].z, y[1].w};
      c[i][0] = c[i][1] = c[i][2] = c[i][3] = 0.f;
#pragma unroll
      for (int j = 0; j < 8; j += 2)
        mma16816(c[i], hmul2(xs[j], ws[j]), hmul2(ys[j], ws[j]), hmul2(xs[j + 1], ws[j + 1]), hmul2(ys[j + 1], ws[j + 1]), 0x3f803f80u, 0x3f803f80u);
    }
    float s = (lane & 2) ? ((lane & 1) ? c[1][2] : c[1][0]) : ((lane & 1) ? c[0][2] : c[0][0]);
#pragma unroll
    for (int o = 4; o < 32; o <<= 1) s += __shfl_xor_sync(0xffffffffu, s, o);
    s = bf_round(s);
    const float gv = 1.f / (1.f + expf(-s));
    const uint32_t w = (tag << 16) | (pack_bf16(gv, 0.f) & 0xffffu);
    if (lane < 4) asm volatile("st.relaxed.gpu.global.u32 [%0], %1;" ::"l"(&g_gate[grow + lane]), "r"(w) : "memory");
  }
  __syncthreads();
  if (threadIdx.x == 0 && atomicAdd(&g_ticket, 1u) == NCTA + NGATE - 1) { g_ticket = 0; g_epoch = epoch + 1; }
}

__global__ void __cluster_dims__(2, 1, 1) __launch_bounds__(640, 1)
ssm_kernel(const __grid_constant__ Params p, const __grid_constant__ CUtensorMap tm_in, const __grid_constant__ CUtensorMap tm_out) {
  extern __shared__ __align__(1024) unsigned char smem_raw[];
  const uint32_t sb = (uint32_t)__cvta_generic_to_shared(smem_raw);
  const int tid = threadIdx.x, lane = tid & 31;
  const int warp = __shfl_sync(0xffffffffu, tid >> 5, 0);
  const int ch = warp >> 2, wq = warp & 3, br = wq >> 1, hf = wq & 1;
  const int g = lane >> 2, t = lane & 3;
  if (__builtin_expect(blockIdx.x < NGATE, 0)) { gate_cta(&p); return; }
  const int bid = blockIdx.x - NGATE;
  const int d = bid * 4 + ch;
  const uint32_t rank = blockIdx.x & 1;
  const uint32_t cb = sb + CH_OFF + ch * CH_BYTES;
  const int wtid = tid & 127;
  const int oc0 = (bid >> 1) * 8;
  STAMP(0); GT(0);

  if (warp >= 16) {
    if (wtid == 0) {
      mbar_init_expect(sb + B_RAW, 32768);
#pragma unroll
      for (int i = 0; i < 4; i++) mbar_init_expect(sb + B_X + 8 * i, 2048);
      asm volatile("mbarrier.init.shared::cta.b64 [%0], 128;" ::"r"(sb + B_U) : "memory");
      asm volatile("mbarrier.init.shared::cta.b64 [%0], 128;" ::"r"(sb + B_W) : "memory");
      asm volatile("mbarrier.init.shared::cta.b64 [%0], 16;" ::"r"(sb + B_Y2) : "memory");
      asm volatile("mbarrier.init.shared::cta.b64 [%0], 16;" ::"r"(sb + B_Y3) : "memory");
      asm volatile("fence.mbarrier_init.release.cluster;" ::: "memory");
      asm volatile("fence.proxy.async.shared::cta;" ::: "memory");
    }
    __syncwarp();
    asm volatile("barrier.cluster.arrive.relaxed.aligned;" ::: "memory");
    unsigned int epoch;
    asm volatile("ld.relaxed.gpu.global.u32 %0, [%1];" : "=r"(epoch) : "l"(&g_epoch) : "memory");
    asm volatile("barrier.cluster.wait.aligned;" ::: "memory");
    if (wtid == 0) {
      asm volatile("cp.async.bulk.tensor.5d.shared::cluster.global.mbarrier::complete_tx::bytes.multicast::cluster [%0], [%1, {%3, %4, %4, %4, %5}], [%2], %6;"
                   ::"r"(sb + RAW_OFF + rank * 16384), "l"(&tm_in), "r"(sb + B_RAW), "r"(oc0), "r"(0), "r"((int)rank * 32), "h"((unsigned short)3) : "memory");
    }
    sts128(sb + CH_OFF + wq * CH_BYTES + U_OFF + (lane >> 3) * U_CS + (64 + (lane & 7)) * 16, 0, 0, 0, 0);
    uint32_t BA[3][4], BC[3][4];
    {
      const int l1 = br ? 3 : 6, h1 = br ? 5 : 10;
#pragma unroll
      for (int i = 0; i < 3; i++) {
        const int e = 16 * hf + g - 2 * t + 16 - 16 * i;
        BA[i][0] = band2(e, l1, h1); BA[i][1] = band2(e + 8, l1, h1); BA[i][2] = band2(e - 8, l1, h1); BA[i][3] = BA[i][0];
        BC[i][0] = band2(e, 3, 4); BC[i][1] = band2(e + 8, 3, 4); BC[i][2] = band2(e - 8, 3, 4); BC[i][3] = BC[i][0];
      }
    }
    const uint32_t tag = (epoch + 1) & 0xffffu;
    if (wtid == 0) sts32(sb + TAG_OFF, tag);
    STAMP(3);
    mbar_wait(sb + B_RAW);
    STAMP(4);
    {
      const uint32_t dst = sb + CH_OFF + (g & 3) * CH_BYTES + U_OFF + t * U_CS + (63 - wq * 16) * 16;
#pragma unroll
      for (int h = 0; h < 2; h++) {
        uint32_t r[8][4];
#pragma unroll
        for (int i = 0; i < 8; i++) ldsm4t(sb + RAW_OFF + (wq * 16 + h * 8 + i) * 512 + lane * 16, r[i][0], r[i][1], r[i][2], r[i][3]);
        if ((uint32_t)(g >> 2) == rank) {
#pragma unroll
          for (int i = 0; i < 8; i++) sts128(dst - (h * 8 + i) * 16, r[i][0], r[i][1], r[i][2], r[i][3]);
        }
      }
    }
    fence_async();
    asm volatile("mbarrier.arrive.shared::cta.b64 _, [%0];" ::"r"(sb + B_U) : "memory");
    bar_sync(5, 128);
    STAMP(5);
    {
      const int mrow = lane & 7, mi = lane >> 3;
      const uint64_t ub0 = mkdesc(sb + CH_OFF + U_OFF, U_CS, 128);
      {
        float w1[24], w3[16];
#pragma unroll
        for (int i = 0; i < 24; i++) w1[i] = 0.f;
#pragma unroll
        for (int i = 0; i < 16; i++) w3[i] = 0.f;
        uint32_t wa[3], sa[2];
#pragma unroll
        for (int i = 0; i < 3; i++) {
          const int c = 4 * (47 - 8 * (2 * i + (mi >> 1)) - mrow) + 2 * hf + (mi & 1);
          wa[i] = sb + CH_OFF + (br ? W3_OFF : W5_OFF) + (5 - (c >> 5)) * 576 + ((c & 31) >> 3) * 144 + (c & 7) * 16;
          if (i) sa[i - 1] = sb + CH_OFF + S2_OFF + (c + (c >> 3)) * 16;
        }
#pragma unroll 1
        for (int k = 0; k < 4; k++) {
          wg_fence();
#pragma unroll
          for (int i = 0; i < 3; i++)
            wgmma_rs<48, 0>(w1, BA[i][0], BA[i][1], BA[i][2], BA[i][3],
                            ub0 + (uint64_t)((k * CH_BYTES + ((2 * i + 2) & 3) * U_CS + (16 + (i == 0)) * 16) >> 4), i);
#pragma unroll
          for (int i = 0; i < 3; i++)
            wgmma_rs<32, 0>(w3, BC[i][0], BC[i][1], BC[i][2], BC[i][3],
                            ub0 + (uint64_t)((k * CH_BYTES + ((2 * i + 2) & 3) * U_CS + (32 + (i == 0)) * 16) >> 4), i);
          wg_commit();
          wg_wait0();
#pragma unroll
          for (int i = 0; i < 3; i++)
            stsm4t(wa[i] + k * CH_BYTES, pack_bf16(w1[8 * i], w1[8 * i + 1]), pack_bf16(w1[8 * i + 2], w1[8 * i + 3]),
                   pack_bf16(w1[8 * i + 4], w1[8 * i + 5]), pack_bf16(w1[8 * i + 6], w1[8 * i + 7]));
          if (br == 0) {
#pragma unroll
            for (int i = 0; i < 2; i++)
              stsm4t(sa[i] + k * CH_BYTES, pack_bf16(w3[8 * i], w3[8 * i + 1]), pack_bf16(w3[8 * i + 2], w3[8 * i + 3]),
                     pack_bf16(w3[8 * i + 4], w3[8 * i + 5]), pack_bf16(w3[8 * i + 6], w3[8 * i + 7]));
          }
        }
      }
      {
        uint32_t BB[4][4];
        const int l2 = br ? 5 : 12, h2 = br ? 11 : 20;
#pragma unroll
        for (int i = 0; i < 4; i++) {
          const int e = 16 * hf + g - 2 * t + 32 - 16 * i;
          BB[i][0] = band2(e, l2, h2); BB[i][1] = band2(e + 8, l2, h2); BB[i][2] = band2(e - 8, l2, h2); BB[i][3] = BB[i][0];
        }
        float w2[2][16];
#pragma unroll
        for (int i = 0; i < 16; i++) { w2[0][i] = 0.f; w2[1][i] = 0.f; }
        uint32_t wa[2];
#pragma unroll
        for (int i = 0; i < 2; i++) {
          const int c = 4 * (31 - 8 * (2 * i + (mi >> 1)) - mrow) + 2 * hf + (mi & 1), pp = c >> 1;
          wa[i] = sb + CH_OFF + (br ? W7_OFF : W9_OFF) + (1 - (pp >> 5)) * 1152 + (c & 1) * 576 + ((pp & 31) >> 3) * 144 + (pp & 7) * 16;
        }
#pragma unroll 1
        for (int kp = 0; kp < 2; kp++) {
          wg_fence();
#pragma unroll
          for (int k = 0; k < 2; k++)
#pragma unroll
            for (int i = 0; i < 4; i++)
              wgmma_rs<32, 0>(w2[k], BB[i][0], BB[i][1], BB[i][2], BB[i][3],
                              ub0 + (uint64_t)(((2 * kp + k) * CH_BYTES + ((2 * i) & 3) * U_CS + (32 + (i < 2)) * 16) >> 4), i);
          wg_commit();
          wg_wait0();
#pragma unroll
          for (int k = 0; k < 2; k++)
#pragma unroll
            for (int i = 0; i < 2; i++)
              stsm4t(wa[i] + (2 * kp + k) * CH_BYTES, pack_bf16(w2[k][8 * i], w2[k][8 * i + 1]), pack_bf16(w2[k][8 * i + 2], w2[k][8 * i + 3]),
                     pack_bf16(w2[k][8 * i + 4], w2[k][8 * i + 5]), pack_bf16(w2[k][8 * i + 6], w2[k][8 * i + 7]));
        }
      }
    }
    fence_async();
    asm volatile("mbarrier.arrive.shared::cta.b64 _, [%0];" ::"r"(sb + B_W) : "memory");
    STAMP(7);
    const uint2 dA = ldg64(p.A_D + bid * 4), dB = ldg64(p.B_D + bid * 4);
    STAMP(8);
    uint32_t gg[4];
    {
      uint2 gl[4];
#pragma unroll
      for (int i = 0; i < 4; i++) gl[i] = gate_ld((i ^ (int)rank ^ 1) * 128 + wtid);
#pragma unroll
      for (int i = 0; i < 4; i++) gg[i] = gate_fin(p, gl[i], (i ^ (int)rank ^ 1) * 128 + wtid, tag);
    }
    {
      uint32_t ua[4][4], ub[4][4], ya[4][4], yb[4][4], yo[4];
#pragma unroll
      for (int i = 0; i < 4; i++) {
        const int x = (i ^ (int)rank ^ 1) * 128 + wtid;
        skip_terms(ua[i], ub[i], sb, x, dA, dB);
        yo[i] = sb + CH_OFF + (x & 3) * 4 + ysw(x >> 2);
      }
      bar_sync(6, 640);
      STAMP(10);
#pragma unroll
      for (int i = 0; i < 4; i++) { ld4ch(ya[i], yo[i] + Y0_OFF); ld4ch(yb[i], yo[i] + Y0_OFF + 4096); }
      send_box(sb, 0, wtid, rank, mix(ya[0], yb[0], ua[0], ub[0], gg[0]));
      merge_box(sb, &tm_out, 0, wtid, rank, oc0, mix(ya[1], yb[1], ua[1], ub[1], gg[1]), 5);
      STAMP(12);
      mbar_wait(sb + B_Y2);
      STAMP(11);
#pragma unroll
      for (int i = 2; i < 4; i++) { ld4ch(ya[i - 2], yo[i] + Y2_OFF - 1024); ld4ch(yb[i - 2], yo[i] + Y2_OFF - 1024 + 3072); }
#pragma unroll
      for (int i = 2; i < 4; i++)
#pragma unroll
        for (int k = 0; k < 4; k++) { ya[i][k] = hadd2(ya[i][k], ya[i - 2][k]); yb[i][k] = hadd2(yb[i][k], yb[i - 2][k]); }
      send_box(sb, 1, wtid, rank, mix(ya[2], yb[2], ua[2], ub[2], gg[2]));
      merge_box(sb, &tm_out, 1, wtid, rank, oc0, mix(ya[3], yb[3], ua[3], ub[3], gg[3]), 5);
      STAMP(13);
    }
    if (wtid == 0) {
      if (atomicAdd(&g_ticket, 1u) == NCTA + NGATE - 1) { g_ticket = 0; g_epoch = epoch + 1; }
      asm volatile("cp.async.bulk.wait_group.read 0;" ::: "memory");
    }
    STAMP(15);
    return;
  }
  asm volatile("barrier.cluster.arrive.relaxed.aligned;" ::: "memory");

  const int moff = (bid * 4 + (tid >> 7)) * NM + (tid & 63) * 2;
  const int brt = (tid >> 6) & 1;
  const __nv_bfloat16* const* tp = p.t + (brt ? 0 : 6);
  const uint32_t q0 = *(const uint32_t*)(tp[0] + moff), q1 = *(const uint32_t*)(tp[1] + moff);
  const uint32_t q2 = *(const uint32_t*)(tp[2] + moff), q3 = *(const uint32_t*)(tp[3] + moff);
  const uint2 ldt4 = *(const uint2*)(tp[4] + bid * 4);
  const uint32_t q4 = *(const uint32_t*)(tp[brt ? 2 : 5] + moff), q5 = *(const uint32_t*)(tp[brt ? 3 : 6] + moff);

  for (int i = wtid & 63; i < R_BR / 16; i += 64) sts128(cb + R_OFF + br * R_BR + i * 16, 0, 0, 0, 0);
  STAMP(1);

  float acc[5][4];
  float k2048 = 0.f;
  const uint32_t scr = cb + Y0_OFF + wq * SCR_BYTES;
  const uint32_t scr2 = sb + XIN_OFF + warp * 640;
  {
    const uint32_t ldt2 = (ch & 2) ? ldt4.y : ldt4.x;
    const float dt = bf_round(expf((ch & 1) ? bf_hi(ldt2) : bf_lo(ldt2)));
#pragma unroll
    for (int i = 0; i < 5; i++) acc[i][0] = acc[i][1] = acc[i][2] = acc[i][3] = 0.f;
    cf cc[2], zz1[2], zz128[2];
#pragma unroll
    for (int r = 0; r < 2; r++) {
      float v0 = r ? bf_hi(q0) : bf_lo(q0), v1 = r ? bf_hi(q1) : bf_lo(q1), v2 = r ? bf_hi(q2) : bf_lo(q2);
      float v3 = r ? bf_hi(q3) : bf_lo(q3), v4 = r ? bf_hi(q4) : bf_lo(q4), v5 = r ? bf_hi(q5) : bf_lo(q5);
      if (br == 0) { cc[r] = cmul(cf{v2, v3}, cf{dt * v4, dt * v5}); }
      else { v0 = -bf_round(expf(v0)); cc[r] = cf{2.f * dt * v2, 2.f * dt * v3}; }
      const float xl = (dt * v0) * 1.4426950408889634f, y = dt * v1;
      zz1[r] = cexp_p(xl, y, 1.f); zz128[r] = cexp_p(xl, y, 128.f);
    }
    STAMP(2);
    const uint32_t tb = scr + lane * 16;
    const uint32_t ta = scr + (lane >> 3) * 512 + (lane & 7) * 16;
    const uint32_t tc = ((lane & 8) ? scr2 : scr + 4096) + (lane >> 4) * 128 + (lane & 7) * 16;
    const uint32_t tm = scr2 + 512 + ((lane >> 3) & 1) * 64 + (lane >> 4) * 16;
#pragma unroll 1
    for (int r = 0; r < 2; r++) {
      const cf c = r ? cc[1] : cc[0], z1 = r ? zz1[1] : zz1[0], z128 = r ? zz128[1] : zz128[0];
      const cf z2 = csq(z1), z4 = csq(z2), z8 = csq(z4);
      const cf z16 = csq(z8), z24 = cmul(z16, z8), z32 = csq(z16), z40 = cmul(z32, z8), z48 = csq(z24), z56 = cmul(z32, z24), z64 = csq(z32);
      const cf z256 = csq(z128), z512 = csq(z256), z1024 = csq(z512), z2048 = csq(z1024);
      {
        float kk = fmaf(c.re, z2048.re, -c.im * z2048.im);
#pragma unroll
        for (int o = 16; o; o >>= 1) kk += __shfl_xor_sync(0xffffffffu, kk, o);
        k2048 += kk;
      }
      __syncwarp();
      {
        uint32_t xr[4] = {pack_bf16(1.f, z8.re), pack_bf16(z16.re, z24.re), pack_bf16(z32.re, z40.re), pack_bf16(z48.re, z56.re)};
        uint32_t xi[4] = {pack_bf16(0.f, -z8.im), pack_bf16(-z16.im, -z24.im), pack_bf16(-z32.im, -z40.im), pack_bf16(-z48.im, -z56.im)};
        sts128(tb + 0 * 512, xr[0], xr[1], xr[2], xr[3]);
        sts128(tb + 2 * 512, xi[0], xi[1], xi[2], xi[3]);
        const uint32_t yr = pack_bf16(z64.re, z64.re), nyi = pack_bf16(z64.im, z64.im), yi = nyi ^ 0x80008000u;
        uint32_t o[4], q[4];
#pragma unroll
        for (int i = 0; i < 4; i++) CMUL2(o[i], q[i], xr[i], xi[i], yr, yi, nyi);
        sts128(tb + 1 * 512, o[0], o[1], o[2], o[3]);
        sts128(tb + 3 * 512, q[0], q[1], q[2], q[3]);
      }
      {
        const cf h1 = cmul(c, z128), h2 = cmul(c, z256), h3 = cmul(h1, z256), h4 = cmul(c, z512), h5 = cmul(h1, z512), h6 = cmul(h2, z512), h7 = cmul(h3, z512);
        const cf e1 = cmul(c, z1), e2 = cmul(c, z2), e3 = cmul(e1, z2), e129 = cmul(h1, z1), e130 = cmul(h1, z2), e131 = cmul(e129, z2);
        const cf e258 = cmul(h2, z2), e386 = cmul(h3, z2);
        const uint32_t pr0 = pack_bf16(c.re, e1.re), pr2 = pack_bf16(h1.re, e129.re), pi0 = pack_bf16(c.im, e1.im), pi2 = pack_bf16(h1.im, e129.im);
        sts128(tb + 4 * 512, pr0, pack_bf16(e2.re, e3.re), pr2, pack_bf16(e130.re, e131.re));
        sts128(tb + 5 * 512, pi0, pack_bf16(e2.im, e3.im), pi2, pack_bf16(e130.im, e131.im));
        uint32_t xr[4] = {pack_bf16(h2.re, e258.re), pack_bf16(h3.re, e386.re), pack_bf16(h4.re, h5.re), pack_bf16(h6.re, h7.re)};
        uint32_t xi[4] = {pack_bf16(h2.im, e258.im), pack_bf16(h3.im, e386.im), pack_bf16(h4.im, h5.im), pack_bf16(h6.im, h7.im)};
        sts128(tb + 6 * 512, xr[0], xr[1], xr[2], xr[3]);
        sts128(tb + 7 * 512, xi[0], xi[1], xi[2], xi[3]);
        xr[1] = __byte_perm(xr[0], xr[1], 0x5410); xi[1] = __byte_perm(xi[0], xi[1], 0x5410);
        xr[0] = __byte_perm(pr0, pr2, 0x5410); xi[0] = __byte_perm(pi0, pi2, 0x5410);
        const uint32_t yr = pack_bf16(z1024.re, z1024.re), yi = pack_bf16(z1024.im, z1024.im), nyi = yi ^ 0x80008000u;
        uint32_t o[4], q[4];
#pragma unroll
        for (int i = 0; i < 4; i++) CMUL2(o[i], q[i], xr[i], xi[i], yr, yi, nyi);
        sts128(tb + 8 * 512, o[0], o[1], o[2], o[3]);
        sts128(scr2 + lane * 16, q[0], q[1], q[2], q[3]);
        const uint32_t m4 = pack_bf16(z4.re, z4.im);
        sts16(scr2 + 512 + lane * 2, m4); sts16(scr2 + 576 + lane * 2, m4 >> 16);
      }
      __syncwarp();
#pragma unroll
      for (int kp = 0; kp < 2; kp++) {
        uint32_t rr[2], ri[2], yr[2], yi[2];
        ldsm4t(tc + kp * 256, rr[0], ri[0], rr[1], ri[1]);
        ldsm4(tm + kp * 32, yr[0], yi[0], yr[1], yi[1]);
#pragma unroll
        for (int k2 = 0; k2 < 2; k2++) {
          const int kk = kp * 2 + k2;
          uint32_t a0, a1, a2, a3, pr, pi, qr, qi, xr, xi;
          ldsm4t(ta + kk * 128, a0, a1, a2, a3);
          ldsm4t(ta + 2048 + kk * 128, pr, pi, qr, qi);
          const uint32_t nyi = yi[k2] ^ 0x80008000u;
          mma16816(acc[0], a0, a1, a2, a3, pr, pi);
          mma16816(acc[2], a0, a1, a2, a3, qr, qi);
          mma16816(acc[4], a0, a1, a2, a3, rr[k2], ri[k2]);
          CMUL2(xr, xi, pr, pi, yr[k2], yi[k2], nyi);
          mma16816(acc[1], a0, a1, a2, a3, xr, xi);
          CMUL2(xr, xi, qr, qi, yr[k2], yi[k2], nyi);
          mma16816(acc[3], a0, a1, a2, a3, xr, xi);
        }
      }
    }
  }
  STAMP(3);
  __syncwarp();
  {
    const uint32_t xs = scr + lane * 16;
#define OTH(i, k) __float_as_uint(hf ? acc[i][k] : acc[i][2 + (k)])
    sts128(xs, OTH(0, 0), OTH(0, 1), OTH(1, 0), OTH(1, 1));
    sts128(xs + 512, OTH(2, 0), OTH(2, 1), OTH(3, 0), OTH(3, 1));
    sts128(xs + 1024, OTH(4, 0), OTH(4, 1), __float_as_uint(k2048), 0);
#undef OTH
  }

  bar_sync(7 + (warp >> 1), 64);
  STAMP(4);
  {
    const uint32_t xo = cb + Y0_OFF + (wq ^ 1) * SCR_BYTES + lane * 16;
    const uint4 o0 = lds128(xo), o1 = lds128(xo + 512), o2 = lds128(xo + 1024);
    const uint32_t rb = cb + R_OFF + br * R_BR;
#define OWN(i, k) (hf ? acc[i][2 + (k)] : acc[i][k])
    const uint32_t vP = pack_bf16(OWN(0, 1) + __uint_as_float(o0.y), OWN(0, 0) + __uint_as_float(o0.x));
    const uint32_t vP4 = pack_bf16(OWN(1, 1) + __uint_as_float(o0.w), OWN(1, 0) + __uint_as_float(o0.z));
    const uint32_t vQ = pack_bf16(OWN(2, 1) + __uint_as_float(o1.y), OWN(2, 0) + __uint_as_float(o1.x));
    const uint32_t vQ4 = pack_bf16(OWN(3, 1) + __uint_as_float(o1.w), OWN(3, 0) + __uint_as_float(o1.z));
    const uint32_t vR = pack_bf16(OWN(4, 1) + __uint_as_float(o2.y), OWN(4, 0) + __uint_as_float(o2.x));
#undef OWN
    const int j = g + 8 * hf;
    {
      const int a = 2 * (t & 1) + 64 * (t & 2) + 8 * j;
      const uint32_t ad = rb + 2 * (RD_X0 - 1 - a);
      const uint32_t a1 = (t & 2) ? ad - 8 : ad, a2 = (t & 2) ? ad : ad - 8;
      const uint32_t w1 = (t & 2) ? vP4 : vP, w2 = (t & 2) ? vP : vP4;
      sts32(a1, w1); sts32(a2, w2);
      sts16(a1 + RD_CS + 2, w1); sts16(a1 + RD_CS + 4, w1 >> 16);
      sts16(a2 + RD_CS + 2, w2); sts16(a2 + RD_CS + 4, w2 >> 16);
    }
    if (t < 2) {
      const int b = 256 + 128 * t + 8 * j;
      const uint32_t ad = rb + 2 * (RD_X0 - 6 - b);
      const uint32_t v22 = __byte_perm(vQ4, 0, 0x3232), v00 = __byte_perm(vQ, 0, 0x3232);
      sts16(ad, vQ4);
      sts64(ad + 2, v22, __byte_perm(vQ4, vQ, 0x5432));
      sts32(ad + 10, v00);
      if (b != 256) { sts16(ad + 14, v00); sts128(ad + RD_CS + 2, vQ4, v22, vQ, v00); }
      else { sts64(ad + RD_CS + 2, vQ4, v22); sts32(ad + RD_CS + 10, vQ); sts16(ad + RD_CS + 14, v00); }
    } else {
      const uint32_t ao = rb + R_O2 + 2 * (159 - (32 * t + j)), ae = ao - (R_O2 - R_E2) + 2;
      sts16(ao, vQ4 >> 16); sts16(ao + RS_CS + 2, vQ4 >> 16); sts16(ao - 32, vQ4); sts16(ao - 32 + RS_CS + 2, vQ4);
      sts16(ae - 32, vQ); sts16(ae - 32 + RS_CS + 2, vQ);
      if (lane != 2 || hf) { sts16(ae, vQ >> 16); sts16(ae + RS_CS + 2, vQ >> 16); }
      else {
        const uint32_t vv = __byte_perm(vQ, 0, 0x3232), ad = rb + 2 * (RD_X0 - 514);
        sts16(ad, vv); sts32(ad + 2, vv); sts16(ad + 6, vv); sts64(ad + RD_CS + 2, vv, vv);
      }
    }
    {
      const uint32_t a = rb + ((g & 1) ? R_O3 : R_E3 + 2) + 2 * (159 - (64 + 16 * t + (j >> 1)));
      const bool p1024 = (lane == 0) && (hf == 0);
      const uint32_t a00 = p1024 ? rb + R_E2 + 2 * (159 - 127) : a;
      sts16(a00, vR >> 16); sts16(a00 + RS_CS + 2, vR >> 16);
      sts16(a - 16, vR); sts16(a - 16 + RS_CS + 2, vR);
      if (p1024) {
        sts32(sb + K1024_OFF + (ch * 2 + br) * 4, __byte_perm(vR, 0, 0x3232));
        const uint32_t kv = pack_bf16(k2048 + __uint_as_float(o2.z), 0.f);
        sts16(rb + R_E3 + 2 * (159 - 127), kv); sts16(rb + R_E3 + 2 * (159 - 127) + RS_CS + 2, kv);
      }
    }
  }
  STAMP(5);
  asm volatile("barrier.cluster.wait.aligned;" ::: "memory");
  bar_sync(7 + (warp >> 1), 64);
  mbar_wait(sb + B_U);
  STAMP(6);

  const uint32_t zz = lds32(cb + R_OFF + br * R_BR);
  conv_dense(cb, zz);
  const uint2 dA = ldg64(p.A_D + bid * 4), dB = ldg64(p.B_D + bid * 4);
  const uint2 gl = gate_ld((4 + ch) * 128 + wtid);
  mbar_wait(sb + B_W);
  conv_far(sb, cb, zz);
  STAMP(10);
  __syncwarp();
  if (lane == 0) asm volatile("mbarrier.arrive.shared::cta.b64 _, [%0];" ::"r"(sb + B_Y3) : "memory");

  {
    const int x = (4 + ch) * 128 + wtid, c = x >> 2;
    const uint32_t g2 = gate_fin(p, gl, x, lds32(sb + TAG_OFF));
    const uint32_t yo = sb + CH_OFF + (x & 3) * 4 + ysw(c);
    uint32_t ua[4], ub[4], ya[4], yb[4], a2[4], b2[4], a3[4], b3[4], s2[4];
    skip_terms(ua, ub, sb, x, dA, dB);
    ld4ch(s2, sb + CH_OFF + (x & 3) * 4 + S2_OFF + ((c - 128) + ((c - 128) >> 3)) * 16);
    mbar_wait(sb + B_Y2);
    const uint4 k0 = lds128(sb + K1024_OFF), k1 = lds128(sb + K1024_OFF + 16);
    const uint32_t kk[8] = {k0.x, k0.y, k0.z, k0.w, k1.x, k1.y, k1.z, k1.w};
    ld4ch(ya, yo + Y0_OFF); ld4ch(yb, yo + Y0_OFF + 4096);
    ld4ch(a2, yo + Y2_OFF - 1024); ld4ch(b2, yo + Y2_OFF - 1024 + 3072);
#pragma unroll
    for (int k = 0; k < 4; k++) { a2[k] = hfma2(kk[2 * k], s2[k], a2[k]); b2[k] = hfma2(kk[2 * k + 1], s2[k], b2[k]); }
    STAMP(11);
    mbar_wait(sb + B_Y3);
    STAMP(12);
    ld4ch(a3, yo + Y3_OFF - 2048); ld4ch(b3, yo + Y3_OFF - 2048 + 2048);
#pragma unroll
    for (int k = 0; k < 4; k++) { ya[k] = hadd2(ya[k], hadd2(a2[k], a3[k])); yb[k] = hadd2(yb[k], hadd2(b2[k], b3[k])); }
    const uint4 r = mix(ya, yb, ua, ub, g2);
    if ((uint32_t)(ch & 1) != rank) send_box(sb, 2 + (ch >> 1), wtid, rank, r);
    else merge_box(sb, &tm_out, 2 + (ch >> 1), wtid, rank, oc0, r, 1 + ch);
  }
  STAMP(14);
  if (wtid == 0) asm volatile("cp.async.bulk.wait_group.read 0;" ::: "memory");
  STAMP(15); GT(1);
}

typedef CUresult (*EncodeFn)(CUtensorMap*, CUtensorMapDataType, cuuint32_t, void*, const cuuint64_t*, const cuuint64_t*,
                             const cuuint32_t*, const cuuint32_t*, CUtensorMapInterleave, CUtensorMapSwizzle,
                             CUtensorMapL2promotion, CUtensorMapFloatOOBfill);

}

extern "C" void kernel_launch(void* const* d_in, const int* in_sizes, int n_in, void* d_out, int out_size) {
  (void)in_sizes; (void)n_in; (void)out_size;
  typedef const __nv_bfloat16* bp;
  Params p;
  p.t[0] = (bp)d_in[10]; p.t[1] = (bp)d_in[11]; p.t[2] = (bp)d_in[12]; p.t[3] = (bp)d_in[13]; p.t[4] = (bp)d_in[14]; p.t[5] = nullptr;
  p.t[6] = (bp)d_in[1]; p.t[7] = (bp)d_in[2]; p.t[8] = (bp)d_in[5]; p.t[9] = (bp)d_in[6]; p.t[10] = (bp)d_in[7];
  p.t[11] = (bp)d_in[3]; p.t[12] = (bp)d_in[4]; p.t[13] = nullptr;
  p.u = (bp)d_in[0]; p.gw = (bp)d_in[16]; p.A_D = (bp)d_in[8]; p.B_D = (bp)d_in[15];
  static EncodeFn enc = nullptr;
  if (!enc) {
    cudaDriverEntryPointQueryResult qr;
    cudaGetDriverEntryPoint("cuTensorMapEncodeTiled", (void**)&enc, cudaEnableDefault, &qr);
    cudaFuncSetAttribute(ssm_kernel, cudaFuncAttributeMaxDynamicSharedMemorySize, SMEM_BYTES);
  }
  CUtensorMap tm_in, tm_out;
  {
    cuuint64_t gd[5] = {512, 2, 4, 4, 64};
    cuuint64_t gs[4] = {1024, 8192, 2048, 32768};
    cuuint32_t bx[5] = {8, 2, 4, 4, 32};
    cuuint32_t es[5] = {1, 1, 1, 1, 1};
    enc(&tm_in, CU_TENSOR_MAP_DATA_TYPE_BFLOAT16, 5, d_in[0], gd, gs, bx, es, CU_TENSOR_MAP_INTERLEAVE_NONE,
        CU_TENSOR_MAP_SWIZZLE_NONE, CU_TENSOR_MAP_L2_PROMOTION_NONE, CU_TENSOR_MAP_FLOAT_OOB_FILL_NONE);
  }
  {
    cuuint64_t gd[3] = {512, 1024, 2};
    cuuint64_t gs[2] = {2048, 1024};
    cuuint32_t bx[3] = {8, 128, 2};
    cuuint32_t es[3] = {1, 1, 1};
    enc(&tm_out, CU_TENSOR_MAP_DATA_TYPE_BFLOAT16, 3, d_out, gd, gs, bx, es, CU_TENSOR_MAP_INTERLEAVE_NONE,
        CU_TENSOR_MAP_SWIZZLE_NONE, CU_TENSOR_MAP_L2_PROMOTION_NONE, CU_TENSOR_MAP_FLOAT_OOB_FILL_NONE);
  }
  ssm_kernel<<<NCTA + NGATE, 640, SMEM_BYTES, cudaStreamPerThread>>>(p, tm_in, tm_out);
}
```

```cpp
#include <cuda_runtime.h>
#include <cuda.h>
#include <cuda_bf16.h>
#include <stdint.h>

namespace {
#define FCPY(x) __uint_as_float(opq(__float_as_uint(x), zz))

constexpr int L = 2048, D = 512, NM = 128;
constexpr int NCTA = 128;
constexpr int NGATE = 4;

constexpr int RAW_OFF = 0;
constexpr int XIN_OFF = 32768;
constexpr int BAR_OFF = XIN_OFF + 10240;
constexpr int CH_OFF = BAR_OFF + 256;
constexpr int U_CS = 1184;
constexpr int U_OFF = 0;
constexpr int R_OFF = 4736;
constexpr int RD_X0 = 565;
constexpr int RD_CS = 1216;
constexpr int RS_CS = 320;
constexpr int R_E2 = 2 * RD_CS, R_O2 = R_E2 + 2 * RS_CS, R_E3 = R_O2 + 2 * RS_CS, R_O3 = R_E3 + 2 * RS_CS;
constexpr int R_BR = R_O3 + 2 * RS_CS;
constexpr int W5_OFF = R_OFF + 2 * R_BR;
constexpr int W3_OFF = W5_OFF + 3456;
constexpr int W9_OFF = W3_OFF + 3456;
constexpr int W7_OFF = W9_OFF + 2304;
constexpr int S2_OFF = W7_OFF + 2304;
constexpr int Y0_OFF = S2_OFF + 2304;
constexpr int Y2_OFF = Y0_OFF + 8192, Y3_OFF = Y2_OFF + 6144;
constexpr int CH_BYTES = Y0_OFF + 18432 + 16;
constexpr int SCR_BYTES = 4608;
constexpr int SMEM_BYTES = CH_OFF + 4 * CH_BYTES;
static_assert(CH_BYTES % 128 == 16, "bank staggering of the channel blocks");
static_assert(SMEM_BYTES <= 232448, "smem");
constexpr int B_RAW = BAR_OFF, B_X = BAR_OFF + 8, B_U = BAR_OFF + 40, B_W = BAR_OFF + 48;
constexpr int TAG_OFF = BAR_OFF + 56;
constexpr int K1024_OFF = BAR_OFF + 64;
constexpr int B_ST = BAR_OFF + 96;

__device__ unsigned int g_gate[L];
__device__ unsigned int g_epoch;
__device__ unsigned int g_ticket;

#define STAMP(k)
#define GT(k)

struct Params {
  const __nv_bfloat16* t[14];
  const __nv_bfloat16 *u, *gw, *A_D, *B_D;
};

template <int N, int TB> __device__ __forceinline__ void wgmma_rs(float* d, uint32_t a0, uint32_t a1, uint32_t a2, uint32_t a3, uint64_t desc, int sc);
template <> __device__ __forceinline__ void wgmma_rs<64, 0>(float* d, uint32_t a0, uint32_t a1, uint32_t a2, uint32_t a3, uint64_t desc, int sc) {
  asm volatile("{\n.reg .pred p;\nsetp.ne.b32 p, %37, 0;\n"
    "wgmma.mma_async.sync.aligned.m64n64k16.f32.bf16.bf16 {%0,%1,%2,%3,%4,%5,%6,%7,%8,%9,%10,%11,%12,%13,%14,%15,%16,%17,%18,%19,%20,%21,%22,%23,%24,%25,%26,%27,%28,%29,%30,%31}, {%32,%33,%34,%35}, %36, p, 1, 1, 0;\n}"
    : "+f"(d[0]), "+f"(d[1]), "+f"(d[2]), "+f"(d[3]), "+f"(d[4]), "+f"(d[5]), "+f"(d[6]), "+f"(d[7]), "+f"(d[8]), "+f"(d[9]), "+f"(d[10]), "+f"(d[11]), "+f"(d[12]), "+f"(d[13]), "+f"(d[14]), "+f"(d[15]), "+f"(d[16]), "+f"(d[17]), "+f"(d[18]), "+f"(d[19]), "+f"(d[20]), "+f"(d[21]), "+f"(d[22]), "+f"(d[23]), "+f"(d[24]), "+f"(d[25]), "+f"(d[26]), "+f"(d[27]), "+f"(d[28]), "+f"(d[29]), "+f"(d[30]), "+f"(d[31]) : "r"(a0), "r"(a1), "r"(a2), "r"(a3), "l"(desc), "r"(sc));
}
template <> __device__ __forceinline__ void wgmma_rs<56, 0>(float* d, uint32_t a0, uint32_t a1, uint32_t a2, uint32_t a3, uint64_t desc, int sc) {
  asm volatile("{\n.reg .pred p;\nsetp.ne.b32 p, %33, 0;\n"
    "wgmma.mma_async.sync.aligned.m64n56k16.f32.bf16.bf16 {%0,%1,%2,%3,%4,%5,%6,%7,%8,%9,%10,%11,%12,%13,%14,%15,%16,%17,%18,%19,%20,%21,%22,%23,%24,%25,%26,%27}, {%28,%29,%30,%31}, %32, p, 1, 1, 0;\n}"
    : "+f"(d[0]), "+f"(d[1]), "+f"(d[2]), "+f"(d[3]), "+f"(d[4]), "+f"(d[5]), "+f"(d[6]), "+f"(d[7]), "+f"(d[8]), "+f"(d[9]), "+f"(d[10]), "+f"(d[11]), "+f"(d[12]), "+f"(d[13]), "+f"(d[14]), "+f"(d[15]), "+f"(d[16]), "+f"(d[17]), "+f"(d[18]), "+f"(d[19]), "+f"(d[20]), "+f"(d[21]), "+f"(d[22]), "+f"(d[23]), "+f"(d[24]), "+f"(d[25]), "+f"(d[26]), "+f"(d[27]) : "r"(a0), "r"(a1), "r"(a2), "r"(a3), "l"(desc), "r"(sc));
}
template <> __device__ __forceinline__ void wgmma_rs<48, 0>(float* d, uint32_t a0, uint32_t a1, uint32_t a2, uint32_t a3, uint64_t desc, int sc) {
  asm volatile("{\n.reg .pred p;\nsetp.ne.b32 p, %29, 0;\n"
    "wgmma.mma_async.sync.aligned.m64n48k16.f32.bf16.bf16 {%0,%1,%2,%3,%4,%5,%6,%7,%8,%9,%10,%11,%12,%13,%14,%15,%16,%17,%18,%19,%20,%21,%22,%23}, {%24,%25,%26,%27}, %28, p, 1, 1, 0;\n}"
    : "+f"(d[0]), "+f"(d[1]), "+f"(d[2]), "+f"(d[3]), "+f"(d[4]), "+f"(d[5]), "+f"(d[6]), "+f"(d[7]), "+f"(d[8]), "+f"(d[9]), "+f"(d[10]), "+f"(d[11]), "+f"(d[12]), "+f"(d[13]), "+f"(d[14]), "+f"(d[15]), "+f"(d[16]), "+f"(d[17]), "+f"(d[18]), "+f"(d[19]), "+f"(d[20]), "+f"(d[21]), "+f"(d[22]), "+f"(d[23]) : "r"(a0), "r"(a1), "r"(a2), "r"(a3), "l"(desc), "r"(sc));
}
template <> __device__ __forceinline__ void wgmma_rs<32, 0>(float* d, uint32_t a0, uint32_t a1, uint32_t a2, uint32_t a3, uint64_t desc, int sc) {
  asm volatile("{\n.reg .pred p;\nsetp.ne.b32 p, %21, 0;\n"
    "wgmma.mma_async.sync.aligned.m64n32k16.f32.bf16.bf16 {%0,%1,%2,%3,%4,%5,%6,%7,%8,%9,%10,%11,%12,%13,%14,%15}, {%16,%17,%18,%19}, %20, p, 1, 1, 0;\n}"
    : "+f"(d[0]), "+f"(d[1]), "+f"(d[2]), "+f"(d[3]), "+f"(d[4]), "+f"(d[5]), "+f"(d[6]), "+f"(d[7]), "+f"(d[8]), "+f"(d[9]), "+f"(d[10]), "+f"(d[11]), "+f"(d[12]), "+f"(d[13]), "+f"(d[14]), "+f"(d[15]) : "r"(a0), "r"(a1), "r"(a2), "r"(a3), "l"(desc), "r"(sc));
}
template <> __device__ __forceinline__ void wgmma_rs<48, 1>(float* d, uint32_t a0, uint32_t a1, uint32_t a2, uint32_t a3, uint64_t desc, int sc) {
  asm volatile("{\n.reg .pred p;\nsetp.ne.b32 p, %29, 0;\n"
    "wgmma.mma_async.sync.aligned.m64n48k16.f32.bf16.bf16 {%0,%1,%2,%3,%4,%5,%6,%7,%8,%9,%10,%11,%12,%13,%14,%15,%16,%17,%18,%19,%20,%21,%22,%23}, {%24,%25,%26,%27}, %28, p, 1, 1, 1;\n}"
    : "+f"(d[0]), "+f"(d[1]), "+f"(d[2]), "+f"(d[3]), "+f"(d[4]), "+f"(d[5]), "+f"(d[6]), "+f"(d[7]), "+f"(d[8]), "+f"(d[9]), "+f"(d[10]), "+f"(d[11]), "+f"(d[12]), "+f"(d[13]), "+f"(d[14]), "+f"(d[15]), "+f"(d[16]), "+f"(d[17]), "+f"(d[18]), "+f"(d[19]), "+f"(d[20]), "+f"(d[21]), "+f"(d[22]), "+f"(d[23]) : "r"(a0), "r"(a1), "r"(a2), "r"(a3), "l"(desc), "r"(sc));
}
template <> __device__ __forceinline__ void wgmma_rs<40, 1>(float* d, uint32_t a0, uint32_t a1, uint32_t a2, uint32_t a3, uint64_t desc, int sc) {
  asm volatile("{\n.reg .pred p;\nsetp.ne.b32 p, %25, 0;\n"
    "wgmma.mma_async.sync.aligned.m64n40k16.f32.bf16.bf16 {%0,%1,%2,%3,%4,%5,%6,%7,%8,%9,%10,%11,%12,%13,%14,%15,%16,%17,%18,%19}, {%20,%21,%22,%23}, %24, p, 1, 1, 1;\n}"
    : "+f"(d[0]), "+f"(d[1]), "+f"(d[2]), "+f"(d[3]), "+f"(d[4]), "+f"(d[5]), "+f"(d[6]), "+f"(d[7]), "+f"(d[8]), "+f"(d[9]), "+f"(d[10]), "+f"(d[11]), "+f"(d[12]), "+f"(d[13]), "+f"(d[14]), "+f"(d[15]), "+f"(d[16]), "+f"(d[17]), "+f"(d[18]), "+f"(d[19]) : "r"(a0), "r"(a1), "r"(a2), "r"(a3), "l"(desc), "r"(sc));
}
template <> __device__ __forceinline__ void wgmma_rs<32, 1>(float* d, uint32_t a0, uint32_t a1, uint32_t a2, uint32_t a3, uint64_t desc, int sc) {
  asm volatile("{\n.reg .pred p;\nsetp.ne.b32 p, %21, 0;\n"
    "wgmma.mma_async.sync.aligned.m64n32k16.f32.bf16.bf16 {%0,%1,%2,%3,%4,%5,%6,%7,%8,%9,%10,%11,%12,%13,%14,%15}, {%16,%17,%18,%19}, %20, p, 1, 1, 1;\n}"
    : "+f"(d[0]), "+f"(d[1]), "+f"(d[2]), "+f"(d[3]), "+f"(d[4]), "+f"(d[5]), "+f"(d[6]), "+f"(d[7]), "+f"(d[8]), "+f"(d[9]), "+f"(d[10]), "+f"(d[11]), "+f"(d[12]), "+f"(d[13]), "+f"(d[14]), "+f"(d[15]) : "r"(a0), "r"(a1), "r"(a2), "r"(a3), "l"(desc), "r"(sc));
}
template <> __device__ __forceinline__ void wgmma_rs<16, 1>(float* d, uint32_t a0, uint32_t a1, uint32_t a2, uint32_t a3, uint64_t desc, int sc) {
  asm volatile("{\n.reg .pred p;\nsetp.ne.b32 p, %13, 0;\n"
    "wgmma.mma_async.sync.aligned.m64n16k16.f32.bf16.bf16 {%0,%1,%2,%3,%4,%5,%6,%7}, {%8,%9,%10,%11}, %12, p, 1, 1, 1;\n}"
    : "+f"(d[0]), "+f"(d[1]), "+f"(d[2]), "+f"(d[3]), "+f"(d[4]), "+f"(d[5]), "+f"(d[6]), "+f"(d[7]) : "r"(a0), "r"(a1), "r"(a2), "r"(a3), "l"(desc), "r"(sc));
}

__device__ __forceinline__ uint32_t pack_bf16(float lo, float hi) {
  uint32_t r; asm("cvt.rn.bf16x2.f32 %0, %1, %2;" : "=r"(r) : "f"(hi), "f"(lo)); return r;
}
__device__ __forceinline__ float bf_lo(uint32_t v) { return __uint_as_float(v << 16); }
__device__ __forceinline__ float bf_hi(uint32_t v) { return __uint_as_float(v & 0xffff0000u); }
__device__ __forceinline__ float bf_round(float x) { return bf_lo(pack_bf16(x, 0.f)); }
__device__ __forceinline__ uint32_t hmul2(uint32_t a, uint32_t b) { uint32_t r; asm("mul.rn.bf16x2 %0, %1, %2;" : "=r"(r) : "r"(a), "r"(b)); return r; }
__device__ __forceinline__ uint32_t hadd2(uint32_t a, uint32_t b) { uint32_t r; asm("add.rn.bf16x2 %0, %1, %2;" : "=r"(r) : "r"(a), "r"(b)); return r; }
__device__ __forceinline__ uint32_t hsub2(uint32_t a, uint32_t b) { uint32_t r; asm("sub.rn.bf16x2 %0, %1, %2;" : "=r"(r) : "r"(a), "r"(b)); return r; }
__device__ __forceinline__ uint32_t hfma2(uint32_t a, uint32_t b, uint32_t c) { uint32_t r; asm("fma.rn.bf16x2 %0, %1, %2, %3;" : "=r"(r) : "r"(a), "r"(b), "r"(c)); return r; }

__device__ __forceinline__ void sts16(uint32_t a, uint32_t v) { asm volatile("st.shared.b16 [%0], %1;" ::"r"(a), "h"((unsigned short)v) : "memory"); }
__device__ __forceinline__ void sts32(uint32_t a, uint32_t v) { asm volatile("st.shared.b32 [%0], %1;" ::"r"(a), "r"(v) : "memory"); }
__device__ __forceinline__ void sts64(uint32_t a, uint32_t x, uint32_t y) { asm volatile("st.shared.v2.b32 [%0], {%1,%2};" ::"r"(a), "r"(x), "r"(y) : "memory"); }
__device__ __forceinline__ void sts128(uint32_t a, uint32_t x, uint32_t y, uint32_t z, uint32_t w) {
  asm volatile("st.shared.v4.b32 [%0], {%1,%2,%3,%4};" ::"r"(a), "r"(x), "r"(y), "r"(z), "r"(w) : "memory");
}
__device__ __forceinline__ uint32_t lds32(uint32_t a) { uint32_t v; asm volatile("ld.shared.b32 %0, [%1];" : "=r"(v) : "r"(a) : "memory"); return v; }
__device__ __forceinline__ uint2 lds64(uint32_t a) { uint2 v; asm volatile("ld.shared.v2.b32 {%0,%1}, [%2];" : "=r"(v.x), "=r"(v.y) : "r"(a) : "memory"); return v; }
__device__ __forceinline__ uint4 lds128(uint32_t a) {
  uint4 v; asm volatile("ld.shared.v4.b32 {%0,%1,%2,%3}, [%4];" : "=r"(v.x), "=r"(v.y), "=r"(v.z), "=r"(v.w) : "r"(a) : "memory"); return v;
}
__device__ __forceinline__ uint4 ldg128(const void* a) {
  uint4 v; asm volatile("ld.global.nc.v4.b32 {%0,%1,%2,%3}, [%4];" : "=r"(v.x), "=r"(v.y), "=r"(v.z), "=r"(v.w) : "l"(a) : "memory"); return v;
}
__device__ __forceinline__ uint2 ldg64(const void* a) {
  uint2 v; asm volatile("ld.global.nc.v2.b32 {%0,%1}, [%2];" : "=r"(v.x), "=r"(v.y) : "l"(a) : "memory"); return v;
}
__device__ __forceinline__ void ldsm4(uint32_t a, uint32_t& r0, uint32_t& r1, uint32_t& r2, uint32_t& r3) {
  asm volatile("ldmatrix.sync.aligned.m8n8.x4.shared.b16 {%0,%1,%2,%3}, [%4];" : "=r"(r0), "=r"(r1), "=r"(r2), "=r"(r3) : "r"(a) : "memory");
}
__device__ __forceinline__ void ldsm4t(uint32_t a, uint32_t& r0, uint32_t& r1, uint32_t& r2, uint32_t& r3) {
  asm volatile("ldmatrix.sync.aligned.m8n8.x4.trans.shared.b16 {%0,%1,%2,%3}, [%4];" : "=r"(r0), "=r"(r1), "=r"(r2), "=r"(r3) : "r"(a) : "memory");
}
__device__ __forceinline__ void stsm4(uint32_t a, uint32_t r0, uint32_t r1, uint32_t r2, uint32_t r3) {
  asm volatile("stmatrix.sync.aligned.m8n8.x4.shared.b16 [%0], {%1,%2,%3,%4};" ::"r"(a), "r"(r0), "r"(r1), "r"(r2), "r"(r3) : "memory");
}
__device__ __forceinline__ void stsm4t(uint32_t a, uint32_t r0, uint32_t r1, uint32_t r2, uint32_t r3) {
  asm volatile("stmatrix.sync.aligned.m8n8.x4.trans.shared.b16 [%0], {%1,%2,%3,%4};" ::"r"(a), "r"(r0), "r"(r1), "r"(r2), "r"(r3) : "memory");
}
__device__ __forceinline__ void stsm2(uint32_t a, uint32_t r0, uint32_t r1) {
  asm volatile("stmatrix.sync.aligned.m8n8.x2.shared.b16 [%0], {%1,%2};" ::"r"(a), "r"(r0), "r"(r1) : "memory");
}
__device__ __forceinline__ void stsm2t(uint32_t a, uint32_t r0, uint32_t r1) {
  asm volatile("stmatrix.sync.aligned.m8n8.x2.trans.shared.b16 [%0], {%1,%2};" ::"r"(a), "r"(r0), "r"(r1) : "memory");
}
__device__ __forceinline__ void mma16816(float* c, uint32_t a0, uint32_t a1, uint32_t a2, uint32_t a3, uint32_t b0, uint32_t b1) {
  asm("mma.sync.aligned.m16n8k16.row.col.f32.bf16.bf16.f32 {%0,%1,%2,%3}, {%4,%5,%6,%7}, {%8,%9}, {%0,%1,%2,%3};"
      : "+f"(c[0]), "+f"(c[1]), "+f"(c[2]), "+f"(c[3]) : "r"(a0), "r"(a1), "r"(a2), "r"(a3), "r"(b0), "r"(b1));
}
__device__ __forceinline__ void bar_sync(int id, int n) { asm volatile("bar.sync %0, %1;" ::"r"(id), "r"(n) : "memory"); }
__device__ __forceinline__ void bar_arrive(int id, int n) { asm volatile("bar.arrive %0, %1;" ::"r"(id), "r"(n) : "memory"); }
__device__ __forceinline__ void wg_fence() { asm volatile("wgmma.fence.sync.aligned;" ::: "memory"); }
__device__ __forceinline__ void wg_commit() { asm volatile("wgmma.commit_group.sync.aligned;" ::: "memory"); }
__device__ __forceinline__ void wg_wait0() { asm volatile("wgmma.wait_group.sync.aligned 0;" ::: "memory"); }
__device__ __forceinline__ void wg_wait1() { asm volatile("wgmma.wait_group.sync.aligned 1;" ::: "memory"); }
__device__ __forceinline__ void fence_async() { asm volatile("fence.proxy.async.shared::cta;" ::: "memory"); }
__device__ __forceinline__ uint32_t opq(uint32_t x, uint32_t z) { uint32_t r; asm volatile("xor.b32 %0, %1, %2;" : "=r"(r) : "r"(x), "r"(z)); return r; }
__device__ __forceinline__ uint64_t mkdesc(uint32_t addr, uint32_t lbo, uint32_t sbo) {
  return (uint64_t)((addr & 0x3FFFF) >> 4) | ((uint64_t)(lbo >> 4) << 16) | ((uint64_t)(sbo >> 4) << 32);
}
__device__ __forceinline__ uint32_t mapa(uint32_t a, uint32_t rank) {
  uint32_t r; asm("mapa.shared::cluster.u32 %0, %1, %2;" : "=r"(r) : "r"(a), "r"(rank)); return r;
}
__device__ __forceinline__ void mbar_init_expect(uint32_t bar, uint32_t bytes) {
  asm volatile("mbarrier.init.shared::cta.b64 [%0], 1;" ::"r"(bar) : "memory");
  asm volatile("mbarrier.arrive.expect_tx.shared::cta.b64 _, [%0], %1;" ::"r"(bar), "r"(bytes) : "memory");
}
__device__ __forceinline__ void mbar_wait(uint32_t bar) {
#pragma unroll 1
  for (int it = 0; it < (1 << 22); it++) {
    uint32_t ok;
    asm volatile("{\n.reg .pred p;\nmbarrier.try_wait.parity.acquire.cluster.shared::cta.b64 p, [%1], 0;\nselp.u32 %0, 1, 0, p;\n}"
                 : "=r"(ok) : "r"(bar) : "memory");
    if (ok) return;
  }
  __trap();
}
__device__ __forceinline__ void st_async4(uint32_t a, uint32_t bar, uint32_t x, uint32_t y, uint32_t z, uint32_t w) {
  asm volatile("st.async.weak.shared::cluster.mbarrier::complete_tx::bytes.v4.b32 [%0], {%2,%3,%4,%5}, [%1];"
               ::"r"(a), "r"(bar), "r"(x), "r"(y), "r"(z), "r"(w) : "memory");
}

struct cf { float re, im; };
__device__ __forceinline__ cf cmul(cf a, cf b) { return {fmaf(a.re, b.re, -a.im * b.im), fmaf(a.re, b.im, a.im * b.re)}; }
__device__ __forceinline__ cf csq(cf a) { return {fmaf(a.re, a.re, -a.im * a.im), (a.re + a.re) * a.im}; }
__device__ __forceinline__ cf cexp_p(float xl, float y, float p) {
  float mag; asm("ex2.approx.ftz.f32 %0, %1;" : "=f"(mag) : "f"(xl * p));
  const float th = y * p;
  const float k = rintf(th * 0.15915494309189535f);
  float r = fmaf(k, -6.2831854820251465f, th);
  r = fmaf(k, 1.7484555314695172e-07f, r);
  return {mag * __cosf(r), mag * __sinf(r)};
}
__device__ __forceinline__ uint32_t ysw(int c) { return (uint32_t)(c ^ ((c >> 3) & 3)) * 16u; }

#define CMUL2(OR, OI, xr, xi, yr, yi, nyi) do { OR = hfma2(xr, yr, hmul2(xi, nyi)); OI = hfma2(xr, yi, hmul2(xi, yr)); } while (0)

__device__ __forceinline__ uint32_t gate_slow(const __nv_bfloat16* u, const __nv_bfloat16* gw, int row) {
  float s = 0.f;
  const uint32_t* xr = (const uint32_t*)(u + (size_t)row * D);
  const uint32_t* wr = (const uint32_t*)gw;
#pragma unroll 1
  for (int j = 0; j < D / 2; j++) { const uint32_t pr = hmul2(xr[j], wr[j]); s += bf_lo(pr); s += bf_hi(pr); }
  s = bf_round(s);
  return pack_bf16(1.f / (1.f + expf(-s)), 0.f);
}

__device__ __forceinline__ uint2 gate_ld(int x) {
  uint2 gv;
  asm volatile("ld.relaxed.gpu.global.v2.u32 {%0,%1}, [%2];" : "=r"(gv.x), "=r"(gv.y) : "l"(g_gate + x * 2) : "memory");
  return gv;
}
__device__ __noinline__ uint32_t gate_poll(const Params* pp, int x, uint32_t tag) {
  uint2 gv;
#pragma unroll 1
  for (int spins = 0; spins < (1 << 16); spins++) {
    gv = gate_ld(x);
    if ((gv.x >> 16) == tag && (gv.y >> 16) == tag) return __byte_perm(gv.x, gv.y, 0x5410);
  }
  return __byte_perm(gate_slow(pp->u, pp->gw, x * 2), gate_slow(pp->u, pp->gw, x * 2 + 1), 0x5410);
}
__device__ __forceinline__ uint32_t gate_fin(const Params& p, uint2 gv, int x, uint32_t tag) {
  if ((gv.x >> 16) == tag && (gv.y >> 16) == tag) return __byte_perm(gv.x, gv.y, 0x5410);
  return gate_poll(&p, x, tag);
}

__device__ __forceinline__ void ld4ch(uint32_t* v, uint32_t addr) {
#pragma unroll
  for (int k = 0; k < 4; k++) v[k] = lds32(addr + k * CH_BYTES);
}
__device__ __forceinline__ void skip_terms(uint32_t* ua, uint32_t* ub, uint32_t sb, int x, uint2 dA, uint2 dB) {
  const int c = x >> 2;
  uint32_t uu[4];
  ld4ch(uu, sb + CH_OFF + (x & 3) * 4 + U_OFF + (c & 3) * U_CS + (63 - (c >> 2)) * 16);
#pragma unroll
  for (int k = 0; k < 4; k++) {
    ua[k] = hmul2(uu[k], __byte_perm((k & 2) ? dA.y : dA.x, 0, (k & 1) ? 0x3232 : 0x1010));
    ub[k] = hmul2(uu[k], __byte_perm((k & 2) ? dB.y : dB.x, 0, (k & 1) ? 0x3232 : 0x1010));
  }
}
__device__ __forceinline__ uint4 mix(const uint32_t* a, const uint32_t* b, const uint32_t* ua, const uint32_t* ub, uint32_t g2) {
  const uint32_t h2 = hsub2(0x3f803f80u, g2);
  uint32_t o[4];
#pragma unroll
  for (int k = 0; k < 4; k++) o[k] = hadd2(hmul2(g2, hadd2(a[k], ua[k])), hmul2(h2, hadd2(b[k], ub[k])));
  return make_uint4(__byte_perm(o[0], o[1], 0x5410), __byte_perm(o[2], o[3], 0x5410), __byte_perm(o[0], o[1], 0x7632), __byte_perm(o[2], o[3], 0x7632));
}
__device__ __forceinline__ void send_box(uint32_t sb, int slot, int wtid, uint32_t rank, uint4 r) {
  st_async4(mapa(sb + XIN_OFF + slot * 2048 + wtid * 16, rank ^ 1), mapa(sb + B_X + slot * 8, rank ^ 1), r.x, r.y, r.z, r.w);
}
__device__ __forceinline__ void merge_box(uint32_t sb, const CUtensorMap* tm_out, int slot, int wtid, uint32_t rank, int oc0, uint4 r, int barid) {
  const uint32_t st = sb + RAW_OFF + slot * 4096 + wtid * 16;
  sts64(st + rank * 8, r.x, r.y); sts64(st + 2048 + rank * 8, r.z, r.w);
  mbar_wait(sb + B_X + slot * 8);
  const uint4 q = lds128(sb + XIN_OFF + slot * 2048 + wtid * 16);
  sts64(st + (rank ^ 1) * 8, q.x, q.y); sts64(st + 2048 + (rank ^ 1) * 8, q.z, q.w);
  fence_async();
  bar_sync(barid, 128);
  if (wtid == 0) {
    asm volatile("cp.async.bulk.tensor.3d.global.shared::cta.bulk_group [%0, {%2, %3, %4}], [%1];"
                 ::"l"(tm_out), "r"(sb + RAW_OFF + slot * 4096), "r"(oc0), "r"((2 * slot + (int)rank) * 128), "r"(0) : "memory");
    asm volatile("cp.async.bulk.commit_group;" ::: "memory");
  }
}

__device__ __forceinline__ uint32_t band2(int e, int lo, int hi) {
  uint32_t r = ((uint32_t)(e - lo) <= (uint32_t)(hi - lo) ? 0x3f80u : 0u) | ((uint32_t)(e - 1 - lo) <= (uint32_t)(hi - lo) ? 0x3f800000u : 0u);
  asm volatile("" : "+r"(r));
  return r;
}

__device__ __forceinline__ void stage_done(uint32_t sb, int stage, int lane) {
  __syncwarp();
  if (lane == 0) asm volatile("mbarrier.arrive.shared::cta.b64 _, [%0];" ::"r"(sb + B_ST + 8 * stage) : "memory");
}
#define PK2(v, i) pack_bf16(v[i], v[(i) + 1])

__device__ __forceinline__ void conv_dense(uint32_t sb, uint32_t cb, uint32_t zz) {
  const int lane = threadIdx.x & 31, wq = (threadIdx.x >> 5) & 3, br = wq >> 1, hf = wq & 1, g = lane >> 2, t = lane & 3;
  const uint32_t rb = cb + R_OFF + br * R_BR;
  const int eo = 16 * hf + g - 2 * t;
  const int x0 = RD_X0 - (eo + 536);
  const uint32_t fa = rb + ((g & 1) ? 2 * x0 : RD_CS + 2 * x0 + 2);
  const uint64_t ub = mkdesc(cb + U_OFF, U_CS, 128);
  const uint32_t yd = cb + Y0_OFF + br * 4096 + ysw(4 * (63 - 8 * (lane >> 4) - (lane & 7)) + 2 * hf + ((lane >> 3) & 1));
  uint32_t A[2][4][4];
  float e64[32], e56[28], e48[24];
  auto loadA = [&](int j) {
#pragma unroll
    for (int k = 0; k < 4; k++) {
      const int s = 34 - 4 * j - k;
      if (s >= 0) {
        if (k == 0 && j == 0) A[0][0][2] = lds32(fa + (2 * s + 2) * 16);
        A[j & 1][k][0] = lds32(fa + (2 * s + 1) * 16);
        A[j & 1][k][1] = lds32(fa + (2 * s) * 16);
      }
    }
#pragma unroll
    for (int k = 0; k < 4; k++) {
      if (34 - 4 * j - k >= 0) {
        A[j & 1][k][3] = A[j & 1][k][0];
        if (k) A[j & 1][k][2] = A[j & 1][k - 1][1];
        else if (j) A[j & 1][0][2] = A[(j - 1) & 1][3][1];
      }
    }
  };
  loadA(0); loadA(1);
#pragma unroll
  for (int j = 0; j < 9; j++) {
    if (j == 4) {
      wg_wait0();
      stsm2t(yd - 7 * 512, PK2(e64, 28), PK2(e64, 30));
#pragma unroll
      for (int i = 0; i < 28; i++) e56[i] = FCPY(e64[i]);
      stage_done(sb, 0, lane);
    }
    if (j == 8) {
      wg_wait0();
      stsm2t(yd - 6 * 512, PK2(e56, 24), PK2(e56, 26));
#pragma unroll
      for (int i = 0; i < 24; i++) e48[i] = FCPY(e56[i]);
      stage_done(sb, 1, lane);
    }
    wg_fence();
#pragma unroll
    for (int k = 0; k < 4; k++) {
      const int s = 34 - 4 * j - k;
      if (s >= 0) {
        const int o = 2 * s - 66 + 128;
        const int cc = o & 3, rs = (o >> 2) - 32;
        const uint64_t desc = ub + (uint64_t)((cc * U_CS - rs * 16) >> 4);
        const uint32_t* a = A[j & 1][k];
        if (j < 4) wgmma_rs<64, 0>(e64, a[0], a[1], a[2], a[3], desc, s != 34);
        else if (j < 8) wgmma_rs<56, 0>(e56, a[0], a[1], a[2], a[3], desc, 1);
        else wgmma_rs<48, 0>(e48, a[0], a[1], a[2], a[3], desc, 1);
      }
    }
    wg_commit();
    if (j >= 1 && j < 8) { wg_wait1(); loadA(j + 1); }
  }
  wg_wait0();
#pragma unroll
  for (int i = 0; i < 6; i += 2) stsm4t(yd - i * 512, PK2(e48, 4 * i), PK2(e48, 4 * i + 2), PK2(e48, 4 * i + 4), PK2(e48, 4 * i + 6));
}

__device__ __noinline__ void gate_cta(const Params* pp) {
  const __nv_bfloat16 *u = pp->u, *gw = pp->gw;
  const int lane = threadIdx.x & 31;
  unsigned int epoch;
  asm volatile("ld.relaxed.gpu.global.u32 %0, [%1];" : "=r"(epoch) : "l"(&g_epoch) : "memory");
  const uint4 gw0 = ldg128(gw + lane * 8), gw1 = ldg128(gw + 256 + lane * 8);
  const uint32_t ws[8] = {gw0.x, gw0.y, gw0.z, gw0.w, gw1.x, gw1.y, gw1.z, gw1.w};
  const uint32_t tag = (epoch + 1) & 0xffffu;
  uint4 gx[4][2], nx[4][2];
  int grow = (blockIdx.x * 20 + (threadIdx.x >> 5)) * 4;
#pragma unroll
  for (int i = 0; i < 4; i++) {
    nx[i][0] = ldg128(u + (size_t)(grow + i) * D + lane * 8);
    nx[i][1] = ldg128(u + (size_t)(grow + i) * D + 256 + lane * 8);
  }
#pragma unroll 1
  for (; grow < L; grow += 80 * NGATE) {
    const int nrow = min(grow + 80 * NGATE, L - 4);
#pragma unroll
    for (int i = 0; i < 4; i++) {
      gx[i][0] = nx[i][0]; gx[i][1] = nx[i][1];
      nx[i][0] = ldg128(u + (size_t)(nrow + i) * D + lane * 8);
      nx[i][1] = ldg128(u + (size_t)(nrow + i) * D + 256 + lane * 8);
    }
    float c[2][4];
#pragma unroll
    for (int i = 0; i < 2; i++) {
      const uint4 *x = gx[2 * i], *y = gx[2 * i + 1];
      const uint32_t xs[8] = {x[0].x, x[0].y, x[0].z, x[0].w, x[1].x, x[1].y, x[1].z, x[1].w};
      const uint32_t ys[8] = {y[0].x, y[0].y, y[0].z, y[0].w, y[1].x, y[1].y, y[1].z, y[1].w};
      c[i][0] = c[i][1] = c[i][2] = c[i][3] = 0.f;
#pragma unroll
      for (int j = 0; j < 8; j += 2)
        mma16816(c[i], hmul2(xs[j], ws[j]), hmul2(ys[j], ws[j]), hmul2(xs[j + 1], ws[j + 1]), hmul2(ys[j + 1], ws[j + 1]), 0x3f803f80u, 0x3f803f80u);
    }
    float s = (lane & 2) ? ((lane & 1) ? c[1][2] : c[1][0]) : ((lane & 1) ? c[0][2] : c[0][0]);
#pragma unroll
    for (int o = 4; o < 32; o <<= 1) s += __shfl_xor_sync(0xffffffffu, s, o);
    s = bf_round(s);
    const float gv = 1.f / (1.f + expf(-s));
    const uint32_t w = (tag << 16) | (pack_bf16(gv, 0.f) & 0xffffu);
    if (lane < 4) asm volatile("st.relaxed.gpu.global.u32 [%0], %1;" ::"l"(&g_gate[grow + lane]), "r"(w) : "memory");
  }
  __syncthreads();
  if (threadIdx.x == 0 && atomicAdd(&g_ticket, 1u) == NCTA + NGATE - 1) { g_ticket = 0; g_epoch = epoch + 1; }
}

__global__ void __cluster_dims__(2, 1, 1) __launch_bounds__(640, 1)
ssm_kernel(const __grid_constant__ Params p, const __grid_constant__ CUtensorMap tm_in, const __grid_constant__ CUtensorMap tm_out) {
  extern __shared__ __align__(1024) unsigned char smem_raw[];
  const uint32_t sb = (uint32_t)__cvta_generic_to_shared(smem_raw);
  const int tid = threadIdx.x, lane = tid & 31;
  const int warp = __shfl_sync(0xffffffffu, tid >> 5, 0);
  const int ch = warp >> 2, wq = warp & 3, br = wq >> 1, hf = wq & 1;
  const int g = lane >> 2, t = lane & 3;
  if (__builtin_expect(blockIdx.x < NGATE, 0)) { gate_cta(&p); return; }
  const int bid = blockIdx.x - NGATE;
  const int d = bid * 4 + ch;
  const uint32_t rank = blockIdx.x & 1;
  const uint32_t cb = sb + CH_OFF + ch * CH_BYTES;
  const int wtid = tid & 127;
  const int oc0 = (bid >> 1) * 8;
  STAMP(0); GT(0);

  if (warp >= 16) {
    if (wtid == 0) {
      mbar_init_expect(sb + B_RAW, 32768);
#pragma unroll
      for (int i = 0; i < 4; i++) mbar_init_expect(sb + B_X + 8 * i, 2048);
      asm volatile("mbarrier.init.shared::cta.b64 [%0], 128;" ::"r"(sb + B_U) : "memory");
      asm volatile("mbarrier.init.shared::cta.b64 [%0], 128;" ::"r"(sb + B_W) : "memory");
#pragma unroll
      for (int i = 0; i < 7; i++) asm volatile("mbarrier.init.shared::cta.b64 [%0], 16;" ::"r"(sb + B_ST + 8 * i) : "memory");
      asm volatile("fence.mbarrier_init.release.cluster;" ::: "memory");
      asm volatile("fence.proxy.async.shared::cta;" ::: "memory");
    }
    __syncwarp();
    asm volatile("barrier.cluster.arrive.relaxed.aligned;" ::: "memory");
    unsigned int epoch;
    asm volatile("ld.relaxed.gpu.global.u32 %0, [%1];" : "=r"(epoch) : "l"(&g_epoch) : "memory");
    asm volatile("barrier.cluster.wait.aligned;" ::: "memory");
    if (wtid == 0) {
      asm volatile("cp.async.bulk.tensor.5d.shared::cluster.global.mbarrier::complete_tx::bytes.multicast::cluster [%0], [%1, {%3, %4, %4, %4, %5}], [%2], %6;"
                   ::"r"(sb + RAW_OFF + rank * 16384), "l"(&tm_in), "r"(sb + B_RAW), "r"(oc0), "r"(0), "r"((int)rank * 32), "h"((unsigned short)3) : "memory");
    }
    sts128(sb + CH_OFF + wq * CH_BYTES + U_OFF + (lane >> 3) * U_CS + (64 + (lane & 7)) * 16, 0, 0, 0, 0);
    uint32_t BA[3][4], BC[3][4];
    {
      const int l1 = br ? 3 : 6, h1 = br ? 5 : 10;
#pragma unroll
      for (int i = 0; i < 3; i++) {
        const int e = 16 * hf + g - 2 * t + 16 - 16 * i;
        BA[i][0] = band2(e, l1, h1); BA[i][1] = band2(e + 8, l1, h1); BA[i][2] = band2(e - 8, l1, h1); BA[i][3] = BA[i][0];
        BC[i][0] = band2(e, 3, 4); BC[i][1] = band2(e + 8, 3, 4); BC[i][2] = band2(e - 8, 3, 4); BC[i][3] = BC[i][0];
      }
    }
    const uint32_t tag = (epoch + 1) & 0xffffu;
    if (wtid == 0) sts32(sb + TAG_OFF, tag);
    STAMP(3);
    mbar_wait(sb + B_RAW);
    STAMP(4);
    {
      const uint32_t dst = sb + CH_OFF + (g & 3) * CH_BYTES + U_OFF + t * U_CS + (63 - wq * 16) * 16;
#pragma unroll
      for (int h = 0; h < 2; h++) {
        uint32_t r[8][4];
#pragma unroll
        for (int i = 0; i < 8; i++) ldsm4t(sb + RAW_OFF + (wq * 16 + h * 8 + i) * 512 + lane * 16, r[i][0], r[i][1], r[i][2], r[i][3]);
        if ((uint32_t)(g >> 2) == rank) {
#pragma unroll
          for (int i = 0; i < 8; i++) sts128(dst - (h * 8 + i) * 16, r[i][0], r[i][1], r[i][2], r[i][3]);
        }
      }
    }
    fence_async();
    asm volatile("mbarrier.arrive.shared::cta.b64 _, [%0];" ::"r"(sb + B_U) : "memory");
    bar_sync(5, 128);
    STAMP(5);
    {
      const int mrow = lane & 7, mi = lane >> 3;
      const uint64_t ub0 = mkdesc(sb + CH_OFF + U_OFF, U_CS, 128);
      {
        float w1[24], w3[16];
#pragma unroll
        for (int i = 0; i < 24; i++) w1[i] = 0.f;
#pragma unroll
        for (int i = 0; i < 16; i++) w3[i] = 0.f;
        uint32_t wa[3], sa[2];
#pragma unroll
        for (int i = 0; i < 3; i++) {
          const int c = 4 * (47 - 8 * (2 * i + (mi >> 1)) - mrow) + 2 * hf + (mi & 1);
          wa[i] = sb + CH_OFF + (br ? W3_OFF : W5_OFF) + (5 - (c >> 5)) * 576 + ((c & 31) >> 3) * 144 + (c & 7) * 16;
          if (i) sa[i - 1] = sb + CH_OFF + S2_OFF + (c + (c >> 3)) * 16;
        }
#pragma unroll 1
        for (int k = 0; k < 4; k++) {
          wg_fence();
#pragma unroll
          for (int i = 0; i < 3; i++)
            wgmma_rs<48, 0>(w1, BA[i][0], BA[i][1], BA[i][2], BA[i][3],
                            ub0 + (uint64_t)((k * CH_BYTES + ((2 * i + 2) & 3) * U_CS + (16 + (i == 0)) * 16) >> 4), i);
#pragma unroll
          for (int i = 0; i < 3; i++)
            wgmma_rs<32, 0>(w3, BC[i][0], BC[i][1], BC[i][2], BC[i][3],
                            ub0 + (uint64_t)((k * CH_BYTES + ((2 * i + 2) & 3) * U_CS + (32 + (i == 0)) * 16) >> 4), i);
          wg_commit();
          wg_wait0();
#pragma unroll
          for (int i = 0; i < 3; i++)
            stsm4t(wa[i] + k * CH_BYTES, pack_bf16(w1[8 * i], w1[8 * i + 1]), pack_bf16(w1[8 * i + 2], w1[8 * i + 3]),
                   pack_bf16(w1[8 * i + 4], w1[8 * i + 5]), pack_bf16(w1[8 * i + 6], w1[8 * i + 7]));
          if (br == 0) {
#pragma unroll
            for (int i = 0; i < 2; i++)
              stsm4t(sa[i] + k * CH_BYTES, pack_bf16(w3[8 * i], w3[8 * i + 1]), pack_bf16(w3[8 * i + 2], w3[8 * i + 3]),
                     pack_bf16(w3[8 * i + 4], w3[8 * i + 5]), pack_bf16(w3[8 * i + 6], w3[8 * i + 7]));
          }
        }
      }
      {
        uint32_t BB[4][4];
        const int l2 = br ? 5 : 12, h2 = br ? 11 : 20;
#pragma unroll
        for (int i = 0; i < 4; i++) {
          const int e = 16 * hf + g - 2 * t + 32 - 16 * i;
          BB[i][0] = band2(e, l2, h2); BB[i][1] = band2(e + 8, l2, h2); BB[i][2] = band2(e - 8, l2, h2); BB[i][3] = BB[i][0];
        }
        float w2[2][16];
#pragma unroll
        for (int i = 0; i < 16; i++) { w2[0][i] = 0.f; w2[1][i] = 0.f; }
        uint32_t wa[2];
#pragma unroll
        for (int i = 0; i < 2; i++) {
          const int c = 4 * (31 - 8 * (2 * i + (mi >> 1)) - mrow) + 2 * hf + (mi & 1), pp = c >> 1;
          wa[i] = sb + CH_OFF + (br ? W7_OFF : W9_OFF) + (1 - (pp >> 5)) * 1152 + (c & 1) * 576 + ((pp & 31) >> 3) * 144 + (pp & 7) * 16;
        }
#pragma unroll 1
        for (int kp = 0; kp < 2; kp++) {
          wg_fence();
#pragma unroll
          for (int k = 0; k < 2; k++)
#pragma unroll
            for (int i = 0; i < 4; i++)
              wgmma_rs<32, 0>(w2[k], BB[i][0], BB[i][1], BB[i][2], BB[i][3],
                              ub0 + (uint64_t)(((2 * kp + k) * CH_BYTES + ((2 * i) & 3) * U_CS + (32 + (i < 2)) * 16) >> 4), i);
          wg_commit();
          wg_wait0();
#pragma unroll
          for (int k = 0; k < 2; k++)
#pragma unroll
            for (int i = 0; i < 2; i++)
              stsm4t(wa[i] + (2 * kp + k) * CH_BYTES, pack_bf16(w2[k][8 * i], w2[k][8 * i + 1]), pack_bf16(w2[k][8 * i + 2], w2[k][8 * i + 3]),
                     pack_bf16(w2[k][8 * i + 4], w2[k][8 * i + 5]), pack_bf16(w2[k][8 * i + 6], w2[k][8 * i + 7]));
        }
      }
    }
    fence_async();
    asm volatile("mbarrier.arrive.shared::cta.b64 _, [%0];" ::"r"(sb + B_W) : "memory");
    STAMP(7);
    const uint2 dA = ldg64(p.A_D + bid * 4), dB = ldg64(p.B_D + bid * 4);
    {
      uint2 gl[4];
#pragma unroll
      for (int i = 0; i < 4; i++) gl[i] = gate_ld(i * 128 + wtid);
#pragma unroll
      for (int box = 0; box < 4; box++) {
        const int x = box * 128 + wtid;
        uint32_t ua[4], ub[4], ya[4], yb[4];
        skip_terms(ua, ub, sb, x, dA, dB);
        const uint32_t g2 = gate_fin(p, gl[box], x, tag);
        const uint32_t yo = sb + CH_OFF + (x & 3) * 4 + ysw(x >> 2);
        mbar_wait(sb + B_ST + 8 * box);
        STAMP(8 + box);
        ld4ch(ya, yo + Y0_OFF); ld4ch(yb, yo + Y0_OFF + 4096);
        if (box >= 2) {
          uint32_t a2[4], b2[4];
          ld4ch(a2, yo + Y2_OFF - 1024); ld4ch(b2, yo + Y2_OFF - 1024 + 3072);
#pragma unroll
          for (int k = 0; k < 4; k++) { ya[k] = hadd2(ya[k], a2[k]); yb[k] = hadd2(yb[k], b2[k]); }
        }
        const uint4 r = mix(ya, yb, ua, ub, g2);
        if ((uint32_t)(box & 1) != rank) send_box(sb, box >> 1, wtid, rank, r);
        else merge_box(sb, &tm_out, box >> 1, wtid, rank, oc0, r, 5);
      }
      STAMP(13);
    }
    if (wtid == 0) {
      if (atomicAdd(&g_ticket, 1u) == NCTA + NGATE - 1) { g_ticket = 0; g_epoch = epoch + 1; }
      asm volatile("cp.async.bulk.wait_group.read 0;" ::: "memory");
    }
    STAMP(15);
    return;
  }
  asm volatile("barrier.cluster.arrive.relaxed.aligned;" ::: "memory");

  const int moff = (bid * 4 + (tid >> 7)) * NM + (tid & 63) * 2;
  const int brt = (tid >> 6) & 1;
  const __nv_bfloat16* const* tp = p.t + (brt ? 0 : 6);
  const uint32_t q0 = *(const uint32_t*)(tp[0] + moff), q1 = *(const uint32_t*)(tp[1] + moff);
  const uint32_t q2 = *(const uint32_t*)(tp[2] + moff), q3 = *(const uint32_t*)(tp[3] + moff);
  const uint2 ldt4 = *(const uint2*)(tp[4] + bid * 4);
  const uint32_t q4 = *(const uint32_t*)(tp[brt ? 2 : 5] + moff), q5 = *(const uint32_t*)(tp[brt ? 3 : 6] + moff);

  for (int i = wtid & 63; i < R_BR / 16; i += 64) sts128(cb + R_OFF + br * R_BR + i * 16, 0, 0, 0, 0);
  STAMP(1);

  float acc[5][4];
  float k2048 = 0.f;
  const uint32_t scr = cb + Y0_OFF + wq * SCR_BYTES;
  const uint32_t scr2 = sb + XIN_OFF + warp * 640;
  {
    const uint32_t ldt2 = (ch & 2) ? ldt4.y : ldt4.x;
    const float dt = bf_round(expf((ch & 1) ? bf_hi(ldt2) : bf_lo(ldt2)));
#pragma unroll
    for (int i = 0; i < 5; i++) acc[i][0] = acc[i][1] = acc[i][2] = acc[i][3] = 0.f;
    cf cc[2], zz1[2], zz128[2];
#pragma unroll
    for (int r = 0; r < 2; r++) {
      float v0 = r ? bf_hi(q0) : bf_lo(q0), v1 = r ? bf_hi(q1) : bf_lo(q1), v2 = r ? bf_hi(q2) : bf_lo(q2);
      float v3 = r ? bf_hi(q3) : bf_lo(q3), v4 = r ? bf_hi(q4) : bf_lo(q4), v5 = r ? bf_hi(q5) : bf_lo(q5);
      if (br == 0) { cc[r] = cmul(cf{v2, v3}, cf{dt * v4, dt * v5}); }
      else { v0 = -bf_round(expf(v0)); cc[r] = cf{2.f * dt * v2, 2.f * dt * v3}; }
      const float xl = (dt * v0) * 1.4426950408889634f, y = dt * v1;
      zz1[r] = cexp_p(xl, y, 1.f); zz128[r] = cexp_p(xl, y, 128.f);
    }
    STAMP(2);
    const uint32_t tb = scr + lane * 16;
    const uint32_t ta = scr + (lane >> 3) * 512 + (lane & 7) * 16;
    const uint32_t tc = ((lane & 8) ? scr2 : scr + 4096) + (lane >> 4) * 128 + (lane & 7) * 16;
    const uint32_t tm = scr2 + 512 + ((lane >> 3) & 1) * 64 + (lane >> 4) * 16;
#pragma unroll 1
    for (int r = 0; r < 2; r++) {
      const cf c = r ? cc[1] : cc[0], z1 = r ? zz1[1] : zz1[0], z128 = r ? zz128[1] : zz128[0];
      const cf z2 = csq(z1), z4 = csq(z2), z8 = csq(z4);
      const cf z16 = csq(z8), z24 = cmul(z16, z8), z32 = csq(z16), z40 = cmul(z32, z8), z48 = csq(z24), z56 = cmul(z32, z24), z64 = csq(z32);
      const cf z256 = csq(z128), z512 = csq(z256), z1024 = csq(z512), z2048 = csq(z1024);
      {
        float kk = fmaf(c.re, z2048.re, -c.im * z2048.im);
#pragma unroll
        for (int o = 16; o; o >>= 1) kk += __shfl_xor_sync(0xffffffffu, kk, o);
        k2048 += kk;
      }
      __syncwarp();
      {
        uint32_t xr[4] = {pack_bf16(1.f, z8.re), pack_bf16(z16.re, z24.re), pack_bf16(z32.re, z40.re), pack_bf16(z48.re, z56.re)};
        uint32_t xi[4] = {pack_bf16(0.f, -z8.im), pack_bf16(-z16.im, -z24.im), pack_bf16(-z32.im, -z40.im), pack_bf16(-z48.im, -z56.im)};
        sts128(tb + 0 * 512, xr[0], xr[1], xr[2], xr[3]);
        sts128(tb + 2 * 512, xi[0], xi[1], xi[2], xi[3]);
        const uint32_t yr = pack_bf16(z64.re, z64.re), nyi = pack_bf16(z64.im, z64.im), yi = nyi ^ 0x80008000u;
        uint32_t o[4], q[4];
#pragma unroll
        for (int i = 0; i < 4; i++) CMUL2(o[i], q[i], xr[i], xi[i], yr, yi, nyi);
        sts128(tb + 1 * 512, o[0], o[1], o[2], o[3]);
        sts128(tb + 3 * 512, q[0], q[1], q[2], q[3]);
      }
      {
        const cf h1 = cmul(c, z128), h2 = cmul(c, z256), h3 = cmul(h1, z256), h4 = cmul(c, z512), h5 = cmul(h1, z512), h6 = cmul(h2, z512), h7 = cmul(h3, z512);
        const cf e1 = cmul(c, z1), e2 = cmul(c, z2), e3 = cmul(e1, z2), e129 = cmul(h1, z1), e130 = cmul(h1, z2), e131 = cmul(e129, z2);
        const cf e258 = cmul(h2, z2), e386 = cmul(h3, z2);
        const uint32_t pr0 = pack_bf16(c.re, e1.re), pr2 = pack_bf16(h1.re, e129.re), pi0 = pack_bf16(c.im, e1.im), pi2 = pack_bf16(h1.im, e129.im);
        sts128(tb + 4 * 512, pr0, pack_bf16(e2.re, e3.re), pr2, pack_bf16(e130.re, e131.re));
        sts128(tb + 5 * 512, pi0, pack_bf16(e2.im, e3.im), pi2, pack_bf16(e130.im, e131.im));
        uint32_t xr[4] = {pack_bf16(h2.re, e258.re), pack_bf16(h3.re, e386.re), pack_bf16(h4.re, h5.re), pack_bf16(h6.re, h7.re)};
        uint32_t xi[4] = {pack_bf16(h2.im, e258.im), pack_bf16(h3.im, e386.im), pack_bf16(h4.im, h5.im), pack_bf16(h6.im, h7.im)};
        sts128(tb + 6 * 512, xr[0], xr[1], xr[2], xr[3]);
        sts128(tb + 7 * 512, xi[0], xi[1], xi[2], xi[3]);
        xr[1] = __byte_perm(xr[0], xr[1], 0x5410); xi[1] = __byte_perm(xi[0], xi[1], 0x5410);
        xr[0] = __byte_perm(pr0, pr2, 0x5410); xi[0] = __byte_perm(pi0, pi2, 0x5410);
        const uint32_t yr = pack_bf16(z1024.re, z1024.re), yi = pack_bf16(z1024.im, z1024.im), nyi = yi ^ 0x80008000u;
        uint32_t o[4], q[4];
#pragma unroll
        for (int i = 0; i < 4; i++) CMUL2(o[i], q[i], xr[i], xi[i], yr, yi, nyi);
        sts128(tb + 8 * 512, o[0], o[1], o[2], o[3]);
        sts128(scr2 + lane * 16, q[0], q[1], q[2], q[3]);
        const uint32_t m4 = pack_bf16(z4.re, z4.im);
        sts16(scr2 + 512 + lane * 2, m4); sts16(scr2 + 576 + lane * 2, m4 >> 16);
      }
      __syncwarp();
#pragma unroll
      for (int kp = 0; kp < 2; kp++) {
        uint32_t rr[2], ri[2], yr[2], yi[2];
        ldsm4t(tc + kp * 256, rr[0], ri[0], rr[1], ri[1]);
        ldsm4(tm + kp * 32, yr[0], yi[0], yr[1], yi[1]);
#pragma unroll
        for (int k2 = 0; k2 < 2; k2++) {
          const int kk = kp * 2 + k2;
          uint32_t a0, a1, a2, a3, pr, pi, qr, qi, xr, xi;
          ldsm4t(ta + kk * 128, a0, a1, a2, a3);
          ldsm4t(ta + 2048 + kk * 128, pr, pi, qr, qi);
          const uint32_t nyi = yi[k2] ^ 0x80008000u;
          mma16816(acc[0], a0, a1, a2, a3, pr, pi);
          mma16816(acc[2], a0, a1, a2, a3, qr, qi);
          mma16816(acc[4], a0, a1, a2, a3, rr[k2], ri[k2]);
          CMUL2(xr, xi, pr, pi, yr[k2], yi[k2], nyi);
          mma16816(acc[1], a0, a1, a2, a3, xr, xi);
          CMUL2(xr, xi, qr, qi, yr[k2], yi[k2], nyi);
          mma16816(acc[3], a0, a1, a2, a3, xr, xi);
        }
      }
    }
  }
  STAMP(3);
  __syncwarp();
  {
    const uint32_t xs = scr + lane * 16;
#define OTH(i, k) __float_as_uint(hf ? acc[i][k] : acc[i][2 + (k)])
    sts128(xs, OTH(0, 0), OTH(0, 1), OTH(1, 0), OTH(1, 1));
    sts128(xs + 512, OTH(2, 0), OTH(2, 1), OTH(3, 0), OTH(3, 1));
    sts128(xs + 1024, OTH(4, 0), OTH(4, 1), __float_as_uint(k2048), 0);
#undef OTH
  }

  bar_sync(7 + (warp >> 1), 64);
  STAMP(4);
  {
    const uint32_t xo = cb + Y0_OFF + (wq ^ 1) * SCR_BYTES + lane * 16;
    const uint4 o0 = lds128(xo), o1 = lds128(xo + 512), o2 = lds128(xo + 1024);
    const uint32_t rb = cb + R_OFF + br * R_BR;
#define OWN(i, k) (hf ? acc[i][2 + (k)] : acc[i][k])
    const uint32_t vP = pack_bf16(OWN(0, 1) + __uint_as_float(o0.y), OWN(0, 0) + __uint_as_float(o0.x));
    const uint32_t vP4 = pack_bf16(OWN(1, 1) + __uint_as_float(o0.w), OWN(1, 0) + __uint_as_float(o0.z));
    const uint32_t vQ = pack_bf16(OWN(2, 1) + __uint_as_float(o1.y), OWN(2, 0) + __uint_as_float(o1.x));
    const uint32_t vQ4 = pack_bf16(OWN(3, 1) + __uint_as_float(o1.w), OWN(3, 0) + __uint_as_float(o1.z));
    const uint32_t vR = pack_bf16(OWN(4, 1) + __uint_as_float(o2.y), OWN(4, 0) + __uint_as_float(o2.x));
#undef OWN
    const int j = g + 8 * hf;
    {
      const int a = 2 * (t & 1) + 64 * (t & 2) + 8 * j;
      const uint32_t ad = rb + 2 * (RD_X0 - 1 - a);
      const uint32_t a1 = (t & 2) ? ad - 8 : ad, a2 = (t & 2) ? ad : ad - 8;
      const uint32_t w1 = (t & 2) ? vP4 : vP, w2 = (t & 2) ? vP : vP4;
      sts32(a1, w1); sts32(a2, w2);
      sts16(a1 + RD_CS + 2, w1); sts16(a1 + RD_CS + 4, w1 >> 16);
      sts16(a2 + RD_CS + 2, w2); sts16(a2 + RD_CS + 4, w2 >> 16);
    }
    if (t < 2) {
      const int b = 256 + 128 * t + 8 * j;
      const uint32_t ad = rb + 2 * (RD_X0 - 6 - b);
      const uint32_t v22 = __byte_perm(vQ4, 0, 0x3232), v00 = __byte_perm(vQ, 0, 0x3232);
      sts16(ad, vQ4);
      sts64(ad + 2, v22, __byte_perm(vQ4, vQ, 0x5432));
      sts32(ad + 10, v00);
      if (b != 256) { sts16(ad + 14, v00); sts128(ad + RD_CS + 2, vQ4, v22, vQ, v00); }
      else { sts64(ad + RD_CS + 2, vQ4, v22); sts32(ad + RD_CS + 10, vQ); sts16(ad + RD_CS + 14, v00); }
    } else {
      const uint32_t ao = rb + R_O2 + 2 * (159 - (32 * t + j)), ae = ao - (R_O2 - R_E2) + 2;
      sts16(ao, vQ4 >> 16); sts16(ao + RS_CS + 2, vQ4 >> 16); sts16(ao - 32, vQ4); sts16(ao - 32 + RS_CS + 2, vQ4);
      sts16(ae - 32, vQ); sts16(ae - 32 + RS_CS + 2, vQ);
      if (lane != 2 || hf) { sts16(ae, vQ >> 16); sts16(ae + RS_CS + 2, vQ >> 16); }
      else {
        const uint32_t vv = __byte_perm(vQ, 0, 0x3232), ad = rb + 2 * (RD_X0 - 514);
        sts16(ad, vv); sts32(ad + 2, vv); sts16(ad + 6, vv); sts64(ad + RD_CS + 2, vv, vv);
      }
    }
    {
      const uint32_t a = rb + ((g & 1) ? R_O3 : R_E3 + 2) + 2 * (159 - (64 + 16 * t + (j >> 1)));
      const bool p1024 = (lane == 0) && (hf == 0);
      const uint32_t a00 = p1024 ? rb + R_E2 + 2 * (159 - 127) : a;
      sts16(a00, vR >> 16); sts16(a00 + RS_CS + 2, vR >> 16);
      sts16(a - 16, vR); sts16(a - 16 + RS_CS + 2, vR);
      if (p1024) {
        sts32(sb + K1024_OFF + (ch * 2 + br) * 4, __byte_perm(vR, 0, 0x3232));
        const uint32_t kv = pack_bf16(k2048 + __uint_as_float(o2.z), 0.f);
        sts16(rb + R_E3 + 2 * (159 - 127), kv); sts16(rb + R_E3 + 2 * (159 - 127) + RS_CS + 2, kv);
      }
    }
  }
  STAMP(5);
  asm volatile("barrier.cluster.wait.aligned;" ::: "memory");
  bar_sync(7 + (warp >> 1), 64);
  mbar_wait(sb + B_U);
  STAMP(6);

  const uint32_t zz = lds32(cb + R_OFF + br * R_BR);
  conv_dense(sb, cb, zz);
  STAMP(8);
  {
    const int x = (4 + ch) * 128 + wtid, c = x >> 2;
    const uint2 dA = ldg64(p.A_D + bid * 4), dB = ldg64(p.B_D + bid * 4);
    const uint2 gl = gate_ld(x);
    const uint32_t rb = cb + R_OFF + br * R_BR;
    float e48[24], e40[20], e32[16], h32[16], h16[8];
    const int x1 = 159 - (16 * hf + g - 2 * t + 136);
    const uint32_t fs = rb + ((g & 1) ? 2 * x1 : RS_CS + 2 * x1 + 2);
    uint32_t A[2][4][4];
    auto loadA = [&](int buf, uint32_t oe, uint32_t oo, int i0) {
#pragma unroll
      for (int a = 0; a < 2; a++) {
        const uint32_t base = fs + (a ? oo : oe) + i0 * 16;
        uint32_t* k0 = A[buf][2 * a];
        uint32_t* k1 = A[buf][2 * a + 1];
        k0[1] = lds32(base); k0[0] = lds32(base + 16); k0[2] = lds32(base + 32); k1[0] = lds32(base + 48); k1[2] = lds32(base + 64);
        k0[3] = k0[0]; k1[1] = k0[2]; k1[3] = k1[0];
      }
    };
    loadA(0, R_E2, R_O2, 8);
    loadA(1, R_E2, R_O2, 4);
    mbar_wait(sb + B_W);
    const uint64_t d5 = mkdesc(cb + W5_OFF, 144, 576), d3 = mkdesc(cb + W3_OFF, 144, 576);
    const uint64_t d9 = mkdesc(cb + W9_OFF, 144, 576), d7 = mkdesc(cb + W7_OFF, 144, 576);
    const uint32_t y2d = cb + Y2_OFF + br * 3072 + ysw(32 * (5 - (lane >> 4)) + 16 * hf + (lane & 15));
    const uint32_t y3d = cb + Y3_OFF + br * 2048 + ysw(2 * (16 * hf + (lane & 15)) + (lane >> 4));
#define FAR4(N, ACC, BUF, DA, DB, OFF, FIRST)                                                            \
    wg_fence();                                                                                           \
    _Pragma("unroll") for (int k = 0; k < 4; k++) {                                                      \
      const uint32_t* a = A[BUF][k];                                                                      \
      wgmma_rs<N, 1>(ACC, a[0], a[1], a[2], a[3], ((k >> 1) ? DB : DA) + (k & 1) * 18 + (OFF), !(FIRST) || k); \
    }                                                                                                     \
    wg_commit();
    FAR4(48, e48, 0, d5, d3, 0, 1)
    wg_wait0();
    loadA(0, R_E2, R_O2, 0);
    stsm2(y2d - 5 * 512, PK2(e48, 20), PK2(e48, 22));
#pragma unroll
    for (int i = 0; i < 20; i++) e40[i] = FCPY(e48[i]);
    stage_done(sb, 2, lane);
    FAR4(40, e40, 1, d5, d3, 36, 0)
    wg_wait0();
    loadA(1, R_E3, R_O3, 8);
    stsm2(y2d - 4 * 512, PK2(e40, 16), PK2(e40, 18));
#pragma unroll
    for (int i = 0; i < 16; i++) e32[i] = FCPY(e40[i]);
    stage_done(sb, 3, lane);
    FAR4(32, e32, 0, d5, d3, 72, 0)
    FAR4(32, h32, 1, d9, d7, 0, 1)
    wg_wait1();
    loadA(0, R_E3, R_O3, 4);
    stsm4(y2d, PK2(e32, 0), PK2(e32, 2), PK2(e32, 4), PK2(e32, 6));
    stsm4(y2d - 2 * 512, PK2(e32, 8), PK2(e32, 10), PK2(e32, 12), PK2(e32, 14));
    stage_done(sb, 4, lane);
    STAMP(9);
    wg_wait0();
    stsm4(y3d, PK2(h32, 8), PK2(h32, 10), PK2(h32, 12), PK2(h32, 14));
#pragma unroll
    for (int i = 0; i < 8; i++) h16[i] = FCPY(h32[i]);
    stage_done(sb, 5, lane);
    FAR4(16, h16, 0, d9, d7, 72, 0)
#undef FAR4
    const uint32_t yo = sb + CH_OFF + (x & 3) * 4 + ysw(c);
    uint32_t ua[4], ub[4], ya[4], yb[4], a2[4], b2[4], a3[4], b3[4], s2[4];
    skip_terms(ua, ub, sb, x, dA, dB);
    ld4ch(s2, sb + CH_OFF + (x & 3) * 4 + S2_OFF + ((c - 128) + ((c - 128) >> 3)) * 16);
    const uint32_t tag = lds32(sb + TAG_OFF);
    wg_wait0();
    stsm4(y3d + 1024, PK2(h16, 0), PK2(h16, 2), PK2(h16, 4), PK2(h16, 6));
    stage_done(sb, 6, lane);
    STAMP(10);
    const uint32_t g2 = gate_fin(p, gl, x, tag);
    mbar_wait(sb + B_ST + 8 * 4);
    const uint4 k0 = lds128(sb + K1024_OFF), k1 = lds128(sb + K1024_OFF + 16);
    const uint32_t kk[8] = {k0.x, k0.y, k0.z, k0.w, k1.x, k1.y, k1.z, k1.w};
    ld4ch(ya, yo + Y0_OFF); ld4ch(yb, yo + Y0_OFF + 4096);
    ld4ch(a2, yo + Y2_OFF - 1024); ld4ch(b2, yo + Y2_OFF - 1024 + 3072);
    mbar_wait(sb + B_ST + 8 * (5 + (ch >> 1)));
    STAMP(12);
    ld4ch(a3, yo + Y3_OFF - 2048); ld4ch(b3, yo + Y3_OFF - 2048 + 2048);
#pragma unroll
    for (int k = 0; k < 4; k++) {
      ya[k] = hadd2(ya[k], hadd2(hfma2(kk[2 * k], s2[k], a2[k]), a3[k]));
      yb[k] = hadd2(yb[k], hadd2(hfma2(kk[2 * k + 1], s2[k], b2[k]), b3[k]));
    }
    const uint4 r = mix(ya, yb, ua, ub, g2);
    if ((uint32_t)(ch & 1) != rank) send_box(sb, 2 + (ch >> 1), wtid, rank, r);
    else merge_box(sb, &tm_out, 2 + (ch >> 1), wtid, rank, oc0, r, 1 + ch);
  }
  STAMP(14);
  if (wtid == 0) asm volatile("cp.async.bulk.wait_group.read 0;" ::: "memory");
  STAMP(15); GT(1);
}

typedef CUresult (*EncodeFn)(CUtensorMap*, CUtensorMapDataType, cuuint32_t, void*, const cuuint64_t*, const cuuint64_t*,
                             const cuuint32_t*, const cuuint32_t*, CUtensorMapInterleave, CUtensorMapSwizzle,
                             CUtensorMapL2promotion, CUtensorMapFloatOOBfill);

}

extern "C" void kernel_launch(void* const* d_in, const int* in_sizes, int n_in, void* d_out, int out_size) {
  (void)in_sizes; (void)n_in; (void)out_size;
  typedef const __nv_bfloat16* bp;
  Params p;
  p.t[0] = (bp)d_in[10]; p.t[1] = (bp)d_in[11]; p.t[2] = (bp)d_in[12]; p.t[3] = (bp)d_in[13]; p.t[4] = (bp)d_in[14]; p.t[5] = nullptr;
  p.t[6] = (bp)d_in[1]; p.t[7] = (bp)d_in[2]; p.t[8] = (bp)d_in[5]; p.t[9] = (bp)d_in[6]; p.t[10] = (bp)d_in[7];
  p.t[11] = (bp)d_in[3]; p.t[12] = (bp)d_in[4]; p.t[13] = nullptr;
  p.u = (bp)d_in[0]; p.gw = (bp)d_in[16]; p.A_D = (bp)d_in[8]; p.B_D = (bp)d_in[15];
  static EncodeFn enc = nullptr;
  if (!enc) {
    cudaDriverEntryPointQueryResult qr;
    cudaGetDriverEntryPoint("cuTensorMapEncodeTiled", (void**)&enc, cudaEnableDefault, &qr);
    cudaFuncSetAttribute(ssm_kernel, cudaFuncAttributeMaxDynamicSharedMemorySize, SMEM_BYTES);
  }
  CUtensorMap tm_in, tm_out;
  {
    cuuint64_t gd[5] = {512, 2, 4, 4, 64};
    cuuint64_t gs[4] = {1024, 8192, 2048, 32768};
    cuuint32_t bx[5] = {8, 2, 4, 4, 32};
    cuuint32_t es[5] = {1, 1, 1, 1, 1};
    enc(&tm_in, CU_TENSOR_MAP_DATA_TYPE_BFLOAT16, 5, d_in[0], gd, gs, bx, es, CU_TENSOR_MAP_INTERLEAVE_NONE,
        CU_TENSOR_MAP_SWIZZLE_NONE, CU_TENSOR_MAP_L2_PROMOTION_NONE, CU_TENSOR_MAP_FLOAT_OOB_FILL_NONE);
  }
  {
    cuuint64_t gd[3] = {512, 1024, 2};
    cuuint64_t gs[2] = {2048, 1024};
    cuuint32_t bx[3] = {8, 128, 2};
    cuuint32_t es[3] = {1, 1, 1};
    enc(&tm_out, CU_TENSOR_MAP_DATA_TYPE_BFLOAT16, 3, d_out, gd, gs, bx, es, CU_TENSOR_MAP_INTERLEAVE_NONE,
        CU_TENSOR_MAP_SWIZZLE_NONE, CU_TENSOR_MAP_L2_PROMOTION_NONE, CU_TENSOR_MAP_FLOAT_OOB_FILL_NONE);
  }
  ssm_kernel<<<NCTA + NGATE, 640, SMEM_BYTES, cudaStreamPerThread>>>(p, tm_in, tm_out);
}
```

```cpp
#include <cuda_runtime.h>
#include <cuda.h>
#include <cuda_bf16.h>
#include <stdint.h>

namespace {
#define FCPY(x) __uint_as_float(opq(__float_as_uint(x), zz))

constexpr int L = 2048, D = 512, NM = 128;
constexpr int NCTA = 128;
constexpr int NGATE = 4;

constexpr int RAW_OFF = 0;
constexpr int XIN_OFF = 32768;
constexpr int BAR_OFF = XIN_OFF + 10240;
constexpr int CH_OFF = BAR_OFF + 256;
constexpr int U_CS = 1184;
constexpr int U_OFF = 0;
constexpr int R_OFF = 4736;
constexpr int RD_X0 = 565;
constexpr int RD_CS = 1216;
constexpr int RS_CS = 320;
constexpr int R_E2 = 2 * RD_CS, R_O2 = R_E2 + 2 * RS_CS, R_E3 = R_O2 + 2 * RS_CS, R_O3 = R_E3 + 2 * RS_CS;
constexpr int R_BR = R_O3 + 2 * RS_CS;
constexpr int W5_OFF = R_OFF + 2 * R_BR;
constexpr int W3_OFF = W5_OFF + 3456;
constexpr int W9_OFF = W3_OFF + 3456;
constexpr int W7_OFF = W9_OFF + 2304;
constexpr int S2_OFF = W7_OFF + 2304;
constexpr int Y0_OFF = S2_OFF + 2304;
constexpr int Y2_OFF = Y0_OFF + 8192, Y3_OFF = Y2_OFF + 6144;
constexpr int CH_BYTES = Y0_OFF + 18432 + 16;
constexpr int SCR_BYTES = 4608;
constexpr int SMEM_BYTES = CH_OFF + 4 * CH_BYTES;
static_assert(CH_BYTES % 128 == 16, "bank staggering of the channel blocks");
static_assert(SMEM_BYTES <= 232448, "smem");
constexpr int B_RAW = BAR_OFF, B_X = BAR_OFF + 8, B_U = BAR_OFF + 40, B_W = BAR_OFF + 48;
constexpr int TAG_OFF = BAR_OFF + 56;
constexpr int K1024_OFF = BAR_OFF + 64;
constexpr int B_ST = BAR_OFF + 96;

__device__ unsigned int g_gate[L];
__device__ unsigned int g_epoch;
__device__ unsigned int g_ticket;

#define STAMP(k)
#define GT(k)

struct Params {
  const __nv_bfloat16* t[14];
  const __nv_bfloat16 *u, *gw, *A_D, *B_D;
};

template <int N, int TB> __device__ __forceinline__ void wgmma_rs(float* d, uint32_t a0, uint32_t a1, uint32_t a2, uint32_t a3, uint64_t desc, int sc);
template <> __device__ __forceinline__ void wgmma_rs<64, 0>(float* d, uint32_t a0, uint32_t a1, uint32_t a2, uint32_t a3, uint64_t desc, int sc) {
  asm volatile("{\n.reg .pred p;\nsetp.ne.b32 p, %37, 0;\n"
    "wgmma.mma_async.sync.aligned.m64n64k16.f32.bf16.bf16 {%0,%1,%2,%3,%4,%5,%6,%7,%8,%9,%10,%11,%12,%13,%14,%15,%16,%17,%18,%19,%20,%21,%22,%23,%24,%25,%26,%27,%28,%29,%30,%31}, {%32,%33,%34,%35}, %36, p, 1, 1, 0;\n}"
    : "+f"(d[0]), "+f"(d[1]), "+f"(d[2]), "+f"(d[3]), "+f"(d[4]), "+f"(d[5]), "+f"(d[6]), "+f"(d[7]), "+f"(d[8]), "+f"(d[9]), "+f"(d[10]), "+f"(d[11]), "+f"(d[12]), "+f"(d[13]), "+f"(d[14]), "+f"(d[15]), "+f"(d[16]), "+f"(d[17]), "+f"(d[18]), "+f"(d[19]), "+f"(d[20]), "+f"(d[21]), "+f"(d[22]), "+f"(d[23]), "+f"(d[24]), "+f"(d[25]), "+f"(d[26]), "+f"(d[27]), "+f"(d[28]), "+f"(d[29]), "+f"(d[30]), "+f"(d[31]) : "r"(a0), "r"(a1), "r"(a2), "r"(a3), "l"(desc), "r"(sc));
}
template <> __device__ __forceinline__ void wgmma_rs<56, 0>(float* d, uint32_t a0, uint32_t a1, uint32_t a2, uint32_t a3, uint64_t desc, int sc) {
  asm volatile("{\n.reg .pred p;\nsetp.ne.b32 p, %33, 0;\n"
    "wgmma.mma_async.sync.aligned.m64n56k16.f32.bf16.bf16 {%0,%1,%2,%3,%4,%5,%6,%7,%8,%9,%10,%11,%12,%13,%14,%15,%16,%17,%18,%19,%20,%21,%22,%23,%24,%25,%26,%27}, {%28,%29,%30,%31}, %32, p, 1, 1, 0;\n}"
    : "+f"(d[0]), "+f"(d[1]), "+f"(d[2]), "+f"(d[3]), "+f"(d[4]), "+f"(d[5]), "+f"(d[6]), "+f"(d[7]), "+f"(d[8]), "+f"(d[9]), "+f"(d[10]), "+f"(d[11]), "+f"(d[12]), "+f"(d[13]), "+f"(d[14]), "+f"(d[15]), "+f"(d[16]), "+f"(d[17]), "+f"(d[18]), "+f"(d[19]), "+f"(d[20]), "+f"(d[21]), "+f"(d[22]), "+f"(d[23]), "+f"(d[24]), "+f"(d[25]), "+f"(d[26]), "+f"(d[27]) : "r"(a0), "r"(a1), "r"(a2), "r"(a3), "l"(desc), "r"(sc));
}
template <> __device__ __forceinline__ void wgmma_rs<48, 0>(float* d, uint32_t a0, uint32_t a1, uint32_t a2, uint32_t a3, uint64_t desc, int sc) {
  asm volatile("{\n.reg .pred p;\nsetp.ne.b32 p, %29, 0;\n"
    "wgmma.mma_async.sync.aligned.m64n48k16.f32.bf16.bf16 {%0,%1,%2,%3,%4,%5,%6,%7,%8,%9,%10,%11,%12,%13,%14,%15,%16,%17,%18,%19,%20,%21,%22,%23}, {%24,%25,%26,%27}, %28, p, 1, 1, 0;\n}"
    : "+f"(d[0]), "+f"(d[1]), "+f"(d[2]), "+f"(d[3]), "+f"(d[4]), "+f"(d[5]), "+f"(d[6]), "+f"(d[7]), "+f"(d[8]), "+f"(d[9]), "+f"(d[10]), "+f"(d[11]), "+f"(d[12]), "+f"(d[13]), "+f"(d[14]), "+f"(d[15]), "+f"(d[16]), "+f"(d[17]), "+f"(d[18]), "+f"(d[19]), "+f"(d[20]), "+f"(d[21]), "+f"(d[22]), "+f"(d[23]) : "r"(a0), "r"(a1), "r"(a2), "r"(a3), "l"(desc), "r"(sc));
}
template <> __device__ __forceinline__ void wgmma_rs<32, 0>(float* d, uint32_t a0, uint32_t a1, uint32_t a2, uint32_t a3, uint64_t desc, int sc) {
  asm volatile("{\n.reg .pred p;\nsetp.ne.b32 p, %21, 0;\n"
    "wgmma.mma_async.sync.aligned.m64n32k16.f32.bf16.bf16 {%0,%1,%2,%3,%4,%5,%6,%7,%8,%9,%10,%11,%12,%13,%14,%15}, {%16,%17,%18,%19}, %20, p, 1, 1, 0;\n}"
    : "+f"(d[0]), "+f"(d[1]), "+f"(d[2]), "+f"(d[3]), "+f"(d[4]), "+f"(d[5]), "+f"(d[6]), "+f"(d[7]), "+f"(d[8]), "+f"(d[9]), "+f"(d[10]), "+f"(d[11]), "+f"(d[12]), "+f"(d[13]), "+f"(d[14]), "+f"(d[15]) : "r"(a0), "r"(a1), "r"(a2), "r"(a3), "l"(desc), "r"(sc));
}
template <> __device__ __forceinline__ void wgmma_rs<48, 1>(float* d, uint32_t a0, uint32_t a1, uint32_t a2, uint32_t a3, uint64_t desc, int sc) {
  asm volatile("{\n.reg .pred p;\nsetp.ne.b32 p, %29, 0;\n"
    "wgmma.mma_async.sync.aligned.m64n48k16.f32.bf16.bf16 {%0,%1,%2,%3,%4,%5,%6,%7,%8,%9,%10,%11,%12,%13,%14,%15,%16,%17,%18,%19,%20,%21,%22,%23}, {%24,%25,%26,%27}, %28, p, 1, 1, 1;\n}"
    : "+f"(d[0]), "+f"(d[1]), "+f"(d[2]), "+f"(d[3]), "+f"(d[4]), "+f"(d[5]), "+f"(d[6]), "+f"(d[7]), "+f"(d[8]), "+f"(d[9]), "+f"(d[10]), "+f"(d[11]), "+f"(d[12]), "+f"(d[13]), "+f"(d[14]), "+f"(d[15]), "+f"(d[16]), "+f"(d[17]), "+f"(d[18]), "+f"(d[19]), "+f"(d[20]), "+f"(d[21]), "+f"(d[22]), "+f"(d[23]) : "r"(a0), "r"(a1), "r"(a2), "r"(a3), "l"(desc), "r"(sc));
}
template <> __device__ __forceinline__ void wgmma_rs<40, 1>(float* d, uint32_t a0, uint32_t a1, uint32_t a2, uint32_t a3, uint64_t desc, int sc) {
  asm volatile("{\n.reg .pred p;\nsetp.ne.b32 p, %25, 0;\n"
    "wgmma.mma_async.sync.aligned.m64n40k16.f32.bf16.bf16 {%0,%1,%2,%3,%4,%5,%6,%7,%8,%9,%10,%11,%12,%13,%14,%15,%16,%17,%18,%19}, {%20,%21,%22,%23}, %24, p, 1, 1, 1;\n}"
    : "+f"(d[0]), "+f"(d[1]), "+f"(d[2]), "+f"(d[3]), "+f"(d[4]), "+f"(d[5]), "+f"(d[6]), "+f"(d[7]), "+f"(d[8]), "+f"(d[9]), "+f"(d[10]), "+f"(d[11]), "+f"(d[12]), "+f"(d[13]), "+f"(d[14]), "+f"(d[15]), "+f"(d[16]), "+f"(d[17]), "+f"(d[18]), "+f"(d[19]) : "r"(a0), "r"(a1), "r"(a2), "r"(a3), "l"(desc), "r"(sc));
}
template <> __device__ __forceinline__ void wgmma_rs<32, 1>(float* d, uint32_t a0, uint32_t a1, uint32_t a2, uint32_t a3, uint64_t desc, int sc) {
  asm volatile("{\n.reg .pred p;\nsetp.ne.b32 p, %21, 0;\n"
    "wgmma.mma_async.sync.aligned.m64n32k16.f32.bf16.bf16 {%0,%1,%2,%3,%4,%5,%6,%7,%8,%9,%10,%11,%12,%13,%14,%15}, {%16,%17,%18,%19}, %20, p, 1, 1, 1;\n}"
    : "+f"(d[0]), "+f"(d[1]), "+f"(d[2]), "+f"(d[3]), "+f"(d[4]), "+f"(d[5]), "+f"(d[6]), "+f"(d[7]), "+f"(d[8]), "+f"(d[9]), "+f"(d[10]), "+f"(d[11]), "+f"(d[12]), "+f"(d[13]), "+f"(d[14]), "+f"(d[15]) : "r"(a0), "r"(a1), "r"(a2), "r"(a3), "l"(desc), "r"(sc));
}
template <> __device__ __forceinline__ void wgmma_rs<16, 1>(float* d, uint32_t a0, uint32_t a1, uint32_t a2, uint32_t a3, uint64_t desc, int sc) {
  asm volatile("{\n.reg .pred p;\nsetp.ne.b32 p, %13, 0;\n"
    "wgmma.mma_async.sync.aligned.m64n16k16.f32.bf16.bf16 {%0,%1,%2,%3,%4,%5,%6,%7}, {%8,%9,%10,%11}, %12, p, 1, 1, 1;\n}"
    : "+f"(d[0]), "+f"(d[1]), "+f"(d[2]), "+f"(d[3]), "+f"(d[4]), "+f"(d[5]), "+f"(d[6]), "+f"(d[7]) : "r"(a0), "r"(a1), "r"(a2), "r"(a3), "l"(desc), "r"(sc));
}

__device__ __forceinline__ uint32_t pack_bf16(float lo, float hi) {
  uint32_t r; asm("cvt.rn.bf16x2.f32 %0, %1, %2;" : "=r"(r) : "f"(hi), "f"(lo)); return r;
}
__device__ __forceinline__ float bf_lo(uint32_t v) { return __uint_as_float(v << 16); }
__device__ __forceinline__ float bf_hi(uint32_t v) { return __uint_as_float(v & 0xffff0000u); }
__device__ __forceinline__ float bf_round(float x) { return bf_lo(pack_bf16(x, 0.f)); }
__device__ __forceinline__ uint32_t hmul2(uint32_t a, uint32_t b) { uint32_t r; asm("mul.rn.bf16x2 %0, %1, %2;" : "=r"(r) : "r"(a), "r"(b)); return r; }
__device__ __forceinline__ uint32_t hadd2(uint32_t a, uint32_t b) { uint32_t r; asm("add.rn.bf16x2 %0, %1, %2;" : "=r"(r) : "r"(a), "r"(b)); return r; }
__device__ __forceinline__ uint32_t hsub2(uint32_t a, uint32_t b) { uint32_t r; asm("sub.rn.bf16x2 %0, %1, %2;" : "=r"(r) : "r"(a), "r"(b)); return r; }
__device__ __forceinline__ uint32_t hfma2(uint32_t a, uint32_t b, uint32_t c) { uint32_t r; asm("fma.rn.bf16x2 %0, %1, %2, %3;" : "=r"(r) : "r"(a), "r"(b), "r"(c)); return r; }

__device__ __forceinline__ void sts16(uint32_t a, uint32_t v) { asm volatile("st.shared.b16 [%0], %1;" ::"r"(a), "h"((unsigned short)v) : "memory"); }
__device__ __forceinline__ void sts32(uint32_t a, uint32_t v) { asm volatile("st.shared.b32 [%0], %1;" ::"r"(a), "r"(v) : "memory"); }
__device__ __forceinline__ void sts64(uint32_t a, uint32_t x, uint32_t y) { asm volatile("st.shared.v2.b32 [%0], {%1,%2};" ::"r"(a), "r"(x), "r"(y) : "memory"); }
__device__ __forceinline__ void sts128(uint32_t a, uint32_t x, uint32_t y, uint32_t z, uint32_t w) {
  asm volatile("st.shared.v4.b32 [%0], {%1,%2,%3,%4};" ::"r"(a), "r"(x), "r"(y), "r"(z), "r"(w) : "memory");
}
__device__ __forceinline__ uint32_t lds32(uint32_t a) { uint32_t v; asm volatile("ld.shared.b32 %0, [%1];" : "=r"(v) : "r"(a) : "memory"); return v; }
__device__ __forceinline__ uint2 lds64(uint32_t a) { uint2 v; asm volatile("ld.shared.v2.b32 {%0,%1}, [%2];" : "=r"(v.x), "=r"(v.y) : "r"(a) : "memory"); return v; }
__device__ __forceinline__ uint4 lds128(uint32_t a) {
  uint4 v; asm volatile("ld.shared.v4.b32 {%0,%1,%2,%3}, [%4];" : "=r"(v.x), "=r"(v.y), "=r"(v.z), "=r"(v.w) : "r"(a) : "memory"); return v;
}
__device__ __forceinline__ uint4 ldg128(const void* a) {
  uint4 v; asm volatile("ld.global.nc.v4.b32 {%0,%1,%2,%3}, [%4];" : "=r"(v.x), "=r"(v.y), "=r"(v.z), "=r"(v.w) : "l"(a) : "memory"); return v;
}
__device__ __forceinline__ uint2 ldg64(const void* a) {
  uint2 v; asm volatile("ld.global.nc.v2.b32 {%0,%1}, [%2];" : "=r"(v.x), "=r"(v.y) : "l"(a) : "memory"); return v;
}
__device__ __forceinline__ void ldsm4(uint32_t a, uint32_t& r0, uint32_t& r1, uint32_t& r2, uint32_t& r3) {
  asm volatile("ldmatrix.sync.aligned.m8n8.x4.shared.b16 {%0,%1,%2,%3}, [%4];" : "=r"(r0), "=r"(r1), "=r"(r2), "=r"(r3) : "r"(a) : "memory");
}
__device__ __forceinline__ void ldsm4t(uint32_t a, uint32_t& r0, uint32_t& r1, uint32_t& r2, uint32_t& r3) {
  asm volatile("ldmatrix.sync.aligned.m8n8.x4.trans.shared.b16 {%0,%1,%2,%3}, [%4];" : "=r"(r0), "=r"(r1), "=r"(r2), "=r"(r3) : "r"(a) : "memory");
}
__device__ __forceinline__ void stsm4(uint32_t a, uint32_t r0, uint32_t r1, uint32_t r2, uint32_t r3) {
  asm volatile("stmatrix.sync.aligned.m8n8.x4.shared.b16 [%0], {%1,%2,%3,%4};" ::"r"(a), "r"(r0), "r"(r1), "r"(r2), "r"(r3) : "memory");
}
__device__ __forceinline__ void stsm4t(uint32_t a, uint32_t r0, uint32_t r1, uint32_t r2, uint32_t r3) {
  asm volatile("stmatrix.sync.aligned.m8n8.x4.trans.shared.b16 [%0], {%1,%2,%3,%4};" ::"r"(a), "r"(r0), "r"(r1), "r"(r2), "r"(r3) : "memory");
}
__device__ __forceinline__ void stsm2(uint32_t a, uint32_t r0, uint32_t r1) {
  asm volatile("stmatrix.sync.aligned.m8n8.x2.shared.b16 [%0], {%1,%2};" ::"r"(a), "r"(r0), "r"(r1) : "memory");
}
__device__ __forceinline__ void stsm2t(uint32_t a, uint32_t r0, uint32_t r1) {
  asm volatile("stmatrix.sync.aligned.m8n8.x2.trans.shared.b16 [%0], {%1,%2};" ::"r"(a), "r"(r0), "r"(r1) : "memory");
}
__device__ __forceinline__ void mma16816(float* c, uint32_t a0, uint32_t a1, uint32_t a2, uint32_t a3, uint32_t b0, uint32_t b1) {
  asm("mma.sync.aligned.m16n8k16.row.col.f32.bf16.bf16.f32 {%0,%1,%2,%3}, {%4,%5,%6,%7}, {%8,%9}, {%0,%1,%2,%3};"
      : "+f"(c[0]), "+f"(c[1]), "+f"(c[2]), "+f"(c[3]) : "r"(a0), "r"(a1), "r"(a2), "r"(a3), "r"(b0), "r"(b1));
}
__device__ __forceinline__ void bar_sync(int id, int n) { asm volatile("bar.sync %0, %1;" ::"r"(id), "r"(n) : "memory"); }
__device__ __forceinline__ void bar_arrive(int id, int n) { asm volatile("bar.arrive %0, %1;" ::"r"(id), "r"(n) : "memory"); }
__device__ __forceinline__ void wg_fence() { asm volatile("wgmma.fence.sync.aligned;" ::: "memory"); }
__device__ __forceinline__ void wg_commit() { asm volatile("wgmma.commit_group.sync.aligned;" ::: "memory"); }
__device__ __forceinline__ void wg_wait0() { asm volatile("wgmma.wait_group.sync.aligned 0;" ::: "memory"); }
__device__ __forceinline__ void wg_wait1() { asm volatile("wgmma.wait_group.sync.aligned 1;" ::: "memory"); }
__device__ __forceinline__ void fence_async() { asm volatile("fence.proxy.async.shared::cta;" ::: "memory"); }
__device__ __forceinline__ uint32_t opq(uint32_t x, uint32_t z) { uint32_t r; asm volatile("xor.b32 %0, %1, %2;" : "=r"(r) : "r"(x), "r"(z)); return r; }
__device__ __forceinline__ uint64_t mkdesc(uint32_t addr, uint32_t lbo, uint32_t sbo) {
  return (uint64_t)((addr & 0x3FFFF) >> 4) | ((uint64_t)(lbo >> 4) << 16) | ((uint64_t)(sbo >> 4) << 32);
}
__device__ __forceinline__ uint32_t mapa(uint32_t a, uint32_t rank) {
  uint32_t r; asm("mapa.shared::cluster.u32 %0, %1, %2;" : "=r"(r) : "r"(a), "r"(rank)); return r;
}
__device__ __forceinline__ void mbar_init_expect(uint32_t bar, uint32_t bytes) {
  asm volatile("mbarrier.init.shared::cta.b64 [%0], 1;" ::"r"(bar) : "memory");
  asm volatile("mbarrier.arrive.expect_tx.shared::cta.b64 _, [%0], %1;" ::"r"(bar), "r"(bytes) : "memory");
}
__device__ __forceinline__ void mbar_wait(uint32_t bar) {
#pragma unroll 1
  for (int it = 0; it < (1 << 22); it++) {
    uint32_t ok;
    asm volatile("{\n.reg .pred p;\nmbarrier.try_wait.parity.acquire.cluster.shared::cta.b64 p, [%1], 0;\nselp.u32 %0, 1, 0, p;\n}"
                 : "=r"(ok) : "r"(bar) : "memory");
    if (ok) return;
  }
  __trap();
}
__device__ __forceinline__ void st_async4(uint32_t a, uint32_t bar, uint32_t x, uint32_t y, uint32_t z, uint32_t w) {
  asm volatile("st.async.weak.shared::cluster.mbarrier::complete_tx::bytes.v4.b32 [%0], {%2,%3,%4,%5}, [%1];"
               ::"r"(a), "r"(bar), "r"(x), "r"(y), "r"(z), "r"(w) : "memory");
}

struct cf { float re, im; };
__device__ __forceinline__ cf cmul(cf a, cf b) { return {fmaf(a.re, b.re, -a.im * b.im), fmaf(a.re, b.im, a.im * b.re)}; }
__device__ __forceinline__ cf csq(cf a) { return {fmaf(a.re, a.re, -a.im * a.im), (a.re + a.re) * a.im}; }
__device__ __forceinline__ cf cexp_p(float xl, float y, float p) {
  float mag; asm("ex2.approx.ftz.f32 %0, %1;" : "=f"(mag) : "f"(xl * p));
  const float th = y * p;
  const float k = rintf(th * 0.15915494309189535f);
  float r = fmaf(k, -6.2831854820251465f, th);
  r = fmaf(k, 1.7484555314695172e-07f, r);
  return {mag * __cosf(r), mag * __sinf(r)};
}
__device__ __forceinline__ uint32_t ysw(int c) { return (uint32_t)(c ^ ((c >> 3) & 3)) * 16u; }

#define CMUL2(OR, OI, xr, xi, yr, yi, nyi) do { OR = hfma2(xr, yr, hmul2(xi, nyi)); OI = hfma2(xr, yi, hmul2(xi, yr)); } while (0)

__device__ __forceinline__ uint32_t gate_slow(const __nv_bfloat16* u, const __nv_bfloat16* gw, int row) {
  float s = 0.f;
  const uint32_t* xr = (const uint32_t*)(u + (size_t)row * D);
  const uint32_t* wr = (const uint32_t*)gw;
#pragma unroll 1
  for (int j = 0; j < D / 2; j++) { const uint32_t pr = hmul2(xr[j], wr[j]); s += bf_lo(pr); s += bf_hi(pr); }
  s = bf_round(s);
  return pack_bf16(1.f / (1.f + expf(-s)), 0.f);
}

__device__ __forceinline__ uint2 gate_ld(int x) {
  uint2 gv;
  asm volatile("ld.relaxed.gpu.global.v2.u32 {%0,%1}, [%2];" : "=r"(gv.x), "=r"(gv.y) : "l"(g_gate + x * 2) : "memory");
  return gv;
}
__device__ __noinline__ uint32_t gate_poll(const Params* pp, int x, uint32_t tag) {
  uint2 gv;
#pragma unroll 1
  for (int spins = 0; spins < (1 << 16); spins++) {
    gv = gate_ld(x);
    if ((gv.x >> 16) == tag && (gv.y >> 16) == tag) return __byte_perm(gv.x, gv.y, 0x5410);
  }
  return __byte_perm(gate_slow(pp->u, pp->gw, x * 2), gate_slow(pp->u, pp->gw, x * 2 + 1), 0x5410);
}
__device__ __forceinline__ uint32_t gate_fin(const Params& p, uint2 gv, int x, uint32_t tag) {
  if ((gv.x >> 16) == tag && (gv.y >> 16) == tag) return __byte_perm(gv.x, gv.y, 0x5410);
  return gate_poll(&p, x, tag);
}

__device__ __forceinline__ void ld4ch(uint32_t* v, uint32_t addr) {
#pragma unroll
  for (int k = 0; k < 4; k++) v[k] = lds32(addr + k * CH_BYTES);
}
__device__ __forceinline__ void skip_terms(uint32_t* ua, uint32_t* ub, uint32_t sb, int x, uint2 dA, uint2 dB) {
  const int c = x >> 2;
  uint32_t uu[4];
  ld4ch(uu, sb + CH_OFF + (x & 3) * 4 + U_OFF + (c & 3) * U_CS + (63 - (c >> 2)) * 16);
#pragma unroll
  for (int k = 0; k < 4; k++) {
    ua[k] = hmul2(uu[k], __byte_perm((k & 2) ? dA.y : dA.x, 0, (k & 1) ? 0x3232 : 0x1010));
    ub[k] = hmul2(uu[k], __byte_perm((k & 2) ? dB.y : dB.x, 0, (k & 1) ? 0x3232 : 0x1010));
  }
}
__device__ __forceinline__ uint4 mix(const uint32_t* a, const uint32_t* b, const uint32_t* ua, const uint32_t* ub, uint32_t g2) {
  const uint32_t h2 = hsub2(0x3f803f80u, g2);
  uint32_t o[4];
#pragma unroll
  for (int k = 0; k < 4; k++) o[k] = hadd2(hmul2(g2, hadd2(a[k], ua[k])), hmul2(h2, hadd2(b[k], ub[k])));
  return make_uint4(__byte_perm(o[0], o[1], 0x5410), __byte_perm(o[2], o[3], 0x5410), __byte_perm(o[0], o[1], 0x7632), __byte_perm(o[2], o[3], 0x7632));
}
__device__ __forceinline__ void send_box(uint32_t sb, int slot, int wtid, uint32_t rank, uint4 r) {
  st_async4(mapa(sb + XIN_OFF + slot * 2048 + wtid * 16, rank ^ 1), mapa(sb + B_X + slot * 8, rank ^ 1), r.x, r.y, r.z, r.w);
}
__device__ __forceinline__ void merge_box(uint32_t sb, const CUtensorMap* tm_out, int slot, int wtid, uint32_t rank, int oc0, uint4 r, int barid) {
  const uint32_t st = sb + RAW_OFF + slot * 4096 + wtid * 16;
  sts64(st + rank * 8, r.x, r.y); sts64(st + 2048 + rank * 8, r.z, r.w);
  mbar_wait(sb + B_X + slot * 8);
  const uint4 q = lds128(sb + XIN_OFF + slot * 2048 + wtid * 16);
  sts64(st + (rank ^ 1) * 8, q.x, q.y); sts64(st + 2048 + (rank ^ 1) * 8, q.z, q.w);
  fence_async();
  bar_sync(barid, 128);
  if (wtid == 0) {
    asm volatile("cp.async.bulk.tensor.3d.global.shared::cta.bulk_group [%0, {%2, %3, %4}], [%1];"
                 ::"l"(tm_out), "r"(sb + RAW_OFF + slot * 4096), "r"(oc0), "r"((2 * slot + (int)rank) * 128), "r"(0) : "memory");
    asm volatile("cp.async.bulk.commit_group;" ::: "memory");
  }
}

__device__ __forceinline__ uint32_t band2(int e, int lo, int hi) {
  uint32_t r = ((uint32_t)(e - lo) <= (uint32_t)(hi - lo) ? 0x3f80u : 0u) | ((uint32_t)(e - 1 - lo) <= (uint32_t)(hi - lo) ? 0x3f800000u : 0u);
  asm volatile("" : "+r"(r));
  return r;
}

__device__ __forceinline__ void stage_done(uint32_t sb, int stage, int lane) {
  __syncwarp();
  if (lane == 0) asm volatile("mbarrier.arrive.shared::cta.b64 _, [%0];" ::"r"(sb + B_ST + 8 * stage) : "memory");
}
#define PK2(v, i) pack_bf16(v[i], v[(i) + 1])

__device__ __forceinline__ void conv_dense(uint32_t sb, uint32_t cb, uint32_t zz) {
  const int lane = threadIdx.x & 31, wq = (threadIdx.x >> 5) & 3, br = wq >> 1, hf = wq & 1, g = lane >> 2, t = lane & 3;
  const uint32_t rb = cb + R_OFF + br * R_BR;
  const int eo = 16 * hf + g - 2 * t;
  const int x0 = RD_X0 - (eo + 536);
  const uint32_t fa = rb + ((g & 1) ? 2 * x0 : RD_CS + 2 * x0 + 2);
  const uint64_t ub = mkdesc(cb + U_OFF, U_CS, 128);
  const uint32_t yd = cb + Y0_OFF + br * 4096 + ysw(4 * (63 - 8 * (lane >> 4) - (lane & 7)) + 2 * hf + ((lane >> 3) & 1));
  uint32_t A[2][4][4];
  float e64[32], e56[28], e48[24];
  auto loadA = [&](int j) {
#pragma unroll
    for (int k = 0; k < 4; k++) {
      const int s = 34 - 4 * j - k;
      if (s >= 0) {
        if (k == 0 && j == 0) A[0][0][2] = lds32(fa + (2 * s + 2) * 16);
        A[j & 1][k][0] = lds32(fa + (2 * s + 1) * 16);
        A[j & 1][k][1] = lds32(fa + (2 * s) * 16);
      }
    }
#pragma unroll
    for (int k = 0; k < 4; k++) {
      if (34 - 4 * j - k >= 0) {
        A[j & 1][k][3] = A[j & 1][k][0];
        if (k) A[j & 1][k][2] = A[j & 1][k - 1][1];
        else if (j) A[j & 1][0][2] = A[(j - 1) & 1][3][1];
      }
    }
  };
  loadA(0); loadA(1);
#pragma unroll
  for (int j = 0; j < 9; j++) {
    if (j == 4) {
      wg_wait0();
      stsm2t(yd - 7 * 512, PK2(e64, 28), PK2(e64, 30));
#pragma unroll
      for (int i = 0; i < 28; i++) e56[i] = FCPY(e64[i]);
      stage_done(sb, 0, lane);
    }
    if (j == 8) {
      wg_wait0();
      stsm2t(yd - 6 * 512, PK2(e56, 24), PK2(e56, 26));
#pragma unroll
      for (int i = 0; i < 24; i++) e48[i] = FCPY(e56[i]);
      stage_done(sb, 1, lane);
    }
    wg_fence();
#pragma unroll
    for (int k = 0; k < 4; k++) {
      const int s = 34 - 4 * j - k;
      if (s >= 0) {
        const int o = 2 * s - 66 + 128;
        const int cc = o & 3, rs = (o >> 2) - 32;
        const uint64_t desc = ub + (uint64_t)((cc * U_CS - rs * 16) >> 4);
        const uint32_t* a = A[j & 1][k];
        if (j < 4) wgmma_rs<64, 0>(e64, a[0], a[1], a[2], a[3], desc, s != 34);
        else if (j < 8) wgmma_rs<56, 0>(e56, a[0], a[1], a[2], a[3], desc, 1);
        else wgmma_rs<48, 0>(e48, a[0], a[1], a[2], a[3], desc, 1);
      }
    }
    wg_commit();
    if (j >= 1 && j < 8) { wg_wait1(); loadA(j + 1); }
  }
  wg_wait0();
#pragma unroll
  for (int i = 0; i < 6; i += 2) stsm4t(yd - i * 512, PK2(e48, 4 * i), PK2(e48, 4 * i + 2), PK2(e48, 4 * i + 4), PK2(e48, 4 * i + 6));
}

__device__ __noinline__ void gate_cta(const Params* pp) {
  const __nv_bfloat16 *u = pp->u, *gw = pp->gw;
  const int lane = threadIdx.x & 31;
  unsigned int epoch;
  asm volatile("ld.relaxed.gpu.global.u32 %0, [%1];" : "=r"(epoch) : "l"(&g_epoch) : "memory");
  const uint4 gw0 = ldg128(gw + lane * 8), gw1 = ldg128(gw + 256 + lane * 8);
  const uint32_t ws[8] = {gw0.x, gw0.y, gw0.z, gw0.w, gw1.x, gw1.y, gw1.z, gw1.w};
  const uint32_t tag = (epoch + 1) & 0xffffu;
  uint4 gx[4][2], nx[4][2];
  int grow = (blockIdx.x * 20 + (threadIdx.x >> 5)) * 4;
#pragma unroll
  for (int i = 0; i < 4; i++) {
    nx[i][0] = ldg128(u + (size_t)(grow + i) * D + lane * 8);
    nx[i][1] = ldg128(u + (size_t)(grow + i) * D + 256 + lane * 8);
  }
#pragma unroll 1
  for (; grow < L; grow += 80 * NGATE) {
    const int nrow = min(grow + 80 * NGATE, L - 4);
#pragma unroll
    for (int i = 0; i < 4; i++) {
      gx[i][0] = nx[i][0]; gx[i][1] = nx[i][1];
      nx[i][0] = ldg128(u + (size_t)(nrow + i) * D + lane * 8);
      nx[i][1] = ldg128(u + (size_t)(nrow + i) * D + 256 + lane * 8);
    }
    float c[2][4];
#pragma unroll
    for (int i = 0; i < 2; i++) {
      const uint4 *x = gx[2 * i], *y = gx[2 * i + 1];
      const uint32_t xs[8] = {x[0].x, x[0].y, x[0].z, x[0].w, x[1].x, x[1].y, x[1].z, x[1].w};
      const uint32_t ys[8] = {y[0].x, y[0].y, y[0].z, y[0].w, y[1].x, y[1].y, y[1].z, y[1].w};
      c[i][0] = c[i][1] = c[i][2] = c[i][3] = 0.f;
#pragma unroll
      for (int j = 0; j < 8; j += 2)
        mma16816(c[i], hmul2(xs[j], ws[j]), hmul2(ys[j], ws[j]), hmul2(xs[j + 1], ws[j + 1]), hmul2(ys[j + 1], ws[j + 1]), 0x3f803f80u, 0x3f803f80u);
    }
    float s = (lane & 2) ? ((lane & 1) ? c[1][2] : c[1][0]) : ((lane & 1) ? c[0][2] : c[0][0]);
#pragma unroll
    for (int o = 4; o < 32; o <<= 1) s += __shfl_xor_sync(0xffffffffu, s, o);
    s = bf_round(s);
    const float gv = 1.f / (1.f + expf(-s));
    const uint32_t w = (tag << 16) | (pack_bf16(gv, 0.f) & 0xffffu);
    if (lane < 4) asm volatile("st.relaxed.gpu.global.u32 [%0], %1;" ::"l"(&g_gate[grow + lane]), "r"(w) : "memory");
  }
  __syncthreads();
  if (threadIdx.x == 0 && atomicAdd(&g_ticket, 1u) == NCTA + NGATE - 1) { g_ticket = 0; g_epoch = epoch + 1; }
}

__global__ void __cluster_dims__(2, 1, 1) __launch_bounds__(640, 1)
ssm_kernel(const __grid_constant__ Params p, const __grid_constant__ CUtensorMap tm_in, const __grid_constant__ CUtensorMap tm_out) {
  extern __shared__ __align__(1024) unsigned char smem_raw[];
  const uint32_t sb = (uint32_t)__cvta_generic_to_shared(smem_raw);
  const int tid = threadIdx.x, lane = tid & 31;
  const int warp = __shfl_sync(0xffffffffu, tid >> 5, 0);
  const int ch = warp >> 2, wq = warp & 3, br = wq >> 1, hf = wq & 1;
  const int g = lane >> 2, t = lane & 3;
  if (__builtin_expect(blockIdx.x < NGATE, 0)) { gate_cta(&p); return; }
  const int bid = blockIdx.x - NGATE;
  const int d = bid * 4 + ch;
  const uint32_t rank = blockIdx.x & 1;
  const uint32_t cb = sb + CH_OFF + ch * CH_BYTES;
  const int wtid = tid & 127;
  const int oc0 = (bid >> 1) * 8;
  STAMP(0); GT(0);

  if (warp >= 16) {
    if (wtid == 0) {
      mbar_init_expect(sb + B_RAW, 32768);
#pragma unroll
      for (int i = 0; i < 4; i++) mbar_init_expect(sb + B_X + 8 * i, 2048);
      asm volatile("mbarrier.init.shared::cta.b64 [%0], 128;" ::"r"(sb + B_U) : "memory");
      asm volatile("mbarrier.init.shared::cta.b64 [%0], 128;" ::"r"(sb + B_W) : "memory");
#pragma unroll
      for (int i = 0; i < 7; i++) asm volatile("mbarrier.init.shared::cta.b64 [%0], 16;" ::"r"(sb + B_ST + 8 * i) : "memory");
      asm volatile("fence.mbarrier_init.release.cluster;" ::: "memory");
      asm volatile("fence.proxy.async.shared::cta;" ::: "memory");
    }
    __syncwarp();
    asm volatile("barrier.cluster.arrive.relaxed.aligned;" ::: "memory");
    unsigned int epoch;
    asm volatile("ld.relaxed.gpu.global.u32 %0, [%1];" : "=r"(epoch) : "l"(&g_epoch) : "memory");
    asm volatile("barrier.cluster.wait.aligned;" ::: "memory");
    if (wtid == 0) {
      asm volatile("cp.async.bulk.tensor.5d.shared::cluster.global.mbarrier::complete_tx::bytes.multicast::cluster [%0], [%1, {%3, %4, %4, %4, %5}], [%2], %6;"
                   ::"r"(sb + RAW_OFF + rank * 16384), "l"(&tm_in), "r"(sb + B_RAW), "r"(oc0), "r"(0), "r"((int)rank * 32), "h"((unsigned short)3) : "memory");
    }
    sts128(sb + CH_OFF + wq * CH_BYTES + U_OFF + (lane >> 3) * U_CS + (64 + (lane & 7)) * 16, 0, 0, 0, 0);
    const uint2 dA = ldg64(p.A_D + bid * 4), dB = ldg64(p.B_D + bid * 4);
    uint32_t BA[3][4], BC[3][4];
    {
      const int l1 = br ? 3 : 6, h1 = br ? 5 : 10;
#pragma unroll
      for (int i = 0; i < 3; i++) {
        const int e = 16 * hf + g - 2 * t + 16 - 16 * i;
        BA[i][0] = band2(e, l1, h1); BA[i][1] = band2(e + 8, l1, h1); BA[i][2] = band2(e - 8, l1, h1); BA[i][3] = BA[i][0];
        BC[i][0] = band2(e, 3, 4); BC[i][1] = band2(e + 8, 3, 4); BC[i][2] = band2(e - 8, 3, 4); BC[i][3] = BC[i][0];
      }
    }
    const uint32_t tag = (epoch + 1) & 0xffffu;
    if (wtid == 0) sts32(sb + TAG_OFF, tag);
    STAMP(3);
    mbar_wait(sb + B_RAW);
    STAMP(4);
    {
      const uint32_t dst = sb + CH_OFF + (g & 3) * CH_BYTES + U_OFF + t * U_CS + (63 - wq * 16) * 16;
#pragma unroll
      for (int h = 0; h < 2; h++) {
        uint32_t r[8][4];
#pragma unroll
        for (int i = 0; i < 8; i++) ldsm4t(sb + RAW_OFF + (wq * 16 + h * 8 + i) * 512 + lane * 16, r[i][0], r[i][1], r[i][2], r[i][3]);
        if ((uint32_t)(g >> 2) == rank) {
#pragma unroll
          for (int i = 0; i < 8; i++) sts128(dst - (h * 8 + i) * 16, r[i][0], r[i][1], r[i][2], r[i][3]);
        }
      }
    }
    fence_async();
    asm volatile("mbarrier.arrive.shared::cta.b64 _, [%0];" ::"r"(sb + B_U) : "memory");
    bar_sync(5, 128);
    STAMP(5);
    {
      const int mrow = lane & 7, mi = lane >> 3;
      const uint64_t ub0 = mkdesc(sb + CH_OFF + U_OFF, U_CS, 128);
      {
        float w1[24], w3[16];
#pragma unroll
        for (int i = 0; i < 24; i++) w1[i] = 0.f;
#pragma unroll
        for (int i = 0; i < 16; i++) w3[i] = 0.f;
        uint32_t wa[3], sa[2];
#pragma unroll
        for (int i = 0; i < 3; i++) {
          const int c = 4 * (47 - 8 * (2 * i + (mi >> 1)) - mrow) + 2 * hf + (mi & 1);
          wa[i] = sb + CH_OFF + (br ? W3_OFF : W5_OFF) + (5 - (c >> 5)) * 576 + ((c & 31) >> 3) * 144 + (c & 7) * 16;
          if (i) sa[i - 1] = sb + CH_OFF + S2_OFF + (c + (c >> 3)) * 16;
        }
#pragma unroll 1
        for (int k = 0; k < 4; k++) {
          wg_fence();
#pragma unroll
          for (int i = 0; i < 3; i++)
            wgmma_rs<48, 0>(w1, BA[i][0], BA[i][1], BA[i][2], BA[i][3],
                            ub0 + (uint64_t)((k * CH_BYTES + ((2 * i + 2) & 3) * U_CS + (16 + (i == 0)) * 16) >> 4), i);
#pragma unroll
          for (int i = 0; i < 3; i++)
            wgmma_rs<32, 0>(w3, BC[i][0], BC[i][1], BC[i][2], BC[i][3],
                            ub0 + (uint64_t)((k * CH_BYTES + ((2 * i + 2) & 3) * U_CS + (32 + (i == 0)) * 16) >> 4), i);
          wg_commit();
          wg_wait0();
#pragma unroll
          for (int i = 0; i < 3; i++)
            stsm4t(wa[i] + k * CH_BYTES, pack_bf16(w1[8 * i], w1[8 * i + 1]), pack_bf16(w1[8 * i + 2], w1[8 * i + 3]),
                   pack_bf16(w1[8 * i + 4], w1[8 * i + 5]), pack_bf16(w1[8 * i + 6], w1[8 * i + 7]));
          if (br == 0) {
#pragma unroll
            for (int i = 0; i < 2; i++)
              stsm4t(sa[i] + k * CH_BYTES, pack_bf16(w3[8 * i], w3[8 * i + 1]), pack_bf16(w3[8 * i + 2], w3[8 * i + 3]),
                     pack_bf16(w3[8 * i + 4], w3[8 * i + 5]), pack_bf16(w3[8 * i + 6], w3[8 * i + 7]));
          }
        }
      }
      {
        uint32_t BB[4][4];
        const int l2 = br ? 5 : 12, h2 = br ? 11 : 20;
#pragma unroll
        for (int i = 0; i < 4; i++) {
          const int e = 16 * hf + g - 2 * t + 32 - 16 * i;
          BB[i][0] = band2(e, l2, h2); BB[i][1] = band2(e + 8, l2, h2); BB[i][2] = band2(e - 8, l2, h2); BB[i][3] = BB[i][0];
        }
        float w2[2][16];
#pragma unroll
        for (int i = 0; i < 16; i++) { w2[0][i] = 0.f; w2[1][i] = 0.f; }
        uint32_t wa[2];
#pragma unroll
        for (int i = 0; i < 2; i++) {
          const int c = 4 * (31 - 8 * (2 * i + (mi >> 1)) - mrow) + 2 * hf + (mi & 1), pp = c >> 1;
          wa[i] = sb + CH_OFF + (br ? W7_OFF : W9_OFF) + (1 - (pp >> 5)) * 1152 + (c & 1) * 576 + ((pp & 31) >> 3) * 144 + (pp & 7) * 16;
        }
#pragma unroll 1
        for (int kp = 0; kp < 2; kp++) {
          wg_fence();
#pragma unroll
          for (int k = 0; k < 2; k++)
#pragma unroll
            for (int i = 0; i < 4; i++)
              wgmma_rs<32, 0>(w2[k], BB[i][0], BB[i][1], BB[i][2], BB[i][3],
                              ub0 + (uint64_t)(((2 * kp + k) * CH_BYTES + ((2 * i) & 3) * U_CS + (32 + (i < 2)) * 16) >> 4), i);
          wg_commit();
          wg_wait0();
#pragma unroll
          for (int k = 0; k < 2; k++)
#pragma unroll
            for (int i = 0; i < 2; i++)
              stsm4t(wa[i] + (2 * kp + k) * CH_BYTES, pack_bf16(w2[k][8 * i], w2[k][8 * i + 1]), pack_bf16(w2[k][8 * i + 2], w2[k][8 * i + 3]),
                     pack_bf16(w2[k][8 * i + 4], w2[k][8 * i + 5]), pack_bf16(w2[k][8 * i + 6], w2[k][8 * i + 7]));
        }
      }
    }
    fence_async();
    asm volatile("mbarrier.arrive.shared::cta.b64 _, [%0];" ::"r"(sb + B_W) : "memory");
    STAMP(7);
    {
      const int bsel = (int)rank ^ br ^ 1, xl = wtid & 63;
      uint2 gl[4];
      uint32_t ua[4][4], ub[4][4];
#pragma unroll
      for (int i = 0; i < 4; i++) gl[i] = gate_ld((2 * (i >> 1) + bsel) * 128 + (i & 1) * 64 + xl);
#pragma unroll
      for (int i = 0; i < 4; i++) skip_terms(ua[i], ub[i], sb, (2 * (i >> 1) + bsel) * 128 + (i & 1) * 64 + xl, dA, dB);
      const uint32_t yo = sb + CH_OFF + (xl & 3) * 4 + ysw(xl >> 2) + bsel * 512;
#pragma unroll
      for (int slot = 0; slot < 2; slot++) {
        const int box = 2 * slot + bsel;
        uint32_t g2[2], ya[2][4], yb[2][4];
#pragma unroll
        for (int h = 0; h < 2; h++) g2[h] = gate_fin(p, gl[2 * slot + h], box * 128 + h * 64 + xl, tag);
        mbar_wait(sb + B_ST + 8 * box);
        STAMP(8 + slot);
#pragma unroll
        for (int h = 0; h < 2; h++) {
          const uint32_t yh = (yo ^ (h * 32)) + h * 256 + slot * 1024;
          ld4ch(ya[h], yh + Y0_OFF); ld4ch(yb[h], yh + Y0_OFF + 4096);
          if (slot) {
            uint32_t a2[4], b2[4];
            ld4ch(a2, yh + Y2_OFF - 1024); ld4ch(b2, yh + Y2_OFF - 1024 + 3072);
#pragma unroll
            for (int k = 0; k < 4; k++) { ya[h][k] = hadd2(ya[h][k], a2[k]); yb[h][k] = hadd2(yb[h][k], b2[k]); }
          }
        }
        const uint4 r0 = mix(ya[0], yb[0], ua[2 * slot], ub[2 * slot], g2[0]), r1 = mix(ya[1], yb[1], ua[2 * slot + 1], ub[2 * slot + 1], g2[1]);
        if (br == 0) { send_box(sb, slot, xl, rank, r0); send_box(sb, slot, xl + 64, rank, r1); }
        else {
          const uint32_t st = sb + RAW_OFF + slot * 4096 + xl * 16, xin = sb + XIN_OFF + slot * 2048 + xl * 16;
          sts64(st + rank * 8, r0.x, r0.y); sts64(st + 2048 + rank * 8, r0.z, r0.w);
          sts64(st + 1024 + rank * 8, r1.x, r1.y); sts64(st + 3072 + rank * 8, r1.z, r1.w);
          mbar_wait(sb + B_X + slot * 8);
          const uint4 q0 = lds128(xin), q1 = lds128(xin + 1024);
          sts64(st + (rank ^ 1) * 8, q0.x, q0.y); sts64(st + 2048 + (rank ^ 1) * 8, q0.z, q0.w);
          sts64(st + 1024 + (rank ^ 1) * 8, q1.x, q1.y); sts64(st + 3072 + (rank ^ 1) * 8, q1.z, q1.w);
          fence_async();
          bar_sync(6, 64);
          if (xl == 0) {
            asm volatile("cp.async.bulk.tensor.3d.global.shared::cta.bulk_group [%0, {%2, %3, %4}], [%1];"
                         ::"l"(&tm_out), "r"(sb + RAW_OFF + slot * 4096), "r"(oc0), "r"(box * 128), "r"(0) : "memory");
            asm volatile("cp.async.bulk.commit_group;" ::: "memory");
          }
        }
        STAMP(10 + slot);
      }
    }
    if (wtid == 0 && atomicAdd(&g_ticket, 1u) == NCTA + NGATE - 1) { g_ticket = 0; g_epoch = epoch + 1; }
    if (wtid == 64) asm volatile("cp.async.bulk.wait_group.read 0;" ::: "memory");
    STAMP(15);
    return;
  }
  asm volatile("barrier.cluster.arrive.relaxed.aligned;" ::: "memory");

  const int moff = (bid * 4 + (tid >> 7)) * NM + (tid & 63) * 2;
  const int brt = (tid >> 6) & 1;
  const __nv_bfloat16* const* tp = p.t + (brt ? 0 : 6);
  const uint32_t q0 = *(const uint32_t*)(tp[0] + moff), q1 = *(const uint32_t*)(tp[1] + moff);
  const uint32_t q2 = *(const uint32_t*)(tp[2] + moff), q3 = *(const uint32_t*)(tp[3] + moff);
  const uint2 ldt4 = *(const uint2*)(tp[4] + bid * 4);
  const uint32_t q4 = *(const uint32_t*)(tp[brt ? 2 : 5] + moff), q5 = *(const uint32_t*)(tp[brt ? 3 : 6] + moff);

  for (int i = wtid & 63; i < R_BR / 16; i += 64) sts128(cb + R_OFF + br * R_BR + i * 16, 0, 0, 0, 0);
  STAMP(1);

  float acc[5][4];
  float k2048 = 0.f;
  const uint32_t scr = cb + Y0_OFF + wq * SCR_BYTES;
  const uint32_t scr2 = sb + XIN_OFF + warp * 640;
  {
    const uint32_t ldt2 = (ch & 2) ? ldt4.y : ldt4.x;
    const float dt = bf_round(expf((ch & 1) ? bf_hi(ldt2) : bf_lo(ldt2)));
#pragma unroll
    for (int i = 0; i < 5; i++) acc[i][0] = acc[i][1] = acc[i][2] = acc[i][3] = 0.f;
    cf cc[2], zz1[2], zz128[2];
#pragma unroll
    for (int r = 0; r < 2; r++) {
      float v0 = r ? bf_hi(q0) : bf_lo(q0), v1 = r ? bf_hi(q1) : bf_lo(q1), v2 = r ? bf_hi(q2) : bf_lo(q2);
      float v3 = r ? bf_hi(q3) : bf_lo(q3), v4 = r ? bf_hi(q4) : bf_lo(q4), v5 = r ? bf_hi(q5) : bf_lo(q5);
      if (br == 0) { cc[r] = cmul(cf{v2, v3}, cf{dt * v4, dt * v5}); }
      else { v0 = -bf_round(expf(v0)); cc[r] = cf{2.f * dt * v2, 2.f * dt * v3}; }
      const float xl = (dt * v0) * 1.4426950408889634f, y = dt * v1;
      zz1[r] = cexp_p(xl, y, 1.f); zz128[r] = cexp_p(xl, y, 128.f);
    }
    STAMP(2);
    const uint32_t tb = scr + lane * 16;
    const uint32_t ta = scr + (lane >> 3) * 512 + (lane & 7) * 16;
    const uint32_t tc = ((lane & 8) ? scr2 : scr + 4096) + (lane >> 4) * 128 + (lane & 7) * 16;
    const uint32_t tm = scr2 + 512 + ((lane >> 3) & 1) * 64 + (lane >> 4) * 16;
#pragma unroll 1
    for (int r = 0; r < 2; r++) {
      const cf c = r ? cc[1] : cc[0], z1 = r ? zz1[1] : zz1[0], z128 = r ? zz128[1] : zz128[0];
      const cf z2 = csq(z1), z4 = csq(z2), z8 = csq(z4);
      const cf z16 = csq(z8), z24 = cmul(z16, z8), z32 = csq(z16), z40 = cmul(z32, z8), z48 = csq(z24), z56 = cmul(z32, z24), z64 = csq(z32);
      const cf z256 = csq(z128), z512 = csq(z256), z1024 = csq(z512), z2048 = csq(z1024);
      {
        float kk = fmaf(c.re, z2048.re, -c.im * z2048.im);
#pragma unroll
        for (int o = 16; o; o >>= 1) kk += __shfl_xor_sync(0xffffffffu, kk, o);
        k2048 += kk;
      }
      __syncwarp();
      {
        uint32_t xr[4] = {pack_bf16(1.f, z8.re), pack_bf16(z16.re, z24.re), pack_bf16(z32.re, z40.re), pack_bf16(z48.re, z56.re)};
        uint32_t xi[4] = {pack_bf16(0.f, -z8.im), pack_bf16(-z16.im, -z24.im), pack_bf16(-z32.im, -z40.im), pack_bf16(-z48.im, -z56.im)};
        sts128(tb + 0 * 512, xr[0], xr[1], xr[2], xr[3]);
        sts128(tb + 2 * 512, xi[0], xi[1], xi[2], xi[3]);
        const uint32_t yr = pack_bf16(z64.re, z64.re), nyi = pack_bf16(z64.im, z64.im), yi = nyi ^ 0x80008000u;
        uint32_t o[4], q[4];
#pragma unroll
        for (int i = 0; i < 4; i++) CMUL2(o[i], q[i], xr[i], xi[i], yr, yi, nyi);
        sts128(tb + 1 * 512, o[0], o[1], o[2], o[3]);
        sts128(tb + 3 * 512, q[0], q[1], q[2], q[3]);
      }
      {
        const cf h1 = cmul(c, z128), h2 = cmul(c, z256), h3 = cmul(h1, z256), h4 = cmul(c, z512), h5 = cmul(h1, z512), h6 = cmul(h2, z512), h7 = cmul(h3, z512);
        const cf e1 = cmul(c, z1), e2 = cmul(c, z2), e3 = cmul(e1, z2), e129 = cmul(h1, z1), e130 = cmul(h1, z2), e131 = cmul(e129, z2);
        const cf e258 = cmul(h2, z2), e386 = cmul(h3, z2);
        const uint32_t pr0 = pack_bf16(c.re, e1.re), pr2 = pack_bf16(h1.re, e129.re), pi0 = pack_bf16(c.im, e1.im), pi2 = pack_bf16(h1.im, e129.im);
        sts128(tb + 4 * 512, pr0, pack_bf16(e2.re, e3.re), pr2, pack_bf16(e130.re, e131.re));
        sts128(tb + 5 * 512, pi0, pack_bf16(e2.im, e3.im), pi2, pack_bf16(e130.im, e131.im));
        uint32_t xr[4] = {pack_bf16(h2.re, e258.re), pack_bf16(h3.re, e386.re), pack_bf16(h4.re, h5.re), pack_bf16(h6.re, h7.re)};
        uint32_t xi[4] = {pack_bf16(h2.im, e258.im), pack_bf16(h3.im, e386.im), pack_bf16(h4.im, h5.im), pack_bf16(h6.im, h7.im)};
        sts128(tb + 6 * 512, xr[0], xr[1], xr[2], xr[3]);
        sts128(tb + 7 * 512, xi[0], xi[1], xi[2], xi[3]);
        xr[1] = __byte_perm(xr[0], xr[1], 0x5410); xi[1] = __byte_perm(xi[0], xi[1], 0x5410);
        xr[0] = __byte_perm(pr0, pr2, 0x5410); xi[0] = __byte_perm(pi0, pi2, 0x5410);
        const uint32_t yr = pack_bf16(z1024.re, z1024.re), yi = pack_bf16(z1024.im, z1024.im), nyi = yi ^ 0x80008000u;
        uint32_t o[4], q[4];
#pragma unroll
        for (int i = 0; i < 4; i++) CMUL2(o[i], q[i], xr[i], xi[i], yr, yi, nyi);
        sts128(tb + 8 * 512, o[0], o[1], o[2], o[3]);
        sts128(scr2 + lane * 16, q[0], q[1], q[2], q[3]);
        const uint32_t m4 = pack_bf16(z4.re, z4.im);
        sts16(scr2 + 512 + lane * 2, m4); sts16(scr2 + 576 + lane * 2, m4 >> 16);
      }
      __syncwarp();
#pragma unroll
      for (int kp = 0; kp < 2; kp++) {
        uint32_t rr[2], ri[2], yr[2], yi[2];
        ldsm4t(tc + kp * 256, rr[0], ri[0], rr[1], ri[1]);
        ldsm4(tm + kp * 32, yr[0], yi[0], yr[1], yi[1]);
#pragma unroll
        for (int k2 = 0; k2 < 2; k2++) {
          const int kk = kp * 2 + k2;
          uint32_t a0, a1, a2, a3, pr, pi, qr, qi, xr, xi;
          ldsm4t(ta + kk * 128, a0, a1, a2, a3);
          ldsm4t(ta + 2048 + kk * 128, pr, pi, qr, qi);
          const uint32_t nyi = yi[k2] ^ 0x80008000u;
          mma16816(acc[0], a0, a1, a2, a3, pr, pi);
          mma16816(acc[2], a0, a1, a2, a3, qr, qi);
          mma16816(acc[4], a0, a1, a2, a3, rr[k2], ri[k2]);
          CMUL2(xr, xi, pr, pi, yr[k2], yi[k2], nyi);
          mma16816(acc[1], a0, a1, a2, a3, xr, xi);
          CMUL2(xr, xi, qr, qi, yr[k2], yi[k2], nyi);
          mma16816(acc[3], a0, a1, a2, a3, xr, xi);
        }
      }
    }
  }
  STAMP(3);
  __syncwarp();
  {
    const uint32_t xs = scr + lane * 16;
#define OTH(i, k) __float_as_uint(hf ? acc[i][k] : acc[i][2 + (k)])
    sts128(xs, OTH(0, 0), OTH(0, 1), OTH(1, 0), OTH(1, 1));
    sts128(xs + 512, OTH(2, 0), OTH(2, 1), OTH(3, 0), OTH(3, 1));
    sts128(xs + 1024, OTH(4, 0), OTH(4, 1), __float_as_uint(k2048), 0);
#undef OTH
  }

  bar_sync(7 + (warp >> 1), 64);
  STAMP(4);
  {
    const uint32_t xo = cb + Y0_OFF + (wq ^ 1) * SCR_BYTES + lane * 16;
    const uint4 o0 = lds128(xo), o1 = lds128(xo + 512), o2 = lds128(xo + 1024);
    const uint32_t rb = cb + R_OFF + br * R_BR;
#define OWN(i, k) (hf ? acc[i][2 + (k)] : acc[i][k])
    const uint32_t vP = pack_bf16(OWN(0, 1) + __uint_as_float(o0.y), OWN(0, 0) + __uint_as_float(o0.x));
    const uint32_t vP4 = pack_bf16(OWN(1, 1) + __uint_as_float(o0.w), OWN(1, 0) + __uint_as_float(o0.z));
    const uint32_t vQ = pack_bf16(OWN(2, 1) + __uint_as_float(o1.y), OWN(2, 0) + __uint_as_float(o1.x));
    const uint32_t vQ4 = pack_bf16(OWN(3, 1) + __uint_as_float(o1.w), OWN(3, 0) + __uint_as_float(o1.z));
    const uint32_t vR = pack_bf16(OWN(4, 1) + __uint_as_float(o2.y), OWN(4, 0) + __uint_as_float(o2.x));
#undef OWN
    const int j = g + 8 * hf;
    {
      const int a = 2 * (t & 1) + 64 * (t & 2) + 8 * j;
      const uint32_t ad = rb + 2 * (RD_X0 - 1 - a);
      const uint32_t a1 = (t & 2) ? ad - 8 : ad, a2 = (t & 2) ? ad : ad - 8;
      const uint32_t w1 = (t & 2) ? vP4 : vP, w2 = (t & 2) ? vP : vP4;
      sts32(a1, w1); sts32(a2, w2);
      sts16(a1 + RD_CS + 2, w1); sts16(a1 + RD_CS + 4, w1 >> 16);
      sts16(a2 + RD_CS + 2, w2); sts16(a2 + RD_CS + 4, w2 >> 16);
    }
    if (t < 2) {
      const int b = 256 + 128 * t + 8 * j;
      const uint32_t ad = rb + 2 * (RD_X0 - 6 - b);
      const uint32_t v22 = __byte_perm(vQ4, 0, 0x3232), v00 = __byte_perm(vQ, 0, 0x3232);
      sts16(ad, vQ4);
      sts64(ad + 2, v22, __byte_perm(vQ4, vQ, 0x5432));
      sts32(ad + 10, v00);
      if (b != 256) { sts16(ad + 14, v00); sts128(ad + RD_CS + 2, vQ4, v22, vQ, v00); }
      else { sts64(ad + RD_CS + 2, vQ4, v22); sts32(ad + RD_CS + 10, vQ); sts16(ad + RD_CS + 14, v00); }
    } else {
      const uint32_t ao = rb + R_O2 + 2 * (159 - (32 * t + j)), ae = ao - (R_O2 - R_E2) + 2;
      sts16(ao, vQ4 >> 16); sts16(ao + RS_CS + 2, vQ4 >> 16); sts16(ao - 32, vQ4); sts16(ao - 32 + RS_CS + 2, vQ4);
      sts16(ae - 32, vQ); sts16(ae - 32 + RS_CS + 2, vQ);
      if (lane != 2 || hf) { sts16(ae, vQ >> 16); sts16(ae + RS_CS + 2, vQ >> 16); }
      else {
        const uint32_t vv = __byte_perm(vQ, 0, 0x3232), ad = rb + 2 * (RD_X0 - 514);
        sts16(ad, vv); sts32(ad + 2, vv); sts16(ad + 6, vv); sts64(ad + RD_CS + 2, vv, vv);
      }
    }
    {
      const uint32_t a = rb + ((g & 1) ? R_O3 : R_E3 + 2) + 2 * (159 - (64 + 16 * t + (j >> 1)));
      const bool p1024 = (lane == 0) && (hf == 0);
      const uint32_t a00 = p1024 ? rb + R_E2 + 2 * (159 - 127) : a;
      sts16(a00, vR >> 16); sts16(a00 + RS_CS + 2, vR >> 16);
      sts16(a - 16, vR); sts16(a - 16 + RS_CS + 2, vR);
      if (p1024) {
        sts32(sb + K1024_OFF + (ch * 2 + br) * 4, __byte_perm(vR, 0, 0x3232));
        const uint32_t kv = pack_bf16(k2048 + __uint_as_float(o2.z), 0.f);
        sts16(rb + R_E3 + 2 * (159 - 127), kv); sts16(rb + R_E3 + 2 * (159 - 127) + RS_CS + 2, kv);
      }
    }
  }
  STAMP(5);
  asm volatile("barrier.cluster.wait.aligned;" ::: "memory");
  bar_sync(7 + (warp >> 1), 64);
  mbar_wait(sb + B_U);
  STAMP(6);

  const uint32_t zz = lds32(cb + R_OFF + br * R_BR);
  conv_dense(sb, cb, zz);
  STAMP(8);
  {
    const int x = (4 + ch) * 128 + wtid, c = x >> 2;
    const uint2 dA = ldg64(p.A_D + bid * 4), dB = ldg64(p.B_D + bid * 4);
    const uint2 gl = gate_ld(x);
    const uint32_t rb = cb + R_OFF + br * R_BR;
    float e48[24], e40[20], e32[16], h32[16], h16[8];
    const int x1 = 159 - (16 * hf + g - 2 * t + 136);
    const uint32_t fs = rb + ((g & 1) ? 2 * x1 : RS_CS + 2 * x1 + 2);
    uint32_t A[2][4][4];
    auto loadA = [&](int buf, uint32_t oe, uint32_t oo, int i0) {
#pragma unroll
      for (int a = 0; a < 2; a++) {
        const uint32_t base = fs + (a ? oo : oe) + i0 * 16;
        uint32_t* k0 = A[buf][2 * a];
        uint32_t* k1 = A[buf][2 * a + 1];
        k0[1] = lds32(base); k0[0] = lds32(base + 16); k0[2] = lds32(base + 32); k1[0] = lds32(base + 48); k1[2] = lds32(base + 64);
        k0[3] = k0[0]; k1[1] = k0[2]; k1[3] = k1[0];
      }
    };
    loadA(0, R_E2, R_O2, 8);
    loadA(1, R_E2, R_O2, 4);
    mbar_wait(sb + B_W);
    const uint64_t d5 = mkdesc(cb + W5_OFF, 144, 576), d3 = mkdesc(cb + W3_OFF, 144, 576);
    const uint64_t d9 = mkdesc(cb + W9_OFF, 144, 576), d7 = mkdesc(cb + W7_OFF, 144, 576);
    const uint32_t y2d = cb + Y2_OFF + br * 3072 + ysw(32 * (5 - (lane >> 4)) + 16 * hf + (lane & 15));
    const uint32_t y3d = cb + Y3_OFF + br * 2048 + ysw(2 * (16 * hf + (lane & 15)) + (lane >> 4));
#define FAR4(N, ACC, BUF, DA, DB, OFF, FIRST)                                                            \
    wg_fence();                                                                                           \
    _Pragma("unroll") for (int k = 0; k < 4; k++) {                                                      \
      const uint32_t* a = A[BUF][k];                                                                      \
      wgmma_rs<N, 1>(ACC, a[0], a[1], a[2], a[3], ((k >> 1) ? DB : DA) + (k & 1) * 18 + (OFF), !(FIRST) || k); \
    }                                                                                                     \
    wg_commit();
    FAR4(48, e48, 0, d5, d3, 0, 1)
    wg_wait0();
    loadA(0, R_E2, R_O2, 0);
    stsm2(y2d - 5 * 512, PK2(e48, 20), PK2(e48, 22));
#pragma unroll
    for (int i = 0; i < 20; i++) e40[i] = FCPY(e48[i]);
    stage_done(sb, 2, lane);
    FAR4(40, e40, 1, d5, d3, 36, 0)
    wg_wait0();
    loadA(1, R_E3, R_O3, 8);
    stsm2(y2d - 4 * 512, PK2(e40, 16), PK2(e40, 18));
#pragma unroll
    for (int i = 0; i < 16; i++) e32[i] = FCPY(e40[i]);
    stage_done(sb, 3, lane);
    FAR4(32, e32, 0, d5, d3, 72, 0)
    FAR4(32, h32, 1, d9, d7, 0, 1)
    wg_wait1();
    loadA(0, R_E3, R_O3, 4);
    stsm4(y2d, PK2(e32, 0), PK2(e32, 2), PK2(e32, 4), PK2(e32, 6));
    stsm4(y2d - 2 * 512, PK2(e32, 8), PK2(e32, 10), PK2(e32, 12), PK2(e32, 14));
    stage_done(sb, 4, lane);
    STAMP(9);
    wg_wait0();
    stsm4(y3d, PK2(h32, 8), PK2(h32, 10), PK2(h32, 12), PK2(h32, 14));
#pragma unroll
    for (int i = 0; i < 8; i++) h16[i] = FCPY(h32[i]);
    stage_done(sb, 5, lane);
    FAR4(16, h16, 0, d9, d7, 72, 0)
#undef FAR4
    const uint32_t yo = sb + CH_OFF + (x & 3) * 4 + ysw(c);
    uint32_t ua[4], ub[4], ya[4], yb[4], a2[4], b2[4], a3[4], b3[4], s2[4];
    skip_terms(ua, ub, sb, x, dA, dB);
    ld4ch(s2, sb + CH_OFF + (x & 3) * 4 + S2_OFF + ((c - 128) + ((c - 128) >> 3)) * 16);
    const uint32_t tag = lds32(sb + TAG_OFF);
    wg_wait0();
    stsm4(y3d + 1024, PK2(h16, 0), PK2(h16, 2), PK2(h16, 4), PK2(h16, 6));
    stage_done(sb, 6, lane);
    STAMP(10);
    const uint32_t g2 = gate_fin(p, gl, x, tag);
    mbar_wait(sb + B_ST + 8 * 4);
    const uint4 k0 = lds128(sb + K1024_OFF), k1 = lds128(sb + K1024_OFF + 16);
    const uint32_t kk[8] = {k0.x, k0.y, k0.z, k0.w, k1.x, k1.y, k1.z, k1.w};
    ld4ch(ya, yo + Y0_OFF); ld4ch(yb, yo + Y0_OFF + 4096);
    ld4ch(a2, yo + Y2_OFF - 1024); ld4ch(b2, yo + Y2_OFF - 1024 + 3072);
    mbar_wait(sb + B_ST + 8 * (5 + (ch >> 1)));
    STAMP(12);
    ld4ch(a3, yo + Y3_OFF - 2048); ld4ch(b3, yo + Y3_OFF - 2048 + 2048);
#pragma unroll
    for (int k = 0; k < 4; k++) {
      ya[k] = hadd2(ya[k], hadd2(hfma2(kk[2 * k], s2[k], a2[k]), a3[k]));
      yb[k] = hadd2(yb[k], hadd2(hfma2(kk[2 * k + 1], s2[k], b2[k]), b3[k]));
    }
    const uint4 r = mix(ya, yb, ua, ub, g2);
    if ((uint32_t)(ch & 1) != rank) send_box(sb, 2 + (ch >> 1), wtid, rank, r);
    else merge_box(sb, &tm_out, 2 + (ch >> 1), wtid, rank, oc0, r, 1 + ch);
  }
  STAMP(14);
  if (wtid == 0) asm volatile("cp.async.bulk.wait_group.read 0;" ::: "memory");
  STAMP(15); GT(1);
}

typedef CUresult (*EncodeFn)(CUtensorMap*, CUtensorMapDataType, cuuint32_t, void*, const cuuint64_t*, const cuuint64_t*,
                             const cuuint32_t*, const cuuint32_t*, CUtensorMapInterleave, CUtensorMapSwizzle,
                             CUtensorMapL2promotion, CUtensorMapFloatOOBfill);

}

extern "C" void kernel_launch(void* const* d_in, const int* in_sizes, int n_in, void* d_out, int out_size) {
  (void)in_sizes; (void)n_in; (void)out_size;
  typedef const __nv_bfloat16* bp;
  Params p;
  p.t[0] = (bp)d_in[10]; p.t[1] = (bp)d_in[11]; p.t[2] = (bp)d_in[12]; p.t[3] = (bp)d_in[13]; p.t[4] = (bp)d_in[14]; p.t[5] = nullptr;
  p.t[6] = (bp)d_in[1]; p.t[7] = (bp)d_in[2]; p.t[8] = (bp)d_in[5]; p.t[9] = (bp)d_in[6]; p.t[10] = (bp)d_in[7];
  p.t[11] = (bp)d_in[3]; p.t[12] = (bp)d_in[4]; p.t[13] = nullptr;
  p.u = (bp)d_in[0]; p.gw = (bp)d_in[16]; p.A_D = (bp)d_in[8]; p.B_D = (bp)d_in[15];
  static EncodeFn enc = nullptr;
  if (!enc) {
    cudaDriverEntryPointQueryResult qr;
    cudaGetDriverEntryPoint("cuTensorMapEncodeTiled", (void**)&enc, cudaEnableDefault, &qr);
    cudaFuncSetAttribute(ssm_kernel, cudaFuncAttributeMaxDynamicSharedMemorySize, SMEM_BYTES);
  }
  CUtensorMap tm_in, tm_out;
  {
    cuuint64_t gd[5] = {512, 2, 4, 4, 64};
    cuuint64_t gs[4] = {1024, 8192, 2048, 32768};
    cuuint32_t bx[5] = {8, 2, 4, 4, 32};
    cuuint32_t es[5] = {1, 1, 1, 1, 1};
    enc(&tm_in, CU_TENSOR_MAP_DATA_TYPE_BFLOAT16, 5, d_in[0], gd, gs, bx, es, CU_TENSOR_MAP_INTERLEAVE_NONE,
        CU_TENSOR_MAP_SWIZZLE_NONE, CU_TENSOR_MAP_L2_PROMOTION_NONE, CU_TENSOR_MAP_FLOAT_OOB_FILL_NONE);
  }
  {
    cuuint64_t gd[3] = {512, 1024, 2};
    cuuint64_t gs[2] = {2048, 1024};
    cuuint32_t bx[3] = {8, 128, 2};
    cuuint32_t es[3] = {1, 1, 1};
    enc(&tm_out, CU_TENSOR_MAP_DATA_TYPE_BFLOAT16, 3, d_out, gd, gs, bx, es, CU_TENSOR_MAP_INTERLEAVE_NONE,
        CU_TENSOR_MAP_SWIZZLE_NONE, CU_TENSOR_MAP_L2_PROMOTION_NONE, CU_TENSOR_MAP_FLOAT_OOB_FILL_NONE);
  }
  ssm_kernel<<<NCTA + NGATE, 640, SMEM_BYTES, cudaStreamPerThread>>>(p, tm_in, tm_out);
}
```

```cpp
#include <cuda_runtime.h>
#include <cuda.h>
#include <cuda_bf16.h>
#include <stdint.h>

namespace {
#define FCPY(x) __uint_as_float(opq(__float_as_uint(x), zz))

constexpr int L = 2048, D = 512, NM = 128;
constexpr int NCTA = 128;
constexpr int NGATE = 4;

constexpr int RAW_OFF = 0;
constexpr int XIN_OFF = 32768;
constexpr int BAR_OFF = XIN_OFF + 10240;
constexpr int CH_OFF = BAR_OFF + 256;
constexpr int U_CS = 1184;
constexpr int U_OFF = 0;
constexpr int R_OFF = 4736;
constexpr int RD_X0 = 565;
constexpr int RD_CS = 1216;
constexpr int RS_CS = 320;
constexpr int R_E2 = 2 * RD_CS, R_O2 = R_E2 + 2 * RS_CS, R_E3 = R_O2 + 2 * RS_CS, R_O3 = R_E3 + 2 * RS_CS;
constexpr int R_BR = R_O3 + 2 * RS_CS;
constexpr int W5_OFF = R_OFF + 2 * R_BR;
constexpr int W3_OFF = W5_OFF + 3456;
constexpr int W9_OFF = W3_OFF + 3456;
constexpr int W7_OFF = W9_OFF + 2304;
constexpr int S2_OFF = W7_OFF + 2304;
constexpr int Y0_OFF = S2_OFF + 2304;
constexpr int Y2_OFF = Y0_OFF + 8192, Y3_OFF = Y2_OFF + 6144;
constexpr int CH_BYTES = Y0_OFF + 18432 + 16;
constexpr int SCR_BYTES = 4608;
constexpr int SMEM_BYTES = CH_OFF + 4 * CH_BYTES;
static_assert(CH_BYTES % 128 == 16, "bank staggering of the channel blocks");
static_assert(SMEM_BYTES <= 232448, "smem");
constexpr int B_RAW = BAR_OFF, B_X = BAR_OFF + 8, B_U = BAR_OFF + 40, B_W = BAR_OFF + 48;
constexpr int TAG_OFF = BAR_OFF + 56;
constexpr int K1024_OFF = BAR_OFF + 64;
constexpr int B_ST = BAR_OFF + 96;

__device__ unsigned int g_gate[L];
__device__ unsigned int g_epoch;
__device__ unsigned int g_ticket;

#define STAMP(k)
#define GT(k)

struct Params {
  const __nv_bfloat16* t[14];
  const __nv_bfloat16 *u, *gw, *A_D, *B_D;
};

template <int N, int TB> __device__ __forceinline__ void wgmma_rs(float* d, uint32_t a0, uint32_t a1, uint32_t a2, uint32_t a3, uint64_t desc, int sc);
template <> __device__ __forceinline__ void wgmma_rs<64, 0>(float* d, uint32_t a0, uint32_t a1, uint32_t a2, uint32_t a3, uint64_t desc, int sc) {
  asm volatile("{\n.reg .pred p;\nsetp.ne.b32 p, %37, 0;\n"
    "wgmma.mma_async.sync.aligned.m64n64k16.f32.bf16.bf16 {%0,%1,%2,%3,%4,%5,%6,%7,%8,%9,%10,%11,%12,%13,%14,%15,%16,%17,%18,%19,%20,%21,%22,%23,%24,%25,%26,%27,%28,%29,%30,%31}, {%32,%33,%34,%35}, %36, p, 1, 1, 0;\n}"
    : "+f"(d[0]), "+f"(d[1]), "+f"(d[2]), "+f"(d[3]), "+f"(d[4]), "+f"(d[5]), "+f"(d[6]), "+f"(d[7]), "+f"(d[8]), "+f"(d[9]), "+f"(d[10]), "+f"(d[11]), "+f"(d[12]), "+f"(d[13]), "+f"(d[14]), "+f"(d[15]), "+f"(d[16]), "+f"(d[17]), "+f"(d[18]), "+f"(d[19]), "+f"(d[20]), "+f"(d[21]), "+f"(d[22]), "+f"(d[23]), "+f"(d[24]), "+f"(d[25]), "+f"(d[26]), "+f"(d[27]), "+f"(d[28]), "+f"(d[29]), "+f"(d[30]), "+f"(d[31]) : "r"(a0), "r"(a1), "r"(a2), "r"(a3), "l"(desc), "r"(sc));
}
template <> __device__ __forceinline__ void wgmma_rs<56, 0>(float* d, uint32_t a0, uint32_t a1, uint32_t a2, uint32_t a3, uint64_t desc, int sc) {
  asm volatile("{\n.reg .pred p;\nsetp.ne.b32 p, %33, 0;\n"
    "wgmma.mma_async.sync.aligned.m64n56k16.f32.bf16.bf16 {%0,%1,%2,%3,%4,%5,%6,%7,%8,%9,%10,%11,%12,%13,%14,%15,%16,%17,%18,%19,%20,%21,%22,%23,%24,%25,%26,%27}, {%28,%29,%30,%31}, %32, p, 1, 1, 0;\n}"
    : "+f"(d[0]), "+f"(d[1]), "+f"(d[2]), "+f"(d[3]), "+f"(d[4]), "+f"(d[5]), "+f"(d[6]), "+f"(d[7]), "+f"(d[8]), "+f"(d[9]), "+f"(d[10]), "+f"(d[11]), "+f"(d[12]), "+f"(d[13]), "+f"(d[14]), "+f"(d[15]), "+f"(d[16]), "+f"(d[17]), "+f"(d[18]), "+f"(d[19]), "+f"(d[20]), "+f"(d[21]), "+f"(d[22]), "+f"(d[23]), "+f"(d[24]), "+f"(d[25]), "+f"(d[26]), "+f"(d[27]) : "r"(a0), "r"(a1), "r"(a2), "r"(a3), "l"(desc), "r"(sc));
}
template <> __device__ __forceinline__ void wgmma_rs<48, 0>(float* d, uint32_t a0, uint32_t a1, uint32_t a2, uint32_t a3, uint64_t desc, int sc) {
  asm volatile("{\n.reg .pred p;\nsetp.ne.b32 p, %29, 0;\n"
    "wgmma.mma_async.sync.aligned.m64n48k16.f32.bf16.bf16 {%0,%1,%2,%3,%4,%5,%6,%7,%8,%9,%10,%11,%12,%13,%14,%15,%16,%17,%18,%19,%20,%21,%22,%23}, {%24,%25,%26,%27}, %28, p, 1, 1, 0;\n}"
    : "+f"(d[0]), "+f"(d[1]), "+f"(d[2]), "+f"(d[3]), "+f"(d[4]), "+f"(d[5]), "+f"(d[6]), "+f"(d[7]), "+f"(d[8]), "+f"(d[9]), "+f"(d[10]), "+f"(d[11]), "+f"(d[12]), "+f"(d[13]), "+f"(d[14]), "+f"(d[15]), "+f"(d[16]), "+f"(d[17]), "+f"(d[18]), "+f"(d[19]), "+f"(d[20]), "+f"(d[21]), "+f"(d[22]), "+f"(d[23]) : "r"(a0), "r"(a1), "r"(a2), "r"(a3), "l"(desc), "r"(sc));
}
template <> __device__ __forceinline__ void wgmma_rs<32, 0>(float* d, uint32_t a0, uint32_t a1, uint32_t a2, uint32_t a3, uint64_t desc, int sc) {
  asm volatile("{\n.reg .pred p;\nsetp.ne.b32 p, %21, 0;\n"
    "wgmma.mma_async.sync.aligned.m64n32k16.f32.bf16.bf16 {%0,%1,%2,%3,%4,%5,%6,%7,%8,%9,%10,%11,%12,%13,%14,%15}, {%16,%17,%18,%19}, %20, p, 1, 1, 0;\n}"
    : "+f"(d[0]), "+f"(d[1]), "+f"(d[2]), "+f"(d[3]), "+f"(d[4]), "+f"(d[5]), "+f"(d[6]), "+f"(d[7]), "+f"(d[8]), "+f"(d[9]), "+f"(d[10]), "+f"(d[11]), "+f"(d[12]), "+f"(d[13]), "+f"(d[14]), "+f"(d[15]) : "r"(a0), "r"(a1), "r"(a2), "r"(a3), "l"(desc), "r"(sc));
}
template <> __device__ __forceinline__ void wgmma_rs<48, 1>(float* d, uint32_t a0, uint32_t a1, uint32_t a2, uint32_t a3, uint64_t desc, int sc) {
  asm volatile("{\n.reg .pred p;\nsetp.ne.b32 p, %29, 0;\n"
    "wgmma.mma_async.sync.aligned.m64n48k16.f32.bf16.bf16 {%0,%1,%2,%3,%4,%5,%6,%7,%8,%9,%10,%11,%12,%13,%14,%15,%16,%17,%18,%19,%20,%21,%22,%23}, {%24,%25,%26,%27}, %28, p, 1, 1, 1;\n}"
    : "+f"(d[0]), "+f"(d[1]), "+f"(d[2]), "+f"(d[3]), "+f"(d[4]), "+f"(d[5]), "+f"(d[6]), "+f"(d[7]), "+f"(d[8]), "+f"(d[9]), "+f"(d[10]), "+f"(d[11]), "+f"(d[12]), "+f"(d[13]), "+f"(d[14]), "+f"(d[15]), "+f"(d[16]), "+f"(d[17]), "+f"(d[18]), "+f"(d[19]), "+f"(d[20]), "+f"(d[21]), "+f"(d[22]), "+f"(d[23]) : "r"(a0), "r"(a1), "r"(a2), "r"(a3), "l"(desc), "r"(sc));
}
template <> __device__ __forceinline__ void wgmma_rs<40, 1>(float* d, uint32_t a0, uint32_t a1, uint32_t a2, uint32_t a3, uint64_t desc, int sc) {
  asm volatile("{\n.reg .pred p;\nsetp.ne.b32 p, %25, 0;\n"
    "wgmma.mma_async.sync.aligned.m64n40k16.f32.bf16.bf16 {%0,%1,%2,%3,%4,%5,%6,%7,%8,%9,%10,%11,%12,%13,%14,%15,%16,%17,%18,%19}, {%20,%21,%22,%23}, %24, p, 1, 1, 1;\n}"
    : "+f"(d[0]), "+f"(d[1]), "+f"(d[2]), "+f"(d[3]), "+f"(d[4]), "+f"(d[5]), "+f"(d[6]), "+f"(d[7]), "+f"(d[8]), "+f"(d[9]), "+f"(d[10]), "+f"(d[11]), "+f"(d[12]), "+f"(d[13]), "+f"(d[14]), "+f"(d[15]), "+f"(d[16]), "+f"(d[17]), "+f"(d[18]), "+f"(d[19]) : "r"(a0), "r"(a1), "r"(a2), "r"(a3), "l"(desc), "r"(sc));
}
template <> __device__ __forceinline__ void wgmma_rs<32, 1>(float* d, uint32_t a0, uint32_t a1, uint32_t a2, uint32_t a3, uint64_t desc, int sc) {
  asm volatile("{\n.reg .pred p;\nsetp.ne.b32 p, %21, 0;\n"
    "wgmma.mma_async.sync.aligned.m64n32k16.f32.bf16.bf16 {%0,%1,%2,%3,%4,%5,%6,%7,%8,%9,%10,%11,%12,%13,%14,%15}, {%16,%17,%18,%19}, %20, p, 1, 1, 1;\n}"
    : "+f"(d[0]), "+f"(d[1]), "+f"(d[2]), "+f"(d[3]), "+f"(d[4]), "+f"(d[5]), "+f"(d[6]), "+f"(d[7]), "+f"(d[8]), "+f"(d[9]), "+f"(d[10]), "+f"(d[11]), "+f"(d[12]), "+f"(d[13]), "+f"(d[14]), "+f"(d[15]) : "r"(a0), "r"(a1), "r"(a2), "r"(a3), "l"(desc), "r"(sc));
}
template <> __device__ __forceinline__ void wgmma_rs<16, 1>(float* d, uint32_t a0, uint32_t a1, uint32_t a2, uint32_t a3, uint64_t desc, int sc) {
  asm volatile("{\n.reg .pred p;\nsetp.ne.b32 p, %13, 0;\n"
    "wgmma.mma_async.sync.aligned.m64n16k16.f32.bf16.bf16 {%0,%1,%2,%3,%4,%5,%6,%7}, {%8,%9,%10,%11}, %12, p, 1, 1, 1;\n}"
    : "+f"(d[0]), "+f"(d[1]), "+f"(d[2]), "+f"(d[3]), "+f"(d[4]), "+f"(d[5]), "+f"(d[6]), "+f"(d[7]) : "r"(a0), "r"(a1), "r"(a2), "r"(a3), "l"(desc), "r"(sc));
}

__device__ __forceinline__ uint32_t pack_bf16(float lo, float hi) {
  uint32_t r; asm("cvt.rn.bf16x2.f32 %0, %1, %2;" : "=r"(r) : "f"(hi), "f"(lo)); return r;
}
__device__ __forceinline__ float bf_lo(uint32_t v) { return __uint_as_float(v << 16); }
__device__ __forceinline__ float bf_hi(uint32_t v) { return __uint_as_float(v & 0xffff0000u); }
__device__ __forceinline__ float bf_round(float x) { return bf_lo(pack_bf16(x, 0.f)); }
__device__ __forceinline__ uint32_t hmul2(uint32_t a, uint32_t b) { uint32_t r; asm("mul.rn.bf16x2 %0, %1, %2;" : "=r"(r) : "r"(a), "r"(b)); return r; }
__device__ __forceinline__ uint32_t hadd2(uint32_t a, uint32_t b) { uint32_t r; asm("add.rn.bf16x2 %0, %1, %2;" : "=r"(r) : "r"(a), "r"(b)); return r; }
__device__ __forceinline__ uint32_t hsub2(uint32_t a, uint32_t b) { uint32_t r; asm("sub.rn.bf16x2 %0, %1, %2;" : "=r"(r) : "r"(a), "r"(b)); return r; }
__device__ __forceinline__ uint32_t hfma2(uint32_t a, uint32_t b, uint32_t c) { uint32_t r; asm("fma.rn.bf16x2 %0, %1, %2, %3;" : "=r"(r) : "r"(a), "r"(b), "r"(c)); return r; }

__device__ __forceinline__ void sts16(uint32_t a, uint32_t v) { asm volatile("st.shared.b16 [%0], %1;" ::"r"(a), "h"((unsigned short)v) : "memory"); }
__device__ __forceinline__ void sts32(uint32_t a, uint32_t v) { asm volatile("st.shared.b32 [%0], %1;" ::"r"(a), "r"(v) : "memory"); }
__device__ __forceinline__ void sts64(uint32_t a, uint32_t x, uint32_t y) { asm volatile("st.shared.v2.b32 [%0], {%1,%2};" ::"r"(a), "r"(x), "r"(y) : "memory"); }
__device__ __forceinline__ void sts128(uint32_t a, uint32_t x, uint32_t y, uint32_t z, uint32_t w) {
  asm volatile("st.shared.v4.b32 [%0], {%1,%2,%3,%4};" ::"r"(a), "r"(x), "r"(y), "r"(z), "r"(w) : "memory");
}
__device__ __forceinline__ uint32_t lds32(uint32_t a) { uint32_t v; asm volatile("ld.shared.b32 %0, [%1];" : "=r"(v) : "r"(a) : "memory"); return v; }
__device__ __forceinline__ uint2 lds64(uint32_t a) { uint2 v; asm volatile("ld.shared.v2.b32 {%0,%1}, [%2];" : "=r"(v.x), "=r"(v.y) : "r"(a) : "memory"); return v; }
__device__ __forceinline__ uint4 lds128(uint32_t a) {
  uint4 v; asm volatile("ld.shared.v4.b32 {%0,%1,%2,%3}, [%4];" : "=r"(v.x), "=r"(v.y), "=r"(v.z), "=r"(v.w) : "r"(a) : "memory"); return v;
}
__device__ __forceinline__ uint4 ldg128(const void* a) {
  uint4 v; asm volatile("ld.global.nc.v4.b32 {%0,%1,%2,%3}, [%4];" : "=r"(v.x), "=r"(v.y), "=r"(v.z), "=r"(v.w) : "l"(a) : "memory"); return v;
}
__device__ __forceinline__ uint2 ldg64(const void* a) {
  uint2 v; asm volatile("ld.global.nc.v2.b32 {%0,%1}, [%2];" : "=r"(v.x), "=r"(v.y) : "l"(a) : "memory"); return v;
}
__device__ __forceinline__ void ldsm4(uint32_t a, uint32_t& r0, uint32_t& r1, uint32_t& r2, uint32_t& r3) {
  asm volatile("ldmatrix.sync.aligned.m8n8.x4.shared.b16 {%0,%1,%2,%3}, [%4];" : "=r"(r0), "=r"(r1), "=r"(r2), "=r"(r3) : "r"(a) : "memory");
}
__device__ __forceinline__ void ldsm4t(uint32_t a, uint32_t& r0, uint32_t& r1, uint32_t& r2, uint32_t& r3) {
  asm volatile("ldmatrix.sync.aligned.m8n8.x4.trans.shared.b16 {%0,%1,%2,%3}, [%4];" : "=r"(r0), "=r"(r1), "=r"(r2), "=r"(r3) : "r"(a) : "memory");
}
__device__ __forceinline__ void stsm4(uint32_t a, uint32_t r0, uint32_t r1, uint32_t r2, uint32_t r3) {
  asm volatile("stmatrix.sync.aligned.m8n8.x4.shared.b16 [%0], {%1,%2,%3,%4};" ::"r"(a), "r"(r0), "r"(r1), "r"(r2), "r"(r3) : "memory");
}
__device__ __forceinline__ void stsm4t(uint32_t a, uint32_t r0, uint32_t r1, uint32_t r2, uint32_t r3) {
  asm volatile("stmatrix.sync.aligned.m8n8.x4.trans.shared.b16 [%0], {%1,%2,%3,%4};" ::"r"(a), "r"(r0), "r"(r1), "r"(r2), "r"(r3) : "memory");
}
__device__ __forceinline__ void stsm2(uint32_t a, uint32_t r0, uint32_t r1) {
  asm volatile("stmatrix.sync.aligned.m8n8.x2.shared.b16 [%0], {%1,%2};" ::"r"(a), "r"(r0), "r"(r1) : "memory");
}
__device__ __forceinline__ void stsm2t(uint32_t a, uint32_t r0, uint32_t r1) {
  asm volatile("stmatrix.sync.aligned.m8n8.x2.trans.shared.b16 [%0], {%1,%2};" ::"r"(a), "r"(r0), "r"(r1) : "memory");
}
__device__ __forceinline__ void mma16816(float* c, uint32_t a0, uint32_t a1, uint32_t a2, uint32_t a3, uint32_t b0, uint32_t b1) {
  asm("mma.sync.aligned.m16n8k16.row.col.f32.bf16.bf16.f32 {%0,%1,%2,%3}, {%4,%5,%6,%7}, {%8,%9}, {%0,%1,%2,%3};"
      : "+f"(c[0]), "+f"(c[1]), "+f"(c[2]), "+f"(c[3]) : "r"(a0), "r"(a1), "r"(a2), "r"(a3), "r"(b0), "r"(b1));
}
__device__ __forceinline__ void bar_sync(int id, int n) { asm volatile("bar.sync %0, %1;" ::"r"(id), "r"(n) : "memory"); }
__device__ __forceinline__ void bar_arrive(int id, int n) { asm volatile("bar.arrive %0, %1;" ::"r"(id), "r"(n) : "memory"); }
__device__ __forceinline__ void wg_fence() { asm volatile("wgmma.fence.sync.aligned;" ::: "memory"); }
__device__ __forceinline__ void wg_commit() { asm volatile("wgmma.commit_group.sync.aligned;" ::: "memory"); }
__device__ __forceinline__ void wg_wait0() { asm volatile("wgmma.wait_group.sync.aligned 0;" ::: "memory"); }
__device__ __forceinline__ void wg_wait1() { asm volatile("wgmma.wait_group.sync.aligned 1;" ::: "memory"); }
__device__ __forceinline__ void fence_async() { asm volatile("fence.proxy.async.shared::cta;" ::: "memory"); }
__device__ __forceinline__ uint32_t opq(uint32_t x, uint32_t z) { uint32_t r; asm volatile("xor.b32 %0, %1, %2;" : "=r"(r) : "r"(x), "r"(z)); return r; }
__device__ __forceinline__ uint64_t mkdesc(uint32_t addr, uint32_t lbo, uint32_t sbo) {
  return (uint64_t)((addr & 0x3FFFF) >> 4) | ((uint64_t)(lbo >> 4) << 16) | ((uint64_t)(sbo >> 4) << 32);
}
__device__ __forceinline__ uint32_t mapa(uint32_t a, uint32_t rank) {
  uint32_t r; asm("mapa.shared::cluster.u32 %0, %1, %2;" : "=r"(r) : "r"(a), "r"(rank)); return r;
}
__device__ __forceinline__ void mbar_init_expect(uint32_t bar, uint32_t bytes) {
  asm volatile("mbarrier.init.shared::cta.b64 [%0], 1;" ::"r"(bar) : "memory");
  asm volatile("mbarrier.arrive.expect_tx.shared::cta.b64 _, [%0], %1;" ::"r"(bar), "r"(bytes) : "memory");
}
__device__ __forceinline__ void mbar_wait(uint32_t bar) {
#pragma unroll 1
  for (int it = 0; it < (1 << 22); it++) {
    uint32_t ok;
    asm volatile("{\n.reg .pred p;\nmbarrier.try_wait.parity.acquire.cluster.shared::cta.b64 p, [%1], 0;\nselp.u32 %0, 1, 0, p;\n}"
                 : "=r"(ok) : "r"(bar) : "memory");
    if (ok) return;
  }
  __trap();
}
__device__ __forceinline__ void st_async4(uint32_t a, uint32_t bar, uint32_t x, uint32_t y, uint32_t z, uint32_t w) {
  asm volatile("st.async.weak.shared::cluster.mbarrier::complete_tx::bytes.v4.b32 [%0], {%2,%3,%4,%5}, [%1];"
               ::"r"(a), "r"(bar), "r"(x), "r"(y), "r"(z), "r"(w) : "memory");
}

struct cf { float re, im; };
__device__ __forceinline__ cf cmul(cf a, cf b) { return {fmaf(a.re, b.re, -a.im * b.im), fmaf(a.re, b.im, a.im * b.re)}; }
__device__ __forceinline__ cf csq(cf a) { return {fmaf(a.re, a.re, -a.im * a.im), (a.re + a.re) * a.im}; }
__device__ __forceinline__ cf cexp_p(float xl, float y, float p) {
  float mag; asm("ex2.approx.ftz.f32 %0, %1;" : "=f"(mag) : "f"(xl * p));
  const float th = y * p;
  const float k = rintf(th * 0.15915494309189535f);
  float r = fmaf(k, -6.2831854820251465f, th);
  r = fmaf(k, 1.7484555314695172e-07f, r);
  return {mag * __cosf(r), mag * __sinf(r)};
}
__device__ __forceinline__ uint32_t ysw(int c) { return (uint32_t)(c ^ ((c >> 3) & 3)) * 16u; }

#define CMUL2(OR, OI, xr, xi, yr, yi, nyi) do { OR = hfma2(xr, yr, hmul2(xi, nyi)); OI = hfma2(xr, yi, hmul2(xi, yr)); } while (0)

__device__ __forceinline__ uint32_t gate_slow(const __nv_bfloat16* u, const __nv_bfloat16* gw, int row) {
  float s = 0.f;
  const uint32_t* xr = (const uint32_t*)(u + (size_t)row * D);
  const uint32_t* wr = (const uint32_t*)gw;
#pragma unroll 1
  for (int j = 0; j < D / 2; j++) { const uint32_t pr = hmul2(xr[j], wr[j]); s += bf_lo(pr); s += bf_hi(pr); }
  s = bf_round(s);
  return pack_bf16(1.f / (1.f + expf(-s)), 0.f);
}

__device__ __forceinline__ uint2 gate_ld(int x) {
  uint2 gv;
  asm volatile("ld.relaxed.gpu.global.v2.u32 {%0,%1}, [%2];" : "=r"(gv.x), "=r"(gv.y) : "l"(g_gate + x * 2) : "memory");
  return gv;
}
__device__ __noinline__ uint32_t gate_poll(const Params* pp, int x, uint32_t tag) {
  uint2 gv;
#pragma unroll 1
  for (int spins = 0; spins < (1 << 16); spins++) {
    gv = gate_ld(x);
    if ((gv.x >> 16) == tag && (gv.y >> 16) == tag) return __byte_perm(gv.x, gv.y, 0x5410);
  }
  return __byte_perm(gate_slow(pp->u, pp->gw, x * 2), gate_slow(pp->u, pp->gw, x * 2 + 1), 0x5410);
}
__device__ __forceinline__ uint32_t gate_fin(const Params& p, uint2 gv, int x, uint32_t tag) {
  if ((gv.x >> 16) == tag && (gv.y >> 16) == tag) return __byte_perm(gv.x, gv.y, 0x5410);
  return gate_poll(&p, x, tag);
}

__device__ __forceinline__ void ld4ch(uint32_t* v, uint32_t addr) {
#pragma unroll
  for (int k = 0; k < 4; k++) v[k] = lds32(addr + k * CH_BYTES);
}
__device__ __forceinline__ void skip_terms(uint32_t* ua, uint32_t* ub, uint32_t sb, int x, uint2 dA, uint2 dB) {
  const int c = x >> 2;
  uint32_t uu[4];
  ld4ch(uu, sb + CH_OFF + (x & 3) * 4 + U_OFF + (c & 3) * U_CS + (63 - (c >> 2)) * 16);
#pragma unroll
  for (int k = 0; k < 4; k++) {
    ua[k] = hmul2(uu[k], __byte_perm((k & 2) ? dA.y : dA.x, 0, (k & 1) ? 0x3232 : 0x1010));
    ub[k] = hmul2(uu[k], __byte_perm((k & 2) ? dB.y : dB.x, 0, (k & 1) ? 0x3232 : 0x1010));
  }
}
__device__ __forceinline__ uint4 mix(const uint32_t* a, const uint32_t* b, const uint32_t* ua, const uint32_t* ub, uint32_t g2) {
  const uint32_t h2 = hsub2(0x3f803f80u, g2);
  uint32_t o[4];
#pragma unroll
  for (int k = 0; k < 4; k++) o[k] = hadd2(hmul2(g2, hadd2(a[k], ua[k])), hmul2(h2, hadd2(b[k], ub[k])));
  return make_uint4(__byte_perm(o[0], o[1], 0x5410), __byte_perm(o[2], o[3], 0x5410), __byte_perm(o[0], o[1], 0x7632), __byte_perm(o[2], o[3], 0x7632));
}
__device__ __forceinline__ void send_box(uint32_t sb, int slot, int wtid, uint32_t rank, uint4 r) {
  st_async4(mapa(sb + XIN_OFF + slot * 2048 + wtid * 16, rank ^ 1), mapa(sb + B_X + slot * 8, rank ^ 1), r.x, r.y, r.z, r.w);
}
__device__ __forceinline__ void merge_box(uint32_t sb, const CUtensorMap* tm_out, int slot, int wtid, uint32_t rank, int oc0, uint4 r, int barid) {
  const uint32_t st = sb + RAW_OFF + slot * 4096 + wtid * 16;
  sts64(st + rank * 8, r.x, r.y); sts64(st + 2048 + rank * 8, r.z, r.w);
  mbar_wait(sb + B_X + slot * 8);
  const uint4 q = lds128(sb + XIN_OFF + slot * 2048 + wtid * 16);
  sts64(st + (rank ^ 1) * 8, q.x, q.y); sts64(st + 2048 + (rank ^ 1) * 8, q.z, q.w);
  fence_async();
  bar_sync(barid, 128);
  if (wtid == 0) {
    asm volatile("cp.async.bulk.tensor.3d.global.shared::cta.bulk_group [%0, {%2, %3, %4}], [%1];"
                 ::"l"(tm_out), "r"(sb + RAW_OFF + slot * 4096), "r"(oc0), "r"((2 * slot + (int)rank) * 128), "r"(0) : "memory");
    asm volatile("cp.async.bulk.commit_group;" ::: "memory");
  }
}

__device__ __forceinline__ uint32_t band2(int e, int lo, int hi) {
  uint32_t r = ((uint32_t)(e - lo) <= (uint32_t)(hi - lo) ? 0x3f80u : 0u) | ((uint32_t)(e - 1 - lo) <= (uint32_t)(hi - lo) ? 0x3f800000u : 0u);
  asm volatile("" : "+r"(r));
  return r;
}

__device__ __forceinline__ void stage_done(uint32_t sb, int stage, int lane) {
  __syncwarp();
  if (lane == 0) asm volatile("mbarrier.arrive.shared::cta.b64 _, [%0];" ::"r"(sb + B_ST + 8 * stage) : "memory");
}
#define PK2(v, i) pack_bf16(v[i], v[(i) + 1])

__device__ __noinline__ void gate_cta(const Params* pp) {
  const __nv_bfloat16 *u = pp->u, *gw = pp->gw;
  const int lane = threadIdx.x & 31;
  unsigned int epoch;
  asm volatile("ld.relaxed.gpu.global.u32 %0, [%1];" : "=r"(epoch) : "l"(&g_epoch) : "memory");
  const uint4 gw0 = ldg128(gw + lane * 8), gw1 = ldg128(gw + 256 + lane * 8);
  const uint32_t ws[8] = {gw0.x, gw0.y, gw0.z, gw0.w, gw1.x, gw1.y, gw1.z, gw1.w};
  const uint32_t tag = (epoch + 1) & 0xffffu;
  uint4 gx[4][2], nx[4][2];
  int grow = (blockIdx.x * 20 + (threadIdx.x >> 5)) * 4;
#pragma unroll
  for (int i = 0; i < 4; i++) {
    nx[i][0] = ldg128(u + (size_t)(grow + i) * D + lane * 8);
    nx[i][1] = ldg128(u + (size_t)(grow + i) * D + 256 + lane * 8);
  }
#pragma unroll 1
  for (; grow < L; grow += 80 * NGATE) {
    const int nrow = min(grow + 80 * NGATE, L - 4);
#pragma unroll
    for (int i = 0; i < 4; i++) {
      gx[i][0] = nx[i][0]; gx[i][1] = nx[i][1];
      nx[i][0] = ldg128(u + (size_t)(nrow + i) * D + lane * 8);
      nx[i][1] = ldg128(u + (size_t)(nrow + i) * D + 256 + lane * 8);
    }
    float c[2][4];
#pragma unroll
    for (int i = 0; i < 2; i++) {
      const uint4 *x = gx[2 * i], *y = gx[2 * i + 1];
      const uint32_t xs[8] = {x[0].x, x[0].y, x[0].z, x[0].w, x[1].x, x[1].y, x[1].z, x[1].w};
      const uint32_t ys[8] = {y[0].x, y[0].y, y[0].z, y[0].w, y[1].x, y[1].y, y[1].z, y[1].w};
      c[i][0] = c[i][1] = c[i][2] = c[i][3] = 0.f;
#pragma unroll
      for (int j = 0; j < 8; j += 2)
        mma16816(c[i], hmul2(xs[j], ws[j]), hmul2(ys[j], ws[j]), hmul2(xs[j + 1], ws[j + 1]), hmul2(ys[j + 1], ws[j + 1]), 0x3f803f80u, 0x3f803f80u);
    }
    float s = (lane & 2) ? ((lane & 1) ? c[1][2] : c[1][0]) : ((lane & 1) ? c[0][2] : c[0][0]);
#pragma unroll
    for (int o = 4; o < 32; o <<= 1) s += __shfl_xor_sync(0xffffffffu, s, o);
    s = bf_round(s);
    const float gv = 1.f / (1.f + expf(-s));
    const uint32_t w = (tag << 16) | (pack_bf16(gv, 0.f) & 0xffffu);
    if (lane < 4) asm volatile("st.relaxed.gpu.global.u32 [%0], %1;" ::"l"(&g_gate[grow + lane]), "r"(w) : "memory");
  }
  __syncthreads();
  if (threadIdx.x == 0 && atomicAdd(&g_ticket, 1u) == NCTA + NGATE - 1) { g_ticket = 0; g_epoch = epoch + 1; }
}

__global__ void __cluster_dims__(2, 1, 1) __launch_bounds__(640, 1)
ssm_kernel(const __grid_constant__ Params p, const __grid_constant__ CUtensorMap tm_in, const __grid_constant__ CUtensorMap tm_out) {
  extern __shared__ __align__(1024) unsigned char smem_raw[];
  const uint32_t sb = (uint32_t)__cvta_generic_to_shared(smem_raw);
  const int tid = threadIdx.x, lane = tid & 31;
  const int warp = __shfl_sync(0xffffffffu, tid >> 5, 0);
  const int ch = warp >> 2, wq = warp & 3, br = wq >> 1, hf = wq & 1;
  const int g = lane >> 2, t = lane & 3;
  if (__builtin_expect(blockIdx.x < NGATE, 0)) { gate_cta(&p); return; }
  const int bid = blockIdx.x - NGATE;
  const int d = bid * 4 + ch;
  const uint32_t rank = blockIdx.x & 1;
  const uint32_t cb = sb + CH_OFF + ch * CH_BYTES;
  const int wtid = tid & 127;
  const int oc0 = (bid >> 1) * 8;
  STAMP(0); GT(0);

  if (warp >= 16) {
    if (wtid == 0) {
      mbar_init_expect(sb + B_RAW, 32768);
#pragma unroll
      for (int i = 0; i < 4; i++) mbar_init_expect(sb + B_X + 8 * i, 2048);
      asm volatile("mbarrier.init.shared::cta.b64 [%0], 128;" ::"r"(sb + B_U) : "memory");
      asm volatile("mbarrier.init.shared::cta.b64 [%0], 128;" ::"r"(sb + B_W) : "memory");
#pragma unroll
      for (int i = 0; i < 5; i++) asm volatile("mbarrier.init.shared::cta.b64 [%0], 16;" ::"r"(sb + B_ST + 8 * i) : "memory");
      asm volatile("fence.mbarrier_init.release.cluster;" ::: "memory");
      asm volatile("fence.proxy.async.shared::cta;" ::: "memory");
    }
    __syncwarp();
    asm volatile("barrier.cluster.arrive.relaxed.aligned;" ::: "memory");
    unsigned int epoch;
    asm volatile("ld.relaxed.gpu.global.u32 %0, [%1];" : "=r"(epoch) : "l"(&g_epoch) : "memory");
    asm volatile("barrier.cluster.wait.aligned;" ::: "memory");
    if (wtid == 0) {
      asm volatile("cp.async.bulk.tensor.5d.shared::cluster.global.mbarrier::complete_tx::bytes.multicast::cluster [%0], [%1, {%3, %4, %4, %4, %5}], [%2], %6;"
                   ::"r"(sb + RAW_OFF + rank * 16384), "l"(&tm_in), "r"(sb + B_RAW), "r"(oc0), "r"(0), "r"((int)rank * 32), "h"((unsigned short)3) : "memory");
    }
    sts128(sb + CH_OFF + wq * CH_BYTES + U_OFF + (lane >> 3) * U_CS + (64 + (lane & 7)) * 16, 0, 0, 0, 0);
    const uint2 dA = ldg64(p.A_D + bid * 4), dB = ldg64(p.B_D + bid * 4);
    uint32_t BA[3][4], BC[3][4];
    {
      const int l1 = br ? 3 : 6, h1 = br ? 5 : 10;
#pragma unroll
      for (int i = 0; i < 3; i++) {
        const int e = 16 * hf + g - 2 * t + 16 - 16 * i;
        BA[i][0] = band2(e, l1, h1); BA[i][1] = band2(e + 8, l1, h1); BA[i][2] = band2(e - 8, l1, h1); BA[i][3] = BA[i][0];
        BC[i][0] = band2(e, 3, 4); BC[i][1] = band2(e + 8, 3, 4); BC[i][2] = band2(e - 8, 3, 4); BC[i][3] = BC[i][0];
      }
    }
    const uint32_t tag = (epoch + 1) & 0xffffu;
    if (wtid == 0) sts32(sb + TAG_OFF, tag);
    STAMP(3);
    mbar_wait(sb + B_RAW);
    STAMP(4);
    {
      const uint32_t dst = sb + CH_OFF + (g & 3) * CH_BYTES + U_OFF + t * U_CS + (63 - wq * 16) * 16;
#pragma unroll
      for (int h = 0; h < 2; h++) {
        uint32_t r[8][4];
#pragma unroll
        for (int i = 0; i < 8; i++) ldsm4t(sb + RAW_OFF + (wq * 16 + h * 8 + i) * 512 + lane * 16, r[i][0], r[i][1], r[i][2], r[i][3]);
        if ((uint32_t)(g >> 2) == rank) {
#pragma unroll
          for (int i = 0; i < 8; i++) sts128(dst - (h * 8 + i) * 16, r[i][0], r[i][1], r[i][2], r[i][3]);
        }
      }
    }
    fence_async();
    asm volatile("mbarrier.arrive.shared::cta.b64 _, [%0];" ::"r"(sb + B_U) : "memory");
    bar_sync(5, 128);
    STAMP(5);
    {
      const int mrow = lane & 7, mi = lane >> 3;
      const uint64_t ub0 = mkdesc(sb + CH_OFF + U_OFF, U_CS, 128);
      {
        float w1[24], w3[16];
#pragma unroll
        for (int i = 0; i < 24; i++) w1[i] = 0.f;
#pragma unroll
        for (int i = 0; i < 16; i++) w3[i] = 0.f;
        uint32_t wa[3], sa[2];
#pragma unroll
        for (int i = 0; i < 3; i++) {
          const int c = 4 * (47 - 8 * (2 * i + (mi >> 1)) - mrow) + 2 * hf + (mi & 1);
          wa[i] = sb + CH_OFF + (br ? W3_OFF : W5_OFF) + (5 - (c >> 5)) * 576 + ((c & 31) >> 3) * 144 + (c & 7) * 16;
          if (i) sa[i - 1] = sb + CH_OFF + S2_OFF + (c + (c >> 3)) * 16;
        }
#pragma unroll 1
        for (int k = 0; k < 4; k++) {
          wg_fence();
#pragma unroll
          for (int i = 0; i < 3; i++)
            wgmma_rs<48, 0>(w1, BA[i][0], BA[i][1], BA[i][2], BA[i][3],
                            ub0 + (uint64_t)((k * CH_BYTES + ((2 * i + 2) & 3) * U_CS + (16 + (i == 0)) * 16) >> 4), i);
#pragma unroll
          for (int i = 0; i < 3; i++)
            wgmma_rs<32, 0>(w3, BC[i][0], BC[i][1], BC[i][2], BC[i][3],
                            ub0 + (uint64_t)((k * CH_BYTES + ((2 * i + 2) & 3) * U_CS + (32 + (i == 0)) * 16) >> 4), i);
          wg_commit();
          wg_wait0();
#pragma unroll
          for (int i = 0; i < 3; i++)
            stsm4t(wa[i] + k * CH_BYTES, pack_bf16(w1[8 * i], w1[8 * i + 1]), pack_bf16(w1[8 * i + 2], w1[8 * i + 3]),
                   pack_bf16(w1[8 * i + 4], w1[8 * i + 5]), pack_bf16(w1[8 * i + 6], w1[8 * i + 7]));
          if (br == 0) {
#pragma unroll
            for (int i = 0; i < 2; i++)
              stsm4t(sa[i] + k * CH_BYTES, pack_bf16(w3[8 * i], w3[8 * i + 1]), pack_bf16(w3[8 * i + 2], w3[8 * i + 3]),
                     pack_bf16(w3[8 * i + 4], w3[8 * i + 5]), pack_bf16(w3[8 * i + 6], w3[8 * i + 7]));
          }
        }
      }
      {
        uint32_t BB[4][4];
        const int l2 = br ? 5 : 12, h2 = br ? 11 : 20;
#pragma unroll
        for (int i = 0; i < 4; i++) {
          const int e = 16 * hf + g - 2 * t + 32 - 16 * i;
          BB[i][0] = band2(e, l2, h2); BB[i][1] = band2(e + 8, l2, h2); BB[i][2] = band2(e - 8, l2, h2); BB[i][3] = BB[i][0];
        }
        float w2[2][16];
#pragma unroll
        for (int i = 0; i < 16; i++) { w2[0][i] = 0.f; w2[1][i] = 0.f; }
        uint32_t wa[2];
#pragma unroll
        for (int i = 0; i < 2; i++) {
          const int c = 4 * (31 - 8 * (2 * i + (mi >> 1)) - mrow) + 2 * hf + (mi & 1), pp = c >> 1;
          wa[i] = sb + CH_OFF + (br ? W7_OFF : W9_OFF) + (1 - (pp >> 5)) * 1152 + (c & 1) * 576 + ((pp & 31) >> 3) * 144 + (pp & 7) * 16;
        }
#pragma unroll 1
        for (int kp = 0; kp < 2; kp++) {
          wg_fence();
#pragma unroll
          for (int k = 0; k < 2; k++)
#pragma unroll
            for (int i = 0; i < 4; i++)
              wgmma_rs<32, 0>(w2[k], BB[i][0], BB[i][1], BB[i][2], BB[i][3],
                              ub0 + (uint64_t)(((2 * kp + k) * CH_BYTES + ((2 * i) & 3) * U_CS + (32 + (i < 2)) * 16) >> 4), i);
          wg_commit();
          wg_wait0();
#pragma unroll
          for (int k = 0; k < 2; k++)
#pragma unroll
            for (int i = 0; i < 2; i++)
              stsm4t(wa[i] + (2 * kp + k) * CH_BYTES, pack_bf16(w2[k][8 * i], w2[k][8 * i + 1]), pack_bf16(w2[k][8 * i + 2], w2[k][8 * i + 3]),
                     pack_bf16(w2[k][8 * i + 4], w2[k][8 * i + 5]), pack_bf16(w2[k][8 * i + 6], w2[k][8 * i + 7]));
        }
      }
    }
    fence_async();
    asm volatile("mbarrier.arrive.shared::cta.b64 _, [%0];" ::"r"(sb + B_W) : "memory");
    STAMP(7);
    {
      const int bsel = (int)rank ^ br ^ 1, xl = wtid & 63;
      uint2 gl[4];
      uint32_t ua[4][4], ub[4][4];
#pragma unroll
      for (int i = 0; i < 4; i++) gl[i] = gate_ld((2 * (i >> 1) + bsel) * 128 + (i & 1) * 64 + xl);
#pragma unroll
      for (int i = 0; i < 4; i++) skip_terms(ua[i], ub[i], sb, (2 * (i >> 1) + bsel) * 128 + (i & 1) * 64 + xl, dA, dB);
      const uint32_t yo = sb + CH_OFF + (xl & 3) * 4 + ysw(xl >> 2) + bsel * 512;
#pragma unroll
      for (int slot = 0; slot < 2; slot++) {
        const int box = 2 * slot + bsel;
        uint32_t g2[2], ya[2][4], yb[2][4];
#pragma unroll
        for (int h = 0; h < 2; h++) g2[h] = gate_fin(p, gl[2 * slot + h], box * 128 + h * 64 + xl, tag);
        mbar_wait(sb + B_ST + 8 * box);
        STAMP(8 + slot);
#pragma unroll
        for (int h = 0; h < 2; h++) {
          const uint32_t yh = (yo ^ (h * 32)) + h * 256 + slot * 1024;
          ld4ch(ya[h], yh + Y0_OFF); ld4ch(yb[h], yh + Y0_OFF + 4096);
          if (slot) {
            uint32_t a2[4], b2[4];
            ld4ch(a2, yh + Y2_OFF - 1024); ld4ch(b2, yh + Y2_OFF - 1024 + 3072);
#pragma unroll
            for (int k = 0; k < 4; k++) { ya[h][k] = hadd2(ya[h][k], a2[k]); yb[h][k] = hadd2(yb[h][k], b2[k]); }
          }
        }
        const uint4 r0 = mix(ya[0], yb[0], ua[2 * slot], ub[2 * slot], g2[0]), r1 = mix(ya[1], yb[1], ua[2 * slot + 1], ub[2 * slot + 1], g2[1]);
        if (br == 0) { send_box(sb, slot, xl, rank, r0); send_box(sb, slot, xl + 64, rank, r1); }
        else {
          const uint32_t st = sb + RAW_OFF + slot * 4096 + xl * 16, xin = sb + XIN_OFF + slot * 2048 + xl * 16;
          sts64(st + rank * 8, r0.x, r0.y); sts64(st + 2048 + rank * 8, r0.z, r0.w);
          sts64(st + 1024 + rank * 8, r1.x, r1.y); sts64(st + 3072 + rank * 8, r1.z, r1.w);
          mbar_wait(sb + B_X + slot * 8);
          const uint4 q0 = lds128(xin), q1 = lds128(xin + 1024);
          sts64(st + (rank ^ 1) * 8, q0.x, q0.y); sts64(st + 2048 + (rank ^ 1) * 8, q0.z, q0.w);
          sts64(st + 1024 + (rank ^ 1) * 8, q1.x, q1.y); sts64(st + 3072 + (rank ^ 1) * 8, q1.z, q1.w);
          fence_async();
          bar_sync(6, 64);
          if (xl == 0) {
            asm volatile("cp.async.bulk.tensor.3d.global.shared::cta.bulk_group [%0, {%2, %3, %4}], [%1];"
                         ::"l"(&tm_out), "r"(sb + RAW_OFF + slot * 4096), "r"(oc0), "r"(box * 128), "r"(0) : "memory");
            asm volatile("cp.async.bulk.commit_group;" ::: "memory");
          }
        }
        STAMP(10 + slot);
      }
    }
    if (wtid == 0 && atomicAdd(&g_ticket, 1u) == NCTA + NGATE - 1) { g_ticket = 0; g_epoch = epoch + 1; }
    if (wtid == 64) asm volatile("cp.async.bulk.wait_group.read 0;" ::: "memory");
    STAMP(15);
    return;
  }
  asm volatile("barrier.cluster.arrive.relaxed.aligned;" ::: "memory");

  const int moff = (bid * 4 + (tid >> 7)) * NM + (tid & 63) * 2;
  const int brt = (tid >> 6) & 1;
  const __nv_bfloat16* const* tp = p.t + (brt ? 0 : 6);
  const uint32_t q0 = *(const uint32_t*)(tp[0] + moff), q1 = *(const uint32_t*)(tp[1] + moff);
  const uint32_t q2 = *(const uint32_t*)(tp[2] + moff), q3 = *(const uint32_t*)(tp[3] + moff);
  const uint2 ldt4 = *(const uint2*)(tp[4] + bid * 4);
  const uint32_t q4 = *(const uint32_t*)(tp[brt ? 2 : 5] + moff), q5 = *(const uint32_t*)(tp[brt ? 3 : 6] + moff);

  for (int i = wtid & 63; i < R_BR / 16; i += 64) sts128(cb + R_OFF + br * R_BR + i * 16, 0, 0, 0, 0);
  STAMP(1);

  float acc[5][4];
  float k2048 = 0.f;
  const uint32_t scr = cb + Y0_OFF + wq * SCR_BYTES;
  const uint32_t scr2 = sb + XIN_OFF + warp * 640;
  {
    const uint32_t ldt2 = (ch & 2) ? ldt4.y : ldt4.x;
    const float dt = bf_round(expf((ch & 1) ? bf_hi(ldt2) : bf_lo(ldt2)));
#pragma unroll
    for (int i = 0; i < 5; i++) acc[i][0] = acc[i][1] = acc[i][2] = acc[i][3] = 0.f;
    cf cc[2], zz1[2], zz128[2];
#pragma unroll
    for (int r = 0; r < 2; r++) {
      float v0 = r ? bf_hi(q0) : bf_lo(q0), v1 = r ? bf_hi(q1) : bf_lo(q1), v2 = r ? bf_hi(q2) : bf_lo(q2);
      float v3 = r ? bf_hi(q3) : bf_lo(q3), v4 = r ? bf_hi(q4) : bf_lo(q4), v5 = r ? bf_hi(q5) : bf_lo(q5);
      if (br == 0) { cc[r] = cmul(cf{v2, v3}, cf{dt * v4, dt * v5}); }
      else { v0 = -bf_round(expf(v0)); cc[r] = cf{2.f * dt * v2, 2.f * dt * v3}; }
      const float xl = (dt * v0) * 1.4426950408889634f, y = dt * v1;
      zz1[r] = cexp_p(xl, y, 1.f); zz128[r] = cexp_p(xl, y, 128.f);
    }
    STAMP(2);
    const uint32_t tb = scr + lane * 16;
    const uint32_t ta = scr + (lane >> 3) * 512 + (lane & 7) * 16;
    const uint32_t tc = ((lane & 8) ? scr2 : scr + 4096) + (lane >> 4) * 128 + (lane & 7) * 16;
    const uint32_t tm = scr2 + 512 + ((lane >> 3) & 1) * 64 + (lane >> 4) * 16;
#pragma unroll 1
    for (int r = 0; r < 2; r++) {
      const cf c = r ? cc[1] : cc[0], z1 = r ? zz1[1] : zz1[0], z128 = r ? zz128[1] : zz128[0];
      const cf z2 = csq(z1), z4 = csq(z2), z8 = csq(z4);
      const cf z16 = csq(z8), z24 = cmul(z16, z8), z32 = csq(z16), z40 = cmul(z32, z8), z48 = csq(z24), z56 = cmul(z32, z24), z64 = csq(z32);
      const cf z256 = csq(z128), z512 = csq(z256), z1024 = csq(z512), z2048 = csq(z1024);
      {
        float kk = fmaf(c.re, z2048.re, -c.im * z2048.im);
#pragma unroll
        for (int o = 16; o; o >>= 1) kk += __shfl_xor_sync(0xffffffffu, kk, o);
        k2048 += kk;
      }
      __syncwarp();
      {
        uint32_t xr[4] = {pack_bf16(1.f, z8.re), pack_bf16(z16.re, z24.re), pack_bf16(z32.re, z40.re), pack_bf16(z48.re, z56.re)};
        uint32_t xi[4] = {pack_bf16(0.f, -z8.im), pack_bf16(-z16.im, -z24.im), pack_bf16(-z32.im, -z40.im), pack_bf16(-z48.im, -z56.im)};
        sts128(tb + 0 * 512, xr[0], xr[1], xr[2], xr[3]);
        sts128(tb + 2 * 512, xi[0], xi[1], xi[2], xi[3]);
        const uint32_t yr = pack_bf16(z64.re, z64.re), nyi = pack_bf16(z64.im, z64.im), yi = nyi ^ 0x80008000u;
        uint32_t o[4], q[4];
#pragma unroll
        for (int i = 0; i < 4; i++) CMUL2(o[i], q[i], xr[i], xi[i], yr, yi, nyi);
        sts128(tb + 1 * 512, o[0], o[1], o[2], o[3]);
        sts128(tb + 3 * 512, q[0], q[1], q[2], q[3]);
      }
      {
        const cf h1 = cmul(c, z128), h2 = cmul(c, z256), h3 = cmul(h1, z256), h4 = cmul(c, z512), h5 = cmul(h1, z512), h6 = cmul(h2, z512), h7 = cmul(h3, z512);
        const cf e1 = cmul(c, z1), e2 = cmul(c, z2), e3 = cmul(e1, z2), e129 = cmul(h1, z1), e130 = cmul(h1, z2), e131 = cmul(e129, z2);
        const cf e258 = cmul(h2, z2), e386 = cmul(h3, z2);
        const uint32_t pr0 = pack_bf16(c.re, e1.re), pr2 = pack_bf16(h1.re, e129.re), pi0 = pack_bf16(c.im, e1.im), pi2 = pack_bf16(h1.im, e129.im);
        sts128(tb + 4 * 512, pr0, pack_bf16(e2.re, e3.re), pr2, pack_bf16(e130.re, e131.re));
        sts128(tb + 5 * 512, pi0, pack_bf16(e2.im, e3.im), pi2, pack_bf16(e130.im, e131.im));
        uint32_t xr[4] = {pack_bf16(h2.re, e258.re), pack_bf16(h3.re, e386.re), pack_bf16(h4.re, h5.re), pack_bf16(h6.re, h7.re)};
        uint32_t xi[4] = {pack_bf16(h2.im, e258.im), pack_bf16(h3.im, e386.im), pack_bf16(h4.im, h5.im), pack_bf16(h6.im, h7.im)};
        sts128(tb + 6 * 512, xr[0], xr[1], xr[2], xr[3]);
        sts128(tb + 7 * 512, xi[0], xi[1], xi[2], xi[3]);
        xr[1] = __byte_perm(xr[0], xr[1], 0x5410); xi[1] = __byte_perm(xi[0], xi[1], 0x5410);
        xr[0] = __byte_perm(pr0, pr2, 0x5410); xi[0] = __byte_perm(pi0, pi2, 0x5410);
        const uint32_t yr = pack_bf16(z1024.re, z1024.re), yi = pack_bf16(z1024.im, z1024.im), nyi = yi ^ 0x80008000u;
        uint32_t o[4], q[4];
#pragma unroll
        for (int i = 0; i < 4; i++) CMUL2(o[i], q[i], xr[i], xi[i], yr, yi, nyi);
        sts128(tb + 8 * 512, o[0], o[1], o[2], o[3]);
        sts128(scr2 + lane * 16, q[0], q[1], q[2], q[3]);
        const uint32_t m4 = pack_bf16(z4.re, z4.im);
        sts16(scr2 + 512 + lane * 2, m4); sts16(scr2 + 576 + lane * 2, m4 >> 16);
      }
      __syncwarp();
#pragma unroll
      for (int kp = 0; kp < 2; kp++) {
        uint32_t rr[2], ri[2], yr[2], yi[2];
        ldsm4t(tc + kp * 256, rr[0], ri[0], rr[1], ri[1]);
        ldsm4(tm + kp * 32, yr[0], yi[0], yr[1], yi[1]);
#pragma unroll
        for (int k2 = 0; k2 < 2; k2++) {
          const int kk = kp * 2 + k2;
          uint32_t a0, a1, a2, a3, pr, pi, qr, qi, xr, xi;
          ldsm4t(ta + kk * 128, a0, a1, a2, a3);
          ldsm4t(ta + 2048 + kk * 128, pr, pi, qr, qi);
          const uint32_t nyi = yi[k2] ^ 0x80008000u;
          mma16816(acc[0], a0, a1, a2, a3, pr, pi);
          mma16816(acc[2], a0, a1, a2, a3, qr, qi);
          mma16816(acc[4], a0, a1, a2, a3, rr[k2], ri[k2]);
          CMUL2(xr, xi, pr, pi, yr[k2], yi[k2], nyi);
          mma16816(acc[1], a0, a1, a2, a3, xr, xi);
          CMUL2(xr, xi, qr, qi, yr[k2], yi[k2], nyi);
          mma16816(acc[3], a0, a1, a2, a3, xr, xi);
        }
      }
    }
  }
  STAMP(3);
  __syncwarp();
  {
    const uint32_t xs = scr + lane * 16;
#define OTH(i, k) __float_as_uint(hf ? acc[i][k] : acc[i][2 + (k)])
    sts128(xs, OTH(0, 0), OTH(0, 1), OTH(1, 0), OTH(1, 1));
    sts128(xs + 512, OTH(2, 0), OTH(2, 1), OTH(3, 0), OTH(3, 1));
    sts128(xs + 1024, OTH(4, 0), OTH(4, 1), __float_as_uint(k2048), 0);
#undef OTH
  }

  bar_sync(7 + (warp >> 1), 64);
  STAMP(4);
  {
    const uint32_t xo = cb + Y0_OFF + (wq ^ 1) * SCR_BYTES + lane * 16;
    const uint4 o0 = lds128(xo), o1 = lds128(xo + 512), o2 = lds128(xo + 1024);
    const uint32_t rb = cb + R_OFF + br * R_BR;
#define OWN(i, k) (hf ? acc[i][2 + (k)] : acc[i][k])
    const uint32_t vP = pack_bf16(OWN(0, 1) + __uint_as_float(o0.y), OWN(0, 0) + __uint_as_float(o0.x));
    const uint32_t vP4 = pack_bf16(OWN(1, 1) + __uint_as_float(o0.w), OWN(1, 0) + __uint_as_float(o0.z));
    const uint32_t vQ = pack_bf16(OWN(2, 1) + __uint_as_float(o1.y), OWN(2, 0) + __uint_as_float(o1.x));
    const uint32_t vQ4 = pack_bf16(OWN(3, 1) + __uint_as_float(o1.w), OWN(3, 0) + __uint_as_float(o1.z));
    const uint32_t vR = pack_bf16(OWN(4, 1) + __uint_as_float(o2.y), OWN(4, 0) + __uint_as_float(o2.x));
#undef OWN
    const int j = g + 8 * hf;
    {
      const int a = 2 * (t & 1) + 64 * (t & 2) + 8 * j;
      const uint32_t ad = rb + 2 * (RD_X0 - 1 - a);
      const uint32_t a1 = (t & 2) ? ad - 8 : ad, a2 = (t & 2) ? ad : ad - 8;
      const uint32_t w1 = (t & 2) ? vP4 : vP, w2 = (t & 2) ? vP : vP4;
      sts32(a1, w1); sts32(a2, w2);
      sts16(a1 + RD_CS + 2, w1); sts16(a1 + RD_CS + 4, w1 >> 16);
      sts16(a2 + RD_CS + 2, w2); sts16(a2 + RD_CS + 4, w2 >> 16);
    }
    if (t < 2) {
      const int b = 256 + 128 * t + 8 * j;
      const uint32_t ad = rb + 2 * (RD_X0 - 6 - b);
      const uint32_t v22 = __byte_perm(vQ4, 0, 0x3232), v00 = __byte_perm(vQ, 0, 0x3232);
      sts16(ad, vQ4);
      sts64(ad + 2, v22, __byte_perm(vQ4, vQ, 0x5432));
      sts32(ad + 10, v00);
      if (b != 256) { sts16(ad + 14, v00); sts128(ad + RD_CS + 2, vQ4, v22, vQ, v00); }
      else { sts64(ad + RD_CS + 2, vQ4, v22); sts32(ad + RD_CS + 10, vQ); sts16(ad + RD_CS + 14, v00); }
    } else {
      const uint32_t ao = rb + R_O2 + 2 * (159 - (32 * t + j)), ae = ao - (R_O2 - R_E2) + 2;
      sts16(ao, vQ4 >> 16); sts16(ao + RS_CS + 2, vQ4 >> 16); sts16(ao - 32, vQ4); sts16(ao - 32 + RS_CS + 2, vQ4);
      sts16(ae - 32, vQ); sts16(ae - 32 + RS_CS + 2, vQ);
      if (lane != 2 || hf) { sts16(ae, vQ >> 16); sts16(ae + RS_CS + 2, vQ >> 16); }
      else {
        const uint32_t vv = __byte_perm(vQ, 0, 0x3232), ad = rb + 2 * (RD_X0 - 514);
        sts16(ad, vv); sts32(ad + 2, vv); sts16(ad + 6, vv); sts64(ad + RD_CS + 2, vv, vv);
      }
    }
    {
      const uint32_t a = rb + ((g & 1) ? R_O3 : R_E3 + 2) + 2 * (159 - (64 + 16 * t + (j >> 1)));
      const bool p1024 = (lane == 0) && (hf == 0);
      const uint32_t a00 = p1024 ? rb + R_E2 + 2 * (159 - 127) : a;
      sts16(a00, vR >> 16); sts16(a00 + RS_CS + 2, vR >> 16);
      sts16(a - 16, vR); sts16(a - 16 + RS_CS + 2, vR);
      if (p1024) {
        sts32(sb + K1024_OFF + (ch * 2 + br) * 4, __byte_perm(vR, 0, 0x3232));
        const uint32_t kv = pack_bf16(k2048 + __uint_as_float(o2.z), 0.f);
        sts16(rb + R_E3 + 2 * (159 - 127), kv); sts16(rb + R_E3 + 2 * (159 - 127) + RS_CS + 2, kv);
      }
    }
  }
  STAMP(5);
  asm volatile("barrier.cluster.wait.aligned;" ::: "memory");
  bar_sync(7 + (warp >> 1), 64);
  mbar_wait(sb + B_U);
  STAMP(6);

  const uint32_t zz = lds32(cb + R_OFF + br * R_BR);
  {
    const int x = (4 + ch) * 128 + wtid, c = x >> 2;
    const uint32_t rb = cb + R_OFF + br * R_BR;
    const int eo = 16 * hf + g - 2 * t;
    uint32_t A[2][4][4];
    float e64[32], e56[28], e48[24], f48[24], f40[20], f32[16], h32[16], h16[8];
    const int x0 = RD_X0 - (eo + 536);
    const uint32_t fa = rb + ((g & 1) ? 2 * x0 : RD_CS + 2 * x0 + 2);
    const uint64_t ud = mkdesc(cb + U_OFF, U_CS, 128);
    const uint32_t yd = cb + Y0_OFF + br * 4096 + ysw(4 * (63 - 8 * (lane >> 4) - (lane & 7)) + 2 * hf + ((lane >> 3) & 1));
    auto loadD = [&](int j) {
#pragma unroll
      for (int k = 0; k < 4; k++) {
        const int s = 34 - 4 * j - k;
        if (s >= 0) {
          if (k == 0 && j == 0) A[0][0][2] = lds32(fa + (2 * s + 2) * 16);
          A[j & 1][k][0] = lds32(fa + (2 * s + 1) * 16);
          A[j & 1][k][1] = lds32(fa + (2 * s) * 16);
        }
      }
#pragma unroll
      for (int k = 0; k < 4; k++) {
        if (34 - 4 * j - k >= 0) {
          A[j & 1][k][3] = A[j & 1][k][0];
          if (k) A[j & 1][k][2] = A[j & 1][k - 1][1];
          else if (j) A[j & 1][0][2] = A[(j - 1) & 1][3][1];
        }
      }
    };
    const int x1 = 159 - (eo + 136);
    const uint32_t fs = rb + ((g & 1) ? 2 * x1 : RS_CS + 2 * x1 + 2);
    auto loadA = [&](int buf, uint32_t oe, uint32_t oo, int i0) {
#pragma unroll
      for (int a = 0; a < 2; a++) {
        const uint32_t base = fs + (a ? oo : oe) + i0 * 16;
        uint32_t* k0 = A[buf][2 * a];
        uint32_t* k1 = A[buf][2 * a + 1];
        k0[1] = lds32(base); k0[0] = lds32(base + 16); k0[2] = lds32(base + 32); k1[0] = lds32(base + 48); k1[2] = lds32(base + 64);
        k0[3] = k0[0]; k1[1] = k0[2]; k1[3] = k1[0];
      }
    };
    loadD(0); loadD(1);
#pragma unroll
    for (int j = 0; j < 9; j++) {
      if (j == 4) {
        wg_wait0();
        stsm2t(yd - 7 * 512, PK2(e64, 28), PK2(e64, 30));
#pragma unroll
        for (int i = 0; i < 28; i++) e56[i] = FCPY(e64[i]);
        stage_done(sb, 0, lane);
      }
      if (j == 8) {
        wg_wait0();
        loadA(1, R_E3, R_O3, 8);
        stsm2t(yd - 6 * 512, PK2(e56, 24), PK2(e56, 26));
#pragma unroll
        for (int i = 0; i < 24; i++) e48[i] = FCPY(e56[i]);
        stage_done(sb, 1, lane);
      }
      wg_fence();
#pragma unroll
      for (int k = 0; k < 4; k++) {
        const int s = 34 - 4 * j - k;
        if (s >= 0) {
          const int o = 2 * s - 66 + 128;
          const int cc = o & 3, rs = (o >> 2) - 32;
          const uint64_t desc = ud + (uint64_t)((cc * U_CS - rs * 16) >> 4);
          const uint32_t* a = A[j & 1][k];
          if (j < 4) wgmma_rs<64, 0>(e64, a[0], a[1], a[2], a[3], desc, s != 34);
          else if (j < 8) wgmma_rs<56, 0>(e56, a[0], a[1], a[2], a[3], desc, 1);
          else wgmma_rs<48, 0>(e48, a[0], a[1], a[2], a[3], desc, 1);
        }
      }
      wg_commit();
      if (j >= 1 && j < 8) { wg_wait1(); loadD(j + 1); }
      if (j == 6) mbar_wait(sb + B_W);
    }
    const uint64_t d5 = mkdesc(cb + W5_OFF, 144, 576), d3 = mkdesc(cb + W3_OFF, 144, 576);
    const uint64_t d9 = mkdesc(cb + W9_OFF, 144, 576), d7 = mkdesc(cb + W7_OFF, 144, 576);
    const uint32_t y2d = cb + Y2_OFF + br * 3072 + ysw(32 * (5 - (lane >> 4)) + 16 * hf + (lane & 15));
    const uint32_t y3d = cb + Y3_OFF + br * 2048 + ysw(2 * (16 * hf + (lane & 15)) + (lane >> 4));
#define FAR4(N, ACC, BUF, DA, DB, OFF, FIRST)                                                            \
    wg_fence();                                                                                           \
    _Pragma("unroll") for (int k = 0; k < 4; k++) {                                                      \
      const uint32_t* a = A[BUF][k];                                                                      \
      wgmma_rs<N, 1>(ACC, a[0], a[1], a[2], a[3], ((k >> 1) ? DB : DA) + (k & 1) * 18 + (OFF), !(FIRST) || k); \
    }                                                                                                     \
    wg_commit();
    FAR4(32, h32, 1, d9, d7, 0, 1)
    wg_wait1();
    loadA(0, R_E2, R_O2, 8);
#pragma unroll
    for (int i = 0; i < 6; i += 2) stsm4t(yd - i * 512, PK2(e48, 4 * i), PK2(e48, 4 * i + 2), PK2(e48, 4 * i + 4), PK2(e48, 4 * i + 6));
    STAMP(8);
    wg_wait0();
    loadA(1, R_E3, R_O3, 4);
    stsm4(y3d, PK2(h32, 8), PK2(h32, 10), PK2(h32, 12), PK2(h32, 14));
#pragma unroll
    for (int i = 0; i < 8; i++) h16[i] = FCPY(h32[i]);
    FAR4(48, f48, 0, d5, d3, 0, 1)
    FAR4(16, h16, 1, d9, d7, 72, 0)
    wg_wait1();
    loadA(0, R_E2, R_O2, 4);
    stsm2(y2d - 5 * 512, PK2(f48, 20), PK2(f48, 22));
#pragma unroll
    for (int i = 0; i < 20; i++) f40[i] = FCPY(f48[i]);
    stage_done(sb, 2, lane);
    FAR4(40, f40, 0, d5, d3, 36, 0)
    wg_wait1();
    loadA(1, R_E2, R_O2, 0);
    stsm4(y3d + 1024, PK2(h16, 0), PK2(h16, 2), PK2(h16, 4), PK2(h16, 6));
    const uint2 dA = ldg64(p.A_D + bid * 4), dB = ldg64(p.B_D + bid * 4);
    const uint2 gl = gate_ld(x);
    wg_wait0();
    stsm2(y2d - 4 * 512, PK2(f40, 16), PK2(f40, 18));
#pragma unroll
    for (int i = 0; i < 16; i++) f32[i] = FCPY(f40[i]);
    stage_done(sb, 3, lane);
    STAMP(9);
    FAR4(32, f32, 1, d5, d3, 72, 0)
#undef FAR4
    const uint32_t yo = sb + CH_OFF + (x & 3) * 4 + ysw(c);
    uint32_t ua[4], ub[4], ya[4], yb[4], a2[4], b2[4], a3[4], b3[4], s2[4];
    skip_terms(ua, ub, sb, x, dA, dB);
    ld4ch(s2, sb + CH_OFF + (x & 3) * 4 + S2_OFF + ((c - 128) + ((c - 128) >> 3)) * 16);
    const uint32_t tag = lds32(sb + TAG_OFF);
    wg_wait0();
    stsm4(y2d, PK2(f32, 0), PK2(f32, 2), PK2(f32, 4), PK2(f32, 6));
    stsm4(y2d - 2 * 512, PK2(f32, 8), PK2(f32, 10), PK2(f32, 12), PK2(f32, 14));
    stage_done(sb, 4, lane);
    STAMP(10);
    const uint32_t g2 = gate_fin(p, gl, x, tag);
    mbar_wait(sb + B_ST + 8 * 3);
    const uint4 k0 = lds128(sb + K1024_OFF), k1 = lds128(sb + K1024_OFF + 16);
    const uint32_t kk[8] = {k0.x, k0.y, k0.z, k0.w, k1.x, k1.y, k1.z, k1.w};
    ld4ch(ya, yo + Y0_OFF); ld4ch(yb, yo + Y0_OFF + 4096);
    ld4ch(a3, yo + Y3_OFF - 2048); ld4ch(b3, yo + Y3_OFF - 2048 + 2048);
    mbar_wait(sb + B_ST + 8 * 4);
    STAMP(12);
    ld4ch(a2, yo + Y2_OFF - 1024); ld4ch(b2, yo + Y2_OFF - 1024 + 3072);
#pragma unroll
    for (int k = 0; k < 4; k++) {
      ya[k] = hadd2(ya[k], hadd2(hfma2(kk[2 * k], s2[k], a3[k]), a2[k]));
      yb[k] = hadd2(yb[k], hadd2(hfma2(kk[2 * k + 1], s2[k], b3[k]), b2[k]));
    }
    const uint4 r = mix(ya, yb, ua, ub, g2);
    if ((uint32_t)(ch & 1) != rank) send_box(sb, 2 + (ch >> 1), wtid, rank, r);
    else merge_box(sb, &tm_out, 2 + (ch >> 1), wtid, rank, oc0, r, 1 + ch);
  }
  STAMP(14);
  if (wtid == 0) asm volatile("cp.async.bulk.wait_group.read 0;" ::: "memory");
  STAMP(15); GT(1);
}

typedef CUresult (*EncodeFn)(CUtensorMap*, CUtensorMapDataType, cuuint32_t, void*, const cuuint64_t*, const cuuint64_t*,
                             const cuuint32_t*, const cuuint32_t*, CUtensorMapInterleave, CUtensorMapSwizzle,
                             CUtensorMapL2promotion, CUtensorMapFloatOOBfill);

}

extern "C" void kernel_launch(void* const* d_in, const int* in_sizes, int n_in, void* d_out, int out_size) {
  (void)in_sizes; (void)n_in; (void)out_size;
  typedef const __nv_bfloat16* bp;
  Params p;
  p.t[0] = (bp)d_in[10]; p.t[1] = (bp)d_in[11]; p.t[2] = (bp)d_in[12]; p.t[3] = (bp)d_in[13]; p.t[4] = (bp)d_in[14]; p.t[5] = nullptr;
  p.t[6] = (bp)d_in[1]; p.t[7] = (bp)d_in[2]; p.t[8] = (bp)d_in[5]; p.t[9] = (bp)d_in[6]; p.t[10] = (bp)d_in[7];
  p.t[11] = (bp)d_in[3]; p.t[12] = (bp)d_in[4]; p.t[13] = nullptr;
  p.u = (bp)d_in[0]; p.gw = (bp)d_in[16]; p.A_D = (bp)d_in[8]; p.B_D = (bp)d_in[15];
  static EncodeFn enc = nullptr;
  if (!enc) {
    cudaDriverEntryPointQueryResult qr;
    cudaGetDriverEntryPoint("cuTensorMapEncodeTiled", (void**)&enc, cudaEnableDefault, &qr);
    cudaFuncSetAttribute(ssm_kernel, cudaFuncAttributeMaxDynamicSharedMemorySize, SMEM_BYTES);
  }
  CUtensorMap tm_in, tm_out;
  {
    cuuint64_t gd[5] = {512, 2, 4, 4, 64};
    cuuint64_t gs[4] = {1024, 8192, 2048, 32768};
    cuuint32_t bx[5] = {8, 2, 4, 4, 32};
    cuuint32_t es[5] = {1, 1, 1, 1, 1};
    enc(&tm_in, CU_TENSOR_MAP_DATA_TYPE_BFLOAT16, 5, d_in[0], gd, gs, bx, es, CU_TENSOR_MAP_INTERLEAVE_NONE,
        CU_TENSOR_MAP_SWIZZLE_NONE, CU_TENSOR_MAP_L2_PROMOTION_NONE, CU_TENSOR_MAP_FLOAT_OOB_FILL_NONE);
  }
  {
    cuuint64_t gd[3] = {512, 1024, 2};
    cuuint64_t gs[2] = {2048, 1024};
    cuuint32_t bx[3] = {8, 128, 2};
    cuuint32_t es[3] = {1, 1, 1};
    enc(&tm_out, CU_TENSOR_MAP_DATA_TYPE_BFLOAT16, 3, d_out, gd, gs, bx, es, CU_TENSOR_MAP_INTERLEAVE_NONE,
        CU_TENSOR_MAP_SWIZZLE_NONE, CU_TENSOR_MAP_L2_PROMOTION_NONE, CU_TENSOR_MAP_FLOAT_OOB_FILL_NONE);
  }
  ssm_kernel<<<NCTA + NGATE, 640, SMEM_BYTES, cudaStreamPerThread>>>(p, tm_in, tm_out);
}
```

```cpp
#include <cuda_runtime.h>
#include <cuda.h>
#include <cuda_bf16.h>
#include <stdint.h>

namespace {
#define FCPY(x) __uint_as_float(opq(__float_as_uint(x), zz))

constexpr int L = 2048, D = 512, NM = 128;
constexpr int NCTA = 128;
constexpr int NGATE = 4;

constexpr int RAW_OFF = 0;
constexpr int XIN_OFF = 32768;
constexpr int BAR_OFF = XIN_OFF + 10240;
constexpr int CH_OFF = BAR_OFF + 256;
constexpr int U_CS = 1184;
constexpr int U_OFF = 0;
constexpr int R_OFF = 4736;
constexpr int RD_X0 = 565;
constexpr int RD_CS = 1216;
constexpr int RS_CS = 320;
constexpr int R_E2 = 2 * RD_CS, R_O2 = R_E2 + 2 * RS_CS, R_E3 = R_O2 + 2 * RS_CS, R_O3 = R_E3 + 2 * RS_CS;
constexpr int R_BR = R_O3 + 2 * RS_CS;
constexpr int W5_OFF = R_OFF + 2 * R_BR;
constexpr int W3_OFF = W5_OFF + 3456;
constexpr int W9_OFF = W3_OFF + 3456;
constexpr int W7_OFF = W9_OFF + 2304;
constexpr int S2_OFF = W7_OFF + 2304;
constexpr int Y0_OFF = S2_OFF + 2304;
constexpr int Y2_OFF = Y0_OFF + 8192, Y3_OFF = Y2_OFF + 6144;
constexpr int CH_BYTES = Y0_OFF + 18432 + 16;
constexpr int SCR_BYTES = 4608;
constexpr int SMEM_BYTES = CH_OFF + 4 * CH_BYTES;
static_assert(CH_BYTES % 128 == 16, "bank staggering of the channel blocks");
static_assert(SMEM_BYTES <= 232448, "smem");
constexpr int B_RAW = BAR_OFF, B_X = BAR_OFF + 8, B_U = BAR_OFF + 40, B_W = BAR_OFF + 48;
constexpr int TAG_OFF = BAR_OFF + 56;
constexpr int K1024_OFF = BAR_OFF + 64;
constexpr int B_ST = BAR_OFF + 96;

__device__ unsigned int g_gate[L];
__device__ unsigned int g_epoch;
__device__ unsigned int g_ticket;

#define STAMP(k)
#define GT(k)

struct Params {
  const __nv_bfloat16* t[14];
  const __nv_bfloat16 *u, *gw, *A_D, *B_D;
};

template <int N, int TB> __device__ __forceinline__ void wgmma_rs(float* d, uint32_t a0, uint32_t a1, uint32_t a2, uint32_t a3, uint64_t desc, int sc);
template <> __device__ __forceinline__ void wgmma_rs<64, 0>(float* d, uint32_t a0, uint32_t a1, uint32_t a2, uint32_t a3, uint64_t desc, int sc) {
  asm volatile("{\n.reg .pred p;\nsetp.ne.b32 p, %37, 0;\n"
    "wgmma.mma_async.sync.aligned.m64n64k16.f32.bf16.bf16 {%0,%1,%2,%3,%4,%5,%6,%7,%8,%9,%10,%11,%12,%13,%14,%15,%16,%17,%18,%19,%20,%21,%22,%23,%24,%25,%26,%27,%28,%29,%30,%31}, {%32,%33,%34,%35}, %36, p, 1, 1, 0;\n}"
    : "+f"(d[0]), "+f"(d[1]), "+f"(d[2]), "+f"(d[3]), "+f"(d[4]), "+f"(d[5]), "+f"(d[6]), "+f"(d[7]), "+f"(d[8]), "+f"(d[9]), "+f"(d[10]), "+f"(d[11]), "+f"(d[12]), "+f"(d[13]), "+f"(d[14]), "+f"(d[15]), "+f"(d[16]), "+f"(d[17]), "+f"(d[18]), "+f"(d[19]), "+f"(d[20]), "+f"(d[21]), "+f"(d[22]), "+f"(d[23]), "+f"(d[24]), "+f"(d[25]), "+f"(d[26]), "+f"(d[27]), "+f"(d[28]), "+f"(d[29]), "+f"(d[30]), "+f"(d[31]) : "r"(a0), "r"(a1), "r"(a2), "r"(a3), "l"(desc), "r"(sc));
}
template <> __device__ __forceinline__ void wgmma_rs<56, 0>(float* d, uint32_t a0, uint32_t a1, uint32_t a2, uint32_t a3, uint64_t desc, int sc) {
  asm volatile("{\n.reg .pred p;\nsetp.ne.b32 p, %33, 0;\n"
    "wgmma.mma_async.sync.aligned.m64n56k16.f32.bf16.bf16 {%0,%1,%2,%3,%4,%5,%6,%7,%8,%9,%10,%11,%12,%13,%14,%15,%16,%17,%18,%19,%20,%21,%22,%23,%24,%25,%26,%27}, {%28,%29,%30,%31}, %32, p, 1, 1, 0;\n}"
    : "+f"(d[0]), "+f"(d[1]), "+f"(d[2]), "+f"(d[3]), "+f"(d[4]), "+f"(d[5]), "+f"(d[6]), "+f"(d[7]), "+f"(d[8]), "+f"(d[9]), "+f"(d[10]), "+f"(d[11]), "+f"(d[12]), "+f"(d[13]), "+f"(d[14]), "+f"(d[15]), "+f"(d[16]), "+f"(d[17]), "+f"(d[18]), "+f"(d[19]), "+f"(d[20]), "+f"(d[21]), "+f"(d[22]), "+f"(d[23]), "+f"(d[24]), "+f"(d[25]), "+f"(d[26]), "+f"(d[27]) : "r"(a0), "r"(a1), "r"(a2), "r"(a3), "l"(desc), "r"(sc));
}
template <> __device__ __forceinline__ void wgmma_rs<48, 0>(float* d, uint32_t a0, uint32_t a1, uint32_t a2, uint32_t a3, uint64_t desc, int sc) {
  asm volatile("{\n.reg .pred p;\nsetp.ne.b32 p, %29, 0;\n"
    "wgmma.mma_async.sync.aligned.m64n48k16.f32.bf16.bf16 {%0,%1,%2,%3,%4,%5,%6,%7,%8,%9,%10,%11,%12,%13,%14,%15,%16,%17,%18,%19,%20,%21,%22,%23}, {%24,%25,%26,%27}, %28, p, 1, 1, 0;\n}"
    : "+f"(d[0]), "+f"(d[1]), "+f"(d[2]), "+f"(d[3]), "+f"(d[4]), "+f"(d[5]), "+f"(d[6]), "+f"(d[7]), "+f"(d[8]), "+f"(d[9]), "+f"(d[10]), "+f"(d[11]), "+f"(d[12]), "+f"(d[13]), "+f"(d[14]), "+f"(d[15]), "+f"(d[16]), "+f"(d[17]), "+f"(d[18]), "+f"(d[19]), "+f"(d[20]), "+f"(d[21]), "+f"(d[22]), "+f"(d[23]) : "r"(a0), "r"(a1), "r"(a2), "r"(a3), "l"(desc), "r"(sc));
}
template <> __device__ __forceinline__ void wgmma_rs<32, 0>(float* d, uint32_t a0, uint32_t a1, uint32_t a2, uint32_t a3, uint64_t desc, int sc) {
  asm volatile("{\n.reg .pred p;\nsetp.ne.b32 p, %21, 0;\n"
    "wgmma.mma_async.sync.aligned.m64n32k16.f32.bf16.bf16 {%0,%1,%2,%3,%4,%5,%6,%7,%8,%9,%10,%11,%12,%13,%14,%15}, {%16,%17,%18,%19}, %20, p, 1, 1, 0;\n}"
    : "+f"(d[0]), "+f"(d[1]), "+f"(d[2]), "+f"(d[3]), "+f"(d[4]), "+f"(d[5]), "+f"(d[6]), "+f"(d[7]), "+f"(d[8]), "+f"(d[9]), "+f"(d[10]), "+f"(d[11]), "+f"(d[12]), "+f"(d[13]), "+f"(d[14]), "+f"(d[15]) : "r"(a0), "r"(a1), "r"(a2), "r"(a3), "l"(desc), "r"(sc));
}
template <> __device__ __forceinline__ void wgmma_rs<48, 1>(float* d, uint32_t a0, uint32_t a1, uint32_t a2, uint32_t a3, uint64_t desc, int sc) {
  asm volatile("{\n.reg .pred p;\nsetp.ne.b32 p, %29, 0;\n"
    "wgmma.mma_async.sync.aligned.m64n48k16.f32.bf16.bf16 {%0,%1,%2,%3,%4,%5,%6,%7,%8,%9,%10,%11,%12,%13,%14,%15,%16,%17,%18,%19,%20,%21,%22,%23}, {%24,%25,%26,%27}, %28, p, 1, 1, 1;\n}"
    : "+f"(d[0]), "+f"(d[1]), "+f"(d[2]), "+f"(d[3]), "+f"(d[4]), "+f"(d[5]), "+f"(d[6]), "+f"(d[7]), "+f"(d[8]), "+f"(d[9]), "+f"(d[10]), "+f"(d[11]), "+f"(d[12]), "+f"(d[13]), "+f"(d[14]), "+f"(d[15]), "+f"(d[16]), "+f"(d[17]), "+f"(d[18]), "+f"(d[19]), "+f"(d[20]), "+f"(d[21]), "+f"(d[22]), "+f"(d[23]) : "r"(a0), "r"(a1), "r"(a2), "r"(a3), "l"(desc), "r"(sc));
}
template <> __device__ __forceinline__ void wgmma_rs<40, 1>(float* d, uint32_t a0, uint32_t a1, uint32_t a2, uint32_t a3, uint64_t desc, int sc) {
  asm volatile("{\n.reg .pred p;\nsetp.ne.b32 p, %25, 0;\n"
    "wgmma.mma_async.sync.aligned.m64n40k16.f32.bf16.bf16 {%0,%1,%2,%3,%4,%5,%6,%7,%8,%9,%10,%11,%12,%13,%14,%15,%16,%17,%18,%19}, {%20,%21,%22,%23}, %24, p, 1, 1, 1;\n}"
    : "+f"(d[0]), "+f"(d[1]), "+f"(d[2]), "+f"(d[3]), "+f"(d[4]), "+f"(d[5]), "+f"(d[6]), "+f"(d[7]), "+f"(d[8]), "+f"(d[9]), "+f"(d[10]), "+f"(d[11]), "+f"(d[12]), "+f"(d[13]), "+f"(d[14]), "+f"(d[15]), "+f"(d[16]), "+f"(d[17]), "+f"(d[18]), "+f"(d[19]) : "r"(a0), "r"(a1), "r"(a2), "r"(a3), "l"(desc), "r"(sc));
}
template <> __device__ __forceinline__ void wgmma_rs<32, 1>(float* d, uint32_t a0, uint32_t a1, uint32_t a2, uint32_t a3, uint64_t desc, int sc) {
  asm volatile("{\n.reg .pred p;\nsetp.ne.b32 p, %21, 0;\n"
    "wgmma.mma_async.sync.aligned.m64n32k16.f32.bf16.bf16 {%0,%1,%2,%3,%4,%5,%6,%7,%8,%9,%10,%11,%12,%13,%14,%15}, {%16,%17,%18,%19}, %20, p, 1, 1, 1;\n}"
    : "+f"(d[0]), "+f"(d[1]), "+f"(d[2]), "+f"(d[3]), "+f"(d[4]), "+f"(d[5]), "+f"(d[6]), "+f"(d[7]), "+f"(d[8]), "+f"(d[9]), "+f"(d[10]), "+f"(d[11]), "+f"(d[12]), "+f"(d[13]), "+f"(d[14]), "+f"(d[15]) : "r"(a0), "r"(a1), "r"(a2), "r"(a3), "l"(desc), "r"(sc));
}
template <> __device__ __forceinline__ void wgmma_rs<16, 1>(float* d, uint32_t a0, uint32_t a1, uint32_t a2, uint32_t a3, uint64_t desc, int sc) {
  asm volatile("{\n.reg .pred p;\nsetp.ne.b32 p, %13, 0;\n"
    "wgmma.mma_async.sync.aligned.m64n16k16.f32.bf16.bf16 {%0,%1,%2,%3,%4,%5,%6,%7}, {%8,%9,%10,%11}, %12, p, 1, 1, 1;\n}"
    : "+f"(d[0]), "+f"(d[1]), "+f"(d[2]), "+f"(d[3]), "+f"(d[4]), "+f"(d[5]), "+f"(d[6]), "+f"(d[7]) : "r"(a0), "r"(a1), "r"(a2), "r"(a3), "l"(desc), "r"(sc));
}

__device__ __forceinline__ uint32_t pack_bf16(float lo, float hi) {
  uint32_t r; asm("cvt.rn.bf16x2.f32 %0, %1, %2;" : "=r"(r) : "f"(hi), "f"(lo)); return r;
}
__device__ __forceinline__ float bf_lo(uint32_t v) { return __uint_as_float(v << 16); }
__device__ __forceinline__ float bf_hi(uint32_t v) { return __uint_as_float(v & 0xffff0000u); }
__device__ __forceinline__ float bf_round(float x) { return bf_lo(pack_bf16(x, 0.f)); }
__device__ __forceinline__ uint32_t hmul2(uint32_t a, uint32_t b) { uint32_t r; asm("mul.rn.bf16x2 %0, %1, %2;" : "=r"(r) : "r"(a), "r"(b)); return r; }
__device__ __forceinline__ uint32_t hadd2(uint32_t a, uint32_t b) { uint32_t r; asm("add.rn.bf16x2 %0, %1, %2;" : "=r"(r) : "r"(a), "r"(b)); return r; }
__device__ __forceinline__ uint32_t hsub2(uint32_t a, uint32_t b) { uint32_t r; asm("sub.rn.bf16x2 %0, %1, %2;" : "=r"(r) : "r"(a), "r"(b)); return r; }
__device__ __forceinline__ uint32_t hfma2(uint32_t a, uint32_t b, uint32_t c) { uint32_t r; asm("fma.rn.bf16x2 %0, %1, %2, %3;" : "=r"(r) : "r"(a), "r"(b), "r"(c)); return r; }

__device__ __forceinline__ void sts16(uint32_t a, uint32_t v) { asm volatile("st.shared.b16 [%0], %1;" ::"r"(a), "h"((unsigned short)v) : "memory"); }
__device__ __forceinline__ void sts32(uint32_t a, uint32_t v) { asm volatile("st.shared.b32 [%0], %1;" ::"r"(a), "r"(v) : "memory"); }
__device__ __forceinline__ void sts64(uint32_t a, uint32_t x, uint32_t y) { asm volatile("st.shared.v2.b32 [%0], {%1,%2};" ::"r"(a), "r"(x), "r"(y) : "memory"); }
__device__ __forceinline__ void sts128(uint32_t a, uint32_t x, uint32_t y, uint32_t z, uint32_t w) {
  asm volatile("st.shared.v4.b32 [%0], {%1,%2,%3,%4};" ::"r"(a), "r"(x), "r"(y), "r"(z), "r"(w) : "memory");
}
__device__ __forceinline__ uint32_t lds32(uint32_t a) { uint32_t v; asm volatile("ld.shared.b32 %0, [%1];" : "=r"(v) : "r"(a) : "memory"); return v; }
__device__ __forceinline__ uint2 lds64(uint32_t a) { uint2 v; asm volatile("ld.shared.v2.b32 {%0,%1}, [%2];" : "=r"(v.x), "=r"(v.y) : "r"(a) : "memory"); return v; }
__device__ __forceinline__ uint4 lds128(uint32_t a) {
  uint4 v; asm volatile("ld.shared.v4.b32 {%0,%1,%2,%3}, [%4];" : "=r"(v.x), "=r"(v.y), "=r"(v.z), "=r"(v.w) : "r"(a) : "memory"); return v;
}
__device__ __forceinline__ uint4 ldg128(const void* a) {
  uint4 v; asm volatile("ld.global.nc.v4.b32 {%0,%1,%2,%3}, [%4];" : "=r"(v.x), "=r"(v.y), "=r"(v.z), "=r"(v.w) : "l"(a) : "memory"); return v;
}
__device__ __forceinline__ uint2 ldg64(const void* a) {
  uint2 v; asm volatile("ld.global.nc.v2.b32 {%0,%1}, [%2];" : "=r"(v.x), "=r"(v.y) : "l"(a) : "memory"); return v;
}
__device__ __forceinline__ void ldsm4(uint32_t a, uint32_t& r0, uint32_t& r1, uint32_t& r2, uint32_t& r3) {
  asm volatile("ldmatrix.sync.aligned.m8n8.x4.shared.b16 {%0,%1,%2,%3}, [%4];" : "=r"(r0), "=r"(r1), "=r"(r2), "=r"(r3) : "r"(a) : "memory");
}
__device__ __forceinline__ void ldsm4t(uint32_t a, uint32_t& r0, uint32_t& r1, uint32_t& r2, uint32_t& r3) {
  asm volatile("ldmatrix.sync.aligned.m8n8.x4.trans.shared.b16 {%0,%1,%2,%3}, [%4];" : "=r"(r0), "=r"(r1), "=r"(r2), "=r"(r3) : "r"(a) : "memory");
}
__device__ __forceinline__ void stsm4(uint32_t a, uint32_t r0, uint32_t r1, uint32_t r2, uint32_t r3) {
  asm volatile("stmatrix.sync.aligned.m8n8.x4.shared.b16 [%0], {%1,%2,%3,%4};" ::"r"(a), "r"(r0), "r"(r1), "r"(r2), "r"(r3) : "memory");
}
__device__ __forceinline__ void stsm4t(uint32_t a, uint32_t r0, uint32_t r1, uint32_t r2, uint32_t r3) {
  asm volatile("stmatrix.sync.aligned.m8n8.x4.trans.shared.b16 [%0], {%1,%2,%3,%4};" ::"r"(a), "r"(r0), "r"(r1), "r"(r2), "r"(r3) : "memory");
}
__device__ __forceinline__ void stsm2(uint32_t a, uint32_t r0, uint32_t r1) {
  asm volatile("stmatrix.sync.aligned.m8n8.x2.shared.b16 [%0], {%1,%2};" ::"r"(a), "r"(r0), "r"(r1) : "memory");
}
__device__ __forceinline__ void stsm2t(uint32_t a, uint32_t r0, uint32_t r1) {
  asm volatile("stmatrix.sync.aligned.m8n8.x2.trans.shared.b16 [%0], {%1,%2};" ::"r"(a), "r"(r0), "r"(r1) : "memory");
}
__device__ __forceinline__ void mma16816(float* c, uint32_t a0, uint32_t a1, uint32_t a2, uint32_t a3, uint32_t b0, uint32_t b1) {
  asm("mma.sync.aligned.m16n8k16.row.col.f32.bf16.bf16.f32 {%0,%1,%2,%3}, {%4,%5,%6,%7}, {%8,%9}, {%0,%1,%2,%3};"
      : "+f"(c[0]), "+f"(c[1]), "+f"(c[2]), "+f"(c[3]) : "r"(a0), "r"(a1), "r"(a2), "r"(a3), "r"(b0), "r"(b1));
}
__device__ __forceinline__ void bar_sync(int id, int n) { asm volatile("bar.sync %0, %1;" ::"r"(id), "r"(n) : "memory"); }
__device__ __forceinline__ void bar_arrive(int id, int n) { asm volatile("bar.arrive %0, %1;" ::"r"(id), "r"(n) : "memory"); }
__device__ __forceinline__ void wg_fence() { asm volatile("wgmma.fence.sync.aligned;" ::: "memory"); }
__device__ __forceinline__ void wg_commit() { asm volatile("wgmma.commit_group.sync.aligned;" ::: "memory"); }
__device__ __forceinline__ void wg_wait0() { asm volatile("wgmma.wait_group.sync.aligned 0;" ::: "memory"); }
__device__ __forceinline__ void wg_wait1() { asm volatile("wgmma.wait_group.sync.aligned 1;" ::: "memory"); }
__device__ __forceinline__ void fence_async() { asm volatile("fence.proxy.async.shared::cta;" ::: "memory"); }
__device__ __forceinline__ uint32_t opq(uint32_t x, uint32_t z) { uint32_t r; asm volatile("xor.b32 %0, %1, %2;" : "=r"(r) : "r"(x), "r"(z)); return r; }
__device__ __forceinline__ uint64_t mkdesc(uint32_t addr, uint32_t lbo, uint32_t sbo) {
  return (uint64_t)((addr & 0x3FFFF) >> 4) | ((uint64_t)(lbo >> 4) << 16) | ((uint64_t)(sbo >> 4) << 32);
}
__device__ __forceinline__ uint32_t mapa(uint32_t a, uint32_t rank) {
  uint32_t r; asm("mapa.shared::cluster.u32 %0, %1, %2;" : "=r"(r) : "r"(a), "r"(rank)); return r;
}
__device__ __forceinline__ void mbar_init_expect(uint32_t bar, uint32_t bytes) {
  asm volatile("mbarrier.init.shared::cta.b64 [%0], 1;" ::"r"(bar) : "memory");
  asm volatile("mbarrier.arrive.expect_tx.shared::cta.b64 _, [%0], %1;" ::"r"(bar), "r"(bytes) : "memory");
}
__device__ __forceinline__ void mbar_wait(uint32_t bar) {
#pragma unroll 1
  for (int it = 0; it < (1 << 22); it++) {
    uint32_t ok;
    asm volatile("{\n.reg .pred p;\nmbarrier.try_wait.parity.acquire.cluster.shared::cta.b64 p, [%1], 0;\nselp.u32 %0, 1, 0, p;\n}"
                 : "=r"(ok) : "r"(bar) : "memory");
    if (ok) return;
  }
  __trap();
}
__device__ __forceinline__ void st_async4(uint32_t a, uint32_t bar, uint32_t x, uint32_t y, uint32_t z, uint32_t w) {
  asm volatile("st.async.weak.shared::cluster.mbarrier::complete_tx::bytes.v4.b32 [%0], {%2,%3,%4,%5}, [%1];"
               ::"r"(a), "r"(bar), "r"(x), "r"(y), "r"(z), "r"(w) : "memory");
}

struct cf { float re, im; };
__device__ __forceinline__ cf cmul(cf a, cf b) { return {fmaf(a.re, b.re, -a.im * b.im), fmaf(a.re, b.im, a.im * b.re)}; }
__device__ __forceinline__ cf csq(cf a) { return {fmaf(a.re, a.re, -a.im * a.im), (a.re + a.re) * a.im}; }
__device__ __forceinline__ cf cexp_p(float xl, float y, float p) {
  float mag; asm("ex2.approx.ftz.f32 %0, %1;" : "=f"(mag) : "f"(xl * p));
  const float th = y * p;
  const float k = __fadd_rn(fmaf(th, 0.15915494309189535f, 12582912.f), -12582912.f);
  float r = fmaf(k, -6.2831854820251465f, th);
  r = fmaf(k, 1.7484555314695172e-07f, r);
  return {mag * __cosf(r), mag * __sinf(r)};
}
__device__ __forceinline__ uint32_t ysw(int c) { return (uint32_t)(c ^ ((c >> 3) & 3)) * 16u; }

#define CMUL2(OR, OI, xr, xi, yr, yi, nyi) do { OR = hfma2(xr, yr, hmul2(xi, nyi)); OI = hfma2(xr, yi, hmul2(xi, yr)); } while (0)

__device__ __forceinline__ uint32_t gate_slow(const __nv_bfloat16* u, const __nv_bfloat16* gw, int row) {
  float s = 0.f;
  const uint32_t* xr = (const uint32_t*)(u + (size_t)row * D);
  const uint32_t* wr = (const uint32_t*)gw;
#pragma unroll 1
  for (int j = 0; j < D / 2; j++) { const uint32_t pr = hmul2(xr[j], wr[j]); s += bf_lo(pr); s += bf_hi(pr); }
  s = bf_round(s);
  return pack_bf16(1.f / (1.f + expf(-s)), 0.f);
}

__device__ __forceinline__ uint2 gate_ld(int x) {
  uint2 gv;
  asm volatile("ld.relaxed.gpu.global.v2.u32 {%0,%1}, [%2];" : "=r"(gv.x), "=r"(gv.y) : "l"(g_gate + x * 2) : "memory");
  return gv;
}
__device__ __noinline__ uint32_t gate_poll(const Params* pp, int x, uint32_t tag) {
  uint2 gv;
#pragma unroll 1
  for (int spins = 0; spins < (1 << 16); spins++) {
    gv = gate_ld(x);
    if ((gv.x >> 16) == tag && (gv.y >> 16) == tag) return __byte_perm(gv.x, gv.y, 0x5410);
  }
  return __byte_perm(gate_slow(pp->u, pp->gw, x * 2), gate_slow(pp->u, pp->gw, x * 2 + 1), 0x5410);
}
__device__ __forceinline__ uint32_t gate_fin(const Params& p, uint2 gv, int x, uint32_t tag) {
  if ((gv.x >> 16) == tag && (gv.y >> 16) == tag) return __byte_perm(gv.x, gv.y, 0x5410);
  return gate_poll(&p, x, tag);
}

__device__ __forceinline__ void ld4ch(uint32_t* v, uint32_t addr) {
#pragma unroll
  for (int k = 0; k < 4; k++) v[k] = lds32(addr + k * CH_BYTES);
}
__device__ __forceinline__ void skip_terms(uint32_t* ua, uint32_t* ub, uint32_t sb, int x, uint2 dA, uint2 dB) {
  const int c = x >> 2;
  uint32_t uu[4];
  ld4ch(uu, sb + CH_OFF + (x & 3) * 4 + U_OFF + (c & 3) * U_CS + (63 - (c >> 2)) * 16);
#pragma unroll
  for (int k = 0; k < 4; k++) {
    ua[k] = hmul2(uu[k], __byte_perm((k & 2) ? dA.y : dA.x, 0, (k & 1) ? 0x3232 : 0x1010));
    ub[k] = hmul2(uu[k], __byte_perm((k & 2) ? dB.y : dB.x, 0, (k & 1) ? 0x3232 : 0x1010));
  }
}
__device__ __forceinline__ uint4 mix(const uint32_t* a, const uint32_t* b, const uint32_t* ua, const uint32_t* ub, uint32_t g2) {
  const uint32_t h2 = hsub2(0x3f803f80u, g2);
  uint32_t o[4];
#pragma unroll
  for (int k = 0; k < 4; k++) o[k] = hadd2(hmul2(g2, hadd2(a[k], ua[k])), hmul2(h2, hadd2(b[k], ub[k])));
  return make_uint4(__byte_perm(o[0], o[1], 0x5410), __byte_perm(o[2], o[3], 0x5410), __byte_perm(o[0], o[1], 0x7632), __byte_perm(o[2], o[3], 0x7632));
}
__device__ __forceinline__ void send_box(uint32_t sb, int slot, int wtid, uint32_t rank, uint4 r) {
  st_async4(mapa(sb + XIN_OFF + slot * 2048 + wtid * 16, rank ^ 1), mapa(sb + B_X + slot * 8, rank ^ 1), r.x, r.y, r.z, r.w);
}
__device__ __forceinline__ void merge_box(uint32_t sb, const CUtensorMap* tm_out, int slot, int wtid, uint32_t rank, int oc0, uint4 r, int barid) {
  const uint32_t st = sb + RAW_OFF + slot * 4096 + wtid * 16;
  sts64(st + rank * 8, r.x, r.y); sts64(st + 2048 + rank * 8, r.z, r.w);
  mbar_wait(sb + B_X + slot * 8);
  const uint4 q = lds128(sb + XIN_OFF + slot * 2048 + wtid * 16);
  sts64(st + (rank ^ 1) * 8, q.x, q.y); sts64(st + 2048 + (rank ^ 1) * 8, q.z, q.w);
  fence_async();
  bar_sync(barid, 128);
  if (wtid == 0) {
    asm volatile("cp.async.bulk.tensor.3d.global.shared::cta.bulk_group [%0, {%2, %3, %4}], [%1];"
                 ::"l"(tm_out), "r"(sb + RAW_OFF + slot * 4096), "r"(oc0), "r"((2 * slot + (int)rank) * 128), "r"(0) : "memory");
    asm volatile("cp.async.bulk.commit_group;" ::: "memory");
  }
}

__device__ __forceinline__ uint32_t band2(int e, int lo, int hi) {
  uint32_t r = ((uint32_t)(e - lo) <= (uint32_t)(hi - lo) ? 0x3f80u : 0u) | ((uint32_t)(e - 1 - lo) <= (uint32_t)(hi - lo) ? 0x3f800000u : 0u);
  asm volatile("" : "+r"(r));
  return r;
}

__device__ __forceinline__ void stage_done(uint32_t sb, int stage, int lane) {
  __syncwarp();
  if (lane == 0) asm volatile("mbarrier.arrive.shared::cta.b64 _, [%0];" ::"r"(sb + B_ST + 8 * stage) : "memory");
}
#define PK2(v, i) pack_bf16(v[i], v[(i) + 1])

__device__ __forceinline__ void conv_dense(uint32_t sb, uint32_t cb, uint32_t zz) {
  const int lane = threadIdx.x & 31, wq = (threadIdx.x >> 5) & 3, br = wq >> 1, hf = wq & 1, g = lane >> 2, t = lane & 3;
  const uint32_t rb = cb + R_OFF + br * R_BR;
  const int eo = 16 * hf + g - 2 * t;
  const int x0 = RD_X0 - (eo + 536);
  const uint32_t fa = rb + ((g & 1) ? 2 * x0 : RD_CS + 2 * x0 + 2);
  const uint64_t ub = mkdesc(cb + U_OFF, U_CS, 128);
  const uint32_t yd = cb + Y0_OFF + br * 4096 + ysw(4 * (63 - 8 * (lane >> 4) - (lane & 7)) + 2 * hf + ((lane >> 3) & 1));
  uint32_t A[2][4][4];
  float e64[32], e56[28], e48[24];
  auto loadA = [&](int j) {
#pragma unroll
    for (int k = 0; k < 4; k++) {
      const int s = 34 - 4 * j - k;
      if (s >= 0) {
        if (k == 0 && j == 0) A[0][0][2] = lds32(fa + (2 * s + 2) * 16);
        A[j & 1][k][0] = lds32(fa + (2 * s + 1) * 16);
        A[j & 1][k][1] = lds32(fa + (2 * s) * 16);
      }
    }
#pragma unroll
    for (int k = 0; k < 4; k++) {
      if (34 - 4 * j - k >= 0) {
        A[j & 1][k][3] = A[j & 1][k][0];
        if (k) A[j & 1][k][2] = A[j & 1][k - 1][1];
        else if (j) A[j & 1][0][2] = A[(j - 1) & 1][3][1];
      }
    }
  };
  loadA(0); loadA(1);
#pragma unroll
  for (int j = 0; j < 9; j++) {
    if (j == 4) {
      wg_wait0();
      stsm2t(yd - 7 * 512, PK2(e64, 28), PK2(e64, 30));
#pragma unroll
      for (int i = 0; i < 28; i++) e56[i] = FCPY(e64[i]);
      stage_done(sb, 0, lane);
    }
    if (j == 8) {
      wg_wait0();
      stsm2t(yd - 6 * 512, PK2(e56, 24), PK2(e56, 26));
#pragma unroll
      for (int i = 0; i < 24; i++) e48[i] = FCPY(e56[i]);
      stage_done(sb, 1, lane);
    }
    wg_fence();
#pragma unroll
    for (int k = 0; k < 4; k++) {
      const int s = 34 - 4 * j - k;
      if (s >= 0) {
        const int o = 2 * s - 66 + 128;
        const int cc = o & 3, rs = (o >> 2) - 32;
        const uint64_t desc = ub + (uint64_t)((cc * U_CS - rs * 16) >> 4);
        const uint32_t* a = A[j & 1][k];
        if (j < 4) wgmma_rs<64, 0>(e64, a[0], a[1], a[2], a[3], desc, s != 34);
        else if (j < 8) wgmma_rs<56, 0>(e56, a[0], a[1], a[2], a[3], desc, 1);
        else wgmma_rs<48, 0>(e48, a[0], a[1], a[2], a[3], desc, 1);
      }
    }
    wg_commit();
    if (j >= 1 && j < 8) { wg_wait1(); loadA(j + 1); }
  }
  wg_wait0();
#pragma unroll
  for (int i = 0; i < 6; i += 2) stsm4t(yd - i * 512, PK2(e48, 4 * i), PK2(e48, 4 * i + 2), PK2(e48, 4 * i + 4), PK2(e48, 4 * i + 6));
}

__device__ __noinline__ void gate_cta(const Params* pp) {
  const __nv_bfloat16 *u = pp->u, *gw = pp->gw;
  const int lane = threadIdx.x & 31;
  unsigned int epoch;
  asm volatile("ld.relaxed.gpu.global.u32 %0, [%1];" : "=r"(epoch) : "l"(&g_epoch) : "memory");
  const uint4 gw0 = ldg128(gw + lane * 8), gw1 = ldg128(gw + 256 + lane * 8);
  const uint32_t ws[8] = {gw0.x, gw0.y, gw0.z, gw0.w, gw1.x, gw1.y, gw1.z, gw1.w};
  const uint32_t tag = (epoch + 1) & 0xffffu;
  uint4 gx[4][2], nx[4][2];
  int grow = (blockIdx.x * 20 + (threadIdx.x >> 5)) * 4;
#pragma unroll
  for (int i = 0; i < 4; i++) {
    nx[i][0] = ldg128(u + (size_t)(grow + i) * D + lane * 8);
    nx[i][1] = ldg128(u + (size_t)(grow + i) * D + 256 + lane * 8);
  }
#pragma unroll 1
  for (; grow < L; grow += 80 * NGATE) {
    const int nrow = min(grow + 80 * NGATE, L - 4);
#pragma unroll
    for (int i = 0; i < 4; i++) {
      gx[i][0] = nx[i][0]; gx[i][1] = nx[i][1];
      nx[i][0] = ldg128(u + (size_t)(nrow + i) * D + lane * 8);
      nx[i][1] = ldg128(u + (size_t)(nrow + i) * D + 256 + lane * 8);
    }
    float c[2][4];
#pragma unroll
    for (int i = 0; i < 2; i++) {
      const uint4 *x = gx[2 * i], *y = gx[2 * i + 1];
      const uint32_t xs[8] = {x[0].x, x[0].y, x[0].z, x[0].w, x[1].x, x[1].y, x[1].z, x[1].w};
      const uint32_t ys[8] = {y[0].x, y[0].y, y[0].z, y[0].w, y[1].x, y[1].y, y[1].z, y[1].w};
      c[i][0] = c[i][1] = c[i][2] = c[i][3] = 0.f;
#pragma unroll
      for (int j = 0; j < 8; j += 2)
        mma16816(c[i], hmul2(xs[j], ws[j]), hmul2(ys[j], ws[j]), hmul2(xs[j + 1], ws[j + 1]), hmul2(ys[j + 1], ws[j + 1]), 0x3f803f80u, 0x3f803f80u);
    }
    float s = (lane & 2) ? ((lane & 1) ? c[1][2] : c[1][0]) : ((lane & 1) ? c[0][2] : c[0][0]);
#pragma unroll
    for (int o = 4; o < 32; o <<= 1) s += __shfl_xor_sync(0xffffffffu, s, o);
    s = bf_round(s);
    const float gv = 1.f / (1.f + expf(-s));
    const uint32_t w = (tag << 16) | (pack_bf16(gv, 0.f) & 0xffffu);
    if (lane < 4) asm volatile("st.relaxed.gpu.global.u32 [%0], %1;" ::"l"(&g_gate[grow + lane]), "r"(w) : "memory");
  }
  __syncthreads();
  if (threadIdx.x == 0 && atomicAdd(&g_ticket, 1u) == NCTA + NGATE - 1) { g_ticket = 0; g_epoch = epoch + 1; }
}

__global__ void __cluster_dims__(2, 1, 1) __launch_bounds__(640, 1)
ssm_kernel(const __grid_constant__ Params p, const __grid_constant__ CUtensorMap tm_in, const __grid_constant__ CUtensorMap tm_out) {
  extern __shared__ __align__(1024) unsigned char smem_raw[];
  const uint32_t sb = (uint32_t)__cvta_generic_to_shared(smem_raw);
  const int tid = threadIdx.x, lane = tid & 31;
  const int warp = __shfl_sync(0xffffffffu, tid >> 5, 0);
  const int ch = warp >> 2, wq = warp & 3, br = wq >> 1, hf = wq & 1;
  const int g = lane >> 2, t = lane & 3;
  if (__builtin_expect(blockIdx.x < NGATE, 0)) { gate_cta(&p); return; }
  const int bid = blockIdx.x - NGATE;
  const int d = bid * 4 + ch;
  const uint32_t rank = blockIdx.x & 1;
  const uint32_t cb = sb + CH_OFF + ch * CH_BYTES;
  const int wtid = tid & 127;
  const int oc0 = (bid >> 1) * 8;
  STAMP(0); GT(0);

  if (warp >= 16) {
    if (wtid == 0) {
      mbar_init_expect(sb + B_RAW, 32768);
#pragma unroll
      for (int i = 0; i < 4; i++) mbar_init_expect(sb + B_X + 8 * i, 2048);
      asm volatile("mbarrier.init.shared::cta.b64 [%0], 128;" ::"r"(sb + B_U) : "memory");
      asm volatile("mbarrier.init.shared::cta.b64 [%0], 128;" ::"r"(sb + B_W) : "memory");
#pragma unroll
      for (int i = 0; i < 7; i++) asm volatile("mbarrier.init.shared::cta.b64 [%0], 16;" ::"r"(sb + B_ST + 8 * i) : "memory");
      asm volatile("fence.mbarrier_init.release.cluster;" ::: "memory");
      asm volatile("fence.proxy.async.shared::cta;" ::: "memory");
    }
    __syncwarp();
    asm volatile("barrier.cluster.arrive.relaxed.aligned;" ::: "memory");
    unsigned int epoch;
    asm volatile("ld.relaxed.gpu.global.u32 %0, [%1];" : "=r"(epoch) : "l"(&g_epoch) : "memory");
    asm volatile("barrier.cluster.wait.aligned;" ::: "memory");
    if (wtid == 0) {
      asm volatile("cp.async.bulk.tensor.5d.shared::cluster.global.mbarrier::complete_tx::bytes.multicast::cluster [%0], [%1, {%3, %4, %4, %4, %5}], [%2], %6;"
                   ::"r"(sb + RAW_OFF + rank * 16384), "l"(&tm_in), "r"(sb + B_RAW), "r"(oc0), "r"(0), "r"((int)rank * 32), "h"((unsigned short)3) : "memory");
    }
    sts128(sb + CH_OFF + wq * CH_BYTES + U_OFF + (lane >> 3) * U_CS + (64 + (lane & 7)) * 16, 0, 0, 0, 0);
    const uint2 dA = ldg64(p.A_D + bid * 4), dB = ldg64(p.B_D + bid * 4);
    uint32_t BA[3][4], BC[3][4];
    {
      const int l1 = br ? 3 : 6, h1 = br ? 5 : 10;
#pragma unroll
      for (int i = 0; i < 3; i++) {
        const int e = 16 * hf + g - 2 * t + 16 - 16 * i;
        BA[i][0] = band2(e, l1, h1); BA[i][1] = band2(e + 8, l1, h1); BA[i][2] = band2(e - 8, l1, h1); BA[i][3] = BA[i][0];
        BC[i][0] = band2(e, 3, 4); BC[i][1] = band2(e + 8, 3, 4); BC[i][2] = band2(e - 8, 3, 4); BC[i][3] = BC[i][0];
      }
    }
    const uint32_t tag = (epoch + 1) & 0xffffu;
    if (wtid == 0) sts32(sb + TAG_OFF, tag);
    STAMP(3);
    mbar_wait(sb + B_RAW);
    STAMP(4);
    {
      const uint32_t dst = sb + CH_OFF + (g & 3) * CH_BYTES + U_OFF + t * U_CS + (63 - wq * 16) * 16;
#pragma unroll
      for (int h = 0; h < 2; h++) {
        uint32_t r[8][4];
#pragma unroll
        for (int i = 0; i < 8; i++) ldsm4t(sb + RAW_OFF + (wq * 16 + h * 8 + i) * 512 + lane * 16, r[i][0], r[i][1], r[i][2], r[i][3]);
        if ((uint32_t)(g >> 2) == rank) {
#pragma unroll
          for (int i = 0; i < 8; i++) sts128(dst - (h * 8 + i) * 16, r[i][0], r[i][1], r[i][2], r[i][3]);
        }
      }
    }
    fence_async();
    asm volatile("mbarrier.arrive.shared::cta.b64 _, [%0];" ::"r"(sb + B_U) : "memory");
    bar_sync(5, 128);
    STAMP(5);
    {
      const int mrow = lane & 7, mi = lane >> 3;
      const uint64_t ub0 = mkdesc(sb + CH_OFF + U_OFF, U_CS, 128);
      {
        float w1[24], w3[16];
#pragma unroll
        for (int i = 0; i < 24; i++) w1[i] = 0.f;
#pragma unroll
        for (int i = 0; i < 16; i++) w3[i] = 0.f;
        uint32_t wa[3], sa[2];
#pragma unroll
        for (int i = 0; i < 3; i++) {
          const int c = 4 * (47 - 8 * (2 * i + (mi >> 1)) - mrow) + 2 * hf + (mi & 1);
          wa[i] = sb + CH_OFF + (br ? W3_OFF : W5_OFF) + (5 - (c >> 5)) * 576 + ((c & 31) >> 3) * 144 + (c & 7) * 16;
          if (i) sa[i - 1] = sb + CH_OFF + S2_OFF + (c + (c >> 3)) * 16;
        }
#pragma unroll 1
        for (int k = 0; k < 4; k++) {
          wg_fence();
#pragma unroll
          for (int i = 0; i < 3; i++)
            wgmma_rs<48, 0>(w1, BA[i][0], BA[i][1], BA[i][2], BA[i][3],
                            ub0 + (uint64_t)((k * CH_BYTES + ((2 * i + 2) & 3) * U_CS + (16 + (i == 0)) * 16) >> 4), i);
#pragma unroll
          for (int i = 0; i < 3; i++)
            wgmma_rs<32, 0>(w3, BC[i][0], BC[i][1], BC[i][2], BC[i][3],
                            ub0 + (uint64_t)((k * CH_BYTES + ((2 * i + 2) & 3) * U_CS + (32 + (i == 0)) * 16) >> 4), i);
          wg_commit();
          wg_wait0();
#pragma unroll
          for (int i = 0; i < 3; i++)
            stsm4t(wa[i] + k * CH_BYTES, pack_bf16(w1[8 * i], w1[8 * i + 1]), pack_bf16(w1[8 * i + 2], w1[8 * i + 3]),
                   pack_bf16(w1[8 * i + 4], w1[8 * i + 5]), pack_bf16(w1[8 * i + 6], w1[8 * i + 7]));
          if (br == 0) {
#pragma unroll
            for (int i = 0; i < 2; i++)
              stsm4t(sa[i] + k * CH_BYTES, pack_bf16(w3[8 * i], w3[8 * i + 1]), pack_bf16(w3[8 * i + 2], w3[8 * i + 3]),
                     pack_bf16(w3[8 * i + 4], w3[8 * i + 5]), pack_bf16(w3[8 * i + 6], w3[8 * i + 7]));
          }
        }
      }
      {
        uint32_t BB[4][4];
        const int l2 = br ? 5 : 12, h2 = br ? 11 : 20;
#pragma unroll
        for (int i = 0; i < 4; i++) {
          const int e = 16 * hf + g - 2 * t + 32 - 16 * i;
          BB[i][0] = band2(e, l2, h2); BB[i][1] = band2(e + 8, l2, h2); BB[i][2] = band2(e - 8, l2, h2); BB[i][3] = BB[i][0];
        }
        float w2[2][16];
#pragma unroll
        for (int i = 0; i < 16; i++) { w2[0][i] = 0.f; w2[1][i] = 0.f; }
        uint32_t wa[2];
#pragma unroll
        for (int i = 0; i < 2; i++) {
          const int c = 4 * (31 - 8 * (2 * i + (mi >> 1)) - mrow) + 2 * hf + (mi & 1), pp = c >> 1;
          wa[i] = sb + CH_OFF + (br ? W7_OFF : W9_OFF) + (1 - (pp >> 5)) * 1152 + (c & 1) * 576 + ((pp & 31) >> 3) * 144 + (pp & 7) * 16;
        }
#pragma unroll 1
        for (int kp = 0; kp < 2; kp++) {
          wg_fence();
#pragma unroll
          for (int k = 0; k < 2; k++)
#pragma unroll
            for (int i = 0; i < 4; i++)
              wgmma_rs<32, 0>(w2[k], BB[i][0], BB[i][1], BB[i][2], BB[i][3],
                              ub0 + (uint64_t)(((2 * kp + k) * CH_BYTES + ((2 * i) & 3) * U_CS + (32 + (i < 2)) * 16) >> 4), i);
          wg_commit();
          wg_wait0();
#pragma unroll
          for (int k = 0; k < 2; k++)
#pragma unroll
            for (int i = 0; i < 2; i++)
              stsm4t(wa[i] + (2 * kp + k) * CH_BYTES, pack_bf16(w2[k][8 * i], w2[k][8 * i + 1]), pack_bf16(w2[k][8 * i + 2], w2[k][8 * i + 3]),
                     pack_bf16(w2[k][8 * i + 4], w2[k][8 * i + 5]), pack_bf16(w2[k][8 * i + 6], w2[k][8 * i + 7]));
        }
      }
    }
    fence_async();
    asm volatile("mbarrier.arrive.shared::cta.b64 _, [%0];" ::"r"(sb + B_W) : "memory");
    STAMP(7);
    {
      const int bsel = (int)rank ^ br ^ 1, xl = wtid & 63;
      uint2 gl[4];
      uint32_t ua[4][4], ub[4][4];
#pragma unroll
      for (int i = 0; i < 4; i++) gl[i] = gate_ld((2 * (i >> 1) + bsel) * 128 + (i & 1) * 64 + xl);
#pragma unroll
      for (int i = 0; i < 4; i++) skip_terms(ua[i], ub[i], sb, (2 * (i >> 1) + bsel) * 128 + (i & 1) * 64 + xl, dA, dB);
      const uint32_t yo = sb + CH_OFF + (xl & 3) * 4 + ysw(xl >> 2) + bsel * 512;
#pragma unroll
      for (int slot = 0; slot < 2; slot++) {
        const int box = 2 * slot + bsel;
        uint32_t g2[2], ya[2][4], yb[2][4];
#pragma unroll
        for (int h = 0; h < 2; h++) g2[h] = gate_fin(p, gl[2 * slot + h], box * 128 + h * 64 + xl, tag);
        mbar_wait(sb + B_ST + 8 * box);
        STAMP(8 + slot);
#pragma unroll
        for (int h = 0; h < 2; h++) {
          const uint32_t yh = (yo ^ (h * 32)) + h * 256 + slot * 1024;
          ld4ch(ya[h], yh + Y0_OFF); ld4ch(yb[h], yh + Y0_OFF + 4096);
          if (slot) {
            uint32_t a2[4], b2[4];
            ld4ch(a2, yh + Y2_OFF - 1024); ld4ch(b2, yh + Y2_OFF - 1024 + 3072);
#pragma unroll
            for (int k = 0; k < 4; k++) { ya[h][k] = hadd2(ya[h][k], a2[k]); yb[h][k] = hadd2(yb[h][k], b2[k]); }
          }
        }
        const uint4 r0 = mix(ya[0], yb[0], ua[2 * slot], ub[2 * slot], g2[0]), r1 = mix(ya[1], yb[1], ua[2 * slot + 1], ub[2 * slot + 1], g2[1]);
        if (br == 0) { send_box(sb, slot, xl, rank, r0); send_box(sb, slot, xl + 64, rank, r1); }
        else {
          const uint32_t st = sb + RAW_OFF + slot * 4096 + xl * 16, xin = sb + XIN_OFF + slot * 2048 + xl * 16;
          sts64(st + rank * 8, r0.x, r0.y); sts64(st + 2048 + rank * 8, r0.z, r0.w);
          sts64(st + 1024 + rank * 8, r1.x, r1.y); sts64(st + 3072 + rank * 8, r1.z, r1.w);
          mbar_wait(sb + B_X + slot * 8);
          const uint4 q0 = lds128(xin), q1 = lds128(xin + 1024);
          sts64(st + (rank ^ 1) * 8, q0.x, q0.y); sts64(st + 2048 + (rank ^ 1) * 8, q0.z, q0.w);
          sts64(st + 1024 + (rank ^ 1) * 8, q1.x, q1.y); sts64(st + 3072 + (rank ^ 1) * 8, q1.z, q1.w);
          fence_async();
          bar_sync(6, 64);
          if (xl == 0) {
            asm volatile("cp.async.bulk.tensor.3d.global.shared::cta.bulk_group [%0, {%2, %3, %4}], [%1];"
                         ::"l"(&tm_out), "r"(sb + RAW_OFF + slot * 4096), "r"(oc0), "r"(box * 128), "r"(0) : "memory");
            asm volatile("cp.async.bulk.commit_group;" ::: "memory");
          }
        }
        STAMP(10 + slot);
      }
    }
    if (wtid == 0 && atomicAdd(&g_ticket, 1u) == NCTA + NGATE - 1) { g_ticket = 0; g_epoch = epoch + 1; }
    if (wtid == 64) asm volatile("cp.async.bulk.wait_group.read 0;" ::: "memory");
    STAMP(15);
    return;
  }
  asm volatile("barrier.cluster.arrive.relaxed.aligned;" ::: "memory");

  const int moff = (bid * 4 + (tid >> 7)) * NM + (tid & 63) * 2;
  const int brt = (tid >> 6) & 1;
  const __nv_bfloat16* const* tp = p.t + (brt ? 0 : 6);
  const uint32_t q0 = *(const uint32_t*)(tp[0] + moff), q1 = *(const uint32_t*)(tp[1] + moff);
  const uint32_t q2 = *(const uint32_t*)(tp[2] + moff), q3 = *(const uint32_t*)(tp[3] + moff);
  const uint2 ldt4 = *(const uint2*)(tp[4] + bid * 4);
  const uint32_t q4 = *(const uint32_t*)(tp[brt ? 2 : 5] + moff), q5 = *(const uint32_t*)(tp[brt ? 3 : 6] + moff);

  for (int i = wtid & 63; i < R_BR / 16; i += 64) sts128(cb + R_OFF + br * R_BR + i * 16, 0, 0, 0, 0);
  STAMP(1);

  float acc[5][4];
  float k2048 = 0.f;
  const uint32_t scr = cb + Y0_OFF + wq * SCR_BYTES;
  const uint32_t scr2 = sb + XIN_OFF + warp * 640;
  {
    const uint32_t ldt2 = (ch & 2) ? ldt4.y : ldt4.x;
    const float dt = bf_round(expf((ch & 1) ? bf_hi(ldt2) : bf_lo(ldt2)));
#pragma unroll
    for (int i = 0; i < 5; i++) acc[i][0] = acc[i][1] = acc[i][2] = acc[i][3] = 0.f;
    STAMP(2);
    const uint32_t tb = scr + lane * 16;
    const uint32_t ta = scr + (lane >> 3) * 512 + (lane & 7) * 16;
    const uint32_t tc = ((lane & 8) ? scr2 : scr + 4096) + (lane >> 4) * 128 + (lane & 7) * 16;
    const uint32_t tm = scr2 + 512 + ((lane >> 3) & 1) * 64 + (lane >> 4) * 16;
#pragma unroll 1
    for (int r = 0; r < 2; r++) {
      cf c, z1, z128;
      {
        const uint32_t sh = r ? 0x3244u : 0x1044u;
        float v0 = __uint_as_float(__byte_perm(q0, 0, sh));
        const float v1 = __uint_as_float(__byte_perm(q1, 0, sh)), v2 = __uint_as_float(__byte_perm(q2, 0, sh)), v3 = __uint_as_float(__byte_perm(q3, 0, sh));
        if (br == 0) { c = cmul(cf{v2, v3}, cf{dt * __uint_as_float(__byte_perm(q4, 0, sh)), dt * __uint_as_float(__byte_perm(q5, 0, sh))}); }
        else { v0 = -bf_round(expf(v0)); c = cf{2.f * dt * v2, 2.f * dt * v3}; }
        const float xl = (dt * v0) * 1.4426950408889634f, y = dt * v1;
        z1 = cexp_p(xl, y, 1.f); z128 = cexp_p(xl, y, 128.f);
      }
      const cf z2 = csq(z1), z4 = csq(z2), z8 = csq(z4);
      const cf w8 = {z8.re, -z8.im};
      const cf z16 = csq(w8), z24 = cmul(z16, w8), z32 = csq(z16), z40 = cmul(z32, w8), z48 = csq(z24), z56 = cmul(z32, z24), z64 = csq(z32);
      const cf z256 = csq(z128), z512 = csq(z256), z1024 = csq(z512), z2048 = csq(z1024);
      {
        float kk = fmaf(c.re, z2048.re, -c.im * z2048.im);
#pragma unroll
        for (int o = 16; o; o >>= 1) kk += __shfl_xor_sync(0xffffffffu, kk, o);
        k2048 += kk;
      }
      __syncwarp();
      {
        uint32_t xr[4] = {pack_bf16(1.f, z8.re), pack_bf16(z16.re, z24.re), pack_bf16(z32.re, z40.re), pack_bf16(z48.re, z56.re)};
        uint32_t xi[4] = {pack_bf16(0.f, w8.im), pack_bf16(z16.im, z24.im), pack_bf16(z32.im, z40.im), pack_bf16(z48.im, z56.im)};
        sts128(tb + 0 * 512, xr[0], xr[1], xr[2], xr[3]);
        sts128(tb + 2 * 512, xi[0], xi[1], xi[2], xi[3]);
        const uint32_t yr = pack_bf16(z64.re, z64.re), yi = pack_bf16(z64.im, z64.im), nyi = yi ^ 0x80008000u;
        uint32_t o[4], q[4];
#pragma unroll
        for (int i = 0; i < 4; i++) CMUL2(o[i], q[i], xr[i], xi[i], yr, yi, nyi);
        sts128(tb + 1 * 512, o[0], o[1], o[2], o[3]);
        sts128(tb + 3 * 512, q[0], q[1], q[2], q[3]);
      }
      {
        const cf h1 = cmul(c, z128), h2 = cmul(c, z256), h3 = cmul(h1, z256), h4 = cmul(c, z512), h5 = cmul(h1, z512), h6 = cmul(h2, z512), h7 = cmul(h3, z512);
        const cf e1 = cmul(c, z1), e2 = cmul(c, z2), e3 = cmul(e1, z2), e129 = cmul(h1, z1), e130 = cmul(h1, z2), e131 = cmul(e129, z2);
        const cf e258 = cmul(h2, z2), e386 = cmul(h3, z2);
        const uint32_t pr0 = pack_bf16(c.re, e1.re), pr2 = pack_bf16(h1.re, e129.re), pi0 = pack_bf16(c.im, e1.im), pi2 = pack_bf16(h1.im, e129.im);
        sts128(tb + 4 * 512, pr0, pack_bf16(e2.re, e3.re), pr2, pack_bf16(e130.re, e131.re));
        sts128(tb + 5 * 512, pi0, pack_bf16(e2.im, e3.im), pi2, pack_bf16(e130.im, e131.im));
        uint32_t xr[4] = {pack_bf16(h2.re, e258.re), pack_bf16(h3.re, e386.re), pack_bf16(h4.re, h5.re), pack_bf16(h6.re, h7.re)};
        uint32_t xi[4] = {pack_bf16(h2.im, e258.im), pack_bf16(h3.im, e386.im), pack_bf16(h4.im, h5.im), pack_bf16(h6.im, h7.im)};
        sts128(tb + 6 * 512, xr[0], xr[1], xr[2], xr[3]);
        sts128(tb + 7 * 512, xi[0], xi[1], xi[2], xi[3]);
        xr[1] = __byte_perm(xr[0], xr[1], 0x5410); xi[1] = __byte_perm(xi[0], xi[1], 0x5410);
        xr[0] = __byte_perm(pr0, pr2, 0x5410); xi[0] = __byte_perm(pi0, pi2, 0x5410);
        const uint32_t yr = pack_bf16(z1024.re, z1024.re), yi = pack_bf16(z1024.im, z1024.im), nyi = yi ^ 0x80008000u;
        uint32_t o[4], q[4];
#pragma unroll
        for (int i = 0; i < 4; i++) CMUL2(o[i], q[i], xr[i], xi[i], yr, yi, nyi);
        sts128(tb + 8 * 512, o[0], o[1], o[2], o[3]);
        sts128(scr2 + lane * 16, q[0], q[1], q[2], q[3]);
        const uint32_t m4 = pack_bf16(z4.re, z4.im);
        sts16(scr2 + 512 + lane * 2, m4); sts16(scr2 + 576 + lane * 2, m4 >> 16);
      }
      __syncwarp();
#pragma unroll
      for (int kp = 0; kp < 2; kp++) {
        uint32_t rr[2], ri[2], yr[2], yi[2];
        ldsm4t(tc + kp * 256, rr[0], ri[0], rr[1], ri[1]);
        ldsm4(tm + kp * 32, yr[0], yi[0], yr[1], yi[1]);
#pragma unroll
        for (int k2 = 0; k2 < 2; k2++) {
          const int kk = kp * 2 + k2;
          uint32_t a0, a1, a2, a3, pr, pi, qr, qi, xr, xi;
          ldsm4t(ta + kk * 128, a0, a1, a2, a3);
          ldsm4t(ta + 2048 + kk * 128, pr, pi, qr, qi);
          const uint32_t nyi = yi[k2] ^ 0x80008000u;
          mma16816(acc[0], a0, a1, a2, a3, pr, pi);
          mma16816(acc[2], a0, a1, a2, a3, qr, qi);
          mma16816(acc[4], a0, a1, a2, a3, rr[k2], ri[k2]);
          CMUL2(xr, xi, pr, pi, yr[k2], yi[k2], nyi);
          mma16816(acc[1], a0, a1, a2, a3, xr, xi);
          CMUL2(xr, xi, qr, qi, yr[k2], yi[k2], nyi);
          mma16816(acc[3], a0, a1, a2, a3, xr, xi);
        }
      }
    }
  }
  STAMP(3);
  __syncwarp();
  {
    const uint32_t xs = scr + lane * 16;
#define OTH(i, k) __float_as_uint(hf ? acc[i][k] : acc[i][2 + (k)])
    sts128(xs, OTH(0, 0), OTH(0, 1), OTH(1, 0), OTH(1, 1));
    sts128(xs + 512, OTH(2, 0), OTH(2, 1), OTH(3, 0), OTH(3, 1));
    sts128(xs + 1024, OTH(4, 0), OTH(4, 1), __float_as_uint(k2048), 0);
#undef OTH
  }

  bar_sync(7 + (warp >> 1), 64);
  STAMP(4);
  {
    const uint32_t xo = cb + Y0_OFF + (wq ^ 1) * SCR_BYTES + lane * 16;
    const uint4 o0 = lds128(xo), o1 = lds128(xo + 512), o2 = lds128(xo + 1024);
    const uint32_t rb = cb + R_OFF + br * R_BR;
#define OWN(i, k) (hf ? acc[i][2 + (k)] : acc[i][k])
    const uint32_t vP = pack_bf16(OWN(0, 1) + __uint_as_float(o0.y), OWN(0, 0) + __uint_as_float(o0.x));
    const uint32_t vP4 = pack_bf16(OWN(1, 1) + __uint_as_float(o0.w), OWN(1, 0) + __uint_as_float(o0.z));
    const uint32_t vQ = pack_bf16(OWN(2, 1) + __uint_as_float(o1.y), OWN(2, 0) + __uint_as_float(o1.x));
    const uint32_t vQ4 = pack_bf16(OWN(3, 1) + __uint_as_float(o1.w), OWN(3, 0) + __uint_as_float(o1.z));
    const uint32_t vR = pack_bf16(OWN(4, 1) + __uint_as_float(o2.y), OWN(4, 0) + __uint_as_float(o2.x));
#undef OWN
    const int j = g + 8 * hf;
    {
      const int a = 2 * (t & 1) + 64 * (t & 2) + 8 * j;
      const uint32_t ad = rb + 2 * (RD_X0 - 1 - a);
      const uint32_t a1 = (t & 2) ? ad - 8 : ad, a2 = (t & 2) ? ad : ad - 8;
      const uint32_t w1 = (t & 2) ? vP4 : vP, w2 = (t & 2) ? vP : vP4;
      sts32(a1, w1); sts32(a2, w2);
      sts16(a1 + RD_CS + 2, w1); sts16(a1 + RD_CS + 4, w1 >> 16);
      sts16(a2 + RD_CS + 2, w2); sts16(a2 + RD_CS + 4, w2 >> 16);
    }
    if (t < 2) {
      const int b = 256 + 128 * t + 8 * j;
      const uint32_t ad = rb + 2 * (RD_X0 - 6 - b);
      const uint32_t v22 = __byte_perm(vQ4, 0, 0x3232), v00 = __byte_perm(vQ, 0, 0x3232);
      sts16(ad, vQ4);
      sts64(ad + 2, v22, __byte_perm(vQ4, vQ, 0x5432));
      sts32(ad + 10, v00);
      if (b != 256) { sts16(ad + 14, v00); sts128(ad + RD_CS + 2, vQ4, v22, vQ, v00); }
      else { sts64(ad + RD_CS + 2, vQ4, v22); sts32(ad + RD_CS + 10, vQ); sts16(ad + RD_CS + 14, v00); }
    } else {
      const uint32_t ao = rb + R_O2 + 2 * (159 - (32 * t + j)), ae = ao - (R_O2 - R_E2) + 2;
      sts16(ao, vQ4 >> 16); sts16(ao + RS_CS + 2, vQ4 >> 16); sts16(ao - 32, vQ4); sts16(ao - 32 + RS_CS + 2, vQ4);
      sts16(ae - 32, vQ); sts16(ae - 32 + RS_CS + 2, vQ);
      if (lane != 2 || hf) { sts16(ae, vQ >> 16); sts16(ae + RS_CS + 2, vQ >> 16); }
      else {
        const uint32_t vv = __byte_perm(vQ, 0, 0x3232), ad = rb + 2 * (RD_X0 - 514);
        sts16(ad, vv); sts32(ad + 2, vv); sts16(ad + 6, vv); sts64(ad + RD_CS + 2, vv, vv);
      }
    }
    {
      const uint32_t a = rb + ((g & 1) ? R_O3 : R_E3 + 2) + 2 * (159 - (64 + 16 * t + (j >> 1)));
      const bool p1024 = (lane == 0) && (hf == 0);
      const uint32_t a00 = p1024 ? rb + R_E2 + 2 * (159 - 127) : a;
      sts16(a00, vR >> 16); sts16(a00 + RS_CS + 2, vR >> 16);
      sts16(a - 16, vR); sts16(a - 16 + RS_CS + 2, vR);
      if (p1024) {
        sts32(sb + K1024_OFF + (ch * 2 + br) * 4, __byte_perm(vR, 0, 0x3232));
        const uint32_t kv = pack_bf16(k2048 + __uint_as_float(o2.z), 0.f);
        sts16(rb + R_E3 + 2 * (159 - 127), kv); sts16(rb + R_E3 + 2 * (159 - 127) + RS_CS + 2, kv);
      }
    }
  }
  STAMP(5);
  asm volatile("barrier.cluster.wait.aligned;" ::: "memory");
  bar_sync(7 + (warp >> 1), 64);
  mbar_wait(sb + B_U);
  STAMP(6);

  const uint32_t zz = lds32(cb + R_OFF + br * R_BR);
  conv_dense(sb, cb, zz);
  STAMP(8);
  {
    const int x = (4 + ch) * 128 + wtid, c = x >> 2;
    const uint2 dA = ldg64(p.A_D + bid * 4), dB = ldg64(p.B_D + bid * 4);
    const uint2 gl = gate_ld(x);
    const uint32_t rb = cb + R_OFF + br * R_BR;
    float e48[24], e40[20], e32[16], h32[16], h16[8];
    const int x1 = 159 - (16 * hf + g - 2 * t + 136);
    const uint32_t fs = rb + ((g & 1) ? 2 * x1 : RS_CS + 2 * x1 + 2);
    uint32_t A[2][4][4];
    auto loadA = [&](int buf, uint32_t oe, uint32_t oo, int i0) {
#pragma unroll
      for (int a = 0; a < 2; a++) {
        const uint32_t base = fs + (a ? oo : oe) + i0 * 16;
        uint32_t* k0 = A[buf][2 * a];
        uint32_t* k1 = A[buf][2 * a + 1];
        k0[1] = lds32(base); k0[0] = lds32(base + 16); k0[2] = lds32(base + 32); k1[0] = lds32(base + 48); k1[2] = lds32(base + 64);
        k0[3] = k0[0]; k1[1] = k0[2]; k1[3] = k1[0];
      }
    };
    loadA(0, R_E2, R_O2, 8);
    loadA(1, R_E2, R_O2, 4);
    mbar_wait(sb + B_W);
    const uint64_t d5 = mkdesc(cb + W5_OFF, 144, 576), d3 = mkdesc(cb + W3_OFF, 144, 576);
    const uint64_t d9 = mkdesc(cb + W9_OFF, 144, 576), d7 = mkdesc(cb + W7_OFF, 144, 576);
    const uint32_t y2d = cb + Y2_OFF + br * 3072 + ysw(32 * (5 - (lane >> 4)) + 16 * hf + (lane & 15));
    const uint32_t y3d = cb + Y3_OFF + br * 2048 + ysw(2 * (16 * hf + (lane & 15)) + (lane >> 4));
#define FAR4(N, ACC, BUF, DA, DB, OFF, FIRST)                                                            \
    wg_fence();                                                                                           \
    _Pragma("unroll") for (int k = 0; k < 4; k++) {                                                      \
      const uint32_t* a = A[BUF][k];                                                                      \
      wgmma_rs<N, 1>(ACC, a[0], a[1], a[2], a[3], ((k >> 1) ? DB : DA) + (k & 1) * 18 + (OFF), !(FIRST) || k); \
    }                                                                                                     \
    wg_commit();
    FAR4(48, e48, 0, d5, d3, 0, 1)
    wg_wait0();
    loadA(0, R_E2, R_O2, 0);
    stsm2(y2d - 5 * 512, PK2(e48, 20), PK2(e48, 22));
#pragma unroll
    for (int i = 0; i < 20; i++) e40[i] = FCPY(e48[i]);
    stage_done(sb, 2, lane);
    FAR4(40, e40, 1, d5, d3, 36, 0)
    wg_wait0();
    loadA(1, R_E3, R_O3, 8);
    stsm2(y2d - 4 * 512, PK2(e40, 16), PK2(e40, 18));
#pragma unroll
    for (int i = 0; i < 16; i++) e32[i] = FCPY(e40[i]);
    stage_done(sb, 3, lane);
    FAR4(32, e32, 0, d5, d3, 72, 0)
    FAR4(32, h32, 1, d9, d7, 0, 1)
    wg_wait1();
    loadA(0, R_E3, R_O3, 4);
    stsm4(y2d, PK2(e32, 0), PK2(e32, 2), PK2(e32, 4), PK2(e32, 6));
    stsm4(y2d - 2 * 512, PK2(e32, 8), PK2(e32, 10), PK2(e32, 12), PK2(e32, 14));
    stage_done(sb, 4, lane);
    STAMP(9);
    wg_wait0();
    stsm4(y3d, PK2(h32, 8), PK2(h32, 10), PK2(h32, 12), PK2(h32, 14));
#pragma unroll
    for (int i = 0; i < 8; i++) h16[i] = FCPY(h32[i]);
    stage_done(sb, 5, lane);
    FAR4(16, h16, 0, d9, d7, 72, 0)
#undef FAR4
    const uint32_t yo = sb + CH_OFF + (x & 3) * 4 + ysw(c);
    uint32_t ua[4], ub[4], ya[4], yb[4], a2[4], b2[4], a3[4], b3[4], s2[4];
    skip_terms(ua, ub, sb, x, dA, dB);
    ld4ch(s2, sb + CH_OFF + (x & 3) * 4 + S2_OFF + ((c - 128) + ((c - 128) >> 3)) * 16);
    const uint32_t tag = lds32(sb + TAG_OFF);
    wg_wait0();
    stsm4(y3d + 1024, PK2(h16, 0), PK2(h16, 2), PK2(h16, 4), PK2(h16, 6));
    stage_done(sb, 6, lane);
    STAMP(10);
    const uint32_t g2 = gate_fin(p, gl, x, tag);
    mbar_wait(sb + B_ST + 8 * 4);
    const uint4 k0 = lds128(sb + K1024_OFF), k1 = lds128(sb + K1024_OFF + 16);
    const uint32_t kk[8] = {k0.x, k0.y, k0.z, k0.w, k1.x, k1.y, k1.z, k1.w};
    ld4ch(ya, yo + Y0_OFF); ld4ch(yb, yo + Y0_OFF + 4096);
    ld4ch(a2, yo + Y2_OFF - 1024); ld4ch(b2, yo + Y2_OFF - 1024 + 3072);
    mbar_wait(sb + B_ST + 8 * (5 + (ch >> 1)));
    STAMP(12);
    ld4ch(a3, yo + Y3_OFF - 2048); ld4ch(b3, yo + Y3_OFF - 2048 + 2048);
#pragma unroll
    for (int k = 0; k < 4; k++) {
      ya[k] = hadd2(ya[k], hadd2(hfma2(kk[2 * k], s2[k], a2[k]), a3[k]));
      yb[k] = hadd2(yb[k], hadd2(hfma2(kk[2 * k + 1], s2[k], b2[k]), b3[k]));
    }
    const uint4 r = mix(ya, yb, ua, ub, g2);
    if ((uint32_t)(ch & 1) != rank) send_box(sb, 2 + (ch >> 1), wtid, rank, r);
    else merge_box(sb, &tm_out, 2 + (ch >> 1), wtid, rank, oc0, r, 1 + ch);
  }
  STAMP(14);
  if (wtid == 0) asm volatile("cp.async.bulk.wait_group.read 0;" ::: "memory");
  STAMP(15); GT(1);
}

typedef CUresult (*EncodeFn)(CUtensorMap*, CUtensorMapDataType, cuuint32_t, void*, const cuuint64_t*, const cuuint64_t*,
                             const cuuint32_t*, const cuuint32_t*, CUtensorMapInterleave, CUtensorMapSwizzle,
                             CUtensorMapL2promotion, CUtensorMapFloatOOBfill);

}

extern "C" void kernel_launch(void* const* d_in, const int* in_sizes, int n_in, void* d_out, int out_size) {
  (void)in_sizes; (void)n_in; (void)out_size;
  typedef const __nv_bfloat16* bp;
  Params p;
  p.t[0] = (bp)d_in[10]; p.t[1] = (bp)d_in[11]; p.t[2] = (bp)d_in[12]; p.t[3] = (bp)d_in[13]; p.t[4] = (bp)d_in[14]; p.t[5] = nullptr;
  p.t[6] = (bp)d_in[1]; p.t[7] = (bp)d_in[2]; p.t[8] = (bp)d_in[5]; p.t[9] = (bp)d_in[6]; p.t[10] = (bp)d_in[7];
  p.t[11] = (bp)d_in[3]; p.t[12] = (bp)d_in[4]; p.t[13] = nullptr;
  p.u = (bp)d_in[0]; p.gw = (bp)d_in[16]; p.A_D = (bp)d_in[8]; p.B_D = (bp)d_in[15];
  static EncodeFn enc = nullptr;
  if (!enc) {
    cudaDriverEntryPointQueryResult qr;
    cudaGetDriverEntryPoint("cuTensorMapEncodeTiled", (void**)&enc, cudaEnableDefault, &qr);
    cudaFuncSetAttribute(ssm_kernel, cudaFuncAttributeMaxDynamicSharedMemorySize, SMEM_BYTES);
  }
  CUtensorMap tm_in, tm_out;
  {
    cuuint64_t gd[5] = {512, 2, 4, 4, 64};
    cuuint64_t gs[4] = {1024, 8192, 2048, 32768};
    cuuint32_t bx[5] = {8, 2, 4, 4, 32};
    cuuint32_t es[5] = {1, 1, 1, 1, 1};
    enc(&tm_in, CU_TENSOR_MAP_DATA_TYPE_BFLOAT16, 5, d_in[0], gd, gs, bx, es, CU_TENSOR_MAP_INTERLEAVE_NONE,
        CU_TENSOR_MAP_SWIZZLE_NONE, CU_TENSOR_MAP_L2_PROMOTION_NONE, CU_TENSOR_MAP_FLOAT_OOB_FILL_NONE);
  }
  {
    cuuint64_t gd[3] = {512, 1024, 2};
    cuuint64_t gs[2] = {2048, 1024};
    cuuint32_t bx[3] = {8, 128, 2};
    cuuint32_t es[3] = {1, 1, 1};
    enc(&tm_out, CU_TENSOR_MAP_DATA_TYPE_BFLOAT16, 3, d_out, gd, gs, bx, es, CU_TENSOR_MAP_INTERLEAVE_NONE,
        CU_TENSOR_MAP_SWIZZLE_NONE, CU_TENSOR_MAP_L2_PROMOTION_NONE, CU_TENSOR_MAP_FLOAT_OOB_FILL_NONE);
  }
  ssm_kernel<<<NCTA + NGATE, 640, SMEM_BYTES, cudaStreamPerThread>>>(p, tm_in, tm_out);
}
```

```cpp
#include <cuda_runtime.h>
#include <cuda.h>
#include <cuda_bf16.h>
#include <stdint.h>

namespace {
#define FCPY(x) __uint_as_float(opq(__float_as_uint(x), zz))

constexpr int L = 2048, D = 512, NM = 128;
constexpr int NCTA = 128;
constexpr int NGATE = 4;

constexpr int RAW_OFF = 0;
constexpr int XIN_OFF = 32768;
constexpr int BAR_OFF = XIN_OFF + 10240;
constexpr int CH_OFF = BAR_OFF + 256;
constexpr int U_CS = 1184;
constexpr int U_OFF = 0;
constexpr int R_OFF = 4736;
constexpr int RD_X0 = 565;
constexpr int RD_CS = 1216;
constexpr int RS_CS = 320;
constexpr int R_E2 = 2 * RD_CS, R_O2 = R_E2 + 2 * RS_CS, R_E3 = R_O2 + 2 * RS_CS, R_O3 = R_E3 + 2 * RS_CS;
constexpr int R_BR = R_O3 + 2 * RS_CS;
constexpr int W5_OFF = R_OFF + 2 * R_BR;
constexpr int W3_OFF = W5_OFF + 3456;
constexpr int W9_OFF = W3_OFF + 3456;
constexpr int W7_OFF = W9_OFF + 2304;
constexpr int S2_OFF = W7_OFF + 2304;
constexpr int Y0_OFF = S2_OFF + 2304;
constexpr int Y2_OFF = Y0_OFF + 8192, Y3_OFF = Y2_OFF + 6144;
constexpr int CH_BYTES = Y0_OFF + 18432 + 16;
constexpr int SCR_BYTES = 4608;
constexpr int SMEM_BYTES = CH_OFF + 4 * CH_BYTES;
static_assert(CH_BYTES % 128 == 16, "bank staggering of the channel blocks");
static_assert(SMEM_BYTES <= 232448, "smem");
constexpr int B_RAW = BAR_OFF, B_X = BAR_OFF + 8, B_U = BAR_OFF + 40, B_W = BAR_OFF + 48;
constexpr int TAG_OFF = BAR_OFF + 56;
constexpr int K1024_OFF = BAR_OFF + 64;
constexpr int B_ST = BAR_OFF + 96;

__device__ unsigned int g_gate[L];
__device__ unsigned int g_epoch;
__device__ unsigned int g_ticket;

#define STAMP(k)
#define GT(k)

struct Params {
  const __nv_bfloat16* t[14];
  const __nv_bfloat16 *u, *gw, *A_D, *B_D;
};

template <int N, int TB> __device__ __forceinline__ void wgmma_rs(float* d, uint32_t a0, uint32_t a1, uint32_t a2, uint32_t a3, uint64_t desc, int sc);
template <> __device__ __forceinline__ void wgmma_rs<64, 0>(float* d, uint32_t a0, uint32_t a1, uint32_t a2, uint32_t a3, uint64_t desc, int sc) {
  asm volatile("{\n.reg .pred p;\nsetp.ne.b32 p, %37, 0;\n"
    "wgmma.mma_async.sync.aligned.m64n64k16.f32.bf16.bf16 {%0,%1,%2,%3,%4,%5,%6,%7,%8,%9,%10,%11,%12,%13,%14,%15,%16,%17,%18,%19,%20,%21,%22,%23,%24,%25,%26,%27,%28,%29,%30,%31}, {%32,%33,%34,%35}, %36, p, 1, 1, 0;\n}"
    : "+f"(d[0]), "+f"(d[1]), "+f"(d[2]), "+f"(d[3]), "+f"(d[4]), "+f"(d[5]), "+f"(d[6]), "+f"(d[7]), "+f"(d[8]), "+f"(d[9]), "+f"(d[10]), "+f"(d[11]), "+f"(d[12]), "+f"(d[13]), "+f"(d[14]), "+f"(d[15]), "+f"(d[16]), "+f"(d[17]), "+f"(d[18]), "+f"(d[19]), "+f"(d[20]), "+f"(d[21]), "+f"(d[22]), "+f"(d[23]), "+f"(d[24]), "+f"(d[25]), "+f"(d[26]), "+f"(d[27]), "+f"(d[28]), "+f"(d[29]), "+f"(d[30]), "+f"(d[31]) : "r"(a0), "r"(a1), "r"(a2), "r"(a3), "l"(desc), "r"(sc));
}
template <> __device__ __forceinline__ void wgmma_rs<56, 0>(float* d, uint32_t a0, uint32_t a1, uint32_t a2, uint32_t a3, uint64_t desc, int sc) {
  asm volatile("{\n.reg .pred p;\nsetp.ne.b32 p, %33, 0;\n"
    "wgmma.mma_async.sync.aligned.m64n56k16.f32.bf16.bf16 {%0,%1,%2,%3,%4,%5,%6,%7,%8,%9,%10,%11,%12,%13,%14,%15,%16,%17,%18,%19,%20,%21,%22,%23,%24,%25,%26,%27}, {%28,%29,%30,%31}, %32, p, 1, 1, 0;\n}"
    : "+f"(d[0]), "+f"(d[1]), "+f"(d[2]), "+f"(d[3]), "+f"(d[4]), "+f"(d[5]), "+f"(d[6]), "+f"(d[7]), "+f"(d[8]), "+f"(d[9]), "+f"(d[10]), "+f"(d[11]), "+f"(d[12]), "+f"(d[13]), "+f"(d[14]), "+f"(d[15]), "+f"(d[16]), "+f"(d[17]), "+f"(d[18]), "+f"(d[19]), "+f"(d[20]), "+f"(d[21]), "+f"(d[22]), "+f"(d[23]), "+f"(d[24]), "+f"(d[25]), "+f"(d[26]), "+f"(d[27]) : "r"(a0), "r"(a1), "r"(a2), "r"(a3), "l"(desc), "r"(sc));
}
template <> __device__ __forceinline__ void wgmma_rs<48, 0>(float* d, uint32_t a0, uint32_t a1, uint32_t a2, uint32_t a3, uint64_t desc, int sc) {
  asm volatile("{\n.reg .pred p;\nsetp.ne.b32 p, %29, 0;\n"
    "wgmma.mma_async.sync.aligned.m64n48k16.f32.bf16.bf16 {%0,%1,%2,%3,%4,%5,%6,%7,%8,%9,%10,%11,%12,%13,%14,%15,%16,%17,%18,%19,%20,%21,%22,%23}, {%24,%25,%26,%27}, %28, p, 1, 1, 0;\n}"
    : "+f"(d[0]), "+f"(d[1]), "+f"(d[2]), "+f"(d[3]), "+f"(d[4]), "+f"(d[5]), "+f"(d[6]), "+f"(d[7]), "+f"(d[8]), "+f"(d[9]), "+f"(d[10]), "+f"(d[11]), "+f"(d[12]), "+f"(d[13]), "+f"(d[14]), "+f"(d[15]), "+f"(d[16]), "+f"(d[17]), "+f"(d[18]), "+f"(d[19]), "+f"(d[20]), "+f"(d[21]), "+f"(d[22]), "+f"(d[23]) : "r"(a0), "r"(a1), "r"(a2), "r"(a3), "l"(desc), "r"(sc));
}
template <> __device__ __forceinline__ void wgmma_rs<32, 0>(float* d, uint32_t a0, uint32_t a1, uint32_t a2, uint32_t a3, uint64_t desc, int sc) {
  asm volatile("{\n.reg .pred p;\nsetp.ne.b32 p, %21, 0;\n"
    "wgmma.mma_async.sync.aligned.m64n32k16.f32.bf16.bf16 {%0,%1,%2,%3,%4,%5,%6,%7,%8,%9,%10,%11,%12,%13,%14,%15}, {%16,%17,%18,%19}, %20, p, 1, 1, 0;\n}"
    : "+f"(d[0]), "+f"(d[1]), "+f"(d[2]), "+f"(d[3]), "+f"(d[4]), "+f"(d[5]), "+f"(d[6]), "+f"(d[7]), "+f"(d[8]), "+f"(d[9]), "+f"(d[10]), "+f"(d[11]), "+f"(d[12]), "+f"(d[13]), "+f"(d[14]), "+f"(d[15]) : "r"(a0), "r"(a1), "r"(a2), "r"(a3), "l"(desc), "r"(sc));
}
template <> __device__ __forceinline__ void wgmma_rs<48, 1>(float* d, uint32_t a0, uint32_t a1, uint32_t a2, uint32_t a3, uint64_t desc, int sc) {
  asm volatile("{\n.reg .pred p;\nsetp.ne.b32 p, %29, 0;\n"
    "wgmma.mma_async.sync.aligned.m64n48k16.f32.bf16.bf16 {%0,%1,%2,%3,%4,%5,%6,%7,%8,%9,%10,%11,%12,%13,%14,%15,%16,%17,%18,%19,%20,%21,%22,%23}, {%24,%25,%26,%27}, %28, p, 1, 1, 1;\n}"
    : "+f"(d[0]), "+f"(d[1]), "+f"(d[2]), "+f"(d[3]), "+f"(d[4]), "+f"(d[5]), "+f"(d[6]), "+f"(d[7]), "+f"(d[8]), "+f"(d[9]), "+f"(d[10]), "+f"(d[11]), "+f"(d[12]), "+f"(d[13]), "+f"(d[14]), "+f"(d[15]), "+f"(d[16]), "+f"(d[17]), "+f"(d[18]), "+f"(d[19]), "+f"(d[20]), "+f"(d[21]), "+f"(d[22]), "+f"(d[23]) : "r"(a0), "r"(a1), "r"(a2), "r"(a3), "l"(desc), "r"(sc));
}
template <> __device__ __forceinline__ void wgmma_rs<40, 1>(float* d, uint32_t a0, uint32_t a1, uint32_t a2, uint32_t a3, uint64_t desc, int sc) {
  asm volatile("{\n.reg .pred p;\nsetp.ne.b32 p, %25, 0;\n"
    "wgmma.mma_async.sync.aligned.m64n40k16.f32.bf16.bf16 {%0,%1,%2,%3,%4,%5,%6,%7,%8,%9,%10,%11,%12,%13,%14,%15,%16,%17,%18,%19}, {%20,%21,%22,%23}, %24, p, 1, 1, 1;\n}"
    : "+f"(d[0]), "+f"(d[1]), "+f"(d[2]), "+f"(d[3]), "+f"(d[4]), "+f"(d[5]), "+f"(d[6]), "+f"(d[7]), "+f"(d[8]), "+f"(d[9]), "+f"(d[10]), "+f"(d[11]), "+f"(d[12]), "+f"(d[13]), "+f"(d[14]), "+f"(d[15]), "+f"(d[16]), "+f"(d[17]), "+f"(d[18]), "+f"(d[19]) : "r"(a0), "r"(a1), "r"(a2), "r"(a3), "l"(desc), "r"(sc));
}
template <> __device__ __forceinline__ void wgmma_rs<32, 1>(float* d, uint32_t a0, uint32_t a1, uint32_t a2, uint32_t a3, uint64_t desc, int sc) {
  asm volatile("{\n.reg .pred p;\nsetp.ne.b32 p, %21, 0;\n"
    "wgmma.mma_async.sync.aligned.m64n32k16.f32.bf16.bf16 {%0,%1,%2,%3,%4,%5,%6,%7,%8,%9,%10,%11,%12,%13,%14,%15}, {%16,%17,%18,%19}, %20, p, 1, 1, 1;\n}"
    : "+f"(d[0]), "+f"(d[1]), "+f"(d[2]), "+f"(d[3]), "+f"(d[4]), "+f"(d[5]), "+f"(d[6]), "+f"(d[7]), "+f"(d[8]), "+f"(d[9]), "+f"(d[10]), "+f"(d[11]), "+f"(d[12]), "+f"(d[13]), "+f"(d[14]), "+f"(d[15]) : "r"(a0), "r"(a1), "r"(a2), "r"(a3), "l"(desc), "r"(sc));
}
template <> __device__ __forceinline__ void wgmma_rs<16, 1>(float* d, uint32_t a0, uint32_t a1, uint32_t a2, uint32_t a3, uint64_t desc, int sc) {
  asm volatile("{\n.reg .pred p;\nsetp.ne.b32 p, %13, 0;\n"
    "wgmma.mma_async.sync.aligned.m64n16k16.f32.bf16.bf16 {%0,%1,%2,%3,%4,%5,%6,%7}, {%8,%9,%10,%11}, %12, p, 1, 1, 1;\n}"
    : "+f"(d[0]), "+f"(d[1]), "+f"(d[2]), "+f"(d[3]), "+f"(d[4]), "+f"(d[5]), "+f"(d[6]), "+f"(d[7]) : "r"(a0), "r"(a1), "r"(a2), "r"(a3), "l"(desc), "r"(sc));
}

__device__ __forceinline__ uint32_t pack_bf16(float lo, float hi) {
  uint32_t r; asm("cvt.rn.bf16x2.f32 %0, %1, %2;" : "=r"(r) : "f"(hi), "f"(lo)); return r;
}
__device__ __forceinline__ float bf_lo(uint32_t v) { return __uint_as_float(v << 16); }
__device__ __forceinline__ float bf_hi(uint32_t v) { return __uint_as_float(v & 0xffff0000u); }
__device__ __forceinline__ float bf_round(float x) { return bf_lo(pack_bf16(x, 0.f)); }
__device__ __forceinline__ uint32_t hmul2(uint32_t a, uint32_t b) { uint32_t r; asm("mul.rn.bf16x2 %0, %1, %2;" : "=r"(r) : "r"(a), "r"(b)); return r; }
__device__ __forceinline__ uint32_t hadd2(uint32_t a, uint32_t b) { uint32_t r; asm("add.rn.bf16x2 %0, %1, %2;" : "=r"(r) : "r"(a), "r"(b)); return r; }
__device__ __forceinline__ uint32_t hsub2(uint32_t a, uint32_t b) { uint32_t r; asm("sub.rn.bf16x2 %0, %1, %2;" : "=r"(r) : "r"(a), "r"(b)); return r; }
__device__ __forceinline__ uint32_t hfma2(uint32_t a, uint32_t b, uint32_t c) { uint32_t r; asm("fma.rn.bf16x2 %0, %1, %2, %3;" : "=r"(r) : "r"(a), "r"(b), "r"(c)); return r; }

__device__ __forceinline__ void sts16(uint32_t a, uint32_t v) { asm volatile("st.shared.b16 [%0], %1;" ::"r"(a), "h"((unsigned short)v) : "memory"); }
__device__ __forceinline__ void sts32(uint32_t a, uint32_t v) { asm volatile("st.shared.b32 [%0], %1;" ::"r"(a), "r"(v) : "memory"); }
__device__ __forceinline__ void sts64(uint32_t a, uint32_t x, uint32_t y) { asm volatile("st.shared.v2.b32 [%0], {%1,%2};" ::"r"(a), "r"(x), "r"(y) : "memory"); }
__device__ __forceinline__ void sts128(uint32_t a, uint32_t x, uint32_t y, uint32_t z, uint32_t w) {
  asm volatile("st.shared.v4.b32 [%0], {%1,%2,%3,%4};" ::"r"(a), "r"(x), "r"(y), "r"(z), "r"(w) : "memory");
}
__device__ __forceinline__ uint32_t lds32(uint32_t a) { uint32_t v; asm volatile("ld.shared.b32 %0, [%1];" : "=r"(v) : "r"(a) : "memory"); return v; }
__device__ __forceinline__ uint2 lds64(uint32_t a) { uint2 v; asm volatile("ld.shared.v2.b32 {%0,%1}, [%2];" : "=r"(v.x), "=r"(v.y) : "r"(a) : "memory"); return v; }
__device__ __forceinline__ uint4 lds128(uint32_t a) {
  uint4 v; asm volatile("ld.shared.v4.b32 {%0,%1,%2,%3}, [%4];" : "=r"(v.x), "=r"(v.y), "=r"(v.z), "=r"(v.w) : "r"(a) : "memory"); return v;
}
__device__ __forceinline__ uint4 ldg128(const void* a) {
  uint4 v; asm volatile("ld.global.nc.v4.b32 {%0,%1,%2,%3}, [%4];" : "=r"(v.x), "=r"(v.y), "=r"(v.z), "=r"(v.w) : "l"(a) : "memory"); return v;
}
__device__ __forceinline__ uint2 ldg64(const void* a) {
  uint2 v; asm volatile("ld.global.nc.v2.b32 {%0,%1}, [%2];" : "=r"(v.x), "=r"(v.y) : "l"(a) : "memory"); return v;
}
__device__ __forceinline__ void ldsm4(uint32_t a, uint32_t& r0, uint32_t& r1, uint32_t& r2, uint32_t& r3) {
  asm volatile("ldmatrix.sync.aligned.m8n8.x4.shared.b16 {%0,%1,%2,%3}, [%4];" : "=r"(r0), "=r"(r1), "=r"(r2), "=r"(r3) : "r"(a) : "memory");
}
__device__ __forceinline__ void ldsm4t(uint32_t a, uint32_t& r0, uint32_t& r1, uint32_t& r2, uint32_t& r3) {
  asm volatile("ldmatrix.sync.aligned.m8n8.x4.trans.shared.b16 {%0,%1,%2,%3}, [%4];" : "=r"(r0), "=r"(r1), "=r"(r2), "=r"(r3) : "r"(a) : "memory");
}
__device__ __forceinline__ void stsm4(uint32_t a, uint32_t r0, uint32_t r1, uint32_t r2, uint32_t r3) {
  asm volatile("stmatrix.sync.aligned.m8n8.x4.shared.b16 [%0], {%1,%2,%3,%4};" ::"r"(a), "r"(r0), "r"(r1), "r"(r2), "r"(r3) : "memory");
}
__device__ __forceinline__ void stsm4t(uint32_t a, uint32_t r0, uint32_t r1, uint32_t r2, uint32_t r3) {
  asm volatile("stmatrix.sync.aligned.m8n8.x4.trans.shared.b16 [%0], {%1,%2,%3,%4};" ::"r"(a), "r"(r0), "r"(r1), "r"(r2), "r"(r3) : "memory");
}
__device__ __forceinline__ void stsm2(uint32_t a, uint32_t r0, uint32_t r1) {
  asm volatile("stmatrix.sync.aligned.m8n8.x2.shared.b16 [%0], {%1,%2};" ::"r"(a), "r"(r0), "r"(r1) : "memory");
}
__device__ __forceinline__ void stsm2t(uint32_t a, uint32_t r0, uint32_t r1) {
  asm volatile("stmatrix.sync.aligned.m8n8.x2.trans.shared.b16 [%0], {%1,%2};" ::"r"(a), "r"(r0), "r"(r1) : "memory");
}
__device__ __forceinline__ void mma16816(float* c, uint32_t a0, uint32_t a1, uint32_t a2, uint32_t a3, uint32_t b0, uint32_t b1) {
  asm("mma.sync.aligned.m16n8k16.row.col.f32.bf16.bf16.f32 {%0,%1,%2,%3}, {%4,%5,%6,%7}, {%8,%9}, {%0,%1,%2,%3};"
      : "+f"(c[0]), "+f"(c[1]), "+f"(c[2]), "+f"(c[3]) : "r"(a0), "r"(a1), "r"(a2), "r"(a3), "r"(b0), "r"(b1));
}
__device__ __forceinline__ void bar_sync(int id, int n) { asm volatile("bar.sync %0, %1;" ::"r"(id), "r"(n) : "memory"); }
__device__ __forceinline__ void bar_arrive(int id, int n) { asm volatile("bar.arrive %0, %1;" ::"r"(id), "r"(n) : "memory"); }
__device__ __forceinline__ void wg_fence() { asm volatile("wgmma.fence.sync.aligned;" ::: "memory"); }
__device__ __forceinline__ void wg_commit() { asm volatile("wgmma.commit_group.sync.aligned;" ::: "memory"); }
__device__ __forceinline__ void wg_wait0() { asm volatile("wgmma.wait_group.sync.aligned 0;" ::: "memory"); }
__device__ __forceinline__ void wg_wait1() { asm volatile("wgmma.wait_group.sync.aligned 1;" ::: "memory"); }
__device__ __forceinline__ void fence_async() { asm volatile("fence.proxy.async.shared::cta;" ::: "memory"); }
__device__ __forceinline__ uint32_t opq(uint32_t x, uint32_t z) { uint32_t r; asm volatile("xor.b32 %0, %1, %2;" : "=r"(r) : "r"(x), "r"(z)); return r; }
__device__ __forceinline__ uint64_t mkdesc(uint32_t addr, uint32_t lbo, uint32_t sbo) {
  return (uint64_t)((addr & 0x3FFFF) >> 4) | ((uint64_t)(lbo >> 4) << 16) | ((uint64_t)(sbo >> 4) << 32);
}
__device__ __forceinline__ uint32_t mapa(uint32_t a, uint32_t rank) {
  uint32_t r; asm("mapa.shared::cluster.u32 %0, %1, %2;" : "=r"(r) : "r"(a), "r"(rank)); return r;
}
__device__ __forceinline__ void mbar_init_expect(uint32_t bar, uint32_t bytes) {
  asm volatile("mbarrier.init.shared::cta.b64 [%0], 1;" ::"r"(bar) : "memory");
  asm volatile("mbarrier.arrive.expect_tx.shared::cta.b64 _, [%0], %1;" ::"r"(bar), "r"(bytes) : "memory");
}
__device__ __forceinline__ void mbar_wait(uint32_t bar) {
#pragma unroll 1
  for (int it = 0; it < (1 << 22); it++) {
    uint32_t ok;
    asm volatile("{\n.reg .pred p;\nmbarrier.try_wait.parity.acquire.cluster.shared::cta.b64 p, [%1], 0;\nselp.u32 %0, 1, 0, p;\n}"
                 : "=r"(ok) : "r"(bar) : "memory");
    if (ok) return;
  }
  __trap();
}
__device__ __forceinline__ void st_async4(uint32_t a, uint32_t bar, uint32_t x, uint32_t y, uint32_t z, uint32_t w) {
  asm volatile("st.async.weak.shared::cluster.mbarrier::complete_tx::bytes.v4.b32 [%0], {%2,%3,%4,%5}, [%1];"
               ::"r"(a), "r"(bar), "r"(x), "r"(y), "r"(z), "r"(w) : "memory");
}

struct cf { float re, im; };
__device__ __forceinline__ cf cmul(cf a, cf b) { return {fmaf(a.re, b.re, -a.im * b.im), fmaf(a.re, b.im, a.im * b.re)}; }
__device__ __forceinline__ cf csq(cf a) { return {fmaf(a.re, a.re, -a.im * a.im), (a.re + a.re) * a.im}; }
__device__ __forceinline__ cf cexp_p(float xl, float y, float p) {
  float mag; asm("ex2.approx.ftz.f32 %0, %1;" : "=f"(mag) : "f"(xl * p));
  const float th = y * p;
  const float k = __fadd_rn(fmaf(th, 0.15915494309189535f, 12582912.f), -12582912.f);
  float r = fmaf(k, -6.2831854820251465f, th);
  r = fmaf(k, 1.7484555314695172e-07f, r);
  return {mag * __cosf(r), mag * __sinf(r)};
}
__device__ __forceinline__ uint32_t ysw(int c) { return (uint32_t)(c ^ ((c >> 3) & 3)) * 16u; }

#define CMUL2(OR, OI, xr, xi, yr, yi, nyi) do { OR = hfma2(xr, yr, hmul2(xi, nyi)); OI = hfma2(xr, yi, hmul2(xi, yr)); } while (0)

__device__ __forceinline__ uint32_t gate_slow(const __nv_bfloat16* u, const __nv_bfloat16* gw, int row) {
  float s = 0.f;
  const uint32_t* xr = (const uint32_t*)(u + (size_t)row * D);
  const uint32_t* wr = (const uint32_t*)gw;
#pragma unroll 1
  for (int j = 0; j < D / 2; j++) { const uint32_t pr = hmul2(xr[j], wr[j]); s += bf_lo(pr); s += bf_hi(pr); }
  s = bf_round(s);
  return pack_bf16(1.f / (1.f + expf(-s)), 0.f);
}

__device__ __forceinline__ uint2 gate_ld(int x) {
  uint2 gv;
  asm volatile("ld.relaxed.gpu.global.v2.u32 {%0,%1}, [%2];" : "=r"(gv.x), "=r"(gv.y) : "l"(g_gate + x * 2) : "memory");
  return gv;
}
__device__ __noinline__ uint32_t gate_poll(const Params* pp, int x, uint32_t tag) {
  uint2 gv;
#pragma unroll 1
  for (int spins = 0; spins < (1 << 16); spins++) {
    gv = gate_ld(x);
    if ((gv.x >> 16) == tag && (gv.y >> 16) == tag) return __byte_perm(gv.x, gv.y, 0x5410);
  }
  return __byte_perm(gate_slow(pp->u, pp->gw, x * 2), gate_slow(pp->u, pp->gw, x * 2 + 1), 0x5410);
}
__device__ __forceinline__ uint32_t gate_fin(const Params& p, uint2 gv, int x, uint32_t tag) {
  if ((gv.x >> 16) == tag && (gv.y >> 16) == tag) return __byte_perm(gv.x, gv.y, 0x5410);
  return gate_poll(&p, x, tag);
}

__device__ __forceinline__ void ld4ch(uint32_t* v, uint32_t addr) {
#pragma unroll
  for (int k = 0; k < 4; k++) v[k] = lds32(addr + k * CH_BYTES);
}
__device__ __forceinline__ void skip_terms(uint32_t* ua, uint32_t* ub, uint32_t sb, int x, uint2 dA, uint2 dB) {
  const int c = x >> 2;
  uint32_t uu[4];
  ld4ch(uu, sb + CH_OFF + (x & 3) * 4 + U_OFF + (c & 3) * U_CS + (63 - (c >> 2)) * 16);
#pragma unroll
  for (int k = 0; k < 4; k++) {
    ua[k] = hmul2(uu[k], __byte_perm((k & 2) ? dA.y : dA.x, 0, (k & 1) ? 0x3232 : 0x1010));
    ub[k] = hmul2(uu[k], __byte_perm((k & 2) ? dB.y : dB.x, 0, (k & 1) ? 0x3232 : 0x1010));
  }
}
__device__ __forceinline__ uint4 mix(const uint32_t* a, const uint32_t* b, const uint32_t* ua, const uint32_t* ub, uint32_t g2) {
  const uint32_t h2 = hsub2(0x3f803f80u, g2);
  uint32_t o[4];
#pragma unroll
  for (int k = 0; k < 4; k++) o[k] = hadd2(hmul2(g2, hadd2(a[k], ua[k])), hmul2(h2, hadd2(b[k], ub[k])));
  return make_uint4(__byte_perm(o[0], o[1], 0x5410), __byte_perm(o[2], o[3], 0x5410), __byte_perm(o[0], o[1], 0x7632), __byte_perm(o[2], o[3], 0x7632));
}
__device__ __forceinline__ void send_box(uint32_t sb, int slot, int wtid, uint32_t rank, uint4 r) {
  st_async4(mapa(sb + XIN_OFF + slot * 2048 + wtid * 16, rank ^ 1), mapa(sb + B_X + slot * 8, rank ^ 1), r.x, r.y, r.z, r.w);
}
__device__ __forceinline__ void merge_box(uint32_t sb, const CUtensorMap* tm_out, int slot, int wtid, uint32_t rank, int oc0, uint4 r, int barid) {
  const uint32_t st = sb + RAW_OFF + slot * 4096 + wtid * 16;
  sts64(st + rank * 8, r.x, r.y); sts64(st + 2048 + rank * 8, r.z, r.w);
  mbar_wait(sb + B_X + slot * 8);
  const uint4 q = lds128(sb + XIN_OFF + slot * 2048 + wtid * 16);
  sts64(st + (rank ^ 1) * 8, q.x, q.y); sts64(st + 2048 + (rank ^ 1) * 8, q.z, q.w);
  fence_async();
  bar_sync(barid, 128);
  if (wtid == 0) {
    asm volatile("cp.async.bulk.tensor.3d.global.shared::cta.bulk_group [%0, {%2, %3, %4}], [%1];"
                 ::"l"(tm_out), "r"(sb + RAW_OFF + slot * 4096), "r"(oc0), "r"((2 * slot + (int)rank) * 128), "r"(0) : "memory");
    asm volatile("cp.async.bulk.commit_group;" ::: "memory");
  }
}

__device__ __forceinline__ uint32_t band2(int e, int lo, int hi) {
  uint32_t r = ((uint32_t)(e - lo) <= (uint32_t)(hi - lo) ? 0x3f80u : 0u) | ((uint32_t)(e - 1 - lo) <= (uint32_t)(hi - lo) ? 0x3f800000u : 0u);
  asm volatile("" : "+r"(r));
  return r;
}

__device__ __forceinline__ void stage_done(uint32_t sb, int stage, int lane) {
  __syncwarp();
  if (lane == 0) asm volatile("mbarrier.arrive.shared::cta.b64 _, [%0];" ::"r"(sb + B_ST + 8 * stage) : "memory");
}
#define PK2(v, i) pack_bf16(v[i], v[(i) + 1])

__device__ __forceinline__ void conv_dense(uint32_t sb, uint32_t cb, uint32_t zz) {
  const int lane = threadIdx.x & 31, wq = (threadIdx.x >> 5) & 3, br = wq >> 1, hf = wq & 1, g = lane >> 2, t = lane & 3;
  const uint32_t rb = cb + R_OFF + br * R_BR;
  const int eo = 16 * hf + g - 2 * t;
  const int x0 = RD_X0 - (eo + 536);
  const uint32_t fa = rb + ((g & 1) ? 2 * x0 : RD_CS + 2 * x0 + 2);
  const uint64_t ub = mkdesc(cb + U_OFF, U_CS, 128);
  const uint32_t yd = cb + Y0_OFF + br * 4096 + ysw(4 * (63 - 8 * (lane >> 4) - (lane & 7)) + 2 * hf + ((lane >> 3) & 1));
  uint32_t A[2][4][4];
  float e64[32], e56[28], e48[24];
  auto loadA = [&](int j) {
#pragma unroll
    for (int k = 0; k < 4; k++) {
      const int s = 34 - 4 * j - k;
      if (s >= 0) {
        if (k == 0 && j == 0) A[0][0][2] = lds32(fa + (2 * s + 2) * 16);
        A[j & 1][k][0] = lds32(fa + (2 * s + 1) * 16);
        A[j & 1][k][1] = lds32(fa + (2 * s) * 16);
      }
    }
#pragma unroll
    for (int k = 0; k < 4; k++) {
      if (34 - 4 * j - k >= 0) {
        A[j & 1][k][3] = A[j & 1][k][0];
        if (k) A[j & 1][k][2] = A[j & 1][k - 1][1];
        else if (j) A[j & 1][0][2] = A[(j - 1) & 1][3][1];
      }
    }
  };
  loadA(0); loadA(1);
#pragma unroll
  for (int j = 0; j < 9; j++) {
    if (j == 4) {
      wg_wait0();
      stsm2t(yd - 7 * 512, PK2(e64, 28), PK2(e64, 30));
#pragma unroll
      for (int i = 0; i < 28; i++) e56[i] = FCPY(e64[i]);
      stage_done(sb, 0, lane);
    }
    if (j == 8) {
      wg_wait0();
      stsm2t(yd - 6 * 512, PK2(e56, 24), PK2(e56, 26));
#pragma unroll
      for (int i = 0; i < 24; i++) e48[i] = FCPY(e56[i]);
      stage_done(sb, 1, lane);
    }
    wg_fence();
#pragma unroll
    for (int k = 0; k < 4; k++) {
      const int s = 34 - 4 * j - k;
      if (s >= 0) {
        const int o = 2 * s - 66 + 128;
        const int cc = o & 3, rs = (o >> 2) - 32;
        const uint64_t desc = ub + (uint64_t)((cc * U_CS - rs * 16) >> 4);
        const uint32_t* a = A[j & 1][k];
        if (j < 4) wgmma_rs<64, 0>(e64, a[0], a[1], a[2], a[3], desc, s != 34);
        else if (j < 8) wgmma_rs<56, 0>(e56, a[0], a[1], a[2], a[3], desc, 1);
        else wgmma_rs<48, 0>(e48, a[0], a[1], a[2], a[3], desc, 1);
      }
    }
    wg_commit();
    if (j >= 1 && j < 8) { wg_wait1(); loadA(j + 1); }
  }
  wg_wait0();
#pragma unroll
  for (int i = 0; i < 6; i += 2) stsm4t(yd - i * 512, PK2(e48, 4 * i), PK2(e48, 4 * i + 2), PK2(e48, 4 * i + 4), PK2(e48, 4 * i + 6));
}

__device__ __noinline__ void gate_cta(const Params* pp) {
  const __nv_bfloat16 *u = pp->u, *gw = pp->gw;
  const int lane = threadIdx.x & 31;
  unsigned int epoch;
  asm volatile("ld.relaxed.gpu.global.u32 %0, [%1];" : "=r"(epoch) : "l"(&g_epoch) : "memory");
  const uint4 gw0 = ldg128(gw + lane * 8), gw1 = ldg128(gw + 256 + lane * 8);
  const uint32_t ws[8] = {gw0.x, gw0.y, gw0.z, gw0.w, gw1.x, gw1.y, gw1.z, gw1.w};
  const uint32_t tag = (epoch + 1) & 0xffffu;
  uint4 gx[4][2], nx[4][2];
  int grow = (blockIdx.x * 20 + (threadIdx.x >> 5)) * 4;
#pragma unroll
  for (int i = 0; i < 4; i++) {
    nx[i][0] = ldg128(u + (size_t)(grow + i) * D + lane * 8);
    nx[i][1] = ldg128(u + (size_t)(grow + i) * D + 256 + lane * 8);
  }
#pragma unroll 1
  for (; grow < L; grow += 80 * NGATE) {
    const int nrow = min(grow + 80 * NGATE, L - 4);
#pragma unroll
    for (int i = 0; i < 4; i++) {
      gx[i][0] = nx[i][0]; gx[i][1] = nx[i][1];
      nx[i][0] = ldg128(u + (size_t)(nrow + i) * D + lane * 8);
      nx[i][1] = ldg128(u + (size_t)(nrow + i) * D + 256 + lane * 8);
    }
    float c[2][4];
#pragma unroll
    for (int i = 0; i < 2; i++) {
      const uint4 *x = gx[2 * i], *y = gx[2 * i + 1];
      const uint32_t xs[8] = {x[0].x, x[0].y, x[0].z, x[0].w, x[1].x, x[1].y, x[1].z, x[1].w};
      const uint32_t ys[8] = {y[0].x, y[0].y, y[0].z, y[0].w, y[1].x, y[1].y, y[1].z, y[1].w};
      c[i][0] = c[i][1] = c[i][2] = c[i][3] = 0.f;
#pragma unroll
      for (int j = 0; j < 8; j += 2)
        mma16816(c[i], hmul2(xs[j], ws[j]), hmul2(ys[j], ws[j]), hmul2(xs[j + 1], ws[j + 1]), hmul2(ys[j + 1], ws[j + 1]), 0x3f803f80u, 0x3f803f80u);
    }
    float s = (lane & 2) ? ((lane & 1) ? c[1][2] : c[1][0]) : ((lane & 1) ? c[0][2] : c[0][0]);
#pragma unroll
    for (int o = 4; o < 32; o <<= 1) s += __shfl_xor_sync(0xffffffffu, s, o);
    s = bf_round(s);
    const float gv = 1.f / (1.f + expf(-s));
    const uint32_t w = (tag << 16) | (pack_bf16(gv, 0.f) & 0xffffu);
    if (lane < 4) asm volatile("st.relaxed.gpu.global.u32 [%0], %1;" ::"l"(&g_gate[grow + lane]), "r"(w) : "memory");
  }
  __syncthreads();
  if (threadIdx.x == 0 && atomicAdd(&g_ticket, 1u) == NCTA + NGATE - 1) { g_ticket = 0; g_epoch = epoch + 1; }
}

__global__ void __cluster_dims__(2, 1, 1) __launch_bounds__(640, 1)
ssm_kernel(const __grid_constant__ Params p, const __grid_constant__ CUtensorMap tm_in, const __grid_constant__ CUtensorMap tm_out) {
  extern __shared__ __align__(1024) unsigned char smem_raw[];
  const uint32_t sb = (uint32_t)__cvta_generic_to_shared(smem_raw);
  const int tid = threadIdx.x, lane = tid & 31;
  const int warp = __shfl_sync(0xffffffffu, tid >> 5, 0);
  const int ch = warp >> 2, wq = warp & 3, br = wq >> 1, hf = wq & 1;
  const int g = lane >> 2, t = lane & 3;
  if (__builtin_expect(blockIdx.x < NGATE, 0)) { gate_cta(&p); return; }
  const int bid = blockIdx.x - NGATE;
  const int d = bid * 4 + ch;
  const uint32_t rank = blockIdx.x & 1;
  const uint32_t cb = sb + CH_OFF + ch * CH_BYTES;
  const int wtid = tid & 127;
  const int oc0 = (bid >> 1) * 8;
  STAMP(0); GT(0);

  if (warp >= 16) {
    if (wtid == 0) {
      mbar_init_expect(sb + B_RAW, 32768);
#pragma unroll
      for (int i = 0; i < 4; i++) mbar_init_expect(sb + B_X + 8 * i, 2048);
      asm volatile("mbarrier.init.shared::cta.b64 [%0], 128;" ::"r"(sb + B_U) : "memory");
      asm volatile("mbarrier.init.shared::cta.b64 [%0], 128;" ::"r"(sb + B_W) : "memory");
#pragma unroll
      for (int i = 0; i < 7; i++) asm volatile("mbarrier.init.shared::cta.b64 [%0], 16;" ::"r"(sb + B_ST + 8 * i) : "memory");
      asm volatile("fence.mbarrier_init.release.cluster;" ::: "memory");
      asm volatile("fence.proxy.async.shared::cta;" ::: "memory");
    }
    __syncwarp();
    asm volatile("barrier.cluster.arrive.relaxed.aligned;" ::: "memory");
    unsigned int epoch;
    asm volatile("ld.relaxed.gpu.global.u32 %0, [%1];" : "=r"(epoch) : "l"(&g_epoch) : "memory");
    asm volatile("barrier.cluster.wait.aligned;" ::: "memory");
    if (wtid == 0) {
      asm volatile("cp.async.bulk.tensor.5d.shared::cluster.global.mbarrier::complete_tx::bytes.multicast::cluster [%0], [%1, {%3, %4, %4, %4, %5}], [%2], %6;"
                   ::"r"(sb + RAW_OFF + rank * 16384), "l"(&tm_in), "r"(sb + B_RAW), "r"(oc0), "r"(0), "r"((int)rank * 32), "h"((unsigned short)3) : "memory");
    }
    sts128(sb + CH_OFF + wq * CH_BYTES + U_OFF + (lane >> 3) * U_CS + (64 + (lane & 7)) * 16, 0, 0, 0, 0);
    const uint2 dA = ldg64(p.A_D + bid * 4), dB = ldg64(p.B_D + bid * 4);
    uint32_t BA[3][4], BC[3][4];
    {
      const int l1 = br ? 3 : 6, h1 = br ? 5 : 10;
#pragma unroll
      for (int i = 0; i < 3; i++) {
        const int e = 16 * hf + g - 2 * t + 16 - 16 * i;
        BA[i][0] = band2(e, l1, h1); BA[i][1] = band2(e + 8, l1, h1); BA[i][2] = band2(e - 8, l1, h1); BA[i][3] = BA[i][0];
        BC[i][0] = band2(e, 3, 4); BC[i][1] = band2(e + 8, 3, 4); BC[i][2] = band2(e - 8, 3, 4); BC[i][3] = BC[i][0];
      }
    }
    const uint32_t tag = (epoch + 1) & 0xffffu;
    if (wtid == 0) sts32(sb + TAG_OFF, tag);
    STAMP(3);
    mbar_wait(sb + B_RAW);
    STAMP(4);
    {
      const uint32_t dst = sb + CH_OFF + (g & 3) * CH_BYTES + U_OFF + t * U_CS + (63 - wq * 16) * 16;
#pragma unroll
      for (int h = 0; h < 2; h++) {
        uint32_t r[8][4];
#pragma unroll
        for (int i = 0; i < 8; i++) ldsm4t(sb + RAW_OFF + (wq * 16 + h * 8 + i) * 512 + lane * 16, r[i][0], r[i][1], r[i][2], r[i][3]);
        if ((uint32_t)(g >> 2) == rank) {
#pragma unroll
          for (int i = 0; i < 8; i++) sts128(dst - (h * 8 + i) * 16, r[i][0], r[i][1], r[i][2], r[i][3]);
        }
      }
    }
    fence_async();
    asm volatile("mbarrier.arrive.shared::cta.b64 _, [%0];" ::"r"(sb + B_U) : "memory");
    bar_sync(5, 128);
    STAMP(5);
    {
      const int mrow = lane & 7, mi = lane >> 3;
      const uint64_t ub0 = mkdesc(sb + CH_OFF + U_OFF, U_CS, 128);
      {
        float w1[24], w3[16];
#pragma unroll
        for (int i = 0; i < 24; i++) w1[i] = 0.f;
#pragma unroll
        for (int i = 0; i < 16; i++) w3[i] = 0.f;
        uint32_t wa[3], sa[2];
#pragma unroll
        for (int i = 0; i < 3; i++) {
          const int c = 4 * (47 - 8 * (2 * i + (mi >> 1)) - mrow) + 2 * hf + (mi & 1);
          wa[i] = sb + CH_OFF + (br ? W3_OFF : W5_OFF) + (5 - (c >> 5)) * 576 + ((c & 31) >> 3) * 144 + (c & 7) * 16;
          if (i) sa[i - 1] = sb + CH_OFF + S2_OFF + (c + (c >> 3)) * 16;
        }
#pragma unroll 1
        for (int k = 0; k < 4; k++) {
          wg_fence();
#pragma unroll
          for (int i = 0; i < 3; i++)
            wgmma_rs<48, 0>(w1, BA[i][0], BA[i][1], BA[i][2], BA[i][3],
                            ub0 + (uint64_t)((k * CH_BYTES + ((2 * i + 2) & 3) * U_CS + (16 + (i == 0)) * 16) >> 4), i);
#pragma unroll
          for (int i = 0; i < 3; i++)
            wgmma_rs<32, 0>(w3, BC[i][0], BC[i][1], BC[i][2], BC[i][3],
                            ub0 + (uint64_t)((k * CH_BYTES + ((2 * i + 2) & 3) * U_CS + (32 + (i == 0)) * 16) >> 4), i);
          wg_commit();
          wg_wait0();
#pragma unroll
          for (int i = 0; i < 3; i++)
            stsm4t(wa[i] + k * CH_BYTES, pack_bf16(w1[8 * i], w1[8 * i + 1]), pack_bf16(w1[8 * i + 2], w1[8 * i + 3]),
                   pack_bf16(w1[8 * i + 4], w1[8 * i + 5]), pack_bf16(w1[8 * i + 6], w1[8 * i + 7]));
          if (br == 0) {
#pragma unroll
            for (int i = 0; i < 2; i++)
              stsm4t(sa[i] + k * CH_BYTES, pack_bf16(w3[8 * i], w3[8 * i + 1]), pack_bf16(w3[8 * i + 2], w3[8 * i + 3]),
                     pack_bf16(w3[8 * i + 4], w3[8 * i + 5]), pack_bf16(w3[8 * i + 6], w3[8 * i + 7]));
          }
        }
      }
      {
        uint32_t BB[4][4];
        const int l2 = br ? 5 : 12, h2 = br ? 11 : 20;
#pragma unroll
        for (int i = 0; i < 4; i++) {
          const int e = 16 * hf + g - 2 * t + 32 - 16 * i;
          BB[i][0] = band2(e, l2, h2); BB[i][1] = band2(e + 8, l2, h2); BB[i][2] = band2(e - 8, l2, h2); BB[i][3] = BB[i][0];
        }
        float w2[2][16];
#pragma unroll
        for (int i = 0; i < 16; i++) { w2[0][i] = 0.f; w2[1][i] = 0.f; }
        uint32_t wa[2];
#pragma unroll
        for (int i = 0; i < 2; i++) {
          const int c = 4 * (31 - 8 * (2 * i + (mi >> 1)) - mrow) + 2 * hf + (mi & 1), pp = c >> 1;
          wa[i] = sb + CH_OFF + (br ? W7_OFF : W9_OFF) + (1 - (pp >> 5)) * 1152 + (c & 1) * 576 + ((pp & 31) >> 3) * 144 + (pp & 7) * 16;
        }
#pragma unroll 1
        for (int kp = 0; kp < 2; kp++) {
          wg_fence();
#pragma unroll
          for (int k = 0; k < 2; k++)
#pragma unroll
            for (int i = 0; i < 4; i++)
              wgmma_rs<32, 0>(w2[k], BB[i][0], BB[i][1], BB[i][2], BB[i][3],
                              ub0 + (uint64_t)(((2 * kp + k) * CH_BYTES + ((2 * i) & 3) * U_CS + (32 + (i < 2)) * 16) >> 4), i);
          wg_commit();
          wg_wait0();
#pragma unroll
          for (int k = 0; k < 2; k++)
#pragma unroll
            for (int i = 0; i < 2; i++)
              stsm4t(wa[i] + (2 * kp + k) * CH_BYTES, pack_bf16(w2[k][8 * i], w2[k][8 * i + 1]), pack_bf16(w2[k][8 * i + 2], w2[k][8 * i + 3]),
                     pack_bf16(w2[k][8 * i + 4], w2[k][8 * i + 5]), pack_bf16(w2[k][8 * i + 6], w2[k][8 * i + 7]));
        }
      }
    }
    fence_async();
    asm volatile("mbarrier.arrive.shared::cta.b64 _, [%0];" ::"r"(sb + B_W) : "memory");
    STAMP(7);
    {
      const int bsel = (int)rank ^ br ^ 1, xl = wtid & 63;
      uint2 gl[4];
      uint32_t ua[4][4], ub[4][4];
#pragma unroll
      for (int i = 0; i < 4; i++) gl[i] = gate_ld((2 * (i >> 1) + bsel) * 128 + (i & 1) * 64 + xl);
#pragma unroll
      for (int i = 0; i < 4; i++) skip_terms(ua[i], ub[i], sb, (2 * (i >> 1) + bsel) * 128 + (i & 1) * 64 + xl, dA, dB);
      const uint32_t yo = sb + CH_OFF + (xl & 3) * 4 + ysw(xl >> 2) + bsel * 512;
#pragma unroll
      for (int slot = 0; slot < 2; slot++) {
        const int box = 2 * slot + bsel;
        uint32_t g2[2], ya[2][4], yb[2][4];
#pragma unroll
        for (int h = 0; h < 2; h++) g2[h] = gate_fin(p, gl[2 * slot + h], box * 128 + h * 64 + xl, tag);
        mbar_wait(sb + B_ST + 8 * box);
        STAMP(8 + slot);
#pragma unroll
        for (int h = 0; h < 2; h++) {
          const uint32_t yh = (yo ^ (h * 32)) + h * 256 + slot * 1024;
          ld4ch(ya[h], yh + Y0_OFF); ld4ch(yb[h], yh + Y0_OFF + 4096);
          if (slot) {
            uint32_t a2[4], b2[4];
            ld4ch(a2, yh + Y2_OFF - 1024); ld4ch(b2, yh + Y2_OFF - 1024 + 3072);
#pragma unroll
            for (int k = 0; k < 4; k++) { ya[h][k] = hadd2(ya[h][k], a2[k]); yb[h][k] = hadd2(yb[h][k], b2[k]); }
          }
        }
        const uint4 r0 = mix(ya[0], yb[0], ua[2 * slot], ub[2 * slot], g2[0]), r1 = mix(ya[1], yb[1], ua[2 * slot + 1], ub[2 * slot + 1], g2[1]);
        if (br == 0) { send_box(sb, slot, xl, rank, r0); send_box(sb, slot, xl + 64, rank, r1); }
        else {
          const uint32_t st = sb + RAW_OFF + slot * 4096 + xl * 16, xin = sb + XIN_OFF + slot * 2048 + xl * 16;
          sts64(st + rank * 8, r0.x, r0.y); sts64(st + 2048 + rank * 8, r0.z, r0.w);
          sts64(st + 1024 + rank * 8, r1.x, r1.y); sts64(st + 3072 + rank * 8, r1.z, r1.w);
          mbar_wait(sb + B_X + slot * 8);
          const uint4 q0 = lds128(xin), q1 = lds128(xin + 1024);
          sts64(st + (rank ^ 1) * 8, q0.x, q0.y); sts64(st + 2048 + (rank ^ 1) * 8, q0.z, q0.w);
          sts64(st + 1024 + (rank ^ 1) * 8, q1.x, q1.y); sts64(st + 3072 + (rank ^ 1) * 8, q1.z, q1.w);
          fence_async();
          bar_sync(6, 64);
          if (xl == 0) {
            asm volatile("cp.async.bulk.tensor.3d.global.shared::cta.bulk_group [%0, {%2, %3, %4}], [%1];"
                         ::"l"(&tm_out), "r"(sb + RAW_OFF + slot * 4096), "r"(oc0), "r"(box * 128), "r"(0) : "memory");
            asm volatile("cp.async.bulk.commit_group;" ::: "memory");
          }
        }
        STAMP(10 + slot);
      }
    }
    if (wtid == 0 && atomicAdd(&g_ticket, 1u) == NCTA + NGATE - 1) { g_ticket = 0; g_epoch = epoch + 1; }
    if (wtid == 64) asm volatile("cp.async.bulk.wait_group.read 0;" ::: "memory");
    STAMP(15);
    return;
  }
  asm volatile("barrier.cluster.arrive.relaxed.aligned;" ::: "memory");

  const int moff = (bid * 4 + (tid >> 7)) * NM + (tid & 63) * 2;
  const int brt = (tid >> 6) & 1;
  const __nv_bfloat16* const* tp = p.t + (brt ? 0 : 6);
  const uint32_t q0 = *(const uint32_t*)(tp[0] + moff), q1 = *(const uint32_t*)(tp[1] + moff);
  const uint32_t q2 = *(const uint32_t*)(tp[2] + moff), q3 = *(const uint32_t*)(tp[3] + moff);
  const uint2 ldt4 = *(const uint2*)(tp[4] + bid * 4);
  const uint32_t q4 = *(const uint32_t*)(tp[brt ? 2 : 5] + moff), q5 = *(const uint32_t*)(tp[brt ? 3 : 6] + moff);

  for (int i = wtid & 63; i < R_BR / 16; i += 64) sts128(cb + R_OFF + br * R_BR + i * 16, 0, 0, 0, 0);
  STAMP(1);

  float acc[5][4];
  float k2048 = 0.f;
  const uint32_t scr = cb + Y0_OFF + wq * SCR_BYTES;
  const uint32_t scr2 = sb + XIN_OFF + warp * 640;
  {
    const uint32_t ldt2 = (ch & 2) ? ldt4.y : ldt4.x;
    const float dt = bf_round(expf((ch & 1) ? bf_hi(ldt2) : bf_lo(ldt2)));
#pragma unroll
    for (int i = 0; i < 5; i++) acc[i][0] = acc[i][1] = acc[i][2] = acc[i][3] = 0.f;
    STAMP(2);
    const uint32_t tb = scr + lane * 16;
    const uint32_t ta = scr + (lane >> 3) * 512 + (lane & 7) * 16;
    const uint32_t tc = ((lane & 8) ? scr2 : scr + 4096) + (lane >> 4) * 128 + (lane & 7) * 16;
    const uint32_t tm = scr2 + 512 + ((lane >> 3) & 1) * 64 + (lane >> 4) * 16;
    cf cc[2], zz1[2], zz128[2];
#pragma unroll
    for (int r = 0; r < 2; r++) {
      float v0 = r ? bf_hi(q0) : bf_lo(q0), v1 = r ? bf_hi(q1) : bf_lo(q1), v2 = r ? bf_hi(q2) : bf_lo(q2);
      float v3 = r ? bf_hi(q3) : bf_lo(q3), v4 = r ? bf_hi(q4) : bf_lo(q4), v5 = r ? bf_hi(q5) : bf_lo(q5);
      if (br == 0) { cc[r] = cmul(cf{v2, v3}, cf{dt * v4, dt * v5}); }
      else { v0 = -bf_round(expf(v0)); cc[r] = cf{2.f * dt * v2, 2.f * dt * v3}; }
      const float xl = (dt * v0) * 1.4426950408889634f, y = dt * v1;
      zz1[r] = cexp_p(xl, y, 1.f); zz128[r] = cexp_p(xl, y, 128.f);
    }
    uint32_t T[10][4], m4;
    auto produce = [&](int r) {
      const cf c = cc[r], z1 = zz1[r], z128 = zz128[r];
      const cf z2 = csq(z1), z4 = csq(z2), z8 = csq(z4);
      const cf w8 = {z8.re, -z8.im};
      const cf z16 = csq(w8), z24 = cmul(z16, w8), z32 = csq(z16), z40 = cmul(z32, w8), z48 = csq(z24), z56 = cmul(z32, z24), z64 = csq(z32);
      const cf z256 = csq(z128), z512 = csq(z256), z1024 = csq(z512), z2048 = csq(z1024);
      k2048 += fmaf(c.re, z2048.re, -c.im * z2048.im);
      {
        T[0][0] = pack_bf16(1.f, z8.re); T[0][1] = pack_bf16(z16.re, z24.re); T[0][2] = pack_bf16(z32.re, z40.re); T[0][3] = pack_bf16(z48.re, z56.re);
        T[2][0] = pack_bf16(0.f, w8.im); T[2][1] = pack_bf16(z16.im, z24.im); T[2][2] = pack_bf16(z32.im, z40.im); T[2][3] = pack_bf16(z48.im, z56.im);
        const uint32_t yr = pack_bf16(z64.re, z64.re), yi = pack_bf16(z64.im, z64.im), nyi = yi ^ 0x80008000u;
#pragma unroll
        for (int i = 0; i < 4; i++) CMUL2(T[1][i], T[3][i], T[0][i], T[2][i], yr, yi, nyi);
      }
      {
        const cf h1 = cmul(c, z128), h2 = cmul(c, z256), h3 = cmul(h1, z256), h4 = cmul(c, z512), h5 = cmul(h1, z512), h6 = cmul(h2, z512), h7 = cmul(h3, z512);
        const cf e1 = cmul(c, z1), e2 = cmul(c, z2), e3 = cmul(e1, z2), e129 = cmul(h1, z1), e130 = cmul(h1, z2), e131 = cmul(e129, z2);
        const cf e258 = cmul(h2, z2), e386 = cmul(h3, z2);
        T[4][0] = pack_bf16(c.re, e1.re); T[4][1] = pack_bf16(e2.re, e3.re); T[4][2] = pack_bf16(h1.re, e129.re); T[4][3] = pack_bf16(e130.re, e131.re);
        T[5][0] = pack_bf16(c.im, e1.im); T[5][1] = pack_bf16(e2.im, e3.im); T[5][2] = pack_bf16(h1.im, e129.im); T[5][3] = pack_bf16(e130.im, e131.im);
        T[6][0] = pack_bf16(h2.re, e258.re); T[6][1] = pack_bf16(h3.re, e386.re); T[6][2] = pack_bf16(h4.re, h5.re); T[6][3] = pack_bf16(h6.re, h7.re);
        T[7][0] = pack_bf16(h2.im, e258.im); T[7][1] = pack_bf16(h3.im, e386.im); T[7][2] = pack_bf16(h4.im, h5.im); T[7][3] = pack_bf16(h6.im, h7.im);
        const uint32_t xr[4] = {__byte_perm(T[4][0], T[4][2], 0x5410), __byte_perm(T[6][0], T[6][1], 0x5410), T[6][2], T[6][3]};
        const uint32_t xi[4] = {__byte_perm(T[5][0], T[5][2], 0x5410), __byte_perm(T[7][0], T[7][1], 0x5410), T[7][2], T[7][3]};
        const uint32_t yr = pack_bf16(z1024.re, z1024.re), yi = pack_bf16(z1024.im, z1024.im), nyi = yi ^ 0x80008000u;
#pragma unroll
        for (int i = 0; i < 4; i++) CMUL2(T[8][i], T[9][i], xr[i], xi[i], yr, yi, nyi);
        m4 = pack_bf16(z4.re, z4.im);
      }
    };
    auto store = [&]() {
#pragma unroll
      for (int m = 0; m < 9; m++) sts128(tb + m * 512, T[m][0], T[m][1], T[m][2], T[m][3]);
      sts128(scr2 + lane * 16, T[9][0], T[9][1], T[9][2], T[9][3]);
      sts16(scr2 + 512 + lane * 2, m4); sts16(scr2 + 576 + lane * 2, m4 >> 16);
    };
    auto consume = [&]() {
#pragma unroll
      for (int kp = 0; kp < 2; kp++) {
        uint32_t rr[2], ri[2], yr[2], yi[2];
        ldsm4t(tc + kp * 256, rr[0], ri[0], rr[1], ri[1]);
        ldsm4(tm + kp * 32, yr[0], yi[0], yr[1], yi[1]);
#pragma unroll
        for (int k2 = 0; k2 < 2; k2++) {
          const int kk = kp * 2 + k2;
          uint32_t a0, a1, a2, a3, pr, pi, qr, qi, xr, xi;
          ldsm4t(ta + kk * 128, a0, a1, a2, a3);
          ldsm4t(ta + 2048 + kk * 128, pr, pi, qr, qi);
          const uint32_t nyi = yi[k2] ^ 0x80008000u;
          mma16816(acc[0], a0, a1, a2, a3, pr, pi);
          mma16816(acc[2], a0, a1, a2, a3, qr, qi);
          mma16816(acc[4], a0, a1, a2, a3, rr[k2], ri[k2]);
          CMUL2(xr, xi, pr, pi, yr[k2], yi[k2], nyi);
          mma16816(acc[1], a0, a1, a2, a3, xr, xi);
          CMUL2(xr, xi, qr, qi, yr[k2], yi[k2], nyi);
          mma16816(acc[3], a0, a1, a2, a3, xr, xi);
        }
      }
    };
    produce(0); store();
    __syncwarp();
    consume(); produce(1);
    __syncwarp();
    store();
#pragma unroll
    for (int o = 16; o; o >>= 1) k2048 += __shfl_xor_sync(0xffffffffu, k2048, o);
    __syncwarp();
    consume();
  }
  STAMP(3);
  __syncwarp();
  {
    const uint32_t xs = scr + lane * 16;
#define OTH(i, k) __float_as_uint(hf ? acc[i][k] : acc[i][2 + (k)])
    sts128(xs, OTH(0, 0), OTH(0, 1), OTH(1, 0), OTH(1, 1));
    sts128(xs + 512, OTH(2, 0), OTH(2, 1), OTH(3, 0), OTH(3, 1));
    sts128(xs + 1024, OTH(4, 0), OTH(4, 1), __float_as_uint(k2048), 0);
#undef OTH
  }

  bar_sync(7 + (warp >> 1), 64);
  STAMP(4);
  {
    const uint32_t xo = cb + Y0_OFF + (wq ^ 1) * SCR_BYTES + lane * 16;
    const uint4 o0 = lds128(xo), o1 = lds128(xo + 512), o2 = lds128(xo + 1024);
    const uint32_t rb = cb + R_OFF + br * R_BR;
#define OWN(i, k) (hf ? acc[i][2 + (k)] : acc[i][k])
    const uint32_t vP = pack_bf16(OWN(0, 1) + __uint_as_float(o0.y), OWN(0, 0) + __uint_as_float(o0.x));
    const uint32_t vP4 = pack_bf16(OWN(1, 1) + __uint_as_float(o0.w), OWN(1, 0) + __uint_as_float(o0.z));
    const uint32_t vQ = pack_bf16(OWN(2, 1) + __uint_as_float(o1.y), OWN(2, 0) + __uint_as_float(o1.x));
    const uint32_t vQ4 = pack_bf16(OWN(3, 1) + __uint_as_float(o1.w), OWN(3, 0) + __uint_as_float(o1.z));
    const uint32_t vR = pack_bf16(OWN(4, 1) + __uint_as_float(o2.y), OWN(4, 0) + __uint_as_float(o2.x));
#undef OWN
    const int j = g + 8 * hf;
    {
      const int a = 2 * (t & 1) + 64 * (t & 2) + 8 * j;
      const uint32_t ad = rb + 2 * (RD_X0 - 1 - a);
      const uint32_t a1 = (t & 2) ? ad - 8 : ad, a2 = (t & 2) ? ad : ad - 8;
      const uint32_t w1 = (t & 2) ? vP4 : vP, w2 = (t & 2) ? vP : vP4;
      sts32(a1, w1); sts32(a2, w2);
      sts16(a1 + RD_CS + 2, w1); sts16(a1 + RD_CS + 4, w1 >> 16);
      sts16(a2 + RD_CS + 2, w2); sts16(a2 + RD_CS + 4, w2 >> 16);
    }
    if (t < 2) {
      const int b = 256 + 128 * t + 8 * j;
      const uint32_t ad = rb + 2 * (RD_X0 - 6 - b);
      const uint32_t v22 = __byte_perm(vQ4, 0, 0x3232), v00 = __byte_perm(vQ, 0, 0x3232);
      sts16(ad, vQ4);
      sts64(ad + 2, v22, __byte_perm(vQ4, vQ, 0x5432));
      sts32(ad + 10, v00);
      if (b != 256) { sts16(ad + 14, v00); sts128(ad + RD_CS + 2, vQ4, v22, vQ, v00); }
      else { sts64(ad + RD_CS + 2, vQ4, v22); sts32(ad + RD_CS + 10, vQ); sts16(ad + RD_CS + 14, v00); }
    } else {
      const uint32_t ao = rb + R_O2 + 2 * (159 - (32 * t + j)), ae = ao - (R_O2 - R_E2) + 2;
      sts16(ao, vQ4 >> 16); sts16(ao + RS_CS + 2, vQ4 >> 16); sts16(ao - 32, vQ4); sts16(ao - 32 + RS_CS + 2, vQ4);
      sts16(ae - 32, vQ); sts16(ae - 32 + RS_CS + 2, vQ);
      if (lane != 2 || hf) { sts16(ae, vQ >> 16); sts16(ae + RS_CS + 2, vQ >> 16); }
      else {
        const uint32_t vv = __byte_perm(vQ, 0, 0x3232), ad = rb + 2 * (RD_X0 - 514);
        sts16(ad, vv); sts32(ad + 2, vv); sts16(ad + 6, vv); sts64(ad + RD_CS + 2, vv, vv);
      }
    }
    {
      const uint32_t a = rb + ((g & 1) ? R_O3 : R_E3 + 2) + 2 * (159 - (64 + 16 * t + (j >> 1)));
      const bool p1024 = (lane == 0) && (hf == 0);
      const uint32_t a00 = p1024 ? rb + R_E2 + 2 * (159 - 127) : a;
      sts16(a00, vR >> 16); sts16(a00 + RS_CS + 2, vR >> 16);
      sts16(a - 16, vR); sts16(a - 16 + RS_CS + 2, vR);
      if (p1024) {
        sts32(sb + K1024_OFF + (ch * 2 + br) * 4, __byte_perm(vR, 0, 0x3232));
        const uint32_t kv = pack_bf16(k2048 + __uint_as_float(o2.z), 0.f);
        sts16(rb + R_E3 + 2 * (159 - 127), kv); sts16(rb + R_E3 + 2 * (159 - 127) + RS_CS + 2, kv);
      }
    }
  }
  STAMP(5);
  asm volatile("barrier.cluster.wait.aligned;" ::: "memory");
  bar_sync(7 + (warp >> 1), 64);
  mbar_wait(sb + B_U);
  STAMP(6);

  const uint32_t zz = lds32(cb + R_OFF + br * R_BR);
  conv_dense(sb, cb, zz);
  STAMP(8);
  {
    const int x = (4 + ch) * 128 + wtid, c = x >> 2;
    const uint2 dA = ldg64(p.A_D + bid * 4), dB = ldg64(p.B_D + bid * 4);
    const uint2 gl = gate_ld(x);
    const uint32_t rb = cb + R_OFF + br * R_BR;
    float e48[24], e40[20], e32[16], h32[16], h16[8];
    const int x1 = 159 - (16 * hf + g - 2 * t + 136);
    const uint32_t fs = rb + ((g & 1) ? 2 * x1 : RS_CS + 2 * x1 + 2);
    uint32_t A[2][4][4];
    auto loadA = [&](int buf, uint32_t oe, uint32_t oo, int i0) {
#pragma unroll
      for (int a = 0; a < 2; a++) {
        const uint32_t base = fs + (a ? oo : oe) + i0 * 16;
        uint32_t* k0 = A[buf][2 * a];
        uint32_t* k1 = A[buf][2 * a + 1];
        k0[1] = lds32(base); k0[0] = lds32(base + 16); k0[2] = lds32(base + 32); k1[0] = lds32(base + 48); k1[2] = lds32(base + 64);
        k0[3] = k0[0]; k1[1] = k0[2]; k1[3] = k1[0];
      }
    };
    loadA(0, R_E2, R_O2, 8);
    loadA(1, R_E2, R_O2, 4);
    mbar_wait(sb + B_W);
    const uint64_t d5 = mkdesc(cb + W5_OFF, 144, 576), d3 = mkdesc(cb + W3_OFF, 144, 576);
    const uint64_t d9 = mkdesc(cb + W9_OFF, 144, 576), d7 = mkdesc(cb + W7_OFF, 144, 576);
    const uint32_t y2d = cb + Y2_OFF + br * 3072 + ysw(32 * (5 - (lane >> 4)) + 16 * hf + (lane & 15));
    const uint32_t y3d = cb + Y3_OFF + br * 2048 + ysw(2 * (16 * hf + (lane & 15)) + (lane >> 4));
#define FAR4(N, ACC, BUF, DA, DB, OFF, FIRST)                                                            \
    wg_fence();                                                                                           \
    _Pragma("unroll") for (int k = 0; k < 4; k++) {                                                      \
      const uint32_t* a = A[BUF][k];                                                                      \
      wgmma_rs<N, 1>(ACC, a[0], a[1], a[2], a[3], ((k >> 1) ? DB : DA) + (k & 1) * 18 + (OFF), !(FIRST) || k); \
    }                                                                                                     \
    wg_commit();
    FAR4(48, e48, 0, d5, d3, 0, 1)
    wg_wait0();
    loadA(0, R_E2, R_O2, 0);
    stsm2(y2d - 5 * 512, PK2(e48, 20), PK2(e48, 22));
#pragma unroll
    for (int i = 0; i < 20; i++) e40[i] = FCPY(e48[i]);
    stage_done(sb, 2, lane);
    FAR4(40, e40, 1, d5, d3, 36, 0)
    wg_wait0();
    loadA(1, R_E3, R_O3, 8);
    stsm2(y2d - 4 * 512, PK2(e40, 16), PK2(e40, 18));
#pragma unroll
    for (int i = 0; i < 16; i++) e32[i] = FCPY(e40[i]);
    stage_done(sb, 3, lane);
    FAR4(32, e32, 0, d5, d3, 72, 0)
    FAR4(32, h32, 1, d9, d7, 0, 1)
    wg_wait1();
    loadA(0, R_E3, R_O3, 4);
    stsm4(y2d, PK2(e32, 0), PK2(e32, 2), PK2(e32, 4), PK2(e32, 6));
    stsm4(y2d - 2 * 512, PK2(e32, 8), PK2(e32, 10), PK2(e32, 12), PK2(e32, 14));
    stage_done(sb, 4, lane);
    STAMP(9);
    wg_wait0();
    stsm4(y3d, PK2(h32, 8), PK2(h32, 10), PK2(h32, 12), PK2(h32, 14));
#pragma unroll
    for (int i = 0; i < 8; i++) h16[i] = FCPY(h32[i]);
    stage_done(sb, 5, lane);
    FAR4(16, h16, 0, d9, d7, 72, 0)
#undef FAR4
    const uint32_t yo = sb + CH_OFF + (x & 3) * 4 + ysw(c);
    uint32_t ua[4], ub[4], ya[4], yb[4], a2[4], b2[4], a3[4], b3[4], s2[4];
    skip_terms(ua, ub, sb, x, dA, dB);
    ld4ch(s2, sb + CH_OFF + (x & 3) * 4 + S2_OFF + ((c - 128) + ((c - 128) >> 3)) * 16);
    const uint32_t tag = lds32(sb + TAG_OFF);
    wg_wait0();
    stsm4(y3d + 1024, PK2(h16, 0), PK2(h16, 2), PK2(h16, 4), PK2(h16, 6));
    stage_done(sb, 6, lane);
    STAMP(10);
    const uint32_t g2 = gate_fin(p, gl, x, tag);
    mbar_wait(sb + B_ST + 8 * 4);
    const uint4 k0 = lds128(sb + K1024_OFF), k1 = lds128(sb + K1024_OFF + 16);
    const uint32_t kk[8] = {k0.x, k0.y, k0.z, k0.w, k1.x, k1.y, k1.z, k1.w};
    ld4ch(ya, yo + Y0_OFF); ld4ch(yb, yo + Y0_OFF + 4096);
    ld4ch(a2, yo + Y2_OFF - 1024); ld4ch(b2, yo + Y2_OFF - 1024 + 3072);
    mbar_wait(sb + B_ST + 8 * (5 + (ch >> 1)));
    STAMP(12);
    ld4ch(a3, yo + Y3_OFF - 2048); ld4ch(b3, yo + Y3_OFF - 2048 + 2048);
#pragma unroll
    for (int k = 0; k < 4; k++) {
      ya[k] = hadd2(ya[k], hadd2(hfma2(kk[2 * k], s2[k], a2[k]), a3[k]));
      yb[k] = hadd2(yb[k], hadd2(hfma2(kk[2 * k + 1], s2[k], b2[k]), b3[k]));
    }
    const uint4 r = mix(ya, yb, ua, ub, g2);
    if ((uint32_t)(ch & 1) != rank) send_box(sb, 2 + (ch >> 1), wtid, rank, r);
    else merge_box(sb, &tm_out, 2 + (ch >> 1), wtid, rank, oc0, r, 1 + ch);
  }
  STAMP(14);
  if (wtid == 0) asm volatile("cp.async.bulk.wait_group.read 0;" ::: "memory");
  STAMP(15); GT(1);
}

typedef CUresult (*EncodeFn)(CUtensorMap*, CUtensorMapDataType, cuuint32_t, void*, const cuuint64_t*, const cuuint64_t*,
                             const cuuint32_t*, const cuuint32_t*, CUtensorMapInterleave, CUtensorMapSwizzle,
                             CUtensorMapL2promotion, CUtensorMapFloatOOBfill);

}

extern "C" void kernel_launch(void* const* d_in, const int* in_sizes, int n_in, void* d_out, int out_size) {
  (void)in_sizes; (void)n_in; (void)out_size;
  typedef const __nv_bfloat16* bp;
  Params p;
  p.t[0] = (bp)d_in[10]; p.t[1] = (bp)d_in[11]; p.t[2] = (bp)d_in[12]; p.t[3] = (bp)d_in[13]; p.t[4] = (bp)d_in[14]; p.t[5] = nullptr;
  p.t[6] = (bp)d_in[1]; p.t[7] = (bp)d_in[2]; p.t[8] = (bp)d_in[5]; p.t[9] = (bp)d_in[6]; p.t[10] = (bp)d_in[7];
  p.t[11] = (bp)d_in[3]; p.t[12] = (bp)d_in[4]; p.t[13] = nullptr;
  p.u = (bp)d_in[0]; p.gw = (bp)d_in[16]; p.A_D = (bp)d_in[8]; p.B_D = (bp)d_in[15];
  static EncodeFn enc = nullptr;
  if (!enc) {
    cudaDriverEntryPointQueryResult qr;
    cudaGetDriverEntryPoint("cuTensorMapEncodeTiled", (void**)&enc, cudaEnableDefault, &qr);
    cudaFuncSetAttribute(ssm_kernel, cudaFuncAttributeMaxDynamicSharedMemorySize, SMEM_BYTES);
  }
  CUtensorMap tm_in, tm_out;
  {
    cuuint64_t gd[5] = {512, 2, 4, 4, 64};
    cuuint64_t gs[4] = {1024, 8192, 2048, 32768};
    cuuint32_t bx[5] = {8, 2, 4, 4, 32};
    cuuint32_t es[5] = {1, 1, 1, 1, 1};
    enc(&tm_in, CU_TENSOR_MAP_DATA_TYPE_BFLOAT16, 5, d_in[0], gd, gs, bx, es, CU_TENSOR_MAP_INTERLEAVE_NONE,
        CU_TENSOR_MAP_SWIZZLE_NONE, CU_TENSOR_MAP_L2_PROMOTION_NONE, CU_TENSOR_MAP_FLOAT_OOB_FILL_NONE);
  }
  {
    cuuint64_t gd[3] = {512, 1024, 2};
    cuuint64_t gs[2] = {2048, 1024};
    cuuint32_t bx[3] = {8, 128, 2};
    cuuint32_t es[3] = {1, 1, 1};
    enc(&tm_out, CU_TENSOR_MAP_DATA_TYPE_BFLOAT16, 3, d_out, gd, gs, bx, es, CU_TENSOR_MAP_INTERLEAVE_NONE,
        CU_TENSOR_MAP_SWIZZLE_NONE, CU_TENSOR_MAP_L2_PROMOTION_NONE, CU_TENSOR_MAP_FLOAT_OOB_FILL_NONE);
  }
  ssm_kernel<<<NCTA + NGATE, 640, SMEM_BYTES, cudaStreamPerThread>>>(p, tm_in, tm_out);
}
```

```cpp
#include <cuda_runtime.h>
#include <cuda.h>
#include <cuda_bf16.h>
#include <stdint.h>

namespace {
#define FCPY(x) __uint_as_float(opq(__float_as_uint(x), zz))

constexpr int L = 2048, D = 512, NM = 128;
constexpr int NCTA = 128;
constexpr int NGATE = 4;

constexpr int RAW_OFF = 0;
constexpr int XIN_OFF = 32768;
constexpr int BAR_OFF = XIN_OFF + 10240;
constexpr int CH_OFF = BAR_OFF + 256;
constexpr int U_CS = 1184;
constexpr int U_OFF = 0;
constexpr int R_OFF = 4736;
constexpr int RD_X0 = 565;
constexpr int RD_CS = 1216;
constexpr int RS_CS = 320;
constexpr int R_E2 = 2 * RD_CS, R_O2 = R_E2 + 2 * RS_CS, R_E3 = R_O2 + 2 * RS_CS, R_O3 = R_E3 + 2 * RS_CS;
constexpr int R_BR = R_O3 + 2 * RS_CS;
constexpr int W5_OFF = R_OFF + 2 * R_BR;
constexpr int W3_OFF = W5_OFF + 3456;
constexpr int W9_OFF = W3_OFF + 3456;
constexpr int W7_OFF = W9_OFF + 2304;
constexpr int Y0_OFF = W7_OFF + 2304;
constexpr int Y2_OFF = Y0_OFF + 8192, Y3_OFF = Y2_OFF + 6144;
constexpr int CH_BYTES = Y0_OFF + 18432 + 16;
constexpr int SCR_BYTES = 4608;
constexpr int SMEM_BYTES = CH_OFF + 4 * CH_BYTES;
static_assert(CH_BYTES % 128 == 16, "bank staggering of the channel blocks");
static_assert(SMEM_BYTES <= 232448, "smem");
constexpr int B_RAW = BAR_OFF, B_X = BAR_OFF + 8, B_U = BAR_OFF + 40, B_W = BAR_OFF + 48;
constexpr int TAG_OFF = BAR_OFF + 56;
constexpr int K1024_OFF = BAR_OFF + 64;
constexpr int B_ST = BAR_OFF + 96;

__device__ unsigned int g_gate[L];
__device__ unsigned int g_epoch;
__device__ unsigned int g_ticket;

#define STAMP(k)
#define GT(k)

struct Params {
  const __nv_bfloat16* t[14];
  const __nv_bfloat16 *u, *gw, *A_D, *B_D;
};

template <int N, int TB> __device__ __forceinline__ void wgmma_rs(float* d, uint32_t a0, uint32_t a1, uint32_t a2, uint32_t a3, uint64_t desc, int sc);
template <> __device__ __forceinline__ void wgmma_rs<64, 0>(float* d, uint32_t a0, uint32_t a1, uint32_t a2, uint32_t a3, uint64_t desc, int sc) {
  asm volatile("{\n.reg .pred p;\nsetp.ne.b32 p, %37, 0;\n"
    "wgmma.mma_async.sync.aligned.m64n64k16.f32.bf16.bf16 {%0,%1,%2,%3,%4,%5,%6,%7,%8,%9,%10,%11,%12,%13,%14,%15,%16,%17,%18,%19,%20,%21,%22,%23,%24,%25,%26,%27,%28,%29,%30,%31}, {%32,%33,%34,%35}, %36, p, 1, 1, 0;\n}"
    : "+f"(d[0]), "+f"(d[1]), "+f"(d[2]), "+f"(d[3]), "+f"(d[4]), "+f"(d[5]), "+f"(d[6]), "+f"(d[7]), "+f"(d[8]), "+f"(d[9]), "+f"(d[10]), "+f"(d[11]), "+f"(d[12]), "+f"(d[13]), "+f"(d[14]), "+f"(d[15]), "+f"(d[16]), "+f"(d[17]), "+f"(d[18]), "+f"(d[19]), "+f"(d[20]), "+f"(d[21]), "+f"(d[22]), "+f"(d[23]), "+f"(d[24]), "+f"(d[25]), "+f"(d[26]), "+f"(d[27]), "+f"(d[28]), "+f"(d[29]), "+f"(d[30]), "+f"(d[31]) : "r"(a0), "r"(a1), "r"(a2), "r"(a3), "l"(desc), "r"(sc));
}
template <> __device__ __forceinline__ void wgmma_rs<56, 0>(float* d, uint32_t a0, uint32_t a1, uint32_t a2, uint32_t a3, uint64_t desc, int sc) {
  asm volatile("{\n.reg .pred p;\nsetp.ne.b32 p, %33, 0;\n"
    "wgmma.mma_async.sync.aligned.m64n56k16.f32.bf16.bf16 {%0,%1,%2,%3,%4,%5,%6,%7,%8,%9,%10,%11,%12,%13,%14,%15,%16,%17,%18,%19,%20,%21,%22,%23,%24,%25,%26,%27}, {%28,%29,%30,%31}, %32, p, 1, 1, 0;\n}"
    : "+f"(d[0]), "+f"(d[1]), "+f"(d[2]), "+f"(d[3]), "+f"(d[4]), "+f"(d[5]), "+f"(d[6]), "+f"(d[7]), "+f"(d[8]), "+f"(d[9]), "+f"(d[10]), "+f"(d[11]), "+f"(d[12]), "+f"(d[13]), "+f"(d[14]), "+f"(d[15]), "+f"(d[16]), "+f"(d[17]), "+f"(d[18]), "+f"(d[19]), "+f"(d[20]), "+f"(d[21]), "+f"(d[22]), "+f"(d[23]), "+f"(d[24]), "+f"(d[25]), "+f"(d[26]), "+f"(d[27]) : "r"(a0), "r"(a1), "r"(a2), "r"(a3), "l"(desc), "r"(sc));
}
template <> __device__ __forceinline__ void wgmma_rs<48, 0>(float* d, uint32_t a0, uint32_t a1, uint32_t a2, uint32_t a3, uint64_t desc, int sc) {
  asm volatile("{\n.reg .pred p;\nsetp.ne.b32 p, %29, 0;\n"
    "wgmma.mma_async.sync.aligned.m64n48k16.f32.bf16.bf16 {%0,%1,%2,%3,%4,%5,%6,%7,%8,%9,%10,%11,%12,%13,%14,%15,%16,%17,%18,%19,%20,%21,%22,%23}, {%24,%25,%26,%27}, %28, p, 1, 1, 0;\n}"
    : "+f"(d[0]), "+f"(d[1]), "+f"(d[2]), "+f"(d[3]), "+f"(d[4]), "+f"(d[5]), "+f"(d[6]), "+f"(d[7]), "+f"(d[8]), "+f"(d[9]), "+f"(d[10]), "+f"(d[11]), "+f"(d[12]), "+f"(d[13]), "+f"(d[14]), "+f"(d[15]), "+f"(d[16]), "+f"(d[17]), "+f"(d[18]), "+f"(d[19]), "+f"(d[20]), "+f"(d[21]), "+f"(d[22]), "+f"(d[23]) : "r"(a0), "r"(a1), "r"(a2), "r"(a3), "l"(desc), "r"(sc));
}
template <> __device__ __forceinline__ void wgmma_rs<32, 0>(float* d, uint32_t a0, uint32_t a1, uint32_t a2, uint32_t a3, uint64_t desc, int sc) {
  asm volatile("{\n.reg .pred p;\nsetp.ne.b32 p, %21, 0;\n"
    "wgmma.mma_async.sync.aligned.m64n32k16.f32.bf16.bf16 {%0,%1,%2,%3,%4,%5,%6,%7,%8,%9,%10,%11,%12,%13,%14,%15}, {%16,%17,%18,%19}, %20, p, 1, 1, 0;\n}"
    : "+f"(d[0]), "+f"(d[1]), "+f"(d[2]), "+f"(d[3]), "+f"(d[4]), "+f"(d[5]), "+f"(d[6]), "+f"(d[7]), "+f"(d[8]), "+f"(d[9]), "+f"(d[10]), "+f"(d[11]), "+f"(d[12]), "+f"(d[13]), "+f"(d[14]), "+f"(d[15]) : "r"(a0), "r"(a1), "r"(a2), "r"(a3), "l"(desc), "r"(sc));
}
template <> __device__ __forceinline__ void wgmma_rs<48, 1>(float* d, uint32_t a0, uint32_t a1, uint32_t a2, uint32_t a3, uint64_t desc, int sc) {
  asm volatile("{\n.reg .pred p;\nsetp.ne.b32 p, %29, 0;\n"
    "wgmma.mma_async.sync.aligned.m64n48k16.f32.bf16.bf16 {%0,%1,%2,%3,%4,%5,%6,%7,%8,%9,%10,%11,%12,%13,%14,%15,%16,%17,%18,%19,%20,%21,%22,%23}, {%24,%25,%26,%27}, %28, p, 1, 1, 1;\n}"
    : "+f"(d[0]), "+f"(d[1]), "+f"(d[2]), "+f"(d[3]), "+f"(d[4]), "+f"(d[5]), "+f"(d[6]), "+f"(d[7]), "+f"(d[8]), "+f"(d[9]), "+f"(d[10]), "+f"(d[11]), "+f"(d[12]), "+f"(d[13]), "+f"(d[14]), "+f"(d[15]), "+f"(d[16]), "+f"(d[17]), "+f"(d[18]), "+f"(d[19]), "+f"(d[20]), "+f"(d[21]), "+f"(d[22]), "+f"(d[23]) : "r"(a0), "r"(a1), "r"(a2), "r"(a3), "l"(desc), "r"(sc));
}
template <> __device__ __forceinline__ void wgmma_rs<40, 1>(float* d, uint32_t a0, uint32_t a1, uint32_t a2, uint32_t a3, uint64_t desc, int sc) {
  asm volatile("{\n.reg .pred p;\nsetp.ne.b32 p, %25, 0;\n"
    "wgmma.mma_async.sync.aligned.m64n40k16.f32.bf16.bf16 {%0,%1,%2,%3,%4,%5,%6,%7,%8,%9,%10,%11,%12,%13,%14,%15,%16,%17,%18,%19}, {%20,%21,%22,%23}, %24, p, 1, 1, 1;\n}"
    : "+f"(d[0]), "+f"(d[1]), "+f"(d[2]), "+f"(d[3]), "+f"(d[4]), "+f"(d[5]), "+f"(d[6]), "+f"(d[7]), "+f"(d[8]), "+f"(d[9]), "+f"(d[10]), "+f"(d[11]), "+f"(d[12]), "+f"(d[13]), "+f"(d[14]), "+f"(d[15]), "+f"(d[16]), "+f"(d[17]), "+f"(d[18]), "+f"(d[19]) : "r"(a0), "r"(a1), "r"(a2), "r"(a3), "l"(desc), "r"(sc));
}
template <> __device__ __forceinline__ void wgmma_rs<32, 1>(float* d, uint32_t a0, uint32_t a1, uint32_t a2, uint32_t a3, uint64_t desc, int sc) {
  asm volatile("{\n.reg .pred p;\nsetp.ne.b32 p, %21, 0;\n"
    "wgmma.mma_async.sync.aligned.m64n32k16.f32.bf16.bf16 {%0,%1,%2,%3,%4,%5,%6,%7,%8,%9,%10,%11,%12,%13,%14,%15}, {%16,%17,%18,%19}, %20, p, 1, 1, 1;\n}"
    : "+f"(d[0]), "+f"(d[1]), "+f"(d[2]), "+f"(d[3]), "+f"(d[4]), "+f"(d[5]), "+f"(d[6]), "+f"(d[7]), "+f"(d[8]), "+f"(d[9]), "+f"(d[10]), "+f"(d[11]), "+f"(d[12]), "+f"(d[13]), "+f"(d[14]), "+f"(d[15]) : "r"(a0), "r"(a1), "r"(a2), "r"(a3), "l"(desc), "r"(sc));
}
template <> __device__ __forceinline__ void wgmma_rs<16, 1>(float* d, uint32_t a0, uint32_t a1, uint32_t a2, uint32_t a3, uint64_t desc, int sc) {
  asm volatile("{\n.reg .pred p;\nsetp.ne.b32 p, %13, 0;\n"
    "wgmma.mma_async.sync.aligned.m64n16k16.f32.bf16.bf16 {%0,%1,%2,%3,%4,%5,%6,%7}, {%8,%9,%10,%11}, %12, p, 1, 1, 1;\n}"
    : "+f"(d[0]), "+f"(d[1]), "+f"(d[2]), "+f"(d[3]), "+f"(d[4]), "+f"(d[5]), "+f"(d[6]), "+f"(d[7]) : "r"(a0), "r"(a1), "r"(a2), "r"(a3), "l"(desc), "r"(sc));
}

__device__ __forceinline__ uint32_t pack_bf16(float lo, float hi) {
  uint32_t r; asm("cvt.rn.bf16x2.f32 %0, %1, %2;" : "=r"(r) : "f"(hi), "f"(lo)); return r;
}
__device__ __forceinline__ float bf_lo(uint32_t v) { return __uint_as_float(v << 16); }
__device__ __forceinline__ float bf_hi(uint32_t v) { return __uint_as_float(v & 0xffff0000u); }
__device__ __forceinline__ float bf_round(float x) { return bf_lo(pack_bf16(x, 0.f)); }
__device__ __forceinline__ uint32_t hmul2(uint32_t a, uint32_t b) { uint32_t r; asm("mul.rn.bf16x2 %0, %1, %2;" : "=r"(r) : "r"(a), "r"(b)); return r; }
__device__ __forceinline__ uint32_t hadd2(uint32_t a, uint32_t b) { uint32_t r; asm("add.rn.bf16x2 %0, %1, %2;" : "=r"(r) : "r"(a), "r"(b)); return r; }
__device__ __forceinline__ uint32_t hsub2(uint32_t a, uint32_t b) { uint32_t r; asm("sub.rn.bf16x2 %0, %1, %2;" : "=r"(r) : "r"(a), "r"(b)); return r; }
__device__ __forceinline__ uint32_t hfma2(uint32_t a, uint32_t b, uint32_t c) { uint32_t r; asm("fma.rn.bf16x2 %0, %1, %2, %3;" : "=r"(r) : "r"(a), "r"(b), "r"(c)); return r; }

__device__ __forceinline__ void sts16(uint32_t a, uint32_t v) { asm volatile("st.shared.b16 [%0], %1;" ::"r"(a), "h"((unsigned short)v) : "memory"); }
__device__ __forceinline__ void sts32(uint32_t a, uint32_t v) { asm volatile("st.shared.b32 [%0], %1;" ::"r"(a), "r"(v) : "memory"); }
__device__ __forceinline__ void sts64(uint32_t a, uint32_t x, uint32_t y) { asm volatile("st.shared.v2.b32 [%0], {%1,%2};" ::"r"(a), "r"(x), "r"(y) : "memory"); }
__device__ __forceinline__ void sts128(uint32_t a, uint32_t x, uint32_t y, uint32_t z, uint32_t w) {
  asm volatile("st.shared.v4.b32 [%0], {%1,%2,%3,%4};" ::"r"(a), "r"(x), "r"(y), "r"(z), "r"(w) : "memory");
}
__device__ __forceinline__ uint32_t lds32(uint32_t a) { uint32_t v; asm volatile("ld.shared.b32 %0, [%1];" : "=r"(v) : "r"(a) : "memory"); return v; }
__device__ __forceinline__ uint2 lds64(uint32_t a) { uint2 v; asm volatile("ld.shared.v2.b32 {%0,%1}, [%2];" : "=r"(v.x), "=r"(v.y) : "r"(a) : "memory"); return v; }
__device__ __forceinline__ uint4 lds128(uint32_t a) {
  uint4 v; asm volatile("ld.shared.v4.b32 {%0,%1,%2,%3}, [%4];" : "=r"(v.x), "=r"(v.y), "=r"(v.z), "=r"(v.w) : "r"(a) : "memory"); return v;
}
__device__ __forceinline__ uint4 ldg128(const void* a) {
  uint4 v; asm volatile("ld.global.nc.v4.b32 {%0,%1,%2,%3}, [%4];" : "=r"(v.x), "=r"(v.y), "=r"(v.z), "=r"(v.w) : "l"(a) : "memory"); return v;
}
__device__ __forceinline__ uint2 ldg64(const void* a) {
  uint2 v; asm volatile("ld.global.nc.v2.b32 {%0,%1}, [%2];" : "=r"(v.x), "=r"(v.y) : "l"(a) : "memory"); return v;
}
__device__ __forceinline__ void ldsm4(uint32_t a, uint32_t& r0, uint32_t& r1, uint32_t& r2, uint32_t& r3) {
  asm volatile("ldmatrix.sync.aligned.m8n8.x4.shared.b16 {%0,%1,%2,%3}, [%4];" : "=r"(r0), "=r"(r1), "=r"(r2), "=r"(r3) : "r"(a) : "memory");
}
__device__ __forceinline__ void ldsm4t(uint32_t a, uint32_t& r0, uint32_t& r1, uint32_t& r2, uint32_t& r3) {
  asm volatile("ldmatrix.sync.aligned.m8n8.x4.trans.shared.b16 {%0,%1,%2,%3}, [%4];" : "=r"(r0), "=r"(r1), "=r"(r2), "=r"(r3) : "r"(a) : "memory");
}
__device__ __forceinline__ void stsm4(uint32_t a, uint32_t r0, uint32_t r1, uint32_t r2, uint32_t r3) {
  asm volatile("stmatrix.sync.aligned.m8n8.x4.shared.b16 [%0], {%1,%2,%3,%4};" ::"r"(a), "r"(r0), "r"(r1), "r"(r2), "r"(r3) : "memory");
}
__device__ __forceinline__ void stsm4t(uint32_t a, uint32_t r0, uint32_t r1, uint32_t r2, uint32_t r3) {
  asm volatile("stmatrix.sync.aligned.m8n8.x4.trans.shared.b16 [%0], {%1,%2,%3,%4};" ::"r"(a), "r"(r0), "r"(r1), "r"(r2), "r"(r3) : "memory");
}
__device__ __forceinline__ void stsm2(uint32_t a, uint32_t r0, uint32_t r1) {
  asm volatile("stmatrix.sync.aligned.m8n8.x2.shared.b16 [%0], {%1,%2};" ::"r"(a), "r"(r0), "r"(r1) : "memory");
}
__device__ __forceinline__ void stsm2t(uint32_t a, uint32_t r0, uint32_t r1) {
  asm volatile("stmatrix.sync.aligned.m8n8.x2.trans.shared.b16 [%0], {%1,%2};" ::"r"(a), "r"(r0), "r"(r1) : "memory");
}
__device__ __forceinline__ void mma16816(float* c, uint32_t a0, uint32_t a1, uint32_t a2, uint32_t a3, uint32_t b0, uint32_t b1) {
  asm("mma.sync.aligned.m16n8k16.row.col.f32.bf16.bf16.f32 {%0,%1,%2,%3}, {%4,%5,%6,%7}, {%8,%9}, {%0,%1,%2,%3};"
      : "+f"(c[0]), "+f"(c[1]), "+f"(c[2]), "+f"(c[3]) : "r"(a0), "r"(a1), "r"(a2), "r"(a3), "r"(b0), "r"(b1));
}
__device__ __forceinline__ void bar_sync(int id, int n) { asm volatile("bar.sync %0, %1;" ::"r"(id), "r"(n) : "memory"); }
__device__ __forceinline__ void bar_arrive(int id, int n) { asm volatile("bar.arrive %0, %1;" ::"r"(id), "r"(n) : "memory"); }
__device__ __forceinline__ void wg_fence() { asm volatile("wgmma.fence.sync.aligned;" ::: "memory"); }
__device__ __forceinline__ void wg_commit() { asm volatile("wgmma.commit_group.sync.aligned;" ::: "memory"); }
__device__ __forceinline__ void wg_wait0() { asm volatile("wgmma.wait_group.sync.aligned 0;" ::: "memory"); }
__device__ __forceinline__ void wg_wait1() { asm volatile("wgmma.wait_group.sync.aligned 1;" ::: "memory"); }
__device__ __forceinline__ void fence_async() { asm volatile("fence.proxy.async.shared::cta;" ::: "memory"); }
__device__ __forceinline__ uint32_t opq(uint32_t x, uint32_t z) { uint32_t r; asm volatile("xor.b32 %0, %1, %2;" : "=r"(r) : "r"(x), "r"(z)); return r; }
__device__ __forceinline__ uint64_t mkdesc(uint32_t addr, uint32_t lbo, uint32_t sbo) {
  return (uint64_t)((addr & 0x3FFFF) >> 4) | ((uint64_t)(lbo >> 4) << 16) | ((uint64_t)(sbo >> 4) << 32);
}
__device__ __forceinline__ uint32_t mapa(uint32_t a, uint32_t rank) {
  uint32_t r; asm("mapa.shared::cluster.u32 %0, %1, %2;" : "=r"(r) : "r"(a), "r"(rank)); return r;
}
__device__ __forceinline__ void mbar_init_expect(uint32_t bar, uint32_t bytes) {
  asm volatile("mbarrier.init.shared::cta.b64 [%0], 1;" ::"r"(bar) : "memory");
  asm volatile("mbarrier.arrive.expect_tx.shared::cta.b64 _, [%0], %1;" ::"r"(bar), "r"(bytes) : "memory");
}
__device__ __forceinline__ void mbar_wait(uint32_t bar) {
#pragma unroll 1
  for (int it = 0; it < (1 << 22); it++) {
    uint32_t ok;
    asm volatile("{\n.reg .pred p;\nmbarrier.try_wait.parity.acquire.cluster.shared::cta.b64 p, [%1], 0;\nselp.u32 %0, 1, 0, p;\n}"
                 : "=r"(ok) : "r"(bar) : "memory");
    if (ok) return;
  }
  __trap();
}
__device__ __forceinline__ void st_async4(uint32_t a, uint32_t bar, uint32_t x, uint32_t y, uint32_t z, uint32_t w) {
  asm volatile("st.async.weak.shared::cluster.mbarrier::complete_tx::bytes.v4.b32 [%0], {%2,%3,%4,%5}, [%1];"
               ::"r"(a), "r"(bar), "r"(x), "r"(y), "r"(z), "r"(w) : "memory");
}

struct cf { float re, im; };
__device__ __forceinline__ cf cmul(cf a, cf b) { return {fmaf(a.re, b.re, -a.im * b.im), fmaf(a.re, b.im, a.im * b.re)}; }
__device__ __forceinline__ cf csq(cf a) { return {fmaf(a.re, a.re, -a.im * a.im), (a.re + a.re) * a.im}; }
__device__ __forceinline__ cf cexp_p(float xl, float y, float p) {
  float mag; asm("ex2.approx.ftz.f32 %0, %1;" : "=f"(mag) : "f"(xl * p));
  const float th = y * p;
  const float k = __fadd_rn(fmaf(th, 0.15915494309189535f, 12582912.f), -12582912.f);
  float r = fmaf(k, -6.2831854820251465f, th);
  r = fmaf(k, 1.7484555314695172e-07f, r);
  return {mag * __cosf(r), mag * __sinf(r)};
}
__device__ __forceinline__ uint32_t ysw(int c) { return (uint32_t)(c ^ ((c >> 3) & 3)) * 16u; }

#define CMUL2(OR, OI, xr, xi, yr, yi, nyi) do { OR = hfma2(xr, yr, hmul2(xi, nyi)); OI = hfma2(xr, yi, hmul2(xi, yr)); } while (0)

__device__ __forceinline__ uint32_t gate_slow(const __nv_bfloat16* u, const __nv_bfloat16* gw, int row) {
  float s = 0.f;
  const uint32_t* xr = (const uint32_t*)(u + (size_t)row * D);
  const uint32_t* wr = (const uint32_t*)gw;
#pragma unroll 1
  for (int j = 0; j < D / 2; j++) { const uint32_t pr = hmul2(xr[j], wr[j]); s += bf_lo(pr); s += bf_hi(pr); }
  s = bf_round(s);
  return pack_bf16(1.f / (1.f + expf(-s)), 0.f);
}

__device__ __forceinline__ uint2 gate_ld(int x) {
  uint2 gv;
  asm volatile("ld.relaxed.gpu.global.v2.u32 {%0,%1}, [%2];" : "=r"(gv.x), "=r"(gv.y) : "l"(g_gate + x * 2) : "memory");
  return gv;
}
__device__ __noinline__ uint32_t gate_poll(const Params* pp, int x, uint32_t tag) {
  uint2 gv;
#pragma unroll 1
  for (int spins = 0; spins < (1 << 16); spins++) {
    gv = gate_ld(x);
    if ((gv.x >> 16) == tag && (gv.y >> 16) == tag) return __byte_perm(gv.x, gv.y, 0x5410);
  }
  return __byte_perm(gate_slow(pp->u, pp->gw, x * 2), gate_slow(pp->u, pp->gw, x * 2 + 1), 0x5410);
}
__device__ __forceinline__ uint32_t gate_fin(const Params& p, uint2 gv, int x, uint32_t tag) {
  if ((gv.x >> 16) == tag && (gv.y >> 16) == tag) return __byte_perm(gv.x, gv.y, 0x5410);
  return gate_poll(&p, x, tag);
}

__device__ __forceinline__ void ld4ch(uint32_t* v, uint32_t addr) {
#pragma unroll
  for (int k = 0; k < 4; k++) v[k] = lds32(addr + k * CH_BYTES);
}
__device__ __forceinline__ void skip_terms(uint32_t* ua, uint32_t* ub, uint32_t sb, int x, uint2 dA, uint2 dB) {
  const int c = x >> 2;
  uint32_t uu[4];
  ld4ch(uu, sb + CH_OFF + (x & 3) * 4 + U_OFF + (c & 3) * U_CS + (63 - (c >> 2)) * 16);
#pragma unroll
  for (int k = 0; k < 4; k++) {
    ua[k] = hmul2(uu[k], __byte_perm((k & 2) ? dA.y : dA.x, 0, (k & 1) ? 0x3232 : 0x1010));
    ub[k] = hmul2(uu[k], __byte_perm((k & 2) ? dB.y : dB.x, 0, (k & 1) ? 0x3232 : 0x1010));
  }
}
__device__ __forceinline__ uint4 mix(const uint32_t* a, const uint32_t* b, const uint32_t* ua, const uint32_t* ub, uint32_t g2) {
  const uint32_t h2 = hsub2(0x3f803f80u, g2);
  uint32_t o[4];
#pragma unroll
  for (int k = 0; k < 4; k++) o[k] = hadd2(hmul2(g2, hadd2(a[k], ua[k])), hmul2(h2, hadd2(b[k], ub[k])));
  return make_uint4(__byte_perm(o[0], o[1], 0x5410), __byte_perm(o[2], o[3], 0x5410), __byte_perm(o[0], o[1], 0x7632), __byte_perm(o[2], o[3], 0x7632));
}
__device__ __forceinline__ void send_box(uint32_t sb, int slot, int wtid, uint32_t rank, uint4 r) {
  st_async4(mapa(sb + XIN_OFF + slot * 2048 + wtid * 16, rank ^ 1), mapa(sb + B_X + slot * 8, rank ^ 1), r.x, r.y, r.z, r.w);
}
__device__ __forceinline__ void merge_box(uint32_t sb, const CUtensorMap* tm_out, int slot, int wtid, uint32_t rank, int oc0, uint4 r, int barid) {
  const uint32_t st = sb + RAW_OFF + slot * 4096 + wtid * 16;
  sts64(st + rank * 8, r.x, r.y); sts64(st + 2048 + rank * 8, r.z, r.w);
  mbar_wait(sb + B_X + slot * 8);
  const uint4 q = lds128(sb + XIN_OFF + slot * 2048 + wtid * 16);
  sts64(st + (rank ^ 1) * 8, q.x, q.y); sts64(st + 2048 + (rank ^ 1) * 8, q.z, q.w);
  fence_async();
  bar_sync(barid, 128);
  if (wtid == 0) {
    asm volatile("cp.async.bulk.tensor.3d.global.shared::cta.bulk_group [%0, {%2, %3, %4}], [%1];"
                 ::"l"(tm_out), "r"(sb + RAW_OFF + slot * 4096), "r"(oc0), "r"((2 * slot + (int)rank) * 128), "r"(0) : "memory");
    asm volatile("cp.async.bulk.commit_group;" ::: "memory");
  }
}

__device__ __forceinline__ uint32_t band2(int e, int lo, int hi) {
  uint32_t r = ((uint32_t)(e - lo) <= (uint32_t)(hi - lo) ? 0x3f80u : 0u) | ((uint32_t)(e - 1 - lo) <= (uint32_t)(hi - lo) ? 0x3f800000u : 0u);
  asm volatile("" : "+r"(r));
  return r;
}

__device__ __forceinline__ void stage_done(uint32_t sb, int stage, int lane) {
  __syncwarp();
  if (lane == 0) asm volatile("mbarrier.arrive.shared::cta.b64 _, [%0];" ::"r"(sb + B_ST + 8 * stage) : "memory");
}
#define PK2(v, i) pack_bf16(v[i], v[(i) + 1])

__device__ __forceinline__ void conv_dense(uint32_t sb, uint32_t cb, uint32_t zz) {
  const int lane = threadIdx.x & 31, wq = (threadIdx.x >> 5) & 3, br = wq >> 1, hf = wq & 1, g = lane >> 2, t = lane & 3;
  const uint32_t rb = cb + R_OFF + br * R_BR;
  const int eo = 16 * hf + g - 2 * t;
  const int x0 = RD_X0 - (eo + 536);
  const uint32_t fa = rb + ((g & 1) ? 2 * x0 : RD_CS + 2 * x0 + 2);
  const uint64_t ub = mkdesc(cb + U_OFF, U_CS, 128);
  const uint32_t yd = cb + Y0_OFF + br * 4096 + ysw(4 * (63 - 8 * (lane >> 4) - (lane & 7)) + 2 * hf + ((lane >> 3) & 1));
  uint32_t A[2][4][4];
  float e64[32], e56[28], e48[24];
  auto loadA = [&](int j) {
#pragma unroll
    for (int k = 0; k < 4; k++) {
      const int s = 34 - 4 * j - k;
      if (s >= 0) {
        if (k == 0 && j == 0) A[0][0][2] = lds32(fa + (2 * s + 2) * 16);
        A[j & 1][k][0] = lds32(fa + (2 * s + 1) * 16);
        A[j & 1][k][1] = lds32(fa + (2 * s) * 16);
      }
    }
#pragma unroll
    for (int k = 0; k < 4; k++) {
      if (34 - 4 * j - k >= 0) {
        A[j & 1][k][3] = A[j & 1][k][0];
        if (k) A[j & 1][k][2] = A[j & 1][k - 1][1];
        else if (j) A[j & 1][0][2] = A[(j - 1) & 1][3][1];
      }
    }
  };
  loadA(0); loadA(1);
#pragma unroll
  for (int j = 0; j < 9; j++) {
    if (j == 4) {
      wg_wait0();
      stsm2t(yd - 7 * 512, PK2(e64, 28), PK2(e64, 30));
#pragma unroll
      for (int i = 0; i < 28; i++) e56[i] = FCPY(e64[i]);
      stage_done(sb, 0, lane);
    }
    if (j == 8) {
      wg_wait0();
      stsm2t(yd - 6 * 512, PK2(e56, 24), PK2(e56, 26));
#pragma unroll
      for (int i = 0; i < 24; i++) e48[i] = FCPY(e56[i]);
      stage_done(sb, 1, lane);
    }
    wg_fence();
#pragma unroll
    for (int k = 0; k < 4; k++) {
      const int s = 34 - 4 * j - k;
      if (s >= 0) {
        const int o = 2 * s - 66 + 128;
        const int cc = o & 3, rs = (o >> 2) - 32;
        const uint64_t desc = ub + (uint64_t)((cc * U_CS - rs * 16) >> 4);
        const uint32_t* a = A[j & 1][k];
        if (j < 4) wgmma_rs<64, 0>(e64, a[0], a[1], a[2], a[3], desc, s != 34);
        else if (j < 8) wgmma_rs<56, 0>(e56, a[0], a[1], a[2], a[3], desc, 1);
        else wgmma_rs<48, 0>(e48, a[0], a[1], a[2], a[3], desc, 1);
      }
    }
    wg_commit();
    if (j >= 1 && j < 8) { wg_wait1(); loadA(j + 1); }
  }
  wg_wait0();
#pragma unroll
  for (int i = 0; i < 6; i += 2) stsm4t(yd - i * 512, PK2(e48, 4 * i), PK2(e48, 4 * i + 2), PK2(e48, 4 * i + 4), PK2(e48, 4 * i + 6));
}

__device__ __noinline__ void gate_cta(const Params* pp) {
  const __nv_bfloat16 *u = pp->u, *gw = pp->gw;
  const int lane = threadIdx.x & 31;
  unsigned int epoch;
  asm volatile("ld.relaxed.gpu.global.u32 %0, [%1];" : "=r"(epoch) : "l"(&g_epoch) : "memory");
  const uint4 gw0 = ldg128(gw + lane * 8), gw1 = ldg128(gw + 256 + lane * 8);
  const uint32_t ws[8] = {gw0.x, gw0.y, gw0.z, gw0.w, gw1.x, gw1.y, gw1.z, gw1.w};
  const uint32_t tag = (epoch + 1) & 0xffffu;
  uint4 gx[4][2], nx[4][2];
  int grow = (blockIdx.x * 20 + (threadIdx.x >> 5)) * 4;
#pragma unroll
  for (int i = 0; i < 4; i++) {
    nx[i][0] = ldg128(u + (size_t)(grow + i) * D + lane * 8);
    nx[i][1] = ldg128(u + (size_t)(grow + i) * D + 256 + lane * 8);
  }
#pragma unroll 1
  for (; grow < L; grow += 80 * NGATE) {
    const int nrow = min(grow + 80 * NGATE, L - 4);
#pragma unroll
    for (int i = 0; i < 4; i++) {
      gx[i][0] = nx[i][0]; gx[i][1] = nx[i][1];
      nx[i][0] = ldg128(u + (size_t)(nrow + i) * D + lane * 8);
      nx[i][1] = ldg128(u + (size_t)(nrow + i) * D + 256 + lane * 8);
    }
    float c[2][4];
#pragma unroll
    for (int i = 0; i < 2; i++) {
      const uint4 *x = gx[2 * i], *y = gx[2 * i + 1];
      const uint32_t xs[8] = {x[0].x, x[0].y, x[0].z, x[0].w, x[1].x, x[1].y, x[1].z, x[1].w};
      const uint32_t ys[8] = {y[0].x, y[0].y, y[0].z, y[0].w, y[1].x, y[1].y, y[1].z, y[1].w};
      c[i][0] = c[i][1] = c[i][2] = c[i][3] = 0.f;
#pragma unroll
      for (int j = 0; j < 8; j += 2)
        mma16816(c[i], hmul2(xs[j], ws[j]), hmul2(ys[j], ws[j]), hmul2(xs[j + 1], ws[j + 1]), hmul2(ys[j + 1], ws[j + 1]), 0x3f803f80u, 0x3f803f80u);
    }
    float s = (lane & 2) ? ((lane & 1) ? c[1][2] : c[1][0]) : ((lane & 1) ? c[0][2] : c[0][0]);
#pragma unroll
    for (int o = 4; o < 32; o <<= 1) s += __shfl_xor_sync(0xffffffffu, s, o);
    s = bf_round(s);
    const float gv = 1.f / (1.f + expf(-s));
    const uint32_t w = (tag << 16) | (pack_bf16(gv, 0.f) & 0xffffu);
    if (lane < 4) asm volatile("st.relaxed.gpu.global.u32 [%0], %1;" ::"l"(&g_gate[grow + lane]), "r"(w) : "memory");
  }
  __syncthreads();
  if (threadIdx.x == 0 && atomicAdd(&g_ticket, 1u) == NCTA + NGATE - 1) { g_ticket = 0; g_epoch = epoch + 1; }
}

__global__ void __cluster_dims__(2, 1, 1) __launch_bounds__(640, 1)
ssm_kernel(const __grid_constant__ Params p, const __grid_constant__ CUtensorMap tm_in, const __grid_constant__ CUtensorMap tm_out) {
  extern __shared__ __align__(1024) unsigned char smem_raw[];
  const uint32_t sb = (uint32_t)__cvta_generic_to_shared(smem_raw);
  const int tid = threadIdx.x, lane = tid & 31;
  const int warp = __shfl_sync(0xffffffffu, tid >> 5, 0);
  const int ch = warp >> 2, wq = warp & 3, br = wq >> 1, hf = wq & 1;
  const int g = lane >> 2, t = lane & 3;
  if (__builtin_expect(blockIdx.x < NGATE, 0)) { gate_cta(&p); return; }
  const int bid = blockIdx.x - NGATE;
  const int d = bid * 4 + ch;
  const uint32_t rank = blockIdx.x & 1;
  const uint32_t cb = sb + CH_OFF + ch * CH_BYTES;
  const int wtid = tid & 127;
  const int oc0 = (bid >> 1) * 8;
  STAMP(0); GT(0);

  if (warp >= 16) {
    if (wtid == 0) {
      mbar_init_expect(sb + B_RAW, 32768);
#pragma unroll
      for (int i = 0; i < 4; i++) mbar_init_expect(sb + B_X + 8 * i, 2048);
      asm volatile("mbarrier.init.shared::cta.b64 [%0], 128;" ::"r"(sb + B_U) : "memory");
      asm volatile("mbarrier.init.shared::cta.b64 [%0], 128;" ::"r"(sb + B_W) : "memory");
#pragma unroll
      for (int i = 0; i < 7; i++) asm volatile("mbarrier.init.shared::cta.b64 [%0], 16;" ::"r"(sb + B_ST + 8 * i) : "memory");
      asm volatile("fence.mbarrier_init.release.cluster;" ::: "memory");
      asm volatile("fence.proxy.async.shared::cta;" ::: "memory");
    }
    __syncwarp();
    asm volatile("barrier.cluster.arrive.relaxed.aligned;" ::: "memory");
    unsigned int epoch;
    asm volatile("ld.relaxed.gpu.global.u32 %0, [%1];" : "=r"(epoch) : "l"(&g_epoch) : "memory");
    asm volatile("barrier.cluster.wait.aligned;" ::: "memory");
    if (wtid == 0) {
      asm volatile("cp.async.bulk.tensor.5d.shared::cluster.global.mbarrier::complete_tx::bytes.multicast::cluster [%0], [%1, {%3, %4, %4, %4, %5}], [%2], %6;"
                   ::"r"(sb + RAW_OFF + rank * 16384), "l"(&tm_in), "r"(sb + B_RAW), "r"(oc0), "r"(0), "r"((int)rank * 32), "h"((unsigned short)3) : "memory");
    }
    sts128(sb + CH_OFF + wq * CH_BYTES + U_OFF + (lane >> 3) * U_CS + (64 + (lane & 7)) * 16, 0, 0, 0, 0);
    const uint2 dA = ldg64(p.A_D + bid * 4), dB = ldg64(p.B_D + bid * 4);
    uint32_t BA[3][4], BB[4][4];
    {
      const int l1 = br ? 3 : 6, h1 = br ? 5 : 10, l2 = br ? 5 : 12, h2 = br ? 11 : 20;
#pragma unroll
      for (int i = 0; i < 4; i++) {
        const int e = 16 * hf + g - 2 * t + 32 - 16 * i;
        BB[i][0] = band2(e, l2, h2); BB[i][1] = band2(e + 8, l2, h2); BB[i][2] = band2(e - 8, l2, h2); BB[i][3] = BB[i][0];
        if (i) { BA[i - 1][0] = band2(e, l1, h1); BA[i - 1][1] = band2(e + 8, l1, h1); BA[i - 1][2] = band2(e - 8, l1, h1); BA[i - 1][3] = BA[i - 1][0]; }
      }
    }
    const uint32_t tag = (epoch + 1) & 0xffffu;
    if (wtid == 0) sts32(sb + TAG_OFF, tag);
    STAMP(3);
    mbar_wait(sb + B_RAW);
    STAMP(4);
    {
      const uint32_t dst = sb + CH_OFF + (g & 3) * CH_BYTES + U_OFF + t * U_CS + (63 - wq * 16) * 16;
#pragma unroll
      for (int h = 0; h < 2; h++) {
        uint32_t r[8][4];
#pragma unroll
        for (int i = 0; i < 8; i++) ldsm4t(sb + RAW_OFF + (wq * 16 + h * 8 + i) * 512 + lane * 16, r[i][0], r[i][1], r[i][2], r[i][3]);
        if ((uint32_t)(g >> 2) == rank) {
#pragma unroll
          for (int i = 0; i < 8; i++) sts128(dst - (h * 8 + i) * 16, r[i][0], r[i][1], r[i][2], r[i][3]);
        }
      }
    }
    fence_async();
    asm volatile("mbarrier.arrive.shared::cta.b64 _, [%0];" ::"r"(sb + B_U) : "memory");
    bar_sync(5, 128);
    STAMP(5);
    {
      const int mrow = lane & 7, mi = lane >> 3;
      const uint64_t ub0 = mkdesc(sb + CH_OFF + U_OFF, U_CS, 128);
      float w1[24], w2[16];
#pragma unroll
      for (int i = 0; i < 24; i++) w1[i] = 0.f;
#pragma unroll
      for (int i = 0; i < 16; i++) w2[i] = 0.f;
      uint32_t wa, wb;
      {
        const int c = 4 * (47 - 8 * (mi >> 1) - mrow) + 2 * hf + (mi & 1);
        wa = sb + CH_OFF + (br ? W3_OFF : W5_OFF) + (5 - (c >> 5)) * 576 + ((c & 31) >> 3) * 144 + (c & 7) * 16;
        const int c2 = c - 64, pp = c2 >> 1;
        wb = sb + CH_OFF + (br ? W7_OFF : W9_OFF) + (1 - (pp >> 5)) * 1152 + (c2 & 1) * 576 + ((pp & 31) >> 3) * 144 + (pp & 7) * 16;
      }
#pragma unroll 1
      for (int k = 0; k < 4; k++) {
        wg_fence();
#pragma unroll
        for (int i = 0; i < 3; i++)
          wgmma_rs<48, 0>(w1, BA[i][0], BA[i][1], BA[i][2], BA[i][3],
                          ub0 + (uint64_t)((k * CH_BYTES + ((2 * i + 2) & 3) * U_CS + (16 + (i == 0)) * 16) >> 4), i);
        wg_commit();
#pragma unroll
        for (int i = 0; i < 4; i++)
          wgmma_rs<32, 0>(w2, BB[i][0], BB[i][1], BB[i][2], BB[i][3],
                          ub0 + (uint64_t)((k * CH_BYTES + ((2 * i) & 3) * U_CS + (32 + (i < 2)) * 16) >> 4), i);
        wg_commit();
        wg_wait1();
#pragma unroll
        for (int i = 0; i < 3; i++) stsm4t(wa + k * CH_BYTES + i * 1152, PK2(w1, 8 * i), PK2(w1, 8 * i + 2), PK2(w1, 8 * i + 4), PK2(w1, 8 * i + 6));
        wg_wait0();
#pragma unroll
        for (int i = 0; i < 2; i++) stsm4t(wb + k * CH_BYTES + i * 1152, PK2(w2, 8 * i), PK2(w2, 8 * i + 2), PK2(w2, 8 * i + 4), PK2(w2, 8 * i + 6));
      }
    }
    fence_async();
    asm volatile("mbarrier.arrive.shared::cta.b64 _, [%0];" ::"r"(sb + B_W) : "memory");
    STAMP(7);
    {
      const int bsel = (int)rank ^ br ^ 1, xl = wtid & 63;
      uint2 gl[4];
      uint32_t ua[4][4], ub[4][4];
#pragma unroll
      for (int i = 0; i < 4; i++) gl[i] = gate_ld((2 * (i >> 1) + bsel) * 128 + (i & 1) * 64 + xl);
#pragma unroll
      for (int i = 0; i < 4; i++) skip_terms(ua[i], ub[i], sb, (2 * (i >> 1) + bsel) * 128 + (i & 1) * 64 + xl, dA, dB);
      const uint32_t yo = sb + CH_OFF + (xl & 3) * 4 + ysw(xl >> 2) + bsel * 512;
#pragma unroll
      for (int slot = 0; slot < 2; slot++) {
        const int box = 2 * slot + bsel;
        uint32_t g2[2], ya[2][4], yb[2][4];
#pragma unroll
        for (int h = 0; h < 2; h++) g2[h] = gate_fin(p, gl[2 * slot + h], box * 128 + h * 64 + xl, tag);
        mbar_wait(sb + B_ST + 8 * box);
        STAMP(8 + slot);
#pragma unroll
        for (int h = 0; h < 2; h++) {
          const uint32_t yh = (yo ^ (h * 32)) + h * 256 + slot * 1024;
          ld4ch(ya[h], yh + Y0_OFF); ld4ch(yb[h], yh + Y0_OFF + 4096);
          if (slot) {
            uint32_t a2[4], b2[4];
            ld4ch(a2, yh + Y2_OFF - 1024); ld4ch(b2, yh + Y2_OFF - 1024 + 3072);
#pragma unroll
            for (int k = 0; k < 4; k++) { ya[h][k] = hadd2(ya[h][k], a2[k]); yb[h][k] = hadd2(yb[h][k], b2[k]); }
          }
        }
        const uint4 r0 = mix(ya[0], yb[0], ua[2 * slot], ub[2 * slot], g2[0]), r1 = mix(ya[1], yb[1], ua[2 * slot + 1], ub[2 * slot + 1], g2[1]);
        if (br == 0) { send_box(sb, slot, xl, rank, r0); send_box(sb, slot, xl + 64, rank, r1); }
        else {
          const uint32_t st = sb + RAW_OFF + slot * 4096 + xl * 16, xin = sb + XIN_OFF + slot * 2048 + xl * 16;
          sts64(st + rank * 8, r0.x, r0.y); sts64(st + 2048 + rank * 8, r0.z, r0.w);
          sts64(st + 1024 + rank * 8, r1.x, r1.y); sts64(st + 3072 + rank * 8, r1.z, r1.w);
          mbar_wait(sb + B_X + slot * 8);
          const uint4 q0 = lds128(xin), q1 = lds128(xin + 1024);
          sts64(st + (rank ^ 1) * 8, q0.x, q0.y); sts64(st + 2048 + (rank ^ 1) * 8, q0.z, q0.w);
          sts64(st + 1024 + (rank ^ 1) * 8, q1.x, q1.y); sts64(st + 3072 + (rank ^ 1) * 8, q1.z, q1.w);
          fence_async();
          bar_sync(6, 64);
          if (xl == 0) {
            asm volatile("cp.async.bulk.tensor.3d.global.shared::cta.bulk_group [%0, {%2, %3, %4}], [%1];"
                         ::"l"(&tm_out), "r"(sb + RAW_OFF + slot * 4096), "r"(oc0), "r"(box * 128), "r"(0) : "memory");
            asm volatile("cp.async.bulk.commit_group;" ::: "memory");
          }
        }
        STAMP(10 + slot);
      }
    }
    if (wtid == 0 && atomicAdd(&g_ticket, 1u) == NCTA + NGATE - 1) { g_ticket = 0; g_epoch = epoch + 1; }
    if (wtid == 64) asm volatile("cp.async.bulk.wait_group.read 0;" ::: "memory");
    STAMP(15);
    return;
  }
  asm volatile("barrier.cluster.arrive.relaxed.aligned;" ::: "memory");

  const int moff = (bid * 4 + (tid >> 7)) * NM + (tid & 63) * 2;
  const int brt = (tid >> 6) & 1;
  const __nv_bfloat16* const* tp = p.t + (brt ? 0 : 6);
  const uint32_t q0 = *(const uint32_t*)(tp[0] + moff), q1 = *(const uint32_t*)(tp[1] + moff);
  const uint32_t q2 = *(const uint32_t*)(tp[2] + moff), q3 = *(const uint32_t*)(tp[3] + moff);
  const uint2 ldt4 = *(const uint2*)(tp[4] + bid * 4);
  const uint32_t q4 = *(const uint32_t*)(tp[brt ? 2 : 5] + moff), q5 = *(const uint32_t*)(tp[brt ? 3 : 6] + moff);

  for (int i = wtid & 63; i < R_BR / 16; i += 64) sts128(cb + R_OFF + br * R_BR + i * 16, 0, 0, 0, 0);
  STAMP(1);

  float acc[5][4];
  float k2048 = 0.f;
  const uint32_t scr = cb + Y0_OFF + wq * SCR_BYTES;
  const uint32_t scr2 = sb + XIN_OFF + warp * 640;
  {
    const uint32_t ldt2 = (ch & 2) ? ldt4.y : ldt4.x;
    const float dt = bf_round(expf((ch & 1) ? bf_hi(ldt2) : bf_lo(ldt2)));
#pragma unroll
    for (int i = 0; i < 5; i++) acc[i][0] = acc[i][1] = acc[i][2] = acc[i][3] = 0.f;
    STAMP(2);
    const uint32_t tb = scr + lane * 16;
    const uint32_t ta = scr + (lane >> 3) * 512 + (lane & 7) * 16;
    const uint32_t tc = ((lane & 8) ? scr2 : scr + 4096) + (lane >> 4) * 128 + (lane & 7) * 16;
    const uint32_t tm = scr2 + 512 + ((lane >> 3) & 1) * 64 + (lane >> 4) * 16;
    cf cc[2], zz1[2], zz128[2];
#pragma unroll
    for (int r = 0; r < 2; r++) {
      float v0 = r ? bf_hi(q0) : bf_lo(q0), v1 = r ? bf_hi(q1) : bf_lo(q1), v2 = r ? bf_hi(q2) : bf_lo(q2);
      float v3 = r ? bf_hi(q3) : bf_lo(q3), v4 = r ? bf_hi(q4) : bf_lo(q4), v5 = r ? bf_hi(q5) : bf_lo(q5);
      if (br == 0) { cc[r] = cmul(cf{v2, v3}, cf{dt * v4, dt * v5}); }
      else { v0 = -bf_round(expf(v0)); cc[r] = cf{2.f * dt * v2, 2.f * dt * v3}; }
      const float xl = (dt * v0) * 1.4426950408889634f, y = dt * v1;
      zz1[r] = cexp_p(xl, y, 1.f); zz128[r] = cexp_p(xl, y, 128.f);
    }
    uint32_t T[10][4], m4;
    auto produce = [&](int r) {
      const cf c = cc[r], z1 = zz1[r], z128 = zz128[r];
      const cf z2 = csq(z1), z4 = csq(z2), z8 = csq(z4);
      const cf w8 = {z8.re, -z8.im};
      const cf z16 = csq(w8), z24 = cmul(z16, w8), z32 = csq(z16), z40 = cmul(z32, w8), z48 = csq(z24), z56 = cmul(z32, z24), z64 = csq(z32);
      const cf z256 = csq(z128), z512 = csq(z256), z1024 = csq(z512), z2048 = csq(z1024);
      k2048 += fmaf(c.re, z2048.re, -c.im * z2048.im);
      {
        T[0][0] = pack_bf16(1.f, z8.re); T[0][1] = pack_bf16(z16.re, z24.re); T[0][2] = pack_bf16(z32.re, z40.re); T[0][3] = pack_bf16(z48.re, z56.re);
        T[2][0] = pack_bf16(0.f, w8.im); T[2][1] = pack_bf16(z16.im, z24.im); T[2][2] = pack_bf16(z32.im, z40.im); T[2][3] = pack_bf16(z48.im, z56.im);
        const uint32_t yr = pack_bf16(z64.re, z64.re), yi = pack_bf16(z64.im, z64.im), nyi = yi ^ 0x80008000u;
#pragma unroll
        for (int i = 0; i < 4; i++) CMUL2(T[1][i], T[3][i], T[0][i], T[2][i], yr, yi, nyi);
      }
      {
        const cf h1 = cmul(c, z128), h2 = cmul(c, z256), h3 = cmul(h1, z256), h4 = cmul(c, z512), h5 = cmul(h1, z512), h6 = cmul(h2, z512), h7 = cmul(h3, z512);
        const cf e1 = cmul(c, z1), e2 = cmul(c, z2), e3 = cmul(e1, z2), e129 = cmul(h1, z1), e130 = cmul(h1, z2), e131 = cmul(e129, z2);
        const cf e258 = cmul(h2, z2), e386 = cmul(h3, z2);
        T[4][0] = pack_bf16(c.re, e1.re); T[4][1] = pack_bf16(e2.re, e3.re); T[4][2] = pack_bf16(h1.re, e129.re); T[4][3] = pack_bf16(e130.re, e131.re);
        T[5][0] = pack_bf16(c.im, e1.im); T[5][1] = pack_bf16(e2.im, e3.im); T[5][2] = pack_bf16(h1.im, e129.im); T[5][3] = pack_bf16(e130.im, e131.im);
        T[6][0] = pack_bf16(h2.re, e258.re); T[6][1] = pack_bf16(h3.re, e386.re); T[6][2] = pack_bf16(h4.re, h5.re); T[6][3] = pack_bf16(h6.re, h7.re);
        T[7][0] = pack_bf16(h2.im, e258.im); T[7][1] = pack_bf16(h3.im, e386.im); T[7][2] = pack_bf16(h4.im, h5.im); T[7][3] = pack_bf16(h6.im, h7.im);
        const uint32_t xr[4] = {__byte_perm(T[4][0], T[4][2], 0x5410), __byte_perm(T[6][0], T[6][1], 0x5410), T[6][2], T[6][3]};
        const uint32_t xi[4] = {__byte_perm(T[5][0], T[5][2], 0x5410), __byte_perm(T[7][0], T[7][1], 0x5410), T[7][2], T[7][3]};
        const uint32_t yr = pack_bf16(z1024.re, z1024.re), yi = pack_bf16(z1024.im, z1024.im), nyi = yi ^ 0x80008000u;
#pragma unroll
        for (int i = 0; i < 4; i++) CMUL2(T[8][i], T[9][i], xr[i], xi[i], yr, yi, nyi);
        m4 = pack_bf16(z4.re, z4.im);
      }
    };
    auto store = [&]() {
#pragma unroll
      for (int m = 0; m < 9; m++) sts128(tb + m * 512, T[m][0], T[m][1], T[m][2], T[m][3]);
      sts128(scr2 + lane * 16, T[9][0], T[9][1], T[9][2], T[9][3]);
      sts16(scr2 + 512 + lane * 2, m4); sts16(scr2 + 576 + lane * 2, m4 >> 16);
    };
    auto consume = [&]() {
#pragma unroll
      for (int kp = 0; kp < 2; kp++) {
        uint32_t rr[2], ri[2], yr[2], yi[2];
        ldsm4t(tc + kp * 256, rr[0], ri[0], rr[1], ri[1]);
        ldsm4(tm + kp * 32, yr[0], yi[0], yr[1], yi[1]);
#pragma unroll
        for (int k2 = 0; k2 < 2; k2++) {
          const int kk = kp * 2 + k2;
          uint32_t a0, a1, a2, a3, pr, pi, qr, qi, xr, xi;
          ldsm4t(ta + kk * 128, a0, a1, a2, a3);
          ldsm4t(ta + 2048 + kk * 128, pr, pi, qr, qi);
          const uint32_t nyi = yi[k2] ^ 0x80008000u;
          mma16816(acc[0], a0, a1, a2, a3, pr, pi);
          mma16816(acc[2], a0, a1, a2, a3, qr, qi);
          mma16816(acc[4], a0, a1, a2, a3, rr[k2], ri[k2]);
          CMUL2(xr, xi, pr, pi, yr[k2], yi[k2], nyi);
          mma16816(acc[1], a0, a1, a2, a3, xr, xi);
          CMUL2(xr, xi, qr, qi, yr[k2], yi[k2], nyi);
          mma16816(acc[3], a0, a1, a2, a3, xr, xi);
        }
      }
    };
    produce(0); store();
    __syncwarp();
    consume(); produce(1);
    __syncwarp();
    store();
#pragma unroll
    for (int o = 16; o; o >>= 1) k2048 += __shfl_xor_sync(0xffffffffu, k2048, o);
    __syncwarp();
    consume();
  }
  STAMP(3);
  __syncwarp();
  {
    const uint32_t xs = scr + lane * 16;
#define OTH(i, k) __float_as_uint(hf ? acc[i][k] : acc[i][2 + (k)])
    sts128(xs, OTH(0, 0), OTH(0, 1), OTH(1, 0), OTH(1, 1));
    sts128(xs + 512, OTH(2, 0), OTH(2, 1), OTH(3, 0), OTH(3, 1));
    sts128(xs + 1024, OTH(4, 0), OTH(4, 1), __float_as_uint(k2048), 0);
#undef OTH
  }

  bar_sync(7 + (warp >> 1), 64);
  STAMP(4);
  {
    const uint32_t xo = cb + Y0_OFF + (wq ^ 1) * SCR_BYTES + lane * 16;
    const uint4 o0 = lds128(xo), o1 = lds128(xo + 512), o2 = lds128(xo + 1024);
    const uint32_t rb = cb + R_OFF + br * R_BR;
#define OWN(i, k) (hf ? acc[i][2 + (k)] : acc[i][k])
    const uint32_t vP = pack_bf16(OWN(0, 1) + __uint_as_float(o0.y), OWN(0, 0) + __uint_as_float(o0.x));
    const uint32_t vP4 = pack_bf16(OWN(1, 1) + __uint_as_float(o0.w), OWN(1, 0) + __uint_as_float(o0.z));
    const uint32_t vQ = pack_bf16(OWN(2, 1) + __uint_as_float(o1.y), OWN(2, 0) + __uint_as_float(o1.x));
    const uint32_t vQ4 = pack_bf16(OWN(3, 1) + __uint_as_float(o1.w), OWN(3, 0) + __uint_as_float(o1.z));
    const uint32_t vR = pack_bf16(OWN(4, 1) + __uint_as_float(o2.y), OWN(4, 0) + __uint_as_float(o2.x));
#undef OWN
    const int j = g + 8 * hf;
    {
      const int a = 2 * (t & 1) + 64 * (t & 2) + 8 * j;
      const uint32_t ad = rb + 2 * (RD_X0 - 1 - a);
      const uint32_t a1 = (t & 2) ? ad - 8 : ad, a2 = (t & 2) ? ad : ad - 8;
      const uint32_t w1 = (t & 2) ? vP4 : vP, w2 = (t & 2) ? vP : vP4;
      sts32(a1, w1); sts32(a2, w2);
      sts16(a1 + RD_CS + 2, w1); sts16(a1 + RD_CS + 4, w1 >> 16);
      sts16(a2 + RD_CS + 2, w2); sts16(a2 + RD_CS + 4, w2 >> 16);
    }
    if (t < 2) {
      const int b = 256 + 128 * t + 8 * j;
      const uint32_t ad = rb + 2 * (RD_X0 - 6 - b);
      const uint32_t v22 = __byte_perm(vQ4, 0, 0x3232), v00 = __byte_perm(vQ, 0, 0x3232);
      sts16(ad, vQ4);
      sts64(ad + 2, v22, __byte_perm(vQ4, vQ, 0x5432));
      sts32(ad + 10, v00);
      if (b != 256) { sts16(ad + 14, v00); sts128(ad + RD_CS + 2, vQ4, v22, vQ, v00); }
      else { sts64(ad + RD_CS + 2, vQ4, v22); sts32(ad + RD_CS + 10, vQ); sts16(ad + RD_CS + 14, v00); }
    } else {
      const uint32_t ao = rb + R_O2 + 2 * (159 - (32 * t + j)), ae = ao - (R_O2 - R_E2) + 2;
      sts16(ao, vQ4 >> 16); sts16(ao + RS_CS + 2, vQ4 >> 16); sts16(ao - 32, vQ4); sts16(ao - 32 + RS_CS + 2, vQ4);
      sts16(ae - 32, vQ); sts16(ae - 32 + RS_CS + 2, vQ);
      if (lane != 2 || hf) { sts16(ae, vQ >> 16); sts16(ae + RS_CS + 2, vQ >> 16); }
      else {
        const uint32_t vv = __byte_perm(vQ, 0, 0x3232), ad = rb + 2 * (RD_X0 - 514);
        sts16(ad, vv); sts32(ad + 2, vv); sts16(ad + 6, vv); sts64(ad + RD_CS + 2, vv, vv);
      }
    }
    {
      const uint32_t a = rb + ((g & 1) ? R_O3 : R_E3 + 2) + 2 * (159 - (64 + 16 * t + (j >> 1)));
      const bool p1024 = (lane == 0) && (hf == 0);
      const uint32_t a00 = p1024 ? rb + R_E2 + 2 * (159 - 127) : a;
      sts16(a00, vR >> 16); sts16(a00 + RS_CS + 2, vR >> 16);
      sts16(a - 16, vR); sts16(a - 16 + RS_CS + 2, vR);
      if (p1024) {
        sts32(sb + K1024_OFF + (ch * 2 + br) * 4, __byte_perm(vR, 0, 0x3232));
        const uint32_t kv = pack_bf16(k2048 + __uint_as_float(o2.z), 0.f);
        sts16(rb + R_E3 + 2 * (159 - 127), kv); sts16(rb + R_E3 + 2 * (159 - 127) + RS_CS + 2, kv);
      }
    }
  }
  STAMP(5);
  asm volatile("barrier.cluster.wait.aligned;" ::: "memory");
  bar_sync(7 + (warp >> 1), 64);
  mbar_wait(sb + B_U);
  STAMP(6);

  const uint32_t zz = lds32(cb + R_OFF + br * R_BR);
  conv_dense(sb, cb, zz);
  STAMP(8);
  {
    const int x = (4 + ch) * 128 + wtid, c = x >> 2;
    const uint2 dA = ldg64(p.A_D + bid * 4), dB = ldg64(p.B_D + bid * 4);
    const uint2 gl = gate_ld(x);
    const uint32_t rb = cb + R_OFF + br * R_BR;
    float e48[24], e40[20], e32[16], h32[16], h16[8];
    const int x1 = 159 - (16 * hf + g - 2 * t + 136);
    const uint32_t fs = rb + ((g & 1) ? 2 * x1 : RS_CS + 2 * x1 + 2);
    uint32_t A[2][4][4];
    auto loadA = [&](int buf, uint32_t oe, uint32_t oo, int i0) {
#pragma unroll
      for (int a = 0; a < 2; a++) {
        const uint32_t base = fs + (a ? oo : oe) + i0 * 16;
        uint32_t* k0 = A[buf][2 * a];
        uint32_t* k1 = A[buf][2 * a + 1];
        k0[1] = lds32(base); k0[0] = lds32(base + 16); k0[2] = lds32(base + 32); k1[0] = lds32(base + 48); k1[2] = lds32(base + 64);
        k0[3] = k0[0]; k1[1] = k0[2]; k1[3] = k1[0];
      }
    };
    loadA(0, R_E2, R_O2, 8);
    loadA(1, R_E2, R_O2, 4);
    mbar_wait(sb + B_W);
    const uint64_t d5 = mkdesc(cb + W5_OFF, 144, 576), d3 = mkdesc(cb + W3_OFF, 144, 576);
    const uint64_t d9 = mkdesc(cb + W9_OFF, 144, 576), d7 = mkdesc(cb + W7_OFF, 144, 576);
    const uint32_t y2d = cb + Y2_OFF + br * 3072 + ysw(32 * (5 - (lane >> 4)) + 16 * hf + (lane & 15));
    const uint32_t y3d = cb + Y3_OFF + br * 2048 + ysw(2 * (16 * hf + (lane & 15)) + (lane >> 4));
#define FAR4(N, ACC, BUF, DA, DB, OFF, FIRST)                                                            \
    wg_fence();                                                                                           \
    _Pragma("unroll") for (int k = 0; k < 4; k++) {                                                      \
      const uint32_t* a = A[BUF][k];                                                                      \
      wgmma_rs<N, 1>(ACC, a[0], a[1], a[2], a[3], ((k >> 1) ? DB : DA) + (k & 1) * 18 + (OFF), !(FIRST) || k); \
    }                                                                                                     \
    wg_commit();
    FAR4(48, e48, 0, d5, d3, 0, 1)
    wg_wait0();
    loadA(0, R_E2, R_O2, 0);
    stsm2(y2d - 5 * 512, PK2(e48, 20), PK2(e48, 22));
#pragma unroll
    for (int i = 0; i < 20; i++) e40[i] = FCPY(e48[i]);
    stage_done(sb, 2, lane);
    FAR4(40, e40, 1, d5, d3, 36, 0)
    wg_wait0();
    loadA(1, R_E3, R_O3, 8);
    stsm2(y2d - 4 * 512, PK2(e40, 16), PK2(e40, 18));
#pragma unroll
    for (int i = 0; i < 16; i++) e32[i] = FCPY(e40[i]);
    stage_done(sb, 3, lane);
    FAR4(32, e32, 0, d5, d3, 72, 0)
    FAR4(32, h32, 1, d9, d7, 0, 1)
    wg_wait1();
    loadA(0, R_E3, R_O3, 4);
    stsm4(y2d, PK2(e32, 0), PK2(e32, 2), PK2(e32, 4), PK2(e32, 6));
    stsm4(y2d - 2 * 512, PK2(e32, 8), PK2(e32, 10), PK2(e32, 12), PK2(e32, 14));
    stage_done(sb, 4, lane);
    STAMP(9);
    wg_wait0();
    stsm4(y3d, PK2(h32, 8), PK2(h32, 10), PK2(h32, 12), PK2(h32, 14));
#pragma unroll
    for (int i = 0; i < 8; i++) h16[i] = FCPY(h32[i]);
    stage_done(sb, 5, lane);
    FAR4(16, h16, 0, d9, d7, 72, 0)
#undef FAR4
    const uint32_t yo = sb + CH_OFF + (x & 3) * 4 + ysw(c);
    uint32_t ua[4], ub[4], ya[4], yb[4], a2[4], b2[4], a3[4], b3[4], s2[4];
    skip_terms(ua, ub, sb, x, dA, dB);
    {
      const int xa = x - 514, xb = x - 513, ca = xa >> 2, cb2 = xb >> 2;
      ld4ch(s2, sb + CH_OFF + U_OFF + (xa & 3) * 4 + (ca & 3) * U_CS + (63 - (ca >> 2)) * 16);
      ld4ch(a3, sb + CH_OFF + U_OFF + (xb & 3) * 4 + (cb2 & 3) * U_CS + (63 - (cb2 >> 2)) * 16);
#pragma unroll
      for (int k = 0; k < 4; k++) s2[k] = hadd2(s2[k], __byte_perm(s2[k], a3[k], 0x5432));
    }
    const uint32_t tag = lds32(sb + TAG_OFF);
    wg_wait0();
    stsm4(y3d + 1024, PK2(h16, 0), PK2(h16, 2), PK2(h16, 4), PK2(h16, 6));
    stage_done(sb, 6, lane);
    STAMP(10);
    const uint32_t g2 = gate_fin(p, gl, x, tag);
    mbar_wait(sb + B_ST + 8 * 4);
    const uint4 k0 = lds128(sb + K1024_OFF), k1 = lds128(sb + K1024_OFF + 16);
    const uint32_t kk[8] = {k0.x, k0.y, k0.z, k0.w, k1.x, k1.y, k1.z, k1.w};
    ld4ch(ya, yo + Y0_OFF); ld4ch(yb, yo + Y0_OFF + 4096);
    ld4ch(a2, yo + Y2_OFF - 1024); ld4ch(b2, yo + Y2_OFF - 1024 + 3072);
    mbar_wait(sb + B_ST + 8 * (5 + (ch >> 1)));
    STAMP(12);
    ld4ch(a3, yo + Y3_OFF - 2048); ld4ch(b3, yo + Y3_OFF - 2048 + 2048);
#pragma unroll
    for (int k = 0; k < 4; k++) {
      ya[k] = hadd2(ya[k], hadd2(hfma2(kk[2 * k], s2[k], a2[k]), a3[k]));
      yb[k] = hadd2(yb[k], hadd2(hfma2(kk[2 * k + 1], s2[k], b2[k]), b3[k]));
    }
    const uint4 r = mix(ya, yb, ua, ub, g2);
    if ((uint32_t)(ch & 1) != rank) send_box(sb, 2 + (ch >> 1), wtid, rank, r);
    else merge_box(sb, &tm_out, 2 + (ch >> 1), wtid, rank, oc0, r, 1 + ch);
  }
  STAMP(14);
  if (wtid == 0) asm volatile("cp.async.bulk.wait_group.read 0;" ::: "memory");
  STAMP(15); GT(1);
}

typedef CUresult (*EncodeFn)(CUtensorMap*, CUtensorMapDataType, cuuint32_t, void*, const cuuint64_t*, const cuuint64_t*,
                             const cuuint32_t*, const cuuint32_t*, CUtensorMapInterleave, CUtensorMapSwizzle,
                             CUtensorMapL2promotion, CUtensorMapFloatOOBfill);

}

extern "C" void kernel_launch(void* const* d_in, const int* in_sizes, int n_in, void* d_out, int out_size) {
  (void)in_sizes; (void)n_in; (void)out_size;
  typedef const __nv_bfloat16* bp;
  Params p;
  p.t[0] = (bp)d_in[10]; p.t[1] = (bp)d_in[11]; p.t[2] = (bp)d_in[12]; p.t[3] = (bp)d_in[13]; p.t[4] = (bp)d_in[14]; p.t[5] = nullptr;
  p.t[6] = (bp)d_in[1]; p.t[7] = (bp)d_in[2]; p.t[8] = (bp)d_in[5]; p.t[9] = (bp)d_in[6]; p.t[10] = (bp)d_in[7];
  p.t[11] = (bp)d_in[3]; p.t[12] = (bp)d_in[4]; p.t[13] = nullptr;
  p.u = (bp)d_in[0]; p.gw = (bp)d_in[16]; p.A_D = (bp)d_in[8]; p.B_D = (bp)d_in[15];
  static EncodeFn enc = nullptr;
  if (!enc) {
    cudaDriverEntryPointQueryResult qr;
    cudaGetDriverEntryPoint("cuTensorMapEncodeTiled", (void**)&enc, cudaEnableDefault, &qr);
    cudaFuncSetAttribute(ssm_kernel, cudaFuncAttributeMaxDynamicSharedMemorySize, SMEM_BYTES);
  }
  CUtensorMap tm_in, tm_out;
  {
    cuuint64_t gd[5] = {512, 2, 4, 4, 64};
    cuuint64_t gs[4] = {1024, 8192, 2048, 32768};
    cuuint32_t bx[5] = {8, 2, 4, 4, 32};
    cuuint32_t es[5] = {1, 1, 1, 1, 1};
    enc(&tm_in, CU_TENSOR_MAP_DATA_TYPE_BFLOAT16, 5, d_in[0], gd, gs, bx, es, CU_TENSOR_MAP_INTERLEAVE_NONE,
        CU_TENSOR_MAP_SWIZZLE_NONE, CU_TENSOR_MAP_L2_PROMOTION_NONE, CU_TENSOR_MAP_FLOAT_OOB_FILL_NONE);
  }
  {
    cuuint64_t gd[3] = {512, 1024, 2};
    cuuint64_t gs[2] = {2048, 1024};
    cuuint32_t bx[3] = {8, 128, 2};
    cuuint32_t es[3] = {1, 1, 1};
    enc(&tm_out, CU_TENSOR_MAP_DATA_TYPE_BFLOAT16, 3, d_out, gd, gs, bx, es, CU_TENSOR_MAP_INTERLEAVE_NONE,
        CU_TENSOR_MAP_SWIZZLE_NONE, CU_TENSOR_MAP_L2_PROMOTION_NONE, CU_TENSOR_MAP_FLOAT_OOB_FILL_NONE);
  }
  ssm_kernel<<<NCTA + NGATE, 640, SMEM_BYTES, cudaStreamPerThread>>>(p, tm_in, tm_out);
}
```

```cpp
#include <cuda_runtime.h>
#include <cuda.h>
#include <cuda_bf16.h>
#include <stdint.h>

namespace {
#define FCPY(x) __uint_as_float(opq(__float_as_uint(x), zz))

constexpr int L = 2048, D = 512, NM = 128;
constexpr int NCTA = 128;
constexpr int NGATE = 4;

constexpr int RAW_OFF = 0;
constexpr int XIN_OFF = 32768;
constexpr int BAR_OFF = XIN_OFF + 10240;
constexpr int CH_OFF = BAR_OFF + 256;
constexpr int U_CS = 1184;
constexpr int U_OFF = 0;
constexpr int R_OFF = 4736;
constexpr int RD_X0 = 565;
constexpr int RD_CS = 1216;
constexpr int RS_CS = 320;
constexpr int R_E2 = 2 * RD_CS, R_O2 = R_E2 + 2 * RS_CS, R_E3 = R_O2 + 2 * RS_CS, R_O3 = R_E3 + 2 * RS_CS;
constexpr int R_BR = R_O3 + 2 * RS_CS;
constexpr int W5_OFF = R_OFF + 2 * R_BR;
constexpr int W3_OFF = W5_OFF + 3456;
constexpr int W9_OFF = W3_OFF + 3456;
constexpr int W7_OFF = W9_OFF + 2304;
constexpr int Y0_OFF = W7_OFF + 2304;
constexpr int Y2_OFF = Y0_OFF + 8192, Y3_OFF = Y2_OFF + 6144;
constexpr int CH_BYTES = Y0_OFF + 18432 + 16;
constexpr int SCR_BYTES = 4608;
constexpr int SMEM_BYTES = CH_OFF + 4 * CH_BYTES;
static_assert(CH_BYTES % 128 == 16, "bank staggering of the channel blocks");
static_assert(SMEM_BYTES <= 232448, "smem");
constexpr int B_RAW = BAR_OFF, B_X = BAR_OFF + 8, B_U = BAR_OFF + 40, B_W = BAR_OFF + 48;
constexpr int TAG_OFF = BAR_OFF + 56;
constexpr int K1024_OFF = BAR_OFF + 64;
constexpr int B_ST = BAR_OFF + 96;

__device__ unsigned int g_gate[L];
__device__ unsigned int g_epoch;
__device__ unsigned int g_ticket;

#define STAMP(k)
#define GT(k)

struct Params {
  const __nv_bfloat16* t[14];
  const __nv_bfloat16 *u, *gw, *A_D, *B_D;
};

template <int N, int TB> __device__ __forceinline__ void wgmma_rs(float* d, uint32_t a0, uint32_t a1, uint32_t a2, uint32_t a3, uint64_t desc, int sc);
template <> __device__ __forceinline__ void wgmma_rs<64, 0>(float* d, uint32_t a0, uint32_t a1, uint32_t a2, uint32_t a3, uint64_t desc, int sc) {
  asm volatile("{\n.reg .pred p;\nsetp.ne.b32 p, %37, 0;\n"
    "wgmma.mma_async.sync.aligned.m64n64k16.f32.bf16.bf16 {%0,%1,%2,%3,%4,%5,%6,%7,%8,%9,%10,%11,%12,%13,%14,%15,%16,%17,%18,%19,%20,%21,%22,%23,%24,%25,%26,%27,%28,%29,%30,%31}, {%32,%33,%34,%35}, %36, p, 1, 1, 0;\n}"
    : "+f"(d[0]), "+f"(d[1]), "+f"(d[2]), "+f"(d[3]), "+f"(d[4]), "+f"(d[5]), "+f"(d[6]), "+f"(d[7]), "+f"(d[8]), "+f"(d[9]), "+f"(d[10]), "+f"(d[11]), "+f"(d[12]), "+f"(d[13]), "+f"(d[14]), "+f"(d[15]), "+f"(d[16]), "+f"(d[17]), "+f"(d[18]), "+f"(d[19]), "+f"(d[20]), "+f"(d[21]), "+f"(d[22]), "+f"(d[23]), "+f"(d[24]), "+f"(d[25]), "+f"(d[26]), "+f"(d[27]), "+f"(d[28]), "+f"(d[29]), "+f"(d[30]), "+f"(d[31]) : "r"(a0), "r"(a1), "r"(a2), "r"(a3), "l"(desc), "r"(sc));
}
template <> __device__ __forceinline__ void wgmma_rs<56, 0>(float* d, uint32_t a0, uint32_t a1, uint32_t a2, uint32_t a3, uint64_t desc, int sc) {
  asm volatile("{\n.reg .pred p;\nsetp.ne.b32 p, %33, 0;\n"
    "wgmma.mma_async.sync.aligned.m64n56k16.f32.bf16.bf16 {%0,%1,%2,%3,%4,%5,%6,%7,%8,%9,%10,%11,%12,%13,%14,%15,%16,%17,%18,%19,%20,%21,%22,%23,%24,%25,%26,%27}, {%28,%29,%30,%31}, %32, p, 1, 1, 0;\n}"
    : "+f"(d[0]), "+f"(d[1]), "+f"(d[2]), "+f"(d[3]), "+f"(d[4]), "+f"(d[5]), "+f"(d[6]), "+f"(d[7]), "+f"(d[8]), "+f"(d[9]), "+f"(d[10]), "+f"(d[11]), "+f"(d[12]), "+f"(d[13]), "+f"(d[14]), "+f"(d[15]), "+f"(d[16]), "+f"(d[17]), "+f"(d[18]), "+f"(d[19]), "+f"(d[20]), "+f"(d[21]), "+f"(d[22]), "+f"(d[23]), "+f"(d[24]), "+f"(d[25]), "+f"(d[26]), "+f"(d[27]) : "r"(a0), "r"(a1), "r"(a2), "r"(a3), "l"(desc), "r"(sc));
}
template <> __device__ __forceinline__ void wgmma_rs<48, 0>(float* d, uint32_t a0, uint32_t a1, uint32_t a2, uint32_t a3, uint64_t desc, int sc) {
  asm volatile("{\n.reg .pred p;\nsetp.ne.b32 p, %29, 0;\n"
    "wgmma.mma_async.sync.aligned.m64n48k16.f32.bf16.bf16 {%0,%1,%2,%3,%4,%5,%6,%7,%8,%9,%10,%11,%12,%13,%14,%15,%16,%17,%18,%19,%20,%21,%22,%23}, {%24,%25,%26,%27}, %28, p, 1, 1, 0;\n}"
    : "+f"(d[0]), "+f"(d[1]), "+f"(d[2]), "+f"(d[3]), "+f"(d[4]), "+f"(d[5]), "+f"(d[6]), "+f"(d[7]), "+f"(d[8]), "+f"(d[9]), "+f"(d[10]), "+f"(d[11]), "+f"(d[12]), "+f"(d[13]), "+f"(d[14]), "+f"(d[15]), "+f"(d[16]), "+f"(d[17]), "+f"(d[18]), "+f"(d[19]), "+f"(d[20]), "+f"(d[21]), "+f"(d[22]), "+f"(d[23]) : "r"(a0), "r"(a1), "r"(a2), "r"(a3), "l"(desc), "r"(sc));
}
template <> __device__ __forceinline__ void wgmma_rs<32, 0>(float* d, uint32_t a0, uint32_t a1, uint32_t a2, uint32_t a3, uint64_t desc, int sc) {
  asm volatile("{\n.reg .pred p;\nsetp.ne.b32 p, %21, 0;\n"
    "wgmma.mma_async.sync.aligned.m64n32k16.f32.bf16.bf16 {%0,%1,%2,%3,%4,%5,%6,%7,%8,%9,%10,%11,%12,%13,%14,%15}, {%16,%17,%18,%19}, %20, p, 1, 1, 0;\n}"
    : "+f"(d[0]), "+f"(d[1]), "+f"(d[2]), "+f"(d[3]), "+f"(d[4]), "+f"(d[5]), "+f"(d[6]), "+f"(d[7]), "+f"(d[8]), "+f"(d[9]), "+f"(d[10]), "+f"(d[11]), "+f"(d[12]), "+f"(d[13]), "+f"(d[14]), "+f"(d[15]) : "r"(a0), "r"(a1), "r"(a2), "r"(a3), "l"(desc), "r"(sc));
}
template <> __device__ __forceinline__ void wgmma_rs<48, 1>(float* d, uint32_t a0, uint32_t a1, uint32_t a2, uint32_t a3, uint64_t desc, int sc) {
  asm volatile("{\n.reg .pred p;\nsetp.ne.b32 p, %29, 0;\n"
    "wgmma.mma_async.sync.aligned.m64n48k16.f32.bf16.bf16 {%0,%1,%2,%3,%4,%5,%6,%7,%8,%9,%10,%11,%12,%13,%14,%15,%16,%17,%18,%19,%20,%21,%22,%23}, {%24,%25,%26,%27}, %28, p, 1, 1, 1;\n}"
    : "+f"(d[0]), "+f"(d[1]), "+f"(d[2]), "+f"(d[3]), "+f"(d[4]), "+f"(d[5]), "+f"(d[6]), "+f"(d[7]), "+f"(d[8]), "+f"(d[9]), "+f"(d[10]), "+f"(d[11]), "+f"(d[12]), "+f"(d[13]), "+f"(d[14]), "+f"(d[15]), "+f"(d[16]), "+f"(d[17]), "+f"(d[18]), "+f"(d[19]), "+f"(d[20]), "+f"(d[21]), "+f"(d[22]), "+f"(d[23]) : "r"(a0), "r"(a1), "r"(a2), "r"(a3), "l"(desc), "r"(sc));
}
template <> __device__ __forceinline__ void wgmma_rs<40, 1>(float* d, uint32_t a0, uint32_t a1, uint32_t a2, uint32_t a3, uint64_t desc, int sc) {
  asm volatile("{\n.reg .pred p;\nsetp.ne.b32 p, %25, 0;\n"
    "wgmma.mma_async.sync.aligned.m64n40k16.f32.bf16.bf16 {%0,%1,%2,%3,%4,%5,%6,%7,%8,%9,%10,%11,%12,%13,%14,%15,%16,%17,%18,%19}, {%20,%21,%22,%23}, %24, p, 1, 1, 1;\n}"
    : "+f"(d[0]), "+f"(d[1]), "+f"(d[2]), "+f"(d[3]), "+f"(d[4]), "+f"(d[5]), "+f"(d[6]), "+f"(d[7]), "+f"(d[8]), "+f"(d[9]), "+f"(d[10]), "+f"(d[11]), "+f"(d[12]), "+f"(d[13]), "+f"(d[14]), "+f"(d[15]), "+f"(d[16]), "+f"(d[17]), "+f"(d[18]), "+f"(d[19]) : "r"(a0), "r"(a1), "r"(a2), "r"(a3), "l"(desc), "r"(sc));
}
template <> __device__ __forceinline__ void wgmma_rs<32, 1>(float* d, uint32_t a0, uint32_t a1, uint32_t a2, uint32_t a3, uint64_t desc, int sc) {
  asm volatile("{\n.reg .pred p;\nsetp.ne.b32 p, %21, 0;\n"
    "wgmma.mma_async.sync.aligned.m64n32k16.f32.bf16.bf16 {%0,%1,%2,%3,%4,%5,%6,%7,%8,%9,%10,%11,%12,%13,%14,%15}, {%16,%17,%18,%19}, %20, p, 1, 1, 1;\n}"
    : "+f"(d[0]), "+f"(d[1]), "+f"(d[2]), "+f"(d[3]), "+f"(d[4]), "+f"(d[5]), "+f"(d[6]), "+f"(d[7]), "+f"(d[8]), "+f"(d[9]), "+f"(d[10]), "+f"(d[11]), "+f"(d[12]), "+f"(d[13]), "+f"(d[14]), "+f"(d[15]) : "r"(a0), "r"(a1), "r"(a2), "r"(a3), "l"(desc), "r"(sc));
}
template <> __device__ __forceinline__ void wgmma_rs<16, 1>(float* d, uint32_t a0, uint32_t a1, uint32_t a2, uint32_t a3, uint64_t desc, int sc) {
  asm volatile("{\n.reg .pred p;\nsetp.ne.b32 p, %13, 0;\n"
    "wgmma.mma_async.sync.aligned.m64n16k16.f32.bf16.bf16 {%0,%1,%2,%3,%4,%5,%6,%7}, {%8,%9,%10,%11}, %12, p, 1, 1, 1;\n}"
    : "+f"(d[0]), "+f"(d[1]), "+f"(d[2]), "+f"(d[3]), "+f"(d[4]), "+f"(d[5]), "+f"(d[6]), "+f"(d[7]) : "r"(a0), "r"(a1), "r"(a2), "r"(a3), "l"(desc), "r"(sc));
}

__device__ __forceinline__ uint32_t pack_bf16(float lo, float hi) {
  uint32_t r; asm("cvt.rn.bf16x2.f32 %0, %1, %2;" : "=r"(r) : "f"(hi), "f"(lo)); return r;
}
__device__ __forceinline__ float bf_lo(uint32_t v) { return __uint_as_float(v << 16); }
__device__ __forceinline__ float bf_hi(uint32_t v) { return __uint_as_float(v & 0xffff0000u); }
__device__ __forceinline__ float bf_round(float x) { return bf_lo(pack_bf16(x, 0.f)); }
__device__ __forceinline__ uint32_t hmul2(uint32_t a, uint32_t b) { uint32_t r; asm("mul.rn.bf16x2 %0, %1, %2;" : "=r"(r) : "r"(a), "r"(b)); return r; }
__device__ __forceinline__ uint32_t hadd2(uint32_t a, uint32_t b) { uint32_t r; asm("add.rn.bf16x2 %0, %1, %2;" : "=r"(r) : "r"(a), "r"(b)); return r; }
__device__ __forceinline__ uint32_t hsub2(uint32_t a, uint32_t b) { uint32_t r; asm("sub.rn.bf16x2 %0, %1, %2;" : "=r"(r) : "r"(a), "r"(b)); return r; }
__device__ __forceinline__ uint32_t hfma2(uint32_t a, uint32_t b, uint32_t c) { uint32_t r; asm("fma.rn.bf16x2 %0, %1, %2, %3;" : "=r"(r) : "r"(a), "r"(b), "r"(c)); return r; }

__device__ __forceinline__ void sts16(uint32_t a, uint32_t v) { asm volatile("st.shared.b16 [%0], %1;" ::"r"(a), "h"((unsigned short)v) : "memory"); }
__device__ __forceinline__ void sts32(uint32_t a, uint32_t v) { asm volatile("st.shared.b32 [%0], %1;" ::"r"(a), "r"(v) : "memory"); }
__device__ __forceinline__ void sts64(uint32_t a, uint32_t x, uint32_t y) { asm volatile("st.shared.v2.b32 [%0], {%1,%2};" ::"r"(a), "r"(x), "r"(y) : "memory"); }
__device__ __forceinline__ void sts128(uint32_t a, uint32_t x, uint32_t y, uint32_t z, uint32_t w) {
  asm volatile("st.shared.v4.b32 [%0], {%1,%2,%3,%4};" ::"r"(a), "r"(x), "r"(y), "r"(z), "r"(w) : "memory");
}
__device__ __forceinline__ uint32_t lds32(uint32_t a) { uint32_t v; asm volatile("ld.shared.b32 %0, [%1];" : "=r"(v) : "r"(a) : "memory"); return v; }
__device__ __forceinline__ uint2 lds64(uint32_t a) { uint2 v; asm volatile("ld.shared.v2.b32 {%0,%1}, [%2];" : "=r"(v.x), "=r"(v.y) : "r"(a) : "memory"); return v; }
__device__ __forceinline__ uint4 lds128(uint32_t a) {
  uint4 v; asm volatile("ld.shared.v4.b32 {%0,%1,%2,%3}, [%4];" : "=r"(v.x), "=r"(v.y), "=r"(v.z), "=r"(v.w) : "r"(a) : "memory"); return v;
}
__device__ __forceinline__ uint4 ldg128(const void* a) {
  uint4 v; asm volatile("ld.global.nc.v4.b32 {%0,%1,%2,%3}, [%4];" : "=r"(v.x), "=r"(v.y), "=r"(v.z), "=r"(v.w) : "l"(a) : "memory"); return v;
}
__device__ __forceinline__ uint2 ldg64(const void* a) {
  uint2 v; asm volatile("ld.global.nc.v2.b32 {%0,%1}, [%2];" : "=r"(v.x), "=r"(v.y) : "l"(a) : "memory"); return v;
}
__device__ __forceinline__ void ldsm4(uint32_t a, uint32_t& r0, uint32_t& r1, uint32_t& r2, uint32_t& r3) {
  asm volatile("ldmatrix.sync.aligned.m8n8.x4.shared.b16 {%0,%1,%2,%3}, [%4];" : "=r"(r0), "=r"(r1), "=r"(r2), "=r"(r3) : "r"(a) : "memory");
}
__device__ __forceinline__ void ldsm4t(uint32_t a, uint32_t& r0, uint32_t& r1, uint32_t& r2, uint32_t& r3) {
  asm volatile("ldmatrix.sync.aligned.m8n8.x4.trans.shared.b16 {%0,%1,%2,%3}, [%4];" : "=r"(r0), "=r"(r1), "=r"(r2), "=r"(r3) : "r"(a) : "memory");
}
__device__ __forceinline__ void stsm4(uint32_t a, uint32_t r0, uint32_t r1, uint32_t r2, uint32_t r3) {
  asm volatile("stmatrix.sync.aligned.m8n8.x4.shared.b16 [%0], {%1,%2,%3,%4};" ::"r"(a), "r"(r0), "r"(r1), "r"(r2), "r"(r3) : "memory");
}
__device__ __forceinline__ void stsm4t(uint32_t a, uint32_t r0, uint32_t r1, uint32_t r2, uint32_t r3) {
  asm volatile("stmatrix.sync.aligned.m8n8.x4.trans.shared.b16 [%0], {%1,%2,%3,%4};" ::"r"(a), "r"(r0), "r"(r1), "r"(r2), "r"(r3) : "memory");
}
__device__ __forceinline__ void stsm2(uint32_t a, uint32_t r0, uint32_t r1) {
  asm volatile("stmatrix.sync.aligned.m8n8.x2.shared.b16 [%0], {%1,%2};" ::"r"(a), "r"(r0), "r"(r1) : "memory");
}
__device__ __forceinline__ void stsm2t(uint32_t a, uint32_t r0, uint32_t r1) {
  asm volatile("stmatrix.sync.aligned.m8n8.x2.trans.shared.b16 [%0], {%1,%2};" ::"r"(a), "r"(r0), "r"(r1) : "memory");
}
__device__ __forceinline__ void mma16816(float* c, uint32_t a0, uint32_t a1, uint32_t a2, uint32_t a3, uint32_t b0, uint32_t b1) {
  asm("mma.sync.aligned.m16n8k16.row.col.f32.bf16.bf16.f32 {%0,%1,%2,%3}, {%4,%5,%6,%7}, {%8,%9}, {%0,%1,%2,%3};"
      : "+f"(c[0]), "+f"(c[1]), "+f"(c[2]), "+f"(c[3]) : "r"(a0), "r"(a1), "r"(a2), "r"(a3), "r"(b0), "r"(b1));
}
__device__ __forceinline__ void bar_sync(int id, int n) { asm volatile("bar.sync %0, %1;" ::"r"(id), "r"(n) : "memory"); }
__device__ __forceinline__ void bar_arrive(int id, int n) { asm volatile("bar.arrive %0, %1;" ::"r"(id), "r"(n) : "memory"); }
__device__ __forceinline__ void wg_fence() { asm volatile("wgmma.fence.sync.aligned;" ::: "memory"); }
__device__ __forceinline__ void wg_commit() { asm volatile("wgmma.commit_group.sync.aligned;" ::: "memory"); }
__device__ __forceinline__ void wg_wait0() { asm volatile("wgmma.wait_group.sync.aligned 0;" ::: "memory"); }
__device__ __forceinline__ void wg_wait1() { asm volatile("wgmma.wait_group.sync.aligned 1;" ::: "memory"); }
__device__ __forceinline__ void fence_async() { asm volatile("fence.proxy.async.shared::cta;" ::: "memory"); }
__device__ __forceinline__ uint32_t opq(uint32_t x, uint32_t z) { uint32_t r; asm volatile("xor.b32 %0, %1, %2;" : "=r"(r) : "r"(x), "r"(z)); return r; }
__device__ __forceinline__ uint64_t mkdesc(uint32_t addr, uint32_t lbo, uint32_t sbo) {
  return (uint64_t)((addr & 0x3FFFF) >> 4) | ((uint64_t)(lbo >> 4) << 16) | ((uint64_t)(sbo >> 4) << 32);
}
__device__ __forceinline__ uint32_t mapa(uint32_t a, uint32_t rank) {
  uint32_t r; asm("mapa.shared::cluster.u32 %0, %1, %2;" : "=r"(r) : "r"(a), "r"(rank)); return r;
}
__device__ __forceinline__ void mbar_init_expect(uint32_t bar, uint32_t bytes) {
  asm volatile("mbarrier.init.shared::cta.b64 [%0], 1;" ::"r"(bar) : "memory");
  asm volatile("mbarrier.arrive.expect_tx.shared::cta.b64 _, [%0], %1;" ::"r"(bar), "r"(bytes) : "memory");
}
__device__ __forceinline__ void mbar_wait(uint32_t bar) {
#pragma unroll 1
  for (int it = 0; it < (1 << 22); it++) {
    uint32_t ok;
    asm volatile("{\n.reg .pred p;\nmbarrier.try_wait.parity.acquire.cluster.shared::cta.b64 p, [%1], 0;\nselp.u32 %0, 1, 0, p;\n}"
                 : "=r"(ok) : "r"(bar) : "memory");
    if (ok) return;
  }
  __trap();
}
__device__ __forceinline__ void st_async4(uint32_t a, uint32_t bar, uint32_t x, uint32_t y, uint32_t z, uint32_t w) {
  asm volatile("st.async.weak.shared::cluster.mbarrier::complete_tx::bytes.v4.b32 [%0], {%2,%3,%4,%5}, [%1];"
               ::"r"(a), "r"(bar), "r"(x), "r"(y), "r"(z), "r"(w) : "memory");
}

struct cf { float re, im; };
__device__ __forceinline__ cf cmul(cf a, cf b) { return {fmaf(a.re, b.re, -a.im * b.im), fmaf(a.re, b.im, a.im * b.re)}; }
__device__ __forceinline__ cf csq(cf a) { return {fmaf(a.re, a.re, -a.im * a.im), (a.re + a.re) * a.im}; }
__device__ __forceinline__ cf cexp_p(float xl, float y, float p) {
  float mag; asm("ex2.approx.ftz.f32 %0, %1;" : "=f"(mag) : "f"(xl * p));
  const float th = y * p;
  const float k = __fadd_rn(fmaf(th, 0.15915494309189535f, 12582912.f), -12582912.f);
  float r = fmaf(k, -6.2831854820251465f, th);
  r = fmaf(k, 1.7484555314695172e-07f, r);
  return {mag * __cosf(r), mag * __sinf(r)};
}
__device__ __forceinline__ uint32_t ysw(int c) { return (uint32_t)(c ^ ((c >> 3) & 3)) * 16u; }

#define CMUL2(OR, OI, xr, xi, yr, yi, nyi) do { OR = hfma2(xr, yr, hmul2(xi, nyi)); OI = hfma2(xr, yi, hmul2(xi, yr)); } while (0)

__device__ __forceinline__ uint32_t gate_slow(const __nv_bfloat16* u, const __nv_bfloat16* gw, int row) {
  float s = 0.f;
  const uint32_t* xr = (const uint32_t*)(u + (size_t)row * D);
  const uint32_t* wr = (const uint32_t*)gw;
#pragma unroll 1
  for (int j = 0; j < D / 2; j++) { const uint32_t pr = hmul2(xr[j], wr[j]); s += bf_lo(pr); s += bf_hi(pr); }
  s = bf_round(s);
  return pack_bf16(1.f / (1.f + expf(-s)), 0.f);
}

__device__ __forceinline__ uint2 gate_ld(int x) {
  uint2 gv;
  asm volatile("ld.relaxed.gpu.global.v2.u32 {%0,%1}, [%2];" : "=r"(gv.x), "=r"(gv.y) : "l"(g_gate + x * 2) : "memory");
  return gv;
}
__device__ __noinline__ uint32_t gate_poll(const Params* pp, int x, uint32_t tag) {
  uint2 gv;
#pragma unroll 1
  for (int spins = 0; spins < (1 << 16); spins++) {
    gv = gate_ld(x);
    if ((gv.x >> 16) == tag && (gv.y >> 16) == tag) return __byte_perm(gv.x, gv.y, 0x5410);
  }
  return __byte_perm(gate_slow(pp->u, pp->gw, x * 2), gate_slow(pp->u, pp->gw, x * 2 + 1), 0x5410);
}
__device__ __forceinline__ uint32_t gate_fin(const Params& p, uint2 gv, int x, uint32_t tag) {
  if ((gv.x >> 16) == tag && (gv.y >> 16) == tag) return __byte_perm(gv.x, gv.y, 0x5410);
  return gate_poll(&p, x, tag);
}

__device__ __forceinline__ void ld4ch(uint32_t* v, uint32_t addr) {
#pragma unroll
  for (int k = 0; k < 4; k++) v[k] = lds32(addr + k * CH_BYTES);
}
__device__ __forceinline__ void skip_terms(uint32_t* ua, uint32_t* ub, uint32_t sb, int x, uint2 dA, uint2 dB) {
  const int c = x >> 2;
  uint32_t uu[4];
  ld4ch(uu, sb + CH_OFF + (x & 3) * 4 + U_OFF + (c & 3) * U_CS + (63 - (c >> 2)) * 16);
#pragma unroll
  for (int k = 0; k < 4; k++) {
    ua[k] = hmul2(uu[k], __byte_perm((k & 2) ? dA.y : dA.x, 0, (k & 1) ? 0x3232 : 0x1010));
    ub[k] = hmul2(uu[k], __byte_perm((k & 2) ? dB.y : dB.x, 0, (k & 1) ? 0x3232 : 0x1010));
  }
}
__device__ __forceinline__ uint4 mix(const uint32_t* a, const uint32_t* b, const uint32_t* ua, const uint32_t* ub, uint32_t g2) {
  const uint32_t h2 = hsub2(0x3f803f80u, g2);
  uint32_t o[4];
#pragma unroll
  for (int k = 0; k < 4; k++) o[k] = hadd2(hmul2(g2, hadd2(a[k], ua[k])), hmul2(h2, hadd2(b[k], ub[k])));
  return make_uint4(__byte_perm(o[0], o[1], 0x5410), __byte_perm(o[2], o[3], 0x5410), __byte_perm(o[0], o[1], 0x7632), __byte_perm(o[2], o[3], 0x7632));
}
__device__ __forceinline__ void send_box(uint32_t sb, int slot, int wtid, uint32_t rank, uint4 r) {
  st_async4(mapa(sb + XIN_OFF + slot * 2048 + wtid * 16, rank ^ 1), mapa(sb + B_X + slot * 8, rank ^ 1), r.x, r.y, r.z, r.w);
}
__device__ __forceinline__ void merge_rows(uint32_t st, uint32_t rank, uint4 r, uint4 q) {
  const uint4 lo = rank ? q : r, hi = rank ? r : q;
  sts128(st, lo.x, lo.y, hi.x, hi.y); sts128(st + 2048, lo.z, lo.w, hi.z, hi.w);
}
__device__ __forceinline__ void merge_box(uint32_t sb, const CUtensorMap* tm_out, int slot, int wtid, uint32_t rank, int oc0, uint4 r, int barid) {
  const uint32_t st = sb + RAW_OFF + slot * 4096 + wtid * 16;
  mbar_wait(sb + B_X + slot * 8);
  merge_rows(st, rank, r, lds128(sb + XIN_OFF + slot * 2048 + wtid * 16));
  fence_async();
  bar_sync(barid, 128);
  if (wtid == 0) {
    asm volatile("cp.async.bulk.tensor.3d.global.shared::cta.bulk_group [%0, {%2, %3, %4}], [%1];"
                 ::"l"(tm_out), "r"(sb + RAW_OFF + slot * 4096), "r"(oc0), "r"((2 * slot + (int)rank) * 128), "r"(0) : "memory");
    asm volatile("cp.async.bulk.commit_group;" ::: "memory");
  }
}

__device__ __forceinline__ uint32_t band2(int e, int lo, int hi) {
  uint32_t r = ((uint32_t)(e - lo) <= (uint32_t)(hi - lo) ? 0x3f80u : 0u) | ((uint32_t)(e - 1 - lo) <= (uint32_t)(hi - lo) ? 0x3f800000u : 0u);
  asm volatile("" : "+r"(r));
  return r;
}

__device__ __forceinline__ void stage_done(uint32_t sb, int stage, int lane) {
  __syncwarp();
  if (lane == 0) asm volatile("mbarrier.arrive.shared::cta.b64 _, [%0];" ::"r"(sb + B_ST + 8 * stage) : "memory");
}
#define PK2(v, i) pack_bf16(v[i], v[(i) + 1])

__device__ __forceinline__ void conv_dense(uint32_t sb, uint32_t cb, uint32_t zz) {
  const int lane = threadIdx.x & 31, wq = (threadIdx.x >> 5) & 3, br = wq >> 1, hf = wq & 1, g = lane >> 2, t = lane & 3;
  const uint32_t rb = cb + R_OFF + br * R_BR;
  const int eo = 16 * hf + g - 2 * t;
  const int x0 = RD_X0 - (eo + 536);
  const uint32_t fa = rb + ((g & 1) ? 2 * x0 : RD_CS + 2 * x0 + 2);
  const uint64_t ub = mkdesc(cb + U_OFF, U_CS, 128);
  const uint32_t yd = cb + Y0_OFF + br * 4096 + ysw(4 * (63 - 8 * (lane >> 4) - (lane & 7)) + 2 * hf + ((lane >> 3) & 1));
  uint32_t A[2][4][4];
  float e64[32], e56[28], e48[24];
  auto loadA = [&](int j) {
#pragma unroll
    for (int k = 0; k < 4; k++) {
      const int s = 34 - 4 * j - k;
      if (s >= 0) {
        if (k == 0 && j == 0) A[0][0][2] = lds32(fa + (2 * s + 2) * 16);
        A[j & 1][k][0] = lds32(fa + (2 * s + 1) * 16);
        A[j & 1][k][1] = lds32(fa + (2 * s) * 16);
      }
    }
#pragma unroll
    for (int k = 0; k < 4; k++) {
      if (34 - 4 * j - k >= 0) {
        A[j & 1][k][3] = A[j & 1][k][0];
        if (k) A[j & 1][k][2] = A[j & 1][k - 1][1];
        else if (j) A[j & 1][0][2] = A[(j - 1) & 1][3][1];
      }
    }
  };
  loadA(0); loadA(1);
#pragma unroll
  for (int j = 0; j < 9; j++) {
    if (j == 4) {
      wg_wait0();
      stsm2t(yd - 7 * 512, PK2(e64, 28), PK2(e64, 30));
#pragma unroll
      for (int i = 0; i < 28; i++) e56[i] = FCPY(e64[i]);
      stage_done(sb, 0, lane);
    }
    if (j == 8) {
      wg_wait0();
      stsm2t(yd - 6 * 512, PK2(e56, 24), PK2(e56, 26));
#pragma unroll
      for (int i = 0; i < 24; i++) e48[i] = FCPY(e56[i]);
      stage_done(sb, 1, lane);
    }
    wg_fence();
#pragma unroll
    for (int k = 0; k < 4; k++) {
      const int s = 34 - 4 * j - k;
      if (s >= 0) {
        const int o = 2 * s - 66 + 128;
        const int cc = o & 3, rs = (o >> 2) - 32;
        const uint64_t desc = ub + (uint64_t)((cc * U_CS - rs * 16) >> 4);
        const uint32_t* a = A[j & 1][k];
        if (j < 4) wgmma_rs<64, 0>(e64, a[0], a[1], a[2], a[3], desc, s != 34);
        else if (j < 8) wgmma_rs<56, 0>(e56, a[0], a[1], a[2], a[3], desc, 1);
        else wgmma_rs<48, 0>(e48, a[0], a[1], a[2], a[3], desc, 1);
      }
    }
    wg_commit();
    if (j >= 1 && j < 8) { wg_wait1(); loadA(j + 1); }
  }
  wg_wait0();
#pragma unroll
  for (int i = 0; i < 6; i += 2) stsm4t(yd - i * 512, PK2(e48, 4 * i), PK2(e48, 4 * i + 2), PK2(e48, 4 * i + 4), PK2(e48, 4 * i + 6));
}

__device__ __noinline__ void gate_cta(const Params* pp) {
  const __nv_bfloat16 *u = pp->u, *gw = pp->gw;
  const int lane = threadIdx.x & 31;
  unsigned int epoch;
  asm volatile("ld.relaxed.gpu.global.u32 %0, [%1];" : "=r"(epoch) : "l"(&g_epoch) : "memory");
  const uint4 gw0 = ldg128(gw + lane * 8), gw1 = ldg128(gw + 256 + lane * 8);
  const uint32_t ws[8] = {gw0.x, gw0.y, gw0.z, gw0.w, gw1.x, gw1.y, gw1.z, gw1.w};
  const uint32_t tag = (epoch + 1) & 0xffffu;
  uint4 gx[4][2], nx[4][2];
  int grow = (blockIdx.x * 20 + (threadIdx.x >> 5)) * 4;
#pragma unroll
  for (int i = 0; i < 4; i++) {
    nx[i][0] = ldg128(u + (size_t)(grow + i) * D + lane * 8);
    nx[i][1] = ldg128(u + (size_t)(grow + i) * D + 256 + lane * 8);
  }
#pragma unroll 1
  for (; grow < L; grow += 80 * NGATE) {
    const int nrow = min(grow + 80 * NGATE, L - 4);
#pragma unroll
    for (int i = 0; i < 4; i++) {
      gx[i][0] = nx[i][0]; gx[i][1] = nx[i][1];
      nx[i][0] = ldg128(u + (size_t)(nrow + i) * D + lane * 8);
      nx[i][1] = ldg128(u + (size_t)(nrow + i) * D + 256 + lane * 8);
    }
    float c[2][4];
#pragma unroll
    for (int i = 0; i < 2; i++) {
      const uint4 *x = gx[2 * i], *y = gx[2 * i + 1];
      const uint32_t xs[8] = {x[0].x, x[0].y, x[0].z, x[0].w, x[1].x, x[1].y, x[1].z, x[1].w};
      const uint32_t ys[8] = {y[0].x, y[0].y, y[0].z, y[0].w, y[1].x, y[1].y, y[1].z, y[1].w};
      c[i][0] = c[i][1] = c[i][2] = c[i][3] = 0.f;
#pragma unroll
      for (int j = 0; j < 8; j += 2)
        mma16816(c[i], hmul2(xs[j], ws[j]), hmul2(ys[j], ws[j]), hmul2(xs[j + 1], ws[j + 1]), hmul2(ys[j + 1], ws[j + 1]), 0x3f803f80u, 0x3f803f80u);
    }
    float s = (lane & 2) ? ((lane & 1) ? c[1][2] : c[1][0]) : ((lane & 1) ? c[0][2] : c[0][0]);
#pragma unroll
    for (int o = 4; o < 32; o <<= 1) s += __shfl_xor_sync(0xffffffffu, s, o);
    s = bf_round(s);
    const float gv = 1.f / (1.f + expf(-s));
    const uint32_t w = (tag << 16) | (pack_bf16(gv, 0.f) & 0xffffu);
    if (lane < 4) asm volatile("st.relaxed.gpu.global.u32 [%0], %1;" ::"l"(&g_gate[grow + lane]), "r"(w) : "memory");
  }
  __syncthreads();
  if (threadIdx.x == 0 && atomicAdd(&g_ticket, 1u) == NCTA + NGATE - 1) { g_ticket = 0; g_epoch = epoch + 1; }
}

__global__ void __cluster_dims__(2, 1, 1) __launch_bounds__(640, 1)
ssm_kernel(const __grid_constant__ Params p, const __grid_constant__ CUtensorMap tm_in, const __grid_constant__ CUtensorMap tm_out) {
  extern __shared__ __align__(1024) unsigned char smem_raw[];
  const uint32_t sb = (uint32_t)__cvta_generic_to_shared(smem_raw);
  const int tid = threadIdx.x, lane = tid & 31;
  const int warp = __shfl_sync(0xffffffffu, tid >> 5, 0);
  const int ch = warp >> 2, wq = warp & 3, br = wq >> 1, hf = wq & 1;
  const int g = lane >> 2, t = lane & 3;
  if (__builtin_expect(blockIdx.x < NGATE, 0)) { gate_cta(&p); return; }
  const int bid = blockIdx.x - NGATE;
  const int d = bid * 4 + ch;
  const uint32_t rank = blockIdx.x & 1;
  const uint32_t cb = sb + CH_OFF + ch * CH_BYTES;
  const int wtid = tid & 127;
  const int oc0 = (bid >> 1) * 8;
  STAMP(0); GT(0);

  if (warp >= 16) {
    if (wtid == 0) {
      mbar_init_expect(sb + B_RAW, 32768);
#pragma unroll
      for (int i = 0; i < 4; i++) mbar_init_expect(sb + B_X + 8 * i, 2048);
      asm volatile("mbarrier.init.shared::cta.b64 [%0], 128;" ::"r"(sb + B_U) : "memory");
      asm volatile("mbarrier.init.shared::cta.b64 [%0], 128;" ::"r"(sb + B_W) : "memory");
#pragma unroll
      for (int i = 0; i < 7; i++) asm volatile("mbarrier.init.shared::cta.b64 [%0], 16;" ::"r"(sb + B_ST + 8 * i) : "memory");
      asm volatile("fence.mbarrier_init.release.cluster;" ::: "memory");
      asm volatile("fence.proxy.async.shared::cta;" ::: "memory");
    }
    __syncwarp();
    asm volatile("barrier.cluster.arrive.relaxed.aligned;" ::: "memory");
    unsigned int epoch;
    asm volatile("ld.relaxed.gpu.global.u32 %0, [%1];" : "=r"(epoch) : "l"(&g_epoch) : "memory");
    asm volatile("barrier.cluster.wait.aligned;" ::: "memory");
    if (wtid == 0) {
      asm volatile("cp.async.bulk.tensor.5d.shared::cluster.global.mbarrier::complete_tx::bytes.multicast::cluster [%0], [%1, {%3, %4, %4, %4, %5}], [%2], %6;"
                   ::"r"(sb + RAW_OFF + rank * 16384), "l"(&tm_in), "r"(sb + B_RAW), "r"(oc0), "r"(0), "r"((int)rank * 32), "h"((unsigned short)3) : "memory");
    }
    sts128(sb + CH_OFF + wq * CH_BYTES + U_OFF + (lane >> 3) * U_CS + (64 + (lane & 7)) * 16, 0, 0, 0, 0);
    const uint2 dA = ldg64(p.A_D + bid * 4), dB = ldg64(p.B_D + bid * 4);
    uint32_t BA[3][4], BB[4][4];
    {
      const int l1 = br ? 3 : 6, h1 = br ? 5 : 10, l2 = br ? 5 : 12, h2 = br ? 11 : 20;
#pragma unroll
      for (int i = 0; i < 4; i++) {
        const int e = 16 * hf + g - 2 * t + 32 - 16 * i;
        BB[i][0] = band2(e, l2, h2); BB[i][1] = band2(e + 8, l2, h2); BB[i][2] = band2(e - 8, l2, h2); BB[i][3] = BB[i][0];
        if (i) { BA[i - 1][0] = band2(e, l1, h1); BA[i - 1][1] = band2(e + 8, l1, h1); BA[i - 1][2] = band2(e - 8, l1, h1); BA[i - 1][3] = BA[i - 1][0]; }
      }
    }
    const uint32_t tag = (epoch + 1) & 0xffffu;
    if (wtid == 0) sts32(sb + TAG_OFF, tag);
    STAMP(3);
    mbar_wait(sb + B_RAW);
    STAMP(4);
    {
      const uint32_t dst = sb + CH_OFF + (g & 3) * CH_BYTES + U_OFF + t * U_CS + (63 - wq * 16) * 16;
#pragma unroll
      for (int h = 0; h < 2; h++) {
        uint32_t r[8][4];
#pragma unroll
        for (int i = 0; i < 8; i++) ldsm4t(sb + RAW_OFF + (wq * 16 + h * 8 + i) * 512 + lane * 16, r[i][0], r[i][1], r[i][2], r[i][3]);
        if ((uint32_t)(g >> 2) == rank) {
#pragma unroll
          for (int i = 0; i < 8; i++) sts128(dst - (h * 8 + i) * 16, r[i][0], r[i][1], r[i][2], r[i][3]);
        }
      }
    }
    fence_async();
    asm volatile("mbarrier.arrive.shared::cta.b64 _, [%0];" ::"r"(sb + B_U) : "memory");
    bar_sync(5, 128);
    STAMP(5);
    {
      const int mrow = lane & 7, mi = lane >> 3;
      const uint64_t ub0 = mkdesc(sb + CH_OFF + U_OFF, U_CS, 128);
      float w1[24];
#pragma unroll
      for (int i = 0; i < 24; i++) w1[i] = 0.f;
      uint32_t wa, wb;
      {
        const int c = 4 * (47 - 8 * (mi >> 1) - mrow) + 2 * hf + (mi & 1);
        wa = sb + CH_OFF + (br ? W3_OFF : W5_OFF) + (5 - (c >> 5)) * 576 + ((c & 31) >> 3) * 144 + (c & 7) * 16;
        const int c2 = c - 64, pp = c2 >> 1;
        wb = sb + CH_OFF + (br ? W7_OFF : W9_OFF) + (1 - (pp >> 5)) * 1152 + (c2 & 1) * 576 + ((pp & 31) >> 3) * 144 + (pp & 7) * 16;
      }
#pragma unroll 1
      for (int k = 0; k < 4; k++) {
        wg_fence();
#pragma unroll
        for (int i = 0; i < 3; i++)
          wgmma_rs<48, 0>(w1, BA[i][0], BA[i][1], BA[i][2], BA[i][3],
                          ub0 + (uint64_t)((k * CH_BYTES + ((2 * i + 2) & 3) * U_CS + (16 + (i == 0)) * 16) >> 4), i);
        wg_commit();
        wg_wait0();
        uint32_t pk[12];
#pragma unroll
        for (int i = 0; i < 12; i++) pk[i] = PK2(w1, 2 * i);
        wg_fence();
#pragma unroll
        for (int i = 0; i < 4; i++)
          wgmma_rs<32, 0>(w1, BB[i][0], BB[i][1], BB[i][2], BB[i][3],
                          ub0 + (uint64_t)((k * CH_BYTES + ((2 * i) & 3) * U_CS + (32 + (i < 2)) * 16) >> 4), i);
        wg_commit();
#pragma unroll
        for (int i = 0; i < 3; i++) stsm4t(wa + k * CH_BYTES + i * 1152, pk[4 * i], pk[4 * i + 1], pk[4 * i + 2], pk[4 * i + 3]);
        wg_wait0();
#pragma unroll
        for (int i = 0; i < 2; i++) stsm4t(wb + k * CH_BYTES + i * 1152, PK2(w1, 8 * i), PK2(w1, 8 * i + 2), PK2(w1, 8 * i + 4), PK2(w1, 8 * i + 6));
      }
    }
    fence_async();
    asm volatile("mbarrier.arrive.shared::cta.b64 _, [%0];" ::"r"(sb + B_W) : "memory");
    STAMP(7);
    {
      const int bsel = (int)rank ^ br ^ 1, xl = wtid & 63;
      uint2 gl[4];
      uint32_t ua[4][4], ub[4][4];
#pragma unroll
      for (int i = 0; i < 4; i++) skip_terms(ua[i], ub[i], sb, (2 * (i >> 1) + bsel) * 128 + (i & 1) * 64 + xl, dA, dB);
      const uint32_t yo = sb + CH_OFF + (xl & 3) * 4 + ysw(xl >> 2) + bsel * 512;
#pragma unroll
      for (int i = 0; i < 2; i++) gl[i] = gate_ld(bsel * 128 + i * 64 + xl);
#pragma unroll
      for (int slot = 0; slot < 2; slot++) {
        const int box = 2 * slot + bsel;
        uint32_t g2[2], ya[2][4], yb[2][4];
#pragma unroll
        for (int h = 0; h < 2; h++) g2[h] = gate_fin(p, gl[2 * slot + h], box * 128 + h * 64 + xl, tag);
        mbar_wait(sb + B_ST + 8 * box);
        STAMP(8 + slot);
        if (slot == 0) { gl[2] = gate_ld((2 + bsel) * 128 + xl); gl[3] = gate_ld((2 + bsel) * 128 + 64 + xl); }
#pragma unroll
        for (int h = 0; h < 2; h++) {
          const uint32_t yh = (yo ^ (h * 32)) + h * 256 + slot * 1024;
          ld4ch(ya[h], yh + Y0_OFF); ld4ch(yb[h], yh + Y0_OFF + 4096);
          if (slot) {
            uint32_t a2[4], b2[4];
            ld4ch(a2, yh + Y2_OFF - 1024); ld4ch(b2, yh + Y2_OFF - 1024 + 3072);
#pragma unroll
            for (int k = 0; k < 4; k++) { ya[h][k] = hadd2(ya[h][k], a2[k]); yb[h][k] = hadd2(yb[h][k], b2[k]); }
          }
        }
        const uint4 r0 = mix(ya[0], yb[0], ua[2 * slot], ub[2 * slot], g2[0]), r1 = mix(ya[1], yb[1], ua[2 * slot + 1], ub[2 * slot + 1], g2[1]);
        if (br == 0) { send_box(sb, slot, xl, rank, r0); send_box(sb, slot, xl + 64, rank, r1); }
        else {
          const uint32_t st = sb + RAW_OFF + slot * 4096 + xl * 16, xin = sb + XIN_OFF + slot * 2048 + xl * 16;
          mbar_wait(sb + B_X + slot * 8);
          const uint4 q0 = lds128(xin), q1 = lds128(xin + 1024);
          merge_rows(st, rank, r0, q0); merge_rows(st + 1024, rank, r1, q1);
          fence_async();
          bar_sync(6, 64);
          if (xl == 0) {
            asm volatile("cp.async.bulk.tensor.3d.global.shared::cta.bulk_group [%0, {%2, %3, %4}], [%1];"
                         ::"l"(&tm_out), "r"(sb + RAW_OFF + slot * 4096), "r"(oc0), "r"(box * 128), "r"(0) : "memory");
            asm volatile("cp.async.bulk.commit_group;" ::: "memory");
          }
        }
        STAMP(10 + slot);
      }
    }
    if (wtid == 0 && atomicAdd(&g_ticket, 1u) == NCTA + NGATE - 1) { g_ticket = 0; g_epoch = epoch + 1; }
    if (wtid == 64) asm volatile("cp.async.bulk.wait_group.read 0;" ::: "memory");
    STAMP(15);
    return;
  }
  asm volatile("barrier.cluster.arrive.relaxed.aligned;" ::: "memory");

  const int moff = (bid * 4 + (tid >> 7)) * NM + (tid & 63) * 2;
  const int brt = (tid >> 6) & 1;
  const __nv_bfloat16* const* tp = p.t + (brt ? 0 : 6);
  const uint32_t q0 = *(const uint32_t*)(tp[0] + moff), q1 = *(const uint32_t*)(tp[1] + moff);
  const uint32_t q2 = *(const uint32_t*)(tp[2] + moff), q3 = *(const uint32_t*)(tp[3] + moff);
  const uint2 ldt4 = *(const uint2*)(tp[4] + bid * 4);
  const uint32_t q4 = *(const uint32_t*)(tp[brt ? 2 : 5] + moff), q5 = *(const uint32_t*)(tp[brt ? 3 : 6] + moff);

  for (int i = wtid & 63; i < R_BR / 16; i += 64) sts128(cb + R_OFF + br * R_BR + i * 16, 0, 0, 0, 0);
  STAMP(1);

  float acc[5][4];
  float k2048 = 0.f;
  const uint32_t scr = cb + Y0_OFF + wq * SCR_BYTES;
  const uint32_t scr2 = sb + XIN_OFF + warp * 640;
  {
    const uint32_t ldt2 = (ch & 2) ? ldt4.y : ldt4.x;
    const float dt = bf_round(expf((ch & 1) ? bf_hi(ldt2) : bf_lo(ldt2)));
#pragma unroll
    for (int i = 0; i < 5; i++) acc[i][0] = acc[i][1] = acc[i][2] = acc[i][3] = 0.f;
    STAMP(2);
    const uint32_t tb = scr + lane * 16;
    const uint32_t ta = scr + (lane >> 3) * 512 + (lane & 7) * 16;
    const uint32_t tc = ((lane & 8) ? scr2 : scr + 4096) + (lane >> 4) * 128 + (lane & 7) * 16;
    const uint32_t tm = scr2 + 512 + ((lane >> 3) & 1) * 64 + (lane >> 4) * 16;
    cf cc[2], zz1[2], zz128[2];
#pragma unroll
    for (int r = 0; r < 2; r++) {
      float v0 = r ? bf_hi(q0) : bf_lo(q0), v1 = r ? bf_hi(q1) : bf_lo(q1), v2 = r ? bf_hi(q2) : bf_lo(q2);
      float v3 = r ? bf_hi(q3) : bf_lo(q3), v4 = r ? bf_hi(q4) : bf_lo(q4), v5 = r ? bf_hi(q5) : bf_lo(q5);
      if (br == 0) { cc[r] = cmul(cf{v2, v3}, cf{dt * v4, dt * v5}); }
      else { v0 = -bf_round(expf(v0)); cc[r] = cf{2.f * dt * v2, 2.f * dt * v3}; }
      const float xl = (dt * v0) * 1.4426950408889634f, y = dt * v1;
      zz1[r] = cexp_p(xl, y, 1.f); zz128[r] = cexp_p(xl, y, 128.f);
    }
    uint32_t T[10][4], m4;
    auto produce = [&](int r) {
      const cf c = cc[r], z1 = zz1[r], z128 = zz128[r];
      const cf z2 = csq(z1), z4 = csq(z2), z8 = csq(z4);
      const cf w8 = {z8.re, -z8.im};
      const cf z16 = csq(w8), z24 = cmul(z16, w8), z32 = csq(z16), z40 = cmul(z32, w8), z48 = csq(z24), z56 = cmul(z32, z24), z64 = csq(z32);
      const cf z256 = csq(z128), z512 = csq(z256), z1024 = csq(z512), z2048 = csq(z1024);
      k2048 += fmaf(c.re, z2048.re, -c.im * z2048.im);
      {
        T[0][0] = pack_bf16(1.f, z8.re); T[0][1] = pack_bf16(z16.re, z24.re); T[0][2] = pack_bf16(z32.re, z40.re); T[0][3] = pack_bf16(z48.re, z56.re);
        T[2][0] = pack_bf16(0.f, w8.im); T[2][1] = pack_bf16(z16.im, z24.im); T[2][2] = pack_bf16(z32.im, z40.im); T[2][3] = pack_bf16(z48.im, z56.im);
        const uint32_t yr = pack_bf16(z64.re, z64.re), yi = pack_bf16(z64.im, z64.im), nyi = yi ^ 0x80008000u;
#pragma unroll
        for (int i = 0; i < 4; i++) CMUL2(T[1][i], T[3][i], T[0][i], T[2][i], yr, yi, nyi);
      }
      {
        const cf h1 = cmul(c, z128), h2 = cmul(c, z256), h3 = cmul(h1, z256), h4 = cmul(c, z512), h5 = cmul(h1, z512), h6 = cmul(h2, z512), h7 = cmul(h3, z512);
        const cf e1 = cmul(c, z1), e2 = cmul(c, z2), e3 = cmul(e1, z2), e129 = cmul(h1, z1), e130 = cmul(h1, z2), e131 = cmul(e129, z2);
        const cf e258 = cmul(h2, z2), e386 = cmul(h3, z2);
        T[4][0] = pack_bf16(c.re, e1.re); T[4][1] = pack_bf16(e2.re, e3.re); T[4][2] = pack_bf16(h1.re, e129.re); T[4][3] = pack_bf16(e130.re, e131.re);
        T[5][0] = pack_bf16(c.im, e1.im); T[5][1] = pack_bf16(e2.im, e3.im); T[5][2] = pack_bf16(h1.im, e129.im); T[5][3] = pack_bf16(e130.im, e131.im);
        T[6][0] = pack_bf16(h2.re, e258.re); T[6][1] = pack_bf16(h3.re, e386.re); T[6][2] = pack_bf16(h4.re, h5.re); T[6][3] = pack_bf16(h6.re, h7.re);
        T[7][0] = pack_bf16(h2.im, e258.im); T[7][1] = pack_bf16(h3.im, e386.im); T[7][2] = pack_bf16(h4.im, h5.im); T[7][3] = pack_bf16(h6.im, h7.im);
        const uint32_t xr[4] = {__byte_perm(T[4][0], T[4][2], 0x5410), __byte_perm(T[6][0], T[6][1], 0x5410), T[6][2], T[6][3]};
        const uint32_t xi[4] = {__byte_perm(T[5][0], T[5][2], 0x5410), __byte_perm(T[7][0], T[7][1], 0x5410), T[7][2], T[7][3]};
        const uint32_t yr = pack_bf16(z1024.re, z1024.re), yi = pack_bf16(z1024.im, z1024.im), nyi = yi ^ 0x80008000u;
#pragma unroll
        for (int i = 0; i < 4; i++) CMUL2(T[8][i], T[9][i], xr[i], xi[i], yr, yi, nyi);
        m4 = pack_bf16(z4.re, z4.im);
      }
    };
    auto store = [&]() {
#pragma unroll
      for (int m = 0; m < 9; m++) sts128(tb + m * 512, T[m][0], T[m][1], T[m][2], T[m][3]);
      sts128(scr2 + lane * 16, T[9][0], T[9][1], T[9][2], T[9][3]);
      sts16(scr2 + 512 + lane * 2, m4); sts16(scr2 + 576 + lane * 2, m4 >> 16);
    };
    auto consume = [&]() {
#pragma unroll
      for (int kp = 0; kp < 2; kp++) {
        uint32_t rr[2], ri[2], yr[2], yi[2];
        ldsm4t(tc + kp * 256, rr[0], ri[0], rr[1], ri[1]);
        ldsm4(tm + kp * 32, yr[0], yi[0], yr[1], yi[1]);
#pragma unroll
        for (int k2 = 0; k2 < 2; k2++) {
          const int kk = kp * 2 + k2;
          uint32_t a0, a1, a2, a3, pr, pi, qr, qi, xr, xi;
          ldsm4t(ta + kk * 128, a0, a1, a2, a3);
          ldsm4t(ta + 2048 + kk * 128, pr, pi, qr, qi);
          const uint32_t nyi = yi[k2] ^ 0x80008000u;
          mma16816(acc[0], a0, a1, a2, a3, pr, pi);
          mma16816(acc[2], a0, a1, a2, a3, qr, qi);
          mma16816(acc[4], a0, a1, a2, a3, rr[k2], ri[k2]);
          CMUL2(xr, xi, pr, pi, yr[k2], yi[k2], nyi);
          mma16816(acc[1], a0, a1, a2, a3, xr, xi);
          CMUL2(xr, xi, qr, qi, yr[k2], yi[k2], nyi);
          mma16816(acc[3], a0, a1, a2, a3, xr, xi);
        }
      }
    };
    produce(0); store();
    __syncwarp();
    consume(); produce(1);
    __syncwarp();
    store();
#pragma unroll
    for (int o = 16; o; o >>= 1) k2048 += __shfl_xor_sync(0xffffffffu, k2048, o);
    __syncwarp();
    consume();
  }
  STAMP(3);
  __syncwarp();
  {
    const uint32_t xs = scr + lane * 16;
#define OTH(i, k) __float_as_uint(hf ? acc[i][k] : acc[i][2 + (k)])
    sts128(xs, OTH(0, 0), OTH(0, 1), OTH(1, 0), OTH(1, 1));
    sts128(xs + 512, OTH(2, 0), OTH(2, 1), OTH(3, 0), OTH(3, 1));
    sts128(xs + 1024, OTH(4, 0), OTH(4, 1), __float_as_uint(k2048), 0);
#undef OTH
  }

  bar_sync(7 + (warp >> 1), 64);
  STAMP(4);
  {
    const uint32_t xo = cb + Y0_OFF + (wq ^ 1) * SCR_BYTES + lane * 16;
    const uint4 o0 = lds128(xo), o1 = lds128(xo + 512), o2 = lds128(xo + 1024);
    const uint32_t rb = cb + R_OFF + br * R_BR;
#define OWN(i, k) (hf ? acc[i][2 + (k)] : acc[i][k])
    const uint32_t vP = pack_bf16(OWN(0, 1) + __uint_as_float(o0.y), OWN(0, 0) + __uint_as_float(o0.x));
    const uint32_t vP4 = pack_bf16(OWN(1, 1) + __uint_as_float(o0.w), OWN(1, 0) + __uint_as_float(o0.z));
    const uint32_t vQ = pack_bf16(OWN(2, 1) + __uint_as_float(o1.y), OWN(2, 0) + __uint_as_float(o1.x));
    const uint32_t vQ4 = pack_bf16(OWN(3, 1) + __uint_as_float(o1.w), OWN(3, 0) + __uint_as_float(o1.z));
    const uint32_t vR = pack_bf16(OWN(4, 1) + __uint_as_float(o2.y), OWN(4, 0) + __uint_as_float(o2.x));
#undef OWN
    const int j = g + 8 * hf;
    {
      const int a = 2 * (t & 1) + 64 * (t & 2) + 8 * j;
      const uint32_t ad = rb + 2 * (RD_X0 - 1 - a);
      const uint32_t a1 = (t & 2) ? ad - 8 : ad, a2 = (t & 2) ? ad : ad - 8;
      const uint32_t w1 = (t & 2) ? vP4 : vP, w2 = (t & 2) ? vP : vP4;
      sts32(a1, w1); sts32(a2, w2);
      sts16(a1 + RD_CS + 2, w1); sts16(a1 + RD_CS + 4, w1 >> 16);
      sts16(a2 + RD_CS + 2, w2); sts16(a2 + RD_CS + 4, w2 >> 16);
    }
    if (t < 2) {
      const int b = 256 + 128 * t + 8 * j;
      const uint32_t ad = rb + 2 * (RD_X0 - 6 - b);
      const uint32_t v22 = __byte_perm(vQ4, 0, 0x3232), v00 = __byte_perm(vQ, 0, 0x3232);
      sts16(ad, vQ4);
      sts64(ad + 2, v22, __byte_perm(vQ4, vQ, 0x5432));
      sts32(ad + 10, v00);
      if (b != 256) { sts16(ad + 14, v00); sts128(ad + RD_CS + 2, vQ4, v22, vQ, v00); }
      else { sts64(ad + RD_CS + 2, vQ4, v22); sts32(ad + RD_CS + 10, vQ); sts16(ad + RD_CS + 14, v00); }
    } else {
      const uint32_t ao = rb + R_O2 + 2 * (159 - (32 * t + j)), ae = ao - (R_O2 - R_E2) + 2;
      sts16(ao, vQ4 >> 16); sts16(ao + RS_CS + 2, vQ4 >> 16); sts16(ao - 32, vQ4); sts16(ao - 32 + RS_CS + 2, vQ4);
      sts16(ae - 32, vQ); sts16(ae - 32 + RS_CS + 2, vQ);
      if (lane != 2 || hf) { sts16(ae, vQ >> 16); sts16(ae + RS_CS + 2, vQ >> 16); }
      else {
        const uint32_t vv = __byte_perm(vQ, 0, 0x3232), ad = rb + 2 * (RD_X0 - 514);
        sts16(ad, vv); sts32(ad + 2, vv); sts16(ad + 6, vv); sts64(ad + RD_CS + 2, vv, vv);
      }
    }
    {
      const uint32_t a = rb + ((g & 1) ? R_O3 : R_E3 + 2) + 2 * (159 - (64 + 16 * t + (j >> 1)));
      const bool p1024 = (lane == 0) && (hf == 0);
      const uint32_t a00 = p1024 ? rb + R_E2 + 2 * (159 - 127) : a;
      sts16(a00, vR >> 16); sts16(a00 + RS_CS + 2, vR >> 16);
      sts16(a - 16, vR); sts16(a - 16 + RS_CS + 2, vR);
      if (p1024) {
        sts32(sb + K1024_OFF + (ch * 2 + br) * 4, __byte_perm(vR, 0, 0x3232));
        const uint32_t kv = pack_bf16(k2048 + __uint_as_float(o2.z), 0.f);
        sts16(rb + R_E3 + 2 * (159 - 127), kv); sts16(rb + R_E3 + 2 * (159 - 127) + RS_CS + 2, kv);
      }
    }
  }
  STAMP(5);
  asm volatile("barrier.cluster.wait.aligned;" ::: "memory");
  bar_sync(7 + (warp >> 1), 64);
  mbar_wait(sb + B_U);
  STAMP(6);

  const uint32_t zz = lds32(cb + R_OFF + br * R_BR);
  conv_dense(sb, cb, zz);
  STAMP(8);
  {
    const int x = (4 + ch) * 128 + wtid, c = x >> 2;
    const uint2 dA = ldg64(p.A_D + bid * 4), dB = ldg64(p.B_D + bid * 4);
    const uint2 gl = gate_ld(x);
    const uint32_t rb = cb + R_OFF + br * R_BR;
    float e48[24], e40[20], e32[16], h32[16], h16[8];
    const int x1 = 159 - (16 * hf + g - 2 * t + 136);
    const uint32_t fs = rb + ((g & 1) ? 2 * x1 : RS_CS + 2 * x1 + 2);
    uint32_t A[2][4][4];
    auto loadA = [&](int buf, uint32_t oe, uint32_t oo, int i0) {
#pragma unroll
      for (int a = 0; a < 2; a++) {
        const uint32_t base = fs + (a ? oo : oe) + i0 * 16;
        uint32_t* k0 = A[buf][2 * a];
        uint32_t* k1 = A[buf][2 * a + 1];
        k0[1] = lds32(base); k0[0] = lds32(base + 16); k0[2] = lds32(base + 32); k1[0] = lds32(base + 48); k1[2] = lds32(base + 64);
        k0[3] = k0[0]; k1[1] = k0[2]; k1[3] = k1[0];
      }
    };
    loadA(0, R_E2, R_O2, 8);
    loadA(1, R_E2, R_O2, 4);
    mbar_wait(sb + B_W);
    const uint64_t d5 = mkdesc(cb + W5_OFF, 144, 576), d3 = mkdesc(cb + W3_OFF, 144, 576);
    const uint64_t d9 = mkdesc(cb + W9_OFF, 144, 576), d7 = mkdesc(cb + W7_OFF, 144, 576);
    const uint32_t y2d = cb + Y2_OFF + br * 3072 + ysw(32 * (5 - (lane >> 4)) + 16 * hf + (lane & 15));
    const uint32_t y3d = cb + Y3_OFF + br * 2048 + ysw(2 * (16 * hf + (lane & 15)) + (lane >> 4));
#define FAR4(N, ACC, BUF, DA, DB, OFF, FIRST)                                                            \
    wg_fence();                                                                                           \
    _Pragma("unroll") for (int k = 0; k < 4; k++) {                                                      \
      const uint32_t* a = A[BUF][k];                                                                      \
      wgmma_rs<N, 1>(ACC, a[0], a[1], a[2], a[3], ((k >> 1) ? DB : DA) + (k & 1) * 18 + (OFF), !(FIRST) || k); \
    }                                                                                                     \
    wg_commit();
    FAR4(48, e48, 0, d5, d3, 0, 1)
    wg_wait0();
    loadA(0, R_E2, R_O2, 0);
    stsm2(y2d - 5 * 512, PK2(e48, 20), PK2(e48, 22));
#pragma unroll
    for (int i = 0; i < 20; i++) e40[i] = FCPY(e48[i]);
    stage_done(sb, 2, lane);
    FAR4(40, e40, 1, d5, d3, 36, 0)
    wg_wait0();
    loadA(1, R_E3, R_O3, 8);
    stsm2(y2d - 4 * 512, PK2(e40, 16), PK2(e40, 18));
#pragma unroll
    for (int i = 0; i < 16; i++) e32[i] = FCPY(e40[i]);
    stage_done(sb, 3, lane);
    FAR4(32, e32, 0, d5, d3, 72, 0)
    FAR4(32, h32, 1, d9, d7, 0, 1)
    wg_wait1();
    loadA(0, R_E3, R_O3, 4);
    stsm4(y2d, PK2(e32, 0), PK2(e32, 2), PK2(e32, 4), PK2(e32, 6));
    stsm4(y2d - 2 * 512, PK2(e32, 8), PK2(e32, 10), PK2(e32, 12), PK2(e32, 14));
    stage_done(sb, 4, lane);
    STAMP(9);
    wg_wait0();
    stsm4(y3d, PK2(h32, 8), PK2(h32, 10), PK2(h32, 12), PK2(h32, 14));
#pragma unroll
    for (int i = 0; i < 8; i++) h16[i] = FCPY(h32[i]);
    stage_done(sb, 5, lane);
    FAR4(16, h16, 0, d9, d7, 72, 0)
#undef FAR4
    const uint32_t yo = sb + CH_OFF + (x & 3) * 4 + ysw(c);
    uint32_t ua[4], ub[4], ya[4], yb[4], a2[4], b2[4], a3[4], b3[4], s2[4];
    skip_terms(ua, ub, sb, x, dA, dB);
    {
      const int xa = x - 514, xb = x - 513, ca = xa >> 2, cb2 = xb >> 2;
      ld4ch(s2, sb + CH_OFF + U_OFF + (xa & 3) * 4 + (ca & 3) * U_CS + (63 - (ca >> 2)) * 16);
      ld4ch(a3, sb + CH_OFF + U_OFF + (xb & 3) * 4 + (cb2 & 3) * U_CS + (63 - (cb2 >> 2)) * 16);
#pragma unroll
      for (int k = 0; k < 4; k++) s2[k] = hadd2(s2[k], __byte_perm(s2[k], a3[k], 0x5432));
    }
    const uint32_t tag = lds32(sb + TAG_OFF);
    wg_wait0();
    stsm4(y3d + 1024, PK2(h16, 0), PK2(h16, 2), PK2(h16, 4), PK2(h16, 6));
    stage_done(sb, 6, lane);
    STAMP(10);
    const uint32_t g2 = gate_fin(p, gl, x, tag);
    mbar_wait(sb + B_ST + 8 * 4);
    const uint4 k0 = lds128(sb + K1024_OFF), k1 = lds128(sb + K1024_OFF + 16);
    const uint32_t kk[8] = {k0.x, k0.y, k0.z, k0.w, k1.x, k1.y, k1.z, k1.w};
    ld4ch(ya, yo + Y0_OFF); ld4ch(yb, yo + Y0_OFF + 4096);
    ld4ch(a2, yo + Y2_OFF - 1024); ld4ch(b2, yo + Y2_OFF - 1024 + 3072);
    mbar_wait(sb + B_ST + 8 * (5 + (ch >> 1)));
    STAMP(12);
    ld4ch(a3, yo + Y3_OFF - 2048); ld4ch(b3, yo + Y3_OFF - 2048 + 2048);
#pragma unroll
    for (int k = 0; k < 4; k++) {
      ya[k] = hadd2(ya[k], hadd2(hfma2(kk[2 * k], s2[k], a2[k]), a3[k]));
      yb[k] = hadd2(yb[k], hadd2(hfma2(kk[2 * k + 1], s2[k], b2[k]), b3[k]));
    }
    const uint4 r = mix(ya, yb, ua, ub, g2);
    if ((uint32_t)(ch & 1) != rank) send_box(sb, 2 + (ch >> 1), wtid, rank, r);
    else merge_box(sb, &tm_out, 2 + (ch >> 1), wtid, rank, oc0, r, 1 + ch);
  }
  STAMP(14);
  if (wtid == 0) asm volatile("cp.async.bulk.wait_group.read 0;" ::: "memory");
  STAMP(15); GT(1);
}

typedef CUresult (*EncodeFn)(CUtensorMap*, CUtensorMapDataType, cuuint32_t, void*, const cuuint64_t*, const cuuint64_t*,
                             const cuuint32_t*, const cuuint32_t*, CUtensorMapInterleave, CUtensorMapSwizzle,
                             CUtensorMapL2promotion, CUtensorMapFloatOOBfill);

}

extern "C" void kernel_launch(void* const* d_in, const int* in_sizes, int n_in, void* d_out, int out_size) {
  (void)in_sizes; (void)n_in; (void)out_size;
  typedef const __nv_bfloat16* bp;
  Params p;
  p.t[0] = (bp)d_in[10]; p.t[1] = (bp)d_in[11]; p.t[2] = (bp)d_in[12]; p.t[3] = (bp)d_in[13]; p.t[4] = (bp)d_in[14]; p.t[5] = nullptr;
  p.t[6] = (bp)d_in[1]; p.t[7] = (bp)d_in[2]; p.t[8] = (bp)d_in[5]; p.t[9] = (bp)d_in[6]; p.t[10] = (bp)d_in[7];
  p.t[11] = (bp)d_in[3]; p.t[12] = (bp)d_in[4]; p.t[13] = nullptr;
  p.u = (bp)d_in[0]; p.gw = (bp)d_in[16]; p.A_D = (bp)d_in[8]; p.B_D = (bp)d_in[15];
  static EncodeFn enc = nullptr;
  if (!enc) {
    cudaDriverEntryPointQueryResult qr;
    cudaGetDriverEntryPoint("cuTensorMapEncodeTiled", (void**)&enc, cudaEnableDefault, &qr);
    cudaFuncSetAttribute(ssm_kernel, cudaFuncAttributeMaxDynamicSharedMemorySize, SMEM_BYTES);
  }
  CUtensorMap tm_in, tm_out;
  {
    cuuint64_t gd[5] = {512, 2, 4, 4, 64};
    cuuint64_t gs[4] = {1024, 8192, 2048, 32768};
    cuuint32_t bx[5] = {8, 2, 4, 4, 32};
    cuuint32_t es[5] = {1, 1, 1, 1, 1};
    enc(&tm_in, CU_TENSOR_MAP_DATA_TYPE_BFLOAT16, 5, d_in[0], gd, gs, bx, es, CU_TENSOR_MAP_INTERLEAVE_NONE,
        CU_TENSOR_MAP_SWIZZLE_NONE, CU_TENSOR_MAP_L2_PROMOTION_NONE, CU_TENSOR_MAP_FLOAT_OOB_FILL_NONE);
  }
  {
    cuuint64_t gd[3] = {512, 1024, 2};
    cuuint64_t gs[2] = {2048, 1024};
    cuuint32_t bx[3] = {8, 128, 2};
    cuuint32_t es[3] = {1, 1, 1};
    enc(&tm_out, CU_TENSOR_MAP_DATA_TYPE_BFLOAT16, 3, d_out, gd, gs, bx, es, CU_TENSOR_MAP_INTERLEAVE_NONE,
        CU_TENSOR_MAP_SWIZZLE_NONE, CU_TENSOR_MAP_L2_PROMOTION_NONE, CU_TENSOR_MAP_FLOAT_OOB_FILL_NONE);
  }
  ssm_kernel<<<NCTA + NGATE, 640, SMEM_BYTES, cudaStreamPerThread>>>(p, tm_in, tm_out);
}
```

```cpp
#include <cuda_runtime.h>
#include <cuda.h>
#include <cuda_bf16.h>
#include <stdint.h>

namespace {
#define FCPY(x) __uint_as_float(opq(__float_as_uint(x), zz))

constexpr int L = 2048, D = 512, NM = 128;
constexpr int NCTA = 128;
constexpr int NGATE = 4;

constexpr int RAW_OFF = 0;
constexpr int XIN_OFF = 32768;
constexpr int BAR_OFF = XIN_OFF + 10240;
constexpr int CH_OFF = BAR_OFF + 256;
constexpr int U_CS = 1184;
constexpr int U_OFF = 0;
constexpr int R_OFF = 4736;
constexpr int RD_X0 = 565;
constexpr int RD_CS = 1216;
constexpr int RS_CS = 320;
constexpr int R_E2 = 2 * RD_CS, R_O2 = R_E2 + 2 * RS_CS, R_E3 = R_O2 + 2 * RS_CS, R_O3 = R_E3 + 2 * RS_CS;
constexpr int R_BR = R_O3 + 2 * RS_CS;
constexpr int W5_OFF = R_OFF + 2 * R_BR;
constexpr int W3_OFF = W5_OFF + 3456;
constexpr int W9_OFF = W3_OFF + 3456;
constexpr int W7_OFF = W9_OFF + 2304;
constexpr int Y0_OFF = W7_OFF + 2304;
constexpr int Y2_OFF = Y0_OFF + 8192, Y3_OFF = Y2_OFF + 6144;
constexpr int CH_BYTES = Y0_OFF + 18432 + 16;
constexpr int SCR_BYTES = 4608;
constexpr int SMEM_BYTES = CH_OFF + 4 * CH_BYTES;
static_assert(CH_BYTES % 128 == 16, "bank staggering of the channel blocks");
static_assert(SMEM_BYTES <= 232448, "smem");
constexpr int B_RAW = BAR_OFF, B_X = BAR_OFF + 8, B_U = BAR_OFF + 40, B_W = BAR_OFF + 48;
constexpr int TAG_OFF = BAR_OFF + 56;
constexpr int K1024_OFF = BAR_OFF + 64;
constexpr int B_ST = BAR_OFF + 96;

__device__ unsigned int g_gate[L];
__device__ unsigned int g_epoch;
__device__ unsigned int g_ticket;

#define STAMP(k)
#define GT(k)

struct Params {
  const __nv_bfloat16* t[14];
  const __nv_bfloat16 *u, *gw, *A_D, *B_D;
};

template <int N, int TB> __device__ __forceinline__ void wgmma_rs(float* d, uint32_t a0, uint32_t a1, uint32_t a2, uint32_t a3, uint64_t desc, int sc);
template <> __device__ __forceinline__ void wgmma_rs<64, 0>(float* d, uint32_t a0, uint32_t a1, uint32_t a2, uint32_t a3, uint64_t desc, int sc) {
  asm volatile("{\n.reg .pred p;\nsetp.ne.b32 p, %37, 0;\n"
    "wgmma.mma_async.sync.aligned.m64n64k16.f32.bf16.bf16 {%0,%1,%2,%3,%4,%5,%6,%7,%8,%9,%10,%11,%12,%13,%14,%15,%16,%17,%18,%19,%20,%21,%22,%23,%24,%25,%26,%27,%28,%29,%30,%31}, {%32,%33,%34,%35}, %36, p, 1, 1, 0;\n}"
    : "+f"(d[0]), "+f"(d[1]), "+f"(d[2]), "+f"(d[3]), "+f"(d[4]), "+f"(d[5]), "+f"(d[6]), "+f"(d[7]), "+f"(d[8]), "+f"(d[9]), "+f"(d[10]), "+f"(d[11]), "+f"(d[12]), "+f"(d[13]), "+f"(d[14]), "+f"(d[15]), "+f"(d[16]), "+f"(d[17]), "+f"(d[18]), "+f"(d[19]), "+f"(d[20]), "+f"(d[21]), "+f"(d[22]), "+f"(d[23]), "+f"(d[24]), "+f"(d[25]), "+f"(d[26]), "+f"(d[27]), "+f"(d[28]), "+f"(d[29]), "+f"(d[30]), "+f"(d[31]) : "r"(a0), "r"(a1), "r"(a2), "r"(a3), "l"(desc), "r"(sc));
}
template <> __device__ __forceinline__ void wgmma_rs<56, 0>(float* d, uint32_t a0, uint32_t a1, uint32_t a2, uint32_t a3, uint64_t desc, int sc) {
  asm volatile("{\n.reg .pred p;\nsetp.ne.b32 p, %33, 0;\n"
    "wgmma.mma_async.sync.aligned.m64n56k16.f32.bf16.bf16 {%0,%1,%2,%3,%4,%5,%6,%7,%8,%9,%10,%11,%12,%13,%14,%15,%16,%17,%18,%19,%20,%21,%22,%23,%24,%25,%26,%27}, {%28,%29,%30,%31}, %32, p, 1, 1, 0;\n}"
    : "+f"(d[0]), "+f"(d[1]), "+f"(d[2]), "+f"(d[3]), "+f"(d[4]), "+f"(d[5]), "+f"(d[6]), "+f"(d[7]), "+f"(d[8]), "+f"(d[9]), "+f"(d[10]), "+f"(d[11]), "+f"(d[12]), "+f"(d[13]), "+f"(d[14]), "+f"(d[15]), "+f"(d[16]), "+f"(d[17]), "+f"(d[18]), "+f"(d[19]), "+f"(d[20]), "+f"(d[21]), "+f"(d[22]), "+f"(d[23]), "+f"(d[24]), "+f"(d[25]), "+f"(d[26]), "+f"(d[27]) : "r"(a0), "r"(a1), "r"(a2), "r"(a3), "l"(desc), "r"(sc));
}
template <> __device__ __forceinline__ void wgmma_rs<48, 0>(float* d, uint32_t a0, uint32_t a1, uint32_t a2, uint32_t a3, uint64_t desc, int sc) {
  asm volatile("{\n.reg .pred p;\nsetp.ne.b32 p, %29, 0;\n"
    "wgmma.mma_async.sync.aligned.m64n48k16.f32.bf16.bf16 {%0,%1,%2,%3,%4,%5,%6,%7,%8,%9,%10,%11,%12,%13,%14,%15,%16,%17,%18,%19,%20,%21,%22,%23}, {%24,%25,%26,%27}, %28, p, 1, 1, 0;\n}"
    : "+f"(d[0]), "+f"(d[1]), "+f"(d[2]), "+f"(d[3]), "+f"(d[4]), "+f"(d[5]), "+f"(d[6]), "+f"(d[7]), "+f"(d[8]), "+f"(d[9]), "+f"(d[10]), "+f"(d[11]), "+f"(d[12]), "+f"(d[13]), "+f"(d[14]), "+f"(d[15]), "+f"(d[16]), "+f"(d[17]), "+f"(d[18]), "+f"(d[19]), "+f"(d[20]), "+f"(d[21]), "+f"(d[22]), "+f"(d[23]) : "r"(a0), "r"(a1), "r"(a2), "r"(a3), "l"(desc), "r"(sc));
}
template <> __device__ __forceinline__ void wgmma_rs<32, 0>(float* d, uint32_t a0, uint32_t a1, uint32_t a2, uint32_t a3, uint64_t desc, int sc) {
  asm volatile("{\n.reg .pred p;\nsetp.ne.b32 p, %21, 0;\n"
    "wgmma.mma_async.sync.aligned.m64n32k16.f32.bf16.bf16 {%0,%1,%2,%3,%4,%5,%6,%7,%8,%9,%10,%11,%12,%13,%14,%15}, {%16,%17,%18,%19}, %20, p, 1, 1, 0;\n}"
    : "+f"(d[0]), "+f"(d[1]), "+f"(d[2]), "+f"(d[3]), "+f"(d[4]), "+f"(d[5]), "+f"(d[6]), "+f"(d[7]), "+f"(d[8]), "+f"(d[9]), "+f"(d[10]), "+f"(d[11]), "+f"(d[12]), "+f"(d[13]), "+f"(d[14]), "+f"(d[15]) : "r"(a0), "r"(a1), "r"(a2), "r"(a3), "l"(desc), "r"(sc));
}
template <> __device__ __forceinline__ void wgmma_rs<48, 1>(float* d, uint32_t a0, uint32_t a1, uint32_t a2, uint32_t a3, uint64_t desc, int sc) {
  asm volatile("{\n.reg .pred p;\nsetp.ne.b32 p, %29, 0;\n"
    "wgmma.mma_async.sync.aligned.m64n48k16.f32.bf16.bf16 {%0,%1,%2,%3,%4,%5,%6,%7,%8,%9,%10,%11,%12,%13,%14,%15,%16,%17,%18,%19,%20,%21,%22,%23}, {%24,%25,%26,%27}, %28, p, 1, 1, 1;\n}"
    : "+f"(d[0]), "+f"(d[1]), "+f"(d[2]), "+f"(d[3]), "+f"(d[4]), "+f"(d[5]), "+f"(d[6]), "+f"(d[7]), "+f"(d[8]), "+f"(d[9]), "+f"(d[10]), "+f"(d[11]), "+f"(d[12]), "+f"(d[13]), "+f"(d[14]), "+f"(d[15]), "+f"(d[16]), "+f"(d[17]), "+f"(d[18]), "+f"(d[19]), "+f"(d[20]), "+f"(d[21]), "+f"(d[22]), "+f"(d[23]) : "r"(a0), "r"(a1), "r"(a2), "r"(a3), "l"(desc), "r"(sc));
}
template <> __device__ __forceinline__ void wgmma_rs<40, 1>(float* d, uint32_t a0, uint32_t a1, uint32_t a2, uint32_t a3, uint64_t desc, int sc) {
  asm volatile("{\n.reg .pred p;\nsetp.ne.b32 p, %25, 0;\n"
    "wgmma.mma_async.sync.aligned.m64n40k16.f32.bf16.bf16 {%0,%1,%2,%3,%4,%5,%6,%7,%8,%9,%10,%11,%12,%13,%14,%15,%16,%17,%18,%19}, {%20,%21,%22,%23}, %24, p, 1, 1, 1;\n}"
    : "+f"(d[0]), "+f"(d[1]), "+f"(d[2]), "+f"(d[3]), "+f"(d[4]), "+f"(d[5]), "+f"(d[6]), "+f"(d[7]), "+f"(d[8]), "+f"(d[9]), "+f"(d[10]), "+f"(d[11]), "+f"(d[12]), "+f"(d[13]), "+f"(d[14]), "+f"(d[15]), "+f"(d[16]), "+f"(d[17]), "+f"(d[18]), "+f"(d[19]) : "r"(a0), "r"(a1), "r"(a2), "r"(a3), "l"(desc), "r"(sc));
}
template <> __device__ __forceinline__ void wgmma_rs<32, 1>(float* d, uint32_t a0, uint32_t a1, uint32_t a2, uint32_t a3, uint64_t desc, int sc) {
  asm volatile("{\n.reg .pred p;\nsetp.ne.b32 p, %21, 0;\n"
    "wgmma.mma_async.sync.aligned.m64n32k16.f32.bf16.bf16 {%0,%1,%2,%3,%4,%5,%6,%7,%8,%9,%10,%11,%12,%13,%14,%15}, {%16,%17,%18,%19}, %20, p, 1, 1, 1;\n}"
    : "+f"(d[0]), "+f"(d[1]), "+f"(d[2]), "+f"(d[3]), "+f"(d[4]), "+f"(d[5]), "+f"(d[6]), "+f"(d[7]), "+f"(d[8]), "+f"(d[9]), "+f"(d[10]), "+f"(d[11]), "+f"(d[12]), "+f"(d[13]), "+f"(d[14]), "+f"(d[15]) : "r"(a0), "r"(a1), "r"(a2), "r"(a3), "l"(desc), "r"(sc));
}
template <> __device__ __forceinline__ void wgmma_rs<16, 1>(float* d, uint32_t a0, uint32_t a1, uint32_t a2, uint32_t a3, uint64_t desc, int sc) {
  asm volatile("{\n.reg .pred p;\nsetp.ne.b32 p, %13, 0;\n"
    "wgmma.mma_async.sync.aligned.m64n16k16.f32.bf16.bf16 {%0,%1,%2,%3,%4,%5,%6,%7}, {%8,%9,%10,%11}, %12, p, 1, 1, 1;\n}"
    : "+f"(d[0]), "+f"(d[1]), "+f"(d[2]), "+f"(d[3]), "+f"(d[4]), "+f"(d[5]), "+f"(d[6]), "+f"(d[7]) : "r"(a0), "r"(a1), "r"(a2), "r"(a3), "l"(desc), "r"(sc));
}

__device__ __forceinline__ uint32_t pack_bf16(float lo, float hi) {
  uint32_t r; asm("cvt.rn.bf16x2.f32 %0, %1, %2;" : "=r"(r) : "f"(hi), "f"(lo)); return r;
}
__device__ __forceinline__ float bf_lo(uint32_t v) { return __uint_as_float(v << 16); }
__device__ __forceinline__ float bf_hi(uint32_t v) { return __uint_as_float(v & 0xffff0000u); }
__device__ __forceinline__ float bf_round(float x) { return bf_lo(pack_bf16(x, 0.f)); }
__device__ __forceinline__ uint32_t hmul2(uint32_t a, uint32_t b) { uint32_t r; asm("mul.rn.bf16x2 %0, %1, %2;" : "=r"(r) : "r"(a), "r"(b)); return r; }
__device__ __forceinline__ uint32_t hadd2(uint32_t a, uint32_t b) { uint32_t r; asm("add.rn.bf16x2 %0, %1, %2;" : "=r"(r) : "r"(a), "r"(b)); return r; }
__device__ __forceinline__ uint32_t hsub2(uint32_t a, uint32_t b) { uint32_t r; asm("sub.rn.bf16x2 %0, %1, %2;" : "=r"(r) : "r"(a), "r"(b)); return r; }
__device__ __forceinline__ uint32_t hfma2(uint32_t a, uint32_t b, uint32_t c) { uint32_t r; asm("fma.rn.bf16x2 %0, %1, %2, %3;" : "=r"(r) : "r"(a), "r"(b), "r"(c)); return r; }

__device__ __forceinline__ void sts16(uint32_t a, uint32_t v) { asm volatile("st.shared.b16 [%0], %1;" ::"r"(a), "h"((unsigned short)v) : "memory"); }
__device__ __forceinline__ void sts32(uint32_t a, uint32_t v) { asm volatile("st.shared.b32 [%0], %1;" ::"r"(a), "r"(v) : "memory"); }
__device__ __forceinline__ void sts64(uint32_t a, uint32_t x, uint32_t y) { asm volatile("st.shared.v2.b32 [%0], {%1,%2};" ::"r"(a), "r"(x), "r"(y) : "memory"); }
__device__ __forceinline__ void sts128(uint32_t a, uint32_t x, uint32_t y, uint32_t z, uint32_t w) {
  asm volatile("st.shared.v4.b32 [%0], {%1,%2,%3,%4};" ::"r"(a), "r"(x), "r"(y), "r"(z), "r"(w) : "memory");
}
__device__ __forceinline__ uint32_t lds32(uint32_t a) { uint32_t v; asm volatile("ld.shared.b32 %0, [%1];" : "=r"(v) : "r"(a) : "memory"); return v; }
__device__ __forceinline__ uint2 lds64(uint32_t a) { uint2 v; asm volatile("ld.shared.v2.b32 {%0,%1}, [%2];" : "=r"(v.x), "=r"(v.y) : "r"(a) : "memory"); return v; }
__device__ __forceinline__ uint4 lds128(uint32_t a) {
  uint4 v; asm volatile("ld.shared.v4.b32 {%0,%1,%2,%3}, [%4];" : "=r"(v.x), "=r"(v.y), "=r"(v.z), "=r"(v.w) : "r"(a) : "memory"); return v;
}
__device__ __forceinline__ uint4 ldg128(const void* a) {
  uint4 v; asm volatile("ld.global.nc.v4.b32 {%0,%1,%2,%3}, [%4];" : "=r"(v.x), "=r"(v.y), "=r"(v.z), "=r"(v.w) : "l"(a) : "memory"); return v;
}
__device__ __forceinline__ uint2 ldg64(const void* a) {
  uint2 v; asm volatile("ld.global.nc.v2.b32 {%0,%1}, [%2];" : "=r"(v.x), "=r"(v.y) : "l"(a) : "memory"); return v;
}
__device__ __forceinline__ void ldsm4(uint32_t a, uint32_t& r0, uint32_t& r1, uint32_t& r2, uint32_t& r3) {
  asm volatile("ldmatrix.sync.aligned.m8n8.x4.shared.b16 {%0,%1,%2,%3}, [%4];" : "=r"(r0), "=r"(r1), "=r"(r2), "=r"(r3) : "r"(a) : "memory");
}
__device__ __forceinline__ void ldsm4t(uint32_t a, uint32_t& r0, uint32_t& r1, uint32_t& r2, uint32_t& r3) {
  asm volatile("ldmatrix.sync.aligned.m8n8.x4.trans.shared.b16 {%0,%1,%2,%3}, [%4];" : "=r"(r0), "=r"(r1), "=r"(r2), "=r"(r3) : "r"(a) : "memory");
}
__device__ __forceinline__ void stsm4(uint32_t a, uint32_t r0, uint32_t r1, uint32_t r2, uint32_t r3) {
  asm volatile("stmatrix.sync.aligned.m8n8.x4.shared.b16 [%0], {%1,%2,%3,%4};" ::"r"(a), "r"(r0), "r"(r1), "r"(r2), "r"(r3) : "memory");
}
__device__ __forceinline__ void stsm4t(uint32_t a, uint32_t r0, uint32_t r1, uint32_t r2, uint32_t r3) {
  asm volatile("stmatrix.sync.aligned.m8n8.x4.trans.shared.b16 [%0], {%1,%2,%3,%4};" ::"r"(a), "r"(r0), "r"(r1), "r"(r2), "r"(r3) : "memory");
}
__device__ __forceinline__ void stsm2(uint32_t a, uint32_t r0, uint32_t r1) {
  asm volatile("stmatrix.sync.aligned.m8n8.x2.shared.b16 [%0], {%1,%2};" ::"r"(a), "r"(r0), "r"(r1) : "memory");
}
__device__ __forceinline__ void stsm2t(uint32_t a, uint32_t r0, uint32_t r1) {
  asm volatile("stmatrix.sync.aligned.m8n8.x2.trans.shared.b16 [%0], {%1,%2};" ::"r"(a), "r"(r0), "r"(r1) : "memory");
}
__device__ __forceinline__ void mma16816(float* c, uint32_t a0, uint32_t a1, uint32_t a2, uint32_t a3, uint32_t b0, uint32_t b1) {
  asm("mma.sync.aligned.m16n8k16.row.col.f32.bf16.bf16.f32 {%0,%1,%2,%3}, {%4,%5,%6,%7}, {%8,%9}, {%0,%1,%2,%3};"
      : "+f"(c[0]), "+f"(c[1]), "+f"(c[2]), "+f"(c[3]) : "r"(a0), "r"(a1), "r"(a2), "r"(a3), "r"(b0), "r"(b1));
}
__device__ __forceinline__ void bar_sync(int id, int n) { asm volatile("bar.sync %0, %1;" ::"r"(id), "r"(n) : "memory"); }
__device__ __forceinline__ void bar_arrive(int id, int n) { asm volatile("bar.arrive %0, %1;" ::"r"(id), "r"(n) : "memory"); }
__device__ __forceinline__ void wg_fence() { asm volatile("wgmma.fence.sync.aligned;" ::: "memory"); }
__device__ __forceinline__ void wg_commit() { asm volatile("wgmma.commit_group.sync.aligned;" ::: "memory"); }
__device__ __forceinline__ void wg_wait0() { asm volatile("wgmma.wait_group.sync.aligned 0;" ::: "memory"); }
__device__ __forceinline__ void wg_wait1() { asm volatile("wgmma.wait_group.sync.aligned 1;" ::: "memory"); }
__device__ __forceinline__ void fence_async() { asm volatile("fence.proxy.async.shared::cta;" ::: "memory"); }
__device__ __forceinline__ uint32_t opq(uint32_t x, uint32_t z) { uint32_t r; asm volatile("xor.b32 %0, %1, %2;" : "=r"(r) : "r"(x), "r"(z)); return r; }
__device__ __forceinline__ uint64_t mkdesc(uint32_t addr, uint32_t lbo, uint32_t sbo) {
  return (uint64_t)((addr & 0x3FFFF) >> 4) | ((uint64_t)(lbo >> 4) << 16) | ((uint64_t)(sbo >> 4) << 32);
}
__device__ __forceinline__ uint32_t mapa(uint32_t a, uint32_t rank) {
  uint32_t r; asm("mapa.shared::cluster.u32 %0, %1, %2;" : "=r"(r) : "r"(a), "r"(rank)); return r;
}
__device__ __forceinline__ void mbar_init_expect(uint32_t bar, uint32_t bytes) {
  asm volatile("mbarrier.init.shared::cta.b64 [%0], 1;" ::"r"(bar) : "memory");
  asm volatile("mbarrier.arrive.expect_tx.shared::cta.b64 _, [%0], %1;" ::"r"(bar), "r"(bytes) : "memory");
}
__device__ __forceinline__ void mbar_wait(uint32_t bar) {
#pragma unroll 1
  for (int it = 0; it < (1 << 22); it++) {
    uint32_t ok;
    asm volatile("{\n.reg .pred p;\nmbarrier.try_wait.parity.acquire.cluster.shared::cta.b64 p, [%1], 0;\nselp.u32 %0, 1, 0, p;\n}"
                 : "=r"(ok) : "r"(bar) : "memory");
    if (ok) return;
  }
  __trap();
}
__device__ __forceinline__ void st_async4(uint32_t a, uint32_t bar, uint32_t x, uint32_t y, uint32_t z, uint32_t w) {
  asm volatile("st.async.weak.shared::cluster.mbarrier::complete_tx::bytes.v4.b32 [%0], {%2,%3,%4,%5}, [%1];"
               ::"r"(a), "r"(bar), "r"(x), "r"(y), "r"(z), "r"(w) : "memory");
}

struct cf { float re, im; };
__device__ __forceinline__ cf cmul(cf a, cf b) { return {fmaf(a.re, b.re, -a.im * b.im), fmaf(a.re, b.im, a.im * b.re)}; }
__device__ __forceinline__ cf csq(cf a) { return {fmaf(a.re, a.re, -a.im * a.im), (a.re + a.re) * a.im}; }
__device__ __forceinline__ cf cexp_p(float xl, float y, float p) {
  float mag; asm("ex2.approx.ftz.f32 %0, %1;" : "=f"(mag) : "f"(xl * p));
  const float th = y * p;
  const float k = __fadd_rn(fmaf(th, 0.15915494309189535f, 12582912.f), -12582912.f);
  float r = fmaf(k, -6.2831854820251465f, th);
  r = fmaf(k, 1.7484555314695172e-07f, r);
  return {mag * __cosf(r), mag * __sinf(r)};
}
__device__ __forceinline__ uint32_t ysw(int c) { return (uint32_t)(c ^ ((c >> 3) & 3)) * 16u; }

#define CMUL2(OR, OI, xr, xi, yr, yi, nyi) do { OR = hfma2(xr, yr, hmul2(xi, nyi)); OI = hfma2(xr, yi, hmul2(xi, yr)); } while (0)

__device__ __forceinline__ uint32_t gate_slow(const __nv_bfloat16* u, const __nv_bfloat16* gw, int row) {
  float s = 0.f;
  const uint32_t* xr = (const uint32_t*)(u + (size_t)row * D);
  const uint32_t* wr = (const uint32_t*)gw;
#pragma unroll 1
  for (int j = 0; j < D / 2; j++) { const uint32_t pr = hmul2(xr[j], wr[j]); s += bf_lo(pr); s += bf_hi(pr); }
  s = bf_round(s);
  return pack_bf16(1.f / (1.f + expf(-s)), 0.f);
}

__device__ __forceinline__ uint2 gate_ld(int x) {
  uint2 gv;
  asm volatile("ld.relaxed.gpu.global.v2.u32 {%0,%1}, [%2];" : "=r"(gv.x), "=r"(gv.y) : "l"(g_gate + x * 2) : "memory");
  return gv;
}
__device__ __noinline__ uint32_t gate_poll(const Params* pp, int x, uint32_t tag) {
  uint2 gv;
#pragma unroll 1
  for (int spins = 0; spins < (1 << 16); spins++) {
    gv = gate_ld(x);
    if ((gv.x >> 16) == tag && (gv.y >> 16) == tag) return __byte_perm(gv.x, gv.y, 0x5410);
  }
  return __byte_perm(gate_slow(pp->u, pp->gw, x * 2), gate_slow(pp->u, pp->gw, x * 2 + 1), 0x5410);
}
__device__ __forceinline__ uint32_t gate_fin(const Params& p, uint2 gv, int x, uint32_t tag) {
  if ((gv.x >> 16) == tag && (gv.y >> 16) == tag) return __byte_perm(gv.x, gv.y, 0x5410);
  return gate_poll(&p, x, tag);
}

__device__ __forceinline__ void ld4ch(uint32_t* v, uint32_t addr) {
#pragma unroll
  for (int k = 0; k < 4; k++) v[k] = lds32(addr + k * CH_BYTES);
}
__device__ __forceinline__ void skip_terms(uint32_t* ua, uint32_t* ub, uint32_t sb, int x, uint2 dA, uint2 dB) {
  const int c = x >> 2;
  uint32_t uu[4];
  ld4ch(uu, sb + CH_OFF + (x & 3) * 4 + U_OFF + (c & 3) * U_CS + (63 - (c >> 2)) * 16);
#pragma unroll
  for (int k = 0; k < 4; k++) {
    ua[k] = hmul2(uu[k], __byte_perm((k & 2) ? dA.y : dA.x, 0, (k & 1) ? 0x3232 : 0x1010));
    ub[k] = hmul2(uu[k], __byte_perm((k & 2) ? dB.y : dB.x, 0, (k & 1) ? 0x3232 : 0x1010));
  }
}
__device__ __forceinline__ uint4 mix(const uint32_t* a, const uint32_t* b, const uint32_t* ua, const uint32_t* ub, uint32_t g2) {
  const uint32_t h2 = hsub2(0x3f803f80u, g2);
  uint32_t o[4];
#pragma unroll
  for (int k = 0; k < 4; k++) o[k] = hadd2(hmul2(g2, hadd2(a[k], ua[k])), hmul2(h2, hadd2(b[k], ub[k])));
  return make_uint4(__byte_perm(o[0], o[1], 0x5410), __byte_perm(o[2], o[3], 0x5410), __byte_perm(o[0], o[1], 0x7632), __byte_perm(o[2], o[3], 0x7632));
}
__device__ __forceinline__ void send_box(uint32_t sb, int slot, int wtid, uint32_t rank, uint4 r) {
  st_async4(mapa(sb + XIN_OFF + slot * 2048 + wtid * 16, rank ^ 1), mapa(sb + B_X + slot * 8, rank ^ 1), r.x, r.y, r.z, r.w);
}
__device__ __forceinline__ void merge_rows(uint32_t st, uint32_t rank, uint4 r, uint4 q) {
  const uint4 lo = rank ? q : r, hi = rank ? r : q;
  sts128(st, lo.x, lo.y, hi.x, hi.y); sts128(st + 2048, lo.z, lo.w, hi.z, hi.w);
}
__device__ __forceinline__ void merge_box(uint32_t sb, const CUtensorMap* tm_out, int slot, int wtid, uint32_t rank, int oc0, uint4 r, int barid) {
  const uint32_t st = sb + RAW_OFF + slot * 4096 + wtid * 16;
  mbar_wait(sb + B_X + slot * 8);
  merge_rows(st, rank, r, lds128(sb + XIN_OFF + slot * 2048 + wtid * 16));
  fence_async();
  bar_sync(barid, 128);
  if (wtid == 0) {
    asm volatile("cp.async.bulk.tensor.3d.global.shared::cta.bulk_group [%0, {%2, %3, %4}], [%1];"
                 ::"l"(tm_out), "r"(sb + RAW_OFF + slot * 4096), "r"(oc0), "r"((2 * slot + (int)rank) * 128), "r"(0) : "memory");
    asm volatile("cp.async.bulk.commit_group;" ::: "memory");
  }
}

__device__ __forceinline__ uint32_t band2(int e, int lo, int hi) {
  uint32_t r = ((uint32_t)(e - lo) <= (uint32_t)(hi - lo) ? 0x3f80u : 0u) | ((uint32_t)(e - 1 - lo) <= (uint32_t)(hi - lo) ? 0x3f800000u : 0u);
  asm volatile("" : "+r"(r));
  return r;
}

__device__ __forceinline__ void stage_done(uint32_t sb, int stage, int lane) {
  __syncwarp();
  if (lane == 0) asm volatile("mbarrier.arrive.shared::cta.b64 _, [%0];" ::"r"(sb + B_ST + 8 * stage) : "memory");
}
#define PK2(v, i) pack_bf16(v[i], v[(i) + 1])

__device__ __forceinline__ void conv_dense(uint32_t sb, uint32_t cb, uint32_t zz) {
  const int lane = threadIdx.x & 31, wq = (threadIdx.x >> 5) & 3, br = wq >> 1, hf = wq & 1, g = lane >> 2, t = lane & 3;
  const uint32_t rb = cb + R_OFF + br * R_BR;
  const int eo = 16 * hf + g - 2 * t;
  const int x0 = RD_X0 - (eo + 536);
  const uint32_t fa = rb + ((g & 1) ? 2 * x0 : RD_CS + 2 * x0 + 2);
  const uint64_t ub = mkdesc(cb + U_OFF, U_CS, 128);
  const uint32_t yd = cb + Y0_OFF + br * 4096 + ysw(4 * (63 - 8 * (lane >> 4) - (lane & 7)) + 2 * hf + ((lane >> 3) & 1));
  uint32_t A[2][4][4];
  float e64[32], e56[28], e48[24];
  auto loadA = [&](int j) {
#pragma unroll
    for (int k = 0; k < 4; k++) {
      const int s = 34 - 4 * j - k;
      if (s >= 0) {
        if (k == 0 && j == 0) A[0][0][2] = lds32(fa + (2 * s + 2) * 16);
        A[j & 1][k][0] = lds32(fa + (2 * s + 1) * 16);
        A[j & 1][k][1] = lds32(fa + (2 * s) * 16);
      }
    }
#pragma unroll
    for (int k = 0; k < 4; k++) {
      if (34 - 4 * j - k >= 0) {
        A[j & 1][k][3] = A[j & 1][k][0];
        if (k) A[j & 1][k][2] = A[j & 1][k - 1][1];
        else if (j) A[j & 1][0][2] = A[(j - 1) & 1][3][1];
      }
    }
  };
  loadA(0); loadA(1);
#pragma unroll
  for (int j = 0; j < 9; j++) {
    if (j == 4) {
      wg_wait0();
      stsm2t(yd - 7 * 512, PK2(e64, 28), PK2(e64, 30));
#pragma unroll
      for (int i = 0; i < 28; i++) e56[i] = FCPY(e64[i]);
      stage_done(sb, 0, lane);
    }
    if (j == 8) {
      wg_wait0();
      stsm2t(yd - 6 * 512, PK2(e56, 24), PK2(e56, 26));
#pragma unroll
      for (int i = 0; i < 24; i++) e48[i] = FCPY(e56[i]);
      stage_done(sb, 1, lane);
    }
    wg_fence();
#pragma unroll
    for (int k = 0; k < 4; k++) {
      const int s = 34 - 4 * j - k;
      if (s >= 0) {
        const int o = 2 * s - 66 + 128;
        const int cc = o & 3, rs = (o >> 2) - 32;
        const uint64_t desc = ub + (uint64_t)((cc * U_CS - rs * 16) >> 4);
        const uint32_t* a = A[j & 1][k];
        if (j < 4) wgmma_rs<64, 0>(e64, a[0], a[1], a[2], a[3], desc, s != 34);
        else if (j < 8) wgmma_rs<56, 0>(e56, a[0], a[1], a[2], a[3], desc, 1);
        else wgmma_rs<48, 0>(e48, a[0], a[1], a[2], a[3], desc, 1);
      }
    }
    wg_commit();
    if (j >= 1 && j < 8) { wg_wait1(); loadA(j + 1); }
  }
  wg_wait0();
#pragma unroll
  for (int i = 0; i < 6; i += 2) stsm4t(yd - i * 512, PK2(e48, 4 * i), PK2(e48, 4 * i + 2), PK2(e48, 4 * i + 4), PK2(e48, 4 * i + 6));
}

__device__ __noinline__ void gate_cta(const Params* pp) {
  const __nv_bfloat16 *u = pp->u, *gw = pp->gw;
  const int lane = threadIdx.x & 31;
  unsigned int epoch;
  asm volatile("ld.relaxed.gpu.global.u32 %0, [%1];" : "=r"(epoch) : "l"(&g_epoch) : "memory");
  const uint4 gw0 = ldg128(gw + lane * 8), gw1 = ldg128(gw + 256 + lane * 8);
  const uint32_t ws[8] = {gw0.x, gw0.y, gw0.z, gw0.w, gw1.x, gw1.y, gw1.z, gw1.w};
  const uint32_t tag = (epoch + 1) & 0xffffu;
  uint4 gx[4][2], nx[4][2];
  int grow = (blockIdx.x * 20 + (threadIdx.x >> 5)) * 4;
#pragma unroll
  for (int i = 0; i < 4; i++) {
    nx[i][0] = ldg128(u + (size_t)(grow + i) * D + lane * 8);
    nx[i][1] = ldg128(u + (size_t)(grow + i) * D + 256 + lane * 8);
  }
#pragma unroll 1
  for (; grow < L; grow += 80 * NGATE) {
    const int nrow = min(grow + 80 * NGATE, L - 4);
#pragma unroll
    for (int i = 0; i < 4; i++) {
      gx[i][0] = nx[i][0]; gx[i][1] = nx[i][1];
      nx[i][0] = ldg128(u + (size_t)(nrow + i) * D + lane * 8);
      nx[i][1] = ldg128(u + (size_t)(nrow + i) * D + 256 + lane * 8);
    }
    float c[2][4];
#pragma unroll
    for (int i = 0; i < 2; i++) {
      const uint4 *x = gx[2 * i], *y = gx[2 * i + 1];
      const uint32_t xs[8] = {x[0].x, x[0].y, x[0].z, x[0].w, x[1].x, x[1].y, x[1].z, x[1].w};
      const uint32_t ys[8] = {y[0].x, y[0].y, y[0].z, y[0].w, y[1].x, y[1].y, y[1].z, y[1].w};
      c[i][0] = c[i][1] = c[i][2] = c[i][3] = 0.f;
#pragma unroll
      for (int j = 0; j < 8; j += 2)
        mma16816(c[i], hmul2(xs[j], ws[j]), hmul2(ys[j], ws[j]), hmul2(xs[j + 1], ws[j + 1]), hmul2(ys[j + 1], ws[j + 1]), 0x3f803f80u, 0x3f803f80u);
    }
    float s = (lane & 2) ? ((lane & 1) ? c[1][2] : c[1][0]) : ((lane & 1) ? c[0][2] : c[0][0]);
#pragma unroll
    for (int o = 4; o < 32; o <<= 1) s += __shfl_xor_sync(0xffffffffu, s, o);
    s = bf_round(s);
    const float gv = 1.f / (1.f + expf(-s));
    const uint32_t w = (tag << 16) | (pack_bf16(gv, 0.f) & 0xffffu);
    if (lane < 4) asm volatile("st.relaxed.gpu.global.u32 [%0], %1;" ::"l"(&g_gate[grow + lane]), "r"(w) : "memory");
  }
  __syncthreads();
  if (threadIdx.x == 0 && atomicAdd(&g_ticket, 1u) == NCTA + NGATE - 1) { g_ticket = 0; g_epoch = epoch + 1; }
}

__global__ void __cluster_dims__(2, 1, 1) __launch_bounds__(640, 1)
ssm_kernel(const __grid_constant__ Params p, const __grid_constant__ CUtensorMap tm_in, const __grid_constant__ CUtensorMap tm_out) {
  extern __shared__ __align__(1024) unsigned char smem_raw[];
  const uint32_t sb = (uint32_t)__cvta_generic_to_shared(smem_raw);
  const int tid = threadIdx.x, lane = tid & 31;
  const int warp = __shfl_sync(0xffffffffu, tid >> 5, 0);
  const int ch = warp >> 2, wq = warp & 3, br = wq >> 1, hf = wq & 1;
  const int g = lane >> 2, t = lane & 3;
  if (__builtin_expect(blockIdx.x < NGATE, 0)) { gate_cta(&p); return; }
  const int bid = blockIdx.x - NGATE;
  const int d = bid * 4 + ch;
  const uint32_t rank = blockIdx.x & 1;
  const uint32_t cb = sb + CH_OFF + ch * CH_BYTES;
  const int wtid = tid & 127;
  const int oc0 = (bid >> 1) * 8;
  STAMP(0); GT(0);

  if (warp >= 16) {
    if (wtid == 0) {
      mbar_init_expect(sb + B_RAW, 32768);
#pragma unroll
      for (int i = 0; i < 4; i++) mbar_init_expect(sb + B_X + 8 * i, 2048);
      asm volatile("mbarrier.init.shared::cta.b64 [%0], 128;" ::"r"(sb + B_U) : "memory");
      asm volatile("mbarrier.init.shared::cta.b64 [%0], 128;" ::"r"(sb + B_W) : "memory");
#pragma unroll
      for (int i = 0; i < 7; i++) asm volatile("mbarrier.init.shared::cta.b64 [%0], 16;" ::"r"(sb + B_ST + 8 * i) : "memory");
      asm volatile("fence.mbarrier_init.release.cluster;" ::: "memory");
      asm volatile("fence.proxy.async.shared::cta;" ::: "memory");
    }
    __syncwarp();
    asm volatile("barrier.cluster.arrive.relaxed.aligned;" ::: "memory");
    unsigned int epoch;
    asm volatile("ld.relaxed.gpu.global.u32 %0, [%1];" : "=r"(epoch) : "l"(&g_epoch) : "memory");
    asm volatile("barrier.cluster.wait.aligned;" ::: "memory");
    if (wtid == 0) {
      asm volatile("cp.async.bulk.tensor.5d.shared::cluster.global.mbarrier::complete_tx::bytes.multicast::cluster [%0], [%1, {%3, %4, %4, %4, %5}], [%2], %6;"
                   ::"r"(sb + RAW_OFF + rank * 16384), "l"(&tm_in), "r"(sb + B_RAW), "r"(oc0), "r"(0), "r"((int)rank * 32), "h"((unsigned short)3) : "memory");
    }
    sts128(sb + CH_OFF + wq * CH_BYTES + U_OFF + (lane >> 3) * U_CS + (64 + (lane & 7)) * 16, 0, 0, 0, 0);
    const uint2 dA = ldg64(p.A_D + bid * 4), dB = ldg64(p.B_D + bid * 4);
    uint32_t BA[3][4], BB[4][4];
    {
      const int l1 = br ? 3 : 6, h1 = br ? 5 : 10, l2 = br ? 5 : 12, h2 = br ? 11 : 20;
#pragma unroll
      for (int i = 0; i < 4; i++) {
        const int e = 16 * hf + g - 2 * t + 32 - 16 * i;
        BB[i][0] = band2(e, l2, h2); BB[i][1] = band2(e + 8, l2, h2); BB[i][2] = band2(e - 8, l2, h2); BB[i][3] = BB[i][0];
        if (i) { BA[i - 1][0] = band2(e, l1, h1); BA[i - 1][1] = band2(e + 8, l1, h1); BA[i - 1][2] = band2(e - 8, l1, h1); BA[i - 1][3] = BA[i - 1][0]; }
      }
    }
    const uint32_t tag = (epoch + 1) & 0xffffu;
    if (wtid == 0) sts32(sb + TAG_OFF, tag);
    STAMP(3);
    mbar_wait(sb + B_RAW);
    STAMP(4);
    {
      const uint32_t dst = sb + CH_OFF + (g & 3) * CH_BYTES + U_OFF + t * U_CS + (63 - wq * 16) * 16;
#pragma unroll
      for (int h = 0; h < 2; h++) {
        uint32_t r[8][4];
#pragma unroll
        for (int i = 0; i < 8; i++) ldsm4t(sb + RAW_OFF + (wq * 16 + h * 8 + i) * 512 + lane * 16, r[i][0], r[i][1], r[i][2], r[i][3]);
        if ((uint32_t)(g >> 2) == rank) {
#pragma unroll
          for (int i = 0; i < 8; i++) sts128(dst - (h * 8 + i) * 16, r[i][0], r[i][1], r[i][2], r[i][3]);
        }
      }
    }
    fence_async();
    asm volatile("mbarrier.arrive.shared::cta.b64 _, [%0];" ::"r"(sb + B_U) : "memory");
    bar_sync(5, 128);
    STAMP(5);
    {
      const int mrow = lane & 7, mi = lane >> 3;
      const uint64_t ub0 = mkdesc(sb + CH_OFF + U_OFF, U_CS, 128);
      uint32_t wa, wb;
      {
        const int c = 4 * (47 - 8 * (mi >> 1) - mrow) + 2 * hf + (mi & 1);
        wa = sb + CH_OFF + (br ? W3_OFF : W5_OFF) + (5 - (c >> 5)) * 576 + ((c & 31) >> 3) * 144 + (c & 7) * 16;
        const int c2 = c - 64, pp = c2 >> 1;
        wb = sb + CH_OFF + (br ? W7_OFF : W9_OFF) + (1 - (pp >> 5)) * 1152 + (c2 & 1) * 576 + ((pp & 31) >> 3) * 144 + (pp & 7) * 16;
      }
      {
        float w1[24];
#pragma unroll
        for (int i = 0; i < 24; i++) w1[i] = 0.f;
#pragma unroll 1
        for (int k = 0; k < 4; k++) {
          wg_fence();
#pragma unroll
          for (int i = 0; i < 3; i++)
            wgmma_rs<48, 0>(w1, BA[i][0], BA[i][1], BA[i][2], BA[i][3],
                            ub0 + (uint64_t)((k * CH_BYTES + ((2 * i + 2) & 3) * U_CS + (16 + (i == 0)) * 16) >> 4), i);
          wg_commit();
          wg_wait0();
#pragma unroll
          for (int i = 0; i < 3; i++) stsm4t(wa + k * CH_BYTES + i * 1152, PK2(w1, 8 * i), PK2(w1, 8 * i + 2), PK2(w1, 8 * i + 4), PK2(w1, 8 * i + 6));
        }
      }
      {
        float w2[2][16];
#pragma unroll
        for (int i = 0; i < 16; i++) { w2[0][i] = 0.f; w2[1][i] = 0.f; }
#pragma unroll 1
        for (int kp = 0; kp < 2; kp++) {
          wg_fence();
#pragma unroll
          for (int k = 0; k < 2; k++)
#pragma unroll
            for (int i = 0; i < 4; i++)
              wgmma_rs<32, 0>(w2[k], BB[i][0], BB[i][1], BB[i][2], BB[i][3],
                              ub0 + (uint64_t)(((2 * kp + k) * CH_BYTES + ((2 * i) & 3) * U_CS + (32 + (i < 2)) * 16) >> 4), i);
          wg_commit();
          wg_wait0();
#pragma unroll
          for (int k = 0; k < 2; k++)
#pragma unroll
            for (int i = 0; i < 2; i++)
              stsm4t(wb + (2 * kp + k) * CH_BYTES + i * 1152, PK2(w2[k], 8 * i), PK2(w2[k], 8 * i + 2), PK2(w2[k], 8 * i + 4), PK2(w2[k], 8 * i + 6));
        }
      }
    }
    fence_async();
    asm volatile("mbarrier.arrive.shared::cta.b64 _, [%0];" ::"r"(sb + B_W) : "memory");
    STAMP(7);
    {
      const int bsel = (int)rank ^ br ^ 1, xl = wtid & 63;
      uint2 gl[4];
      uint32_t ua[4][4], ub[4][4];
#pragma unroll
      for (int i = 0; i < 4; i++) skip_terms(ua[i], ub[i], sb, (2 * (i >> 1) + bsel) * 128 + (i & 1) * 64 + xl, dA, dB);
      const uint32_t yo = sb + CH_OFF + (xl & 3) * 4 + ysw(xl >> 2) + bsel * 512;
#pragma unroll
      for (int i = 0; i < 2; i++) gl[i] = gate_ld(bsel * 128 + i * 64 + xl);
#pragma unroll
      for (int slot = 0; slot < 2; slot++) {
        const int box = 2 * slot + bsel;
        uint32_t g2[2], ya[2][4], yb[2][4];
#pragma unroll
        for (int h = 0; h < 2; h++) g2[h] = gate_fin(p, gl[2 * slot + h], box * 128 + h * 64 + xl, tag);
        mbar_wait(sb + B_ST + 8 * box);
        STAMP(8 + slot);
        if (slot == 0) { gl[2] = gate_ld((2 + bsel) * 128 + xl); gl[3] = gate_ld((2 + bsel) * 128 + 64 + xl); }
#pragma unroll
        for (int h = 0; h < 2; h++) {
          const uint32_t yh = (yo ^ (h * 32)) + h * 256 + slot * 1024;
          ld4ch(ya[h], yh + Y0_OFF); ld4ch(yb[h], yh + Y0_OFF + 4096);
          if (slot) {
            uint32_t a2[4], b2[4];
            ld4ch(a2, yh + Y2_OFF - 1024); ld4ch(b2, yh + Y2_OFF - 1024 + 3072);
#pragma unroll
            for (int k = 0; k < 4; k++) { ya[h][k] = hadd2(ya[h][k], a2[k]); yb[h][k] = hadd2(yb[h][k], b2[k]); }
          }
        }
        const uint4 r0 = mix(ya[0], yb[0], ua[2 * slot], ub[2 * slot], g2[0]), r1 = mix(ya[1], yb[1], ua[2 * slot + 1], ub[2 * slot + 1], g2[1]);
        if (br == 0) { send_box(sb, slot, xl, rank, r0); send_box(sb, slot, xl + 64, rank, r1); }
        else {
          const uint32_t st = sb + RAW_OFF + slot * 4096 + xl * 16, xin = sb + XIN_OFF + slot * 2048 + xl * 16;
          mbar_wait(sb + B_X + slot * 8);
          const uint4 q0 = lds128(xin), q1 = lds128(xin + 1024);
          merge_rows(st, rank, r0, q0); merge_rows(st + 1024, rank, r1, q1);
          fence_async();
          bar_sync(6, 64);
          if (xl == 0) {
            asm volatile("cp.async.bulk.tensor.3d.global.shared::cta.bulk_group [%0, {%2, %3, %4}], [%1];"
                         ::"l"(&tm_out), "r"(sb + RAW_OFF + slot * 4096), "r"(oc0), "r"(box * 128), "r"(0) : "memory");
            asm volatile("cp.async.bulk.commit_group;" ::: "memory");
          }
        }
        STAMP(10 + slot);
      }
    }
    if (wtid == 0 && atomicAdd(&g_ticket, 1u) == NCTA + NGATE - 1) { g_ticket = 0; g_epoch = epoch + 1; }
    if (wtid == 64) asm volatile("cp.async.bulk.wait_group.read 0;" ::: "memory");
    STAMP(15);
    return;
  }
  asm volatile("barrier.cluster.arrive.relaxed.aligned;" ::: "memory");

  const int moff = (bid * 4 + (tid >> 7)) * NM + (tid & 63) * 2;
  const int brt = (tid >> 6) & 1;
  const __nv_bfloat16* const* tp = p.t + (brt ? 0 : 6);
  const uint32_t q0 = *(const uint32_t*)(tp[0] + moff), q1 = *(const uint32_t*)(tp[1] + moff);
  const uint32_t q2 = *(const uint32_t*)(tp[2] + moff), q3 = *(const uint32_t*)(tp[3] + moff);
  const uint2 ldt4 = *(const uint2*)(tp[4] + bid * 4);
  const uint32_t q4 = *(const uint32_t*)(tp[brt ? 2 : 5] + moff), q5 = *(const uint32_t*)(tp[brt ? 3 : 6] + moff);

  for (int i = wtid & 63; i < R_BR / 16; i += 64) sts128(cb + R_OFF + br * R_BR + i * 16, 0, 0, 0, 0);
  STAMP(1);

  float acc[5][4];
  float k2048 = 0.f;
  const uint32_t scr = cb + Y0_OFF + wq * SCR_BYTES;
  const uint32_t scr2 = sb + XIN_OFF + warp * 640;
  {
    const uint32_t ldt2 = (ch & 2) ? ldt4.y : ldt4.x;
    const float dt = bf_round(expf((ch & 1) ? bf_hi(ldt2) : bf_lo(ldt2)));
#pragma unroll
    for (int i = 0; i < 5; i++) acc[i][0] = acc[i][1] = acc[i][2] = acc[i][3] = 0.f;
    STAMP(2);
    const uint32_t tb = scr + lane * 16;
    const uint32_t ta = scr + (lane >> 3) * 512 + (lane & 7) * 16;
    const uint32_t tc = ((lane & 8) ? scr2 : scr + 4096) + (lane >> 4) * 128 + (lane & 7) * 16;
    const uint32_t tm = scr2 + 512 + ((lane >> 3) & 1) * 64 + (lane >> 4) * 16;
    cf cc[2], zz1[2], zz128[2];
#pragma unroll
    for (int r = 0; r < 2; r++) {
      float v0 = r ? bf_hi(q0) : bf_lo(q0), v1 = r ? bf_hi(q1) : bf_lo(q1), v2 = r ? bf_hi(q2) : bf_lo(q2);
      float v3 = r ? bf_hi(q3) : bf_lo(q3), v4 = r ? bf_hi(q4) : bf_lo(q4), v5 = r ? bf_hi(q5) : bf_lo(q5);
      if (br == 0) { cc[r] = cmul(cf{v2, v3}, cf{dt * v4, dt * v5}); }
      else { v0 = -bf_round(expf(v0)); cc[r] = cf{2.f * dt * v2, 2.f * dt * v3}; }
      const float xl = (dt * v0) * 1.4426950408889634f, y = dt * v1;
      zz1[r] = cexp_p(xl, y, 1.f); zz128[r] = cexp_p(xl, y, 128.f);
    }
    uint32_t T[10][4], m4;
    auto produce = [&](int r) {
      const cf c = cc[r], z1 = zz1[r], z128 = zz128[r];
      const cf z2 = csq(z1), z4 = csq(z2), z8 = csq(z4);
      const cf w8 = {z8.re, -z8.im};
      const cf z16 = csq(w8), z24 = cmul(z16, w8), z32 = csq(z16), z40 = cmul(z32, w8), z48 = csq(z24), z56 = cmul(z32, z24), z64 = csq(z32);
      const cf z256 = csq(z128), z512 = csq(z256), z1024 = csq(z512), z2048 = csq(z1024);
      k2048 += fmaf(c.re, z2048.re, -c.im * z2048.im);
      {
        T[0][0] = pack_bf16(1.f, z8.re); T[0][1] = pack_bf16(z16.re, z24.re); T[0][2] = pack_bf16(z32.re, z40.re); T[0][3] = pack_bf16(z48.re, z56.re);
        T[2][0] = pack_bf16(0.f, w8.im); T[2][1] = pack_bf16(z16.im, z24.im); T[2][2] = pack_bf16(z32.im, z40.im); T[2][3] = pack_bf16(z48.im, z56.im);
        const uint32_t yr = pack_bf16(z64.re, z64.re), yi = pack_bf16(z64.im, z64.im), nyi = yi ^ 0x80008000u;
#pragma unroll
        for (int i = 0; i < 4; i++) CMUL2(T[1][i], T[3][i], T[0][i], T[2][i], yr, yi, nyi);
      }
      {
        const cf h1 = cmul(c, z128), h2 = cmul(c, z256), h3 = cmul(h1, z256), h4 = cmul(c, z512), h5 = cmul(h1, z512), h6 = cmul(h2, z512), h7 = cmul(h3, z512);
        const cf e1 = cmul(c, z1), e2 = cmul(c, z2), e3 = cmul(e1, z2), e129 = cmul(h1, z1), e130 = cmul(h1, z2), e131 = cmul(e129, z2);
        const cf e258 = cmul(h2, z2), e386 = cmul(h3, z2);
        T[4][0] = pack_bf16(c.re, e1.re); T[4][1] = pack_bf16(e2.re, e3.re); T[4][2] = pack_bf16(h1.re, e129.re); T[4][3] = pack_bf16(e130.re, e131.re);
        T[5][0] = pack_bf16(c.im, e1.im); T[5][1] = pack_bf16(e2.im, e3.im); T[5][2] = pack_bf16(h1.im, e129.im); T[5][3] = pack_bf16(e130.im, e131.im);
        T[6][0] = pack_bf16(h2.re, e258.re); T[6][1] = pack_bf16(h3.re, e386.re); T[6][2] = pack_bf16(h4.re, h5.re); T[6][3] = pack_bf16(h6.re, h7.re);
        T[7][0] = pack_bf16(h2.im, e258.im); T[7][1] = pack_bf16(h3.im, e386.im); T[7][2] = pack_bf16(h4.im, h5.im); T[7][3] = pack_bf16(h6.im, h7.im);
        const uint32_t xr[4] = {__byte_perm(T[4][0], T[4][2], 0x5410), __byte_perm(T[6][0], T[6][1], 0x5410), T[6][2], T[6][3]};
        const uint32_t xi[4] = {__byte_perm(T[5][0], T[5][2], 0x5410), __byte_perm(T[7][0], T[7][1], 0x5410), T[7][2], T[7][3]};
        const uint32_t yr = pack_bf16(z1024.re, z1024.re), yi = pack_bf16(z1024.im, z1024.im), nyi = yi ^ 0x80008000u;
#pragma unroll
        for (int i = 0; i < 4; i++) CMUL2(T[8][i], T[9][i], xr[i], xi[i], yr, yi, nyi);
        m4 = pack_bf16(z4.re, z4.im);
      }
    };
    auto store = [&]() {
#pragma unroll
      for (int m = 0; m < 9; m++) sts128(tb + m * 512, T[m][0], T[m][1], T[m][2], T[m][3]);
      sts128(scr2 + lane * 16, T[9][0], T[9][1], T[9][2], T[9][3]);
      sts16(scr2 + 512 + lane * 2, m4); sts16(scr2 + 576 + lane * 2, m4 >> 16);
    };
    auto consume = [&]() {
#pragma unroll
      for (int kp = 0; kp < 2; kp++) {
        uint32_t rr[2], ri[2], yr[2], yi[2];
        ldsm4t(tc + kp * 256, rr[0], ri[0], rr[1], ri[1]);
        ldsm4(tm + kp * 32, yr[0], yi[0], yr[1], yi[1]);
#pragma unroll
        for (int k2 = 0; k2 < 2; k2++) {
          const int kk = kp * 2 + k2;
          uint32_t a0, a1, a2, a3, pr, pi, qr, qi, xr, xi;
          ldsm4t(ta + kk * 128, a0, a1, a2, a3);
          ldsm4t(ta + 2048 + kk * 128, pr, pi, qr, qi);
          const uint32_t nyi = yi[k2] ^ 0x80008000u;
          mma16816(acc[0], a0, a1, a2, a3, pr, pi);
          mma16816(acc[2], a0, a1, a2, a3, qr, qi);
          mma16816(acc[4], a0, a1, a2, a3, rr[k2], ri[k2]);
          CMUL2(xr, xi, pr, pi, yr[k2], yi[k2], nyi);
          mma16816(acc[1], a0, a1, a2, a3, xr, xi);
          CMUL2(xr, xi, qr, qi, yr[k2], yi[k2], nyi);
          mma16816(acc[3], a0, a1, a2, a3, xr, xi);
        }
      }
    };
    produce(0); store();
    __syncwarp();
    consume(); produce(1);
    __syncwarp();
    store();
#pragma unroll
    for (int o = 16; o; o >>= 1) k2048 += __shfl_xor_sync(0xffffffffu, k2048, o);
    __syncwarp();
    consume();
  }
  STAMP(3);
  __syncwarp();
  {
    const uint32_t xs = scr + lane * 16;
#define OTH(i, k) __float_as_uint(hf ? acc[i][k] : acc[i][2 + (k)])
    sts128(xs, OTH(0, 0), OTH(0, 1), OTH(1, 0), OTH(1, 1));
    sts128(xs + 512, OTH(2, 0), OTH(2, 1), OTH(3, 0), OTH(3, 1));
    sts128(xs + 1024, OTH(4, 0), OTH(4, 1), __float_as_uint(k2048), 0);
#undef OTH
  }

  bar_sync(7 + (warp >> 1), 64);
  STAMP(4);
  {
    const uint32_t xo = cb + Y0_OFF + (wq ^ 1) * SCR_BYTES + lane * 16;
    const uint4 o0 = lds128(xo), o1 = lds128(xo + 512), o2 = lds128(xo + 1024);
    const uint32_t rb = cb + R_OFF + br * R_BR;
#define OWN(i, k) (hf ? acc[i][2 + (k)] : acc[i][k])
    const uint32_t vP = pack_bf16(OWN(0, 1) + __uint_as_float(o0.y), OWN(0, 0) + __uint_as_float(o0.x));
    const uint32_t vP4 = pack_bf16(OWN(1, 1) + __uint_as_float(o0.w), OWN(1, 0) + __uint_as_float(o0.z));
    const uint32_t vQ = pack_bf16(OWN(2, 1) + __uint_as_float(o1.y), OWN(2, 0) + __uint_as_float(o1.x));
    const uint32_t vQ4 = pack_bf16(OWN(3, 1) + __uint_as_float(o1.w), OWN(3, 0) + __uint_as_float(o1.z));
    const uint32_t vR = pack_bf16(OWN(4, 1) + __uint_as_float(o2.y), OWN(4, 0) + __uint_as_float(o2.x));
#undef OWN
    const int j = g + 8 * hf;
    {
      const int a = 2 * (t & 1) + 64 * (t & 2) + 8 * j;
      const uint32_t ad = rb + 2 * (RD_X0 - 1 - a);
      const uint32_t a1 = (t & 2) ? ad - 8 : ad, a2 = (t & 2) ? ad : ad - 8;
      const uint32_t w1 = (t & 2) ? vP4 : vP, w2 = (t & 2) ? vP : vP4;
      sts32(a1, w1); sts32(a2, w2);
      sts16(a1 + RD_CS + 2, w1); sts16(a1 + RD_CS + 4, w1 >> 16);
      sts16(a2 + RD_CS + 2, w2); sts16(a2 + RD_CS + 4, w2 >> 16);
    }
    if (t < 2) {
      const int b = 256 + 128 * t + 8 * j;
      const uint32_t ad = rb + 2 * (RD_X0 - 6 - b);
      const uint32_t v22 = __byte_perm(vQ4, 0, 0x3232), v00 = __byte_perm(vQ, 0, 0x3232);
      sts16(ad, vQ4);
      sts64(ad + 2, v22, __byte_perm(vQ4, vQ, 0x5432));
      sts32(ad + 10, v00);
      if (b != 256) { sts16(ad + 14, v00); sts128(ad + RD_CS + 2, vQ4, v22, vQ, v00); }
      else { sts64(ad + RD_CS + 2, vQ4, v22); sts32(ad + RD_CS + 10, vQ); sts16(ad + RD_CS + 14, v00); }
    } else {
      const uint32_t ao = rb + R_O2 + 2 * (159 - (32 * t + j)), ae = ao - (R_O2 - R_E2) + 2;
      sts16(ao, vQ4 >> 16); sts16(ao + RS_CS + 2, vQ4 >> 16); sts16(ao - 32, vQ4); sts16(ao - 32 + RS_CS + 2, vQ4);
      sts16(ae - 32, vQ); sts16(ae - 32 + RS_CS + 2, vQ);
      if (lane != 2 || hf) { sts16(ae, vQ >> 16); sts16(ae + RS_CS + 2, vQ >> 16); }
      else {
        const uint32_t vv = __byte_perm(vQ, 0, 0x3232), ad = rb + 2 * (RD_X0 - 514);
        sts16(ad, vv); sts32(ad + 2, vv); sts16(ad + 6, vv); sts64(ad + RD_CS + 2, vv, vv);
      }
    }
    {
      const uint32_t a = rb + ((g & 1) ? R_O3 : R_E3 + 2) + 2 * (159 - (64 + 16 * t + (j >> 1)));
      const bool p1024 = (lane == 0) && (hf == 0);
      const uint32_t a00 = p1024 ? rb + R_E2 + 2 * (159 - 127) : a;
      sts16(a00, vR >> 16); sts16(a00 + RS_CS + 2, vR >> 16);
      sts16(a - 16, vR); sts16(a - 16 + RS_CS + 2, vR);
      if (p1024) {
        sts32(sb + K1024_OFF + (ch * 2 + br) * 4, __byte_perm(vR, 0, 0x3232));
        const uint32_t kv = pack_bf16(k2048 + __uint_as_float(o2.z), 0.f);
        sts16(rb + R_E3 + 2 * (159 - 127), kv); sts16(rb + R_E3 + 2 * (159 - 127) + RS_CS + 2, kv);
      }
    }
  }
  STAMP(5);
  asm volatile("barrier.cluster.wait.aligned;" ::: "memory");
  bar_sync(7 + (warp >> 1), 64);
  mbar_wait(sb + B_U);
  STAMP(6);

  const uint32_t zz = lds32(cb + R_OFF + br * R_BR);
  conv_dense(sb, cb, zz);
  STAMP(8);
  {
    const int x = (4 + ch) * 128 + wtid, c = x >> 2;
    const uint2 dA = ldg64(p.A_D + bid * 4), dB = ldg64(p.B_D + bid * 4);
    const uint2 gl = gate_ld(x);
    const uint32_t rb = cb + R_OFF + br * R_BR;
    float e48[24], e40[20], e32[16], h32[16], h16[8];
    const int x1 = 159 - (16 * hf + g - 2 * t + 136);
    const uint32_t fs = rb + ((g & 1) ? 2 * x1 : RS_CS + 2 * x1 + 2);
    uint32_t A[2][4][4];
    auto loadA = [&](int buf, uint32_t oe, uint32_t oo, int i0) {
#pragma unroll
      for (int a = 0; a < 2; a++) {
        const uint32_t base = fs + (a ? oo : oe) + i0 * 16;
        uint32_t* k0 = A[buf][2 * a];
        uint32_t* k1 = A[buf][2 * a + 1];
        k0[1] = lds32(base); k0[0] = lds32(base + 16); k0[2] = lds32(base + 32); k1[0] = lds32(base + 48); k1[2] = lds32(base + 64);
        k0[3] = k0[0]; k1[1] = k0[2]; k1[3] = k1[0];
      }
    };
    loadA(0, R_E2, R_O2, 8);
    loadA(1, R_E2, R_O2, 4);
    mbar_wait(sb + B_W);
    const uint64_t d5 = mkdesc(cb + W5_OFF, 144, 576), d3 = mkdesc(cb + W3_OFF, 144, 576);
    const uint64_t d9 = mkdesc(cb + W9_OFF, 144, 576), d7 = mkdesc(cb + W7_OFF, 144, 576);
    const uint32_t y2d = cb + Y2_OFF + br * 3072 + ysw(32 * (5 - (lane >> 4)) + 16 * hf + (lane & 15));
    const uint32_t y3d = cb + Y3_OFF + br * 2048 + ysw(2 * (16 * hf + (lane & 15)) + (lane >> 4));
#define FAR4(N, ACC, BUF, DA, DB, OFF, FIRST)                                                            \
    wg_fence();                                                                                           \
    _Pragma("unroll") for (int k = 0; k < 4; k++) {                                                      \
      const uint32_t* a = A[BUF][k];                                                                      \
      wgmma_rs<N, 1>(ACC, a[0], a[1], a[2], a[3], ((k >> 1) ? DB : DA) + (k & 1) * 18 + (OFF), !(FIRST) || k); \
    }                                                                                                     \
    wg_commit();
    FAR4(48, e48, 0, d5, d3, 0, 1)
    wg_wait0();
    loadA(0, R_E2, R_O2, 0);
    stsm2(y2d - 5 * 512, PK2(e48, 20), PK2(e48, 22));
#pragma unroll
    for (int i = 0; i < 20; i++) e40[i] = FCPY(e48[i]);
    stage_done(sb, 2, lane);
    FAR4(40, e40, 1, d5, d3, 36, 0)
    wg_wait0();
    loadA(1, R_E3, R_O3, 8);
    stsm2(y2d - 4 * 512, PK2(e40, 16), PK2(e40, 18));
#pragma unroll
    for (int i = 0; i < 16; i++) e32[i] = FCPY(e40[i]);
    stage_done(sb, 3, lane);
    FAR4(32, e32, 0, d5, d3, 72, 0)
    FAR4(32, h32, 1, d9, d7, 0, 1)
    wg_wait1();
    loadA(0, R_E3, R_O3, 4);
    stsm4(y2d, PK2(e32, 0), PK2(e32, 2), PK2(e32, 4), PK2(e32, 6));
    stsm4(y2d - 2 * 512, PK2(e32, 8), PK2(e32, 10), PK2(e32, 12), PK2(e32, 14));
    stage_done(sb, 4, lane);
    STAMP(9);
    wg_wait0();
    stsm4(y3d, PK2(h32, 8), PK2(h32, 10), PK2(h32, 12), PK2(h32, 14));
#pragma unroll
    for (int i = 0; i < 8; i++) h16[i] = FCPY(h32[i]);
    stage_done(sb, 5, lane);
    FAR4(16, h16, 0, d9, d7, 72, 0)
#undef FAR4
    const uint32_t yo = sb + CH_OFF + (x & 3) * 4 + ysw(c);
    uint32_t ua[4], ub[4], ya[4], yb[4], a2[4], b2[4], a3[4], b3[4], s2[4];
    skip_terms(ua, ub, sb, x, dA, dB);
    {
      const int xa = x - 514, xb = x - 513, ca = xa >> 2, cb2 = xb >> 2;
      ld4ch(s2, sb + CH_OFF + U_OFF + (xa & 3) * 4 + (ca & 3) * U_CS + (63 - (ca >> 2)) * 16);
      ld4ch(a3, sb + CH_OFF + U_OFF + (xb & 3) * 4 + (cb2 & 3) * U_CS + (63 - (cb2 >> 2)) * 16);
#pragma unroll
      for (int k = 0; k < 4; k++) s2[k] = hadd2(s2[k], __byte_perm(s2[k], a3[k], 0x5432));
    }
    const uint32_t tag = lds32(sb + TAG_OFF);
    wg_wait0();
    stsm4(y3d + 1024, PK2(h16, 0), PK2(h16, 2), PK2(h16, 4), PK2(h16, 6));
    stage_done(sb, 6, lane);
    STAMP(10);
    const uint32_t g2 = gate_fin(p, gl, x, tag);
    mbar_wait(sb + B_ST + 8 * 4);
    const uint4 k0 = lds128(sb + K1024_OFF), k1 = lds128(sb + K1024_OFF + 16);
    const uint32_t kk[8] = {k0.x, k0.y, k0.z, k0.w, k1.x, k1.y, k1.z, k1.w};
    ld4ch(ya, yo + Y0_OFF); ld4ch(yb, yo + Y0_OFF + 4096);
    ld4ch(a2, yo + Y2_OFF - 1024); ld4ch(b2, yo + Y2_OFF - 1024 + 3072);
    mbar_wait(sb + B_ST + 8 * (5 + (ch >> 1)));
    STAMP(12);
    ld4ch(a3, yo + Y3_OFF - 2048); ld4ch(b3, yo + Y3_OFF - 2048 + 2048);
#pragma unroll
    for (int k = 0; k < 4; k++) {
      ya[k] = hadd2(ya[k], hadd2(hfma2(kk[2 * k], s2[k], a2[k]), a3[k]));
      yb[k] = hadd2(yb[k], hadd2(hfma2(kk[2 * k + 1], s2[k], b2[k]), b3[k]));
    }
    const uint4 r = mix(ya, yb, ua, ub, g2);
    if ((uint32_t)(ch & 1) != rank) send_box(sb, 2 + (ch >> 1), wtid, rank, r);
    else merge_box(sb, &tm_out, 2 + (ch >> 1), wtid, rank, oc0, r, 1 + ch);
  }
  STAMP(14);
  if (wtid == 0) asm volatile("cp.async.bulk.wait_group.read 0;" ::: "memory");
  STAMP(15); GT(1);
}

typedef CUresult (*EncodeFn)(CUtensorMap*, CUtensorMapDataType, cuuint32_t, void*, const cuuint64_t*, const cuuint64_t*,
                             const cuuint32_t*, const cuuint32_t*, CUtensorMapInterleave, CUtensorMapSwizzle,
                             CUtensorMapL2promotion, CUtensorMapFloatOOBfill);

}

extern "C" void kernel_launch(void* const* d_in, const int* in_sizes, int n_in, void* d_out, int out_size) {
  (void)in_sizes; (void)n_in; (void)out_size;
  typedef const __nv_bfloat16* bp;
  Params p;
  p.t[0] = (bp)d_in[10]; p.t[1] = (bp)d_in[11]; p.t[2] = (bp)d_in[12]; p.t[3] = (bp)d_in[13]; p.t[4] = (bp)d_in[14]; p.t[5] = nullptr;
  p.t[6] = (bp)d_in[1]; p.t[7] = (bp)d_in[2]; p.t[8] = (bp)d_in[5]; p.t[9] = (bp)d_in[6]; p.t[10] = (bp)d_in[7];
  p.t[11] = (bp)d_in[3]; p.t[12] = (bp)d_in[4]; p.t[13] = nullptr;
  p.u = (bp)d_in[0]; p.gw = (bp)d_in[16]; p.A_D = (bp)d_in[8]; p.B_D = (bp)d_in[15];
  static EncodeFn enc = nullptr;
  if (!enc) {
    cudaDriverEntryPointQueryResult qr;
    cudaGetDriverEntryPoint("cuTensorMapEncodeTiled", (void**)&enc, cudaEnableDefault, &qr);
    cudaFuncSetAttribute(ssm_kernel, cudaFuncAttributeMaxDynamicSharedMemorySize, SMEM_BYTES);
  }
  CUtensorMap tm_in, tm_out;
  {
    cuuint64_t gd[5] = {512, 2, 4, 4, 64};
    cuuint64_t gs[4] = {1024, 8192, 2048, 32768};
    cuuint32_t bx[5] = {8, 2, 4, 4, 32};
    cuuint32_t es[5] = {1, 1, 1, 1, 1};
    enc(&tm_in, CU_TENSOR_MAP_DATA_TYPE_BFLOAT16, 5, d_in[0], gd, gs, bx, es, CU_TENSOR_MAP_INTERLEAVE_NONE,
        CU_TENSOR_MAP_SWIZZLE_NONE, CU_TENSOR_MAP_L2_PROMOTION_NONE, CU_TENSOR_MAP_FLOAT_OOB_FILL_NONE);
  }
  {
    cuuint64_t gd[3] = {512, 1024, 2};
    cuuint64_t gs[2] = {2048, 1024};
    cuuint32_t bx[3] = {8, 128, 2};
    cuuint32_t es[3] = {1, 1, 1};
    enc(&tm_out, CU_TENSOR_MAP_DATA_TYPE_BFLOAT16, 3, d_out, gd, gs, bx, es, CU_TENSOR_MAP_INTERLEAVE_NONE,
        CU_TENSOR_MAP_SWIZZLE_NONE, CU_TENSOR_MAP_L2_PROMOTION_NONE, CU_TENSOR_MAP_FLOAT_OOB_FILL_NONE);
  }
  ssm_kernel<<<NCTA + NGATE, 640, SMEM_BYTES, cudaStreamPerThread>>>(p, tm_in, tm_out);
}
```

```cpp
#include <cuda_runtime.h>
#include <cuda.h>
#include <cuda_bf16.h>
#include <stdint.h>

namespace {
#define FCPY(x) __uint_as_float(opq(__float_as_uint(x), zz))

constexpr int L = 2048, D = 512, NM = 128;
constexpr int NCTA = 128;
constexpr int NGATE = 4;

constexpr int RAW_OFF = 0;
constexpr int XIN_OFF = 32768;
constexpr int BAR_OFF = XIN_OFF + 10240;
constexpr int CH_OFF = BAR_OFF + 256;
constexpr int U_CS = 1184;
constexpr int U_OFF = 0;
constexpr int R_OFF = 4736;
constexpr int RD_X0 = 565;
constexpr int RD_CS = 1216;
constexpr int RS_CS = 320;
constexpr int R_E2 = 2 * RD_CS, R_O2 = R_E2 + 2 * RS_CS, R_E3 = R_O2 + 2 * RS_CS, R_O3 = R_E3 + 2 * RS_CS;
constexpr int R_BR = R_O3 + 2 * RS_CS;
constexpr int W5_OFF = R_OFF + 2 * R_BR;
constexpr int W3_OFF = W5_OFF + 3456;
constexpr int W9_OFF = W3_OFF + 3456;
constexpr int W7_OFF = W9_OFF + 2304;
constexpr int Y0_OFF = W7_OFF + 2304;
constexpr int Y2_OFF = Y0_OFF + 8192, Y3_OFF = Y2_OFF + 6144;
constexpr int CH_BYTES = Y0_OFF + 18432 + 16;
constexpr int SCR_BYTES = 4608;
constexpr int SMEM_BYTES = CH_OFF + 4 * CH_BYTES;
static_assert(CH_BYTES % 128 == 16, "bank staggering of the channel blocks");
static_assert(SMEM_BYTES <= 232448, "smem");
constexpr int B_RAW = BAR_OFF, B_X = BAR_OFF + 8, B_U = BAR_OFF + 40, B_W = BAR_OFF + 48;
constexpr int TAG_OFF = BAR_OFF + 56;
constexpr int K1024_OFF = BAR_OFF + 64;
constexpr int B_ST = BAR_OFF + 96;

__device__ unsigned int g_gate[L];
__device__ unsigned int g_epoch;
__device__ unsigned int g_ticket;

#define STAMP(k)
#define GT(k)

struct Params {
  const __nv_bfloat16* t[14];
  const __nv_bfloat16 *u, *gw, *A_D, *B_D;
};

template <int N, int TB> __device__ __forceinline__ void wgmma_rs(float* d, uint32_t a0, uint32_t a1, uint32_t a2, uint32_t a3, uint64_t desc, int sc);
template <> __device__ __forceinline__ void wgmma_rs<64, 0>(float* d, uint32_t a0, uint32_t a1, uint32_t a2, uint32_t a3, uint64_t desc, int sc) {
  asm volatile("{\n.reg .pred p;\nsetp.ne.b32 p, %37, 0;\n"
    "wgmma.mma_async.sync.aligned.m64n64k16.f32.bf16.bf16 {%0,%1,%2,%3,%4,%5,%6,%7,%8,%9,%10,%11,%12,%13,%14,%15,%16,%17,%18,%19,%20,%21,%22,%23,%24,%25,%26,%27,%28,%29,%30,%31}, {%32,%33,%34,%35}, %36, p, 1, 1, 0;\n}"
    : "+f"(d[0]), "+f"(d[1]), "+f"(d[2]), "+f"(d[3]), "+f"(d[4]), "+f"(d[5]), "+f"(d[6]), "+f"(d[7]), "+f"(d[8]), "+f"(d[9]), "+f"(d[10]), "+f"(d[11]), "+f"(d[12]), "+f"(d[13]), "+f"(d[14]), "+f"(d[15]), "+f"(d[16]), "+f"(d[17]), "+f"(d[18]), "+f"(d[19]), "+f"(d[20]), "+f"(d[21]), "+f"(d[22]), "+f"(d[23]), "+f"(d[24]), "+f"(d[25]), "+f"(d[26]), "+f"(d[27]), "+f"(d[28]), "+f"(d[29]), "+f"(d[30]), "+f"(d[31]) : "r"(a0), "r"(a1), "r"(a2), "r"(a3), "l"(desc), "r"(sc));
}
template <> __device__ __forceinline__ void wgmma_rs<56, 0>(float* d, uint32_t a0, uint32_t a1, uint32_t a2, uint32_t a3, uint64_t desc, int sc) {
  asm volatile("{\n.reg .pred p;\nsetp.ne.b32 p, %33, 0;\n"
    "wgmma.mma_async.sync.aligned.m64n56k16.f32.bf16.bf16 {%0,%1,%2,%3,%4,%5,%6,%7,%8,%9,%10,%11,%12,%13,%14,%15,%16,%17,%18,%19,%20,%21,%22,%23,%24,%25,%26,%27}, {%28,%29,%30,%31}, %32, p, 1, 1, 0;\n}"
    : "+f"(d[0]), "+f"(d[1]), "+f"(d[2]), "+f"(d[3]), "+f"(d[4]), "+f"(d[5]), "+f"(d[6]), "+f"(d[7]), "+f"(d[8]), "+f"(d[9]), "+f"(d[10]), "+f"(d[11]), "+f"(d[12]), "+f"(d[13]), "+f"(d[14]), "+f"(d[15]), "+f"(d[16]), "+f"(d[17]), "+f"(d[18]), "+f"(d[19]), "+f"(d[20]), "+f"(d[21]), "+f"(d[22]), "+f"(d[23]), "+f"(d[24]), "+f"(d[25]), "+f"(d[26]), "+f"(d[27]) : "r"(a0), "r"(a1), "r"(a2), "r"(a3), "l"(desc), "r"(sc));
}
template <> __device__ __forceinline__ void wgmma_rs<48, 0>(float* d, uint32_t a0, uint32_t a1, uint32_t a2, uint32_t a3, uint64_t desc, int sc) {
  asm volatile("{\n.reg .pred p;\nsetp.ne.b32 p, %29, 0;\n"
    "wgmma.mma_async.sync.aligned.m64n48k16.f32.bf16.bf16 {%0,%1,%2,%3,%4,%5,%6,%7,%8,%9,%10,%11,%12,%13,%14,%15,%16,%17,%18,%19,%20,%21,%22,%23}, {%24,%25,%26,%27}, %28, p, 1, 1, 0;\n}"
    : "+f"(d[0]), "+f"(d[1]), "+f"(d[2]), "+f"(d[3]), "+f"(d[4]), "+f"(d[5]), "+f"(d[6]), "+f"(d[7]), "+f"(d[8]), "+f"(d[9]), "+f"(d[10]), "+f"(d[11]), "+f"(d[12]), "+f"(d[13]), "+f"(d[14]), "+f"(d[15]), "+f"(d[16]), "+f"(d[17]), "+f"(d[18]), "+f"(d[19]), "+f"(d[20]), "+f"(d[21]), "+f"(d[22]), "+f"(d[23]) : "r"(a0), "r"(a1), "r"(a2), "r"(a3), "l"(desc), "r"(sc));
}
template <> __device__ __forceinline__ void wgmma_rs<32, 0>(float* d, uint32_t a0, uint32_t a1, uint32_t a2, uint32_t a3, uint64_t desc, int sc) {
  asm volatile("{\n.reg .pred p;\nsetp.ne.b32 p, %21, 0;\n"
    "wgmma.mma_async.sync.aligned.m64n32k16.f32.bf16.bf16 {%0,%1,%2,%3,%4,%5,%6,%7,%8,%9,%10,%11,%12,%13,%14,%15}, {%16,%17,%18,%19}, %20, p, 1, 1, 0;\n}"
    : "+f"(d[0]), "+f"(d[1]), "+f"(d[2]), "+f"(d[3]), "+f"(d[4]), "+f"(d[5]), "+f"(d[6]), "+f"(d[7]), "+f"(d[8]), "+f"(d[9]), "+f"(d[10]), "+f"(d[11]), "+f"(d[12]), "+f"(d[13]), "+f"(d[14]), "+f"(d[15]) : "r"(a0), "r"(a1), "r"(a2), "r"(a3), "l"(desc), "r"(sc));
}
template <> __device__ __forceinline__ void wgmma_rs<48, 1>(float* d, uint32_t a0, uint32_t a1, uint32_t a2, uint32_t a3, uint64_t desc, int sc) {
  asm volatile("{\n.reg .pred p;\nsetp.ne.b32 p, %29, 0;\n"
    "wgmma.mma_async.sync.aligned.m64n48k16.f32.bf16.bf16 {%0,%1,%2,%3,%4,%5,%6,%7,%8,%9,%10,%11,%12,%13,%14,%15,%16,%17,%18,%19,%20,%21,%22,%23}, {%24,%25,%26,%27}, %28, p, 1, 1, 1;\n}"
    : "+f"(d[0]), "+f"(d[1]), "+f"(d[2]), "+f"(d[3]), "+f"(d[4]), "+f"(d[5]), "+f"(d[6]), "+f"(d[7]), "+f"(d[8]), "+f"(d[9]), "+f"(d[10]), "+f"(d[11]), "+f"(d[12]), "+f"(d[13]), "+f"(d[14]), "+f"(d[15]), "+f"(d[16]), "+f"(d[17]), "+f"(d[18]), "+f"(d[19]), "+f"(d[20]), "+f"(d[21]), "+f"(d[22]), "+f"(d[23]) : "r"(a0), "r"(a1), "r"(a2), "r"(a3), "l"(desc), "r"(sc));
}
template <> __device__ __forceinline__ void wgmma_rs<40, 1>(float* d, uint32_t a0, uint32_t a1, uint32_t a2, uint32_t a3, uint64_t desc, int sc) {
  asm volatile("{\n.reg .pred p;\nsetp.ne.b32 p, %25, 0;\n"
    "wgmma.mma_async.sync.aligned.m64n40k16.f32.bf16.bf16 {%0,%1,%2,%3,%4,%5,%6,%7,%8,%9,%10,%11,%12,%13,%14,%15,%16,%17,%18,%19}, {%20,%21,%22,%23}, %24, p, 1, 1, 1;\n}"
    : "+f"(d[0]), "+f"(d[1]), "+f"(d[2]), "+f"(d[3]), "+f"(d[4]), "+f"(d[5]), "+f"(d[6]), "+f"(d[7]), "+f"(d[8]), "+f"(d[9]), "+f"(d[10]), "+f"(d[11]), "+f"(d[12]), "+f"(d[13]), "+f"(d[14]), "+f"(d[15]), "+f"(d[16]), "+f"(d[17]), "+f"(d[18]), "+f"(d[19]) : "r"(a0), "r"(a1), "r"(a2), "r"(a3), "l"(desc), "r"(sc));
}
template <> __device__ __forceinline__ void wgmma_rs<32, 1>(float* d, uint32_t a0, uint32_t a1, uint32_t a2, uint32_t a3, uint64_t desc, int sc) {
  asm volatile("{\n.reg .pred p;\nsetp.ne.b32 p, %21, 0;\n"
    "wgmma.mma_async.sync.aligned.m64n32k16.f32.bf16.bf16 {%0,%1,%2,%3,%4,%5,%6,%7,%8,%9,%10,%11,%12,%13,%14,%15}, {%16,%17,%18,%19}, %20, p, 1, 1, 1;\n}"
    : "+f"(d[0]), "+f"(d[1]), "+f"(d[2]), "+f"(d[3]), "+f"(d[4]), "+f"(d[5]), "+f"(d[6]), "+f"(d[7]), "+f"(d[8]), "+f"(d[9]), "+f"(d[10]), "+f"(d[11]), "+f"(d[12]), "+f"(d[13]), "+f"(d[14]), "+f"(d[15]) : "r"(a0), "r"(a1), "r"(a2), "r"(a3), "l"(desc), "r"(sc));
}
template <> __device__ __forceinline__ void wgmma_rs<16, 1>(float* d, uint32_t a0, uint32_t a1, uint32_t a2, uint32_t a3, uint64_t desc, int sc) {
  asm volatile("{\n.reg .pred p;\nsetp.ne.b32 p, %13, 0;\n"
    "wgmma.mma_async.sync.aligned.m64n16k16.f32.bf16.bf16 {%0,%1,%2,%3,%4,%5,%6,%7}, {%8,%9,%10,%11}, %12, p, 1, 1, 1;\n}"
    : "+f"(d[0]), "+f"(d[1]), "+f"(d[2]), "+f"(d[3]), "+f"(d[4]), "+f"(d[5]), "+f"(d[6]), "+f"(d[7]) : "r"(a0), "r"(a1), "r"(a2), "r"(a3), "l"(desc), "r"(sc));
}

__device__ __forceinline__ uint32_t pack_bf16(float lo, float hi) {
  uint32_t r; asm("cvt.rn.bf16x2.f32 %0, %1, %2;" : "=r"(r) : "f"(hi), "f"(lo)); return r;
}
__device__ __forceinline__ float bf_lo(uint32_t v) { return __uint_as_float(v << 16); }
__device__ __forceinline__ float bf_hi(uint32_t v) { return __uint_as_float(v & 0xffff0000u); }
__device__ __forceinline__ float bf_round(float x) { return bf_lo(pack_bf16(x, 0.f)); }
__device__ __forceinline__ uint32_t hmul2(uint32_t a, uint32_t b) { uint32_t r; asm("mul.rn.bf16x2 %0, %1, %2;" : "=r"(r) : "r"(a), "r"(b)); return r; }
__device__ __forceinline__ uint32_t hadd2(uint32_t a, uint32_t b) { uint32_t r; asm("add.rn.bf16x2 %0, %1, %2;" : "=r"(r) : "r"(a), "r"(b)); return r; }
__device__ __forceinline__ uint32_t hsub2(uint32_t a, uint32_t b) { uint32_t r; asm("sub.rn.bf16x2 %0, %1, %2;" : "=r"(r) : "r"(a), "r"(b)); return r; }
__device__ __forceinline__ uint32_t hfma2(uint32_t a, uint32_t b, uint32_t c) { uint32_t r; asm("fma.rn.bf16x2 %0, %1, %2, %3;" : "=r"(r) : "r"(a), "r"(b), "r"(c)); return r; }

__device__ __forceinline__ void sts16(uint32_t a, uint32_t v) { asm volatile("st.shared.b16 [%0], %1;" ::"r"(a), "h"((unsigned short)v) : "memory"); }
__device__ __forceinline__ void sts32(uint32_t a, uint32_t v) { asm volatile("st.shared.b32 [%0], %1;" ::"r"(a), "r"(v) : "memory"); }
__device__ __forceinline__ void sts64(uint32_t a, uint32_t x, uint32_t y) { asm volatile("st.shared.v2.b32 [%0], {%1,%2};" ::"r"(a), "r"(x), "r"(y) : "memory"); }
__device__ __forceinline__ void sts128(uint32_t a, uint32_t x, uint32_t y, uint32_t z, uint32_t w) {
  asm volatile("st.shared.v4.b32 [%0], {%1,%2,%3,%4};" ::"r"(a), "r"(x), "r"(y), "r"(z), "r"(w) : "memory");
}
__device__ __forceinline__ uint32_t lds32(uint32_t a) { uint32_t v; asm volatile("ld.shared.b32 %0, [%1];" : "=r"(v) : "r"(a) : "memory"); return v; }
__device__ __forceinline__ uint2 lds64(uint32_t a) { uint2 v; asm volatile("ld.shared.v2.b32 {%0,%1}, [%2];" : "=r"(v.x), "=r"(v.y) : "r"(a) : "memory"); return v; }
__device__ __forceinline__ uint4 lds128(uint32_t a) {
  uint4 v; asm volatile("ld.shared.v4.b32 {%0,%1,%2,%3}, [%4];" : "=r"(v.x), "=r"(v.y), "=r"(v.z), "=r"(v.w) : "r"(a) : "memory"); return v;
}
__device__ __forceinline__ uint4 ldg128(const void* a) {
  uint4 v; asm volatile("ld.global.nc.v4.b32 {%0,%1,%2,%3}, [%4];" : "=r"(v.x), "=r"(v.y), "=r"(v.z), "=r"(v.w) : "l"(a) : "memory"); return v;
}
__device__ __forceinline__ uint2 ldg64(const void* a) {
  uint2 v; asm volatile("ld.global.nc.v2.b32 {%0,%1}, [%2];" : "=r"(v.x), "=r"(v.y) : "l"(a) : "memory"); return v;
}
__device__ __forceinline__ void ldsm4(uint32_t a, uint32_t& r0, uint32_t& r1, uint32_t& r2, uint32_t& r3) {
  asm volatile("ldmatrix.sync.aligned.m8n8.x4.shared.b16 {%0,%1,%2,%3}, [%4];" : "=r"(r0), "=r"(r1), "=r"(r2), "=r"(r3) : "r"(a) : "memory");
}
__device__ __forceinline__ void ldsm4t(uint32_t a, uint32_t& r0, uint32_t& r1, uint32_t& r2, uint32_t& r3) {
  asm volatile("ldmatrix.sync.aligned.m8n8.x4.trans.shared.b16 {%0,%1,%2,%3}, [%4];" : "=r"(r0), "=r"(r1), "=r"(r2), "=r"(r3) : "r"(a) : "memory");
}
__device__ __forceinline__ void stsm4(uint32_t a, uint32_t r0, uint32_t r1, uint32_t r2, uint32_t r3) {
  asm volatile("stmatrix.sync.aligned.m8n8.x4.shared.b16 [%0], {%1,%2,%3,%4};" ::"r"(a), "r"(r0), "r"(r1), "r"(r2), "r"(r3) : "memory");
}
__device__ __forceinline__ void stsm4t(uint32_t a, uint32_t r0, uint32_t r1, uint32_t r2, uint32_t r3) {
  asm volatile("stmatrix.sync.aligned.m8n8.x4.trans.shared.b16 [%0], {%1,%2,%3,%4};" ::"r"(a), "r"(r0), "r"(r1), "r"(r2), "r"(r3) : "memory");
}
__device__ __forceinline__ void stsm2(uint32_t a, uint32_t r0, uint32_t r1) {
  asm volatile("stmatrix.sync.aligned.m8n8.x2.shared.b16 [%0], {%1,%2};" ::"r"(a), "r"(r0), "r"(r1) : "memory");
}
__device__ __forceinline__ void stsm2t(uint32_t a, uint32_t r0, uint32_t r1) {
  asm volatile("stmatrix.sync.aligned.m8n8.x2.trans.shared.b16 [%0], {%1,%2};" ::"r"(a), "r"(r0), "r"(r1) : "memory");
}
__device__ __forceinline__ void mma16816(float* c, uint32_t a0, uint32_t a1, uint32_t a2, uint32_t a3, uint32_t b0, uint32_t b1) {
  asm("mma.sync.aligned.m16n8k16.row.col.f32.bf16.bf16.f32 {%0,%1,%2,%3}, {%4,%5,%6,%7}, {%8,%9}, {%0,%1,%2,%3};"
      : "+f"(c[0]), "+f"(c[1]), "+f"(c[2]), "+f"(c[3]) : "r"(a0), "r"(a1), "r"(a2), "r"(a3), "r"(b0), "r"(b1));
}
__device__ __forceinline__ void bar_sync(int id, int n) { asm volatile("bar.sync %0, %1;" ::"r"(id), "r"(n) : "memory"); }
__device__ __forceinline__ void bar_arrive(int id, int n) { asm volatile("bar.arrive %0, %1;" ::"r"(id), "r"(n) : "memory"); }
__device__ __forceinline__ void wg_fence() { asm volatile("wgmma.fence.sync.aligned;" ::: "memory"); }
__device__ __forceinline__ void wg_commit() { asm volatile("wgmma.commit_group.sync.aligned;" ::: "memory"); }
__device__ __forceinline__ void wg_wait0() { asm volatile("wgmma.wait_group.sync.aligned 0;" ::: "memory"); }
__device__ __forceinline__ void wg_wait1() { asm volatile("wgmma.wait_group.sync.aligned 1;" ::: "memory"); }
__device__ __forceinline__ void fence_async() { asm volatile("fence.proxy.async.shared::cta;" ::: "memory"); }
__device__ __forceinline__ uint32_t opq(uint32_t x, uint32_t z) { uint32_t r; asm volatile("xor.b32 %0, %1, %2;" : "=r"(r) : "r"(x), "r"(z)); return r; }
__device__ __forceinline__ uint64_t mkdesc(uint32_t addr, uint32_t lbo, uint32_t sbo) {
  return (uint64_t)((addr & 0x3FFFF) >> 4) | ((uint64_t)(lbo >> 4) << 16) | ((uint64_t)(sbo >> 4) << 32);
}
__device__ __forceinline__ uint32_t mapa(uint32_t a, uint32_t rank) {
  uint32_t r; asm("mapa.shared::cluster.u32 %0, %1, %2;" : "=r"(r) : "r"(a), "r"(rank)); return r;
}
__device__ __forceinline__ void mbar_init_expect(uint32_t bar, uint32_t bytes) {
  asm volatile("mbarrier.init.shared::cta.b64 [%0], 1;" ::"r"(bar) : "memory");
  asm volatile("mbarrier.arrive.expect_tx.shared::cta.b64 _, [%0], %1;" ::"r"(bar), "r"(bytes) : "memory");
}
__device__ __forceinline__ void mbar_wait(uint32_t bar) {
#pragma unroll 1
  for (int it = 0; it < (1 << 22); it++) {
    uint32_t ok;
    asm volatile("{\n.reg .pred p;\nmbarrier.try_wait.parity.acquire.cluster.shared::cta.b64 p, [%1], 0;\nselp.u32 %0, 1, 0, p;\n}"
                 : "=r"(ok) : "r"(bar) : "memory");
    if (ok) return;
  }
  __trap();
}
__device__ __forceinline__ void st_async4(uint32_t a, uint32_t bar, uint32_t x, uint32_t y, uint32_t z, uint32_t w) {
  asm volatile("st.async.weak.shared::cluster.mbarrier::complete_tx::bytes.v4.b32 [%0], {%2,%3,%4,%5}, [%1];"
               ::"r"(a), "r"(bar), "r"(x), "r"(y), "r"(z), "r"(w) : "memory");
}

struct cf { float re, im; };
__device__ __forceinline__ cf cmul(cf a, cf b) { return {fmaf(a.re, b.re, -a.im * b.im), fmaf(a.re, b.im, a.im * b.re)}; }
__device__ __forceinline__ cf csq(cf a) { return {fmaf(a.re, a.re, -a.im * a.im), (a.re + a.re) * a.im}; }
__device__ __forceinline__ cf cexp_p(float xl, float y, float p) {
  float mag; asm("ex2.approx.ftz.f32 %0, %1;" : "=f"(mag) : "f"(xl * p));
  const float th = y * p;
  const float k = __fadd_rn(fmaf(th, 0.15915494309189535f, 12582912.f), -12582912.f);
  float r = fmaf(k, -6.2831854820251465f, th);
  r = fmaf(k, 1.7484555314695172e-07f, r);
  return {mag * __cosf(r), mag * __sinf(r)};
}
__device__ __forceinline__ uint32_t ysw(int c) { return (uint32_t)(c ^ ((c >> 3) & 3)) * 16u; }

#define CMUL2(OR, OI, xr, xi, yr, yi, nyi) do { OR = hfma2(xr, yr, hmul2(xi, nyi)); OI = hfma2(xr, yi, hmul2(xi, yr)); } while (0)

__device__ __forceinline__ uint32_t gate_slow(const __nv_bfloat16* u, const __nv_bfloat16* gw, int row) {
  float s = 0.f;
  const uint32_t* xr = (const uint32_t*)(u + (size_t)row * D);
  const uint32_t* wr = (const uint32_t*)gw;
#pragma unroll 1
  for (int j = 0; j < D / 2; j++) { const uint32_t pr = hmul2(xr[j], wr[j]); s += bf_lo(pr); s += bf_hi(pr); }
  s = bf_round(s);
  return pack_bf16(1.f / (1.f + expf(-s)), 0.f);
}

__device__ __forceinline__ uint2 gate_ld(int x) {
  uint2 gv;
  asm volatile("ld.relaxed.gpu.global.v2.u32 {%0,%1}, [%2];" : "=r"(gv.x), "=r"(gv.y) : "l"(g_gate + x * 2) : "memory");
  return gv;
}
__device__ __noinline__ uint32_t gate_poll(const Params* pp, int x, uint32_t tag) {
  uint2 gv;
#pragma unroll 1
  for (int spins = 0; spins < (1 << 16); spins++) {
    gv = gate_ld(x);
    if ((gv.x >> 16) == tag && (gv.y >> 16) == tag) return __byte_perm(gv.x, gv.y, 0x5410);
  }
  return __byte_perm(gate_slow(pp->u, pp->gw, x * 2), gate_slow(pp->u, pp->gw, x * 2 + 1), 0x5410);
}
__device__ __forceinline__ uint32_t gate_fin(const Params& p, uint2 gv, int x, uint32_t tag) {
  if ((gv.x >> 16) == tag && (gv.y >> 16) == tag) return __byte_perm(gv.x, gv.y, 0x5410);
  return gate_poll(&p, x, tag);
}

__device__ __forceinline__ void ld4ch(uint32_t* v, uint32_t addr) {
#pragma unroll
  for (int k = 0; k < 4; k++) v[k] = lds32(addr + k * CH_BYTES);
}
__device__ __forceinline__ void skip_terms(uint32_t* ua, uint32_t* ub, uint32_t sb, int x, uint2 dA, uint2 dB) {
  const int c = x >> 2;
  uint32_t uu[4];
  ld4ch(uu, sb + CH_OFF + (x & 3) * 4 + U_OFF + (c & 3) * U_CS + (63 - (c >> 2)) * 16);
#pragma unroll
  for (int k = 0; k < 4; k++) {
    ua[k] = hmul2(uu[k], __byte_perm((k & 2) ? dA.y : dA.x, 0, (k & 1) ? 0x3232 : 0x1010));
    ub[k] = hmul2(uu[k], __byte_perm((k & 2) ? dB.y : dB.x, 0, (k & 1) ? 0x3232 : 0x1010));
  }
}
__device__ __forceinline__ uint4 mix(const uint32_t* a, const uint32_t* b, const uint32_t* ua, const uint32_t* ub, uint32_t g2) {
  const uint32_t h2 = hsub2(0x3f803f80u, g2);
  uint32_t o[4];
#pragma unroll
  for (int k = 0; k < 4; k++) o[k] = hadd2(hmul2(g2, hadd2(a[k], ua[k])), hmul2(h2, hadd2(b[k], ub[k])));
  return make_uint4(__byte_perm(o[0], o[1], 0x5410), __byte_perm(o[2], o[3], 0x5410), __byte_perm(o[0], o[1], 0x7632), __byte_perm(o[2], o[3], 0x7632));
}
__device__ __forceinline__ void send_box(uint32_t sb, int slot, int wtid, uint32_t rank, uint4 r) {
  st_async4(mapa(sb + XIN_OFF + slot * 2048 + wtid * 16, rank ^ 1), mapa(sb + B_X + slot * 8, rank ^ 1), r.x, r.y, r.z, r.w);
}
__device__ __forceinline__ void merge_rows(uint32_t st, uint32_t rank, uint4 r, uint4 q) {
  const uint4 lo = rank ? q : r, hi = rank ? r : q;
  sts128(st, lo.x, lo.y, hi.x, hi.y); sts128(st + 2048, lo.z, lo.w, hi.z, hi.w);
}
__device__ __forceinline__ void merge_box(uint32_t sb, const CUtensorMap* tm_out, int slot, int wtid, uint32_t rank, int oc0, uint4 r, int barid) {
  const uint32_t st = sb + RAW_OFF + slot * 4096 + wtid * 16;
  mbar_wait(sb + B_X + slot * 8);
  merge_rows(st, rank, r, lds128(sb + XIN_OFF + slot * 2048 + wtid * 16));
  fence_async();
  bar_sync(barid, 128);
  if (wtid == 0) {
    asm volatile("cp.async.bulk.tensor.3d.global.shared::cta.bulk_group [%0, {%2, %3, %4}], [%1];"
                 ::"l"(tm_out), "r"(sb + RAW_OFF + slot * 4096), "r"(oc0), "r"((2 * slot + (int)rank) * 128), "r"(0) : "memory");
    asm volatile("cp.async.bulk.commit_group;" ::: "memory");
  }
}

__device__ __forceinline__ uint32_t band2(int e, int lo, int hi) {
  uint32_t r = ((uint32_t)(e - lo) <= (uint32_t)(hi - lo) ? 0x3f80u : 0u) | ((uint32_t)(e - 1 - lo) <= (uint32_t)(hi - lo) ? 0x3f800000u : 0u);
  asm volatile("" : "+r"(r));
  return r;
}

__device__ __forceinline__ void stage_done(uint32_t sb, int stage, int lane) {
  __syncwarp();
  if (lane == 0) asm volatile("mbarrier.arrive.shared::cta.b64 _, [%0];" ::"r"(sb + B_ST + 8 * stage) : "memory");
}
#define PK2(v, i) pack_bf16(v[i], v[(i) + 1])

__device__ __forceinline__ void conv_dense(uint32_t sb, uint32_t cb, uint32_t zz) {
  const int lane = threadIdx.x & 31, wq = (threadIdx.x >> 5) & 3, br = wq >> 1, hf = wq & 1, g = lane >> 2, t = lane & 3;
  const uint32_t rb = cb + R_OFF + br * R_BR;
  const int eo = 16 * hf + g - 2 * t;
  const int x0 = RD_X0 - (eo + 536);
  const uint32_t fa = rb + ((g & 1) ? 2 * x0 : RD_CS + 2 * x0 + 2);
  const uint64_t ub = mkdesc(cb + U_OFF, U_CS, 128);
  const uint32_t yd = cb + Y0_OFF + br * 4096 + ysw(4 * (63 - 8 * (lane >> 4) - (lane & 7)) + 2 * hf + ((lane >> 3) & 1));
  uint32_t A[2][4][4];
  float e64[32], e56[28], e48[24];
  auto loadA = [&](int j) {
#pragma unroll
    for (int k = 0; k < 4; k++) {
      const int s = 34 - 4 * j - k;
      if (s >= 0) {
        if (k == 0 && j == 0) A[0][0][2] = lds32(fa + (2 * s + 2) * 16);
        A[j & 1][k][0] = lds32(fa + (2 * s + 1) * 16);
        A[j & 1][k][1] = lds32(fa + (2 * s) * 16);
      }
    }
#pragma unroll
    for (int k = 0; k < 4; k++) {
      if (34 - 4 * j - k >= 0) {
        A[j & 1][k][3] = A[j & 1][k][0];
        if (k) A[j & 1][k][2] = A[j & 1][k - 1][1];
        else if (j) A[j & 1][0][2] = A[(j - 1) & 1][3][1];
      }
    }
  };
  loadA(0); loadA(1);
#pragma unroll
  for (int j = 0; j < 9; j++) {
    if (j == 4) {
      wg_wait0();
      stsm2t(yd - 7 * 512, PK2(e64, 28), PK2(e64, 30));
#pragma unroll
      for (int i = 0; i < 28; i++) e56[i] = FCPY(e64[i]);
      stage_done(sb, 0, lane);
    }
    if (j == 8) {
      wg_wait0();
      stsm2t(yd - 6 * 512, PK2(e56, 24), PK2(e56, 26));
#pragma unroll
      for (int i = 0; i < 24; i++) e48[i] = FCPY(e56[i]);
      stage_done(sb, 1, lane);
    }
    wg_fence();
#pragma unroll
    for (int k = 0; k < 4; k++) {
      const int s = 34 - 4 * j - k;
      if (s >= 0) {
        const int o = 2 * s - 66 + 128;
        const int cc = o & 3, rs = (o >> 2) - 32;
        const uint64_t desc = ub + (uint64_t)((cc * U_CS - rs * 16) >> 4);
        const uint32_t* a = A[j & 1][k];
        if (j < 4) wgmma_rs<64, 0>(e64, a[0], a[1], a[2], a[3], desc, s != 34);
        else if (j < 8) wgmma_rs<56, 0>(e56, a[0], a[1], a[2], a[3], desc, 1);
        else wgmma_rs<48, 0>(e48, a[0], a[1], a[2], a[3], desc, 1);
      }
    }
    wg_commit();
    if (j >= 1 && j < 8) { wg_wait1(); loadA(j + 1); }
  }
  wg_wait0();
#pragma unroll
  for (int i = 0; i < 6; i += 2) stsm4t(yd - i * 512, PK2(e48, 4 * i), PK2(e48, 4 * i + 2), PK2(e48, 4 * i + 4), PK2(e48, 4 * i + 6));
}

__device__ __noinline__ void gate_rows(const Params* pp, int grow, int step, int rend, uint32_t tag) {
  const __nv_bfloat16 *u = pp->u, *gw = pp->gw;
  const int lane = threadIdx.x & 31;
  uint4 gx[4][2], nx[4][2];
#pragma unroll
  for (int i = 0; i < 4; i++) {
    nx[i][0] = ldg128(u + (size_t)(grow + i) * D + lane * 8);
    nx[i][1] = ldg128(u + (size_t)(grow + i) * D + 256 + lane * 8);
  }
  const uint4 gw0 = ldg128(gw + lane * 8), gw1 = ldg128(gw + 256 + lane * 8);
  const uint32_t ws[8] = {gw0.x, gw0.y, gw0.z, gw0.w, gw1.x, gw1.y, gw1.z, gw1.w};
#pragma unroll 1
  for (; grow < rend; grow += step) {
#pragma unroll
    for (int i = 0; i < 4; i++) { gx[i][0] = nx[i][0]; gx[i][1] = nx[i][1]; }
    if (grow + step < rend) {
#pragma unroll
      for (int i = 0; i < 4; i++) {
        nx[i][0] = ldg128(u + (size_t)(grow + step + i) * D + lane * 8);
        nx[i][1] = ldg128(u + (size_t)(grow + step + i) * D + 256 + lane * 8);
      }
    }
    float c[2][4];
#pragma unroll
    for (int i = 0; i < 2; i++) {
      const uint4 *x = gx[2 * i], *y = gx[2 * i + 1];
      const uint32_t xs[8] = {x[0].x, x[0].y, x[0].z, x[0].w, x[1].x, x[1].y, x[1].z, x[1].w};
      const uint32_t ys[8] = {y[0].x, y[0].y, y[0].z, y[0].w, y[1].x, y[1].y, y[1].z, y[1].w};
      c[i][0] = c[i][1] = c[i][2] = c[i][3] = 0.f;
#pragma unroll
      for (int j = 0; j < 8; j += 2)
        mma16816(c[i], hmul2(xs[j], ws[j]), hmul2(ys[j], ws[j]), hmul2(xs[j + 1], ws[j + 1]), hmul2(ys[j + 1], ws[j + 1]), 0x3f803f80u, 0x3f803f80u);
    }
    float s = (lane & 2) ? ((lane & 1) ? c[1][2] : c[1][0]) : ((lane & 1) ? c[0][2] : c[0][0]);
#pragma unroll
    for (int o = 4; o < 32; o <<= 1) s += __shfl_xor_sync(0xffffffffu, s, o);
    s = bf_round(s);
    const float gv = 1.f / (1.f + expf(-s));
    const uint32_t w = (tag << 16) | (pack_bf16(gv, 0.f) & 0xffffu);
    if (lane < 4) asm volatile("st.relaxed.gpu.global.u32 [%0], %1;" ::"l"(&g_gate[grow + lane]), "r"(w) : "memory");
  }
}
constexpr int GSPLIT = L - 4 * NCTA;
__device__ __noinline__ void gate_cta(const Params* pp) {
  unsigned int epoch;
  asm volatile("ld.relaxed.gpu.global.u32 %0, [%1];" : "=r"(epoch) : "l"(&g_epoch) : "memory");
  gate_rows(pp, (blockIdx.x * 20 + (threadIdx.x >> 5)) * 4, 80 * NGATE, GSPLIT, (epoch + 1) & 0xffffu);
  __syncthreads();
  if (threadIdx.x == 0 && atomicAdd(&g_ticket, 1u) == NCTA + NGATE - 1) { g_ticket = 0; g_epoch = epoch + 1; }
}

__global__ void __cluster_dims__(2, 1, 1) __launch_bounds__(640, 1)
ssm_kernel(const __grid_constant__ Params p, const __grid_constant__ CUtensorMap tm_in, const __grid_constant__ CUtensorMap tm_out) {
  extern __shared__ __align__(1024) unsigned char smem_raw[];
  const uint32_t sb = (uint32_t)__cvta_generic_to_shared(smem_raw);
  const int tid = threadIdx.x, lane = tid & 31;
  const int warp = __shfl_sync(0xffffffffu, tid >> 5, 0);
  const int ch = warp >> 2, wq = warp & 3, br = wq >> 1, hf = wq & 1;
  const int g = lane >> 2, t = lane & 3;
  if (__builtin_expect(blockIdx.x < NGATE, 0)) { gate_cta(&p); return; }
  const int bid = blockIdx.x - NGATE;
  const int d = bid * 4 + ch;
  const uint32_t rank = blockIdx.x & 1;
  const uint32_t cb = sb + CH_OFF + ch * CH_BYTES;
  const int wtid = tid & 127;
  const int oc0 = (bid >> 1) * 8;
  STAMP(0); GT(0);

  if (warp >= 16) {
    if (wtid == 0) {
      mbar_init_expect(sb + B_RAW, 32768);
#pragma unroll
      for (int i = 0; i < 4; i++) mbar_init_expect(sb + B_X + 8 * i, 2048);
      asm volatile("mbarrier.init.shared::cta.b64 [%0], 128;" ::"r"(sb + B_U) : "memory");
      asm volatile("mbarrier.init.shared::cta.b64 [%0], 128;" ::"r"(sb + B_W) : "memory");
#pragma unroll
      for (int i = 0; i < 7; i++) asm volatile("mbarrier.init.shared::cta.b64 [%0], 16;" ::"r"(sb + B_ST + 8 * i) : "memory");
      asm volatile("fence.mbarrier_init.release.cluster;" ::: "memory");
      asm volatile("fence.proxy.async.shared::cta;" ::: "memory");
    }
    __syncwarp();
    asm volatile("barrier.cluster.arrive.relaxed.aligned;" ::: "memory");
    unsigned int epoch;
    asm volatile("ld.relaxed.gpu.global.u32 %0, [%1];" : "=r"(epoch) : "l"(&g_epoch) : "memory");
    asm volatile("barrier.cluster.wait.aligned;" ::: "memory");
    if (wtid == 0) {
      asm volatile("cp.async.bulk.tensor.5d.shared::cluster.global.mbarrier::complete_tx::bytes.multicast::cluster [%0], [%1, {%3, %4, %4, %4, %5}], [%2], %6;"
                   ::"r"(sb + RAW_OFF + rank * 16384), "l"(&tm_in), "r"(sb + B_RAW), "r"(oc0), "r"(0), "r"((int)rank * 32), "h"((unsigned short)3) : "memory");
    }
    sts128(sb + CH_OFF + wq * CH_BYTES + U_OFF + (lane >> 3) * U_CS + (64 + (lane & 7)) * 16, 0, 0, 0, 0);
    if (wq == 3) gate_rows(&p, GSPLIT + bid * 4, L, L, (epoch + 1) & 0xffffu);
    const uint2 dA = ldg64(p.A_D + bid * 4), dB = ldg64(p.B_D + bid * 4);
    uint32_t BA[3][4], BB[4][4];
    {
      const int l1 = br ? 3 : 6, h1 = br ? 5 : 10, l2 = br ? 5 : 12, h2 = br ? 11 : 20;
#pragma unroll
      for (int i = 0; i < 4; i++) {
        const int e = 16 * hf + g - 2 * t + 32 - 16 * i;
        BB[i][0] = band2(e, l2, h2); BB[i][1] = band2(e + 8, l2, h2); BB[i][2] = band2(e - 8, l2, h2); BB[i][3] = BB[i][0];
        if (i) { BA[i - 1][0] = band2(e, l1, h1); BA[i - 1][1] = band2(e + 8, l1, h1); BA[i - 1][2] = band2(e - 8, l1, h1); BA[i - 1][3] = BA[i - 1][0]; }
      }
    }
    const uint32_t tag = (epoch + 1) & 0xffffu;
    if (wtid == 0) sts32(sb + TAG_OFF, tag);
    STAMP(3);
    mbar_wait(sb + B_RAW);
    STAMP(4);
    {
      const uint32_t dst = sb + CH_OFF + (g & 3) * CH_BYTES + U_OFF + t * U_CS + (63 - wq * 16) * 16;
#pragma unroll
      for (int h = 0; h < 2; h++) {
        uint32_t r[8][4];
#pragma unroll
        for (int i = 0; i < 8; i++) ldsm4t(sb + RAW_OFF + (wq * 16 + h * 8 + i) * 512 + lane * 16, r[i][0], r[i][1], r[i][2], r[i][3]);
        if ((uint32_t)(g >> 2) == rank) {
#pragma unroll
          for (int i = 0; i < 8; i++) sts128(dst - (h * 8 + i) * 16, r[i][0], r[i][1], r[i][2], r[i][3]);
        }
      }
    }
    fence_async();
    asm volatile("mbarrier.arrive.shared::cta.b64 _, [%0];" ::"r"(sb + B_U) : "memory");
    bar_sync(5, 128);
    STAMP(5);
    {
      const int mrow = lane & 7, mi = lane >> 3;
      const uint64_t ub0 = mkdesc(sb + CH_OFF + U_OFF, U_CS, 128);
      uint32_t wa, wb;
      {
        const int c = 4 * (47 - 8 * (mi >> 1) - mrow) + 2 * hf + (mi & 1);
        wa = sb + CH_OFF + (br ? W3_OFF : W5_OFF) + (5 - (c >> 5)) * 576 + ((c & 31) >> 3) * 144 + (c & 7) * 16;
        const int c2 = c - 64, pp = c2 >> 1;
        wb = sb + CH_OFF + (br ? W7_OFF : W9_OFF) + (1 - (pp >> 5)) * 1152 + (c2 & 1) * 576 + ((pp & 31) >> 3) * 144 + (pp & 7) * 16;
      }
      {
        float w1[24];
#pragma unroll
        for (int i = 0; i < 24; i++) w1[i] = 0.f;
#pragma unroll 1
        for (int k = 0; k < 4; k++) {
          wg_fence();
#pragma unroll
          for (int i = 0; i < 3; i++)
            wgmma_rs<48, 0>(w1, BA[i][0], BA[i][1], BA[i][2], BA[i][3],
                            ub0 + (uint64_t)((k * CH_BYTES + ((2 * i + 2) & 3) * U_CS + (16 + (i == 0)) * 16) >> 4), i);
          wg_commit();
          wg_wait0();
#pragma unroll
          for (int i = 0; i < 3; i++) stsm4t(wa + k * CH_BYTES + i * 1152, PK2(w1, 8 * i), PK2(w1, 8 * i + 2), PK2(w1, 8 * i + 4), PK2(w1, 8 * i + 6));
        }
      }
      {
        float w2[2][16];
#pragma unroll
        for (int i = 0; i < 16; i++) { w2[0][i] = 0.f; w2[1][i] = 0.f; }
#pragma unroll 1
        for (int kp = 0; kp < 2; kp++) {
          wg_fence();
#pragma unroll
          for (int k = 0; k < 2; k++)
#pragma unroll
            for (int i = 0; i < 4; i++)
              wgmma_rs<32, 0>(w2[k], BB[i][0], BB[i][1], BB[i][2], BB[i][3],
                              ub0 + (uint64_t)(((2 * kp + k) * CH_BYTES + ((2 * i) & 3) * U_CS + (32 + (i < 2)) * 16) >> 4), i);
          wg_commit();
          wg_wait0();
#pragma unroll
          for (int k = 0; k < 2; k++)
#pragma unroll
            for (int i = 0; i < 2; i++)
              stsm4t(wb + (2 * kp + k) * CH_BYTES + i * 1152, PK2(w2[k], 8 * i), PK2(w2[k], 8 * i + 2), PK2(w2[k], 8 * i + 4), PK2(w2[k], 8 * i + 6));
        }
      }
    }
    fence_async();
    asm volatile("mbarrier.arrive.shared::cta.b64 _, [%0];" ::"r"(sb + B_W) : "memory");
    STAMP(7);
    {
      const int bsel = (int)rank ^ br ^ 1, xl = wtid & 63;
      uint2 gl[4];
      uint32_t ua[4][4], ub[4][4];
#pragma unroll
      for (int i = 0; i < 4; i++) skip_terms(ua[i], ub[i], sb, (2 * (i >> 1) + bsel) * 128 + (i & 1) * 64 + xl, dA, dB);
      const uint32_t yo = sb + CH_OFF + (xl & 3) * 4 + ysw(xl >> 2) + bsel * 512;
#pragma unroll
      for (int i = 0; i < 2; i++) gl[i] = gate_ld(bsel * 128 + i * 64 + xl);
#pragma unroll
      for (int slot = 0; slot < 2; slot++) {
        const int box = 2 * slot + bsel;
        uint32_t g2[2], ya[2][4], yb[2][4];
#pragma unroll
        for (int h = 0; h < 2; h++) g2[h] = gate_fin(p, gl[2 * slot + h], box * 128 + h * 64 + xl, tag);
        mbar_wait(sb + B_ST + 8 * box);
        STAMP(8 + slot);
        if (slot == 0) { gl[2] = gate_ld((2 + bsel) * 128 + xl); gl[3] = gate_ld((2 + bsel) * 128 + 64 + xl); }
#pragma unroll
        for (int h = 0; h < 2; h++) {
          const uint32_t yh = (yo ^ (h * 32)) + h * 256 + slot * 1024;
          ld4ch(ya[h], yh + Y0_OFF); ld4ch(yb[h], yh + Y0_OFF + 4096);
          if (slot) {
            uint32_t a2[4], b2[4];
            ld4ch(a2, yh + Y2_OFF - 1024); ld4ch(b2, yh + Y2_OFF - 1024 + 3072);
#pragma unroll
            for (int k = 0; k < 4; k++) { ya[h][k] = hadd2(ya[h][k], a2[k]); yb[h][k] = hadd2(yb[h][k], b2[k]); }
          }
        }
        const uint4 r0 = mix(ya[0], yb[0], ua[2 * slot], ub[2 * slot], g2[0]), r1 = mix(ya[1], yb[1], ua[2 * slot + 1], ub[2 * slot + 1], g2[1]);
        if (br == 0) { send_box(sb, slot, xl, rank, r0); send_box(sb, slot, xl + 64, rank, r1); }
        else {
          const uint32_t st = sb + RAW_OFF + slot * 4096 + xl * 16, xin = sb + XIN_OFF + slot * 2048 + xl * 16;
          mbar_wait(sb + B_X + slot * 8);
          const uint4 q0 = lds128(xin), q1 = lds128(xin + 1024);
          merge_rows(st, rank, r0, q0); merge_rows(st + 1024, rank, r1, q1);
          fence_async();
          bar_sync(6, 64);
          if (xl == 0) {
            asm volatile("cp.async.bulk.tensor.3d.global.shared::cta.bulk_group [%0, {%2, %3, %4}], [%1];"
                         ::"l"(&tm_out), "r"(sb + RAW_OFF + slot * 4096), "r"(oc0), "r"(box * 128), "r"(0) : "memory");
            asm volatile("cp.async.bulk.commit_group;" ::: "memory");
          }
        }
        STAMP(10 + slot);
      }
    }
    if (wtid == 0 && atomicAdd(&g_ticket, 1u) == NCTA + NGATE - 1) { g_ticket = 0; g_epoch = epoch + 1; }
    if (wtid == 64) asm volatile("cp.async.bulk.wait_group.read 0;" ::: "memory");
    STAMP(15);
    return;
  }
  asm volatile("barrier.cluster.arrive.relaxed.aligned;" ::: "memory");

  const int moff = (bid * 4 + (tid >> 7)) * NM + (tid & 63) * 2;
  const int brt = (tid >> 6) & 1;
  const __nv_bfloat16* const* tp = p.t + (brt ? 0 : 6);
  const uint32_t q0 = *(const uint32_t*)(tp[0] + moff), q1 = *(const uint32_t*)(tp[1] + moff);
  const uint32_t q2 = *(const uint32_t*)(tp[2] + moff), q3 = *(const uint32_t*)(tp[3] + moff);
  const uint2 ldt4 = *(const uint2*)(tp[4] + bid * 4);
  const uint32_t q4 = *(const uint32_t*)(tp[brt ? 2 : 5] + moff), q5 = *(const uint32_t*)(tp[brt ? 3 : 6] + moff);

  for (int i = wtid & 63; i < R_BR / 16; i += 64) sts128(cb + R_OFF + br * R_BR + i * 16, 0, 0, 0, 0);
  STAMP(1);

  float acc[5][4];
  float k2048 = 0.f;
  const uint32_t scr = cb + Y0_OFF + wq * SCR_BYTES;
  const uint32_t scr2 = sb + XIN_OFF + warp * 640;
  {
    const uint32_t ldt2 = (ch & 2) ? ldt4.y : ldt4.x;
    const float dt = bf_round(expf((ch & 1) ? bf_hi(ldt2) : bf_lo(ldt2)));
#pragma unroll
    for (int i = 0; i < 5; i++) acc[i][0] = acc[i][1] = acc[i][2] = acc[i][3] = 0.f;
    STAMP(2);
    const uint32_t tb = scr + lane * 16;
    const uint32_t ta = scr + (lane >> 3) * 512 + (lane & 7) * 16;
    const uint32_t tc = ((lane & 8) ? scr2 : scr + 4096) + (lane >> 4) * 128 + (lane & 7) * 16;
    const uint32_t tm = scr2 + 512 + ((lane >> 3) & 1) * 64 + (lane >> 4) * 16;
    cf cc[2], zz1[2], zz128[2];
#pragma unroll
    for (int r = 0; r < 2; r++) {
      float v0 = r ? bf_hi(q0) : bf_lo(q0), v1 = r ? bf_hi(q1) : bf_lo(q1), v2 = r ? bf_hi(q2) : bf_lo(q2);
      float v3 = r ? bf_hi(q3) : bf_lo(q3), v4 = r ? bf_hi(q4) : bf_lo(q4), v5 = r ? bf_hi(q5) : bf_lo(q5);
      if (br == 0) { cc[r] = cmul(cf{v2, v3}, cf{dt * v4, dt * v5}); }
      else { v0 = -bf_round(expf(v0)); cc[r] = cf{2.f * dt * v2, 2.f * dt * v3}; }
      const float xl = (dt * v0) * 1.4426950408889634f, y = dt * v1;
      zz1[r] = cexp_p(xl, y, 1.f); zz128[r] = cexp_p(xl, y, 128.f);
    }
    uint32_t T[10][4], m4;
    auto produce = [&](int r) {
      const cf c = cc[r], z1 = zz1[r], z128 = zz128[r];
      const cf z2 = csq(z1), z4 = csq(z2), z8 = csq(z4);
      const cf w8 = {z8.re, -z8.im};
      const cf z16 = csq(w8), z24 = cmul(z16, w8), z32 = csq(z16), z40 = cmul(z32, w8), z48 = csq(z24), z56 = cmul(z32, z24), z64 = csq(z32);
      const cf z256 = csq(z128), z512 = csq(z256), z1024 = csq(z512), z2048 = csq(z1024);
      k2048 += fmaf(c.re, z2048.re, -c.im * z2048.im);
      {
        T[0][0] = pack_bf16(1.f, z8.re); T[0][1] = pack_bf16(z16.re, z24.re); T[0][2] = pack_bf16(z32.re, z40.re); T[0][3] = pack_bf16(z48.re, z56.re);
        T[2][0] = pack_bf16(0.f, w8.im); T[2][1] = pack_bf16(z16.im, z24.im); T[2][2] = pack_bf16(z32.im, z40.im); T[2][3] = pack_bf16(z48.im, z56.im);
        const uint32_t yr = pack_bf16(z64.re, z64.re), yi = pack_bf16(z64.im, z64.im), nyi = yi ^ 0x80008000u;
#pragma unroll
        for (int i = 0; i < 4; i++) CMUL2(T[1][i], T[3][i], T[0][i], T[2][i], yr, yi, nyi);
      }
      {
        const cf h1 = cmul(c, z128), h2 = cmul(c, z256), h3 = cmul(h1, z256), h4 = cmul(c, z512), h5 = cmul(h1, z512), h6 = cmul(h2, z512), h7 = cmul(h3, z512);
        const cf e1 = cmul(c, z1), e2 = cmul(c, z2), e3 = cmul(e1, z2), e129 = cmul(h1, z1), e130 = cmul(h1, z2), e131 = cmul(e129, z2);
        const cf e258 = cmul(h2, z2), e386 = cmul(h3, z2);
        T[4][0] = pack_bf16(c.re, e1.re); T[4][1] = pack_bf16(e2.re, e3.re); T[4][2] = pack_bf16(h1.re, e129.re); T[4][3] = pack_bf16(e130.re, e131.re);
        T[5][0] = pack_bf16(c.im, e1.im); T[5][1] = pack_bf16(e2.im, e3.im); T[5][2] = pack_bf16(h1.im, e129.im); T[5][3] = pack_bf16(e130.im, e131.im);
        T[6][0] = pack_bf16(h2.re, e258.re); T[6][1] = pack_bf16(h3.re, e386.re); T[6][2] = pack_bf16(h4.re, h5.re); T[6][3] = pack_bf16(h6.re, h7.re);
        T[7][0] = pack_bf16(h2.im, e258.im); T[7][1] = pack_bf16(h3.im, e386.im); T[7][2] = pack_bf16(h4.im, h5.im); T[7][3] = pack_bf16(h6.im, h7.im);
        const uint32_t xr[4] = {__byte_perm(T[4][0], T[4][2], 0x5410), __byte_perm(T[6][0], T[6][1], 0x5410), T[6][2], T[6][3]};
        const uint32_t xi[4] = {__byte_perm(T[5][0], T[5][2], 0x5410), __byte_perm(T[7][0], T[7][1], 0x5410), T[7][2], T[7][3]};
        const uint32_t yr = pack_bf16(z1024.re, z1024.re), yi = pack_bf16(z1024.im, z1024.im), nyi = yi ^ 0x80008000u;
#pragma unroll
        for (int i = 0; i < 4; i++) CMUL2(T[8][i], T[9][i], xr[i], xi[i], yr, yi, nyi);
        m4 = pack_bf16(z4.re, z4.im);
      }
    };
    auto store = [&]() {
#pragma unroll
      for (int m = 0; m < 9; m++) sts128(tb + m * 512, T[m][0], T[m][1], T[m][2], T[m][3]);
      sts128(scr2 + lane * 16, T[9][0], T[9][1], T[9][2], T[9][3]);
      sts16(scr2 + 512 + lane * 2, m4); sts16(scr2 + 576 + lane * 2, m4 >> 16);
    };
    auto consume = [&]() {
#pragma unroll
      for (int kp = 0; kp < 2; kp++) {
        uint32_t rr[2], ri[2], yr[2], yi[2];
        ldsm4t(tc + kp * 256, rr[0], ri[0], rr[1], ri[1]);
        ldsm4(tm + kp * 32, yr[0], yi[0], yr[1], yi[1]);
#pragma unroll
        for (int k2 = 0; k2 < 2; k2++) {
          const int kk = kp * 2 + k2;
          uint32_t a0, a1, a2, a3, pr, pi, qr, qi, xr, xi;
          ldsm4t(ta + kk * 128, a0, a1, a2, a3);
          ldsm4t(ta + 2048 + kk * 128, pr, pi, qr, qi);
          const uint32_t nyi = yi[k2] ^ 0x80008000u;
          mma16816(acc[0], a0, a1, a2, a3, pr, pi);
          mma16816(acc[2], a0, a1, a2, a3, qr, qi);
          mma16816(acc[4], a0, a1, a2, a3, rr[k2], ri[k2]);
          CMUL2(xr, xi, pr, pi, yr[k2], yi[k2], nyi);
          mma16816(acc[1], a0, a1, a2, a3, xr, xi);
          CMUL2(xr, xi, qr, qi, yr[k2], yi[k2], nyi);
          mma16816(acc[3], a0, a1, a2, a3, xr, xi);
        }
      }
    };
    produce(0); store();
    __syncwarp();
    consume(); produce(1);
    __syncwarp();
    store();
#pragma unroll
    for (int o = 16; o; o >>= 1) k2048 += __shfl_xor_sync(0xffffffffu, k2048, o);
    __syncwarp();
    consume();
  }
  STAMP(3);
  __syncwarp();
  {
    const uint32_t xs = scr + lane * 16;
#define OTH(i, k) __float_as_uint(hf ? acc[i][k] : acc[i][2 + (k)])
    sts128(xs, OTH(0, 0), OTH(0, 1), OTH(1, 0), OTH(1, 1));
    sts128(xs + 512, OTH(2, 0), OTH(2, 1), OTH(3, 0), OTH(3, 1));
    sts128(xs + 1024, OTH(4, 0), OTH(4, 1), __float_as_uint(k2048), 0);
#undef OTH
  }

  bar_sync(7 + (warp >> 1), 64);
  STAMP(4);
  {
    const uint32_t xo = cb + Y0_OFF + (wq ^ 1) * SCR_BYTES + lane * 16;
    const uint4 o0 = lds128(xo), o1 = lds128(xo + 512), o2 = lds128(xo + 1024);
    const uint32_t rb = cb + R_OFF + br * R_BR;
#define OWN(i, k) (hf ? acc[i][2 + (k)] : acc[i][k])
    const uint32_t vP = pack_bf16(OWN(0, 1) + __uint_as_float(o0.y), OWN(0, 0) + __uint_as_float(o0.x));
    const uint32_t vP4 = pack_bf16(OWN(1, 1) + __uint_as_float(o0.w), OWN(1, 0) + __uint_as_float(o0.z));
    const uint32_t vQ = pack_bf16(OWN(2, 1) + __uint_as_float(o1.y), OWN(2, 0) + __uint_as_float(o1.x));
    const uint32_t vQ4 = pack_bf16(OWN(3, 1) + __uint_as_float(o1.w), OWN(3, 0) + __uint_as_float(o1.z));
    const uint32_t vR = pack_bf16(OWN(4, 1) + __uint_as_float(o2.y), OWN(4, 0) + __uint_as_float(o2.x));
#undef OWN
    const int j = g + 8 * hf;
    {
      const int a = 2 * (t & 1) + 64 * (t & 2) + 8 * j;
      const uint32_t ad = rb + 2 * (RD_X0 - 1 - a);
      const uint32_t a1 = (t & 2) ? ad - 8 : ad, a2 = (t & 2) ? ad : ad - 8;
      const uint32_t w1 = (t & 2) ? vP4 : vP, w2 = (t & 2) ? vP : vP4;
      sts32(a1, w1); sts32(a2, w2);
      sts16(a1 + RD_CS + 2, w1); sts16(a1 + RD_CS + 4, w1 >> 16);
      sts16(a2 + RD_CS + 2, w2); sts16(a2 + RD_CS + 4, w2 >> 16);
    }
    if (t < 2) {
      const int b = 256 + 128 * t + 8 * j;
      const uint32_t ad = rb + 2 * (RD_X0 - 6 - b);
      const uint32_t v22 = __byte_perm(vQ4, 0, 0x3232), v00 = __byte_perm(vQ, 0, 0x3232);
      sts16(ad, vQ4);
      sts64(ad + 2, v22, __byte_perm(vQ4, vQ, 0x5432));
      sts32(ad + 10, v00);
      if (b != 256) { sts16(ad + 14, v00); sts128(ad + RD_CS + 2, vQ4, v22, vQ, v00); }
      else { sts64(ad + RD_CS + 2, vQ4, v22); sts32(ad + RD_CS + 10, vQ); sts16(ad + RD_CS + 14, v00); }
    } else {
      const uint32_t ao = rb + R_O2 + 2 * (159 - (32 * t + j)), ae = ao - (R_O2 - R_E2) + 2;
      sts16(ao, vQ4 >> 16); sts16(ao + RS_CS + 2, vQ4 >> 16); sts16(ao - 32, vQ4); sts16(ao - 32 + RS_CS + 2, vQ4);
      sts16(ae - 32, vQ); sts16(ae - 32 + RS_CS + 2, vQ);
      if (lane != 2 || hf) { sts16(ae, vQ >> 16); sts16(ae + RS_CS + 2, vQ >> 16); }
      else {
        const uint32_t vv = __byte_perm(vQ, 0, 0x3232), ad = rb + 2 * (RD_X0 - 514);
        sts16(ad, vv); sts32(ad + 2, vv); sts16(ad + 6, vv); sts64(ad + RD_CS + 2, vv, vv);
      }
    }
    {
      const uint32_t a = rb + ((g & 1) ? R_O3 : R_E3 + 2) + 2 * (159 - (64 + 16 * t + (j >> 1)));
      const bool p1024 = (lane == 0) && (hf == 0);
      const uint32_t a00 = p1024 ? rb + R_E2 + 2 * (159 - 127) : a;
      sts16(a00, vR >> 16); sts16(a00 + RS_CS + 2, vR >> 16);
      sts16(a - 16, vR); sts16(a - 16 + RS_CS + 2, vR);
      if (p1024) {
        sts32(sb + K1024_OFF + (ch * 2 + br) * 4, __byte_perm(vR, 0, 0x3232));
        const uint32_t kv = pack_bf16(k2048 + __uint_as_float(o2.z), 0.f);
        sts16(rb + R_E3 + 2 * (159 - 127), kv); sts16(rb + R_E3 + 2 * (159 - 127) + RS_CS + 2, kv);
      }
    }
  }
  STAMP(5);
  asm volatile("barrier.cluster.wait.aligned;" ::: "memory");
  bar_sync(7 + (warp >> 1), 64);
  mbar_wait(sb + B_U);
  STAMP(6);

  const uint32_t zz = lds32(cb + R_OFF + br * R_BR);
  conv_dense(sb, cb, zz);
  STAMP(8);
  {
    const int x = (4 + ch) * 128 + wtid, c = x >> 2;
    const uint2 dA = ldg64(p.A_D + bid * 4), dB = ldg64(p.B_D + bid * 4);
    const uint2 gl = gate_ld(x);
    const uint32_t rb = cb + R_OFF + br * R_BR;
    float e48[24], e40[20], e32[16], h32[16], h16[8];
    const int x1 = 159 - (16 * hf + g - 2 * t + 136);
    const uint32_t fs = rb + ((g & 1) ? 2 * x1 : RS_CS + 2 * x1 + 2);
    uint32_t A[2][4][4];
    auto loadA = [&](int buf, uint32_t oe, uint32_t oo, int i0) {
#pragma unroll
      for (int a = 0; a < 2; a++) {
        const uint32_t base = fs + (a ? oo : oe) + i0 * 16;
        uint32_t* k0 = A[buf][2 * a];
        uint32_t* k1 = A[buf][2 * a + 1];
        k0[1] = lds32(base); k0[0] = lds32(base + 16); k0[2] = lds32(base + 32); k1[0] = lds32(base + 48); k1[2] = lds32(base + 64);
        k0[3] = k0[0]; k1[1] = k0[2]; k1[3] = k1[0];
      }
    };
    loadA(0, R_E2, R_O2, 8);
    loadA(1, R_E2, R_O2, 4);
    mbar_wait(sb + B_W);
    const uint64_t d5 = mkdesc(cb + W5_OFF, 144, 576), d3 = mkdesc(cb + W3_OFF, 144, 576);
    const uint64_t d9 = mkdesc(cb + W9_OFF, 144, 576), d7 = mkdesc(cb + W7_OFF, 144, 576);
    const uint32_t y2d = cb + Y2_OFF + br * 3072 + ysw(32 * (5 - (lane >> 4)) + 16 * hf + (lane & 15));
    const uint32_t y3d = cb + Y3_OFF + br * 2048 + ysw(2 * (16 * hf + (lane & 15)) + (lane >> 4));
#define FAR4(N, ACC, BUF, DA, DB, OFF, FIRST)                                                            \
    wg_fence();                                                                                           \
    _Pragma("unroll") for (int k = 0; k < 4; k++) {                                                      \
      const uint32_t* a = A[BUF][k];                                                                      \
      wgmma_rs<N, 1>(ACC, a[0], a[1], a[2], a[3], ((k >> 1) ? DB : DA) + (k & 1) * 18 + (OFF), !(FIRST) || k); \
    }                                                                                                     \
    wg_commit();
    FAR4(48, e48, 0, d5, d3, 0, 1)
    wg_wait0();
    loadA(0, R_E2, R_O2, 0);
    stsm2(y2d - 5 * 512, PK2(e48, 20), PK2(e48, 22));
#pragma unroll
    for (int i = 0; i < 20; i++) e40[i] = FCPY(e48[i]);
    stage_done(sb, 2, lane);
    FAR4(40, e40, 1, d5, d3, 36, 0)
    wg_wait0();
    loadA(1, R_E3, R_O3, 8);
    stsm2(y2d - 4 * 512, PK2(e40, 16), PK2(e40, 18));
#pragma unroll
    for (int i = 0; i < 16; i++) e32[i] = FCPY(e40[i]);
    stage_done(sb, 3, lane);
    FAR4(32, e32, 0, d5, d3, 72, 0)
    FAR4(32, h32, 1, d9, d7, 0, 1)
    wg_wait1();
    loadA(0, R_E3, R_O3, 4);
    stsm4(y2d, PK2(e32, 0), PK2(e32, 2), PK2(e32, 4), PK2(e32, 6));
    stsm4(y2d - 2 * 512, PK2(e32, 8), PK2(e32, 10), PK2(e32, 12), PK2(e32, 14));
    stage_done(sb, 4, lane);
    STAMP(9);
    wg_wait0();
    stsm4(y3d, PK2(h32, 8), PK2(h32, 10), PK2(h32, 12), PK2(h32, 14));
#pragma unroll
    for (int i = 0; i < 8; i++) h16[i] = FCPY(h32[i]);
    stage_done(sb, 5, lane);
    FAR4(16, h16, 0, d9, d7, 72, 0)
#undef FAR4
    const uint32_t yo = sb + CH_OFF + (x & 3) * 4 + ysw(c);
    uint32_t ua[4], ub[4], ya[4], yb[4], a2[4], b2[4], a3[4], b3[4], s2[4];
    skip_terms(ua, ub, sb, x, dA, dB);
    {
      const int xa = x - 514, xb = x - 513, ca = xa >> 2, cb2 = xb >> 2;
      ld4ch(s2, sb + CH_OFF + U_OFF + (xa & 3) * 4 + (ca & 3) * U_CS + (63 - (ca >> 2)) * 16);
      ld4ch(a3, sb + CH_OFF + U_OFF + (xb & 3) * 4 + (cb2 & 3) * U_CS + (63 - (cb2 >> 2)) * 16);
#pragma unroll
      for (int k = 0; k < 4; k++) s2[k] = hadd2(s2[k], __byte_perm(s2[k], a3[k], 0x5432));
    }
    const uint32_t tag = lds32(sb + TAG_OFF);
    wg_wait0();
    stsm4(y3d + 1024, PK2(h16, 0), PK2(h16, 2), PK2(h16, 4), PK2(h16, 6));
    stage_done(sb, 6, lane);
    STAMP(10);
    const uint32_t g2 = gate_fin(p, gl, x, tag);
    mbar_wait(sb + B_ST + 8 * 4);
    const uint4 k0 = lds128(sb + K1024_OFF), k1 = lds128(sb + K1024_OFF + 16);
    const uint32_t kk[8] = {k0.x, k0.y, k0.z, k0.w, k1.x, k1.y, k1.z, k1.w};
    ld4ch(ya, yo + Y0_OFF); ld4ch(yb, yo + Y0_OFF + 4096);
    ld4ch(a2, yo + Y2_OFF - 1024); ld4ch(b2, yo + Y2_OFF - 1024 + 3072);
    mbar_wait(sb + B_ST + 8 * (5 + (ch >> 1)));
    STAMP(12);
    ld4ch(a3, yo + Y3_OFF - 2048); ld4ch(b3, yo + Y3_OFF - 2048 + 2048);
#pragma unroll
    for (int k = 0; k < 4; k++) {
      ya[k] = hadd2(ya[k], hadd2(hfma2(kk[2 * k], s2[k], a2[k]), a3[k]));
      yb[k] = hadd2(yb[k], hadd2(hfma2(kk[2 * k + 1], s2[k], b2[k]), b3[k]));
    }
    const uint4 r = mix(ya, yb, ua, ub, g2);
    if ((uint32_t)(ch & 1) != rank) send_box(sb, 2 + (ch >> 1), wtid, rank, r);
    else merge_box(sb, &tm_out, 2 + (ch >> 1), wtid, rank, oc0, r, 1 + ch);
  }
  STAMP(14);
  if (wtid == 0) asm volatile("cp.async.bulk.wait_group.read 0;" ::: "memory");
  STAMP(15); GT(1);
}

typedef CUresult (*EncodeFn)(CUtensorMap*, CUtensorMapDataType, cuuint32_t, void*, const cuuint64_t*, const cuuint64_t*,
                             const cuuint32_t*, const cuuint32_t*, CUtensorMapInterleave, CUtensorMapSwizzle,
                             CUtensorMapL2promotion, CUtensorMapFloatOOBfill);

}

extern "C" void kernel_launch(void* const* d_in, const int* in_sizes, int n_in, void* d_out, int out_size) {
  (void)in_sizes; (void)n_in; (void)out_size;
  typedef const __nv_bfloat16* bp;
  Params p;
  p.t[0] = (bp)d_in[10]; p.t[1] = (bp)d_in[11]; p.t[2] = (bp)d_in[12]; p.t[3] = (bp)d_in[13]; p.t[4] = (bp)d_in[14]; p.t[5] = nullptr;
  p.t[6] = (bp)d_in[1]; p.t[7] = (bp)d_in[2]; p.t[8] = (bp)d_in[5]; p.t[9] = (bp)d_in[6]; p.t[10] = (bp)d_in[7];
  p.t[11] = (bp)d_in[3]; p.t[12] = (bp)d_in[4]; p.t[13] = nullptr;
  p.u = (bp)d_in[0]; p.gw = (bp)d_in[16]; p.A_D = (bp)d_in[8]; p.B_D = (bp)d_in[15];
  static EncodeFn enc = nullptr;
  if (!enc) {
    cudaDriverEntryPointQueryResult qr;
    cudaGetDriverEntryPoint("cuTensorMapEncodeTiled", (void**)&enc, cudaEnableDefault, &qr);
    cudaFuncSetAttribute(ssm_kernel, cudaFuncAttributeMaxDynamicSharedMemorySize, SMEM_BYTES);
  }
  CUtensorMap tm_in, tm_out;
  {
    cuuint64_t gd[5] = {512, 2, 4, 4, 64};
    cuuint64_t gs[4] = {1024, 8192, 2048, 32768};
    cuuint32_t bx[5] = {8, 2, 4, 4, 32};
    cuuint32_t es[5] = {1, 1, 1, 1, 1};
    enc(&tm_in, CU_TENSOR_MAP_DATA_TYPE_BFLOAT16, 5, d_in[0], gd, gs, bx, es, CU_TENSOR_MAP_INTERLEAVE_NONE,
        CU_TENSOR_MAP_SWIZZLE_NONE, CU_TENSOR_MAP_L2_PROMOTION_NONE, CU_TENSOR_MAP_FLOAT_OOB_FILL_NONE);
  }
  {
    cuuint64_t gd[3] = {512, 1024, 2};
    cuuint64_t gs[2] = {2048, 1024};
    cuuint32_t bx[3] = {8, 128, 2};
    cuuint32_t es[3] = {1, 1, 1};
    enc(&tm_out, CU_TENSOR_MAP_DATA_TYPE_BFLOAT16, 3, d_out, gd, gs, bx, es, CU_TENSOR_MAP_INTERLEAVE_NONE,
        CU_TENSOR_MAP_SWIZZLE_NONE, CU_TENSOR_MAP_L2_PROMOTION_NONE, CU_TENSOR_MAP_FLOAT_OOB_FILL_NONE);
  }
  ssm_kernel<<<NCTA + NGATE, 640, SMEM_BYTES, cudaStreamPerThread>>>(p, tm_in, tm_out);
}
```

```cpp
#include <cuda_runtime.h>
#include <cuda.h>
#include <cuda_bf16.h>
#include <stdint.h>

namespace {
#define FCPY(x) __uint_as_float(opq(__float_as_uint(x), zz))

constexpr int L = 2048, D = 512, NM = 128;
constexpr int NCTA = 128;
constexpr int NGATE = 4;

constexpr int RAW_OFF = 0;
constexpr int XIN_OFF = 32768;
constexpr int SC2_OFF = XIN_OFF + 8192;
constexpr int BAR_OFF = SC2_OFF + 10240;
constexpr int CH_OFF = BAR_OFF + 256;
constexpr int U_CS = 1184;
constexpr int U_OFF = 0;
constexpr int R_OFF = 4736;
constexpr int RD_X0 = 565;
constexpr int RD_CS = 1216;
constexpr int RS_CS = 320;
constexpr int R_E2 = 2 * RD_CS, R_O2 = R_E2 + 2 * RS_CS, R_E3 = R_O2 + 2 * RS_CS, R_O3 = R_E3 + 2 * RS_CS;
constexpr int R_BR = R_O3 + 2 * RS_CS;
constexpr int W5_OFF = R_OFF + 2 * R_BR;
constexpr int W3_OFF = W5_OFF + 3456;
constexpr int W9_OFF = W3_OFF + 3456;
constexpr int W7_OFF = W9_OFF + 2304;
constexpr int Y0_OFF = W7_OFF + 2304;
constexpr int Y2_OFF = Y0_OFF + 8192, Y3_OFF = Y2_OFF + 6144;
constexpr int CH_BYTES = Y0_OFF + 18432 + 16;
constexpr int SCR_BYTES = 4608;
constexpr int SMEM_BYTES = CH_OFF + 4 * CH_BYTES;
static_assert(CH_BYTES % 128 == 16, "bank staggering of the channel blocks");
static_assert(SMEM_BYTES <= 232448, "smem");
constexpr int B_RAW = BAR_OFF, B_X = BAR_OFF + 8, B_U = BAR_OFF + 40, B_W = BAR_OFF + 48;
constexpr int TAG_OFF = BAR_OFF + 56;
constexpr int K1024_OFF = BAR_OFF + 64;
constexpr int B_ST = BAR_OFF + 96;

__device__ unsigned int g_gate[L];
__device__ unsigned int g_epoch;
__device__ unsigned int g_ticket;

#define STAMP(k)
#define GT(k)

struct Params {
  const __nv_bfloat16* t[14];
  const __nv_bfloat16 *u, *gw, *A_D, *B_D;
};

template <int N, int TB> __device__ __forceinline__ void wgmma_rs(float* d, uint32_t a0, uint32_t a1, uint32_t a2, uint32_t a3, uint64_t desc, int sc);
template <> __device__ __forceinline__ void wgmma_rs<64, 0>(float* d, uint32_t a0, uint32_t a1, uint32_t a2, uint32_t a3, uint64_t desc, int sc) {
  asm volatile("{\n.reg .pred p;\nsetp.ne.b32 p, %37, 0;\n"
    "wgmma.mma_async.sync.aligned.m64n64k16.f32.bf16.bf16 {%0,%1,%2,%3,%4,%5,%6,%7,%8,%9,%10,%11,%12,%13,%14,%15,%16,%17,%18,%19,%20,%21,%22,%23,%24,%25,%26,%27,%28,%29,%30,%31}, {%32,%33,%34,%35}, %36, p, 1, 1, 0;\n}"
    : "+f"(d[0]), "+f"(d[1]), "+f"(d[2]), "+f"(d[3]), "+f"(d[4]), "+f"(d[5]), "+f"(d[6]), "+f"(d[7]), "+f"(d[8]), "+f"(d[9]), "+f"(d[10]), "+f"(d[11]), "+f"(d[12]), "+f"(d[13]), "+f"(d[14]), "+f"(d[15]), "+f"(d[16]), "+f"(d[17]), "+f"(d[18]), "+f"(d[19]), "+f"(d[20]), "+f"(d[21]), "+f"(d[22]), "+f"(d[23]), "+f"(d[24]), "+f"(d[25]), "+f"(d[26]), "+f"(d[27]), "+f"(d[28]), "+f"(d[29]), "+f"(d[30]), "+f"(d[31]) : "r"(a0), "r"(a1), "r"(a2), "r"(a3), "l"(desc), "r"(sc));
}
template <> __device__ __forceinline__ void wgmma_rs<56, 0>(float* d, uint32_t a0, uint32_t a1, uint32_t a2, uint32_t a3, uint64_t desc, int sc) {
  asm volatile("{\n.reg .pred p;\nsetp.ne.b32 p, %33, 0;\n"
    "wgmma.mma_async.sync.aligned.m64n56k16.f32.bf16.bf16 {%0,%1,%2,%3,%4,%5,%6,%7,%8,%9,%10,%11,%12,%13,%14,%15,%16,%17,%18,%19,%20,%21,%22,%23,%24,%25,%26,%27}, {%28,%29,%30,%31}, %32, p, 1, 1, 0;\n}"
    : "+f"(d[0]), "+f"(d[1]), "+f"(d[2]), "+f"(d[3]), "+f"(d[4]), "+f"(d[5]), "+f"(d[6]), "+f"(d[7]), "+f"(d[8]), "+f"(d[9]), "+f"(d[10]), "+f"(d[11]), "+f"(d[12]), "+f"(d[13]), "+f"(d[14]), "+f"(d[15]), "+f"(d[16]), "+f"(d[17]), "+f"(d[18]), "+f"(d[19]), "+f"(d[20]), "+f"(d[21]), "+f"(d[22]), "+f"(d[23]), "+f"(d[24]), "+f"(d[25]), "+f"(d[26]), "+f"(d[27]) : "r"(a0), "r"(a1), "r"(a2), "r"(a3), "l"(desc), "r"(sc));
}
template <> __device__ __forceinline__ void wgmma_rs<48, 0>(float* d, uint32_t a0, uint32_t a1, uint32_t a2, uint32_t a3, uint64_t desc, int sc) {
  asm volatile("{\n.reg .pred p;\nsetp.ne.b32 p, %29, 0;\n"
    "wgmma.mma_async.sync.aligned.m64n48k16.f32.bf16.bf16 {%0,%1,%2,%3,%4,%5,%6,%7,%8,%9,%10,%11,%12,%13,%14,%15,%16,%17,%18,%19,%20,%21,%22,%23}, {%24,%25,%26,%27}, %28, p, 1, 1, 0;\n}"
    : "+f"(d[0]), "+f"(d[1]), "+f"(d[2]), "+f"(d[3]), "+f"(d[4]), "+f"(d[5]), "+f"(d[6]), "+f"(d[7]), "+f"(d[8]), "+f"(d[9]), "+f"(d[10]), "+f"(d[11]), "+f"(d[12]), "+f"(d[13]), "+f"(d[14]), "+f"(d[15]), "+f"(d[16]), "+f"(d[17]), "+f"(d[18]), "+f"(d[19]), "+f"(d[20]), "+f"(d[21]), "+f"(d[22]), "+f"(d[23]) : "r"(a0), "r"(a1), "r"(a2), "r"(a3), "l"(desc), "r"(sc));
}
template <> __device__ __forceinline__ void wgmma_rs<32, 0>(float* d, uint32_t a0, uint32_t a1, uint32_t a2, uint32_t a3, uint64_t desc, int sc) {
  asm volatile("{\n.reg .pred p;\nsetp.ne.b32 p, %21, 0;\n"
    "wgmma.mma_async.sync.aligned.m64n32k16.f32.bf16.bf16 {%0,%1,%2,%3,%4,%5,%6,%7,%8,%9,%10,%11,%12,%13,%14,%15}, {%16,%17,%18,%19}, %20, p, 1, 1, 0;\n}"
    : "+f"(d[0]), "+f"(d[1]), "+f"(d[2]), "+f"(d[3]), "+f"(d[4]), "+f"(d[5]), "+f"(d[6]), "+f"(d[7]), "+f"(d[8]), "+f"(d[9]), "+f"(d[10]), "+f"(d[11]), "+f"(d[12]), "+f"(d[13]), "+f"(d[14]), "+f"(d[15]) : "r"(a0), "r"(a1), "r"(a2), "r"(a3), "l"(desc), "r"(sc));
}
template <> __device__ __forceinline__ void wgmma_rs<48, 1>(float* d, uint32_t a0, uint32_t a1, uint32_t a2, uint32_t a3, uint64_t desc, int sc) {
  asm volatile("{\n.reg .pred p;\nsetp.ne.b32 p, %29, 0;\n"
    "wgmma.mma_async.sync.aligned.m64n48k16.f32.bf16.bf16 {%0,%1,%2,%3,%4,%5,%6,%7,%8,%9,%10,%11,%12,%13,%14,%15,%16,%17,%18,%19,%20,%21,%22,%23}, {%24,%25,%26,%27}, %28, p, 1, 1, 1;\n}"
    : "+f"(d[0]), "+f"(d[1]), "+f"(d[2]), "+f"(d[3]), "+f"(d[4]), "+f"(d[5]), "+f"(d[6]), "+f"(d[7]), "+f"(d[8]), "+f"(d[9]), "+f"(d[10]), "+f"(d[11]), "+f"(d[12]), "+f"(d[13]), "+f"(d[14]), "+f"(d[15]), "+f"(d[16]), "+f"(d[17]), "+f"(d[18]), "+f"(d[19]), "+f"(d[20]), "+f"(d[21]), "+f"(d[22]), "+f"(d[23]) : "r"(a0), "r"(a1), "r"(a2), "r"(a3), "l"(desc), "r"(sc));
}
template <> __device__ __forceinline__ void wgmma_rs<40, 1>(float* d, uint32_t a0, uint32_t a1, uint32_t a2, uint32_t a3, uint64_t desc, int sc) {
  asm volatile("{\n.reg .pred p;\nsetp.ne.b32 p, %25, 0;\n"
    "wgmma.mma_async.sync.aligned.m64n40k16.f32.bf16.bf16 {%0,%1,%2,%3,%4,%5,%6,%7,%8,%9,%10,%11,%12,%13,%14,%15,%16,%17,%18,%19}, {%20,%21,%22,%23}, %24, p, 1, 1, 1;\n}"
    : "+f"(d[0]), "+f"(d[1]), "+f"(d[2]), "+f"(d[3]), "+f"(d[4]), "+f"(d[5]), "+f"(d[6]), "+f"(d[7]), "+f"(d[8]), "+f"(d[9]), "+f"(d[10]), "+f"(d[11]), "+f"(d[12]), "+f"(d[13]), "+f"(d[14]), "+f"(d[15]), "+f"(d[16]), "+f"(d[17]), "+f"(d[18]), "+f"(d[19]) : "r"(a0), "r"(a1), "r"(a2), "r"(a3), "l"(desc), "r"(sc));
}
template <> __device__ __forceinline__ void wgmma_rs<32, 1>(float* d, uint32_t a0, uint32_t a1, uint32_t a2, uint32_t a3, uint64_t desc, int sc) {
  asm volatile("{\n.reg .pred p;\nsetp.ne.b32 p, %21, 0;\n"
    "wgmma.mma_async.sync.aligned.m64n32k16.f32.bf16.bf16 {%0,%1,%2,%3,%4,%5,%6,%7,%8,%9,%10,%11,%12,%13,%14,%15}, {%16,%17,%18,%19}, %20, p, 1, 1, 1;\n}"
    : "+f"(d[0]), "+f"(d[1]), "+f"(d[2]), "+f"(d[3]), "+f"(d[4]), "+f"(d[5]), "+f"(d[6]), "+f"(d[7]), "+f"(d[8]), "+f"(d[9]), "+f"(d[10]), "+f"(d[11]), "+f"(d[12]), "+f"(d[13]), "+f"(d[14]), "+f"(d[15]) : "r"(a0), "r"(a1), "r"(a2), "r"(a3), "l"(desc), "r"(sc));
}
template <> __device__ __forceinline__ void wgmma_rs<16, 1>(float* d, uint32_t a0, uint32_t a1, uint32_t a2, uint32_t a3, uint64_t desc, int sc) {
  asm volatile("{\n.reg .pred p;\nsetp.ne.b32 p, %13, 0;\n"
    "wgmma.mma_async.sync.aligned.m64n16k16.f32.bf16.bf16 {%0,%1,%2,%3,%4,%5,%6,%7}, {%8,%9,%10,%11}, %12, p, 1, 1, 1;\n}"
    : "+f"(d[0]), "+f"(d[1]), "+f"(d[2]), "+f"(d[3]), "+f"(d[4]), "+f"(d[5]), "+f"(d[6]), "+f"(d[7]) : "r"(a0), "r"(a1), "r"(a2), "r"(a3), "l"(desc), "r"(sc));
}

__device__ __forceinline__ uint32_t pack_bf16(float lo, float hi) {
  uint32_t r; asm("cvt.rn.bf16x2.f32 %0, %1, %2;" : "=r"(r) : "f"(hi), "f"(lo)); return r;
}
__device__ __forceinline__ float bf_lo(uint32_t v) { return __uint_as_float(v << 16); }
__device__ __forceinline__ float bf_hi(uint32_t v) { return __uint_as_float(v & 0xffff0000u); }
__device__ __forceinline__ float bf_round(float x) { return bf_lo(pack_bf16(x, 0.f)); }
__device__ __forceinline__ uint32_t hmul2(uint32_t a, uint32_t b) { uint32_t r; asm("mul.rn.bf16x2 %0, %1, %2;" : "=r"(r) : "r"(a), "r"(b)); return r; }
__device__ __forceinline__ uint32_t hadd2(uint32_t a, uint32_t b) { uint32_t r; asm("add.rn.bf16x2 %0, %1, %2;" : "=r"(r) : "r"(a), "r"(b)); return r; }
__device__ __forceinline__ uint32_t hsub2(uint32_t a, uint32_t b) { uint32_t r; asm("sub.rn.bf16x2 %0, %1, %2;" : "=r"(r) : "r"(a), "r"(b)); return r; }
__device__ __forceinline__ uint32_t hfma2(uint32_t a, uint32_t b, uint32_t c) { uint32_t r; asm("fma.rn.bf16x2 %0, %1, %2, %3;" : "=r"(r) : "r"(a), "r"(b), "r"(c)); return r; }

__device__ __forceinline__ void sts16(uint32_t a, uint32_t v) { asm volatile("st.shared.b16 [%0], %1;" ::"r"(a), "h"((unsigned short)v) : "memory"); }
__device__ __forceinline__ void sts32(uint32_t a, uint32_t v) { asm volatile("st.shared.b32 [%0], %1;" ::"r"(a), "r"(v) : "memory"); }
__device__ __forceinline__ void sts64(uint32_t a, uint32_t x, uint32_t y) { asm volatile("st.shared.v2.b32 [%0], {%1,%2};" ::"r"(a), "r"(x), "r"(y) : "memory"); }
__device__ __forceinline__ void sts128(uint32_t a, uint32_t x, uint32_t y, uint32_t z, uint32_t w) {
  asm volatile("st.shared.v4.b32 [%0], {%1,%2,%3,%4};" ::"r"(a), "r"(x), "r"(y), "r"(z), "r"(w) : "memory");
}
__device__ __forceinline__ uint32_t lds32(uint32_t a) { uint32_t v; asm volatile("ld.shared.b32 %0, [%1];" : "=r"(v) : "r"(a) : "memory"); return v; }
__device__ __forceinline__ uint2 lds64(uint32_t a) { uint2 v; asm volatile("ld.shared.v2.b32 {%0,%1}, [%2];" : "=r"(v.x), "=r"(v.y) : "r"(a) : "memory"); return v; }
__device__ __forceinline__ uint4 lds128(uint32_t a) {
  uint4 v; asm volatile("ld.shared.v4.b32 {%0,%1,%2,%3}, [%4];" : "=r"(v.x), "=r"(v.y), "=r"(v.z), "=r"(v.w) : "r"(a) : "memory"); return v;
}
__device__ __forceinline__ uint4 ldg128(const void* a) {
  uint4 v; asm volatile("ld.global.nc.v4.b32 {%0,%1,%2,%3}, [%4];" : "=r"(v.x), "=r"(v.y), "=r"(v.z), "=r"(v.w) : "l"(a) : "memory"); return v;
}
__device__ __forceinline__ uint2 ldg64(const void* a) {
  uint2 v; asm volatile("ld.global.nc.v2.b32 {%0,%1}, [%2];" : "=r"(v.x), "=r"(v.y) : "l"(a) : "memory"); return v;
}
__device__ __forceinline__ void ldsm4(uint32_t a, uint32_t& r0, uint32_t& r1, uint32_t& r2, uint32_t& r3) {
  asm volatile("ldmatrix.sync.aligned.m8n8.x4.shared.b16 {%0,%1,%2,%3}, [%4];" : "=r"(r0), "=r"(r1), "=r"(r2), "=r"(r3) : "r"(a) : "memory");
}
__device__ __forceinline__ void ldsm4t(uint32_t a, uint32_t& r0, uint32_t& r1, uint32_t& r2, uint32_t& r3) {
  asm volatile("ldmatrix.sync.aligned.m8n8.x4.trans.shared.b16 {%0,%1,%2,%3}, [%4];" : "=r"(r0), "=r"(r1), "=r"(r2), "=r"(r3) : "r"(a) : "memory");
}
__device__ __forceinline__ void stsm4(uint32_t a, uint32_t r0, uint32_t r1, uint32_t r2, uint32_t r3) {
  asm volatile("stmatrix.sync.aligned.m8n8.x4.shared.b16 [%0], {%1,%2,%3,%4};" ::"r"(a), "r"(r0), "r"(r1), "r"(r2), "r"(r3) : "memory");
}
__device__ __forceinline__ void stsm4t(uint32_t a, uint32_t r0, uint32_t r1, uint32_t r2, uint32_t r3) {
  asm volatile("stmatrix.sync.aligned.m8n8.x4.trans.shared.b16 [%0], {%1,%2,%3,%4};" ::"r"(a), "r"(r0), "r"(r1), "r"(r2), "r"(r3) : "memory");
}
__device__ __forceinline__ void stsm2(uint32_t a, uint32_t r0, uint32_t r1) {
  asm volatile("stmatrix.sync.aligned.m8n8.x2.shared.b16 [%0], {%1,%2};" ::"r"(a), "r"(r0), "r"(r1) : "memory");
}
__device__ __forceinline__ void stsm2t(uint32_t a, uint32_t r0, uint32_t r1) {
  asm volatile("stmatrix.sync.aligned.m8n8.x2.trans.shared.b16 [%0], {%1,%2};" ::"r"(a), "r"(r0), "r"(r1) : "memory");
}
__device__ __forceinline__ void mma16816(float* c, uint32_t a0, uint32_t a1, uint32_t a2, uint32_t a3, uint32_t b0, uint32_t b1) {
  asm("mma.sync.aligned.m16n8k16.row.col.f32.bf16.bf16.f32 {%0,%1,%2,%3}, {%4,%5,%6,%7}, {%8,%9}, {%0,%1,%2,%3};"
      : "+f"(c[0]), "+f"(c[1]), "+f"(c[2]), "+f"(c[3]) : "r"(a0), "r"(a1), "r"(a2), "r"(a3), "r"(b0), "r"(b1));
}
__device__ __forceinline__ void bar_sync(int id, int n) { asm volatile("bar.sync %0, %1;" ::"r"(id), "r"(n) : "memory"); }
__device__ __forceinline__ void bar_arrive(int id, int n) { asm volatile("bar.arrive %0, %1;" ::"r"(id), "r"(n) : "memory"); }
__device__ __forceinline__ void wg_fence() { asm volatile("wgmma.fence.sync.aligned;" ::: "memory"); }
__device__ __forceinline__ void wg_commit() { asm volatile("wgmma.commit_group.sync.aligned;" ::: "memory"); }
__device__ __forceinline__ void wg_wait0() { asm volatile("wgmma.wait_group.sync.aligned 0;" ::: "memory"); }
__device__ __forceinline__ void wg_wait1() { asm volatile("wgmma.wait_group.sync.aligned 1;" ::: "memory"); }
__device__ __forceinline__ void fence_async() { asm volatile("fence.proxy.async.shared::cta;" ::: "memory"); }
__device__ __forceinline__ uint32_t opq(uint32_t x, uint32_t z) { uint32_t r; asm volatile("xor.b32 %0, %1, %2;" : "=r"(r) : "r"(x), "r"(z)); return r; }
__device__ __forceinline__ uint64_t mkdesc(uint32_t addr, uint32_t lbo, uint32_t sbo) {
  return (uint64_t)((addr & 0x3FFFF) >> 4) | ((uint64_t)(lbo >> 4) << 16) | ((uint64_t)(sbo >> 4) << 32);
}
__device__ __forceinline__ uint32_t mapa(uint32_t a, uint32_t rank) {
  uint32_t r; asm("mapa.shared::cluster.u32 %0, %1, %2;" : "=r"(r) : "r"(a), "r"(rank)); return r;
}
__device__ __forceinline__ void mbar_init_expect(uint32_t bar, uint32_t bytes) {
  asm volatile("mbarrier.init.shared::cta.b64 [%0], 1;" ::"r"(bar) : "memory");
  asm volatile("mbarrier.arrive.expect_tx.shared::cta.b64 _, [%0], %1;" ::"r"(bar), "r"(bytes) : "memory");
}
__device__ __forceinline__ void mbar_wait(uint32_t bar) {
#pragma unroll 1
  for (int it = 0; it < (1 << 22); it++) {
    uint32_t ok;
    asm volatile("{\n.reg .pred p;\nmbarrier.try_wait.parity.acquire.cluster.shared::cta.b64 p, [%1], 0;\nselp.u32 %0, 1, 0, p;\n}"
                 : "=r"(ok) : "r"(bar) : "memory");
    if (ok) return;
  }
  __trap();
}
__device__ __forceinline__ void st_async4(uint32_t a, uint32_t bar, uint32_t x, uint32_t y, uint32_t z, uint32_t w) {
  asm volatile("st.async.weak.shared::cluster.mbarrier::complete_tx::bytes.v4.b32 [%0], {%2,%3,%4,%5}, [%1];"
               ::"r"(a), "r"(bar), "r"(x), "r"(y), "r"(z), "r"(w) : "memory");
}

struct cf { float re, im; };
__device__ __forceinline__ cf cmul(cf a, cf b) { return {fmaf(a.re, b.re, -a.im * b.im), fmaf(a.re, b.im, a.im * b.re)}; }
__device__ __forceinline__ cf csq(cf a) { return {fmaf(a.re, a.re, -a.im * a.im), (a.re + a.re) * a.im}; }
__device__ __forceinline__ cf cexp_p(float xl, float y, float p) {
  float mag; asm("ex2.approx.ftz.f32 %0, %1;" : "=f"(mag) : "f"(xl * p));
  const float th = y * p;
  const float k = __fadd_rn(fmaf(th, 0.15915494309189535f, 12582912.f), -12582912.f);
  float r = fmaf(k, -6.2831854820251465f, th);
  r = fmaf(k, 1.7484555314695172e-07f, r);
  return {mag * __cosf(r), mag * __sinf(r)};
}
__device__ __forceinline__ uint32_t ysw(int c) { return (uint32_t)(c ^ ((c >> 3) & 3)) * 16u; }

#define CMUL2(OR, OI, xr, xi, yr, yi, nyi) do { OR = hfma2(xr, yr, hmul2(xi, nyi)); OI = hfma2(xr, yi, hmul2(xi, yr)); } while (0)

__device__ __forceinline__ uint32_t gate_slow(const __nv_bfloat16* u, const __nv_bfloat16* gw, int row) {
  float s = 0.f;
  const uint32_t* xr = (const uint32_t*)(u + (size_t)row * D);
  const uint32_t* wr = (const uint32_t*)gw;
#pragma unroll 1
  for (int j = 0; j < D / 2; j++) { const uint32_t pr = hmul2(xr[j], wr[j]); s += bf_lo(pr); s += bf_hi(pr); }
  s = bf_round(s);
  return pack_bf16(1.f / (1.f + expf(-s)), 0.f);
}

__device__ __forceinline__ uint2 gate_ld(int x) {
  uint2 gv;
  asm volatile("ld.relaxed.gpu.global.v2.u32 {%0,%1}, [%2];" : "=r"(gv.x), "=r"(gv.y) : "l"(g_gate + x * 2) : "memory");
  return gv;
}
__device__ __noinline__ uint32_t gate_poll(const Params* pp, int x, uint32_t tag) {
  uint2 gv;
#pragma unroll 1
  for (int spins = 0; spins < (1 << 16); spins++) {
    gv = gate_ld(x);
    if ((gv.x >> 16) == tag && (gv.y >> 16) == tag) return __byte_perm(gv.x, gv.y, 0x5410);
  }
  return __byte_perm(gate_slow(pp->u, pp->gw, x * 2), gate_slow(pp->u, pp->gw, x * 2 + 1), 0x5410);
}
__device__ __forceinline__ uint32_t gate_fin(const Params& p, uint2 gv, int x, uint32_t tag) {
  if ((gv.x >> 16) == tag && (gv.y >> 16) == tag) return __byte_perm(gv.x, gv.y, 0x5410);
  return gate_poll(&p, x, tag);
}

__device__ __forceinline__ void ld4ch(uint32_t* v, uint32_t addr) {
#pragma unroll
  for (int k = 0; k < 4; k++) v[k] = lds32(addr + k * CH_BYTES);
}
__device__ __forceinline__ void skip_terms(uint32_t* ua, uint32_t* ub, uint32_t sb, int x, uint2 dA, uint2 dB) {
  const int c = x >> 2;
  uint32_t uu[4];
  ld4ch(uu, sb + CH_OFF + (x & 3) * 4 + U_OFF + (c & 3) * U_CS + (63 - (c >> 2)) * 16);
#pragma unroll
  for (int k = 0; k < 4; k++) {
    ua[k] = hmul2(uu[k], __byte_perm((k & 2) ? dA.y : dA.x, 0, (k & 1) ? 0x3232 : 0x1010));
    ub[k] = hmul2(uu[k], __byte_perm((k & 2) ? dB.y : dB.x, 0, (k & 1) ? 0x3232 : 0x1010));
  }
}
__device__ __forceinline__ uint4 mix(const uint32_t* a, const uint32_t* b, const uint32_t* ua, const uint32_t* ub, uint32_t g2) {
  const uint32_t h2 = hsub2(0x3f803f80u, g2);
  uint32_t o[4];
#pragma unroll
  for (int k = 0; k < 4; k++) o[k] = hadd2(hmul2(g2, hadd2(a[k], ua[k])), hmul2(h2, hadd2(b[k], ub[k])));
  return make_uint4(__byte_perm(o[0], o[1], 0x5410), __byte_perm(o[2], o[3], 0x5410), __byte_perm(o[0], o[1], 0x7632), __byte_perm(o[2], o[3], 0x7632));
}
__device__ __forceinline__ void send_box(uint32_t sb, int slot, int wtid, uint32_t rank, uint4 r) {
  st_async4(mapa(sb + XIN_OFF + slot * 2048 + wtid * 16, rank ^ 1), mapa(sb + B_X + slot * 8, rank ^ 1), r.x, r.y, r.z, r.w);
}
__device__ __forceinline__ void merge_rows(uint32_t st, uint32_t rank, uint4 r, uint4 q) {
  const uint4 lo = rank ? q : r, hi = rank ? r : q;
  sts128(st, lo.x, lo.y, hi.x, hi.y); sts128(st + 2048, lo.z, lo.w, hi.z, hi.w);
}
__device__ __forceinline__ void merge_box(uint32_t sb, const CUtensorMap* tm_out, int slot, int wtid, uint32_t rank, int oc0, uint4 r, int barid) {
  const uint32_t st = sb + RAW_OFF + slot * 4096 + wtid * 16;
  mbar_wait(sb + B_X + slot * 8);
  merge_rows(st, rank, r, lds128(sb + XIN_OFF + slot * 2048 + wtid * 16));
  fence_async();
  bar_sync(barid, 128);
  if (wtid == 0) {
    asm volatile("cp.async.bulk.tensor.3d.global.shared::cta.bulk_group [%0, {%2, %3, %4}], [%1];"
                 ::"l"(tm_out), "r"(sb + RAW_OFF + slot * 4096), "r"(oc0), "r"((2 * slot + (int)rank) * 128), "r"(0) : "memory");
    asm volatile("cp.async.bulk.commit_group;" ::: "memory");
  }
}

__device__ __forceinline__ uint32_t band2(int e, int lo, int hi) {
  uint32_t r = ((uint32_t)(e - lo) <= (uint32_t)(hi - lo) ? 0x3f80u : 0u) | ((uint32_t)(e - 1 - lo) <= (uint32_t)(hi - lo) ? 0x3f800000u : 0u);
  asm volatile("" : "+r"(r));
  return r;
}

__device__ __forceinline__ void stage_done(uint32_t sb, int stage, int lane) {
  __syncwarp();
  if (lane == 0) asm volatile("mbarrier.arrive.shared::cta.b64 _, [%0];" ::"r"(sb + B_ST + 8 * stage) : "memory");
}
#define PK2(v, i) pack_bf16(v[i], v[(i) + 1])

__device__ __forceinline__ void conv_dense(uint32_t sb, uint32_t cb, uint32_t zz) {
  const int lane = threadIdx.x & 31, wq = (threadIdx.x >> 5) & 3, br = wq >> 1, hf = wq & 1, g = lane >> 2, t = lane & 3;
  const uint32_t rb = cb + R_OFF + br * R_BR;
  const int eo = 16 * hf + g - 2 * t;
  const int x0 = RD_X0 - (eo + 536);
  const uint32_t fa = rb + ((g & 1) ? 2 * x0 : RD_CS + 2 * x0 + 2);
  const uint64_t ub = mkdesc(cb + U_OFF, U_CS, 128);
  const uint32_t yd = cb + Y0_OFF + br * 4096 + ysw(4 * (63 - 8 * (lane >> 4) - (lane & 7)) + 2 * hf + ((lane >> 3) & 1));
  uint32_t A[2][4][4];
  float e64[32], e56[28], e48[24];
  auto loadA = [&](int j) {
#pragma unroll
    for (int k = 0; k < 4; k++) {
      const int s = 34 - 4 * j - k;
      if (s >= 0) {
        if (k == 0 && j == 0) A[0][0][2] = lds32(fa + (2 * s + 2) * 16);
        A[j & 1][k][0] = lds32(fa + (2 * s + 1) * 16);
        A[j & 1][k][1] = lds32(fa + (2 * s) * 16);
      }
    }
#pragma unroll
    for (int k = 0; k < 4; k++) {
      if (34 - 4 * j - k >= 0) {
        A[j & 1][k][3] = A[j & 1][k][0];
        if (k) A[j & 1][k][2] = A[j & 1][k - 1][1];
        else if (j) A[j & 1][0][2] = A[(j - 1) & 1][3][1];
      }
    }
  };
  loadA(0); loadA(1);
#pragma unroll
  for (int j = 0; j < 9; j++) {
    if (j == 4) {
      wg_wait0();
      stsm2t(yd - 7 * 512, PK2(e64, 28), PK2(e64, 30));
#pragma unroll
      for (int i = 0; i < 28; i++) e56[i] = FCPY(e64[i]);
      stage_done(sb, 0, lane);
    }
    if (j == 8) {
      wg_wait0();
      stsm2t(yd - 6 * 512, PK2(e56, 24), PK2(e56, 26));
#pragma unroll
      for (int i = 0; i < 24; i++) e48[i] = FCPY(e56[i]);
      stage_done(sb, 1, lane);
    }
    wg_fence();
#pragma unroll
    for (int k = 0; k < 4; k++) {
      const int s = 34 - 4 * j - k;
      if (s >= 0) {
        const int o = 2 * s - 66 + 128;
        const int cc = o & 3, rs = (o >> 2) - 32;
        const uint64_t desc = ub + (uint64_t)((cc * U_CS - rs * 16) >> 4);
        const uint32_t* a = A[j & 1][k];
        if (j < 4) wgmma_rs<64, 0>(e64, a[0], a[1], a[2], a[3], desc, s != 34);
        else if (j < 8) wgmma_rs<56, 0>(e56, a[0], a[1], a[2], a[3], desc, 1);
        else wgmma_rs<48, 0>(e48, a[0], a[1], a[2], a[3], desc, 1);
      }
    }
    wg_commit();
    if (j >= 1 && j < 8) { wg_wait1(); loadA(j + 1); }
  }
  wg_wait0();
#pragma unroll
  for (int i = 0; i < 6; i += 2) stsm4t(yd - i * 512, PK2(e48, 4 * i), PK2(e48, 4 * i + 2), PK2(e48, 4 * i + 4), PK2(e48, 4 * i + 6));
}

__device__ __noinline__ void gate_cta(const Params* pp) {
  const __nv_bfloat16 *u = pp->u, *gw = pp->gw;
  const int lane = threadIdx.x & 31;
  unsigned int epoch;
  asm volatile("ld.relaxed.gpu.global.u32 %0, [%1];" : "=r"(epoch) : "l"(&g_epoch) : "memory");
  const uint4 gw0 = ldg128(gw + lane * 8), gw1 = ldg128(gw + 256 + lane * 8);
  const uint32_t ws[8] = {gw0.x, gw0.y, gw0.z, gw0.w, gw1.x, gw1.y, gw1.z, gw1.w};
  const uint32_t tag = (epoch + 1) & 0xffffu;
  uint4 gx[4][2], nx[4][2];
  int grow = (blockIdx.x * 20 + (threadIdx.x >> 5)) * 4;
#pragma unroll
  for (int i = 0; i < 4; i++) {
    nx[i][0] = ldg128(u + (size_t)(grow + i) * D + lane * 8);
    nx[i][1] = ldg128(u + (size_t)(grow + i) * D + 256 + lane * 8);
  }
#pragma unroll 1
  for (; grow < L; grow += 80 * NGATE) {
    const int nrow = min(grow + 80 * NGATE, L - 4);
#pragma unroll
    for (int i = 0; i < 4; i++) {
      gx[i][0] = nx[i][0]; gx[i][1] = nx[i][1];
      nx[i][0] = ldg128(u + (size_t)(nrow + i) * D + lane * 8);
      nx[i][1] = ldg128(u + (size_t)(nrow + i) * D + 256 + lane * 8);
    }
    float c[2][4];
#pragma unroll
    for (int i = 0; i < 2; i++) {
      const uint4 *x = gx[2 * i], *y = gx[2 * i + 1];
      const uint32_t xs[8] = {x[0].x, x[0].y, x[0].z, x[0].w, x[1].x, x[1].y, x[1].z, x[1].w};
      const uint32_t ys[8] = {y[0].x, y[0].y, y[0].z, y[0].w, y[1].x, y[1].y, y[1].z, y[1].w};
      c[i][0] = c[i][1] = c[i][2] = c[i][3] = 0.f;
#pragma unroll
      for (int j = 0; j < 8; j += 2)
        mma16816(c[i], hmul2(xs[j], ws[j]), hmul2(ys[j], ws[j]), hmul2(xs[j + 1], ws[j + 1]), hmul2(ys[j + 1], ws[j + 1]), 0x3f803f80u, 0x3f803f80u);
    }
    float s = (lane & 2) ? ((lane & 1) ? c[1][2] : c[1][0]) : ((lane & 1) ? c[0][2] : c[0][0]);
#pragma unroll
    for (int o = 4; o < 32; o <<= 1) s += __shfl_xor_sync(0xffffffffu, s, o);
    s = bf_round(s);
    const float gv = 1.f / (1.f + expf(-s));
    const uint32_t w = (tag << 16) | (pack_bf16(gv, 0.f) & 0xffffu);
    if (lane < 4) asm volatile("st.relaxed.gpu.global.u32 [%0], %1;" ::"l"(&g_gate[grow + lane]), "r"(w) : "memory");
  }
  __syncthreads();
  if (threadIdx.x == 0 && atomicAdd(&g_ticket, 1u) == NCTA + NGATE - 1) { g_ticket = 0; g_epoch = epoch + 1; }
}

__global__ void __cluster_dims__(2, 1, 1) __launch_bounds__(640, 1)
ssm_kernel(const __grid_constant__ Params p, const __grid_constant__ CUtensorMap tm_in, const __grid_constant__ CUtensorMap tm_out) {
  extern __shared__ __align__(1024) unsigned char smem_raw[];
  const uint32_t sb = (uint32_t)__cvta_generic_to_shared(smem_raw);
  const int tid = threadIdx.x, lane = tid & 31;
  const int warp = __shfl_sync(0xffffffffu, tid >> 5, 0);
  const int ch = warp >> 2, wq = warp & 3, br = wq >> 1, hf = wq & 1;
  const int g = lane >> 2, t = lane & 3;
  if (__builtin_expect(blockIdx.x < NGATE, 0)) { gate_cta(&p); return; }
  const int bid = blockIdx.x - NGATE;
  const int d = bid * 4 + ch;
  const uint32_t rank = blockIdx.x & 1;
  const uint32_t cb = sb + CH_OFF + ch * CH_BYTES;
  const int wtid = tid & 127;
  const int oc0 = (bid >> 1) * 8;
  STAMP(0); GT(0);

  if (warp >= 16) {
    if (wtid == 0) {
      mbar_init_expect(sb + B_RAW, 32768);
#pragma unroll
      for (int i = 0; i < 4; i++) mbar_init_expect(sb + B_X + 8 * i, 2048);
      asm volatile("mbarrier.init.shared::cta.b64 [%0], 128;" ::"r"(sb + B_U) : "memory");
      asm volatile("mbarrier.init.shared::cta.b64 [%0], 128;" ::"r"(sb + B_W) : "memory");
#pragma unroll
      for (int i = 0; i < 7; i++) asm volatile("mbarrier.init.shared::cta.b64 [%0], 16;" ::"r"(sb + B_ST + 8 * i) : "memory");
      asm volatile("fence.mbarrier_init.release.cluster;" ::: "memory");
      asm volatile("fence.proxy.async.shared::cta;" ::: "memory");
    }
    __syncwarp();
    asm volatile("barrier.cluster.arrive.relaxed.aligned;" ::: "memory");
    unsigned int epoch;
    asm volatile("ld.relaxed.gpu.global.u32 %0, [%1];" : "=r"(epoch) : "l"(&g_epoch) : "memory");
    asm volatile("barrier.cluster.wait.aligned;" ::: "memory");
    if (wtid == 0) {
      asm volatile("cp.async.bulk.tensor.5d.shared::cluster.global.mbarrier::complete_tx::bytes.multicast::cluster [%0], [%1, {%3, %4, %4, %4, %5}], [%2], %6;"
                   ::"r"(sb + RAW_OFF + rank * 16384), "l"(&tm_in), "r"(sb + B_RAW), "r"(oc0), "r"(0), "r"((int)rank * 32), "h"((unsigned short)3) : "memory");
    }
    sts128(sb + CH_OFF + wq * CH_BYTES + U_OFF + (lane >> 3) * U_CS + (64 + (lane & 7)) * 16, 0, 0, 0, 0);
    const uint2 dA = ldg64(p.A_D + bid * 4), dB = ldg64(p.B_D + bid * 4);
    uint32_t BA[3][4], BB[4][4];
    {
      const int l1 = br ? 3 : 6, h1 = br ? 5 : 10, l2 = br ? 5 : 12, h2 = br ? 11 : 20;
#pragma unroll
      for (int i = 0; i < 4; i++) {
        const int e = 16 * hf + g - 2 * t + 32 - 16 * i;
        BB[i][0] = band2(e, l2, h2); BB[i][1] = band2(e + 8, l2, h2); BB[i][2] = band2(e - 8, l2, h2); BB[i][3] = BB[i][0];
        if (i) { BA[i - 1][0] = band2(e, l1, h1); BA[i - 1][1] = band2(e + 8, l1, h1); BA[i - 1][2] = band2(e - 8, l1, h1); BA[i - 1][3] = BA[i - 1][0]; }
      }
    }
    const uint32_t tag = (epoch + 1) & 0xffffu;
    if (wtid == 0) sts32(sb + TAG_OFF, tag);
    STAMP(3);
    mbar_wait(sb + B_RAW);
    STAMP(4);
    {
      const uint32_t dst = sb + CH_OFF + (g & 3) * CH_BYTES + U_OFF + t * U_CS + (63 - wq * 16) * 16;
#pragma unroll
      for (int h = 0; h < 2; h++) {
        uint32_t r[8][4];
#pragma unroll
        for (int i = 0; i < 8; i++) ldsm4t(sb + RAW_OFF + (wq * 16 + h * 8 + i) * 512 + lane * 16, r[i][0], r[i][1], r[i][2], r[i][3]);
        if ((uint32_t)(g >> 2) == rank) {
#pragma unroll
          for (int i = 0; i < 8; i++) sts128(dst - (h * 8 + i) * 16, r[i][0], r[i][1], r[i][2], r[i][3]);
        }
      }
    }
    fence_async();
    asm volatile("mbarrier.arrive.shared::cta.b64 _, [%0];" ::"r"(sb + B_U) : "memory");
    bar_sync(5, 128);
    STAMP(5);
    {
      const int mrow = lane & 7, mi = lane >> 3;
      const uint64_t ub0 = mkdesc(sb + CH_OFF + U_OFF, U_CS, 128);
      uint32_t wa, wb;
      {
        const int c = 4 * (47 - 8 * (mi >> 1) - mrow) + 2 * hf + (mi & 1);
        wa = sb + CH_OFF + (br ? W3_OFF : W5_OFF) + (5 - (c >> 5)) * 576 + ((c & 31) >> 3) * 144 + (c & 7) * 16;
        const int c2 = c - 64, pp = c2 >> 1;
        wb = sb + CH_OFF + (br ? W7_OFF : W9_OFF) + (1 - (pp >> 5)) * 1152 + (c2 & 1) * 576 + ((pp & 31) >> 3) * 144 + (pp & 7) * 16;
      }
      {
        float w1[24];
#pragma unroll
        for (int i = 0; i < 24; i++) w1[i] = 0.f;
#pragma unroll 1
        for (int k = 0; k < 4; k++) {
          wg_fence();
#pragma unroll
          for (int i = 0; i < 3; i++)
            wgmma_rs<48, 0>(w1, BA[i][0], BA[i][1], BA[i][2], BA[i][3],
                            ub0 + (uint64_t)((k * CH_BYTES + ((2 * i + 2) & 3) * U_CS + (16 + (i == 0)) * 16) >> 4), i);
          wg_commit();
          wg_wait0();
#pragma unroll
          for (int i = 0; i < 3; i++) stsm4t(wa + k * CH_BYTES + i * 1152, PK2(w1, 8 * i), PK2(w1, 8 * i + 2), PK2(w1, 8 * i + 4), PK2(w1, 8 * i + 6));
        }
      }
      {
        float w2[2][16];
#pragma unroll
        for (int i = 0; i < 16; i++) { w2[0][i] = 0.f; w2[1][i] = 0.f; }
#pragma unroll 1
        for (int kp = 0; kp < 2; kp++) {
          wg_fence();
#pragma unroll
          for (int k = 0; k < 2; k++)
#pragma unroll
            for (int i = 0; i < 4; i++)
              wgmma_rs<32, 0>(w2[k], BB[i][0], BB[i][1], BB[i][2], BB[i][3],
                              ub0 + (uint64_t)(((2 * kp + k) * CH_BYTES + ((2 * i) & 3) * U_CS + (32 + (i < 2)) * 16) >> 4), i);
          wg_commit();
          wg_wait0();
#pragma unroll
          for (int k = 0; k < 2; k++)
#pragma unroll
            for (int i = 0; i < 2; i++)
              stsm4t(wb + (2 * kp + k) * CH_BYTES + i * 1152, PK2(w2[k], 8 * i), PK2(w2[k], 8 * i + 2), PK2(w2[k], 8 * i + 4), PK2(w2[k], 8 * i + 6));
        }
      }
    }
    fence_async();
    asm volatile("mbarrier.arrive.shared::cta.b64 _, [%0];" ::"r"(sb + B_W) : "memory");
    STAMP(7);
    {
      const int bsel = (int)rank ^ br ^ 1, xl = wtid & 63;
      uint2 gl[4];
      uint32_t ua[4][4], ub[4][4];
#pragma unroll
      for (int i = 0; i < 4; i++) skip_terms(ua[i], ub[i], sb, (2 * (i >> 1) + bsel) * 128 + (i & 1) * 64 + xl, dA, dB);
      const uint32_t yo = sb + CH_OFF + (xl & 3) * 4 + ysw(xl >> 2) + bsel * 512;
#pragma unroll
      for (int i = 0; i < 2; i++) gl[i] = gate_ld(bsel * 128 + i * 64 + xl);
#pragma unroll
      for (int slot = 0; slot < 2; slot++) {
        const int box = 2 * slot + bsel;
        uint32_t g2[2], ya[2][4], yb[2][4];
#pragma unroll
        for (int h = 0; h < 2; h++) g2[h] = gate_fin(p, gl[2 * slot + h], box * 128 + h * 64 + xl, tag);
        mbar_wait(sb + B_ST + 8 * box);
        STAMP(8 + slot);
        if (slot == 0) { gl[2] = gate_ld((2 + bsel) * 128 + xl); gl[3] = gate_ld((2 + bsel) * 128 + 64 + xl); }
#pragma unroll
        for (int h = 0; h < 2; h++) {
          const uint32_t yh = (yo ^ (h * 32)) + h * 256 + slot * 1024;
          ld4ch(ya[h], yh + Y0_OFF); ld4ch(yb[h], yh + Y0_OFF + 4096);
          if (slot) {
            uint32_t a2[4], b2[4];
            ld4ch(a2, yh + Y2_OFF - 1024); ld4ch(b2, yh + Y2_OFF - 1024 + 3072);
#pragma unroll
            for (int k = 0; k < 4; k++) { ya[h][k] = hadd2(ya[h][k], a2[k]); yb[h][k] = hadd2(yb[h][k], b2[k]); }
          }
        }
        const uint4 r0 = mix(ya[0], yb[0], ua[2 * slot], ub[2 * slot], g2[0]), r1 = mix(ya[1], yb[1], ua[2 * slot + 1], ub[2 * slot + 1], g2[1]);
        if (br == 0) { send_box(sb, slot, xl, rank, r0); send_box(sb, slot, xl + 64, rank, r1); }
        else {
          const uint32_t st = sb + RAW_OFF + slot * 4096 + xl * 16, xin = sb + XIN_OFF + slot * 2048 + xl * 16;
          mbar_wait(sb + B_X + slot * 8);
          const uint4 q0 = lds128(xin), q1 = lds128(xin + 1024);
          merge_rows(st, rank, r0, q0); merge_rows(st + 1024, rank, r1, q1);
          fence_async();
          bar_sync(6, 64);
          if (xl == 0) {
            asm volatile("cp.async.bulk.tensor.3d.global.shared::cta.bulk_group [%0, {%2, %3, %4}], [%1];"
                         ::"l"(&tm_out), "r"(sb + RAW_OFF + slot * 4096), "r"(oc0), "r"(box * 128), "r"(0) : "memory");
            asm volatile("cp.async.bulk.commit_group;" ::: "memory");
          }
        }
        STAMP(10 + slot);
      }
    }
    if (wtid == 0 && atomicAdd(&g_ticket, 1u) == NCTA + NGATE - 1) { g_ticket = 0; g_epoch = epoch + 1; }
    if (wtid == 64) asm volatile("cp.async.bulk.wait_group.read 0;" ::: "memory");
    STAMP(15);
    return;
  }
  asm volatile("barrier.cluster.arrive.relaxed.aligned;" ::: "memory");

  const int moff = (bid * 4 + (tid >> 7)) * NM + (tid & 63) * 2;
  const int brt = (tid >> 6) & 1;
  const __nv_bfloat16* const* tp = p.t + (brt ? 0 : 6);
  const uint32_t q0 = *(const uint32_t*)(tp[0] + moff), q1 = *(const uint32_t*)(tp[1] + moff);
  const uint32_t q2 = *(const uint32_t*)(tp[2] + moff), q3 = *(const uint32_t*)(tp[3] + moff);
  const uint2 ldt4 = *(const uint2*)(tp[4] + bid * 4);
  const uint32_t q4 = *(const uint32_t*)(tp[brt ? 2 : 5] + moff), q5 = *(const uint32_t*)(tp[brt ? 3 : 6] + moff);

  for (int i = wtid & 63; i < R_BR / 16; i += 64) sts128(cb + R_OFF + br * R_BR + i * 16, 0, 0, 0, 0);
  STAMP(1);

  float acc[5][4];
  float k2048 = 0.f;
  const uint32_t scr = cb + Y0_OFF + wq * SCR_BYTES;
  const uint32_t scr2 = sb + SC2_OFF + warp * 640;
  {
    const uint32_t ldt2 = (ch & 2) ? ldt4.y : ldt4.x;
    const float dt = bf_round(expf((ch & 1) ? bf_hi(ldt2) : bf_lo(ldt2)));
#pragma unroll
    for (int i = 0; i < 5; i++) acc[i][0] = acc[i][1] = acc[i][2] = acc[i][3] = 0.f;
    STAMP(2);
    const uint32_t tb = scr + lane * 16;
    const uint32_t ta = scr + (lane >> 3) * 512 + (lane & 7) * 16;
    const uint32_t tc = ((lane & 8) ? scr2 : scr + 4096) + (lane >> 4) * 128 + (lane & 7) * 16;
    const uint32_t tm = scr2 + 512 + ((lane >> 3) & 1) * 64 + (lane >> 4) * 16;
    cf cc[2], zz1[2], zz128[2];
#pragma unroll
    for (int r = 0; r < 2; r++) {
      float v0 = r ? bf_hi(q0) : bf_lo(q0), v1 = r ? bf_hi(q1) : bf_lo(q1), v2 = r ? bf_hi(q2) : bf_lo(q2);
      float v3 = r ? bf_hi(q3) : bf_lo(q3), v4 = r ? bf_hi(q4) : bf_lo(q4), v5 = r ? bf_hi(q5) : bf_lo(q5);
      if (br == 0) { cc[r] = cmul(cf{v2, v3}, cf{dt * v4, dt * v5}); }
      else { v0 = -bf_round(expf(v0)); cc[r] = cf{2.f * dt * v2, 2.f * dt * v3}; }
      const float xl = (dt * v0) * 1.4426950408889634f, y = dt * v1;
      zz1[r] = cexp_p(xl, y, 1.f); zz128[r] = cexp_p(xl, y, 128.f);
    }
    uint32_t T[10][4], m4;
    auto produce = [&](int r) {
      const cf c = cc[r], z1 = zz1[r], z128 = zz128[r];
      const cf z2 = csq(z1), z4 = csq(z2), z8 = csq(z4);
      const cf w8 = {z8.re, -z8.im};
      const cf z16 = csq(w8), z24 = cmul(z16, w8), z32 = csq(z16), z40 = cmul(z32, w8), z48 = csq(z24), z56 = cmul(z32, z24), z64 = csq(z32);
      const cf z256 = csq(z128), z512 = csq(z256), z1024 = csq(z512), z2048 = csq(z1024);
      k2048 += fmaf(c.re, z2048.re, -c.im * z2048.im);
      {
        T[0][0] = pack_bf16(1.f, z8.re); T[0][1] = pack_bf16(z16.re, z24.re); T[0][2] = pack_bf16(z32.re, z40.re); T[0][3] = pack_bf16(z48.re, z56.re);
        T[2][0] = pack_bf16(0.f, w8.im); T[2][1] = pack_bf16(z16.im, z24.im); T[2][2] = pack_bf16(z32.im, z40.im); T[2][3] = pack_bf16(z48.im, z56.im);
        const uint32_t yr = pack_bf16(z64.re, z64.re), yi = pack_bf16(z64.im, z64.im), nyi = yi ^ 0x80008000u;
#pragma unroll
        for (int i = 0; i < 4; i++) CMUL2(T[1][i], T[3][i], T[0][i], T[2][i], yr, yi, nyi);
      }
      {
        const cf h1 = cmul(c, z128), h2 = cmul(c, z256), h3 = cmul(h1, z256), h4 = cmul(c, z512), h5 = cmul(h1, z512), h6 = cmul(h2, z512), h7 = cmul(h3, z512);
        const cf e1 = cmul(c, z1), e2 = cmul(c, z2), e3 = cmul(e1, z2), e129 = cmul(h1, z1), e130 = cmul(h1, z2), e131 = cmul(e129, z2);
        const cf e258 = cmul(h2, z2), e386 = cmul(h3, z2);
        T[4][0] = pack_bf16(c.re, e1.re); T[4][1] = pack_bf16(e2.re, e3.re); T[4][2] = pack_bf16(h1.re, e129.re); T[4][3] = pack_bf16(e130.re, e131.re);
        T[5][0] = pack_bf16(c.im, e1.im); T[5][1] = pack_bf16(e2.im, e3.im); T[5][2] = pack_bf16(h1.im, e129.im); T[5][3] = pack_bf16(e130.im, e131.im);
        T[6][0] = pack_bf16(h2.re, e258.re); T[6][1] = pack_bf16(h3.re, e386.re); T[6][2] = pack_bf16(h4.re, h5.re); T[6][3] = pack_bf16(h6.re, h7.re);
        T[7][0] = pack_bf16(h2.im, e258.im); T[7][1] = pack_bf16(h3.im, e386.im); T[7][2] = pack_bf16(h4.im, h5.im); T[7][3] = pack_bf16(h6.im, h7.im);
        const uint32_t xr[4] = {__byte_perm(T[4][0], T[4][2], 0x5410), __byte_perm(T[6][0], T[6][1], 0x5410), T[6][2], T[6][3]};
        const uint32_t xi[4] = {__byte_perm(T[5][0], T[5][2], 0x5410), __byte_perm(T[7][0], T[7][1], 0x5410), T[7][2], T[7][3]};
        const uint32_t yr = pack_bf16(z1024.re, z1024.re), yi = pack_bf16(z1024.im, z1024.im), nyi = yi ^ 0x80008000u;
#pragma unroll
        for (int i = 0; i < 4; i++) CMUL2(T[8][i], T[9][i], xr[i], xi[i], yr, yi, nyi);
        m4 = pack_bf16(z4.re, z4.im);
      }
    };
    auto store = [&]() {
#pragma unroll
      for (int m = 0; m < 9; m++) sts128(tb + m * 512, T[m][0], T[m][1], T[m][2], T[m][3]);
      sts128(scr2 + lane * 16, T[9][0], T[9][1], T[9][2], T[9][3]);
      sts16(scr2 + 512 + lane * 2, m4); sts16(scr2 + 576 + lane * 2, m4 >> 16);
    };
    auto consume = [&]() {
#pragma unroll
      for (int kp = 0; kp < 2; kp++) {
        uint32_t rr[2], ri[2], yr[2], yi[2];
        ldsm4t(tc + kp * 256, rr[0], ri[0], rr[1], ri[1]);
        ldsm4(tm + kp * 32, yr[0], yi[0], yr[1], yi[1]);
#pragma unroll
        for (int k2 = 0; k2 < 2; k2++) {
          const int kk = kp * 2 + k2;
          uint32_t a0, a1, a2, a3, pr, pi, qr, qi, xr, xi;
          ldsm4t(ta + kk * 128, a0, a1, a2, a3);
          ldsm4t(ta + 2048 + kk * 128, pr, pi, qr, qi);
          const uint32_t nyi = yi[k2] ^ 0x80008000u;
          mma16816(acc[0], a0, a1, a2, a3, pr, pi);
          mma16816(acc[2], a0, a1, a2, a3, qr, qi);
          mma16816(acc[4], a0, a1, a2, a3, rr[k2], ri[k2]);
          CMUL2(xr, xi, pr, pi, yr[k2], yi[k2], nyi);
          mma16816(acc[1], a0, a1, a2, a3, xr, xi);
          CMUL2(xr, xi, qr, qi, yr[k2], yi[k2], nyi);
          mma16816(acc[3], a0, a1, a2, a3, xr, xi);
        }
      }
    };
    produce(0); store();
    __syncwarp();
    consume(); produce(1);
    __syncwarp();
    store();
#pragma unroll
    for (int o = 16; o; o >>= 1) k2048 += __shfl_xor_sync(0xffffffffu, k2048, o);
    __syncwarp();
    consume();
  }
  STAMP(3);
  __syncwarp();
  {
    const uint32_t xs = scr + lane * 16;
#define OTH(i, k) __float_as_uint(hf ? acc[i][k] : acc[i][2 + (k)])
    sts128(xs, OTH(0, 0), OTH(0, 1), OTH(1, 0), OTH(1, 1));
    sts128(xs + 512, OTH(2, 0), OTH(2, 1), OTH(3, 0), OTH(3, 1));
    sts128(xs + 1024, OTH(4, 0), OTH(4, 1), __float_as_uint(k2048), 0);
#undef OTH
  }

  bar_sync(7 + (warp >> 1), 64);
  STAMP(4);
  {
    const uint32_t xo = cb + Y0_OFF + (wq ^ 1) * SCR_BYTES + lane * 16;
    const uint4 o0 = lds128(xo), o1 = lds128(xo + 512), o2 = lds128(xo + 1024);
    const uint32_t rb = cb + R_OFF + br * R_BR;
#define OWN(i, k) (hf ? acc[i][2 + (k)] : acc[i][k])
    const uint32_t vP = pack_bf16(OWN(0, 1) + __uint_as_float(o0.y), OWN(0, 0) + __uint_as_float(o0.x));
    const uint32_t vP4 = pack_bf16(OWN(1, 1) + __uint_as_float(o0.w), OWN(1, 0) + __uint_as_float(o0.z));
    const uint32_t vQ = pack_bf16(OWN(2, 1) + __uint_as_float(o1.y), OWN(2, 0) + __uint_as_float(o1.x));
    const uint32_t vQ4 = pack_bf16(OWN(3, 1) + __uint_as_float(o1.w), OWN(3, 0) + __uint_as_float(o1.z));
    const uint32_t vR = pack_bf16(OWN(4, 1) + __uint_as_float(o2.y), OWN(4, 0) + __uint_as_float(o2.x));
#undef OWN
    const int j = g + 8 * hf;
    {
      const int a = 2 * (t & 1) + 64 * (t & 2) + 8 * j;
      const uint32_t ad = rb + 2 * (RD_X0 - 1 - a);
      const uint32_t a1 = (t & 2) ? ad - 8 : ad, a2 = (t & 2) ? ad : ad - 8;
      const uint32_t w1 = (t & 2) ? vP4 : vP, w2 = (t & 2) ? vP : vP4;
      sts32(a1, w1); sts32(a2, w2);
      sts16(a1 + RD_CS + 2, w1); sts16(a1 + RD_CS + 4, w1 >> 16);
      sts16(a2 + RD_CS + 2, w2); sts16(a2 + RD_CS + 4, w2 >> 16);
    }
    if (t < 2) {
      const int b = 256 + 128 * t + 8 * j;
      const uint32_t ad = rb + 2 * (RD_X0 - 6 - b);
      const uint32_t v22 = __byte_perm(vQ4, 0, 0x3232), v00 = __byte_perm(vQ, 0, 0x3232);
      sts16(ad, vQ4);
      sts64(ad + 2, v22, __byte_perm(vQ4, vQ, 0x5432));
      sts32(ad + 10, v00);
      if (b != 256) { sts16(ad + 14, v00); sts128(ad + RD_CS + 2, vQ4, v22, vQ, v00); }
      else { sts64(ad + RD_CS + 2, vQ4, v22); sts32(ad + RD_CS + 10, vQ); sts16(ad + RD_CS + 14, v00); }
    } else {
      const uint32_t ao = rb + R_O2 + 2 * (159 - (32 * t + j)), ae = ao - (R_O2 - R_E2) + 2;
      sts16(ao, vQ4 >> 16); sts16(ao + RS_CS + 2, vQ4 >> 16); sts16(ao - 32, vQ4); sts16(ao - 32 + RS_CS + 2, vQ4);
      sts16(ae - 32, vQ); sts16(ae - 32 + RS_CS + 2, vQ);
      if (lane != 2 || hf) { sts16(ae, vQ >> 16); sts16(ae + RS_CS + 2, vQ >> 16); }
      else {
        const uint32_t vv = __byte_perm(vQ, 0, 0x3232), ad = rb + 2 * (RD_X0 - 514);
        sts16(ad, vv); sts32(ad + 2, vv); sts16(ad + 6, vv); sts64(ad + RD_CS + 2, vv, vv);
      }
    }
    {
      const uint32_t a = rb + ((g & 1) ? R_O3 : R_E3 + 2) + 2 * (159 - (64 + 16 * t + (j >> 1)));
      const bool p1024 = (lane == 0) && (hf == 0);
      const uint32_t a00 = p1024 ? rb + R_E2 + 2 * (159 - 127) : a;
      sts16(a00, vR >> 16); sts16(a00 + RS_CS + 2, vR >> 16);
      sts16(a - 16, vR); sts16(a - 16 + RS_CS + 2, vR);
      if (p1024) {
        sts32(sb + K1024_OFF + (ch * 2 + br) * 4, __byte_perm(vR, 0, 0x3232));
        const uint32_t kv = pack_bf16(k2048 + __uint_as_float(o2.z), 0.f);
        sts16(rb + R_E3 + 2 * (159 - 127), kv); sts16(rb + R_E3 + 2 * (159 - 127) + RS_CS + 2, kv);
      }
    }
  }
  STAMP(5);
  asm volatile("barrier.cluster.wait.aligned;" ::: "memory");
  bar_sync(7 + (warp >> 1), 64);
  mbar_wait(sb + B_U);
  STAMP(6);

  const uint32_t zz = lds32(cb + R_OFF + br * R_BR);
  conv_dense(sb, cb, zz);
  STAMP(8);
  {
    const int x = (4 + ch) * 128 + wtid, c = x >> 2;
    const uint2 dA = ldg64(p.A_D + bid * 4), dB = ldg64(p.B_D + bid * 4);
    const uint2 gl = gate_ld(x);
    const uint32_t rb = cb + R_OFF + br * R_BR;
    float e48[24], e40[20], e32[16], h32[16], h16[8];
    const int x1 = 159 - (16 * hf + g - 2 * t + 136);
    const uint32_t fs = rb + ((g & 1) ? 2 * x1 : RS_CS + 2 * x1 + 2);
    uint32_t A[2][4][4];
    auto loadA = [&](int buf, uint32_t oe, uint32_t oo, int i0) {
#pragma unroll
      for (int a = 0; a < 2; a++) {
        const uint32_t base = fs + (a ? oo : oe) + i0 * 16;
        uint32_t* k0 = A[buf][2 * a];
        uint32_t* k1 = A[buf][2 * a + 1];
        k0[1] = lds32(base); k0[0] = lds32(base + 16); k0[2] = lds32(base + 32); k1[0] = lds32(base + 48); k1[2] = lds32(base + 64);
        k0[3] = k0[0]; k1[1] = k0[2]; k1[3] = k1[0];
      }
    };
    loadA(0, R_E2, R_O2, 8);
    loadA(1, R_E2, R_O2, 4);
    mbar_wait(sb + B_W);
    const uint64_t d5 = mkdesc(cb + W5_OFF, 144, 576), d3 = mkdesc(cb + W3_OFF, 144, 576);
    const uint64_t d9 = mkdesc(cb + W9_OFF, 144, 576), d7 = mkdesc(cb + W7_OFF, 144, 576);
    const uint32_t y2d = cb + Y2_OFF + br * 3072 + ysw(32 * (5 - (lane >> 4)) + 16 * hf + (lane & 15));
    const uint32_t y3d = cb + Y3_OFF + br * 2048 + ysw(2 * (16 * hf + (lane & 15)) + (lane >> 4));
#define FAR4(N, ACC, BUF, DA, DB, OFF, FIRST)                                                            \
    wg_fence();                                                                                           \
    _Pragma("unroll") for (int k = 0; k < 4; k++) {                                                      \
      const uint32_t* a = A[BUF][k];                                                                      \
      wgmma_rs<N, 1>(ACC, a[0], a[1], a[2], a[3], ((k >> 1) ? DB : DA) + (k & 1) * 18 + (OFF), !(FIRST) || k); \
    }                                                                                                     \
    wg_commit();
    FAR4(48, e48, 0, d5, d3, 0, 1)
    wg_wait0();
    loadA(0, R_E2, R_O2, 0);
    stsm2(y2d - 5 * 512, PK2(e48, 20), PK2(e48, 22));
#pragma unroll
    for (int i = 0; i < 20; i++) e40[i] = FCPY(e48[i]);
    stage_done(sb, 2, lane);
    FAR4(40, e40, 1, d5, d3, 36, 0)
    wg_wait0();
    loadA(1, R_E3, R_O3, 8);
    stsm2(y2d - 4 * 512, PK2(e40, 16), PK2(e40, 18));
#pragma unroll
    for (int i = 0; i < 16; i++) e32[i] = FCPY(e40[i]);
    stage_done(sb, 3, lane);
    FAR4(32, e32, 0, d5, d3, 72, 0)
    FAR4(32, h32, 1, d9, d7, 0, 1)
    wg_wait1();
    loadA(0, R_E3, R_O3, 4);
    stsm4(y2d, PK2(e32, 0), PK2(e32, 2), PK2(e32, 4), PK2(e32, 6));
    stsm4(y2d - 2 * 512, PK2(e32, 8), PK2(e32, 10), PK2(e32, 12), PK2(e32, 14));
    stage_done(sb, 4, lane);
    STAMP(9);
    wg_wait0();
    stsm4(y3d, PK2(h32, 8), PK2(h32, 10), PK2(h32, 12), PK2(h32, 14));
#pragma unroll
    for (int i = 0; i < 8; i++) h16[i] = FCPY(h32[i]);
    stage_done(sb, 5, lane);
    FAR4(16, h16, 0, d9, d7, 72, 0)
#undef FAR4
    const uint32_t yo = sb + CH_OFF + (x & 3) * 4 + ysw(c);
    uint32_t ua[4], ub[4], ya[4], yb[4], a2[4], b2[4], a3[4], b3[4], s2[4];
    skip_terms(ua, ub, sb, x, dA, dB);
    {
      const int xa = x - 514, xb = x - 513, ca = xa >> 2, cb2 = xb >> 2;
      ld4ch(s2, sb + CH_OFF + U_OFF + (xa & 3) * 4 + (ca & 3) * U_CS + (63 - (ca >> 2)) * 16);
      ld4ch(a3, sb + CH_OFF + U_OFF + (xb & 3) * 4 + (cb2 & 3) * U_CS + (63 - (cb2 >> 2)) * 16);
#pragma unroll
      for (int k = 0; k < 4; k++) s2[k] = hadd2(s2[k], __byte_perm(s2[k], a3[k], 0x5432));
    }
    const uint32_t tag = lds32(sb + TAG_OFF);
    wg_wait0();
    stsm4(y3d + 1024, PK2(h16, 0), PK2(h16, 2), PK2(h16, 4), PK2(h16, 6));
    stage_done(sb, 6, lane);
    STAMP(10);
    const uint32_t g2 = gate_fin(p, gl, x, tag);
    mbar_wait(sb + B_ST + 8 * 4);
    const uint4 k0 = lds128(sb + K1024_OFF), k1 = lds128(sb + K1024_OFF + 16);
    const uint32_t kk[8] = {k0.x, k0.y, k0.z, k0.w, k1.x, k1.y, k1.z, k1.w};
    ld4ch(ya, yo + Y0_OFF); ld4ch(yb, yo + Y0_OFF + 4096);
    ld4ch(a2, yo + Y2_OFF - 1024); ld4ch(b2, yo + Y2_OFF - 1024 + 3072);
    mbar_wait(sb + B_ST + 8 * (5 + (ch >> 1)));
    STAMP(12);
    ld4ch(a3, yo + Y3_OFF - 2048); ld4ch(b3, yo + Y3_OFF - 2048 + 2048);
#pragma unroll
    for (int k = 0; k < 4; k++) {
      ya[k] = hadd2(ya[k], hadd2(hfma2(kk[2 * k], s2[k], a2[k]), a3[k]));
      yb[k] = hadd2(yb[k], hadd2(hfma2(kk[2 * k + 1], s2[k], b2[k]), b3[k]));
    }
    const uint4 r = mix(ya, yb, ua, ub, g2);
    if ((uint32_t)(ch & 1) != rank) send_box(sb, 2 + (ch >> 1), wtid, rank, r);
    else merge_box(sb, &tm_out, 2 + (ch >> 1), wtid, rank, oc0, r, 1 + ch);
  }
  STAMP(14);
  if (wtid == 0) asm volatile("cp.async.bulk.wait_group.read 0;" ::: "memory");
  STAMP(15); GT(1);
}

typedef CUresult (*EncodeFn)(CUtensorMap*, CUtensorMapDataType, cuuint32_t, void*, const cuuint64_t*, const cuuint64_t*,
                             const cuuint32_t*, const cuuint32_t*, CUtensorMapInterleave, CUtensorMapSwizzle,
                             CUtensorMapL2promotion, CUtensorMapFloatOOBfill);

}

extern "C" void kernel_launch(void* const* d_in, const int* in_sizes, int n_in, void* d_out, int out_size) {
  (void)in_sizes; (void)n_in; (void)out_size;
  typedef const __nv_bfloat16* bp;
  Params p;
  p.t[0] = (bp)d_in[10]; p.t[1] = (bp)d_in[11]; p.t[2] = (bp)d_in[12]; p.t[3] = (bp)d_in[13]; p.t[4] = (bp)d_in[14]; p.t[5] = nullptr;
  p.t[6] = (bp)d_in[1]; p.t[7] = (bp)d_in[2]; p.t[8] = (bp)d_in[5]; p.t[9] = (bp)d_in[6]; p.t[10] = (bp)d_in[7];
  p.t[11] = (bp)d_in[3]; p.t[12] = (bp)d_in[4]; p.t[13] = nullptr;
  p.u = (bp)d_in[0]; p.gw = (bp)d_in[16]; p.A_D = (bp)d_in[8]; p.B_D = (bp)d_in[15];
  static EncodeFn enc = nullptr;
  if (!enc) {
    cudaDriverEntryPointQueryResult qr;
    cudaGetDriverEntryPoint("cuTensorMapEncodeTiled", (void**)&enc, cudaEnableDefault, &qr);
    cudaFuncSetAttribute(ssm_kernel, cudaFuncAttributeMaxDynamicSharedMemorySize, SMEM_BYTES);
  }
  CUtensorMap tm_in, tm_out;
  {
    cuuint64_t gd[5] = {512, 2, 4, 4, 64};
    cuuint64_t gs[4] = {1024, 8192, 2048, 32768};
    cuuint32_t bx[5] = {8, 2, 4, 4, 32};
    cuuint32_t es[5] = {1, 1, 1, 1, 1};
    enc(&tm_in, CU_TENSOR_MAP_DATA_TYPE_BFLOAT16, 5, d_in[0], gd, gs, bx, es, CU_TENSOR_MAP_INTERLEAVE_NONE,
        CU_TENSOR_MAP_SWIZZLE_NONE, CU_TENSOR_MAP_L2_PROMOTION_NONE, CU_TENSOR_MAP_FLOAT_OOB_FILL_NONE);
  }
  {
    cuuint64_t gd[3] = {512, 1024, 2};
    cuuint64_t gs[2] = {2048, 1024};
    cuuint32_t bx[3] = {8, 128, 2};
    cuuint32_t es[3] = {1, 1, 1};
    enc(&tm_out, CU_TENSOR_MAP_DATA_TYPE_BFLOAT16, 3, d_out, gd, gs, bx, es, CU_TENSOR_MAP_INTERLEAVE_NONE,
        CU_TENSOR_MAP_SWIZZLE_NONE, CU_TENSOR_MAP_L2_PROMOTION_NONE, CU_TENSOR_MAP_FLOAT_OOB_FILL_NONE);
  }
  ssm_kernel<<<NCTA + NGATE, 640, SMEM_BYTES, cudaStreamPerThread>>>(p, tm_in, tm_out);
}
```

```cpp
#include <cuda_runtime.h>
#include <cuda.h>
#include <cuda_bf16.h>
#include <stdint.h>

namespace {
#define FCPY(v, i) (((i) % 3 == 2) ? __uint_as_float(opq(__float_as_uint(v[i]), zz)) : opqf(v[i], zz))

constexpr int L = 2048, D = 512, NM = 128;
constexpr int NCTA = 128;
constexpr int NGATE = 4;

constexpr int RAW_OFF = 0;
constexpr int XIN_OFF = 32768;
constexpr int SC2_OFF = XIN_OFF + 8192;
constexpr int BAR_OFF = SC2_OFF + 10240;
constexpr int CH_OFF = BAR_OFF + 256;
constexpr int U_CS = 1184;
constexpr int U_OFF = 0;
constexpr int R_OFF = 4736;
constexpr int RD_X0 = 565;
constexpr int RD_CS = 1216;
constexpr int RS_CS = 320;
constexpr int R_E2 = 2 * RD_CS, R_O2 = R_E2 + 2 * RS_CS, R_E3 = R_O2 + 2 * RS_CS, R_O3 = R_E3 + 2 * RS_CS;
constexpr int R_BR = R_O3 + 2 * RS_CS;
constexpr int W5_OFF = R_OFF + 2 * R_BR;
constexpr int W3_OFF = W5_OFF + 3456;
constexpr int W9_OFF = W3_OFF + 3456;
constexpr int W7_OFF = W9_OFF + 2304;
constexpr int Y0_OFF = W7_OFF + 2304;
constexpr int Y2_OFF = Y0_OFF + 8192, Y3_OFF = Y2_OFF + 6144;
constexpr int CH_BYTES = Y0_OFF + 18432 + 16;
constexpr int SCR_BYTES = 4608;
constexpr int SMEM_BYTES = CH_OFF + 4 * CH_BYTES;
static_assert(CH_BYTES % 128 == 16, "bank staggering of the channel blocks");
static_assert(SMEM_BYTES <= 232448, "smem");
constexpr int B_RAW = BAR_OFF, B_X = BAR_OFF + 8, B_U = BAR_OFF + 40, B_W = BAR_OFF + 48;
constexpr int TAG_OFF = BAR_OFF + 56;
constexpr int K1024_OFF = BAR_OFF + 64;
constexpr int B_ST = BAR_OFF + 96;

__device__ unsigned int g_gate[L];
__device__ unsigned int g_epoch;
__device__ unsigned int g_ticket;

#define STAMP(k)
#define GT(k)

struct Params {
  const __nv_bfloat16* t[14];
  const __nv_bfloat16 *u, *gw, *A_D, *B_D;
};

template <int N, int TB> __device__ __forceinline__ void wgmma_rs(float* d, uint32_t a0, uint32_t a1, uint32_t a2, uint32_t a3, uint64_t desc, int sc);
template <> __device__ __forceinline__ void wgmma_rs<64, 0>(float* d, uint32_t a0, uint32_t a1, uint32_t a2, uint32_t a3, uint64_t desc, int sc) {
  asm volatile("{\n.reg .pred p;\nsetp.ne.b32 p, %37, 0;\n"
    "wgmma.mma_async.sync.aligned.m64n64k16.f32.bf16.bf16 {%0,%1,%2,%3,%4,%5,%6,%7,%8,%9,%10,%11,%12,%13,%14,%15,%16,%17,%18,%19,%20,%21,%22,%23,%24,%25,%26,%27,%28,%29,%30,%31}, {%32,%33,%34,%35}, %36, p, 1, 1, 0;\n}"
    : "+f"(d[0]), "+f"(d[1]), "+f"(d[2]), "+f"(d[3]), "+f"(d[4]), "+f"(d[5]), "+f"(d[6]), "+f"(d[7]), "+f"(d[8]), "+f"(d[9]), "+f"(d[10]), "+f"(d[11]), "+f"(d[12]), "+f"(d[13]), "+f"(d[14]), "+f"(d[15]), "+f"(d[16]), "+f"(d[17]), "+f"(d[18]), "+f"(d[19]), "+f"(d[20]), "+f"(d[21]), "+f"(d[22]), "+f"(d[23]), "+f"(d[24]), "+f"(d[25]), "+f"(d[26]), "+f"(d[27]), "+f"(d[28]), "+f"(d[29]), "+f"(d[30]), "+f"(d[31]) : "r"(a0), "r"(a1), "r"(a2), "r"(a3), "l"(desc), "r"(sc));
}
template <> __device__ __forceinline__ void wgmma_rs<56, 0>(float* d, uint32_t a0, uint32_t a1, uint32_t a2, uint32_t a3, uint64_t desc, int sc) {
  asm volatile("{\n.reg .pred p;\nsetp.ne.b32 p, %33, 0;\n"
    "wgmma.mma_async.sync.aligned.m64n56k16.f32.bf16.bf16 {%0,%1,%2,%3,%4,%5,%6,%7,%8,%9,%10,%11,%12,%13,%14,%15,%16,%17,%18,%19,%20,%21,%22,%23,%24,%25,%26,%27}, {%28,%29,%30,%31}, %32, p, 1, 1, 0;\n}"
    : "+f"(d[0]), "+f"(d[1]), "+f"(d[2]), "+f"(d[3]), "+f"(d[4]), "+f"(d[5]), "+f"(d[6]), "+f"(d[7]), "+f"(d[8]), "+f"(d[9]), "+f"(d[10]), "+f"(d[11]), "+f"(d[12]), "+f"(d[13]), "+f"(d[14]), "+f"(d[15]), "+f"(d[16]), "+f"(d[17]), "+f"(d[18]), "+f"(d[19]), "+f"(d[20]), "+f"(d[21]), "+f"(d[22]), "+f"(d[23]), "+f"(d[24]), "+f"(d[25]), "+f"(d[26]), "+f"(d[27]) : "r"(a0), "r"(a1), "r"(a2), "r"(a3), "l"(desc), "r"(sc));
}
template <> __device__ __forceinline__ void wgmma_rs<48, 0>(float* d, uint32_t a0, uint32_t a1, uint32_t a2, uint32_t a3, uint64_t desc, int sc) {
  asm volatile("{\n.reg .pred p;\nsetp.ne.b32 p, %29, 0;\n"
    "wgmma.mma_async.sync.aligned.m64n48k16.f32.bf16.bf16 {%0,%1,%2,%3,%4,%5,%6,%7,%8,%9,%10,%11,%12,%13,%14,%15,%16,%17,%18,%19,%20,%21,%22,%23}, {%24,%25,%26,%27}, %28, p, 1, 1, 0;\n}"
    : "+f"(d[0]), "+f"(d[1]), "+f"(d[2]), "+f"(d[3]), "+f"(d[4]), "+f"(d[5]), "+f"(d[6]), "+f"(d[7]), "+f"(d[8]), "+f"(d[9]), "+f"(d[10]), "+f"(d[11]), "+f"(d[12]), "+f"(d[13]), "+f"(d[14]), "+f"(d[15]), "+f"(d[16]), "+f"(d[17]), "+f"(d[18]), "+f"(d[19]), "+f"(d[20]), "+f"(d[21]), "+f"(d[22]), "+f"(d[23]) : "r"(a0), "r"(a1), "r"(a2), "r"(a3), "l"(desc), "r"(sc));
}
template <> __device__ __forceinline__ void wgmma_rs<32, 0>(float* d, uint32_t a0, uint32_t a1, uint32_t a2, uint32_t a3, uint64_t desc, int sc) {
  asm volatile("{\n.reg .pred p;\nsetp.ne.b32 p, %21, 0;\n"
    "wgmma.mma_async.sync.aligned.m64n32k16.f32.bf16.bf16 {%0,%1,%2,%3,%4,%5,%6,%7,%8,%9,%10,%11,%12,%13,%14,%15}, {%16,%17,%18,%19}, %20, p, 1, 1, 0;\n}"
    : "+f"(d[0]), "+f"(d[1]), "+f"(d[2]), "+f"(d[3]), "+f"(d[4]), "+f"(d[5]), "+f"(d[6]), "+f"(d[7]), "+f"(d[8]), "+f"(d[9]), "+f"(d[10]), "+f"(d[11]), "+f"(d[12]), "+f"(d[13]), "+f"(d[14]), "+f"(d[15]) : "r"(a0), "r"(a1), "r"(a2), "r"(a3), "l"(desc), "r"(sc));
}
template <> __device__ __forceinline__ void wgmma_rs<48, 1>(float* d, uint32_t a0, uint32_t a1, uint32_t a2, uint32_t a3, uint64_t desc, int sc) {
  asm volatile("{\n.reg .pred p;\nsetp.ne.b32 p, %29, 0;\n"
    "wgmma.mma_async.sync.aligned.m64n48k16.f32.bf16.bf16 {%0,%1,%2,%3,%4,%5,%6,%7,%8,%9,%10,%11,%12,%13,%14,%15,%16,%17,%18,%19,%20,%21,%22,%23}, {%24,%25,%26,%27}, %28, p, 1, 1, 1;\n}"
    : "+f"(d[0]), "+f"(d[1]), "+f"(d[2]), "+f"(d[3]), "+f"(d[4]), "+f"(d[5]), "+f"(d[6]), "+f"(d[7]), "+f"(d[8]), "+f"(d[9]), "+f"(d[10]), "+f"(d[11]), "+f"(d[12]), "+f"(d[13]), "+f"(d[14]), "+f"(d[15]), "+f"(d[16]), "+f"(d[17]), "+f"(d[18]), "+f"(d[19]), "+f"(d[20]), "+f"(d[21]), "+f"(d[22]), "+f"(d[23]) : "r"(a0), "r"(a1), "r"(a2), "r"(a3), "l"(desc), "r"(sc));
}
template <> __device__ __forceinline__ void wgmma_rs<40, 1>(float* d, uint32_t a0, uint32_t a1, uint32_t a2, uint32_t a3, uint64_t desc, int sc) {
  asm volatile("{\n.reg .pred p;\nsetp.ne.b32 p, %25, 0;\n"
    "wgmma.mma_async.sync.aligned.m64n40k16.f32.bf16.bf16 {%0,%1,%2,%3,%4,%5,%6,%7,%8,%9,%10,%11,%12,%13,%14,%15,%16,%17,%18,%19}, {%20,%21,%22,%23}, %24, p, 1, 1, 1;\n}"
    : "+f"(d[0]), "+f"(d[1]), "+f"(d[2]), "+f"(d[3]), "+f"(d[4]), "+f"(d[5]), "+f"(d[6]), "+f"(d[7]), "+f"(d[8]), "+f"(d[9]), "+f"(d[10]), "+f"(d[11]), "+f"(d[12]), "+f"(d[13]), "+f"(d[14]), "+f"(d[15]), "+f"(d[16]), "+f"(d[17]), "+f"(d[18]), "+f"(d[19]) : "r"(a0), "r"(a1), "r"(a2), "r"(a3), "l"(desc), "r"(sc));
}
template <> __device__ __forceinline__ void wgmma_rs<32, 1>(float* d, uint32_t a0, uint32_t a1, uint32_t a2, uint32_t a3, uint64_t desc, int sc) {
  asm volatile("{\n.reg .pred p;\nsetp.ne.b32 p, %21, 0;\n"
    "wgmma.mma_async.sync.aligned.m64n32k16.f32.bf16.bf16 {%0,%1,%2,%3,%4,%5,%6,%7,%8,%9,%10,%11,%12,%13,%14,%15}, {%16,%17,%18,%19}, %20, p, 1, 1, 1;\n}"
    : "+f"(d[0]), "+f"(d[1]), "+f"(d[2]), "+f"(d[3]), "+f"(d[4]), "+f"(d[5]), "+f"(d[6]), "+f"(d[7]), "+f"(d[8]), "+f"(d[9]), "+f"(d[10]), "+f"(d[11]), "+f"(d[12]), "+f"(d[13]), "+f"(d[14]), "+f"(d[15]) : "r"(a0), "r"(a1), "r"(a2), "r"(a3), "l"(desc), "r"(sc));
}
template <> __device__ __forceinline__ void wgmma_rs<16, 1>(float* d, uint32_t a0, uint32_t a1, uint32_t a2, uint32_t a3, uint64_t desc, int sc) {
  asm volatile("{\n.reg .pred p;\nsetp.ne.b32 p, %13, 0;\n"
    "wgmma.mma_async.sync.aligned.m64n16k16.f32.bf16.bf16 {%0,%1,%2,%3,%4,%5,%6,%7}, {%8,%9,%10,%11}, %12, p, 1, 1, 1;\n}"
    : "+f"(d[0]), "+f"(d[1]), "+f"(d[2]), "+f"(d[3]), "+f"(d[4]), "+f"(d[5]), "+f"(d[6]), "+f"(d[7]) : "r"(a0), "r"(a1), "r"(a2), "r"(a3), "l"(desc), "r"(sc));
}

__device__ __forceinline__ uint32_t pack_bf16(float lo, float hi) {
  uint32_t r; asm("cvt.rn.bf16x2.f32 %0, %1, %2;" : "=r"(r) : "f"(hi), "f"(lo)); return r;
}
__device__ __forceinline__ float bf_lo(uint32_t v) { return __uint_as_float(v << 16); }
__device__ __forceinline__ float bf_hi(uint32_t v) { return __uint_as_float(v & 0xffff0000u); }
__device__ __forceinline__ float bf_round(float x) { return bf_lo(pack_bf16(x, 0.f)); }
__device__ __forceinline__ uint32_t hmul2(uint32_t a, uint32_t b) { uint32_t r; asm("mul.rn.bf16x2 %0, %1, %2;" : "=r"(r) : "r"(a), "r"(b)); return r; }
__device__ __forceinline__ uint32_t hadd2(uint32_t a, uint32_t b) { uint32_t r; asm("add.rn.bf16x2 %0, %1, %2;" : "=r"(r) : "r"(a), "r"(b)); return r; }
__device__ __forceinline__ uint32_t hsub2(uint32_t a, uint32_t b) { uint32_t r; asm("sub.rn.bf16x2 %0, %1, %2;" : "=r"(r) : "r"(a), "r"(b)); return r; }
__device__ __forceinline__ uint32_t hfma2(uint32_t a, uint32_t b, uint32_t c) { uint32_t r; asm("fma.rn.bf16x2 %0, %1, %2, %3;" : "=r"(r) : "r"(a), "r"(b), "r"(c)); return r; }

__device__ __forceinline__ void sts16(uint32_t a, uint32_t v) { asm volatile("st.shared.b16 [%0], %1;" ::"r"(a), "h"((unsigned short)v) : "memory"); }
__device__ __forceinline__ void sts32(uint32_t a, uint32_t v) { asm volatile("st.shared.b32 [%0], %1;" ::"r"(a), "r"(v) : "memory"); }
__device__ __forceinline__ void sts64(uint32_t a, uint32_t x, uint32_t y) { asm volatile("st.shared.v2.b32 [%0], {%1,%2};" ::"r"(a), "r"(x), "r"(y) : "memory"); }
__device__ __forceinline__ void sts128(uint32_t a, uint32_t x, uint32_t y, uint32_t z, uint32_t w) {
  asm volatile("st.shared.v4.b32 [%0], {%1,%2,%3,%4};" ::"r"(a), "r"(x), "r"(y), "r"(z), "r"(w) : "memory");
}
__device__ __forceinline__ uint32_t lds32(uint32_t a) { uint32_t v; asm volatile("ld.shared.b32 %0, [%1];" : "=r"(v) : "r"(a) : "memory"); return v; }
__device__ __forceinline__ uint2 lds64(uint32_t a) { uint2 v; asm volatile("ld.shared.v2.b32 {%0,%1}, [%2];" : "=r"(v.x), "=r"(v.y) : "r"(a) : "memory"); return v; }
__device__ __forceinline__ uint4 lds128(uint32_t a) {
  uint4 v; asm volatile("ld.shared.v4.b32 {%0,%1,%2,%3}, [%4];" : "=r"(v.x), "=r"(v.y), "=r"(v.z), "=r"(v.w) : "r"(a) : "memory"); return v;
}
__device__ __forceinline__ uint4 ldg128(const void* a) {
  uint4 v; asm volatile("ld.global.nc.v4.b32 {%0,%1,%2,%3}, [%4];" : "=r"(v.x), "=r"(v.y), "=r"(v.z), "=r"(v.w) : "l"(a) : "memory"); return v;
}
__device__ __forceinline__ uint2 ldg64(const void* a) {
  uint2 v; asm volatile("ld.global.nc.v2.b32 {%0,%1}, [%2];" : "=r"(v.x), "=r"(v.y) : "l"(a) : "memory"); return v;
}
__device__ __forceinline__ void ldsm4(uint32_t a, uint32_t& r0, uint32_t& r1, uint32_t& r2, uint32_t& r3) {
  asm volatile("ldmatrix.sync.aligned.m8n8.x4.shared.b16 {%0,%1,%2,%3}, [%4];" : "=r"(r0), "=r"(r1), "=r"(r2), "=r"(r3) : "r"(a) : "memory");
}
__device__ __forceinline__ void ldsm4t(uint32_t a, uint32_t& r0, uint32_t& r1, uint32_t& r2, uint32_t& r3) {
  asm volatile("ldmatrix.sync.aligned.m8n8.x4.trans.shared.b16 {%0,%1,%2,%3}, [%4];" : "=r"(r0), "=r"(r1), "=r"(r2), "=r"(r3) : "r"(a) : "memory");
}
__device__ __forceinline__ void stsm4(uint32_t a, uint32_t r0, uint32_t r1, uint32_t r2, uint32_t r3) {
  asm volatile("stmatrix.sync.aligned.m8n8.x4.shared.b16 [%0], {%1,%2,%3,%4};" ::"r"(a), "r"(r0), "r"(r1), "r"(r2), "r"(r3) : "memory");
}
__device__ __forceinline__ void stsm4t(uint32_t a, uint32_t r0, uint32_t r1, uint32_t r2, uint32_t r3) {
  asm volatile("stmatrix.sync.aligned.m8n8.x4.trans.shared.b16 [%0], {%1,%2,%3,%4};" ::"r"(a), "r"(r0), "r"(r1), "r"(r2), "r"(r3) : "memory");
}
__device__ __forceinline__ void stsm2(uint32_t a, uint32_t r0, uint32_t r1) {
  asm volatile("stmatrix.sync.aligned.m8n8.x2.shared.b16 [%0], {%1,%2};" ::"r"(a), "r"(r0), "r"(r1) : "memory");
}
__device__ __forceinline__ void stsm2t(uint32_t a, uint32_t r0, uint32_t r1) {
  asm volatile("stmatrix.sync.aligned.m8n8.x2.trans.shared.b16 [%0], {%1,%2};" ::"r"(a), "r"(r0), "r"(r1) : "memory");
}
__device__ __forceinline__ void mma16816(float* c, uint32_t a0, uint32_t a1, uint32_t a2, uint32_t a3, uint32_t b0, uint32_t b1) {
  asm("mma.sync.aligned.m16n8k16.row.col.f32.bf16.bf16.f32 {%0,%1,%2,%3}, {%4,%5,%6,%7}, {%8,%9}, {%0,%1,%2,%3};"
      : "+f"(c[0]), "+f"(c[1]), "+f"(c[2]), "+f"(c[3]) : "r"(a0), "r"(a1), "r"(a2), "r"(a3), "r"(b0), "r"(b1));
}
__device__ __forceinline__ void bar_sync(int id, int n) { asm volatile("bar.sync %0, %1;" ::"r"(id), "r"(n) : "memory"); }
__device__ __forceinline__ void bar_arrive(int id, int n) { asm volatile("bar.arrive %0, %1;" ::"r"(id), "r"(n) : "memory"); }
__device__ __forceinline__ void wg_fence() { asm volatile("wgmma.fence.sync.aligned;" ::: "memory"); }
__device__ __forceinline__ void wg_commit() { asm volatile("wgmma.commit_group.sync.aligned;" ::: "memory"); }
__device__ __forceinline__ void wg_wait0() { asm volatile("wgmma.wait_group.sync.aligned 0;" ::: "memory"); }
__device__ __forceinline__ void wg_wait1() { asm volatile("wgmma.wait_group.sync.aligned 1;" ::: "memory"); }
__device__ __forceinline__ void fence_async() { asm volatile("fence.proxy.async.shared::cta;" ::: "memory"); }
__device__ __forceinline__ uint32_t opq(uint32_t x, uint32_t z) { uint32_t r; asm volatile("xor.b32 %0, %1, %2;" : "=r"(r) : "r"(x), "r"(z)); return r; }
__device__ __forceinline__ float opqf(float x, uint32_t z) { float r; asm volatile("add.rn.f32 %0, %1, %2;" : "=f"(r) : "f"(x), "f"(__uint_as_float(z))); return r; }
__device__ __forceinline__ uint64_t mkdesc(uint32_t addr, uint32_t lbo, uint32_t sbo) {
  return (uint64_t)((addr & 0x3FFFF) >> 4) | ((uint64_t)(lbo >> 4) << 16) | ((uint64_t)(sbo >> 4) << 32);
}
__device__ __forceinline__ uint32_t mapa(uint32_t a, uint32_t rank) {
  uint32_t r; asm("mapa.shared::cluster.u32 %0, %1, %2;" : "=r"(r) : "r"(a), "r"(rank)); return r;
}
__device__ __forceinline__ void mbar_init_expect(uint32_t bar, uint32_t bytes) {
  asm volatile("mbarrier.init.shared::cta.b64 [%0], 1;" ::"r"(bar) : "memory");
  asm volatile("mbarrier.arrive.expect_tx.shared::cta.b64 _, [%0], %1;" ::"r"(bar), "r"(bytes) : "memory");
}
__device__ __forceinline__ void mbar_wait(uint32_t bar) {
#pragma unroll 1
  for (int it = 0; it < (1 << 22); it++) {
    uint32_t ok;
    asm volatile("{\n.reg .pred p;\nmbarrier.try_wait.parity.acquire.cluster.shared::cta.b64 p, [%1], 0;\nselp.u32 %0, 1, 0, p;\n}"
                 : "=r"(ok) : "r"(bar) : "memory");
    if (ok) return;
  }
  __trap();
}
__device__ __forceinline__ void st_async4(uint32_t a, uint32_t bar, uint32_t x, uint32_t y, uint32_t z, uint32_t w) {
  asm volatile("st.async.weak.shared::cluster.mbarrier::complete_tx::bytes.v4.b32 [%0], {%2,%3,%4,%5}, [%1];"
               ::"r"(a), "r"(bar), "r"(x), "r"(y), "r"(z), "r"(w) : "memory");
}

struct cf { float re, im; };
__device__ __forceinline__ cf cmul(cf a, cf b) { return {fmaf(a.re, b.re, -a.im * b.im), fmaf(a.re, b.im, a.im * b.re)}; }
__device__ __forceinline__ cf csq(cf a) { return {fmaf(a.re, a.re, -a.im * a.im), (a.re + a.re) * a.im}; }
__device__ __forceinline__ cf cexp_p(float xl, float y, float p) {
  float mag; asm("ex2.approx.ftz.f32 %0, %1;" : "=f"(mag) : "f"(xl * p));
  const float th = y * p;
  const float k = __fadd_rn(fmaf(th, 0.15915494309189535f, 12582912.f), -12582912.f);
  float r = fmaf(k, -6.2831854820251465f, th);
  r = fmaf(k, 1.7484555314695172e-07f, r);
  return {mag * __cosf(r), mag * __sinf(r)};
}
__device__ __forceinline__ uint32_t ysw(int c) { return (uint32_t)(c ^ ((c >> 3) & 3)) * 16u; }

#define CMUL2(OR, OI, xr, xi, yr, yi, nyi) do { OR = hfma2(xr, yr, hmul2(xi, nyi)); OI = hfma2(xr, yi, hmul2(xi, yr)); } while (0)

__device__ __forceinline__ uint32_t gate_slow(const __nv_bfloat16* u, const __nv_bfloat16* gw, int row) {
  float s = 0.f;
  const uint32_t* xr = (const uint32_t*)(u + (size_t)row * D);
  const uint32_t* wr = (const uint32_t*)gw;
#pragma unroll 1
  for (int j = 0; j < D / 2; j++) { const uint32_t pr = hmul2(xr[j], wr[j]); s += bf_lo(pr); s += bf_hi(pr); }
  s = bf_round(s);
  return pack_bf16(1.f / (1.f + expf(-s)), 0.f);
}

__device__ __forceinline__ uint2 gate_ld(int x) {
  uint2 gv;
  asm volatile("ld.relaxed.gpu.global.v2.u32 {%0,%1}, [%2];" : "=r"(gv.x), "=r"(gv.y) : "l"(g_gate + x * 2) : "memory");
  return gv;
}
__device__ __noinline__ uint32_t gate_poll(const Params* pp, int x, uint32_t tag) {
  uint2 gv;
#pragma unroll 1
  for (int spins = 0; spins < (1 << 16); spins++) {
    gv = gate_ld(x);
    if ((gv.x >> 16) == tag && (gv.y >> 16) == tag) return __byte_perm(gv.x, gv.y, 0x5410);
  }
  return __byte_perm(gate_slow(pp->u, pp->gw, x * 2), gate_slow(pp->u, pp->gw, x * 2 + 1), 0x5410);
}
__device__ __forceinline__ uint32_t gate_fin(const Params& p, uint2 gv, int x, uint32_t tag) {
  if ((gv.x >> 16) == tag && (gv.y >> 16) == tag) return __byte_perm(gv.x, gv.y, 0x5410);
  return gate_poll(&p, x, tag);
}

__device__ __forceinline__ void ld4ch(uint32_t* v, uint32_t addr) {
#pragma unroll
  for (int k = 0; k < 4; k++) v[k] = lds32(addr + k * CH_BYTES);
}
__device__ __forceinline__ void skip_terms(uint32_t* ua, uint32_t* ub, uint32_t sb, int x, uint2 dA, uint2 dB) {
  const int c = x >> 2;
  uint32_t uu[4];
  ld4ch(uu, sb + CH_OFF + (x & 3) * 4 + U_OFF + (c & 3) * U_CS + (63 - (c >> 2)) * 16);
#pragma unroll
  for (int k = 0; k < 4; k++) {
    ua[k] = hmul2(uu[k], __byte_perm((k & 2) ? dA.y : dA.x, 0, (k & 1) ? 0x3232 : 0x1010));
    ub[k] = hmul2(uu[k], __byte_perm((k & 2) ? dB.y : dB.x, 0, (k & 1) ? 0x3232 : 0x1010));
  }
}
__device__ __forceinline__ uint4 mix(const uint32_t* a, const uint32_t* b, const uint32_t* ua, const uint32_t* ub, uint32_t g2) {
  const uint32_t h2 = hsub2(0x3f803f80u, g2);
  uint32_t o[4];
#pragma unroll
  for (int k = 0; k < 4; k++) o[k] = hadd2(hmul2(g2, hadd2(a[k], ua[k])), hmul2(h2, hadd2(b[k], ub[k])));
  return make_uint4(__byte_perm(o[0], o[1], 0x5410), __byte_perm(o[2], o[3], 0x5410), __byte_perm(o[0], o[1], 0x7632), __byte_perm(o[2], o[3], 0x7632));
}
__device__ __forceinline__ void send_box(uint32_t sb, int slot, int wtid, uint32_t rank, uint4 r) {
  st_async4(mapa(sb + XIN_OFF + slot * 2048 + wtid * 16, rank ^ 1), mapa(sb + B_X + slot * 8, rank ^ 1), r.x, r.y, r.z, r.w);
}
__device__ __forceinline__ void merge_rows(uint32_t st, uint32_t rank, uint4 r, uint4 q) {
  const uint4 lo = rank ? q : r, hi = rank ? r : q;
  sts128(st, lo.x, lo.y, hi.x, hi.y); sts128(st + 2048, lo.z, lo.w, hi.z, hi.w);
}
__device__ __forceinline__ void merge_box(uint32_t sb, const CUtensorMap* tm_out, int slot, int wtid, uint32_t rank, int oc0, uint4 r, int barid) {
  const uint32_t st = sb + RAW_OFF + slot * 4096 + wtid * 16;
  mbar_wait(sb + B_X + slot * 8);
  merge_rows(st, rank, r, lds128(sb + XIN_OFF + slot * 2048 + wtid * 16));
  fence_async();
  bar_sync(barid, 128);
  if (wtid == 0) {
    asm volatile("cp.async.bulk.tensor.3d.global.shared::cta.bulk_group [%0, {%2, %3, %4}], [%1];"
                 ::"l"(tm_out), "r"(sb + RAW_OFF + slot * 4096), "r"(oc0), "r"((2 * slot + (int)rank) * 128), "r"(0) : "memory");
    asm volatile("cp.async.bulk.commit_group;" ::: "memory");
  }
}

__device__ __forceinline__ uint32_t band2(int e, int lo, int hi) {
  uint32_t r = ((uint32_t)(e - lo) <= (uint32_t)(hi - lo) ? 0x3f80u : 0u) | ((uint32_t)(e - 1 - lo) <= (uint32_t)(hi - lo) ? 0x3f800000u : 0u);
  asm volatile("" : "+r"(r));
  return r;
}

__device__ __forceinline__ void stage_done(uint32_t sb, int stage, int lane) {
  __syncwarp();
  if (lane == 0) asm volatile("mbarrier.arrive.shared::cta.b64 _, [%0];" ::"r"(sb + B_ST + 8 * stage) : "memory");
}
#define PK2(v, i) pack_bf16(v[i], v[(i) + 1])

__device__ __forceinline__ void conv_dense(uint32_t sb, uint32_t cb, uint32_t zz) {
  const int lane = threadIdx.x & 31, wq = (threadIdx.x >> 5) & 3, br = wq >> 1, hf = wq & 1, g = lane >> 2, t = lane & 3;
  const uint32_t rb = cb + R_OFF + br * R_BR;
  const int eo = 16 * hf + g - 2 * t;
  const int x0 = RD_X0 - (eo + 536);
  const uint32_t fa = rb + ((g & 1) ? 2 * x0 : RD_CS + 2 * x0 + 2);
  const uint64_t ub = mkdesc(cb + U_OFF, U_CS, 128);
  const uint32_t yd = cb + Y0_OFF + br * 4096 + ysw(4 * (63 - 8 * (lane >> 4) - (lane & 7)) + 2 * hf + ((lane >> 3) & 1));
  uint32_t A[2][4][4];
  float e64[32], e56[28], e48[24];
  auto loadA = [&](int j) {
#pragma unroll
    for (int k = 0; k < 4; k++) {
      const int s = 34 - 4 * j - k;
      if (s >= 0) {
        if (k == 0 && j == 0) A[0][0][2] = lds32(fa + (2 * s + 2) * 16);
        A[j & 1][k][0] = lds32(fa + (2 * s + 1) * 16);
        A[j & 1][k][1] = lds32(fa + (2 * s) * 16);
      }
    }
#pragma unroll
    for (int k = 0; k < 4; k++) {
      if (34 - 4 * j - k >= 0) {
        A[j & 1][k][3] = A[j & 1][k][0];
        if (k) A[j & 1][k][2] = A[j & 1][k - 1][1];
        else if (j) A[j & 1][0][2] = A[(j - 1) & 1][3][1];
      }
    }
  };
  loadA(0); loadA(1);
#pragma unroll
  for (int j = 0; j < 9; j++) {
    if (j == 4) {
      wg_wait0();
      stsm2t(yd - 7 * 512, PK2(e64, 28), PK2(e64, 30));
#pragma unroll
      for (int i = 0; i < 28; i++) e56[i] = FCPY(e64, i);
      stage_done(sb, 0, lane);
    }
    if (j == 8) {
      wg_wait0();
      stsm2t(yd - 6 * 512, PK2(e56, 24), PK2(e56, 26));
#pragma unroll
      for (int i = 0; i < 24; i++) e48[i] = FCPY(e56, i);
      stage_done(sb, 1, lane);
    }
    wg_fence();
#pragma unroll
    for (int k = 0; k < 4; k++) {
      const int s = 34 - 4 * j - k;
      if (s >= 0) {
        const int o = 2 * s - 66 + 128;
        const int cc = o & 3, rs = (o >> 2) - 32;
        const uint64_t desc = ub + (uint64_t)((cc * U_CS - rs * 16) >> 4);
        const uint32_t* a = A[j & 1][k];
        if (j < 4) wgmma_rs<64, 0>(e64, a[0], a[1], a[2], a[3], desc, s != 34);
        else if (j < 8) wgmma_rs<56, 0>(e56, a[0], a[1], a[2], a[3], desc, 1);
        else wgmma_rs<48, 0>(e48, a[0], a[1], a[2], a[3], desc, 1);
      }
    }
    wg_commit();
    if (j >= 1 && j < 8) { wg_wait1(); loadA(j + 1); }
  }
  wg_wait0();
#pragma unroll
  for (int i = 0; i < 6; i += 2) stsm4t(yd - i * 512, PK2(e48, 4 * i), PK2(e48, 4 * i + 2), PK2(e48, 4 * i + 4), PK2(e48, 4 * i + 6));
}

__device__ __noinline__ void gate_cta(const Params* pp) {
  const __nv_bfloat16 *u = pp->u, *gw = pp->gw;
  const int lane = threadIdx.x & 31;
  unsigned int epoch;
  asm volatile("ld.relaxed.gpu.global.u32 %0, [%1];" : "=r"(epoch) : "l"(&g_epoch) : "memory");
  const uint4 gw0 = ldg128(gw + lane * 8), gw1 = ldg128(gw + 256 + lane * 8);
  const uint32_t ws[8] = {gw0.x, gw0.y, gw0.z, gw0.w, gw1.x, gw1.y, gw1.z, gw1.w};
  const uint32_t tag = (epoch + 1) & 0xffffu;
  uint4 gx[4][2], nx[4][2];
  int grow = (blockIdx.x * 20 + (threadIdx.x >> 5)) * 4;
#pragma unroll
  for (int i = 0; i < 4; i++) {
    nx[i][0] = ldg128(u + (size_t)(grow + i) * D + lane * 8);
    nx[i][1] = ldg128(u + (size_t)(grow + i) * D + 256 + lane * 8);
  }
#pragma unroll 1
  for (; grow < L; grow += 80 * NGATE) {
    const int nrow = min(grow + 80 * NGATE, L - 4);
#pragma unroll
    for (int i = 0; i < 4; i++) {
      gx[i][0] = nx[i][0]; gx[i][1] = nx[i][1];
      nx[i][0] = ldg128(u + (size_t)(nrow + i) * D + lane * 8);
      nx[i][1] = ldg128(u + (size_t)(nrow + i) * D + 256 + lane * 8);
    }
    float c[2][4];
#pragma unroll
    for (int i = 0; i < 2; i++) {
      const uint4 *x = gx[2 * i], *y = gx[2 * i + 1];
      const uint32_t xs[8] = {x[0].x, x[0].y, x[0].z, x[0].w, x[1].x, x[1].y, x[1].z, x[1].w};
      const uint32_t ys[8] = {y[0].x, y[0].y, y[0].z, y[0].w, y[1].x, y[1].y, y[1].z, y[1].w};
      c[i][0] = c[i][1] = c[i][2] = c[i][3] = 0.f;
#pragma unroll
      for (int j = 0; j < 8; j += 2)
        mma16816(c[i], hmul2(xs[j], ws[j]), hmul2(ys[j], ws[j]), hmul2(xs[j + 1], ws[j + 1]), hmul2(ys[j + 1], ws[j + 1]), 0x3f803f80u, 0x3f803f80u);
    }
    float s = (lane & 2) ? ((lane & 1) ? c[1][2] : c[1][0]) : ((lane & 1) ? c[0][2] : c[0][0]);
#pragma unroll
    for (int o = 4; o < 32; o <<= 1) s += __shfl_xor_sync(0xffffffffu, s, o);
    s = bf_round(s);
    const float gv = 1.f / (1.f + expf(-s));
    const uint32_t w = (tag << 16) | (pack_bf16(gv, 0.f) & 0xffffu);
    if (lane < 4) asm volatile("st.relaxed.gpu.global.u32 [%0], %1;" ::"l"(&g_gate[grow + lane]), "r"(w) : "memory");
  }
  __syncthreads();
  if (threadIdx.x == 0 && atomicAdd(&g_ticket, 1u) == NCTA + NGATE - 1) { g_ticket = 0; g_epoch = epoch + 1; }
}

__global__ void __cluster_dims__(2, 1, 1) __launch_bounds__(640, 1)
ssm_kernel(const __grid_constant__ Params p, const __grid_constant__ CUtensorMap tm_in, const __grid_constant__ CUtensorMap tm_out) {
  extern __shared__ __align__(1024) unsigned char smem_raw[];
  const uint32_t sb = (uint32_t)__cvta_generic_to_shared(smem_raw);
  const int tid = threadIdx.x, lane = tid & 31;
  const int warp = __shfl_sync(0xffffffffu, tid >> 5, 0);
  const int ch = warp >> 2, wq = warp & 3, br = wq >> 1, hf = wq & 1;
  const int g = lane >> 2, t = lane & 3;
  if (__builtin_expect(blockIdx.x < NGATE, 0)) { gate_cta(&p); return; }
  const int bid = blockIdx.x - NGATE;
  const int d = bid * 4 + ch;
  const uint32_t rank = blockIdx.x & 1;
  const uint32_t cb = sb + CH_OFF + ch * CH_BYTES;
  const int wtid = tid & 127;
  const int oc0 = (bid >> 1) * 8;
  STAMP(0); GT(0);

  if (warp >= 16) {
    if (wtid == 0) {
      mbar_init_expect(sb + B_RAW, 32768);
#pragma unroll
      for (int i = 0; i < 4; i++) mbar_init_expect(sb + B_X + 8 * i, 2048);
      asm volatile("mbarrier.init.shared::cta.b64 [%0], 128;" ::"r"(sb + B_U) : "memory");
      asm volatile("mbarrier.init.shared::cta.b64 [%0], 128;" ::"r"(sb + B_W) : "memory");
#pragma unroll
      for (int i = 0; i < 7; i++) asm volatile("mbarrier.init.shared::cta.b64 [%0], 16;" ::"r"(sb + B_ST + 8 * i) : "memory");
      asm volatile("fence.mbarrier_init.release.cluster;" ::: "memory");
      asm volatile("fence.proxy.async.shared::cta;" ::: "memory");
    }
    __syncwarp();
    asm volatile("barrier.cluster.arrive.relaxed.aligned;" ::: "memory");
    unsigned int epoch;
    asm volatile("ld.relaxed.gpu.global.u32 %0, [%1];" : "=r"(epoch) : "l"(&g_epoch) : "memory");
    asm volatile("barrier.cluster.wait.aligned;" ::: "memory");
    if (wtid == 0) {
      asm volatile("cp.async.bulk.tensor.5d.shared::cluster.global.mbarrier::complete_tx::bytes.multicast::cluster [%0], [%1, {%3, %4, %4, %4, %5}], [%2], %6;"
                   ::"r"(sb + RAW_OFF + rank * 16384), "l"(&tm_in), "r"(sb + B_RAW), "r"(oc0), "r"(0), "r"((int)rank * 32), "h"((unsigned short)3) : "memory");
    }
    sts128(sb + CH_OFF + wq * CH_BYTES + U_OFF + (lane >> 3) * U_CS + (64 + (lane & 7)) * 16, 0, 0, 0, 0);
    const uint2 dA = ldg64(p.A_D + bid * 4), dB = ldg64(p.B_D + bid * 4);
    uint32_t BA[3][4], BB[4][4];
    {
      const int l1 = br ? 3 : 6, h1 = br ? 5 : 10, l2 = br ? 5 : 12, h2 = br ? 11 : 20;
#pragma unroll
      for (int i = 0; i < 4; i++) {
        const int e = 16 * hf + g - 2 * t + 32 - 16 * i;
        BB[i][0] = band2(e, l2, h2); BB[i][1] = band2(e + 8, l2, h2); BB[i][2] = band2(e - 8, l2, h2); BB[i][3] = BB[i][0];
        if (i) { BA[i - 1][0] = band2(e, l1, h1); BA[i - 1][1] = band2(e + 8, l1, h1); BA[i - 1][2] = band2(e - 8, l1, h1); BA[i - 1][3] = BA[i - 1][0]; }
      }
    }
    const uint32_t tag = (epoch + 1) & 0xffffu;
    if (wtid == 0) sts32(sb + TAG_OFF, tag);
    STAMP(3);
    mbar_wait(sb + B_RAW);
    STAMP(4);
    {
      const uint32_t dst = sb + CH_OFF + (g & 3) * CH_BYTES + U_OFF + t * U_CS + (63 - wq * 16) * 16;
#pragma unroll
      for (int h = 0; h < 2; h++) {
        uint32_t r[8][4];
#pragma unroll
        for (int i = 0; i < 8; i++) ldsm4t(sb + RAW_OFF + (wq * 16 + h * 8 + i) * 512 + lane * 16, r[i][0], r[i][1], r[i][2], r[i][3]);
        if ((uint32_t)(g >> 2) == rank) {
#pragma unroll
          for (int i = 0; i < 8; i++) sts128(dst - (h * 8 + i) * 16, r[i][0], r[i][1], r[i][2], r[i][3]);
        }
      }
    }
    fence_async();
    asm volatile("mbarrier.arrive.shared::cta.b64 _, [%0];" ::"r"(sb + B_U) : "memory");
    bar_sync(5, 128);
    STAMP(5);
    {
      const int mrow = lane & 7, mi = lane >> 3;
      const uint64_t ub0 = mkdesc(sb + CH_OFF + U_OFF, U_CS, 128);
      uint32_t wa, wb;
      {
        const int c = 4 * (47 - 8 * (mi >> 1) - mrow) + 2 * hf + (mi & 1);
        wa = sb + CH_OFF + (br ? W3_OFF : W5_OFF) + (5 - (c >> 5)) * 576 + ((c & 31) >> 3) * 144 + (c & 7) * 16;
        const int c2 = c - 64, pp = c2 >> 1;
        wb = sb + CH_OFF + (br ? W7_OFF : W9_OFF) + (1 - (pp >> 5)) * 1152 + (c2 & 1) * 576 + ((pp & 31) >> 3) * 144 + (pp & 7) * 16;
      }
      {
        float w1[24];
#pragma unroll
        for (int i = 0; i < 24; i++) w1[i] = 0.f;
#pragma unroll 1
        for (int k = 0; k < 4; k++) {
          wg_fence();
#pragma unroll
          for (int i = 0; i < 3; i++)
            wgmma_rs<48, 0>(w1, BA[i][0], BA[i][1], BA[i][2], BA[i][3],
                            ub0 + (uint64_t)((k * CH_BYTES + ((2 * i + 2) & 3) * U_CS + (16 + (i == 0)) * 16) >> 4), i);
          wg_commit();
          wg_wait0();
#pragma unroll
          for (int i = 0; i < 3; i++) stsm4t(wa + k * CH_BYTES + i * 1152, PK2(w1, 8 * i), PK2(w1, 8 * i + 2), PK2(w1, 8 * i + 4), PK2(w1, 8 * i + 6));
        }
      }
      {
        float w2[2][16];
#pragma unroll
        for (int i = 0; i < 16; i++) { w2[0][i] = 0.f; w2[1][i] = 0.f; }
#pragma unroll 1
        for (int kp = 0; kp < 2; kp++) {
          wg_fence();
#pragma unroll
          for (int k = 0; k < 2; k++)
#pragma unroll
            for (int i = 0; i < 4; i++)
              wgmma_rs<32, 0>(w2[k], BB[i][0], BB[i][1], BB[i][2], BB[i][3],
                              ub0 + (uint64_t)(((2 * kp + k) * CH_BYTES + ((2 * i) & 3) * U_CS + (32 + (i < 2)) * 16) >> 4), i);
          wg_commit();
          wg_wait0();
#pragma unroll
          for (int k = 0; k < 2; k++)
#pragma unroll
            for (int i = 0; i < 2; i++)
              stsm4t(wb + (2 * kp + k) * CH_BYTES + i * 1152, PK2(w2[k], 8 * i), PK2(w2[k], 8 * i + 2), PK2(w2[k], 8 * i + 4), PK2(w2[k], 8 * i + 6));
        }
      }
    }
    fence_async();
    asm volatile("mbarrier.arrive.shared::cta.b64 _, [%0];" ::"r"(sb + B_W) : "memory");
    STAMP(7);
    {
      const int bsel = (int)rank ^ br ^ 1, xl = wtid & 63;
      uint2 gl[4];
      uint32_t ua[4][4], ub[4][4];
#pragma unroll
      for (int i = 0; i < 4; i++) skip_terms(ua[i], ub[i], sb, (2 * (i >> 1) + bsel) * 128 + (i & 1) * 64 + xl, dA, dB);
      const uint32_t yo = sb + CH_OFF + (xl & 3) * 4 + ysw(xl >> 2) + bsel * 512;
#pragma unroll
      for (int i = 0; i < 2; i++) gl[i] = gate_ld(bsel * 128 + i * 64 + xl);
#pragma unroll
      for (int slot = 0; slot < 2; slot++) {
        const int box = 2 * slot + bsel;
        uint32_t g2[2], ya[2][4], yb[2][4];
#pragma unroll
        for (int h = 0; h < 2; h++) g2[h] = gate_fin(p, gl[2 * slot + h], box * 128 + h * 64 + xl, tag);
        mbar_wait(sb + B_ST + 8 * box);
        STAMP(8 + slot);
        if (slot == 0) { gl[2] = gate_ld((2 + bsel) * 128 + xl); gl[3] = gate_ld((2 + bsel) * 128 + 64 + xl); }
#pragma unroll
        for (int h = 0; h < 2; h++) {
          const uint32_t yh = (yo ^ (h * 32)) + h * 256 + slot * 1024;
          ld4ch(ya[h], yh + Y0_OFF); ld4ch(yb[h], yh + Y0_OFF + 4096);
          if (slot) {
            uint32_t a2[4], b2[4];
            ld4ch(a2, yh + Y2_OFF - 1024); ld4ch(b2, yh + Y2_OFF - 1024 + 3072);
#pragma unroll
            for (int k = 0; k < 4; k++) { ya[h][k] = hadd2(ya[h][k], a2[k]); yb[h][k] = hadd2(yb[h][k], b2[k]); }
          }
        }
        const uint4 r0 = mix(ya[0], yb[0], ua[2 * slot], ub[2 * slot], g2[0]), r1 = mix(ya[1], yb[1], ua[2 * slot + 1], ub[2 * slot + 1], g2[1]);
        if (br == 0) { send_box(sb, slot, xl, rank, r0); send_box(sb, slot, xl + 64, rank, r1); }
        else {
          const uint32_t st = sb + RAW_OFF + slot * 4096 + xl * 16, xin = sb + XIN_OFF + slot * 2048 + xl * 16;
          mbar_wait(sb + B_X + slot * 8);
          const uint4 q0 = lds128(xin), q1 = lds128(xin + 1024);
          merge_rows(st, rank, r0, q0); merge_rows(st + 1024, rank, r1, q1);
          fence_async();
          bar_sync(6, 64);
          if (xl == 0) {
            asm volatile("cp.async.bulk.tensor.3d.global.shared::cta.bulk_group [%0, {%2, %3, %4}], [%1];"
                         ::"l"(&tm_out), "r"(sb + RAW_OFF + slot * 4096), "r"(oc0), "r"(box * 128), "r"(0) : "memory");
            asm volatile("cp.async.bulk.commit_group;" ::: "memory");
          }
        }
        STAMP(10 + slot);
      }
    }
    if (wtid == 0 && atomicAdd(&g_ticket, 1u) == NCTA + NGATE - 1) { g_ticket = 0; g_epoch = epoch + 1; }
    if (wtid == 64) asm volatile("cp.async.bulk.wait_group.read 0;" ::: "memory");
    STAMP(15);
    return;
  }
  asm volatile("barrier.cluster.arrive.relaxed.aligned;" ::: "memory");

  const int moff = (bid * 4 + (tid >> 7)) * NM + (tid & 63) * 2;
  const int brt = (tid >> 6) & 1;
  const __nv_bfloat16* const* tp = p.t + (brt ? 0 : 6);
  const uint32_t q0 = *(const uint32_t*)(tp[0] + moff), q1 = *(const uint32_t*)(tp[1] + moff);
  const uint32_t q2 = *(const uint32_t*)(tp[2] + moff), q3 = *(const uint32_t*)(tp[3] + moff);
  const uint2 ldt4 = *(const uint2*)(tp[4] + bid * 4);
  const uint32_t q4 = *(const uint32_t*)(tp[brt ? 2 : 5] + moff), q5 = *(const uint32_t*)(tp[brt ? 3 : 6] + moff);

  for (int i = wtid & 63; i < R_BR / 16; i += 64) sts128(cb + R_OFF + br * R_BR + i * 16, 0, 0, 0, 0);
  STAMP(1);

  float acc[5][4];
  float k2048 = 0.f;
  const uint32_t scr = cb + Y0_OFF + wq * SCR_BYTES;
  const uint32_t scr2 = sb + SC2_OFF + warp * 640;
  {
    const uint32_t ldt2 = (ch & 2) ? ldt4.y : ldt4.x;
    const float dt = bf_round(expf((ch & 1) ? bf_hi(ldt2) : bf_lo(ldt2)));
#pragma unroll
    for (int i = 0; i < 5; i++) acc[i][0] = acc[i][1] = acc[i][2] = acc[i][3] = 0.f;
    STAMP(2);
    const uint32_t tb = scr + lane * 16;
    const uint32_t ta = scr + (lane >> 3) * 512 + (lane & 7) * 16;
    const uint32_t tc = ((lane & 8) ? scr2 : scr + 4096) + (lane >> 4) * 128 + (lane & 7) * 16;
    const uint32_t tm = scr2 + 512 + ((lane >> 3) & 1) * 64 + (lane >> 4) * 16;
    cf cc[2], zz1[2], zz128[2];
#pragma unroll
    for (int r = 0; r < 2; r++) {
      float v0 = r ? bf_hi(q0) : bf_lo(q0), v1 = r ? bf_hi(q1) : bf_lo(q1), v2 = r ? bf_hi(q2) : bf_lo(q2);
      float v3 = r ? bf_hi(q3) : bf_lo(q3), v4 = r ? bf_hi(q4) : bf_lo(q4), v5 = r ? bf_hi(q5) : bf_lo(q5);
      if (br == 0) { cc[r] = cmul(cf{v2, v3}, cf{dt * v4, dt * v5}); }
      else { v0 = -bf_round(expf(v0)); cc[r] = cf{2.f * dt * v2, 2.f * dt * v3}; }
      const float xl = (dt * v0) * 1.4426950408889634f, y = dt * v1;
      zz1[r] = cexp_p(xl, y, 1.f); zz128[r] = cexp_p(xl, y, 128.f);
    }
    uint32_t T[10][4], m4;
    auto produce = [&](int r) {
      const cf c = cc[r], z1 = zz1[r], z128 = zz128[r];
      const cf z2 = csq(z1), z4 = csq(z2), z8 = csq(z4);
      const cf w8 = {z8.re, -z8.im};
      const cf z16 = csq(w8), z24 = cmul(z16, w8), z32 = csq(z16), z40 = cmul(z32, w8), z48 = csq(z24), z56 = cmul(z32, z24), z64 = csq(z32);
      const cf z256 = csq(z128), z512 = csq(z256), z1024 = csq(z512), z2048 = csq(z1024);
      k2048 += fmaf(c.re, z2048.re, -c.im * z2048.im);
      {
        T[0][0] = pack_bf16(1.f, z8.re); T[0][1] = pack_bf16(z16.re, z24.re); T[0][2] = pack_bf16(z32.re, z40.re); T[0][3] = pack_bf16(z48.re, z56.re);
        T[2][0] = pack_bf16(0.f, w8.im); T[2][1] = pack_bf16(z16.im, z24.im); T[2][2] = pack_bf16(z32.im, z40.im); T[2][3] = pack_bf16(z48.im, z56.im);
        const uint32_t yr = pack_bf16(z64.re, z64.re), yi = pack_bf16(z64.im, z64.im), nyi = yi ^ 0x80008000u;
#pragma unroll
        for (int i = 0; i < 4; i++) CMUL2(T[1][i], T[3][i], T[0][i], T[2][i], yr, yi, nyi);
      }
      {
        const cf h1 = cmul(c, z128), h2 = cmul(c, z256), h3 = cmul(h1, z256), h4 = cmul(c, z512), h5 = cmul(h1, z512), h6 = cmul(h2, z512), h7 = cmul(h3, z512);
        const cf e1 = cmul(c, z1), e2 = cmul(c, z2), e3 = cmul(e1, z2), e129 = cmul(h1, z1), e130 = cmul(h1, z2), e131 = cmul(e129, z2);
        const cf e258 = cmul(h2, z2), e386 = cmul(h3, z2);
        T[4][0] = pack_bf16(c.re, e1.re); T[4][1] = pack_bf16(e2.re, e3.re); T[4][2] = pack_bf16(h1.re, e129.re); T[4][3] = pack_bf16(e130.re, e131.re);
        T[5][0] = pack_bf16(c.im, e1.im); T[5][1] = pack_bf16(e2.im, e3.im); T[5][2] = pack_bf16(h1.im, e129.im); T[5][3] = pack_bf16(e130.im, e131.im);
        T[6][0] = pack_bf16(h2.re, e258.re); T[6][1] = pack_bf16(h3.re, e386.re); T[6][2] = pack_bf16(h4.re, h5.re); T[6][3] = pack_bf16(h6.re, h7.re);
        T[7][0] = pack_bf16(h2.im, e258.im); T[7][1] = pack_bf16(h3.im, e386.im); T[7][2] = pack_bf16(h4.im, h5.im); T[7][3] = pack_bf16(h6.im, h7.im);
        const uint32_t xr[4] = {__byte_perm(T[4][0], T[4][2], 0x5410), __byte_perm(T[6][0], T[6][1], 0x5410), T[6][2], T[6][3]};
        const uint32_t xi[4] = {__byte_perm(T[5][0], T[5][2], 0x5410), __byte_perm(T[7][0], T[7][1], 0x5410), T[7][2], T[7][3]};
        const uint32_t yr = pack_bf16(z1024.re, z1024.re), yi = pack_bf16(z1024.im, z1024.im), nyi = yi ^ 0x80008000u;
#pragma unroll
        for (int i = 0; i < 4; i++) CMUL2(T[8][i], T[9][i], xr[i], xi[i], yr, yi, nyi);
        m4 = pack_bf16(z4.re, z4.im);
      }
    };
    auto store = [&]() {
#pragma unroll
      for (int m = 0; m < 9; m++) sts128(tb + m * 512, T[m][0], T[m][1], T[m][2], T[m][3]);
      sts128(scr2 + lane * 16, T[9][0], T[9][1], T[9][2], T[9][3]);
      sts16(scr2 + 512 + lane * 2, m4); sts16(scr2 + 576 + lane * 2, m4 >> 16);
    };
    auto consume = [&]() {
#pragma unroll
      for (int kp = 0; kp < 2; kp++) {
        uint32_t rr[2], ri[2], yr[2], yi[2];
        ldsm4t(tc + kp * 256, rr[0], ri[0], rr[1], ri[1]);
        ldsm4(tm + kp * 32, yr[0], yi[0], yr[1], yi[1]);
#pragma unroll
        for (int k2 = 0; k2 < 2; k2++) {
          const int kk = kp * 2 + k2;
          uint32_t a0, a1, a2, a3, pr, pi, qr, qi, xr, xi;
          ldsm4t(ta + kk * 128, a0, a1, a2, a3);
          ldsm4t(ta + 2048 + kk * 128, pr, pi, qr, qi);
          const uint32_t nyi = yi[k2] ^ 0x80008000u;
          mma16816(acc[0], a0, a1, a2, a3, pr, pi);
          mma16816(acc[2], a0, a1, a2, a3, qr, qi);
          mma16816(acc[4], a0, a1, a2, a3, rr[k2], ri[k2]);
          CMUL2(xr, xi, pr, pi, yr[k2], yi[k2], nyi);
          mma16816(acc[1], a0, a1, a2, a3, xr, xi);
          CMUL2(xr, xi, qr, qi, yr[k2], yi[k2], nyi);
          mma16816(acc[3], a0, a1, a2, a3, xr, xi);
        }
      }
    };
    produce(0); store();
    __syncwarp();
    consume(); produce(1);
    __syncwarp();
    store();
#pragma unroll
    for (int o = 16; o; o >>= 1) k2048 += __shfl_xor_sync(0xffffffffu, k2048, o);
    __syncwarp();
    consume();
  }
  STAMP(3);
  __syncwarp();
  {
    const uint32_t xs = scr + lane * 16;
#define OTH(i, k) __float_as_uint(hf ? acc[i][k] : acc[i][2 + (k)])
    sts128(xs, OTH(0, 0), OTH(0, 1), OTH(1, 0), OTH(1, 1));
    sts128(xs + 512, OTH(2, 0), OTH(2, 1), OTH(3, 0), OTH(3, 1));
    sts128(xs + 1024, OTH(4, 0), OTH(4, 1), __float_as_uint(k2048), 0);
#undef OTH
  }

  bar_sync(7 + (warp >> 1), 64);
  STAMP(4);
  {
    const uint32_t xo = cb + Y0_OFF + (wq ^ 1) * SCR_BYTES + lane * 16;
    const uint4 o0 = lds128(xo), o1 = lds128(xo + 512), o2 = lds128(xo + 1024);
    const uint32_t rb = cb + R_OFF + br * R_BR;
#define OWN(i, k) (hf ? acc[i][2 + (k)] : acc[i][k])
    const uint32_t vP = pack_bf16(OWN(0, 1) + __uint_as_float(o0.y), OWN(0, 0) + __uint_as_float(o0.x));
    const uint32_t vP4 = pack_bf16(OWN(1, 1) + __uint_as_float(o0.w), OWN(1, 0) + __uint_as_float(o0.z));
    const uint32_t vQ = pack_bf16(OWN(2, 1) + __uint_as_float(o1.y), OWN(2, 0) + __uint_as_float(o1.x));
    const uint32_t vQ4 = pack_bf16(OWN(3, 1) + __uint_as_float(o1.w), OWN(3, 0) + __uint_as_float(o1.z));
    const uint32_t vR = pack_bf16(OWN(4, 1) + __uint_as_float(o2.y), OWN(4, 0) + __uint_as_float(o2.x));
#undef OWN
    const int j = g + 8 * hf;
    {
      const int a = 2 * (t & 1) + 64 * (t & 2) + 8 * j;
      const uint32_t ad = rb + 2 * (RD_X0 - 1 - a);
      const uint32_t a1 = (t & 2) ? ad - 8 : ad, a2 = (t & 2) ? ad : ad - 8;
      const uint32_t w1 = (t & 2) ? vP4 : vP, w2 = (t & 2) ? vP : vP4;
      sts32(a1, w1); sts32(a2, w2);
      sts16(a1 + RD_CS + 2, w1); sts16(a1 + RD_CS + 4, w1 >> 16);
      sts16(a2 + RD_CS + 2, w2); sts16(a2 + RD_CS + 4, w2 >> 16);
    }
    if (t < 2) {
      const int b = 256 + 128 * t + 8 * j;
      const uint32_t ad = rb + 2 * (RD_X0 - 6 - b);
      const uint32_t v22 = __byte_perm(vQ4, 0, 0x3232), v00 = __byte_perm(vQ, 0, 0x3232);
      sts16(ad, vQ4);
      sts64(ad + 2, v22, __byte_perm(vQ4, vQ, 0x5432));
      sts32(ad + 10, v00);
      if (b != 256) { sts16(ad + 14, v00); sts128(ad + RD_CS + 2, vQ4, v22, vQ, v00); }
      else { sts64(ad + RD_CS + 2, vQ4, v22); sts32(ad + RD_CS + 10, vQ); sts16(ad + RD_CS + 14, v00); }
    } else {
      const uint32_t ao = rb + R_O2 + 2 * (159 - (32 * t + j)), ae = ao - (R_O2 - R_E2) + 2;
      sts16(ao, vQ4 >> 16); sts16(ao + RS_CS + 2, vQ4 >> 16); sts16(ao - 32, vQ4); sts16(ao - 32 + RS_CS + 2, vQ4);
      sts16(ae - 32, vQ); sts16(ae - 32 + RS_CS + 2, vQ);
      if (lane != 2 || hf) { sts16(ae, vQ >> 16); sts16(ae + RS_CS + 2, vQ >> 16); }
      else {
        const uint32_t vv = __byte_perm(vQ, 0, 0x3232), ad = rb + 2 * (RD_X0 - 514);
        sts16(ad, vv); sts32(ad + 2, vv); sts16(ad + 6, vv); sts64(ad + RD_CS + 2, vv, vv);
      }
    }
    {
      const uint32_t a = rb + ((g & 1) ? R_O3 : R_E3 + 2) + 2 * (159 - (64 + 16 * t + (j >> 1)));
      const bool p1024 = (lane == 0) && (hf == 0);
      const uint32_t a00 = p1024 ? rb + R_E2 + 2 * (159 - 127) : a;
      sts16(a00, vR >> 16); sts16(a00 + RS_CS + 2, vR >> 16);
      sts16(a - 16, vR); sts16(a - 16 + RS_CS + 2, vR);
      if (p1024) {
        sts32(sb + K1024_OFF + (ch * 2 + br) * 4, __byte_perm(vR, 0, 0x3232));
        const uint32_t kv = pack_bf16(k2048 + __uint_as_float(o2.z), 0.f);
        sts16(rb + R_E3 + 2 * (159 - 127), kv); sts16(rb + R_E3 + 2 * (159 - 127) + RS_CS + 2, kv);
      }
    }
  }
  STAMP(5);
  asm volatile("barrier.cluster.wait.aligned;" ::: "memory");
  bar_sync(7 + (warp >> 1), 64);
  mbar_wait(sb + B_U);
  STAMP(6);

  const uint32_t zz = lds32(cb + R_OFF + br * R_BR);
  conv_dense(sb, cb, zz);
  STAMP(8);
  {
    const int x = (4 + ch) * 128 + wtid, c = x >> 2;
    const uint2 dA = ldg64(p.A_D + bid * 4), dB = ldg64(p.B_D + bid * 4);
    const uint2 gl = gate_ld(x);
    const uint32_t rb = cb + R_OFF + br * R_BR;
    float e48[24], e40[20], e32[16], h32[16], h16[8];
    const int x1 = 159 - (16 * hf + g - 2 * t + 136);
    const uint32_t fs = rb + ((g & 1) ? 2 * x1 : RS_CS + 2 * x1 + 2);
    uint32_t A[2][4][4];
    auto loadA = [&](int buf, uint32_t oe, uint32_t oo, int i0) {
#pragma unroll
      for (int a = 0; a < 2; a++) {
        const uint32_t base = fs + (a ? oo : oe) + i0 * 16;
        uint32_t* k0 = A[buf][2 * a];
        uint32_t* k1 = A[buf][2 * a + 1];
        k0[1] = lds32(base); k0[0] = lds32(base + 16); k0[2] = lds32(base + 32); k1[0] = lds32(base + 48); k1[2] = lds32(base + 64);
        k0[3] = k0[0]; k1[1] = k0[2]; k1[3] = k1[0];
      }
    };
    loadA(0, R_E2, R_O2, 8);
    loadA(1, R_E2, R_O2, 4);
    mbar_wait(sb + B_W);
    const uint64_t d5 = mkdesc(cb + W5_OFF, 144, 576), d3 = mkdesc(cb + W3_OFF, 144, 576);
    const uint64_t d9 = mkdesc(cb + W9_OFF, 144, 576), d7 = mkdesc(cb + W7_OFF, 144, 576);
    const uint32_t y2d = cb + Y2_OFF + br * 3072 + ysw(32 * (5 - (lane >> 4)) + 16 * hf + (lane & 15));
    const uint32_t y3d = cb + Y3_OFF + br * 2048 + ysw(2 * (16 * hf + (lane & 15)) + (lane >> 4));
#define FAR4(N, ACC, BUF, DA, DB, OFF, FIRST)                                                            \
    wg_fence();                                                                                           \
    _Pragma("unroll") for (int k = 0; k < 4; k++) {                                                      \
      const uint32_t* a = A[BUF][k];                                                                      \
      wgmma_rs<N, 1>(ACC, a[0], a[1], a[2], a[3], ((k >> 1) ? DB : DA) + (k & 1) * 18 + (OFF), !(FIRST) || k); \
    }                                                                                                     \
    wg_commit();
    FAR4(48, e48, 0, d5, d3, 0, 1)
    wg_wait0();
    loadA(0, R_E2, R_O2, 0);
    stsm2(y2d - 5 * 512, PK2(e48, 20), PK2(e48, 22));
#pragma unroll
    for (int i = 0; i < 20; i++) e40[i] = FCPY(e48, i);
    stage_done(sb, 2, lane);
    FAR4(40, e40, 1, d5, d3, 36, 0)
    wg_wait0();
    loadA(1, R_E3, R_O3, 8);
    stsm2(y2d - 4 * 512, PK2(e40, 16), PK2(e40, 18));
#pragma unroll
    for (int i = 0; i < 16; i++) e32[i] = FCPY(e40, i);
    stage_done(sb, 3, lane);
    FAR4(32, e32, 0, d5, d3, 72, 0)
    FAR4(32, h32, 1, d9, d7, 0, 1)
    wg_wait1();
    loadA(0, R_E3, R_O3, 4);
    stsm4(y2d, PK2(e32, 0), PK2(e32, 2), PK2(e32, 4), PK2(e32, 6));
    stsm4(y2d - 2 * 512, PK2(e32, 8), PK2(e32, 10), PK2(e32, 12), PK2(e32, 14));
    stage_done(sb, 4, lane);
    STAMP(9);
    wg_wait0();
    stsm4(y3d, PK2(h32, 8), PK2(h32, 10), PK2(h32, 12), PK2(h32, 14));
#pragma unroll
    for (int i = 0; i < 8; i++) h16[i] = FCPY(h32, i);
    stage_done(sb, 5, lane);
    FAR4(16, h16, 0, d9, d7, 72, 0)
#undef FAR4
    const uint32_t yo = sb + CH_OFF + (x & 3) * 4 + ysw(c);
    uint32_t ua[4], ub[4], ya[4], yb[4], a2[4], b2[4], a3[4], b3[4], s2[4];
    skip_terms(ua, ub, sb, x, dA, dB);
    {
      const int xa = x - 514, xb = x - 513, ca = xa >> 2, cb2 = xb >> 2;
      ld4ch(s2, sb + CH_OFF + U_OFF + (xa & 3) * 4 + (ca & 3) * U_CS + (63 - (ca >> 2)) * 16);
      ld4ch(a3, sb + CH_OFF + U_OFF + (xb & 3) * 4 + (cb2 & 3) * U_CS + (63 - (cb2 >> 2)) * 16);
#pragma unroll
      for (int k = 0; k < 4; k++) s2[k] = hadd2(s2[k], __byte_perm(s2[k], a3[k], 0x5432));
    }
    const uint32_t tag = lds32(sb + TAG_OFF);
    wg_wait0();
    stsm4(y3d + 1024, PK2(h16, 0), PK2(h16, 2), PK2(h16, 4), PK2(h16, 6));
    stage_done(sb, 6, lane);
    STAMP(10);
    const uint32_t g2 = gate_fin(p, gl, x, tag);
    mbar_wait(sb + B_ST + 8 * 4);
    const uint4 k0 = lds128(sb + K1024_OFF), k1 = lds128(sb + K1024_OFF + 16);
    const uint32_t kk[8] = {k0.x, k0.y, k0.z, k0.w, k1.x, k1.y, k1.z, k1.w};
    ld4ch(ya, yo + Y0_OFF); ld4ch(yb, yo + Y0_OFF + 4096);
    ld4ch(a2, yo + Y2_OFF - 1024); ld4ch(b2, yo + Y2_OFF - 1024 + 3072);
    mbar_wait(sb + B_ST + 8 * (5 + (ch >> 1)));
    STAMP(12);
    ld4ch(a3, yo + Y3_OFF - 2048); ld4ch(b3, yo + Y3_OFF - 2048 + 2048);
#pragma unroll
    for (int k = 0; k < 4; k++) {
      ya[k] = hadd2(ya[k], hadd2(hfma2(kk[2 * k], s2[k], a2[k]), a3[k]));
      yb[k] = hadd2(yb[k], hadd2(hfma2(kk[2 * k + 1], s2[k], b2[k]), b3[k]));
    }
    const uint4 r = mix(ya, yb, ua, ub, g2);
    if ((uint32_t)(ch & 1) != rank) send_box(sb, 2 + (ch >> 1), wtid, rank, r);
    else merge_box(sb, &tm_out, 2 + (ch >> 1), wtid, rank, oc0, r, 1 + ch);
  }
  STAMP(14);
  if (wtid == 0) asm volatile("cp.async.bulk.wait_group.read 0;" ::: "memory");
  STAMP(15); GT(1);
}

typedef CUresult (*EncodeFn)(CUtensorMap*, CUtensorMapDataType, cuuint32_t, void*, const cuuint64_t*, const cuuint64_t*,
                             const cuuint32_t*, const cuuint32_t*, CUtensorMapInterleave, CUtensorMapSwizzle,
                             CUtensorMapL2promotion, CUtensorMapFloatOOBfill);

}

extern "C" void kernel_launch(void* const* d_in, const int* in_sizes, int n_in, void* d_out, int out_size) {
  (void)in_sizes; (void)n_in; (void)out_size;
  typedef const __nv_bfloat16* bp;
  Params p;
  p.t[0] = (bp)d_in[10]; p.t[1] = (bp)d_in[11]; p.t[2] = (bp)d_in[12]; p.t[3] = (bp)d_in[13]; p.t[4] = (bp)d_in[14]; p.t[5] = nullptr;
  p.t[6] = (bp)d_in[1]; p.t[7] = (bp)d_in[2]; p.t[8] = (bp)d_in[5]; p.t[9] = (bp)d_in[6]; p.t[10] = (bp)d_in[7];
  p.t[11] = (bp)d_in[3]; p.t[12] = (bp)d_in[4]; p.t[13] = nullptr;
  p.u = (bp)d_in[0]; p.gw = (bp)d_in[16]; p.A_D = (bp)d_in[8]; p.B_D = (bp)d_in[15];
  static EncodeFn enc = nullptr;
  if (!enc) {
    cudaDriverEntryPointQueryResult qr;
    cudaGetDriverEntryPoint("cuTensorMapEncodeTiled", (void**)&enc, cudaEnableDefault, &qr);
    cudaFuncSetAttribute(ssm_kernel, cudaFuncAttributeMaxDynamicSharedMemorySize, SMEM_BYTES);
  }
  CUtensorMap tm_in, tm_out;
  {
    cuuint64_t gd[5] = {512, 2, 4, 4, 64};
    cuuint64_t gs[4] = {1024, 8192, 2048, 32768};
    cuuint32_t bx[5] = {8, 2, 4, 4, 32};
    cuuint32_t es[5] = {1, 1, 1, 1, 1};
    enc(&tm_in, CU_TENSOR_MAP_DATA_TYPE_BFLOAT16, 5, d_in[0], gd, gs, bx, es, CU_TENSOR_MAP_INTERLEAVE_NONE,
        CU_TENSOR_MAP_SWIZZLE_NONE, CU_TENSOR_MAP_L2_PROMOTION_NONE, CU_TENSOR_MAP_FLOAT_OOB_FILL_NONE);
  }
  {
    cuuint64_t gd[3] = {512, 1024, 2};
    cuuint64_t gs[2] = {2048, 1024};
    cuuint32_t bx[3] = {8, 128, 2};
    cuuint32_t es[3] = {1, 1, 1};
    enc(&tm_out, CU_TENSOR_MAP_DATA_TYPE_BFLOAT16, 3, d_out, gd, gs, bx, es, CU_TENSOR_MAP_INTERLEAVE_NONE,
        CU_TENSOR_MAP_SWIZZLE_NONE, CU_TENSOR_MAP_L2_PROMOTION_NONE, CU_TENSOR_MAP_FLOAT_OOB_FILL_NONE);
  }
  ssm_kernel<<<NCTA + NGATE, 640, SMEM_BYTES, cudaStreamPerThread>>>(p, tm_in, tm_out);
}
```

```cpp
#include <cuda_runtime.h>
#include <cuda.h>
#include <cuda_bf16.h>
#include <stdint.h>

namespace {
#define FCPY(v, i) (((i) % 3 == 2) ? __uint_as_float(opq(__float_as_uint(v[i]), zz)) : opqf(v[i], zz))

constexpr int L = 2048, D = 512, NM = 128;
constexpr int NCTA = 128;
constexpr int NGATE = 4;

constexpr int RAW_OFF = 0;
constexpr int XIN_OFF = 32768;
constexpr int SC2_OFF = XIN_OFF + 8192;
constexpr int BAR_OFF = SC2_OFF + 10240;
constexpr int CH_OFF = BAR_OFF + 256;
constexpr int U_CS = 1184;
constexpr int U_OFF = 0;
constexpr int R_OFF = 4736;
constexpr int RD_X0 = 567;
constexpr int RD_CS = 1216;
constexpr int RS_CS = 320;
constexpr int R_E2 = 2 * RD_CS, R_O2 = R_E2 + 2 * RS_CS, R_E3 = R_O2 + 2 * RS_CS, R_O3 = R_E3 + 2 * RS_CS;
constexpr int R_BR = R_O3 + 2 * RS_CS;
constexpr int W5_OFF = R_OFF + 2 * R_BR;
constexpr int W3_OFF = W5_OFF + 3456;
constexpr int W9_OFF = W3_OFF + 3456;
constexpr int W7_OFF = W9_OFF + 2304;
constexpr int Y0_OFF = W7_OFF + 2304;
constexpr int Y2_OFF = Y0_OFF + 8192, Y3_OFF = Y2_OFF + 6144;
constexpr int CH_BYTES = Y0_OFF + 18432 + 16;
constexpr int SMEM_BYTES = CH_OFF + 4 * CH_BYTES;
static_assert(CH_BYTES % 128 == 16, "bank staggering of the channel blocks");
static_assert(SMEM_BYTES <= 232448, "smem");
constexpr int B_RAW = BAR_OFF, B_X = BAR_OFF + 8, B_U = BAR_OFF + 40, B_W = BAR_OFF + 48;
constexpr int TAG_OFF = BAR_OFF + 56;
constexpr int K1024_OFF = BAR_OFF + 64;
constexpr int K2048_OFF = BAR_OFF + 160;
constexpr int B_ST = BAR_OFF + 96;

__device__ unsigned int g_gate[L];
__device__ unsigned int g_epoch;
__device__ unsigned int g_ticket;

#define STAMP(k)
#define GT(k)

struct Params {
  const __nv_bfloat16* t[14];
  const __nv_bfloat16 *u, *gw, *A_D, *B_D;
};

template <int N, int TB> __device__ __forceinline__ void wgmma_rs(float* d, uint32_t a0, uint32_t a1, uint32_t a2, uint32_t a3, uint64_t desc, int sc);
template <> __device__ __forceinline__ void wgmma_rs<64, 0>(float* d, uint32_t a0, uint32_t a1, uint32_t a2, uint32_t a3, uint64_t desc, int sc) {
  asm volatile("{\n.reg .pred p;\nsetp.ne.b32 p, %37, 0;\n"
    "wgmma.mma_async.sync.aligned.m64n64k16.f32.bf16.bf16 {%0,%1,%2,%3,%4,%5,%6,%7,%8,%9,%10,%11,%12,%13,%14,%15,%16,%17,%18,%19,%20,%21,%22,%23,%24,%25,%26,%27,%28,%29,%30,%31}, {%32,%33,%34,%35}, %36, p, 1, 1, 0;\n}"
    : "+f"(d[0]), "+f"(d[1]), "+f"(d[2]), "+f"(d[3]), "+f"(d[4]), "+f"(d[5]), "+f"(d[6]), "+f"(d[7]), "+f"(d[8]), "+f"(d[9]), "+f"(d[10]), "+f"(d[11]), "+f"(d[12]), "+f"(d[13]), "+f"(d[14]), "+f"(d[15]), "+f"(d[16]), "+f"(d[17]), "+f"(d[18]), "+f"(d[19]), "+f"(d[20]), "+f"(d[21]), "+f"(d[22]), "+f"(d[23]), "+f"(d[24]), "+f"(d[25]), "+f"(d[26]), "+f"(d[27]), "+f"(d[28]), "+f"(d[29]), "+f"(d[30]), "+f"(d[31]) : "r"(a0), "r"(a1), "r"(a2), "r"(a3), "l"(desc), "r"(sc));
}
template <> __device__ __forceinline__ void wgmma_rs<56, 0>(float* d, uint32_t a0, uint32_t a1, uint32_t a2, uint32_t a3, uint64_t desc, int sc) {
  asm volatile("{\n.reg .pred p;\nsetp.ne.b32 p, %33, 0;\n"
    "wgmma.mma_async.sync.aligned.m64n56k16.f32.bf16.bf16 {%0,%1,%2,%3,%4,%5,%6,%7,%8,%9,%10,%11,%12,%13,%14,%15,%16,%17,%18,%19,%20,%21,%22,%23,%24,%25,%26,%27}, {%28,%29,%30,%31}, %32, p, 1, 1, 0;\n}"
    : "+f"(d[0]), "+f"(d[1]), "+f"(d[2]), "+f"(d[3]), "+f"(d[4]), "+f"(d[5]), "+f"(d[6]), "+f"(d[7]), "+f"(d[8]), "+f"(d[9]), "+f"(d[10]), "+f"(d[11]), "+f"(d[12]), "+f"(d[13]), "+f"(d[14]), "+f"(d[15]), "+f"(d[16]), "+f"(d[17]), "+f"(d[18]), "+f"(d[19]), "+f"(d[20]), "+f"(d[21]), "+f"(d[22]), "+f"(d[23]), "+f"(d[24]), "+f"(d[25]), "+f"(d[26]), "+f"(d[27]) : "r"(a0), "r"(a1), "r"(a2), "r"(a3), "l"(desc), "r"(sc));
}
template <> __device__ __forceinline__ void wgmma_rs<48, 0>(float* d, uint32_t a0, uint32_t a1, uint32_t a2, uint32_t a3, uint64_t desc, int sc) {
  asm volatile("{\n.reg .pred p;\nsetp.ne.b32 p, %29, 0;\n"
    "wgmma.mma_async.sync.aligned.m64n48k16.f32.bf16.bf16 {%0,%1,%2,%3,%4,%5,%6,%7,%8,%9,%10,%11,%12,%13,%14,%15,%16,%17,%18,%19,%20,%21,%22,%23}, {%24,%25,%26,%27}, %28, p, 1, 1, 0;\n}"
    : "+f"(d[0]), "+f"(d[1]), "+f"(d[2]), "+f"(d[3]), "+f"(d[4]), "+f"(d[5]), "+f"(d[6]), "+f"(d[7]), "+f"(d[8]), "+f"(d[9]), "+f"(d[10]), "+f"(d[11]), "+f"(d[12]), "+f"(d[13]), "+f"(d[14]), "+f"(d[15]), "+f"(d[16]), "+f"(d[17]), "+f"(d[18]), "+f"(d[19]), "+f"(d[20]), "+f"(d[21]), "+f"(d[22]), "+f"(d[23]) : "r"(a0), "r"(a1), "r"(a2), "r"(a3), "l"(desc), "r"(sc));
}
template <> __device__ __forceinline__ void wgmma_rs<32, 0>(float* d, uint32_t a0, uint32_t a1, uint32_t a2, uint32_t a3, uint64_t desc, int sc) {
  asm volatile("{\n.reg .pred p;\nsetp.ne.b32 p, %21, 0;\n"
    "wgmma.mma_async.sync.aligned.m64n32k16.f32.bf16.bf16 {%0,%1,%2,%3,%4,%5,%6,%7,%8,%9,%10,%11,%12,%13,%14,%15}, {%16,%17,%18,%19}, %20, p, 1, 1, 0;\n}"
    : "+f"(d[0]), "+f"(d[1]), "+f"(d[2]), "+f"(d[3]), "+f"(d[4]), "+f"(d[5]), "+f"(d[6]), "+f"(d[7]), "+f"(d[8]), "+f"(d[9]), "+f"(d[10]), "+f"(d[11]), "+f"(d[12]), "+f"(d[13]), "+f"(d[14]), "+f"(d[15]) : "r"(a0), "r"(a1), "r"(a2), "r"(a3), "l"(desc), "r"(sc));
}
template <> __device__ __forceinline__ void wgmma_rs<48, 1>(float* d, uint32_t a0, uint32_t a1, uint32_t a2, uint32_t a3, uint64_t desc, int sc) {
  asm volatile("{\n.reg .pred p;\nsetp.ne.b32 p, %29, 0;\n"
    "wgmma.mma_async.sync.aligned.m64n48k16.f32.bf16.bf16 {%0,%1,%2,%3,%4,%5,%6,%7,%8,%9,%10,%11,%12,%13,%14,%15,%16,%17,%18,%19,%20,%21,%22,%23}, {%24,%25,%26,%27}, %28, p, 1, 1, 1;\n}"
    : "+f"(d[0]), "+f"(d[1]), "+f"(d[2]), "+f"(d[3]), "+f"(d[4]), "+f"(d[5]), "+f"(d[6]), "+f"(d[7]), "+f"(d[8]), "+f"(d[9]), "+f"(d[10]), "+f"(d[11]), "+f"(d[12]), "+f"(d[13]), "+f"(d[14]), "+f"(d[15]), "+f"(d[16]), "+f"(d[17]), "+f"(d[18]), "+f"(d[19]), "+f"(d[20]), "+f"(d[21]), "+f"(d[22]), "+f"(d[23]) : "r"(a0), "r"(a1), "r"(a2), "r"(a3), "l"(desc), "r"(sc));
}
template <> __device__ __forceinline__ void wgmma_rs<40, 1>(float* d, uint32_t a0, uint32_t a1, uint32_t a2, uint32_t a3, uint64_t desc, int sc) {
  asm volatile("{\n.reg .pred p;\nsetp.ne.b32 p, %25, 0;\n"
    "wgmma.mma_async.sync.aligned.m64n40k16.f32.bf16.bf16 {%0,%1,%2,%3,%4,%5,%6,%7,%8,%9,%10,%11,%12,%13,%14,%15,%16,%17,%18,%19}, {%20,%21,%22,%23}, %24, p, 1, 1, 1;\n}"
    : "+f"(d[0]), "+f"(d[1]), "+f"(d[2]), "+f"(d[3]), "+f"(d[4]), "+f"(d[5]), "+f"(d[6]), "+f"(d[7]), "+f"(d[8]), "+f"(d[9]), "+f"(d[10]), "+f"(d[11]), "+f"(d[12]), "+f"(d[13]), "+f"(d[14]), "+f"(d[15]), "+f"(d[16]), "+f"(d[17]), "+f"(d[18]), "+f"(d[19]) : "r"(a0), "r"(a1), "r"(a2), "r"(a3), "l"(desc), "r"(sc));
}
template <> __device__ __forceinline__ void wgmma_rs<32, 1>(float* d, uint32_t a0, uint32_t a1, uint32_t a2, uint32_t a3, uint64_t desc, int sc) {
  asm volatile("{\n.reg .pred p;\nsetp.ne.b32 p, %21, 0;\n"
    "wgmma.mma_async.sync.aligned.m64n32k16.f32.bf16.bf16 {%0,%1,%2,%3,%4,%5,%6,%7,%8,%9,%10,%11,%12,%13,%14,%15}, {%16,%17,%18,%19}, %20, p, 1, 1, 1;\n}"
    : "+f"(d[0]), "+f"(d[1]), "+f"(d[2]), "+f"(d[3]), "+f"(d[4]), "+f"(d[5]), "+f"(d[6]), "+f"(d[7]), "+f"(d[8]), "+f"(d[9]), "+f"(d[10]), "+f"(d[11]), "+f"(d[12]), "+f"(d[13]), "+f"(d[14]), "+f"(d[15]) : "r"(a0), "r"(a1), "r"(a2), "r"(a3), "l"(desc), "r"(sc));
}
template <> __device__ __forceinline__ void wgmma_rs<16, 1>(float* d, uint32_t a0, uint32_t a1, uint32_t a2, uint32_t a3, uint64_t desc, int sc) {
  asm volatile("{\n.reg .pred p;\nsetp.ne.b32 p, %13, 0;\n"
    "wgmma.mma_async.sync.aligned.m64n16k16.f32.bf16.bf16 {%0,%1,%2,%3,%4,%5,%6,%7}, {%8,%9,%10,%11}, %12, p, 1, 1, 1;\n}"
    : "+f"(d[0]), "+f"(d[1]), "+f"(d[2]), "+f"(d[3]), "+f"(d[4]), "+f"(d[5]), "+f"(d[6]), "+f"(d[7]) : "r"(a0), "r"(a1), "r"(a2), "r"(a3), "l"(desc), "r"(sc));
}

__device__ __forceinline__ uint32_t pack_bf16(float lo, float hi) {
  uint32_t r; asm("cvt.rn.bf16x2.f32 %0, %1, %2;" : "=r"(r) : "f"(hi), "f"(lo)); return r;
}
__device__ __forceinline__ float bf_lo(uint32_t v) { return __uint_as_float(v << 16); }
__device__ __forceinline__ float bf_hi(uint32_t v) { return __uint_as_float(v & 0xffff0000u); }
__device__ __forceinline__ float bf_round(float x) { return bf_lo(pack_bf16(x, 0.f)); }
__device__ __forceinline__ uint32_t hmul2(uint32_t a, uint32_t b) { uint32_t r; asm("mul.rn.bf16x2 %0, %1, %2;" : "=r"(r) : "r"(a), "r"(b)); return r; }
__device__ __forceinline__ uint32_t hadd2(uint32_t a, uint32_t b) { uint32_t r; asm("add.rn.bf16x2 %0, %1, %2;" : "=r"(r) : "r"(a), "r"(b)); return r; }
__device__ __forceinline__ uint32_t hsub2(uint32_t a, uint32_t b) { uint32_t r; asm("sub.rn.bf16x2 %0, %1, %2;" : "=r"(r) : "r"(a), "r"(b)); return r; }
__device__ __forceinline__ uint32_t hfma2(uint32_t a, uint32_t b, uint32_t c) { uint32_t r; asm("fma.rn.bf16x2 %0, %1, %2, %3;" : "=r"(r) : "r"(a), "r"(b), "r"(c)); return r; }

__device__ __forceinline__ void sts16(uint32_t a, uint32_t v) { asm volatile("st.shared.b16 [%0], %1;" ::"r"(a), "h"((unsigned short)v) : "memory"); }
__device__ __forceinline__ void sts32(uint32_t a, uint32_t v) { asm volatile("st.shared.b32 [%0], %1;" ::"r"(a), "r"(v) : "memory"); }
__device__ __forceinline__ void sts64(uint32_t a, uint32_t x, uint32_t y) { asm volatile("st.shared.v2.b32 [%0], {%1,%2};" ::"r"(a), "r"(x), "r"(y) : "memory"); }
__device__ __forceinline__ void sts128(uint32_t a, uint32_t x, uint32_t y, uint32_t z, uint32_t w) {
  asm volatile("st.shared.v4.b32 [%0], {%1,%2,%3,%4};" ::"r"(a), "r"(x), "r"(y), "r"(z), "r"(w) : "memory");
}
__device__ __forceinline__ uint32_t lds32(uint32_t a) { uint32_t v; asm volatile("ld.shared.b32 %0, [%1];" : "=r"(v) : "r"(a) : "memory"); return v; }
__device__ __forceinline__ uint2 lds64(uint32_t a) { uint2 v; asm volatile("ld.shared.v2.b32 {%0,%1}, [%2];" : "=r"(v.x), "=r"(v.y) : "r"(a) : "memory"); return v; }
__device__ __forceinline__ uint4 lds128(uint32_t a) {
  uint4 v; asm volatile("ld.shared.v4.b32 {%0,%1,%2,%3}, [%4];" : "=r"(v.x), "=r"(v.y), "=r"(v.z), "=r"(v.w) : "r"(a) : "memory"); return v;
}
__device__ __forceinline__ uint4 ldg128(const void* a) {
  uint4 v; asm volatile("ld.global.nc.v4.b32 {%0,%1,%2,%3}, [%4];" : "=r"(v.x), "=r"(v.y), "=r"(v.z), "=r"(v.w) : "l"(a) : "memory"); return v;
}
__device__ __forceinline__ uint2 ldg64(const void* a) {
  uint2 v; asm volatile("ld.global.nc.v2.b32 {%0,%1}, [%2];" : "=r"(v.x), "=r"(v.y) : "l"(a) : "memory"); return v;
}
__device__ __forceinline__ void ldsm4(uint32_t a, uint32_t& r0, uint32_t& r1, uint32_t& r2, uint32_t& r3) {
  asm volatile("ldmatrix.sync.aligned.m8n8.x4.shared.b16 {%0,%1,%2,%3}, [%4];" : "=r"(r0), "=r"(r1), "=r"(r2), "=r"(r3) : "r"(a) : "memory");
}
__device__ __forceinline__ void ldsm4t(uint32_t a, uint32_t& r0, uint32_t& r1, uint32_t& r2, uint32_t& r3) {
  asm volatile("ldmatrix.sync.aligned.m8n8.x4.trans.shared.b16 {%0,%1,%2,%3}, [%4];" : "=r"(r0), "=r"(r1), "=r"(r2), "=r"(r3) : "r"(a) : "memory");
}
__device__ __forceinline__ void stsm4(uint32_t a, uint32_t r0, uint32_t r1, uint32_t r2, uint32_t r3) {
  asm volatile("stmatrix.sync.aligned.m8n8.x4.shared.b16 [%0], {%1,%2,%3,%4};" ::"r"(a), "r"(r0), "r"(r1), "r"(r2), "r"(r3) : "memory");
}
__device__ __forceinline__ void stsm4t(uint32_t a, uint32_t r0, uint32_t r1, uint32_t r2, uint32_t r3) {
  asm volatile("stmatrix.sync.aligned.m8n8.x4.trans.shared.b16 [%0], {%1,%2,%3,%4};" ::"r"(a), "r"(r0), "r"(r1), "r"(r2), "r"(r3) : "memory");
}
__device__ __forceinline__ void stsm2(uint32_t a, uint32_t r0, uint32_t r1) {
  asm volatile("stmatrix.sync.aligned.m8n8.x2.shared.b16 [%0], {%1,%2};" ::"r"(a), "r"(r0), "r"(r1) : "memory");
}
__device__ __forceinline__ void stsm2t(uint32_t a, uint32_t r0, uint32_t r1) {
  asm volatile("stmatrix.sync.aligned.m8n8.x2.trans.shared.b16 [%0], {%1,%2};" ::"r"(a), "r"(r0), "r"(r1) : "memory");
}
__device__ __forceinline__ void mma16816(float* c, uint32_t a0, uint32_t a1, uint32_t a2, uint32_t a3, uint32_t b0, uint32_t b1) {
  asm("mma.sync.aligned.m16n8k16.row.col.f32.bf16.bf16.f32 {%0,%1,%2,%3}, {%4,%5,%6,%7}, {%8,%9}, {%0,%1,%2,%3};"
      : "+f"(c[0]), "+f"(c[1]), "+f"(c[2]), "+f"(c[3]) : "r"(a0), "r"(a1), "r"(a2), "r"(a3), "r"(b0), "r"(b1));
}
__device__ __forceinline__ void bar_sync(int id, int n) { asm volatile("bar.sync %0, %1;" ::"r"(id), "r"(n) : "memory"); }
__device__ __forceinline__ void bar_arrive(int id, int n) { asm volatile("bar.arrive %0, %1;" ::"r"(id), "r"(n) : "memory"); }
__device__ __forceinline__ void wg_fence() { asm volatile("wgmma.fence.sync.aligned;" ::: "memory"); }
__device__ __forceinline__ void wg_commit() { asm volatile("wgmma.commit_group.sync.aligned;" ::: "memory"); }
__device__ __forceinline__ void wg_wait0() { asm volatile("wgmma.wait_group.sync.aligned 0;" ::: "memory"); }
__device__ __forceinline__ void wg_wait1() { asm volatile("wgmma.wait_group.sync.aligned 1;" ::: "memory"); }
__device__ __forceinline__ void fence_async() { asm volatile("fence.proxy.async.shared::cta;" ::: "memory"); }
__device__ __forceinline__ uint32_t opq(uint32_t x, uint32_t z) { uint32_t r; asm volatile("xor.b32 %0, %1, %2;" : "=r"(r) : "r"(x), "r"(z)); return r; }
__device__ __forceinline__ float opqf(float x, uint32_t z) { float r; asm volatile("add.rn.f32 %0, %1, %2;" : "=f"(r) : "f"(x), "f"(__uint_as_float(z))); return r; }
__device__ __forceinline__ uint64_t mkdesc(uint32_t addr, uint32_t lbo, uint32_t sbo) {
  return (uint64_t)((addr & 0x3FFFF) >> 4) | ((uint64_t)(lbo >> 4) << 16) | ((uint64_t)(sbo >> 4) << 32);
}
__device__ __forceinline__ uint32_t mapa(uint32_t a, uint32_t rank) {
  uint32_t r; asm("mapa.shared::cluster.u32 %0, %1, %2;" : "=r"(r) : "r"(a), "r"(rank)); return r;
}
__device__ __forceinline__ void mbar_init_expect(uint32_t bar, uint32_t bytes) {
  asm volatile("mbarrier.init.shared::cta.b64 [%0], 1;" ::"r"(bar) : "memory");
  asm volatile("mbarrier.arrive.expect_tx.shared::cta.b64 _, [%0], %1;" ::"r"(bar), "r"(bytes) : "memory");
}
__device__ __forceinline__ void mbar_wait(uint32_t bar) {
#pragma unroll 1
  for (int it = 0; it < (1 << 22); it++) {
    uint32_t ok;
    asm volatile("{\n.reg .pred p;\nmbarrier.try_wait.parity.acquire.cluster.shared::cta.b64 p, [%1], 0;\nselp.u32 %0, 1, 0, p;\n}"
                 : "=r"(ok) : "r"(bar) : "memory");
    if (ok) return;
  }
  __trap();
}
__device__ __forceinline__ void st_async4(uint32_t a, uint32_t bar, uint32_t x, uint32_t y, uint32_t z, uint32_t w) {
  asm volatile("st.async.weak.shared::cluster.mbarrier::complete_tx::bytes.v4.b32 [%0], {%2,%3,%4,%5}, [%1];"
               ::"r"(a), "r"(bar), "r"(x), "r"(y), "r"(z), "r"(w) : "memory");
}

struct cf { float re, im; };
__device__ __forceinline__ cf cmul(cf a, cf b) { return {fmaf(a.re, b.re, -a.im * b.im), fmaf(a.re, b.im, a.im * b.re)}; }
__device__ __forceinline__ cf csq(cf a) { return {fmaf(a.re, a.re, -a.im * a.im), (a.re + a.re) * a.im}; }
__device__ __forceinline__ cf cexp_p(float xl, float y, float p) {
  float mag; asm("ex2.approx.ftz.f32 %0, %1;" : "=f"(mag) : "f"(xl * p));
  const float th = y * p;
  const float k = __fadd_rn(fmaf(th, 0.15915494309189535f, 12582912.f), -12582912.f);
  float r = fmaf(k, -6.2831854820251465f, th);
  r = fmaf(k, 1.7484555314695172e-07f, r);
  return {mag * __cosf(r), mag * __sinf(r)};
}
__device__ __forceinline__ uint32_t ysw(int c) { return (uint32_t)(c ^ ((c >> 3) & 3)) * 16u; }

#define CMUL2(OR, OI, xr, xi, yr, yi, nyi) do { OR = hfma2(xr, yr, hmul2(xi, nyi)); OI = hfma2(xr, yi, hmul2(xi, yr)); } while (0)

__device__ __forceinline__ uint32_t gate_slow(const __nv_bfloat16* u, const __nv_bfloat16* gw, int row) {
  float s = 0.f;
  const uint32_t* xr = (const uint32_t*)(u + (size_t)row * D);
  const uint32_t* wr = (const uint32_t*)gw;
#pragma unroll 1
  for (int j = 0; j < D / 2; j++) { const uint32_t pr = hmul2(xr[j], wr[j]); s += bf_lo(pr); s += bf_hi(pr); }
  s = bf_round(s);
  return pack_bf16(1.f / (1.f + expf(-s)), 0.f);
}

__device__ __forceinline__ uint2 gate_ld(int x) {
  uint2 gv;
  asm volatile("ld.relaxed.gpu.global.v2.u32 {%0,%1}, [%2];" : "=r"(gv.x), "=r"(gv.y) : "l"(g_gate + x * 2) : "memory");
  return gv;
}
__device__ __noinline__ uint32_t gate_poll(const Params* pp, int x, uint32_t tag) {
  uint2 gv;
#pragma unroll 1
  for (int spins = 0; spins < (1 << 16); spins++) {
    gv = gate_ld(x);
    if ((gv.x >> 16) == tag && (gv.y >> 16) == tag) return __byte_perm(gv.x, gv.y, 0x5410);
  }
  return __byte_perm(gate_slow(pp->u, pp->gw, x * 2), gate_slow(pp->u, pp->gw, x * 2 + 1), 0x5410);
}
__device__ __forceinline__ uint32_t gate_fin(const Params& p, uint2 gv, int x, uint32_t tag) {
  if ((gv.x >> 16) == tag && (gv.y >> 16) == tag) return __byte_perm(gv.x, gv.y, 0x5410);
  return gate_poll(&p, x, tag);
}

__device__ __forceinline__ void ld4ch(uint32_t* v, uint32_t addr) {
#pragma unroll
  for (int k = 0; k < 4; k++) v[k] = lds32(addr + k * CH_BYTES);
}
__device__ __forceinline__ void skip_terms(uint32_t* ua, uint32_t* ub, uint32_t sb, int x, uint2 dA, uint2 dB) {
  const int c = x >> 2;
  uint32_t uu[4];
  ld4ch(uu, sb + CH_OFF + (x & 3) * 4 + U_OFF + (c & 3) * U_CS + (63 - (c >> 2)) * 16);
#pragma unroll
  for (int k = 0; k < 4; k++) {
    ua[k] = hmul2(uu[k], __byte_perm((k & 2) ? dA.y : dA.x, 0, (k & 1) ? 0x3232 : 0x1010));
    ub[k] = hmul2(uu[k], __byte_perm((k & 2) ? dB.y : dB.x, 0, (k & 1) ? 0x3232 : 0x1010));
  }
}
__device__ __forceinline__ uint4 mix(const uint32_t* a, const uint32_t* b, const uint32_t* ua, const uint32_t* ub, uint32_t g2) {
  const uint32_t h2 = hsub2(0x3f803f80u, g2);
  uint32_t o[4];
#pragma unroll
  for (int k = 0; k < 4; k++) o[k] = hadd2(hmul2(g2, hadd2(a[k], ua[k])), hmul2(h2, hadd2(b[k], ub[k])));
  return make_uint4(__byte_perm(o[0], o[1], 0x5410), __byte_perm(o[2], o[3], 0x5410), __byte_perm(o[0], o[1], 0x7632), __byte_perm(o[2], o[3], 0x7632));
}
__device__ __forceinline__ void send_box(uint32_t sb, int slot, int wtid, uint32_t rank, uint4 r) {
  st_async4(mapa(sb + XIN_OFF + slot * 2048 + wtid * 16, rank ^ 1), mapa(sb + B_X + slot * 8, rank ^ 1), r.x, r.y, r.z, r.w);
}
__device__ __forceinline__ void merge_rows(uint32_t st, uint32_t rank, uint4 r, uint4 q) {
  const uint4 lo = rank ? q : r, hi = rank ? r : q;
  sts128(st, lo.x, lo.y, hi.x, hi.y); sts128(st + 2048, lo.z, lo.w, hi.z, hi.w);
}
__device__ __forceinline__ void merge_box(uint32_t sb, const CUtensorMap* tm_out, int slot, int wtid, uint32_t rank, int oc0, uint4 r, int barid) {
  const uint32_t st = sb + RAW_OFF + slot * 4096 + wtid * 16;
  mbar_wait(sb + B_X + slot * 8);
  merge_rows(st, rank, r, lds128(sb + XIN_OFF + slot * 2048 + wtid * 16));
  fence_async();
  bar_sync(barid, 128);
  if (wtid == 0) {
    asm volatile("cp.async.bulk.tensor.3d.global.shared::cta.bulk_group [%0, {%2, %3, %4}], [%1];"
                 ::"l"(tm_out), "r"(sb + RAW_OFF + slot * 4096), "r"(oc0), "r"((2 * slot + (int)rank) * 128), "r"(0) : "memory");
    asm volatile("cp.async.bulk.commit_group;" ::: "memory");
  }
}

__device__ __forceinline__ uint32_t band2(int e, int lo, int hi) {
  uint32_t r = ((uint32_t)(e - lo) <= (uint32_t)(hi - lo) ? 0x3f80u : 0u) | ((uint32_t)(e - 1 - lo) <= (uint32_t)(hi - lo) ? 0x3f800000u : 0u);
  asm volatile("" : "+r"(r));
  return r;
}

__device__ __forceinline__ void stage_done(uint32_t sb, int stage, int lane) {
  __syncwarp();
  if (lane == 0) asm volatile("mbarrier.arrive.shared::cta.b64 _, [%0];" ::"r"(sb + B_ST + 8 * stage) : "memory");
}
#define PK2(v, i) pack_bf16(v[i], v[(i) + 1])

__device__ __forceinline__ void conv_dense(uint32_t sb, uint32_t cb, uint32_t zz) {
  const int lane = threadIdx.x & 31, wq = (threadIdx.x >> 5) & 3, br = wq >> 1, hf = wq & 1, g = lane >> 2, t = lane & 3;
  const uint32_t rb = cb + R_OFF + br * R_BR;
  const int eo = 16 * hf + g - 2 * t;
  const int x0 = RD_X0 - (eo + 536);
  const uint32_t fa = rb + ((g & 1) ? 2 * x0 : RD_CS + 2 * x0 + 2);
  const uint64_t ub = mkdesc(cb + U_OFF, U_CS, 128);
  const uint32_t yd = cb + Y0_OFF + br * 4096 + ysw(4 * (63 - 8 * (lane >> 4) - (lane & 7)) + 2 * hf + ((lane >> 3) & 1));
  uint32_t A[2][4][4];
  float e64[32], e56[28], e48[24];
  auto loadA = [&](int j) {
#pragma unroll
    for (int k = 0; k < 4; k++) {
      const int s = 34 - 4 * j - k;
      if (s >= 0) {
        if (k == 0 && j == 0) A[0][0][2] = lds32(fa + (2 * s + 2) * 16);
        A[j & 1][k][0] = lds32(fa + (2 * s + 1) * 16);
        A[j & 1][k][1] = lds32(fa + (2 * s) * 16);
      }
    }
#pragma unroll
    for (int k = 0; k < 4; k++) {
      if (34 - 4 * j - k >= 0) {
        A[j & 1][k][3] = A[j & 1][k][0];
        if (k) A[j & 1][k][2] = A[j & 1][k - 1][1];
        else if (j) A[j & 1][0][2] = A[(j - 1) & 1][3][1];
      }
    }
  };
  loadA(0); loadA(1);
#pragma unroll
  for (int j = 0; j < 9; j++) {
    if (j == 4) {
      wg_wait0();
      stsm2t(yd - 7 * 512, PK2(e64, 28), PK2(e64, 30));
#pragma unroll
      for (int i = 0; i < 28; i++) e56[i] = FCPY(e64, i);
      stage_done(sb, 0, lane);
    }
    if (j == 8) {
      wg_wait0();
      stsm2t(yd - 6 * 512, PK2(e56, 24), PK2(e56, 26));
#pragma unroll
      for (int i = 0; i < 24; i++) e48[i] = FCPY(e56, i);
      stage_done(sb, 1, lane);
    }
    wg_fence();
#pragma unroll
    for (int k = 0; k < 4; k++) {
      const int s = 34 - 4 * j - k;
      if (s >= 0) {
        const int o = 2 * s - 66 + 128;
        const int cc = o & 3, rs = (o >> 2) - 32;
        const uint64_t desc = ub + (uint64_t)((cc * U_CS - rs * 16) >> 4);
        const uint32_t* a = A[j & 1][k];
        if (j < 4) wgmma_rs<64, 0>(e64, a[0], a[1], a[2], a[3], desc, s != 34);
        else if (j < 8) wgmma_rs<56, 0>(e56, a[0], a[1], a[2], a[3], desc, 1);
        else wgmma_rs<48, 0>(e48, a[0], a[1], a[2], a[3], desc, 1);
      }
    }
    wg_commit();
    if (j >= 1 && j < 8) { wg_wait1(); loadA(j + 1); }
  }
  wg_wait0();
#pragma unroll
  for (int i = 0; i < 6; i += 2) stsm4t(yd - i * 512, PK2(e48, 4 * i), PK2(e48, 4 * i + 2), PK2(e48, 4 * i + 4), PK2(e48, 4 * i + 6));
}

__device__ __noinline__ unsigned int gate_rows(const Params* pp, int grow, int step, int rend) {
  const __nv_bfloat16 *u = pp->u, *gw = pp->gw;
  const int lane = threadIdx.x & 31;
  uint4 gx[4][2], nx[4][2];
#pragma unroll
  for (int i = 0; i < 4; i++) {
    nx[i][0] = ldg128(u + (size_t)(grow + i) * D + lane * 8);
    nx[i][1] = ldg128(u + (size_t)(grow + i) * D + 256 + lane * 8);
  }
  const uint4 gw0 = ldg128(gw + lane * 8), gw1 = ldg128(gw + 256 + lane * 8);
  const uint32_t ws[8] = {gw0.x, gw0.y, gw0.z, gw0.w, gw1.x, gw1.y, gw1.z, gw1.w};
  unsigned int epoch;
  asm volatile("ld.relaxed.gpu.global.u32 %0, [%1];" : "=r"(epoch) : "l"(&g_epoch) : "memory");
#pragma unroll 1
  for (; grow < rend; grow += step) {
#pragma unroll
    for (int i = 0; i < 4; i++) { gx[i][0] = nx[i][0]; gx[i][1] = nx[i][1]; }
    if (grow + step < rend) {
#pragma unroll
      for (int i = 0; i < 4; i++) {
        nx[i][0] = ldg128(u + (size_t)(grow + step + i) * D + lane * 8);
        nx[i][1] = ldg128(u + (size_t)(grow + step + i) * D + 256 + lane * 8);
      }
    }
    float c[2][4];
#pragma unroll
    for (int i = 0; i < 2; i++) {
      const uint4 *x = gx[2 * i], *y = gx[2 * i + 1];
      const uint32_t xs[8] = {x[0].x, x[0].y, x[0].z, x[0].w, x[1].x, x[1].y, x[1].z, x[1].w};
      const uint32_t ys[8] = {y[0].x, y[0].y, y[0].z, y[0].w, y[1].x, y[1].y, y[1].z, y[1].w};
      c[i][0] = c[i][1] = c[i][2] = c[i][3] = 0.f;
#pragma unroll
      for (int j = 0; j < 8; j += 2)
        mma16816(c[i], hmul2(xs[j], ws[j]), hmul2(ys[j], ws[j]), hmul2(xs[j + 1], ws[j + 1]), hmul2(ys[j + 1], ws[j + 1]), 0x3f803f80u, 0x3f803f80u);
    }
    float s = (lane & 2) ? ((lane & 1) ? c[1][2] : c[1][0]) : ((lane & 1) ? c[0][2] : c[0][0]);
#pragma unroll
    for (int o = 4; o < 32; o <<= 1) s += __shfl_xor_sync(0xffffffffu, s, o);
    s = bf_round(s);
    const float gv = 1.f / (1.f + expf(-s));
    const uint32_t w = ((epoch + 1) << 16) | (pack_bf16(gv, 0.f) & 0xffffu);
    if (lane < 4) asm volatile("st.relaxed.gpu.global.u32 [%0], %1;" ::"l"(&g_gate[grow + lane]), "r"(w) : "memory");
  }
  return epoch;
}
#define GW 1
constexpr int GSPLIT = L - 4 * GW * NCTA;
__device__ __noinline__ void gate_cta(const Params* pp) {
  const unsigned int epoch = gate_rows(pp, (blockIdx.x * 20 + (threadIdx.x >> 5)) * 4, 80 * NGATE, GSPLIT);
  __syncthreads();
  if (threadIdx.x == 0 && atomicAdd(&g_ticket, 1u) == NCTA + NGATE - 1) { g_ticket = 0; g_epoch = epoch + 1; }
}

__global__ void __cluster_dims__(2, 1, 1) __launch_bounds__(640, 1)
ssm_kernel(const __grid_constant__ Params p, const __grid_constant__ CUtensorMap tm_in, const __grid_constant__ CUtensorMap tm_out) {
  extern __shared__ __align__(1024) unsigned char smem_raw[];
  const uint32_t sb = (uint32_t)__cvta_generic_to_shared(smem_raw);
  const int tid = threadIdx.x, lane = tid & 31;
  const int warp = __shfl_sync(0xffffffffu, tid >> 5, 0);
  const int ch = warp >> 2, wq = warp & 3, br = wq >> 1, hf = wq & 1;
  const int g = lane >> 2, t = lane & 3;
  if (__builtin_expect(blockIdx.x < NGATE, 0)) { gate_cta(&p); return; }
  const int bid = blockIdx.x - NGATE;
  const int d = bid * 4 + ch;
  const uint32_t rank = blockIdx.x & 1;
  const uint32_t cb = sb + CH_OFF + ch * CH_BYTES;
  const int wtid = tid & 127;
  const int oc0 = (bid >> 1) * 8;
  STAMP(0); GT(0);

  if (warp >= 16) {
    if (wtid == 0) {
      mbar_init_expect(sb + B_RAW, 32768);
#pragma unroll
      for (int i = 0; i < 4; i++) mbar_init_expect(sb + B_X + 8 * i, 2048);
      asm volatile("mbarrier.init.shared::cta.b64 [%0], 128;" ::"r"(sb + B_U) : "memory");
      asm volatile("mbarrier.init.shared::cta.b64 [%0], 128;" ::"r"(sb + B_W) : "memory");
#pragma unroll
      for (int i = 0; i < 7; i++) asm volatile("mbarrier.init.shared::cta.b64 [%0], 16;" ::"r"(sb + B_ST + 8 * i) : "memory");
      asm volatile("fence.mbarrier_init.release.cluster;" ::: "memory");
      asm volatile("fence.proxy.async.shared::cta;" ::: "memory");
    }
    __syncwarp();
    asm volatile("barrier.cluster.arrive.relaxed.aligned;" ::: "memory");
    if (wq >= 4 - GW) gate_rows(&p, GSPLIT + (bid * GW + 3 - wq) * 4, L, L);
    unsigned int epoch;
    asm volatile("ld.relaxed.gpu.global.u32 %0, [%1];" : "=r"(epoch) : "l"(&g_epoch) : "memory");
    asm volatile("barrier.cluster.wait.aligned;" ::: "memory");
    if (wtid == 0) {
      asm volatile("cp.async.bulk.tensor.5d.shared::cluster.global.mbarrier::complete_tx::bytes.multicast::cluster [%0], [%1, {%3, %4, %4, %4, %5}], [%2], %6;"
                   ::"r"(sb + RAW_OFF + rank * 16384), "l"(&tm_in), "r"(sb + B_RAW), "r"(oc0), "r"(0), "r"((int)rank * 32), "h"((unsigned short)3) : "memory");
    }
    sts128(sb + CH_OFF + wq * CH_BYTES + U_OFF + (lane >> 3) * U_CS + (64 + (lane & 7)) * 16, 0, 0, 0, 0);
    const uint2 dA = ldg64(p.A_D + bid * 4), dB = ldg64(p.B_D + bid * 4);
    uint32_t BA[3][4], BB[4][4];
    {
      const int l1 = br ? 3 : 6, h1 = br ? 5 : 10, l2 = br ? 5 : 12, h2 = br ? 11 : 20;
#pragma unroll
      for (int i = 0; i < 4; i++) {
        const int e = 16 * hf + g - 2 * t + 32 - 16 * i;
        BB[i][0] = band2(e, l2, h2); BB[i][1] = band2(e + 8, l2, h2); BB[i][2] = band2(e - 8, l2, h2); BB[i][3] = BB[i][0];
        if (i) { BA[i - 1][0] = band2(e, l1, h1); BA[i - 1][1] = band2(e + 8, l1, h1); BA[i - 1][2] = band2(e - 8, l1, h1); BA[i - 1][3] = BA[i - 1][0]; }
      }
    }
    const uint32_t tag = (epoch + 1) & 0xffffu;
    if (wtid == 0) sts32(sb + TAG_OFF, tag);
    STAMP(3);
    mbar_wait(sb + B_RAW);
    STAMP(4);
    {
      const uint32_t dst = sb + CH_OFF + (g & 3) * CH_BYTES + U_OFF + t * U_CS + (63 - wq * 16) * 16;
#pragma unroll
      for (int h = 0; h < 2; h++) {
        uint32_t r[8][4];
#pragma unroll
        for (int i = 0; i < 8; i++) ldsm4t(sb + RAW_OFF + (wq * 16 + h * 8 + i) * 512 + lane * 16, r[i][0], r[i][1], r[i][2], r[i][3]);
        if ((uint32_t)(g >> 2) == rank) {
#pragma unroll
          for (int i = 0; i < 8; i++) sts128(dst - (h * 8 + i) * 16, r[i][0], r[i][1], r[i][2], r[i][3]);
        }
      }
    }
    fence_async();
    asm volatile("mbarrier.arrive.shared::cta.b64 _, [%0];" ::"r"(sb + B_U) : "memory");
    bar_sync(5, 128);
    STAMP(5);
    {
      const int mrow = lane & 7, mi = lane >> 3;
      const uint64_t ub0 = mkdesc(sb + CH_OFF + U_OFF, U_CS, 128);
      uint32_t wa, wb;
      {
        const int c = 4 * (47 - 8 * (mi >> 1) - mrow) + 2 * hf + (mi & 1);
        wa = sb + CH_OFF + (br ? W3_OFF : W5_OFF) + (5 - (c >> 5)) * 576 + ((c & 31) >> 3) * 144 + (c & 7) * 16;
        const int c2 = c - 64, pp = c2 >> 1;
        wb = sb + CH_OFF + (br ? W7_OFF : W9_OFF) + (1 - (pp >> 5)) * 1152 + (c2 & 1) * 576 + ((pp & 31) >> 3) * 144 + (pp & 7) * 16;
      }
      {
        float w1[24];
#pragma unroll
        for (int i = 0; i < 24; i++) w1[i] = 0.f;
#pragma unroll 1
        for (int k = 0; k < 4; k++) {
          wg_fence();
#pragma unroll
          for (int i = 0; i < 3; i++)
            wgmma_rs<48, 0>(w1, BA[i][0], BA[i][1], BA[i][2], BA[i][3],
                            ub0 + (uint64_t)((k * CH_BYTES + ((2 * i + 2) & 3) * U_CS + (16 + (i == 0)) * 16) >> 4), i);
          wg_commit();
          wg_wait0();
#pragma unroll
          for (int i = 0; i < 3; i++) stsm4t(wa + k * CH_BYTES + i * 1152, PK2(w1, 8 * i), PK2(w1, 8 * i + 2), PK2(w1, 8 * i + 4), PK2(w1, 8 * i + 6));
        }
      }
      {
        float w2[2][16];
#pragma unroll
        for (int i = 0; i < 16; i++) { w2[0][i] = 0.f; w2[1][i] = 0.f; }
#pragma unroll 1
        for (int kp = 0; kp < 2; kp++) {
          wg_fence();
#pragma unroll
          for (int k = 0; k < 2; k++)
#pragma unroll
            for (int i = 0; i < 4; i++)
              wgmma_rs<32, 0>(w2[k], BB[i][0], BB[i][1], BB[i][2], BB[i][3],
                              ub0 + (uint64_t)(((2 * kp + k) * CH_BYTES + ((2 * i) & 3) * U_CS + (32 + (i < 2)) * 16) >> 4), i);
          wg_commit();
          wg_wait0();
#pragma unroll
          for (int k = 0; k < 2; k++)
#pragma unroll
            for (int i = 0; i < 2; i++)
              stsm4t(wb + (2 * kp + k) * CH_BYTES + i * 1152, PK2(w2[k], 8 * i), PK2(w2[k], 8 * i + 2), PK2(w2[k], 8 * i + 4), PK2(w2[k], 8 * i + 6));
        }
      }
    }
    fence_async();
    asm volatile("mbarrier.arrive.shared::cta.b64 _, [%0];" ::"r"(sb + B_W) : "memory");
    STAMP(7);
    {
      const int bsel = (int)rank ^ br ^ 1, xl = wtid & 63;
      uint2 gl[4];
      uint32_t ua[4][4], ub[4][4];
#pragma unroll
      for (int i = 0; i < 4; i++) skip_terms(ua[i], ub[i], sb, (2 * (i >> 1) + bsel) * 128 + (i & 1) * 64 + xl, dA, dB);
      const uint32_t yo = sb + CH_OFF + (xl & 3) * 4 + ysw(xl >> 2) + bsel * 512;
#pragma unroll
      for (int i = 0; i < 2; i++) gl[i] = gate_ld(bsel * 128 + i * 64 + xl);
#pragma unroll
      for (int slot = 0; slot < 2; slot++) {
        const int box = 2 * slot + bsel;
        uint32_t g2[2], ya[2][4], yb[2][4];
#pragma unroll
        for (int h = 0; h < 2; h++) g2[h] = gate_fin(p, gl[2 * slot + h], box * 128 + h * 64 + xl, tag);
        mbar_wait(sb + B_ST + 8 * box);
        STAMP(8 + slot);
        if (slot == 0) { gl[2] = gate_ld((2 + bsel) * 128 + xl); gl[3] = gate_ld((2 + bsel) * 128 + 64 + xl); }
#pragma unroll
        for (int h = 0; h < 2; h++) {
          const uint32_t yh = (yo ^ (h * 32)) + h * 256 + slot * 1024;
          ld4ch(ya[h], yh + Y0_OFF); ld4ch(yb[h], yh + Y0_OFF + 4096);
          if (slot) {
            uint32_t a2[4], b2[4];
            ld4ch(a2, yh + Y2_OFF - 1024); ld4ch(b2, yh + Y2_OFF - 1024 + 3072);
#pragma unroll
            for (int k = 0; k < 4; k++) { ya[h][k] = hadd2(ya[h][k], a2[k]); yb[h][k] = hadd2(yb[h][k], b2[k]); }
          }
        }
        const uint4 r0 = mix(ya[0], yb[0], ua[2 * slot], ub[2 * slot], g2[0]), r1 = mix(ya[1], yb[1], ua[2 * slot + 1], ub[2 * slot + 1], g2[1]);
        if (br == 0) { send_box(sb, slot, xl, rank, r0); send_box(sb, slot, xl + 64, rank, r1); }
        else {
          const uint32_t st = sb + RAW_OFF + slot * 4096 + xl * 16, xin = sb + XIN_OFF + slot * 2048 + xl * 16;
          mbar_wait(sb + B_X + slot * 8);
          const uint4 q0 = lds128(xin), q1 = lds128(xin + 1024);
          merge_rows(st, rank, r0, q0); merge_rows(st + 1024, rank, r1, q1);
          fence_async();
          bar_sync(6, 64);
          if (xl == 0) {
            asm volatile("cp.async.bulk.tensor.3d.global.shared::cta.bulk_group [%0, {%2, %3, %4}], [%1];"
                         ::"l"(&tm_out), "r"(sb + RAW_OFF + slot * 4096), "r"(oc0), "r"(box * 128), "r"(0) : "memory");
            asm volatile("cp.async.bulk.commit_group;" ::: "memory");
          }
        }
        STAMP(10 + slot);
      }
    }
    if (wtid == 0 && atomicAdd(&g_ticket, 1u) == NCTA + NGATE - 1) { g_ticket = 0; g_epoch = epoch + 1; }
    if (wtid == 64) asm volatile("cp.async.bulk.wait_group.read 0;" ::: "memory");
    STAMP(15);
    return;
  }
  asm volatile("barrier.cluster.arrive.relaxed.aligned;" ::: "memory");

  const int moff = (bid * 4 + (tid >> 7)) * NM + (tid & 63) * 2;
  const int brt = (tid >> 6) & 1;
  const __nv_bfloat16* const* tp = p.t + (brt ? 0 : 6);
  const uint32_t q0 = *(const uint32_t*)(tp[0] + moff), q1 = *(const uint32_t*)(tp[1] + moff);
  const uint32_t q2 = *(const uint32_t*)(tp[2] + moff), q3 = *(const uint32_t*)(tp[3] + moff);
  const uint2 ldt4 = *(const uint2*)(tp[4] + bid * 4);
  const uint32_t q4 = *(const uint32_t*)(tp[brt ? 2 : 5] + moff), q5 = *(const uint32_t*)(tp[brt ? 3 : 6] + moff);

  for (int i = wtid & 63; i < R_BR / 16; i += 64) sts128(cb + R_OFF + br * R_BR + i * 16, 0, 0, 0, 0);
  STAMP(1);

  float acc0[8], acc1[8];
  {
    const uint32_t scr = cb + Y0_OFF, scr2 = sb + SC2_OFF + ch * 2560;
    const uint32_t ldt2 = (ch & 2) ? ldt4.y : ldt4.x;
    const float dt = bf_round(expf((ch & 1) ? bf_hi(ldt2) : bf_lo(ldt2)));
    STAMP(2);
    const uint32_t tb = scr + br * 9216 + (wtid & 63) * 16, tb2 = scr2 + br * 1280;
    const uint32_t ta = scr + br * 9216 + 4096 + (lane >> 3) * 1024 + (lane & 7) * 16;
    const uint32_t tc = ((lane & 8) ? scr2 + (br ^ 1) * 1280 : scr + (br ^ 1) * 9216 + 8192) + (lane >> 4) * 128 + (lane & 7) * 16;
    const uint32_t tm = tb2 + 1024 + ((lane >> 3) & 1) * 128 + (lane >> 4) * 16;
    const uint64_t db0 = mkdesc(scr, 1024, 2048), db1 = mkdesc(scr + 9216, 1024, 2048);
    float k2048 = 0.f;
    uint32_t QA[2][2][4], QB[2][2][4];
#pragma unroll
    for (int i = 0; i < 8; i++) { acc0[i] = 0.f; acc1[i] = 0.f; }
    auto loadQ = [&](int gi) {
      uint32_t (*qa)[4] = QA[gi & 1];
      uint32_t (*qb)[4] = QB[gi & 1];
      if (wq == 0) {
        ldsm4t(ta + gi * 256, qa[0][0], qa[0][1], qa[0][2], qa[0][3]); ldsm4t(ta + gi * 256 + 128, qa[1][0], qa[1][1], qa[1][2], qa[1][3]);
        ldsm4t(tc + gi * 256, qb[0][0], qb[0][2], qb[1][0], qb[1][2]);
        qb[0][1] = qb[0][3] = qb[1][1] = qb[1][3] = 0;
      } else if (wq == 3) {
        ldsm4t(ta + gi * 256, qb[0][0], qb[0][1], qb[0][2], qb[0][3]); ldsm4t(ta + gi * 256 + 128, qb[1][0], qb[1][1], qb[1][2], qb[1][3]);
        ldsm4t(tc + gi * 256, qa[0][0], qa[0][2], qa[1][0], qa[1][2]);
        qa[0][1] = qa[0][3] = qa[1][1] = qa[1][3] = 0;
      } else {
        uint32_t x[2][4], yr[2], yi[2], o[2][4];
        ldsm4t(ta + gi * 256, x[0][0], x[0][1], x[0][2], x[0][3]); ldsm4t(ta + gi * 256 + 128, x[1][0], x[1][1], x[1][2], x[1][3]);
        ldsm4(tm + gi * 32, yr[0], yi[0], yr[1], yi[1]);
#pragma unroll
        for (int k = 0; k < 2; k++) {
          const uint32_t nyi = yi[k] ^ 0x80008000u;
          CMUL2(o[k][0], o[k][2], x[k][0], x[k][2], yr[k], yi[k], nyi);
          CMUL2(o[k][1], o[k][3], x[k][1], x[k][3], yr[k], yi[k], nyi);
        }
#pragma unroll
        for (int k = 0; k < 2; k++)
#pragma unroll
          for (int i = 0; i < 4; i++) { qa[k][i] = o[k][i]; qb[k][i] = o[k][i]; }
      }
    };
#pragma unroll 1
    for (int r = 0; r < 2; r++) {
      cf c, z1, z128;
      {
        const uint32_t sh = r ? 0x3244u : 0x1044u;
        float v0 = __uint_as_float(__byte_perm(q0, 0, sh));
        const float v1 = __uint_as_float(__byte_perm(q1, 0, sh)), v2 = __uint_as_float(__byte_perm(q2, 0, sh)), v3 = __uint_as_float(__byte_perm(q3, 0, sh));
        if (br == 0) { c = cmul(cf{v2, v3}, cf{dt * __uint_as_float(__byte_perm(q4, 0, sh)), dt * __uint_as_float(__byte_perm(q5, 0, sh))}); }
        else { v0 = -bf_round(expf(v0)); c = cf{2.f * dt * v2, 2.f * dt * v3}; }
        const float xl = (dt * v0) * 1.4426950408889634f, y = dt * v1;
        z1 = cexp_p(xl, y, 1.f); z128 = cexp_p(xl, y, 128.f);
      }
      const cf z2 = csq(z1), z4 = csq(z2), z8 = csq(z4);
      const cf w8 = {z8.re, -z8.im};
      const cf z16 = csq(w8), z24 = cmul(z16, w8), z32 = csq(z16), z40 = cmul(z32, w8), z48 = csq(z24), z56 = cmul(z32, z24), z64 = csq(z32);
      const cf z256 = csq(z128), z512 = csq(z256), z1024 = csq(z512), z2048 = csq(z1024), z1152 = cmul(z1024, z128);
      k2048 += fmaf(c.re, z2048.re, -c.im * z2048.im);
      const cf e1 = cmul(c, z1), e2 = cmul(c, z2), e3 = cmul(e1, z2), e4 = cmul(c, z4), e5 = cmul(e1, z4), e6 = cmul(e2, z4), e7 = cmul(e3, z4);
      const cf h2 = cmul(c, z256), e258 = cmul(e2, z256), e260 = cmul(e4, z256), e262 = cmul(e6, z256);
      const cf h4 = cmul(c, z512), e516 = cmul(e4, z512), h6 = cmul(h2, z512), e772 = cmul(e260, z512);
      if (r) bar_sync(1 + ch, 128);
      {
        const uint32_t xr[4] = {pack_bf16(1.f, z8.re), pack_bf16(z16.re, z24.re), pack_bf16(z32.re, z40.re), pack_bf16(z48.re, z56.re)};
        const uint32_t xi[4] = {pack_bf16(0.f, w8.im), pack_bf16(z16.im, z24.im), pack_bf16(z32.im, z40.im), pack_bf16(z48.im, z56.im)};
        sts128(tb, xr[0], xr[1], xr[2], xr[3]);
        sts128(tb + 1024, xi[0], xi[1], xi[2], xi[3]);
        const uint32_t yr = pack_bf16(z64.re, z64.re), yi = pack_bf16(z64.im, z64.im), nyi = yi ^ 0x80008000u;
        uint32_t o[4], q[4];
#pragma unroll
        for (int i = 0; i < 4; i++) CMUL2(o[i], q[i], xr[i], xi[i], yr, yi, nyi);
        sts128(tb + 2048, o[0], o[1], o[2], o[3]);
        sts128(tb + 3072, q[0], q[1], q[2], q[3]);
      }
      {
        sts128(tb + 4096, pack_bf16(e7.re, e6.re), pack_bf16(e5.re, e4.re), pack_bf16(e3.re, e2.re), pack_bf16(e1.re, c.re));
        sts128(tb + 6144, pack_bf16(e7.im, e6.im), pack_bf16(e5.im, e4.im), pack_bf16(e3.im, e2.im), pack_bf16(e1.im, c.im));
        sts128(tb + 5120, pack_bf16(h2.re, e258.re), pack_bf16(e260.re, e262.re), pack_bf16(h4.re, e516.re), pack_bf16(h6.re, e772.re));
        sts128(tb + 7168, pack_bf16(h2.im, e258.im), pack_bf16(e260.im, e262.im), pack_bf16(h4.im, e516.im), pack_bf16(h6.im, e772.im));
        const uint32_t xr[2] = {pack_bf16(c.re, h2.re), pack_bf16(h4.re, h6.re)}, xi[2] = {pack_bf16(c.im, h2.im), pack_bf16(h4.im, h6.im)};
        uint32_t o[4], q[4];
        {
          const uint32_t yr = pack_bf16(z1024.re, z1024.re), yi = pack_bf16(z1024.im, z1024.im), nyi = yi ^ 0x80008000u;
          CMUL2(o[0], q[0], xr[0], xi[0], yr, yi, nyi); CMUL2(o[1], q[1], xr[1], xi[1], yr, yi, nyi);
        }
        {
          const uint32_t yr = pack_bf16(z1152.re, z1152.re), yi = pack_bf16(z1152.im, z1152.im), nyi = yi ^ 0x80008000u;
          CMUL2(o[2], q[2], xr[0], xi[0], yr, yi, nyi); CMUL2(o[3], q[3], xr[1], xi[1], yr, yi, nyi);
        }
        sts128(tb + 8192, o[0], o[1], o[2], o[3]);
        sts128(tb2 + (wtid & 63) * 16, q[0], q[1], q[2], q[3]);
        const uint32_t m = pack_bf16(z128.re, z128.im);
        sts16(tb2 + 1024 + (wtid & 63) * 2, m); sts16(tb2 + 1152 + (wtid & 63) * 2, m >> 16);
      }
      if (r) {
#pragma unroll
        for (int o = 16; o; o >>= 1) k2048 += __shfl_xor_sync(0xffffffffu, k2048, o);
        if (lane == 0) sts32(sb + K2048_OFF + warp * 4, __float_as_uint(k2048));
      }
      fence_async();
      bar_sync(1 + ch, 128);
      loadQ(0); loadQ(1);
#pragma unroll
      for (int gi = 0; gi < 4; gi++) {
        wg_fence();
#pragma unroll
        for (int k = 0; k < 2; k++) {
          const uint32_t* a = QA[gi & 1][k];
          const uint32_t* b = QB[gi & 1][k];
          wgmma_rs<16, 1>(acc0, a[0], a[1], a[2], a[3], db0 + (2 * gi + k) * 8, 1);
          wgmma_rs<16, 1>(acc1, b[0], b[1], b[2], b[3], db1 + (2 * gi + k) * 8, 1);
        }
        wg_commit();
        if (gi == 1 || gi == 2) { wg_wait1(); loadQ(gi + 1); }
      }
      wg_wait0();
    }
  }
  STAMP(3);

  {
    const uint32_t rb = cb + R_OFF + br * R_BR;
    const int off = (wq == 1 || wq == 2) ? 128 : 0;
#define MV(i) (br ? acc1[i] : acc0[i])
    const uint32_t p01 = pack_bf16(MV(0), MV(1)), p45 = pack_bf16(MV(4), MV(5)), q01 = pack_bf16(MV(2), MV(3)), q45 = pack_bf16(MV(6), MV(7));
#undef MV
    stsm2t(rb + 2 * (RD_X0 - 7 - off - 8 * (lane & 15)), p01, p45);
    {
      const uint32_t a = rb + RD_CS + 2 + 2 * (RD_X0 - 7 - off - 16 * t + g);
      sts16(a, p01); sts16(a - 16, p01 >> 16); sts16(a - 128, p45); sts16(a - 144, p45 >> 16);
    }
    {
      const bool lo = g < 4, tri = lo && !(g & 1);
      const uint32_t x0 = rb + 2 * (RD_X0 - (256 + off + 2 * g + 16 * t));
      const uint32_t xs = rb + ((g & 1) ? R_O2 : R_E2 + 2) + 2 * (159 - (64 + 16 * (g & 2) + (off >> 3) + 2 * t));
      const uint32_t a = lo ? (tri ? x0 + 2 : x0) : xs, b = lo ? (tri ? x0 + RD_CS : x0 + RD_CS + 2) : xs + RS_CS + 2;
      const uint32_t st = lo ? 16 : 2;
      const bool first = (off == 0) && (t == 0);
      const uint32_t v0 = __byte_perm(q01, 0, 0x1010), v1 = __byte_perm(q01, 0, 0x3232), v2 = __byte_perm(q45, 0, 0x1010), v3 = __byte_perm(q45, 0, 0x3232);
      if (!(first && (g & 3) == 0)) sts16(a, v0);
      if (!(first && g == 4)) sts16(b, v0);
      sts16(a - st, v1); sts16(b - st, v1);
      sts16(a - 8 * st, v2); sts16(b - 8 * st, v2);
      sts16(a - 9 * st, v3); sts16(b - 9 * st, v3);
      if (tri) {
        sts32(x0 - 2, v0); sts32(x0 - 18, v1); sts32(x0 - 130, v2); sts32(x0 - 146, v3);
        if (first && g == 0) sts16(x0 + RD_CS + 2, v0); else sts32(x0 + RD_CS + 2, v0);
        sts32(x0 + RD_CS + 2 - 16, v1); sts32(x0 + RD_CS + 2 - 128, v2); sts32(x0 + RD_CS + 2 - 144, v3);
      }
      if (first && g == 4) {
        const uint32_t ad = rb + 2 * (RD_X0 - 514);
        sts16(ad, v0); sts32(ad + 2, v0); sts16(ad + 6, v0); sts32(ad + RD_CS + 2, v0); sts32(ad + RD_CS + 6, v0);
      }
    }
    if (off == 0) {
      const uint32_t ro = cb + R_OFF + (br ^ 1) * R_BR;
      const uint32_t r01 = br ? pack_bf16(acc0[0], acc0[1]) : pack_bf16(acc1[0], acc1[1]);
      const uint32_t r45 = br ? pack_bf16(acc0[4], acc0[5]) : pack_bf16(acc1[4], acc1[5]);
      const uint32_t ao = ro + R_O3 + 2 * (159 - (64 + 16 * (g & 3) + 8 * (g >> 2) + t)), ae = ao - (R_O3 - R_E3) + 2;
      const uint32_t a00 = lane ? ae : ro + R_E2 + 2 * (159 - 127);
      sts16(a00, r01); sts16(a00 + RS_CS + 2, r01);
      sts16(ao, r01 >> 16); sts16(ao + RS_CS + 2, r01 >> 16);
      sts16(ae - 8, r45); sts16(ae - 8 + RS_CS + 2, r45);
      sts16(ao - 8, r45 >> 16); sts16(ao - 8 + RS_CS + 2, r45 >> 16);
      if (lane == 0) {
        sts32(sb + K1024_OFF + (ch * 2 + (br ^ 1)) * 4, __byte_perm(r01, 0, 0x1010));
        const uint2 kq = lds64(sb + K2048_OFF + (ch * 4 + (br ^ 1) * 2) * 4);
        const uint32_t kv = pack_bf16(__uint_as_float(kq.x) + __uint_as_float(kq.y), 0.f);
        sts16(ro + R_E3 + 2 * (159 - 127), kv); sts16(ro + R_E3 + 2 * (159 - 127) + RS_CS + 2, kv);
      }
    }
  }
  STAMP(5);
  asm volatile("barrier.cluster.wait.aligned;" ::: "memory");
  bar_sync(1 + ch, 128);
  mbar_wait(sb + B_U);
  STAMP(6);

  const uint32_t zz = lds32(cb + R_OFF + br * R_BR);
  conv_dense(sb, cb, zz);
  STAMP(8);
  {
    const int x = (4 + ch) * 128 + wtid, c = x >> 2;
    const uint2 dA = ldg64(p.A_D + bid * 4), dB = ldg64(p.B_D + bid * 4);
    const uint2 gl = gate_ld(x);
    const uint32_t rb = cb + R_OFF + br * R_BR;
    float e48[24], e40[20], e32[16], h32[16], h16[8];
    const int x1 = 159 - (16 * hf + g - 2 * t + 136);
    const uint32_t fs = rb + ((g & 1) ? 2 * x1 : RS_CS + 2 * x1 + 2);
    uint32_t A[2][4][4];
    auto loadA = [&](int buf, uint32_t oe, uint32_t oo, int i0) {
#pragma unroll
      for (int a = 0; a < 2; a++) {
        const uint32_t base = fs + (a ? oo : oe) + i0 * 16;
        uint32_t* k0 = A[buf][2 * a];
        uint32_t* k1 = A[buf][2 * a + 1];
        k0[1] = lds32(base); k0[0] = lds32(base + 16); k0[2] = lds32(base + 32); k1[0] = lds32(base + 48); k1[2] = lds32(base + 64);
        k0[3] = k0[0]; k1[1] = k0[2]; k1[3] = k1[0];
      }
    };
    loadA(0, R_E2, R_O2, 8);
    loadA(1, R_E2, R_O2, 4);
    mbar_wait(sb + B_W);
    const uint64_t d5 = mkdesc(cb + W5_OFF, 144, 576), d3 = mkdesc(cb + W3_OFF, 144, 576);
    const uint64_t d9 = mkdesc(cb + W9_OFF, 144, 576), d7 = mkdesc(cb + W7_OFF, 144, 576);
    const uint32_t y2d = cb + Y2_OFF + br * 3072 + ysw(32 * (5 - (lane >> 4)) + 16 * hf + (lane & 15));
    const uint32_t y3d = cb + Y3_OFF + br * 2048 + ysw(2 * (16 * hf + (lane & 15)) + (lane >> 4));
#define FAR4(N, ACC, BUF, DA, DB, OFF, FIRST)                                                            \
    wg_fence();                                                                                           \
    _Pragma("unroll") for (int k = 0; k < 4; k++) {                                                      \
      const uint32_t* a = A[BUF][k];                                                                      \
      wgmma_rs<N, 1>(ACC, a[0], a[1], a[2], a[3], ((k >> 1) ? DB : DA) + (k & 1) * 18 + (OFF), !(FIRST) || k); \
    }                                                                                                     \
    wg_commit();
    FAR4(48, e48, 0, d5, d3, 0, 1)
    wg_wait0();
    loadA(0, R_E2, R_O2, 0);
    stsm2(y2d - 5 * 512, PK2(e48, 20), PK2(e48, 22));
#pragma unroll
    for (int i = 0; i < 20; i++) e40[i] = FCPY(e48, i);
    stage_done(sb, 2, lane);
    FAR4(40, e40, 1, d5, d3, 36, 0)
    wg_wait0();
    loadA(1, R_E3, R_O3, 8);
    stsm2(y2d - 4 * 512, PK2(e40, 16), PK2(e40, 18));
#pragma unroll
    for (int i = 0; i < 16; i++) e32[i] = FCPY(e40, i);
    stage_done(sb, 3, lane);
    FAR4(32, e32, 0, d5, d3, 72, 0)
    FAR4(32, h32, 1, d9, d7, 0, 1)
    wg_wait1();
    loadA(0, R_E3, R_O3, 4);
    stsm4(y2d, PK2(e32, 0), PK2(e32, 2), PK2(e32, 4), PK2(e32, 6));
    stsm4(y2d - 2 * 512, PK2(e32, 8), PK2(e32, 10), PK2(e32, 12), PK2(e32, 14));
    stage_done(sb, 4, lane);
    STAMP(9);
    wg_wait0();
    stsm4(y3d, PK2(h32, 8), PK2(h32, 10), PK2(h32, 12), PK2(h32, 14));
#pragma unroll
    for (int i = 0; i < 8; i++) h16[i] = FCPY(h32, i);
    stage_done(sb, 5, lane);
    FAR4(16, h16, 0, d9, d7, 72, 0)
#undef FAR4
    const uint32_t yo = sb + CH_OFF + (x & 3) * 4 + ysw(c);
    uint32_t ua[4], ub[4], ya[4], yb[4], a2[4], b2[4], a3[4], b3[4], s2[4];
    skip_terms(ua, ub, sb, x, dA, dB);
    {
      const int xa = x - 514, xb = x - 513, ca = xa >> 2, cb2 = xb >> 2;
      ld4ch(s2, sb + CH_OFF + U_OFF + (xa & 3) * 4 + (ca & 3) * U_CS + (63 - (ca >> 2)) * 16);
      ld4ch(a3, sb + CH_OFF + U_OFF + (xb & 3) * 4 + (cb2 & 3) * U_CS + (63 - (cb2 >> 2)) * 16);
#pragma unroll
      for (int k = 0; k < 4; k++) s2[k] = hadd2(s2[k], __byte_perm(s2[k], a3[k], 0x5432));
    }
    const uint32_t tag = lds32(sb + TAG_OFF);
    wg_wait0();
    stsm4(y3d + 1024, PK2(h16, 0), PK2(h16, 2), PK2(h16, 4), PK2(h16, 6));
    stage_done(sb, 6, lane);
    STAMP(10);
    const uint32_t g2 = gate_fin(p, gl, x, tag);
    mbar_wait(sb + B_ST + 8 * 4);
    const uint4 k0 = lds128(sb + K1024_OFF), k1 = lds128(sb + K1024_OFF + 16);
    const uint32_t kk[8] = {k0.x, k0.y, k0.z, k0.w, k1.x, k1.y, k1.z, k1.w};
    ld4ch(ya, yo + Y0_OFF); ld4ch(yb, yo + Y0_OFF + 4096);
    ld4ch(a2, yo + Y2_OFF - 1024); ld4ch(b2, yo + Y2_OFF - 1024 + 3072);
    mbar_wait(sb + B_ST + 8 * (5 + (ch >> 1)));
    STAMP(12);
    ld4ch(a3, yo + Y3_OFF - 2048); ld4ch(b3, yo + Y3_OFF - 2048 + 2048);
#pragma unroll
    for (int k = 0; k < 4; k++) {
      ya[k] = hadd2(ya[k], hadd2(hfma2(kk[2 * k], s2[k], a2[k]), a3[k]));
      yb[k] = hadd2(yb[k], hadd2(hfma2(kk[2 * k + 1], s2[k], b2[k]), b3[k]));
    }
    const uint4 r = mix(ya, yb, ua, ub, g2);
    if ((uint32_t)(ch & 1) != rank) send_box(sb, 2 + (ch >> 1), wtid, rank, r);
    else merge_box(sb, &tm_out, 2 + (ch >> 1), wtid, rank, oc0, r, 1 + ch);
  }
  STAMP(14);
  if (wtid == 0) asm volatile("cp.async.bulk.wait_group.read 0;" ::: "memory");
  STAMP(15); GT(1);
}

typedef CUresult (*EncodeFn)(CUtensorMap*, CUtensorMapDataType, cuuint32_t, void*, const cuuint64_t*, const cuuint64_t*,
                             const cuuint32_t*, const cuuint32_t*, CUtensorMapInterleave, CUtensorMapSwizzle,
                             CUtensorMapL2promotion, CUtensorMapFloatOOBfill);

}

extern "C" void kernel_launch(void* const* d_in, const int* in_sizes, int n_in, void* d_out, int out_size) {
  (void)in_sizes; (void)n_in; (void)out_size;
  typedef const __nv_bfloat16* bp;
  Params p;
  p.t[0] = (bp)d_in[10]; p.t[1] = (bp)d_in[11]; p.t[2] = (bp)d_in[12]; p.t[3] = (bp)d_in[13]; p.t[4] = (bp)d_in[14]; p.t[5] = nullptr;
  p.t[6] = (bp)d_in[1]; p.t[7] = (bp)d_in[2]; p.t[8] = (bp)d_in[5]; p.t[9] = (bp)d_in[6]; p.t[10] = (bp)d_in[7];
  p.t[11] = (bp)d_in[3]; p.t[12] = (bp)d_in[4]; p.t[13] = nullptr;
  p.u = (bp)d_in[0]; p.gw = (bp)d_in[16]; p.A_D = (bp)d_in[8]; p.B_D = (bp)d_in[15];
  static EncodeFn enc = nullptr;
  if (!enc) {
    cudaDriverEntryPointQueryResult qr;
    cudaGetDriverEntryPoint("cuTensorMapEncodeTiled", (void**)&enc, cudaEnableDefault, &qr);
    cudaFuncSetAttribute(ssm_kernel, cudaFuncAttributeMaxDynamicSharedMemorySize, SMEM_BYTES);
  }
  CUtensorMap tm_in, tm_out;
  {
    cuuint64_t gd[5] = {512, 2, 4, 4, 64};
    cuuint64_t gs[4] = {1024, 8192, 2048, 32768};
    cuuint32_t bx[5] = {8, 2, 4, 4, 32};
    cuuint32_t es[5] = {1, 1, 1, 1, 1};
    enc(&tm_in, CU_TENSOR_MAP_DATA_TYPE_BFLOAT16, 5, d_in[0], gd, gs, bx, es, CU_TENSOR_MAP_INTERLEAVE_NONE,
        CU_TENSOR_MAP_SWIZZLE_NONE, CU_TENSOR_MAP_L2_PROMOTION_NONE, CU_TENSOR_MAP_FLOAT_OOB_FILL_NONE);
  }
  {
    cuuint64_t gd[3] = {512, 1024, 2};
    cuuint64_t gs[2] = {2048, 1024};
    cuuint32_t bx[3] = {8, 128, 2};
    cuuint32_t es[3] = {1, 1, 1};
    enc(&tm_out, CU_TENSOR_MAP_DATA_TYPE_BFLOAT16, 3, d_out, gd, gs, bx, es, CU_TENSOR_MAP_INTERLEAVE_NONE,
        CU_TENSOR_MAP_SWIZZLE_NONE, CU_TENSOR_MAP_L2_PROMOTION_NONE, CU_TENSOR_MAP_FLOAT_OOB_FILL_NONE);
  }
  ssm_kernel<<<NCTA + NGATE, 640, SMEM_BYTES, cudaStreamPerThread>>>(p, tm_in, tm_out);
}
```

```cpp
#include <cuda_runtime.h>
#include <cuda.h>
#include <cuda_bf16.h>
#include <stdint.h>

namespace {
#define FCPY(v, i) (((i) % 3 == 2) ? __uint_as_float(opq(__float_as_uint(v[i]), zz)) : opqf(v[i], zz))

constexpr int L = 2048, D = 512, NM = 128;
constexpr int NCTA = 128;
constexpr int NGATE = 4;

constexpr int RAW_OFF = 0;
constexpr int XIN_OFF = 32768;
constexpr int SC2_OFF = XIN_OFF + 8192;
constexpr int BAR_OFF = SC2_OFF + 10240;
constexpr int CH_OFF = BAR_OFF + 256;
constexpr int U_CS = 1184;
constexpr int U_OFF = 0;
constexpr int R_OFF = 4736;
constexpr int RD_X0 = 565;
constexpr int RD_CS = 1216;
constexpr int RS_CS = 320;
constexpr int R_E2 = 2 * RD_CS, R_O2 = R_E2 + 2 * RS_CS, R_E3 = R_O2 + 2 * RS_CS, R_O3 = R_E3 + 2 * RS_CS;
constexpr int R_BR = R_O3 + 2 * RS_CS;
constexpr int W5_OFF = R_OFF + 2 * R_BR;
constexpr int W3_OFF = W5_OFF + 3456;
constexpr int W9_OFF = W3_OFF + 3456;
constexpr int W7_OFF = W9_OFF + 2304;
constexpr int Y0_OFF = W7_OFF + 2304;
constexpr int Y2_OFF = Y0_OFF + 8192, Y3_OFF = Y2_OFF + 6144;
constexpr int CH_BYTES = Y0_OFF + 18432 + 16;
constexpr int SCR_BYTES = 4608;
constexpr int SMEM_BYTES = CH_OFF + 4 * CH_BYTES;
static_assert(CH_BYTES % 128 == 16, "bank staggering of the channel blocks");
static_assert(SMEM_BYTES <= 232448, "smem");
constexpr int B_RAW = BAR_OFF, B_X = BAR_OFF + 8, B_U = BAR_OFF + 40, B_W = BAR_OFF + 48;
constexpr int TAG_OFF = BAR_OFF + 56;
constexpr int K1024_OFF = BAR_OFF + 64;
constexpr int B_ST = BAR_OFF + 96;

__device__ unsigned int g_gate[L];
__device__ unsigned int g_epoch;
__device__ unsigned int g_ticket;

#define STAMP(k)
#define GT(k)

struct Params {
  const __nv_bfloat16* t[14];
  const __nv_bfloat16 *u, *gw, *A_D, *B_D;
};

template <int N, int TB> __device__ __forceinline__ void wgmma_rs(float* d, uint32_t a0, uint32_t a1, uint32_t a2, uint32_t a3, uint64_t desc, int sc);
template <> __device__ __forceinline__ void wgmma_rs<64, 0>(float* d, uint32_t a0, uint32_t a1, uint32_t a2, uint32_t a3, uint64_t desc, int sc) {
  asm volatile("{\n.reg .pred p;\nsetp.ne.b32 p, %37, 0;\n"
    "wgmma.mma_async.sync.aligned.m64n64k16.f32.bf16.bf16 {%0,%1,%2,%3,%4,%5,%6,%7,%8,%9,%10,%11,%12,%13,%14,%15,%16,%17,%18,%19,%20,%21,%22,%23,%24,%25,%26,%27,%28,%29,%30,%31}, {%32,%33,%34,%35}, %36, p, 1, 1, 0;\n}"
    : "+f"(d[0]), "+f"(d[1]), "+f"(d[2]), "+f"(d[3]), "+f"(d[4]), "+f"(d[5]), "+f"(d[6]), "+f"(d[7]), "+f"(d[8]), "+f"(d[9]), "+f"(d[10]), "+f"(d[11]), "+f"(d[12]), "+f"(d[13]), "+f"(d[14]), "+f"(d[15]), "+f"(d[16]), "+f"(d[17]), "+f"(d[18]), "+f"(d[19]), "+f"(d[20]), "+f"(d[21]), "+f"(d[22]), "+f"(d[23]), "+f"(d[24]), "+f"(d[25]), "+f"(d[26]), "+f"(d[27]), "+f"(d[28]), "+f"(d[29]), "+f"(d[30]), "+f"(d[31]) : "r"(a0), "r"(a1), "r"(a2), "r"(a3), "l"(desc), "r"(sc));
}
template <> __device__ __forceinline__ void wgmma_rs<56, 0>(float* d, uint32_t a0, uint32_t a1, uint32_t a2, uint32_t a3, uint64_t desc, int sc) {
  asm volatile("{\n.reg .pred p;\nsetp.ne.b32 p, %33, 0;\n"
    "wgmma.mma_async.sync.aligned.m64n56k16.f32.bf16.bf16 {%0,%1,%2,%3,%4,%5,%6,%7,%8,%9,%10,%11,%12,%13,%14,%15,%16,%17,%18,%19,%20,%21,%22,%23,%24,%25,%26,%27}, {%28,%29,%30,%31}, %32, p, 1, 1, 0;\n}"
    : "+f"(d[0]), "+f"(d[1]), "+f"(d[2]), "+f"(d[3]), "+f"(d[4]), "+f"(d[5]), "+f"(d[6]), "+f"(d[7]), "+f"(d[8]), "+f"(d[9]), "+f"(d[10]), "+f"(d[11]), "+f"(d[12]), "+f"(d[13]), "+f"(d[14]), "+f"(d[15]), "+f"(d[16]), "+f"(d[17]), "+f"(d[18]), "+f"(d[19]), "+f"(d[20]), "+f"(d[21]), "+f"(d[22]), "+f"(d[23]), "+f"(d[24]), "+f"(d[25]), "+f"(d[26]), "+f"(d[27]) : "r"(a0), "r"(a1), "r"(a2), "r"(a3), "l"(desc), "r"(sc));
}
template <> __device__ __forceinline__ void wgmma_rs<48, 0>(float* d, uint32_t a0, uint32_t a1, uint32_t a2, uint32_t a3, uint64_t desc, int sc) {
  asm volatile("{\n.reg .pred p;\nsetp.ne.b32 p, %29, 0;\n"
    "wgmma.mma_async.sync.aligned.m64n48k16.f32.bf16.bf16 {%0,%1,%2,%3,%4,%5,%6,%7,%8,%9,%10,%11,%12,%13,%14,%15,%16,%17,%18,%19,%20,%21,%22,%23}, {%24,%25,%26,%27}, %28, p, 1, 1, 0;\n}"
    : "+f"(d[0]), "+f"(d[1]), "+f"(d[2]), "+f"(d[3]), "+f"(d[4]), "+f"(d[5]), "+f"(d[6]), "+f"(d[7]), "+f"(d[8]), "+f"(d[9]), "+f"(d[10]), "+f"(d[11]), "+f"(d[12]), "+f"(d[13]), "+f"(d[14]), "+f"(d[15]), "+f"(d[16]), "+f"(d[17]), "+f"(d[18]), "+f"(d[19]), "+f"(d[20]), "+f"(d[21]), "+f"(d[22]), "+f"(d[23]) : "r"(a0), "r"(a1), "r"(a2), "r"(a3), "l"(desc), "r"(sc));
}
template <> __device__ __forceinline__ void wgmma_rs<32, 0>(float* d, uint32_t a0, uint32_t a1, uint32_t a2, uint32_t a3, uint64_t desc, int sc) {
  asm volatile("{\n.reg .pred p;\nsetp.ne.b32 p, %21, 0;\n"
    "wgmma.mma_async.sync.aligned.m64n32k16.f32.bf16.bf16 {%0,%1,%2,%3,%4,%5,%6,%7,%8,%9,%10,%11,%12,%13,%14,%15}, {%16,%17,%18,%19}, %20, p, 1, 1, 0;\n}"
    : "+f"(d[0]), "+f"(d[1]), "+f"(d[2]), "+f"(d[3]), "+f"(d[4]), "+f"(d[5]), "+f"(d[6]), "+f"(d[7]), "+f"(d[8]), "+f"(d[9]), "+f"(d[10]), "+f"(d[11]), "+f"(d[12]), "+f"(d[13]), "+f"(d[14]), "+f"(d[15]) : "r"(a0), "r"(a1), "r"(a2), "r"(a3), "l"(desc), "r"(sc));
}
template <> __device__ __forceinline__ void wgmma_rs<48, 1>(float* d, uint32_t a0, uint32_t a1, uint32_t a2, uint32_t a3, uint64_t desc, int sc) {
  asm volatile("{\n.reg .pred p;\nsetp.ne.b32 p, %29, 0;\n"
    "wgmma.mma_async.sync.aligned.m64n48k16.f32.bf16.bf16 {%0,%1,%2,%3,%4,%5,%6,%7,%8,%9,%10,%11,%12,%13,%14,%15,%16,%17,%18,%19,%20,%21,%22,%23}, {%24,%25,%26,%27}, %28, p, 1, 1, 1;\n}"
    : "+f"(d[0]), "+f"(d[1]), "+f"(d[2]), "+f"(d[3]), "+f"(d[4]), "+f"(d[5]), "+f"(d[6]), "+f"(d[7]), "+f"(d[8]), "+f"(d[9]), "+f"(d[10]), "+f"(d[11]), "+f"(d[12]), "+f"(d[13]), "+f"(d[14]), "+f"(d[15]), "+f"(d[16]), "+f"(d[17]), "+f"(d[18]), "+f"(d[19]), "+f"(d[20]), "+f"(d[21]), "+f"(d[22]), "+f"(d[23]) : "r"(a0), "r"(a1), "r"(a2), "r"(a3), "l"(desc), "r"(sc));
}
template <> __device__ __forceinline__ void wgmma_rs<40, 1>(float* d, uint32_t a0, uint32_t a1, uint32_t a2, uint32_t a3, uint64_t desc, int sc) {
  asm volatile("{\n.reg .pred p;\nsetp.ne.b32 p, %25, 0;\n"
    "wgmma.mma_async.sync.aligned.m64n40k16.f32.bf16.bf16 {%0,%1,%2,%3,%4,%5,%6,%7,%8,%9,%10,%11,%12,%13,%14,%15,%16,%17,%18,%19}, {%20,%21,%22,%23}, %24, p, 1, 1, 1;\n}"
    : "+f"(d[0]), "+f"(d[1]), "+f"(d[2]), "+f"(d[3]), "+f"(d[4]), "+f"(d[5]), "+f"(d[6]), "+f"(d[7]), "+f"(d[8]), "+f"(d[9]), "+f"(d[10]), "+f"(d[11]), "+f"(d[12]), "+f"(d[13]), "+f"(d[14]), "+f"(d[15]), "+f"(d[16]), "+f"(d[17]), "+f"(d[18]), "+f"(d[19]) : "r"(a0), "r"(a1), "r"(a2), "r"(a3), "l"(desc), "r"(sc));
}
template <> __device__ __forceinline__ void wgmma_rs<32, 1>(float* d, uint32_t a0, uint32_t a1, uint32_t a2, uint32_t a3, uint64_t desc, int sc) {
  asm volatile("{\n.reg .pred p;\nsetp.ne.b32 p, %21, 0;\n"
    "wgmma.mma_async.sync.aligned.m64n32k16.f32.bf16.bf16 {%0,%1,%2,%3,%4,%5,%6,%7,%8,%9,%10,%11,%12,%13,%14,%15}, {%16,%17,%18,%19}, %20, p, 1, 1, 1;\n}"
    : "+f"(d[0]), "+f"(d[1]), "+f"(d[2]), "+f"(d[3]), "+f"(d[4]), "+f"(d[5]), "+f"(d[6]), "+f"(d[7]), "+f"(d[8]), "+f"(d[9]), "+f"(d[10]), "+f"(d[11]), "+f"(d[12]), "+f"(d[13]), "+f"(d[14]), "+f"(d[15]) : "r"(a0), "r"(a1), "r"(a2), "r"(a3), "l"(desc), "r"(sc));
}
template <> __device__ __forceinline__ void wgmma_rs<16, 1>(float* d, uint32_t a0, uint32_t a1, uint32_t a2, uint32_t a3, uint64_t desc, int sc) {
  asm volatile("{\n.reg .pred p;\nsetp.ne.b32 p, %13, 0;\n"
    "wgmma.mma_async.sync.aligned.m64n16k16.f32.bf16.bf16 {%0,%1,%2,%3,%4,%5,%6,%7}, {%8,%9,%10,%11}, %12, p, 1, 1, 1;\n}"
    : "+f"(d[0]), "+f"(d[1]), "+f"(d[2]), "+f"(d[3]), "+f"(d[4]), "+f"(d[5]), "+f"(d[6]), "+f"(d[7]) : "r"(a0), "r"(a1), "r"(a2), "r"(a3), "l"(desc), "r"(sc));
}

__device__ __forceinline__ uint32_t pack_bf16(float lo, float hi) {
  uint32_t r; asm("cvt.rn.bf16x2.f32 %0, %1, %2;" : "=r"(r) : "f"(hi), "f"(lo)); return r;
}
__device__ __forceinline__ float bf_lo(uint32_t v) { return __uint_as_float(v << 16); }
__device__ __forceinline__ float bf_hi(uint32_t v) { return __uint_as_float(v & 0xffff0000u); }
__device__ __forceinline__ float bf_round(float x) { return bf_lo(pack_bf16(x, 0.f)); }
__device__ __forceinline__ uint32_t hmul2(uint32_t a, uint32_t b) { uint32_t r; asm("mul.rn.bf16x2 %0, %1, %2;" : "=r"(r) : "r"(a), "r"(b)); return r; }
__device__ __forceinline__ uint32_t hadd2(uint32_t a, uint32_t b) { uint32_t r; asm("add.rn.bf16x2 %0, %1, %2;" : "=r"(r) : "r"(a), "r"(b)); return r; }
__device__ __forceinline__ uint32_t hsub2(uint32_t a, uint32_t b) { uint32_t r; asm("sub.rn.bf16x2 %0, %1, %2;" : "=r"(r) : "r"(a), "r"(b)); return r; }
__device__ __forceinline__ uint32_t hfma2(uint32_t a, uint32_t b, uint32_t c) { uint32_t r; asm("fma.rn.bf16x2 %0, %1, %2, %3;" : "=r"(r) : "r"(a), "r"(b), "r"(c)); return r; }

__device__ __forceinline__ void sts16(uint32_t a, uint32_t v) { asm volatile("st.shared.b16 [%0], %1;" ::"r"(a), "h"((unsigned short)v) : "memory"); }
__device__ __forceinline__ void sts32(uint32_t a, uint32_t v) { asm volatile("st.shared.b32 [%0], %1;" ::"r"(a), "r"(v) : "memory"); }
__device__ __forceinline__ void sts64(uint32_t a, uint32_t x, uint32_t y) { asm volatile("st.shared.v2.b32 [%0], {%1,%2};" ::"r"(a), "r"(x), "r"(y) : "memory"); }
__device__ __forceinline__ void sts128(uint32_t a, uint32_t x, uint32_t y, uint32_t z, uint32_t w) {
  asm volatile("st.shared.v4.b32 [%0], {%1,%2,%3,%4};" ::"r"(a), "r"(x), "r"(y), "r"(z), "r"(w) : "memory");
}
__device__ __forceinline__ uint32_t lds32(uint32_t a) { uint32_t v; asm volatile("ld.shared.b32 %0, [%1];" : "=r"(v) : "r"(a) : "memory"); return v; }
__device__ __forceinline__ uint4 lds128(uint32_t a) {
  uint4 v; asm volatile("ld.shared.v4.b32 {%0,%1,%2,%3}, [%4];" : "=r"(v.x), "=r"(v.y), "=r"(v.z), "=r"(v.w) : "r"(a) : "memory"); return v;
}
__device__ __forceinline__ uint4 ldg128(const void* a) {
  uint4 v; asm volatile("ld.global.nc.v4.b32 {%0,%1,%2,%3}, [%4];" : "=r"(v.x), "=r"(v.y), "=r"(v.z), "=r"(v.w) : "l"(a) : "memory"); return v;
}
__device__ __forceinline__ uint2 ldg64(const void* a) {
  uint2 v; asm volatile("ld.global.nc.v2.b32 {%0,%1}, [%2];" : "=r"(v.x), "=r"(v.y) : "l"(a) : "memory"); return v;
}
__device__ __forceinline__ void ldsm4(uint32_t a, uint32_t& r0, uint32_t& r1, uint32_t& r2, uint32_t& r3) {
  asm volatile("ldmatrix.sync.aligned.m8n8.x4.shared.b16 {%0,%1,%2,%3}, [%4];" : "=r"(r0), "=r"(r1), "=r"(r2), "=r"(r3) : "r"(a) : "memory");
}
__device__ __forceinline__ void ldsm4t(uint32_t a, uint32_t& r0, uint32_t& r1, uint32_t& r2, uint32_t& r3) {
  asm volatile("ldmatrix.sync.aligned.m8n8.x4.trans.shared.b16 {%0,%1,%2,%3}, [%4];" : "=r"(r0), "=r"(r1), "=r"(r2), "=r"(r3) : "r"(a) : "memory");
}
__device__ __forceinline__ void stsm4(uint32_t a, uint32_t r0, uint32_t r1, uint32_t r2, uint32_t r3) {
  asm volatile("stmatrix.sync.aligned.m8n8.x4.shared.b16 [%0], {%1,%2,%3,%4};" ::"r"(a), "r"(r0), "r"(r1), "r"(r2), "r"(r3) : "memory");
}
__device__ __forceinline__ void stsm4t(uint32_t a, uint32_t r0, uint32_t r1, uint32_t r2, uint32_t r3) {
  asm volatile("stmatrix.sync.aligned.m8n8.x4.trans.shared.b16 [%0], {%1,%2,%3,%4};" ::"r"(a), "r"(r0), "r"(r1), "r"(r2), "r"(r3) : "memory");
}
__device__ __forceinline__ void stsm2(uint32_t a, uint32_t r0, uint32_t r1) {
  asm volatile("stmatrix.sync.aligned.m8n8.x2.shared.b16 [%0], {%1,%2};" ::"r"(a), "r"(r0), "r"(r1) : "memory");
}
__device__ __forceinline__ void stsm2t(uint32_t a, uint32_t r0, uint32_t r1) {
  asm volatile("stmatrix.sync.aligned.m8n8.x2.trans.shared.b16 [%0], {%1,%2};" ::"r"(a), "r"(r0), "r"(r1) : "memory");
}
__device__ __forceinline__ void mma16816(float* c, uint32_t a0, uint32_t a1, uint32_t a2, uint32_t a3, uint32_t b0, uint32_t b1) {
  asm("mma.sync.aligned.m16n8k16.row.col.f32.bf16.bf16.f32 {%0,%1,%2,%3}, {%4,%5,%6,%7}, {%8,%9}, {%0,%1,%2,%3};"
      : "+f"(c[0]), "+f"(c[1]), "+f"(c[2]), "+f"(c[3]) : "r"(a0), "r"(a1), "r"(a2), "r"(a3), "r"(b0), "r"(b1));
}
__device__ __forceinline__ void bar_sync(int id, int n) { asm volatile("bar.sync %0, %1;" ::"r"(id), "r"(n) : "memory"); }
__device__ __forceinline__ void wg_fence() { asm volatile("wgmma.fence.sync.aligned;" ::: "memory"); }
__device__ __forceinline__ void wg_commit() { asm volatile("wgmma.commit_group.sync.aligned;" ::: "memory"); }
__device__ __forceinline__ void wg_wait0() { asm volatile("wgmma.wait_group.sync.aligned 0;" ::: "memory"); }
__device__ __forceinline__ void wg_wait1() { asm volatile("wgmma.wait_group.sync.aligned 1;" ::: "memory"); }
__device__ __forceinline__ void fence_async() { asm volatile("fence.proxy.async.shared::cta;" ::: "memory"); }
__device__ __forceinline__ uint32_t opq(uint32_t x, uint32_t z) { uint32_t r; asm volatile("xor.b32 %0, %1, %2;" : "=r"(r) : "r"(x), "r"(z)); return r; }
__device__ __forceinline__ float opqf(float x, uint32_t z) { float r; asm volatile("add.rn.f32 %0, %1, %2;" : "=f"(r) : "f"(x), "f"(__uint_as_float(z))); return r; }
__device__ __forceinline__ uint64_t mkdesc(uint32_t addr, uint32_t lbo, uint32_t sbo) {
  return (uint64_t)((addr & 0x3FFFF) >> 4) | ((uint64_t)(lbo >> 4) << 16) | ((uint64_t)(sbo >> 4) << 32);
}
__device__ __forceinline__ uint32_t mapa(uint32_t a, uint32_t rank) {
  uint32_t r; asm("mapa.shared::cluster.u32 %0, %1, %2;" : "=r"(r) : "r"(a), "r"(rank)); return r;
}
__device__ __forceinline__ void mbar_init_expect(uint32_t bar, uint32_t bytes) {
  asm volatile("mbarrier.init.shared::cta.b64 [%0], 1;" ::"r"(bar) : "memory");
  asm volatile("mbarrier.arrive.expect_tx.shared::cta.b64 _, [%0], %1;" ::"r"(bar), "r"(bytes) : "memory");
}
__device__ __forceinline__ void mbar_wait(uint32_t bar) {
#pragma unroll 1
  for (int it = 0; it < (1 << 22); it++) {
    uint32_t ok;
    asm volatile("{\n.reg .pred p;\nmbarrier.try_wait.parity.acquire.cluster.shared::cta.b64 p, [%1], 0;\nselp.u32 %0, 1, 0, p;\n}"
                 : "=r"(ok) : "r"(bar) : "memory");
    if (ok) return;
  }
  __trap();
}
__device__ __forceinline__ void st_async4(uint32_t a, uint32_t bar, uint32_t x, uint32_t y, uint32_t z, uint32_t w) {
  asm volatile("st.async.weak.shared::cluster.mbarrier::complete_tx::bytes.v4.b32 [%0], {%2,%3,%4,%5}, [%1];"
               ::"r"(a), "r"(bar), "r"(x), "r"(y), "r"(z), "r"(w) : "memory");
}

struct cf { float re, im; };
__device__ __forceinline__ cf cmul(cf a, cf b) { return {fmaf(a.re, b.re, -a.im * b.im), fmaf(a.re, b.im, a.im * b.re)}; }
__device__ __forceinline__ cf csq(cf a) { return {fmaf(a.re, a.re, -a.im * a.im), (a.re + a.re) * a.im}; }
__device__ __forceinline__ cf cexp_p(float xl, float y, float p) {
  float mag; asm("ex2.approx.ftz.f32 %0, %1;" : "=f"(mag) : "f"(xl * p));
  const float th = y * p;
  const float k = __fadd_rn(fmaf(th, 0.15915494309189535f, 12582912.f), -12582912.f);
  float r = fmaf(k, -6.2831854820251465f, th);
  r = fmaf(k, 1.7484555314695172e-07f, r);
  return {mag * __cosf(r), mag * __sinf(r)};
}
__device__ __forceinline__ uint32_t ysw(int c) { return (uint32_t)(c ^ ((c >> 3) & 3)) * 16u; }

#define CMUL2(OR, OI, xr, xi, yr, yi, nyi) do { OR = hfma2(xr, yr, hmul2(xi, nyi)); OI = hfma2(xr, yi, hmul2(xi, yr)); } while (0)

__device__ __forceinline__ uint32_t gate_slow(const __nv_bfloat16* u, const __nv_bfloat16* gw, int row) {
  float s = 0.f;
  const uint32_t* xr = (const uint32_t*)(u + (size_t)row * D);
  const uint32_t* wr = (const uint32_t*)gw;
#pragma unroll 1
  for (int j = 0; j < D / 2; j++) { const uint32_t pr = hmul2(xr[j], wr[j]); s += bf_lo(pr); s += bf_hi(pr); }
  s = bf_round(s);
  return pack_bf16(1.f / (1.f + expf(-s)), 0.f);
}

__device__ __forceinline__ uint2 gate_ld(int x) {
  uint2 gv;
  asm volatile("ld.relaxed.gpu.global.v2.u32 {%0,%1}, [%2];" : "=r"(gv.x), "=r"(gv.y) : "l"(g_gate + x * 2) : "memory");
  return gv;
}
__device__ __noinline__ uint32_t gate_poll(const Params* pp, int x, uint32_t tag) {
  uint2 gv;
#pragma unroll 1
  for (int spins = 0; spins < (1 << 16); spins++) {
    gv = gate_ld(x);
    if ((gv.x >> 16) == tag && (gv.y >> 16) == tag) return __byte_perm(gv.x, gv.y, 0x5410);
  }
  return __byte_perm(gate_slow(pp->u, pp->gw, x * 2), gate_slow(pp->u, pp->gw, x * 2 + 1), 0x5410);
}
__device__ __forceinline__ uint32_t gate_fin(const Params& p, uint2 gv, int x, uint32_t tag) {
  if ((gv.x >> 16) == tag && (gv.y >> 16) == tag) return __byte_perm(gv.x, gv.y, 0x5410);
  return gate_poll(&p, x, tag);
}

__device__ __forceinline__ void ld4ch(uint32_t* v, uint32_t addr) {
#pragma unroll
  for (int k = 0; k < 4; k++) v[k] = lds32(addr + k * CH_BYTES);
}
__device__ __forceinline__ void skip_terms(uint32_t* ua, uint32_t* ub, uint32_t sb, int x, uint2 dA, uint2 dB) {
  const int c = x >> 2;
  uint32_t uu[4];
  ld4ch(uu, sb + CH_OFF + (x & 3) * 4 + U_OFF + (c & 3) * U_CS + (63 - (c >> 2)) * 16);
#pragma unroll
  for (int k = 0; k < 4; k++) {
    ua[k] = hmul2(uu[k], __byte_perm((k & 2) ? dA.y : dA.x, 0, (k & 1) ? 0x3232 : 0x1010));
    ub[k] = hmul2(uu[k], __byte_perm((k & 2) ? dB.y : dB.x, 0, (k & 1) ? 0x3232 : 0x1010));
  }
}
__device__ __forceinline__ uint4 mix(const uint32_t* a, const uint32_t* b, const uint32_t* ua, const uint32_t* ub, uint32_t g2) {
  const uint32_t h2 = hsub2(0x3f803f80u, g2);
  uint32_t o[4];
#pragma unroll
  for (int k = 0; k < 4; k++) o[k] = hadd2(hmul2(g2, hadd2(a[k], ua[k])), hmul2(h2, hadd2(b[k], ub[k])));
  return make_uint4(__byte_perm(o[0], o[1], 0x5410), __byte_perm(o[2], o[3], 0x5410), __byte_perm(o[0], o[1], 0x7632), __byte_perm(o[2], o[3], 0x7632));
}
__device__ __forceinline__ void send_box(uint32_t sb, int slot, int wtid, uint32_t rank, uint4 r) {
  st_async4(mapa(sb + XIN_OFF + slot * 2048 + wtid * 16, rank ^ 1), mapa(sb + B_X + slot * 8, rank ^ 1), r.x, r.y, r.z, r.w);
}
__device__ __forceinline__ void merge_rows(uint32_t st, uint32_t rank, uint4 r, uint4 q) {
  const uint4 lo = rank ? q : r, hi = rank ? r : q;
  sts128(st, lo.x, lo.y, hi.x, hi.y); sts128(st + 2048, lo.z, lo.w, hi.z, hi.w);
}
__device__ __forceinline__ void merge_box(uint32_t sb, const CUtensorMap* tm_out, int slot, int wtid, uint32_t rank, int oc0, uint4 r, int barid) {
  const uint32_t st = sb + RAW_OFF + slot * 4096 + wtid * 16;
  mbar_wait(sb + B_X + slot * 8);
  merge_rows(st, rank, r, lds128(sb + XIN_OFF + slot * 2048 + wtid * 16));
  fence_async();
  bar_sync(barid, 128);
  if (wtid == 0) {
    asm volatile("cp.async.bulk.tensor.3d.global.shared::cta.bulk_group [%0, {%2, %3, %4}], [%1];"
                 ::"l"(tm_out), "r"(sb + RAW_OFF + slot * 4096), "r"(oc0), "r"((2 * slot + (int)rank) * 128), "r"(0) : "memory");
    asm volatile("cp.async.bulk.commit_group;" ::: "memory");
  }
}

__device__ __forceinline__ uint32_t band2(int e, int lo, int hi) {
  uint32_t r = ((uint32_t)(e - lo) <= (uint32_t)(hi - lo) ? 0x3f80u : 0u) | ((uint32_t)(e - 1 - lo) <= (uint32_t)(hi - lo) ? 0x3f800000u : 0u);
  asm volatile("" : "+r"(r));
  return r;
}

__device__ __forceinline__ void stage_done(uint32_t sb, int stage, int lane) {
  __syncwarp();
  if (lane == 0) asm volatile("mbarrier.arrive.shared::cta.b64 _, [%0];" ::"r"(sb + B_ST + 8 * stage) : "memory");
}
#define PK2(v, i) pack_bf16(v[i], v[(i) + 1])

__device__ __forceinline__ void conv_dense(uint32_t sb, uint32_t cb, uint32_t zz) {
  const int lane = threadIdx.x & 31, wq = (threadIdx.x >> 5) & 3, br = wq >> 1, hf = wq & 1, g = lane >> 2, t = lane & 3;
  const uint32_t rb = cb + R_OFF + br * R_BR;
  const int eo = 16 * hf + g - 2 * t;
  const int x0 = RD_X0 - (eo + 536);
  const uint32_t fa = rb + ((g & 1) ? 2 * x0 : RD_CS + 2 * x0 + 2);
  const uint64_t ub = mkdesc(cb + U_OFF, U_CS, 128);
  const uint32_t yd = cb + Y0_OFF + br * 4096 + ysw(4 * (63 - 8 * (lane >> 4) - (lane & 7)) + 2 * hf + ((lane >> 3) & 1));
  uint32_t A[2][4][4];
  float e64[32], e56[28], e48[24];
  auto loadA = [&](int j) {
#pragma unroll
    for (int k = 0; k < 4; k++) {
      const int s = 34 - 4 * j - k;
      if (s >= 0) {
        if (k == 0 && j == 0) A[0][0][2] = lds32(fa + (2 * s + 2) * 16);
        A[j & 1][k][0] = lds32(fa + (2 * s + 1) * 16);
        A[j & 1][k][1] = lds32(fa + (2 * s) * 16);
      }
    }
#pragma unroll
    for (int k = 0; k < 4; k++) {
      if (34 - 4 * j - k >= 0) {
        A[j & 1][k][3] = A[j & 1][k][0];
        if (k) A[j & 1][k][2] = A[j & 1][k - 1][1];
        else if (j) A[j & 1][0][2] = A[(j - 1) & 1][3][1];
      }
    }
  };
  loadA(0); loadA(1);
#pragma unroll
  for (int j = 0; j < 9; j++) {
    if (j == 4) {
      wg_wait0();
      stsm2t(yd - 7 * 512, PK2(e64, 28), PK2(e64, 30));
#pragma unroll
      for (int i = 0; i < 28; i++) e56[i] = FCPY(e64, i);
      stage_done(sb, 0, lane);
    }
    if (j == 8) {
      wg_wait0();
      stsm2t(yd - 6 * 512, PK2(e56, 24), PK2(e56, 26));
#pragma unroll
      for (int i = 0; i < 24; i++) e48[i] = FCPY(e56, i);
      stage_done(sb, 1, lane);
    }
    wg_fence();
#pragma unroll
    for (int k = 0; k < 4; k++) {
      const int s = 34 - 4 * j - k;
      if (s >= 0) {
        const int o = 2 * s - 66 + 128;
        const int cc = o & 3, rs = (o >> 2) - 32;
        const uint64_t desc = ub + (uint64_t)((cc * U_CS - rs * 16) >> 4);
        const uint32_t* a = A[j & 1][k];
        if (j < 4) wgmma_rs<64, 0>(e64, a[0], a[1], a[2], a[3], desc, s != 34);
        else if (j < 8) wgmma_rs<56, 0>(e56, a[0], a[1], a[2], a[3], desc, 1);
        else wgmma_rs<48, 0>(e48, a[0], a[1], a[2], a[3], desc, 1);
      }
    }
    wg_commit();
    if (j >= 1 && j < 8) { wg_wait1(); loadA(j + 1); }
  }
  wg_wait0();
#pragma unroll
  for (int i = 0; i < 6; i += 2) stsm4t(yd - i * 512, PK2(e48, 4 * i), PK2(e48, 4 * i + 2), PK2(e48, 4 * i + 4), PK2(e48, 4 * i + 6));
}

__device__ __noinline__ unsigned int gate_rows(const Params* pp, int grow, int step, int rend) {
  const __nv_bfloat16 *u = pp->u, *gw = pp->gw;
  const int lane = threadIdx.x & 31;
  uint4 gx[4][2], nx[4][2];
#pragma unroll
  for (int i = 0; i < 4; i++) {
    nx[i][0] = ldg128(u + (size_t)(grow + i) * D + lane * 8);
    nx[i][1] = ldg128(u + (size_t)(grow + i) * D + 256 + lane * 8);
  }
  const uint4 gw0 = ldg128(gw + lane * 8), gw1 = ldg128(gw + 256 + lane * 8);
  const uint32_t ws[8] = {gw0.x, gw0.y, gw0.z, gw0.w, gw1.x, gw1.y, gw1.z, gw1.w};
  unsigned int epoch;
  asm volatile("ld.relaxed.gpu.global.u32 %0, [%1];" : "=r"(epoch) : "l"(&g_epoch) : "memory");
#pragma unroll 1
  for (; grow < rend; grow += step) {
#pragma unroll
    for (int i = 0; i < 4; i++) { gx[i][0] = nx[i][0]; gx[i][1] = nx[i][1]; }
    if (grow + step < rend) {
#pragma unroll
      for (int i = 0; i < 4; i++) {
        nx[i][0] = ldg128(u + (size_t)(grow + step + i) * D + lane * 8);
        nx[i][1] = ldg128(u + (size_t)(grow + step + i) * D + 256 + lane * 8);
      }
    }
    float c[2][4];
#pragma unroll
    for (int i = 0; i < 2; i++) {
      const uint4 *x = gx[2 * i], *y = gx[2 * i + 1];
      const uint32_t xs[8] = {x[0].x, x[0].y, x[0].z, x[0].w, x[1].x, x[1].y, x[1].z, x[1].w};
      const uint32_t ys[8] = {y[0].x, y[0].y, y[0].z, y[0].w, y[1].x, y[1].y, y[1].z, y[1].w};
      c[i][0] = c[i][1] = c[i][2] = c[i][3] = 0.f;
#pragma unroll
      for (int j = 0; j < 8; j += 2)
        mma16816(c[i], hmul2(xs[j], ws[j]), hmul2(ys[j], ws[j]), hmul2(xs[j + 1], ws[j + 1]), hmul2(ys[j + 1], ws[j + 1]), 0x3f803f80u, 0x3f803f80u);
    }
    float s = (lane & 2) ? ((lane & 1) ? c[1][2] : c[1][0]) : ((lane & 1) ? c[0][2] : c[0][0]);
#pragma unroll
    for (int o = 4; o < 32; o <<= 1) s += __shfl_xor_sync(0xffffffffu, s, o);
    s = bf_round(s);
    const float gv = 1.f / (1.f + expf(-s));
    const uint32_t w = ((epoch + 1) << 16) | (pack_bf16(gv, 0.f) & 0xffffu);
    if (lane < 4) asm volatile("st.relaxed.gpu.global.u32 [%0], %1;" ::"l"(&g_gate[grow + lane]), "r"(w) : "memory");
  }
  return epoch;
}
#define GW 1
constexpr int GSPLIT = L - 4 * GW * NCTA;
__device__ __noinline__ void gate_cta(const Params* pp) {
  const unsigned int epoch = gate_rows(pp, (blockIdx.x * 20 + (threadIdx.x >> 5)) * 4, 80 * NGATE, GSPLIT);
  __syncthreads();
  if (threadIdx.x == 0 && atomicAdd(&g_ticket, 1u) == NCTA + NGATE - 1) { g_ticket = 0; g_epoch = epoch + 1; }
}

__global__ void __cluster_dims__(2, 1, 1) __launch_bounds__(640, 1)
ssm_kernel(const __grid_constant__ Params p, const __grid_constant__ CUtensorMap tm_in, const __grid_constant__ CUtensorMap tm_out) {
  extern __shared__ __align__(1024) unsigned char smem_raw[];
  const uint32_t sb = (uint32_t)__cvta_generic_to_shared(smem_raw);
  const int tid = threadIdx.x, lane = tid & 31;
  const int warp = __shfl_sync(0xffffffffu, tid >> 5, 0);
  const int ch = warp >> 2, wq = warp & 3, br = wq >> 1, hf = wq & 1;
  const int g = lane >> 2, t = lane & 3;
  if (__builtin_expect(blockIdx.x < NGATE, 0)) { gate_cta(&p); return; }
  const int bid = blockIdx.x - NGATE;
  const uint32_t rank = blockIdx.x & 1;
  const uint32_t cb = sb + CH_OFF + ch * CH_BYTES;
  const int wtid = tid & 127;
  const int oc0 = (bid >> 1) * 8;
  STAMP(0); GT(0);

  if (warp >= 16) {
    if (wtid == 0) {
      mbar_init_expect(sb + B_RAW, 32768);
#pragma unroll
      for (int i = 0; i < 4; i++) mbar_init_expect(sb + B_X + 8 * i, 2048);
      asm volatile("mbarrier.init.shared::cta.b64 [%0], 128;" ::"r"(sb + B_U) : "memory");
      asm volatile("mbarrier.init.shared::cta.b64 [%0], 128;" ::"r"(sb + B_W) : "memory");
#pragma unroll
      for (int i = 0; i < 7; i++) asm volatile("mbarrier.init.shared::cta.b64 [%0], 16;" ::"r"(sb + B_ST + 8 * i) : "memory");
      asm volatile("fence.mbarrier_init.release.cluster;" ::: "memory");
      asm volatile("fence.proxy.async.shared::cta;" ::: "memory");
    }
    __syncwarp();
    asm volatile("barrier.cluster.arrive.relaxed.aligned;" ::: "memory");
    if (wq >= 4 - GW) gate_rows(&p, GSPLIT + (bid * GW + 3 - wq) * 4, L, L);
    unsigned int epoch;
    asm volatile("ld.relaxed.gpu.global.u32 %0, [%1];" : "=r"(epoch) : "l"(&g_epoch) : "memory");
    asm volatile("barrier.cluster.wait.aligned;" ::: "memory");
    if (wtid == 0) {
      asm volatile("cp.async.bulk.tensor.5d.shared::cluster.global.mbarrier::complete_tx::bytes.multicast::cluster [%0], [%1, {%3, %4, %4, %4, %5}], [%2], %6;"
                   ::"r"(sb + RAW_OFF + rank * 16384), "l"(&tm_in), "r"(sb + B_RAW), "r"(oc0), "r"(0), "r"((int)rank * 32), "h"((unsigned short)3) : "memory");
    }
    sts128(sb + CH_OFF + wq * CH_BYTES + U_OFF + (lane >> 3) * U_CS + (64 + (lane & 7)) * 16, 0, 0, 0, 0);
    const uint2 dA = ldg64(p.A_D + bid * 4), dB = ldg64(p.B_D + bid * 4);
    uint32_t BA[3][4], BB[4][4];
    {
      const int l1 = br ? 3 : 6, h1 = br ? 5 : 10, l2 = br ? 5 : 12, h2 = br ? 11 : 20;
#pragma unroll
      for (int i = 0; i < 4; i++) {
        const int e = 16 * hf + g - 2 * t + 32 - 16 * i;
        BB[i][0] = band2(e, l2, h2); BB[i][1] = band2(e + 8, l2, h2); BB[i][2] = band2(e - 8, l2, h2); BB[i][3] = BB[i][0];
        if (i) { BA[i - 1][0] = band2(e, l1, h1); BA[i - 1][1] = band2(e + 8, l1, h1); BA[i - 1][2] = band2(e - 8, l1, h1); BA[i - 1][3] = BA[i - 1][0]; }
      }
    }
    const uint32_t tag = (epoch + 1) & 0xffffu;
    if (wtid == 0) sts32(sb + TAG_OFF, tag);
    STAMP(3);
    mbar_wait(sb + B_RAW);
    STAMP(4);
    {
      const uint32_t dst = sb + CH_OFF + (g & 3) * CH_BYTES + U_OFF + t * U_CS + (63 - wq * 16) * 16;
#pragma unroll
      for (int h = 0; h < 2; h++) {
        uint32_t r[8][4];
#pragma unroll
        for (int i = 0; i < 8; i++) ldsm4t(sb + RAW_OFF + (wq * 16 + h * 8 + i) * 512 + lane * 16, r[i][0], r[i][1], r[i][2], r[i][3]);
        if ((uint32_t)(g >> 2) == rank) {
#pragma unroll
          for (int i = 0; i < 8; i++) sts128(dst - (h * 8 + i) * 16, r[i][0], r[i][1], r[i][2], r[i][3]);
        }
      }
    }
    fence_async();
    asm volatile("mbarrier.arrive.shared::cta.b64 _, [%0];" ::"r"(sb + B_U) : "memory");
    bar_sync(5, 128);
    STAMP(5);
    {
      const int mrow = lane & 7, mi = lane >> 3;
      const uint64_t ub0 = mkdesc(sb + CH_OFF + U_OFF, U_CS, 128);
      uint32_t wa, wb;
      {
        const int c = 4 * (47 - 8 * (mi >> 1) - mrow) + 2 * hf + (mi & 1);
        wa = sb + CH_OFF + (br ? W3_OFF : W5_OFF) + (5 - (c >> 5)) * 576 + ((c & 31) >> 3) * 144 + (c & 7) * 16;
        const int c2 = c - 64, pp = c2 >> 1;
        wb = sb + CH_OFF + (br ? W7_OFF : W9_OFF) + (1 - (pp >> 5)) * 1152 + (c2 & 1) * 576 + ((pp & 31) >> 3) * 144 + (pp & 7) * 16;
      }
      {
        float w1[24];
#pragma unroll
        for (int i = 0; i < 24; i++) w1[i] = 0.f;
#pragma unroll 1
        for (int k = 0; k < 4; k++) {
          wg_fence();
#pragma unroll
          for (int i = 0; i < 3; i++)
            wgmma_rs<48, 0>(w1, BA[i][0], BA[i][1], BA[i][2], BA[i][3],
                            ub0 + (uint64_t)((k * CH_BYTES + ((2 * i + 2) & 3) * U_CS + (16 + (i == 0)) * 16) >> 4), i);
          wg_commit();
          wg_wait0();
#pragma unroll
          for (int i = 0; i < 3; i++) stsm4t(wa + k * CH_BYTES + i * 1152, PK2(w1, 8 * i), PK2(w1, 8 * i + 2), PK2(w1, 8 * i + 4), PK2(w1, 8 * i + 6));
        }
      }
      {
        float w2[2][16];
#pragma unroll
        for (int i = 0; i < 16; i++) { w2[0][i] = 0.f; w2[1][i] = 0.f; }
#pragma unroll 1
        for (int kp = 0; kp < 2; kp++) {
          wg_fence();
#pragma unroll
          for (int k = 0; k < 2; k++)
#pragma unroll
            for (int i = 0; i < 4; i++)
              wgmma_rs<32, 0>(w2[k], BB[i][0], BB[i][1], BB[i][2], BB[i][3],
                              ub0 + (uint64_t)(((2 * kp + k) * CH_BYTES + ((2 * i) & 3) * U_CS + (32 + (i < 2)) * 16) >> 4), i);
          wg_commit();
          wg_wait0();
#pragma unroll
          for (int k = 0; k < 2; k++)
#pragma unroll
            for (int i = 0; i < 2; i++)
              stsm4t(wb + (2 * kp + k) * CH_BYTES + i * 1152, PK2(w2[k], 8 * i), PK2(w2[k], 8 * i + 2), PK2(w2[k], 8 * i + 4), PK2(w2[k], 8 * i + 6));
        }
      }
    }
    fence_async();
    asm volatile("mbarrier.arrive.shared::cta.b64 _, [%0];" ::"r"(sb + B_W) : "memory");
    STAMP(7);
    {
      const int bsel = (int)rank ^ br ^ 1, xl = wtid & 63;
      uint2 gl[4];
      uint32_t ua[4][4], ub[4][4];
#pragma unroll
      for (int i = 0; i < 4; i++) skip_terms(ua[i], ub[i], sb, (2 * (i >> 1) + bsel) * 128 + (i & 1) * 64 + xl, dA, dB);
      const uint32_t yo = sb + CH_OFF + (xl & 3) * 4 + ysw(xl >> 2) + bsel * 512;
#pragma unroll
      for (int i = 0; i < 2; i++) gl[i] = gate_ld(bsel * 128 + i * 64 + xl);
#pragma unroll
      for (int slot = 0; slot < 2; slot++) {
        const int box = 2 * slot + bsel;
        uint32_t g2[2], ya[2][4], yb[2][4];
#pragma unroll
        for (int h = 0; h < 2; h++) g2[h] = gate_fin(p, gl[2 * slot + h], box * 128 + h * 64 + xl, tag);
        mbar_wait(sb + B_ST + 8 * box);
        STAMP(8 + slot);
        if (slot == 0) { gl[2] = gate_ld((2 + bsel) * 128 + xl); gl[3] = gate_ld((2 + bsel) * 128 + 64 + xl); }
#pragma unroll
        for (int h = 0; h < 2; h++) {
          const uint32_t yh = (yo ^ (h * 32)) + h * 256 + slot * 1024;
          ld4ch(ya[h], yh + Y0_OFF); ld4ch(yb[h], yh + Y0_OFF + 4096);
          if (slot) {
            uint32_t a2[4], b2[4];
            ld4ch(a2, yh + Y2_OFF - 1024); ld4ch(b2, yh + Y2_OFF - 1024 + 3072);
#pragma unroll
            for (int k = 0; k < 4; k++) { ya[h][k] = hadd2(ya[h][k], a2[k]); yb[h][k] = hadd2(yb[h][k], b2[k]); }
          }
        }
        const uint4 r0 = mix(ya[0], yb[0], ua[2 * slot], ub[2 * slot], g2[0]), r1 = mix(ya[1], yb[1], ua[2 * slot + 1], ub[2 * slot + 1], g2[1]);
        if (br == 0) { send_box(sb, slot, xl, rank, r0); send_box(sb, slot, xl + 64, rank, r1); }
        else {
          const uint32_t st = sb + RAW_OFF + slot * 4096 + xl * 16, xin = sb + XIN_OFF + slot * 2048 + xl * 16;
          mbar_wait(sb + B_X + slot * 8);
          const uint4 q0 = lds128(xin), q1 = lds128(xin + 1024);
          merge_rows(st, rank, r0, q0); merge_rows(st + 1024, rank, r1, q1);
          fence_async();
          bar_sync(6, 64);
          if (xl == 0) {
            asm volatile("cp.async.bulk.tensor.3d.global.shared::cta.bulk_group [%0, {%2, %3, %4}], [%1];"
                         ::"l"(&tm_out), "r"(sb + RAW_OFF + slot * 4096), "r"(oc0), "r"(box * 128), "r"(0) : "memory");
            asm volatile("cp.async.bulk.commit_group;" ::: "memory");
          }
        }
        STAMP(10 + slot);
      }
    }
    if (wtid == 0 && atomicAdd(&g_ticket, 1u) == NCTA + NGATE - 1) { g_ticket = 0; g_epoch = epoch + 1; }
    if (wtid == 64) asm volatile("cp.async.bulk.wait_group.read 0;" ::: "memory");
    STAMP(15);
    return;
  }
  asm volatile("barrier.cluster.arrive.relaxed.aligned;" ::: "memory");

  const int moff = (bid * 4 + (tid >> 7)) * NM + (tid & 63) * 2;
  const int brt = (tid >> 6) & 1;
  const __nv_bfloat16* const* tp = p.t + (brt ? 0 : 6);
  const uint32_t q0 = *(const uint32_t*)(tp[0] + moff), q1 = *(const uint32_t*)(tp[1] + moff);
  const uint32_t q2 = *(const uint32_t*)(tp[2] + moff), q3 = *(const uint32_t*)(tp[3] + moff);
  const uint2 ldt4 = *(const uint2*)(tp[4] + bid * 4);
  const uint32_t q4 = *(const uint32_t*)(tp[brt ? 2 : 5] + moff), q5 = *(const uint32_t*)(tp[brt ? 3 : 6] + moff);

  for (int i = wtid & 63; i < R_BR / 16; i += 64) sts128(cb + R_OFF + br * R_BR + i * 16, 0, 0, 0, 0);
  STAMP(1);

  float acc[5][4];
  float k2048 = 0.f;
  const uint32_t scr = cb + Y0_OFF + wq * SCR_BYTES;
  const uint32_t scr2 = sb + SC2_OFF + warp * 640;
  {
    const uint32_t ldt2 = (ch & 2) ? ldt4.y : ldt4.x;
    const float dt = bf_round(expf((ch & 1) ? bf_hi(ldt2) : bf_lo(ldt2)));
#pragma unroll
    for (int i = 0; i < 5; i++) acc[i][0] = acc[i][1] = acc[i][2] = acc[i][3] = 0.f;
    STAMP(2);
    const uint32_t tb = scr + lane * 16;
    const uint32_t ta = scr + (lane >> 3) * 512 + (lane & 7) * 16;
    const uint32_t tc = ((lane & 8) ? scr2 : scr + 4096) + (lane >> 4) * 128 + (lane & 7) * 16;
    const uint32_t tm = scr2 + 512 + ((lane >> 3) & 1) * 64 + (lane >> 4) * 16;
    cf cc[2], zz1[2], zz128[2];
#pragma unroll
    for (int r = 0; r < 2; r++) {
      float v0 = r ? bf_hi(q0) : bf_lo(q0), v1 = r ? bf_hi(q1) : bf_lo(q1), v2 = r ? bf_hi(q2) : bf_lo(q2);
      float v3 = r ? bf_hi(q3) : bf_lo(q3), v4 = r ? bf_hi(q4) : bf_lo(q4), v5 = r ? bf_hi(q5) : bf_lo(q5);
      if (br == 0) { cc[r] = cmul(cf{v2, v3}, cf{dt * v4, dt * v5}); }
      else { v0 = -bf_round(expf(v0)); cc[r] = cf{2.f * dt * v2, 2.f * dt * v3}; }
      const float xl = (dt * v0) * 1.4426950408889634f, y = dt * v1;
      zz1[r] = cexp_p(xl, y, 1.f); zz128[r] = cexp_p(xl, y, 128.f);
    }
    uint32_t T[10][4], m4;
    auto produce = [&](int r) {
      const cf c = cc[r], z1 = zz1[r], z128 = zz128[r];
      const cf z2 = csq(z1), z4 = csq(z2), z8 = csq(z4);
      const cf w8 = {z8.re, -z8.im};
      const cf z16 = csq(w8), z24 = cmul(z16, w8), z32 = csq(z16), z40 = cmul(z32, w8), z48 = csq(z24), z56 = cmul(z32, z24), z64 = csq(z32);
      const cf z256 = csq(z128), z512 = csq(z256), z1024 = csq(z512), z2048 = csq(z1024);
      k2048 += fmaf(c.re, z2048.re, -c.im * z2048.im);
      {
        T[0][0] = pack_bf16(1.f, z8.re); T[0][1] = pack_bf16(z16.re, z24.re); T[0][2] = pack_bf16(z32.re, z40.re); T[0][3] = pack_bf16(z48.re, z56.re);
        T[2][0] = pack_bf16(0.f, w8.im); T[2][1] = pack_bf16(z16.im, z24.im); T[2][2] = pack_bf16(z32.im, z40.im); T[2][3] = pack_bf16(z48.im, z56.im);
        const uint32_t yr = pack_bf16(z64.re, z64.re), yi = pack_bf16(z64.im, z64.im), nyi = yi ^ 0x80008000u;
#pragma unroll
        for (int i = 0; i < 4; i++) CMUL2(T[1][i], T[3][i], T[0][i], T[2][i], yr, yi, nyi);
      }
      {
        const cf h1 = cmul(c, z128), h2 = cmul(c, z256), h3 = cmul(h1, z256), h4 = cmul(c, z512), h5 = cmul(h1, z512), h6 = cmul(h2, z512), h7 = cmul(h3, z512);
        const cf e1 = cmul(c, z1), e2 = cmul(c, z2), e3 = cmul(e1, z2), e129 = cmul(h1, z1), e130 = cmul(h1, z2), e131 = cmul(e129, z2);
        const cf e258 = cmul(h2, z2), e386 = cmul(h3, z2);
        T[4][0] = pack_bf16(c.re, e1.re); T[4][1] = pack_bf16(e2.re, e3.re); T[4][2] = pack_bf16(h1.re, e129.re); T[4][3] = pack_bf16(e130.re, e131.re);
        T[5][0] = pack_bf16(c.im, e1.im); T[5][1] = pack_bf16(e2.im, e3.im); T[5][2] = pack_bf16(h1.im, e129.im); T[5][3] = pack_bf16(e130.im, e131.im);
        T[6][0] = pack_bf16(h2.re, e258.re); T[6][1] = pack_bf16(h3.re, e386.re); T[6][2] = pack_bf16(h4.re, h5.re); T[6][3] = pack_bf16(h6.re, h7.re);
        T[7][0] = pack_bf16(h2.im, e258.im); T[7][1] = pack_bf16(h3.im, e386.im); T[7][2] = pack_bf16(h4.im, h5.im); T[7][3] = pack_bf16(h6.im, h7.im);
        const uint32_t xr[4] = {__byte_perm(T[4][0], T[4][2], 0x5410), __byte_perm(T[6][0], T[6][1], 0x5410), T[6][2], T[6][3]};
        const uint32_t xi[4] = {__byte_perm(T[5][0], T[5][2], 0x5410), __byte_perm(T[7][0], T[7][1], 0x5410), T[7][2], T[7][3]};
        const uint32_t yr = pack_bf16(z1024.re, z1024.re), yi = pack_bf16(z1024.im, z1024.im), nyi = yi ^ 0x80008000u;
#pragma unroll
        for (int i = 0; i < 4; i++) CMUL2(T[8][i], T[9][i], xr[i], xi[i], yr, yi, nyi);
        m4 = pack_bf16(z4.re, z4.im);
      }
    };
    auto store = [&]() {
#pragma unroll
      for (int m = 0; m < 9; m++) sts128(tb + m * 512, T[m][0], T[m][1], T[m][2], T[m][3]);
      sts128(scr2 + lane * 16, T[9][0], T[9][1], T[9][2], T[9][3]);
      sts16(scr2 + 512 + lane * 2, m4); sts16(scr2 + 576 + lane * 2, m4 >> 16);
    };
    auto consume = [&]() {
#pragma unroll
      for (int kp = 0; kp < 2; kp++) {
        uint32_t rr[2], ri[2], yr[2], yi[2];
        ldsm4t(tc + kp * 256, rr[0], ri[0], rr[1], ri[1]);
        ldsm4(tm + kp * 32, yr[0], yi[0], yr[1], yi[1]);
#pragma unroll
        for (int k2 = 0; k2 < 2; k2++) {
          const int kk = kp * 2 + k2;
          uint32_t a0, a1, a2, a3, pr, pi, qr, qi, xr, xi;
          ldsm4t(ta + kk * 128, a0, a1, a2, a3);
          ldsm4t(ta + 2048 + kk * 128, pr, pi, qr, qi);
          const uint32_t nyi = yi[k2] ^ 0x80008000u;
          mma16816(acc[0], a0, a1, a2, a3, pr, pi);
          mma16816(acc[2], a0, a1, a2, a3, qr, qi);
          mma16816(acc[4], a0, a1, a2, a3, rr[k2], ri[k2]);
          CMUL2(xr, xi, pr, pi, yr[k2], yi[k2], nyi);
          mma16816(acc[1], a0, a1, a2, a3, xr, xi);
          CMUL2(xr, xi, qr, qi, yr[k2], yi[k2], nyi);
          mma16816(acc[3], a0, a1, a2, a3, xr, xi);
        }
      }
    };
    produce(0); store();
    __syncwarp();
    consume(); produce(1);
    __syncwarp();
    store();
#pragma unroll
    for (int o = 16; o; o >>= 1) k2048 += __shfl_xor_sync(0xffffffffu, k2048, o);
    __syncwarp();
    consume();
  }
  STAMP(3);
  __syncwarp();
  {
    const uint32_t xs = scr + lane * 16;
#define OTH(i, k) __float_as_uint(hf ? acc[i][k] : acc[i][2 + (k)])
    sts128(xs, OTH(0, 0), OTH(0, 1), OTH(1, 0), OTH(1, 1));
    sts128(xs + 512, OTH(2, 0), OTH(2, 1), OTH(3, 0), OTH(3, 1));
    sts128(xs + 1024, OTH(4, 0), OTH(4, 1), __float_as_uint(k2048), 0);
#undef OTH
  }

  bar_sync(7 + (warp >> 1), 64);
  STAMP(4);
  {
    const uint32_t xo = cb + Y0_OFF + (wq ^ 1) * SCR_BYTES + lane * 16;
    const uint4 o0 = lds128(xo), o1 = lds128(xo + 512), o2 = lds128(xo + 1024);
    const uint32_t rb = cb + R_OFF + br * R_BR;
#define OWN(i, k) (hf ? acc[i][2 + (k)] : acc[i][k])
    const uint32_t vP = pack_bf16(OWN(0, 1) + __uint_as_float(o0.y), OWN(0, 0) + __uint_as_float(o0.x));
    const uint32_t vP4 = pack_bf16(OWN(1, 1) + __uint_as_float(o0.w), OWN(1, 0) + __uint_as_float(o0.z));
    const uint32_t vQ = pack_bf16(OWN(2, 1) + __uint_as_float(o1.y), OWN(2, 0) + __uint_as_float(o1.x));
    const uint32_t vQ4 = pack_bf16(OWN(3, 1) + __uint_as_float(o1.w), OWN(3, 0) + __uint_as_float(o1.z));
    const uint32_t vR = pack_bf16(OWN(4, 1) + __uint_as_float(o2.y), OWN(4, 0) + __uint_as_float(o2.x));
#undef OWN
    const int j = g + 8 * hf;
    {
      const int a = 2 * (t & 1) + 64 * (t & 2) + 8 * j;
      const uint32_t ad = rb + 2 * (RD_X0 - 1 - a);
      const uint32_t a1 = (t & 2) ? ad - 8 : ad, a2 = (t & 2) ? ad : ad - 8;
      const uint32_t w1 = (t & 2) ? vP4 : vP, w2 = (t & 2) ? vP : vP4;
      sts32(a1, w1); sts32(a2, w2);
      sts16(a1 + RD_CS + 2, w1); sts16(a1 + RD_CS + 4, w1 >> 16);
      sts16(a2 + RD_CS + 2, w2); sts16(a2 + RD_CS + 4, w2 >> 16);
    }
    if (t < 2) {
      const int b = 256 + 128 * t + 8 * j;
      const uint32_t ad = rb + 2 * (RD_X0 - 6 - b);
      const uint32_t v22 = __byte_perm(vQ4, 0, 0x3232), v00 = __byte_perm(vQ, 0, 0x3232);
      sts16(ad, vQ4);
      sts64(ad + 2, v22, __byte_perm(vQ4, vQ, 0x5432));
      sts32(ad + 10, v00);
      if (b != 256) { sts16(ad + 14, v00); sts128(ad + RD_CS + 2, vQ4, v22, vQ, v00); }
      else { sts64(ad + RD_CS + 2, vQ4, v22); sts32(ad + RD_CS + 10, vQ); sts16(ad + RD_CS + 14, v00); }
    } else {
      const uint32_t ao = rb + R_O2 + 2 * (159 - (32 * t + j)), ae = ao - (R_O2 - R_E2) + 2;
      sts16(ao, vQ4 >> 16); sts16(ao + RS_CS + 2, vQ4 >> 16); sts16(ao - 32, vQ4); sts16(ao - 32 + RS_CS + 2, vQ4);
      sts16(ae - 32, vQ); sts16(ae - 32 + RS_CS + 2, vQ);
      if (lane != 2 || hf) { sts16(ae, vQ >> 16); sts16(ae + RS_CS + 2, vQ >> 16); }
      else {
        const uint32_t vv = __byte_perm(vQ, 0, 0x3232), ad = rb + 2 * (RD_X0 - 514);
        sts16(ad, vv); sts32(ad + 2, vv); sts16(ad + 6, vv); sts64(ad + RD_CS + 2, vv, vv);
      }
    }
    {
      const uint32_t a = rb + ((g & 1) ? R_O3 : R_E3 + 2) + 2 * (159 - (64 + 16 * t + (j >> 1)));
      const bool p1024 = (lane == 0) && (hf == 0);
      const uint32_t a00 = p1024 ? rb + R_E2 + 2 * (159 - 127) : a;
      sts16(a00, vR >> 16); sts16(a00 + RS_CS + 2, vR >> 16);
      sts16(a - 16, vR); sts16(a - 16 + RS_CS + 2, vR);
      if (p1024) {
        sts32(sb + K1024_OFF + (ch * 2 + br) * 4, __byte_perm(vR, 0, 0x3232));
        const uint32_t kv = pack_bf16(k2048 + __uint_as_float(o2.z), 0.f);
        sts16(rb + R_E3 + 2 * (159 - 127), kv); sts16(rb + R_E3 + 2 * (159 - 127) + RS_CS + 2, kv);
      }
    }
  }
  STAMP(5);
  asm volatile("barrier.cluster.wait.aligned;" ::: "memory");
  bar_sync(7 + (warp >> 1), 64);
  mbar_wait(sb + B_U);
  STAMP(6);

  const uint32_t zz = lds32(cb + R_OFF + br * R_BR);
  conv_dense(sb, cb, zz);
  STAMP(8);
  {
    const int x = (4 + ch) * 128 + wtid, c = x >> 2;
    const uint2 dA = ldg64(p.A_D + bid * 4), dB = ldg64(p.B_D + bid * 4);
    const uint2 gl = gate_ld(x);
    const uint32_t rb = cb + R_OFF + br * R_BR;
    float e48[24], e40[20], e32[16], h32[16], h16[8];
    const int x1 = 159 - (16 * hf + g - 2 * t + 136);
    const uint32_t fs = rb + ((g & 1) ? 2 * x1 : RS_CS + 2 * x1 + 2);
    uint32_t A[2][4][4];
    auto loadA = [&](int buf, uint32_t oe, uint32_t oo, int i0) {
#pragma unroll
      for (int a = 0; a < 2; a++) {
        const uint32_t base = fs + (a ? oo : oe) + i0 * 16;
        uint32_t* k0 = A[buf][2 * a];
        uint32_t* k1 = A[buf][2 * a + 1];
        k0[1] = lds32(base); k0[0] = lds32(base + 16); k0[2] = lds32(base + 32); k1[0] = lds32(base + 48); k1[2] = lds32(base + 64);
        k0[3] = k0[0]; k1[1] = k0[2]; k1[3] = k1[0];
      }
    };
    loadA(0, R_E2, R_O2, 8);
    loadA(1, R_E2, R_O2, 4);
    mbar_wait(sb + B_W);
    const uint64_t d5 = mkdesc(cb + W5_OFF, 144, 576), d3 = mkdesc(cb + W3_OFF, 144, 576);
    const uint64_t d9 = mkdesc(cb + W9_OFF, 144, 576), d7 = mkdesc(cb + W7_OFF, 144, 576);
    const uint32_t y2d = cb + Y2_OFF + br * 3072 + ysw(32 * (5 - (lane >> 4)) + 16 * hf + (lane & 15));
    const uint32_t y3d = cb + Y3_OFF + br * 2048 + ysw(2 * (16 * hf + (lane & 15)) + (lane >> 4));
#define FAR4(N, ACC, BUF, DA, DB, OFF, FIRST)                                                            \
    wg_fence();                                                                                           \
    _Pragma("unroll") for (int k = 0; k < 4; k++) {                                                      \
      const uint32_t* a = A[BUF][k];                                                                      \
      wgmma_rs<N, 1>(ACC, a[0], a[1], a[2], a[3], ((k >> 1) ? DB : DA) + (k & 1) * 18 + (OFF), !(FIRST) || k); \
    }                                                                                                     \
    wg_commit();
    FAR4(48, e48, 0, d5, d3, 0, 1)
    wg_wait0();
    loadA(0, R_E2, R_O2, 0);
    stsm2(y2d - 5 * 512, PK2(e48, 20), PK2(e48, 22));
#pragma unroll
    for (int i = 0; i < 20; i++) e40[i] = FCPY(e48, i);
    stage_done(sb, 2, lane);
    FAR4(40, e40, 1, d5, d3, 36, 0)
    wg_wait0();
    loadA(1, R_E3, R_O3, 8);
    stsm2(y2d - 4 * 512, PK2(e40, 16), PK2(e40, 18));
#pragma unroll
    for (int i = 0; i < 16; i++) e32[i] = FCPY(e40, i);
    stage_done(sb, 3, lane);
    FAR4(32, e32, 0, d5, d3, 72, 0)
    FAR4(32, h32, 1, d9, d7, 0, 1)
    wg_wait1();
    loadA(0, R_E3, R_O3, 4);
    stsm4(y2d, PK2(e32, 0), PK2(e32, 2), PK2(e32, 4), PK2(e32, 6));
    stsm4(y2d - 2 * 512, PK2(e32, 8), PK2(e32, 10), PK2(e32, 12), PK2(e32, 14));
    stage_done(sb, 4, lane);
    STAMP(9);
    wg_wait0();
    stsm4(y3d, PK2(h32, 8), PK2(h32, 10), PK2(h32, 12), PK2(h32, 14));
#pragma unroll
    for (int i = 0; i < 8; i++) h16[i] = FCPY(h32, i);
    stage_done(sb, 5, lane);
    FAR4(16, h16, 0, d9, d7, 72, 0)
#undef FAR4
    const uint32_t yo = sb + CH_OFF + (x & 3) * 4 + ysw(c);
    uint32_t ua[4], ub[4], ya[4], yb[4], a2[4], b2[4], a3[4], b3[4], s2[4];
    skip_terms(ua, ub, sb, x, dA, dB);
    {
      const int xa = x - 514, xb = x - 513, ca = xa >> 2, cb2 = xb >> 2;
      ld4ch(s2, sb + CH_OFF + U_OFF + (xa & 3) * 4 + (ca & 3) * U_CS + (63 - (ca >> 2)) * 16);
      ld4ch(a3, sb + CH_OFF + U_OFF + (xb & 3) * 4 + (cb2 & 3) * U_CS + (63 - (cb2 >> 2)) * 16);
#pragma unroll
      for (int k = 0; k < 4; k++) s2[k] = hadd2(s2[k], __byte_perm(s2[k], a3[k], 0x5432));
    }
    const uint32_t tag = lds32(sb + TAG_OFF);
    wg_wait0();
    stsm4(y3d + 1024, PK2(h16, 0), PK2(h16, 2), PK2(h16, 4), PK2(h16, 6));
    stage_done(sb, 6, lane);
    STAMP(10);
    const uint32_t g2 = gate_fin(p, gl, x, tag);
    mbar_wait(sb + B_ST + 8 * 4);
    const uint4 k0 = lds128(sb + K1024_OFF), k1 = lds128(sb + K1024_OFF + 16);
    const uint32_t kk[8] = {k0.x, k0.y, k0.z, k0.w, k1.x, k1.y, k1.z, k1.w};
    ld4ch(ya, yo + Y0_OFF); ld4ch(yb, yo + Y0_OFF + 4096);
    ld4ch(a2, yo + Y2_OFF - 1024); ld4ch(b2, yo + Y2_OFF - 1024 + 3072);
    mbar_wait(sb + B_ST + 8 * (5 + (ch >> 1)));
    STAMP(12);
    ld4ch(a3, yo + Y3_OFF - 2048); ld4ch(b3, yo + Y3_OFF - 2048 + 2048);
#pragma unroll
    for (int k = 0; k < 4; k++) {
      ya[k] = hadd2(ya[k], hadd2(hfma2(kk[2 * k], s2[k], a2[k]), a3[k]));
      yb[k] = hadd2(yb[k], hadd2(hfma2(kk[2 * k + 1], s2[k], b2[k]), b3[k]));
    }
    const uint4 r = mix(ya, yb, ua, ub, g2);
    if ((uint32_t)(ch & 1) != rank) send_box(sb, 2 + (ch >> 1), wtid, rank, r);
    else merge_box(sb, &tm_out, 2 + (ch >> 1), wtid, rank, oc0, r, 1 + ch);
  }
  STAMP(14);
  if (wtid == 0) asm volatile("cp.async.bulk.wait_group.read 0;" ::: "memory");
  STAMP(15); GT(1);
}

typedef CUresult (*EncodeFn)(CUtensorMap*, CUtensorMapDataType, cuuint32_t, void*, const cuuint64_t*, const cuuint64_t*,
                             const cuuint32_t*, const cuuint32_t*, CUtensorMapInterleave, CUtensorMapSwizzle,
                             CUtensorMapL2promotion, CUtensorMapFloatOOBfill);

}

extern "C" void kernel_launch(void* const* d_in, const int* in_sizes, int n_in, void* d_out, int out_size) {
  (void)in_sizes; (void)n_in; (void)out_size;
  typedef const __nv_bfloat16* bp;
  Params p;
  p.t[0] = (bp)d_in[10]; p.t[1] = (bp)d_in[11]; p.t[2] = (bp)d_in[12]; p.t[3] = (bp)d_in[13]; p.t[4] = (bp)d_in[14]; p.t[5] = nullptr;
  p.t[6] = (bp)d_in[1]; p.t[7] = (bp)d_in[2]; p.t[8] = (bp)d_in[5]; p.t[9] = (bp)d_in[6]; p.t[10] = (bp)d_in[7];
  p.t[11] = (bp)d_in[3]; p.t[12] = (bp)d_in[4]; p.t[13] = nullptr;
  p.u = (bp)d_in[0]; p.gw = (bp)d_in[16]; p.A_D = (bp)d_in[8]; p.B_D = (bp)d_in[15];
  static EncodeFn enc = nullptr;
  if (!enc) {
    cudaDriverEntryPointQueryResult qr;
    cudaGetDriverEntryPoint("cuTensorMapEncodeTiled", (void**)&enc, cudaEnableDefault, &qr);
    cudaFuncSetAttribute(ssm_kernel, cudaFuncAttributeMaxDynamicSharedMemorySize, SMEM_BYTES);
  }
  CUtensorMap tm_in, tm_out;
  {
    cuuint64_t gd[5] = {512, 2, 4, 4, 64};
    cuuint64_t gs[4] = {1024, 8192, 2048, 32768};
    cuuint32_t bx[5] = {8, 2, 4, 4, 32};
    cuuint32_t es[5] = {1, 1, 1, 1, 1};
    enc(&tm_in, CU_TENSOR_MAP_DATA_TYPE_BFLOAT16, 5, d_in[0], gd, gs, bx, es, CU_TENSOR_MAP_INTERLEAVE_NONE,
        CU_TENSOR_MAP_SWIZZLE_NONE, CU_TENSOR_MAP_L2_PROMOTION_NONE, CU_TENSOR_MAP_FLOAT_OOB_FILL_NONE);
  }
  {
    cuuint64_t gd[3] = {512, 1024, 2};
    cuuint64_t gs[2] = {2048, 1024};
    cuuint32_t bx[3] = {8, 128, 2};
    cuuint32_t es[3] = {1, 1, 1};
    enc(&tm_out, CU_TENSOR_MAP_DATA_TYPE_BFLOAT16, 3, d_out, gd, gs, bx, es, CU_TENSOR_MAP_INTERLEAVE_NONE,
        CU_TENSOR_MAP_SWIZZLE_NONE, CU_TENSOR_MAP_L2_PROMOTION_NONE, CU_TENSOR_MAP_FLOAT_OOB_FILL_NONE);
  }
  ssm_kernel<<<NCTA + NGATE, 640, SMEM_BYTES, cudaStreamPerThread>>>(p, tm_in, tm_out);
}
```

```cpp
#include <cuda_runtime.h>
#include <cuda.h>
#include <cuda_bf16.h>
#include <stdint.h>

namespace {
#define FCPY(v, i) (((i) % 3 == 2) ? __uint_as_float(opq(__float_as_uint(v[i]), zz)) : opqf(v[i], zz))

constexpr int L = 2048, D = 512, NM = 128;
constexpr int NCTA = 128;
constexpr int NGATE = 4;

constexpr int RAW_OFF = 0;
constexpr int XIN_OFF = 32768;
constexpr int SC2_OFF = XIN_OFF + 8192;
constexpr int BAR_OFF = SC2_OFF + 10240;
constexpr int CH_OFF = BAR_OFF + 256;
constexpr int U_CS = 1184;
constexpr int U_OFF = 0;
constexpr int R_OFF = 4736;
constexpr int RD_X0 = 565;
constexpr int RD_CS = 1216;
constexpr int RS_CS = 320;
constexpr int R_E2 = 2 * RD_CS, R_O2 = R_E2 + 2 * RS_CS, R_E3 = R_O2 + 2 * RS_CS, R_O3 = R_E3 + 2 * RS_CS;
constexpr int R_BR = R_O3 + 2 * RS_CS;
constexpr int W5_OFF = R_OFF + 2 * R_BR;
constexpr int W3_OFF = W5_OFF + 3456;
constexpr int W9_OFF = W3_OFF + 3456;
constexpr int W7_OFF = W9_OFF + 2304;
constexpr int Y0_OFF = W7_OFF + 2304;
constexpr int Y2_OFF = Y0_OFF + 8192, Y3_OFF = Y2_OFF + 6144;
constexpr int CH_BYTES = Y0_OFF + 18432 + 16;
constexpr int SCR_BYTES = 4608;
constexpr int SMEM_BYTES = CH_OFF + 4 * CH_BYTES;
static_assert(CH_BYTES % 128 == 16, "bank staggering of the channel blocks");
static_assert(SMEM_BYTES <= 232448, "smem");
constexpr int B_RAW = BAR_OFF, B_X = BAR_OFF + 8, B_U = BAR_OFF + 40, B_W = BAR_OFF + 48;
constexpr int TAG_OFF = BAR_OFF + 56;
constexpr int K1024_OFF = BAR_OFF + 64;
constexpr int B_ST = BAR_OFF + 96;

__device__ unsigned int g_gate[L];
__device__ unsigned int g_epoch;
__device__ unsigned int g_ticket;

#define STAMP(k)
#define GT(k)

struct Params {
  const __nv_bfloat16* t[14];
  const __nv_bfloat16 *u, *gw, *A_D, *B_D;
};

template <int N, int TB> __device__ __forceinline__ void wgmma_rs(float* d, uint32_t a0, uint32_t a1, uint32_t a2, uint32_t a3, uint64_t desc, int sc);
template <> __device__ __forceinline__ void wgmma_rs<64, 0>(float* d, uint32_t a0, uint32_t a1, uint32_t a2, uint32_t a3, uint64_t desc, int sc) {
  asm volatile("{\n.reg .pred p;\nsetp.ne.b32 p, %37, 0;\n"
    "wgmma.mma_async.sync.aligned.m64n64k16.f32.bf16.bf16 {%0,%1,%2,%3,%4,%5,%6,%7,%8,%9,%10,%11,%12,%13,%14,%15,%16,%17,%18,%19,%20,%21,%22,%23,%24,%25,%26,%27,%28,%29,%30,%31}, {%32,%33,%34,%35}, %36, p, 1, 1, 0;\n}"
    : "+f"(d[0]), "+f"(d[1]), "+f"(d[2]), "+f"(d[3]), "+f"(d[4]), "+f"(d[5]), "+f"(d[6]), "+f"(d[7]), "+f"(d[8]), "+f"(d[9]), "+f"(d[10]), "+f"(d[11]), "+f"(d[12]), "+f"(d[13]), "+f"(d[14]), "+f"(d[15]), "+f"(d[16]), "+f"(d[17]), "+f"(d[18]), "+f"(d[19]), "+f"(d[20]), "+f"(d[21]), "+f"(d[22]), "+f"(d[23]), "+f"(d[24]), "+f"(d[25]), "+f"(d[26]), "+f"(d[27]), "+f"(d[28]), "+f"(d[29]), "+f"(d[30]), "+f"(d[31]) : "r"(a0), "r"(a1), "r"(a2), "r"(a3), "l"(desc), "r"(sc));
}
template <> __device__ __forceinline__ void wgmma_rs<56, 0>(float* d, uint32_t a0, uint32_t a1, uint32_t a2, uint32_t a3, uint64_t desc, int sc) {
  asm volatile("{\n.reg .pred p;\nsetp.ne.b32 p, %33, 0;\n"
    "wgmma.mma_async.sync.aligned.m64n56k16.f32.bf16.bf16 {%0,%1,%2,%3,%4,%5,%6,%7,%8,%9,%10,%11,%12,%13,%14,%15,%16,%17,%18,%19,%20,%21,%22,%23,%24,%25,%26,%27}, {%28,%29,%30,%31}, %32, p, 1, 1, 0;\n}"
    : "+f"(d[0]), "+f"(d[1]), "+f"(d[2]), "+f"(d[3]), "+f"(d[4]), "+f"(d[5]), "+f"(d[6]), "+f"(d[7]), "+f"(d[8]), "+f"(d[9]), "+f"(d[10]), "+f"(d[11]), "+f"(d[12]), "+f"(d[13]), "+f"(d[14]), "+f"(d[15]), "+f"(d[16]), "+f"(d[17]), "+f"(d[18]), "+f"(d[19]), "+f"(d[20]), "+f"(d[21]), "+f"(d[22]), "+f"(d[23]), "+f"(d[24]), "+f"(d[25]), "+f"(d[26]), "+f"(d[27]) : "r"(a0), "r"(a1), "r"(a2), "r"(a3), "l"(desc), "r"(sc));
}
template <> __device__ __forceinline__ void wgmma_rs<48, 0>(float* d, uint32_t a0, uint32_t a1, uint32_t a2, uint32_t a3, uint64_t desc, int sc) {
  asm volatile("{\n.reg .pred p;\nsetp.ne.b32 p, %29, 0;\n"
    "wgmma.mma_async.sync.aligned.m64n48k16.f32.bf16.bf16 {%0,%1,%2,%3,%4,%5,%6,%7,%8,%9,%10,%11,%12,%13,%14,%15,%16,%17,%18,%19,%20,%21,%22,%23}, {%24,%25,%26,%27}, %28, p, 1, 1, 0;\n}"
    : "+f"(d[0]), "+f"(d[1]), "+f"(d[2]), "+f"(d[3]), "+f"(d[4]), "+f"(d[5]), "+f"(d[6]), "+f"(d[7]), "+f"(d[8]), "+f"(d[9]), "+f"(d[10]), "+f"(d[11]), "+f"(d[12]), "+f"(d[13]), "+f"(d[14]), "+f"(d[15]), "+f"(d[16]), "+f"(d[17]), "+f"(d[18]), "+f"(d[19]), "+f"(d[20]), "+f"(d[21]), "+f"(d[22]), "+f"(d[23]) : "r"(a0), "r"(a1), "r"(a2), "r"(a3), "l"(desc), "r"(sc));
}
template <> __device__ __forceinline__ void wgmma_rs<32, 0>(float* d, uint32_t a0, uint32_t a1, uint32_t a2, uint32_t a3, uint64_t desc, int sc) {
  asm volatile("{\n.reg .pred p;\nsetp.ne.b32 p, %21, 0;\n"
    "wgmma.mma_async.sync.aligned.m64n32k16.f32.bf16.bf16 {%0,%1,%2,%3,%4,%5,%6,%7,%8,%9,%10,%11,%12,%13,%14,%15}, {%16,%17,%18,%19}, %20, p, 1, 1, 0;\n}"
    : "+f"(d[0]), "+f"(d[1]), "+f"(d[2]), "+f"(d[3]), "+f"(d[4]), "+f"(d[5]), "+f"(d[6]), "+f"(d[7]), "+f"(d[8]), "+f"(d[9]), "+f"(d[10]), "+f"(d[11]), "+f"(d[12]), "+f"(d[13]), "+f"(d[14]), "+f"(d[15]) : "r"(a0), "r"(a1), "r"(a2), "r"(a3), "l"(desc), "r"(sc));
}
template <> __device__ __forceinline__ void wgmma_rs<48, 1>(float* d, uint32_t a0, uint32_t a1, uint32_t a2, uint32_t a3, uint64_t desc, int sc) {
  asm volatile("{\n.reg .pred p;\nsetp.ne.b32 p, %29, 0;\n"
    "wgmma.mma_async.sync.aligned.m64n48k16.f32.bf16.bf16 {%0,%1,%2,%3,%4,%5,%6,%7,%8,%9,%10,%11,%12,%13,%14,%15,%16,%17,%18,%19,%20,%21,%22,%23}, {%24,%25,%26,%27}, %28, p, 1, 1, 1;\n}"
    : "+f"(d[0]), "+f"(d[1]), "+f"(d[2]), "+f"(d[3]), "+f"(d[4]), "+f"(d[5]), "+f"(d[6]), "+f"(d[7]), "+f"(d[8]), "+f"(d[9]), "+f"(d[10]), "+f"(d[11]), "+f"(d[12]), "+f"(d[13]), "+f"(d[14]), "+f"(d[15]), "+f"(d[16]), "+f"(d[17]), "+f"(d[18]), "+f"(d[19]), "+f"(d[20]), "+f"(d[21]), "+f"(d[22]), "+f"(d[23]) : "r"(a0), "r"(a1), "r"(a2), "r"(a3), "l"(desc), "r"(sc));
}
template <> __device__ __forceinline__ void wgmma_rs<40, 1>(float* d, uint32_t a0, uint32_t a1, uint32_t a2, uint32_t a3, uint64_t desc, int sc) {
  asm volatile("{\n.reg .pred p;\nsetp.ne.b32 p, %25, 0;\n"
    "wgmma.mma_async.sync.aligned.m64n40k16.f32.bf16.bf16 {%0,%1,%2,%3,%4,%5,%6,%7,%8,%9,%10,%11,%12,%13,%14,%15,%16,%17,%18,%19}, {%20,%21,%22,%23}, %24, p, 1, 1, 1;\n}"
    : "+f"(d[0]), "+f"(d[1]), "+f"(d[2]), "+f"(d[3]), "+f"(d[4]), "+f"(d[5]), "+f"(d[6]), "+f"(d[7]), "+f"(d[8]), "+f"(d[9]), "+f"(d[10]), "+f"(d[11]), "+f"(d[12]), "+f"(d[13]), "+f"(d[14]), "+f"(d[15]), "+f"(d[16]), "+f"(d[17]), "+f"(d[18]), "+f"(d[19]) : "r"(a0), "r"(a1), "r"(a2), "r"(a3), "l"(desc), "r"(sc));
}
template <> __device__ __forceinline__ void wgmma_rs<32, 1>(float* d, uint32_t a0, uint32_t a1, uint32_t a2, uint32_t a3, uint64_t desc, int sc) {
  asm volatile("{\n.reg .pred p;\nsetp.ne.b32 p, %21, 0;\n"
    "wgmma.mma_async.sync.aligned.m64n32k16.f32.bf16.bf16 {%0,%1,%2,%3,%4,%5,%6,%7,%8,%9,%10,%11,%12,%13,%14,%15}, {%16,%17,%18,%19}, %20, p, 1, 1, 1;\n}"
    : "+f"(d[0]), "+f"(d[1]), "+f"(d[2]), "+f"(d[3]), "+f"(d[4]), "+f"(d[5]), "+f"(d[6]), "+f"(d[7]), "+f"(d[8]), "+f"(d[9]), "+f"(d[10]), "+f"(d[11]), "+f"(d[12]), "+f"(d[13]), "+f"(d[14]), "+f"(d[15]) : "r"(a0), "r"(a1), "r"(a2), "r"(a3), "l"(desc), "r"(sc));
}
template <> __device__ __forceinline__ void wgmma_rs<16, 1>(float* d, uint32_t a0, uint32_t a1, uint32_t a2, uint32_t a3, uint64_t desc, int sc) {
  asm volatile("{\n.reg .pred p;\nsetp.ne.b32 p, %13, 0;\n"
    "wgmma.mma_async.sync.aligned.m64n16k16.f32.bf16.bf16 {%0,%1,%2,%3,%4,%5,%6,%7}, {%8,%9,%10,%11}, %12, p, 1, 1, 1;\n}"
    : "+f"(d[0]), "+f"(d[1]), "+f"(d[2]), "+f"(d[3]), "+f"(d[4]), "+f"(d[5]), "+f"(d[6]), "+f"(d[7]) : "r"(a0), "r"(a1), "r"(a2), "r"(a3), "l"(desc), "r"(sc));
}

__device__ __forceinline__ uint32_t pack_bf16(float lo, float hi) {
  uint32_t r; asm("cvt.rn.bf16x2.f32 %0, %1, %2;" : "=r"(r) : "f"(hi), "f"(lo)); return r;
}
__device__ __forceinline__ float bf_lo(uint32_t v) { return __uint_as_float(v << 16); }
__device__ __forceinline__ float bf_hi(uint32_t v) { return __uint_as_float(v & 0xffff0000u); }
__device__ __forceinline__ float bf_round(float x) { return bf_lo(pack_bf16(x, 0.f)); }
__device__ __forceinline__ uint32_t hmul2(uint32_t a, uint32_t b) { uint32_t r; asm("mul.rn.bf16x2 %0, %1, %2;" : "=r"(r) : "r"(a), "r"(b)); return r; }
__device__ __forceinline__ uint32_t hadd2(uint32_t a, uint32_t b) { uint32_t r; asm("add.rn.bf16x2 %0, %1, %2;" : "=r"(r) : "r"(a), "r"(b)); return r; }
__device__ __forceinline__ uint32_t hsub2(uint32_t a, uint32_t b) { uint32_t r; asm("sub.rn.bf16x2 %0, %1, %2;" : "=r"(r) : "r"(a), "r"(b)); return r; }
__device__ __forceinline__ uint32_t hfma2(uint32_t a, uint32_t b, uint32_t c) { uint32_t r; asm("fma.rn.bf16x2 %0, %1, %2, %3;" : "=r"(r) : "r"(a), "r"(b), "r"(c)); return r; }

__device__ __forceinline__ void sts16(uint32_t a, uint32_t v) { asm volatile("st.shared.b16 [%0], %1;" ::"r"(a), "h"((unsigned short)v) : "memory"); }
__device__ __forceinline__ void sts32(uint32_t a, uint32_t v) { asm volatile("st.shared.b32 [%0], %1;" ::"r"(a), "r"(v) : "memory"); }
__device__ __forceinline__ void sts64(uint32_t a, uint32_t x, uint32_t y) { asm volatile("st.shared.v2.b32 [%0], {%1,%2};" ::"r"(a), "r"(x), "r"(y) : "memory"); }
__device__ __forceinline__ void sts128(uint32_t a, uint32_t x, uint32_t y, uint32_t z, uint32_t w) {
  asm volatile("st.shared.v4.b32 [%0], {%1,%2,%3,%4};" ::"r"(a), "r"(x), "r"(y), "r"(z), "r"(w) : "memory");
}
__device__ __forceinline__ uint32_t lds32(uint32_t a) { uint32_t v; asm volatile("ld.shared.b32 %0, [%1];" : "=r"(v) : "r"(a) : "memory"); return v; }
__device__ __forceinline__ uint4 lds128(uint32_t a) {
  uint4 v; asm volatile("ld.shared.v4.b32 {%0,%1,%2,%3}, [%4];" : "=r"(v.x), "=r"(v.y), "=r"(v.z), "=r"(v.w) : "r"(a) : "memory"); return v;
}
__device__ __forceinline__ uint4 ldg128(const void* a) {
  uint4 v; asm volatile("ld.global.nc.v4.b32 {%0,%1,%2,%3}, [%4];" : "=r"(v.x), "=r"(v.y), "=r"(v.z), "=r"(v.w) : "l"(a) : "memory"); return v;
}
__device__ __forceinline__ uint2 ldg64(const void* a) {
  uint2 v; asm volatile("ld.global.nc.v2.b32 {%0,%1}, [%2];" : "=r"(v.x), "=r"(v.y) : "l"(a) : "memory"); return v;
}
__device__ __forceinline__ void ldsm4(uint32_t a, uint32_t& r0, uint32_t& r1, uint32_t& r2, uint32_t& r3) {
  asm volatile("ldmatrix.sync.aligned.m8n8.x4.shared.b16 {%0,%1,%2,%3}, [%4];" : "=r"(r0), "=r"(r1), "=r"(r2), "=r"(r3) : "r"(a) : "memory");
}
__device__ __forceinline__ void ldsm4t(uint32_t a, uint32_t& r0, uint32_t& r1, uint32_t& r2, uint32_t& r3) {
  asm volatile("ldmatrix.sync.aligned.m8n8.x4.trans.shared.b16 {%0,%1,%2,%3}, [%4];" : "=r"(r0), "=r"(r1), "=r"(r2), "=r"(r3) : "r"(a) : "memory");
}
__device__ __forceinline__ void stsm4(uint32_t a, uint32_t r0, uint32_t r1, uint32_t r2, uint32_t r3) {
  asm volatile("stmatrix.sync.aligned.m8n8.x4.shared.b16 [%0], {%1,%2,%3,%4};" ::"r"(a), "r"(r0), "r"(r1), "r"(r2), "r"(r3) : "memory");
}
__device__ __forceinline__ void stsm4t(uint32_t a, uint32_t r0, uint32_t r1, uint32_t r2, uint32_t r3) {
  asm volatile("stmatrix.sync.aligned.m8n8.x4.trans.shared.b16 [%0], {%1,%2,%3,%4};" ::"r"(a), "r"(r0), "r"(r1), "r"(r2), "r"(r3) : "memory");
}
__device__ __forceinline__ void stsm2(uint32_t a, uint32_t r0, uint32_t r1) {
  asm volatile("stmatrix.sync.aligned.m8n8.x2.shared.b16 [%0], {%1,%2};" ::"r"(a), "r"(r0), "r"(r1) : "memory");
}
__device__ __forceinline__ void stsm2t(uint32_t a, uint32_t r0, uint32_t r1) {
  asm volatile("stmatrix.sync.aligned.m8n8.x2.trans.shared.b16 [%0], {%1,%2};" ::"r"(a), "r"(r0), "r"(r1) : "memory");
}
__device__ __forceinline__ void mma16816(float* c, uint32_t a0, uint32_t a1, uint32_t a2, uint32_t a3, uint32_t b0, uint32_t b1) {
  asm("mma.sync.aligned.m16n8k16.row.col.f32.bf16.bf16.f32 {%0,%1,%2,%3}, {%4,%5,%6,%7}, {%8,%9}, {%0,%1,%2,%3};"
      : "+f"(c[0]), "+f"(c[1]), "+f"(c[2]), "+f"(c[3]) : "r"(a0), "r"(a1), "r"(a2), "r"(a3), "r"(b0), "r"(b1));
}
__device__ __forceinline__ void bar_sync(int id, int n) { asm volatile("bar.sync %0, %1;" ::"r"(id), "r"(n) : "memory"); }
__device__ __forceinline__ void wg_fence() { asm volatile("wgmma.fence.sync.aligned;" ::: "memory"); }
__device__ __forceinline__ void wg_commit() { asm volatile("wgmma.commit_group.sync.aligned;" ::: "memory"); }
__device__ __forceinline__ void wg_wait0() { asm volatile("wgmma.wait_group.sync.aligned 0;" ::: "memory"); }
__device__ __forceinline__ void wg_wait1() { asm volatile("wgmma.wait_group.sync.aligned 1;" ::: "memory"); }
__device__ __forceinline__ void fence_async() { asm volatile("fence.proxy.async.shared::cta;" ::: "memory"); }
__device__ __forceinline__ uint32_t opq(uint32_t x, uint32_t z) { uint32_t r; asm volatile("xor.b32 %0, %1, %2;" : "=r"(r) : "r"(x), "r"(z)); return r; }
__device__ __forceinline__ float opqf(float x, uint32_t z) { float r; asm volatile("add.rn.f32 %0, %1, %2;" : "=f"(r) : "f"(x), "f"(__uint_as_float(z))); return r; }
__device__ __forceinline__ uint64_t mkdesc(uint32_t addr, uint32_t lbo, uint32_t sbo) {
  return (uint64_t)((addr & 0x3FFFF) >> 4) | ((uint64_t)(lbo >> 4) << 16) | ((uint64_t)(sbo >> 4) << 32);
}
__device__ __forceinline__ uint32_t mapa(uint32_t a, uint32_t rank) {
  uint32_t r; asm("mapa.shared::cluster.u32 %0, %1, %2;" : "=r"(r) : "r"(a), "r"(rank)); return r;
}
__device__ __forceinline__ void mbar_init_expect(uint32_t bar, uint32_t bytes) {
  asm volatile("mbarrier.init.shared::cta.b64 [%0], 1;" ::"r"(bar) : "memory");
  asm volatile("mbarrier.arrive.expect_tx.shared::cta.b64 _, [%0], %1;" ::"r"(bar), "r"(bytes) : "memory");
}
__device__ __forceinline__ void mbar_wait(uint32_t bar) {
#pragma unroll 1
  for (int it = 0; it < (1 << 22); it++) {
    uint32_t ok;
    asm volatile("{\n.reg .pred p;\nmbarrier.try_wait.parity.acquire.cluster.shared::cta.b64 p, [%1], 0;\nselp.u32 %0, 1, 0, p;\n}"
                 : "=r"(ok) : "r"(bar) : "memory");
    if (ok) return;
  }
  __trap();
}
__device__ __forceinline__ void st_async4(uint32_t a, uint32_t bar, uint32_t x, uint32_t y, uint32_t z, uint32_t w) {
  asm volatile("st.async.weak.shared::cluster.mbarrier::complete_tx::bytes.v4.b32 [%0], {%2,%3,%4,%5}, [%1];"
               ::"r"(a), "r"(bar), "r"(x), "r"(y), "r"(z), "r"(w) : "memory");
}

struct cf { float re, im; };
__device__ __forceinline__ cf cmul(cf a, cf b) { return {fmaf(a.re, b.re, -a.im * b.im), fmaf(a.re, b.im, a.im * b.re)}; }
__device__ __forceinline__ cf csq(cf a) { return {fmaf(a.re, a.re, -a.im * a.im), (a.re + a.re) * a.im}; }
__device__ __forceinline__ cf cexp_p(float xl, float y, float p) {
  float mag; asm("ex2.approx.ftz.f32 %0, %1;" : "=f"(mag) : "f"(xl * p));
  const float th = y * p;
  const float k = __fadd_rn(fmaf(th, 0.15915494309189535f, 12582912.f), -12582912.f);
  float r = fmaf(k, -6.2831854820251465f, th);
  r = fmaf(k, 1.7484555314695172e-07f, r);
  return {mag * __cosf(r), mag * __sinf(r)};
}
__device__ __forceinline__ uint32_t ysw(int c) { return (uint32_t)(c ^ ((c >> 3) & 3)) * 16u; }

#define CMUL2(OR, OI, xr, xi, yr, yi, nyi) do { OR = hfma2(xr, yr, hmul2(xi, nyi)); OI = hfma2(xr, yi, hmul2(xi, yr)); } while (0)

__device__ __forceinline__ uint32_t gate_slow(const __nv_bfloat16* u, const __nv_bfloat16* gw, int row) {
  float s = 0.f;
  const uint32_t* xr = (const uint32_t*)(u + (size_t)row * D);
  const uint32_t* wr = (const uint32_t*)gw;
#pragma unroll 1
  for (int j = 0; j < D / 2; j++) { const uint32_t pr = hmul2(xr[j], wr[j]); s += bf_lo(pr); s += bf_hi(pr); }
  s = bf_round(s);
  return pack_bf16(1.f / (1.f + expf(-s)), 0.f);
}

__device__ __forceinline__ uint2 gate_ld(int x) {
  uint2 gv;
  asm volatile("ld.relaxed.gpu.global.v2.u32 {%0,%1}, [%2];" : "=r"(gv.x), "=r"(gv.y) : "l"(g_gate + x * 2) : "memory");
  return gv;
}
__device__ __noinline__ uint32_t gate_poll(const Params* pp, int x, uint32_t tag) {
  uint2 gv;
#pragma unroll 1
  for (int spins = 0; spins < (1 << 16); spins++) {
    gv = gate_ld(x);
    if ((gv.x >> 16) == tag && (gv.y >> 16) == tag) return __byte_perm(gv.x, gv.y, 0x5410);
  }
  return __byte_perm(gate_slow(pp->u, pp->gw, x * 2), gate_slow(pp->u, pp->gw, x * 2 + 1), 0x5410);
}
__device__ __forceinline__ uint32_t gate_fin(const Params& p, uint2 gv, int x, uint32_t tag) {
  if ((gv.x >> 16) == tag && (gv.y >> 16) == tag) return __byte_perm(gv.x, gv.y, 0x5410);
  return gate_poll(&p, x, tag);
}

__device__ __forceinline__ void ld4ch(uint32_t* v, uint32_t addr) {
#pragma unroll
  for (int k = 0; k < 4; k++) v[k] = lds32(addr + k * CH_BYTES);
}
__device__ __forceinline__ void skip_terms(uint32_t* ua, uint32_t* ub, uint32_t sb, int x, uint2 dA, uint2 dB) {
  const int c = x >> 2;
  uint32_t uu[4];
  ld4ch(uu, sb + CH_OFF + (x & 3) * 4 + U_OFF + (c & 3) * U_CS + (63 - (c >> 2)) * 16);
#pragma unroll
  for (int k = 0; k < 4; k++) {
    ua[k] = hmul2(uu[k], __byte_perm((k & 2) ? dA.y : dA.x, 0, (k & 1) ? 0x3232 : 0x1010));
    ub[k] = hmul2(uu[k], __byte_perm((k & 2) ? dB.y : dB.x, 0, (k & 1) ? 0x3232 : 0x1010));
  }
}
__device__ __forceinline__ uint4 mix(const uint32_t* a, const uint32_t* b, const uint32_t* ua, const uint32_t* ub, uint32_t g2) {
  const uint32_t h2 = hsub2(0x3f803f80u, g2);
  uint32_t o[4];
#pragma unroll
  for (int k = 0; k < 4; k++) o[k] = hadd2(hmul2(g2, hadd2(a[k], ua[k])), hmul2(h2, hadd2(b[k], ub[k])));
  return make_uint4(__byte_perm(o[0], o[1], 0x5410), __byte_perm(o[2], o[3], 0x5410), __byte_perm(o[0], o[1], 0x7632), __byte_perm(o[2], o[3], 0x7632));
}
__device__ __forceinline__ void send_box(uint32_t sb, int slot, int wtid, uint32_t rank, uint4 r) {
  st_async4(mapa(sb + XIN_OFF + slot * 2048 + wtid * 16, rank ^ 1), mapa(sb + B_X + slot * 8, rank ^ 1), r.x, r.y, r.z, r.w);
}
__device__ __forceinline__ void merge_rows(uint32_t st, uint32_t rank, uint4 r, uint4 q) {
  const uint4 lo = rank ? q : r, hi = rank ? r : q;
  sts128(st, lo.x, lo.y, hi.x, hi.y); sts128(st + 2048, lo.z, lo.w, hi.z, hi.w);
}
__device__ __forceinline__ void merge_box(uint32_t sb, const CUtensorMap* tm_out, int slot, int wtid, uint32_t rank, int oc0, uint4 r, int barid) {
  const uint32_t st = sb + RAW_OFF + slot * 4096 + wtid * 16;
  mbar_wait(sb + B_X + slot * 8);
  merge_rows(st, rank, r, lds128(sb + XIN_OFF + slot * 2048 + wtid * 16));
  fence_async();
  bar_sync(barid, 128);
  if (wtid == 0) {
    asm volatile("cp.async.bulk.tensor.3d.global.shared::cta.bulk_group [%0, {%2, %3, %4}], [%1];"
                 ::"l"(tm_out), "r"(sb + RAW_OFF + slot * 4096), "r"(oc0), "r"((2 * slot + (int)rank) * 128), "r"(0) : "memory");
    asm volatile("cp.async.bulk.commit_group;" ::: "memory");
  }
}

__device__ __forceinline__ uint32_t band2(int e, int lo, int hi) {
  uint32_t r = ((uint32_t)(e - lo) <= (uint32_t)(hi - lo) ? 0x3f80u : 0u) | ((uint32_t)(e - 1 - lo) <= (uint32_t)(hi - lo) ? 0x3f800000u : 0u);
  asm volatile("" : "+r"(r));
  return r;
}

__device__ __forceinline__ void stage_done(uint32_t sb, int stage, int lane) {
  __syncwarp();
  if (lane == 0) asm volatile("mbarrier.arrive.shared::cta.b64 _, [%0];" ::"r"(sb + B_ST + 8 * stage) : "memory");
}
#define PK2(v, i) pack_bf16(v[i], v[(i) + 1])

__device__ __forceinline__ void conv_dense(uint32_t sb, uint32_t cb, uint32_t zz) {
  const int lane = threadIdx.x & 31, wq = (threadIdx.x >> 5) & 3, br = wq >> 1, hf = wq & 1, g = lane >> 2, t = lane & 3;
  const uint32_t rb = cb + R_OFF + br * R_BR;
  const int eo = 16 * hf + g - 2 * t;
  const int x0 = RD_X0 - (eo + 536);
  const uint32_t fa = rb + ((g & 1) ? 2 * x0 : RD_CS + 2 * x0 + 2);
  const uint64_t ub = mkdesc(cb + U_OFF, U_CS, 128);
  const uint32_t yd = cb + Y0_OFF + br * 4096 + ysw(4 * (63 - 8 * (lane >> 4) - (lane & 7)) + 2 * hf + ((lane >> 3) & 1));
  uint32_t A[2][4][4];
  float e64[32], e56[28], e48[24];
  auto loadA = [&](int j) {
#pragma unroll
    for (int k = 0; k < 4; k++) {
      const int s = 34 - 4 * j - k;
      if (s >= 0) {
        if (k == 0 && j == 0) A[0][0][2] = lds32(fa + (2 * s + 2) * 16);
        A[j & 1][k][0] = lds32(fa + (2 * s + 1) * 16);
        A[j & 1][k][1] = lds32(fa + (2 * s) * 16);
      }
    }
#pragma unroll
    for (int k = 0; k < 4; k++) {
      if (34 - 4 * j - k >= 0) {
        A[j & 1][k][3] = A[j & 1][k][0];
        if (k) A[j & 1][k][2] = A[j & 1][k - 1][1];
        else if (j) A[j & 1][0][2] = A[(j - 1) & 1][3][1];
      }
    }
  };
  loadA(0); loadA(1);
#pragma unroll
  for (int j = 0; j < 9; j++) {
    if (j == 4) {
      wg_wait0();
      stsm2t(yd - 7 * 512, PK2(e64, 28), PK2(e64, 30));
#pragma unroll
      for (int i = 0; i < 28; i++) e56[i] = FCPY(e64, i);
      stage_done(sb, 0, lane);
    }
    if (j == 8) {
      wg_wait0();
      stsm2t(yd - 6 * 512, PK2(e56, 24), PK2(e56, 26));
#pragma unroll
      for (int i = 0; i < 24; i++) e48[i] = FCPY(e56, i);
      stage_done(sb, 1, lane);
    }
    wg_fence();
#pragma unroll
    for (int k = 0; k < 4; k++) {
      const int s = 34 - 4 * j - k;
      if (s >= 0) {
        const int o = 2 * s - 66 + 128;
        const int cc = o & 3, rs = (o >> 2) - 32;
        const uint64_t desc = ub + (uint64_t)((cc * U_CS - rs * 16) >> 4);
        const uint32_t* a = A[j & 1][k];
        if (j < 4) wgmma_rs<64, 0>(e64, a[0], a[1], a[2], a[3], desc, s != 34);
        else if (j < 8) wgmma_rs<56, 0>(e56, a[0], a[1], a[2], a[3], desc, 1);
        else wgmma_rs<48, 0>(e48, a[0], a[1], a[2], a[3], desc, 1);
      }
    }
    wg_commit();
    if (j >= 1 && j < 8) { wg_wait1(); loadA(j + 1); }
  }
  wg_wait0();
#pragma unroll
  for (int i = 0; i < 6; i += 2) stsm4t(yd - i * 512, PK2(e48, 4 * i), PK2(e48, 4 * i + 2), PK2(e48, 4 * i + 4), PK2(e48, 4 * i + 6));
}

__device__ __noinline__ unsigned int gate_rows(const Params* pp, int grow, int step, int rend) {
  const __nv_bfloat16 *u = pp->u, *gw = pp->gw;
  const int lane = threadIdx.x & 31;
  uint4 gx[4][2], nx[4][2];
#pragma unroll
  for (int i = 0; i < 4; i++) {
    nx[i][0] = ldg128(u + (size_t)(grow + i) * D + lane * 8);
    nx[i][1] = ldg128(u + (size_t)(grow + i) * D + 256 + lane * 8);
  }
  const uint4 gw0 = ldg128(gw + lane * 8), gw1 = ldg128(gw + 256 + lane * 8);
  const uint32_t ws[8] = {gw0.x, gw0.y, gw0.z, gw0.w, gw1.x, gw1.y, gw1.z, gw1.w};
  unsigned int epoch;
  asm volatile("ld.relaxed.gpu.global.u32 %0, [%1];" : "=r"(epoch) : "l"(&g_epoch) : "memory");
#pragma unroll 1
  for (; grow < rend; grow += step) {
#pragma unroll
    for (int i = 0; i < 4; i++) { gx[i][0] = nx[i][0]; gx[i][1] = nx[i][1]; }
    if (grow + step < rend) {
#pragma unroll
      for (int i = 0; i < 4; i++) {
        nx[i][0] = ldg128(u + (size_t)(grow + step + i) * D + lane * 8);
        nx[i][1] = ldg128(u + (size_t)(grow + step + i) * D + 256 + lane * 8);
      }
    }
    float c[2][4];
#pragma unroll
    for (int i = 0; i < 2; i++) {
      const uint4 *x = gx[2 * i], *y = gx[2 * i + 1];
      const uint32_t xs[8] = {x[0].x, x[0].y, x[0].z, x[0].w, x[1].x, x[1].y, x[1].z, x[1].w};
      const uint32_t ys[8] = {y[0].x, y[0].y, y[0].z, y[0].w, y[1].x, y[1].y, y[1].z, y[1].w};
      c[i][0] = c[i][1] = c[i][2] = c[i][3] = 0.f;
#pragma unroll
      for (int j = 0; j < 8; j += 2)
        mma16816(c[i], hmul2(xs[j], ws[j]), hmul2(ys[j], ws[j]), hmul2(xs[j + 1], ws[j + 1]), hmul2(ys[j + 1], ws[j + 1]), 0x3f803f80u, 0x3f803f80u);
    }
    float s = (lane & 2) ? ((lane & 1) ? c[1][2] : c[1][0]) : ((lane & 1) ? c[0][2] : c[0][0]);
#pragma unroll
    for (int o = 4; o < 32; o <<= 1) s += __shfl_xor_sync(0xffffffffu, s, o);
    s = bf_round(s);
    const float gv = 1.f / (1.f + expf(-s));
    const uint32_t w = ((epoch + 1) << 16) | (pack_bf16(gv, 0.f) & 0xffffu);
    if (lane < 4) asm volatile("st.relaxed.gpu.global.u32 [%0], %1;" ::"l"(&g_gate[grow + lane]), "r"(w) : "memory");
  }
  return epoch;
}
#define GW 1
constexpr int GSPLIT = L - 4 * GW * NCTA;
__device__ __noinline__ void gate_cta(const Params* pp) {
  const unsigned int epoch = gate_rows(pp, (blockIdx.x * 20 + (threadIdx.x >> 5)) * 4, 80 * NGATE, GSPLIT);
  __syncthreads();
  if (threadIdx.x == 0 && atomicAdd(&g_ticket, 1u) == NCTA + NGATE - 1) { g_ticket = 0; g_epoch = epoch + 1; }
}

__global__ void __cluster_dims__(2, 1, 1) __launch_bounds__(640, 1)
ssm_kernel(const __grid_constant__ Params p, const __grid_constant__ CUtensorMap tm_in, const __grid_constant__ CUtensorMap tm_out) {
  extern __shared__ __align__(1024) unsigned char smem_raw[];
  const uint32_t sb = (uint32_t)__cvta_generic_to_shared(smem_raw);
  const int tid = threadIdx.x, lane = tid & 31;
  const int warp = __shfl_sync(0xffffffffu, tid >> 5, 0);
  const int ch = warp >> 2, wq = warp & 3, br = wq >> 1, hf = wq & 1;
  const int g = lane >> 2, t = lane & 3;
  if (__builtin_expect(blockIdx.x < NGATE, 0)) { gate_cta(&p); return; }
  const int bid = blockIdx.x - NGATE;
  const uint32_t rank = blockIdx.x & 1;
  const uint32_t cb = sb + CH_OFF + ch * CH_BYTES;
  const int wtid = tid & 127;
  const int oc0 = (bid >> 1) * 8;
  STAMP(0); GT(0);

  if (warp >= 16) {
    if (wtid == 0) {
      mbar_init_expect(sb + B_RAW, 32768);
#pragma unroll
      for (int i = 0; i < 4; i++) mbar_init_expect(sb + B_X + 8 * i, 2048);
      asm volatile("mbarrier.init.shared::cta.b64 [%0], 128;" ::"r"(sb + B_U) : "memory");
      asm volatile("mbarrier.init.shared::cta.b64 [%0], 128;" ::"r"(sb + B_W) : "memory");
#pragma unroll
      for (int i = 0; i < 7; i++) asm volatile("mbarrier.init.shared::cta.b64 [%0], 16;" ::"r"(sb + B_ST + 8 * i) : "memory");
      asm volatile("fence.mbarrier_init.release.cluster;" ::: "memory");
      asm volatile("fence.proxy.async.shared::cta;" ::: "memory");
    }
    __syncwarp();
    asm volatile("barrier.cluster.arrive.relaxed.aligned;" ::: "memory");
    if (wq >= 4 - GW) gate_rows(&p, GSPLIT + (bid * GW + 3 - wq) * 4, L, L);
    unsigned int epoch;
    asm volatile("ld.relaxed.gpu.global.u32 %0, [%1];" : "=r"(epoch) : "l"(&g_epoch) : "memory");
    asm volatile("barrier.cluster.wait.aligned;" ::: "memory");
    if (wtid == 0) {
      asm volatile("cp.async.bulk.tensor.5d.shared::cluster.global.mbarrier::complete_tx::bytes.multicast::cluster [%0], [%1, {%3, %4, %4, %4, %5}], [%2], %6;"
                   ::"r"(sb + RAW_OFF + rank * 16384), "l"(&tm_in), "r"(sb + B_RAW), "r"(oc0), "r"(0), "r"((int)rank * 32), "h"((unsigned short)3) : "memory");
    }
    sts128(sb + CH_OFF + wq * CH_BYTES + U_OFF + (lane >> 3) * U_CS + (64 + (lane & 7)) * 16, 0, 0, 0, 0);
    const uint2 dA = ldg64(p.A_D + bid * 4), dB = ldg64(p.B_D + bid * 4);
    uint32_t BA[3][4], BB[4][4];
    {
      const int l1 = br ? 3 : 6, h1 = br ? 5 : 10, l2 = br ? 5 : 12, h2 = br ? 11 : 20;
#pragma unroll
      for (int i = 0; i < 4; i++) {
        const int e = 16 * hf + g - 2 * t + 32 - 16 * i;
        BB[i][0] = band2(e, l2, h2); BB[i][1] = band2(e + 8, l2, h2); BB[i][2] = band2(e - 8, l2, h2); BB[i][3] = BB[i][0];
        if (i) { BA[i - 1][0] = band2(e, l1, h1); BA[i - 1][1] = band2(e + 8, l1, h1); BA[i - 1][2] = band2(e - 8, l1, h1); BA[i - 1][3] = BA[i - 1][0]; }
      }
    }
    const uint32_t tag = (epoch + 1) & 0xffffu;
    if (wtid == 0) sts32(sb + TAG_OFF, tag);
    STAMP(3);
    mbar_wait(sb + B_RAW);
    STAMP(4);
    {
      const uint32_t dst = sb + CH_OFF + (g & 3) * CH_BYTES + U_OFF + t * U_CS + (63 - wq * 16) * 16;
#pragma unroll
      for (int h = 0; h < 2; h++) {
        uint32_t r[8][4];
#pragma unroll
        for (int i = 0; i < 8; i++) ldsm4t(sb + RAW_OFF + (wq * 16 + h * 8 + i) * 512 + lane * 16, r[i][0], r[i][1], r[i][2], r[i][3]);
        if ((uint32_t)(g >> 2) == rank) {
#pragma unroll
          for (int i = 0; i < 8; i++) sts128(dst - (h * 8 + i) * 16, r[i][0], r[i][1], r[i][2], r[i][3]);
        }
      }
    }
    fence_async();
    asm volatile("mbarrier.arrive.shared::cta.b64 _, [%0];" ::"r"(sb + B_U) : "memory");
    bar_sync(5, 128);
    STAMP(5);
    {
      const int mrow = lane & 7, mi = lane >> 3;
      const uint64_t ub0 = mkdesc(sb + CH_OFF + U_OFF, U_CS, 128);
      uint32_t wa, wb;
      {
        const int c = 4 * (47 - 8 * (mi >> 1) - mrow) + 2 * hf + (mi & 1);
        wa = sb + CH_OFF + (br ? W3_OFF : W5_OFF) + (5 - (c >> 5)) * 576 + ((c & 31) >> 3) * 144 + (c & 7) * 16;
        const int c2 = c - 64, pp = c2 >> 1;
        wb = sb + CH_OFF + (br ? W7_OFF : W9_OFF) + (1 - (pp >> 5)) * 1152 + (c2 & 1) * 576 + ((pp & 31) >> 3) * 144 + (pp & 7) * 16;
      }
      {
        float w1[24];
#pragma unroll
        for (int i = 0; i < 24; i++) w1[i] = 0.f;
#pragma unroll 1
        for (int k = 0; k < 4; k++) {
          wg_fence();
#pragma unroll
          for (int i = 0; i < 3; i++)
            wgmma_rs<48, 0>(w1, BA[i][0], BA[i][1], BA[i][2], BA[i][3],
                            ub0 + (uint64_t)((k * CH_BYTES + ((2 * i + 2) & 3) * U_CS + (16 + (i == 0)) * 16) >> 4), i);
          wg_commit();
          wg_wait0();
#pragma unroll
          for (int i = 0; i < 3; i++) stsm4t(wa + k * CH_BYTES + i * 1152, PK2(w1, 8 * i), PK2(w1, 8 * i + 2), PK2(w1, 8 * i + 4), PK2(w1, 8 * i + 6));
        }
      }
      {
        float w2[2][16];
#pragma unroll
        for (int i = 0; i < 16; i++) { w2[0][i] = 0.f; w2[1][i] = 0.f; }
#pragma unroll 1
        for (int kp = 0; kp < 2; kp++) {
          wg_fence();
#pragma unroll
          for (int k = 0; k < 2; k++)
#pragma unroll
            for (int i = 0; i < 4; i++)
              wgmma_rs<32, 0>(w2[k], BB[i][0], BB[i][1], BB[i][2], BB[i][3],
                              ub0 + (uint64_t)(((2 * kp + k) * CH_BYTES + ((2 * i) & 3) * U_CS + (32 + (i < 2)) * 16) >> 4), i);
          wg_commit();
          wg_wait0();
#pragma unroll
          for (int k = 0; k < 2; k++)
#pragma unroll
            for (int i = 0; i < 2; i++)
              stsm4t(wb + (2 * kp + k) * CH_BYTES + i * 1152, PK2(w2[k], 8 * i), PK2(w2[k], 8 * i + 2), PK2(w2[k], 8 * i + 4), PK2(w2[k], 8 * i + 6));
        }
      }
    }
    fence_async();
    asm volatile("mbarrier.arrive.shared::cta.b64 _, [%0];" ::"r"(sb + B_W) : "memory");
    STAMP(7);
    {
      const int bsel = (int)rank ^ br ^ 1, xl = wtid & 63;
      uint2 gl[4];
      uint32_t ua[4][4], ub[4][4];
#pragma unroll
      for (int i = 0; i < 4; i++) skip_terms(ua[i], ub[i], sb, (2 * (i >> 1) + bsel) * 128 + (i & 1) * 64 + xl, dA, dB);
      const uint32_t yo = sb + CH_OFF + (xl & 3) * 4 + ysw(xl >> 2) + bsel * 512;
#pragma unroll
      for (int i = 0; i < 2; i++) gl[i] = gate_ld(bsel * 128 + i * 64 + xl);
#pragma unroll
      for (int slot = 0; slot < 2; slot++) {
        const int box = 2 * slot + bsel;
        uint32_t g2[2], ya[2][4], yb[2][4];
#pragma unroll
        for (int h = 0; h < 2; h++) g2[h] = gate_fin(p, gl[2 * slot + h], box * 128 + h * 64 + xl, tag);
        mbar_wait(sb + B_ST + 8 * box);
        STAMP(8 + slot);
        if (slot == 0) { gl[2] = gate_ld((2 + bsel) * 128 + xl); gl[3] = gate_ld((2 + bsel) * 128 + 64 + xl); }
#pragma unroll
        for (int h = 0; h < 2; h++) {
          const uint32_t yh = (yo ^ (h * 32)) + h * 256 + slot * 1024;
          ld4ch(ya[h], yh + Y0_OFF); ld4ch(yb[h], yh + Y0_OFF + 4096);
          if (slot) {
            uint32_t a2[4], b2[4];
            ld4ch(a2, yh + Y2_OFF - 1024); ld4ch(b2, yh + Y2_OFF - 1024 + 3072);
#pragma unroll
            for (int k = 0; k < 4; k++) { ya[h][k] = hadd2(ya[h][k], a2[k]); yb[h][k] = hadd2(yb[h][k], b2[k]); }
          }
        }
        const uint4 r0 = mix(ya[0], yb[0], ua[2 * slot], ub[2 * slot], g2[0]), r1 = mix(ya[1], yb[1], ua[2 * slot + 1], ub[2 * slot + 1], g2[1]);
        if (br == 0) { send_box(sb, slot, xl, rank, r0); send_box(sb, slot, xl + 64, rank, r1); }
        else {
          const uint32_t st = sb + RAW_OFF + slot * 4096 + xl * 16, xin = sb + XIN_OFF + slot * 2048 + xl * 16;
          mbar_wait(sb + B_X + slot * 8);
          const uint4 q0 = lds128(xin), q1 = lds128(xin + 1024);
          merge_rows(st, rank, r0, q0); merge_rows(st + 1024, rank, r1, q1);
          fence_async();
          bar_sync(6, 64);
          if (xl == 0) {
            asm volatile("cp.async.bulk.tensor.3d.global.shared::cta.bulk_group [%0, {%2, %3, %4}], [%1];"
                         ::"l"(&tm_out), "r"(sb + RAW_OFF + slot * 4096), "r"(oc0), "r"(box * 128), "r"(0) : "memory");
            asm volatile("cp.async.bulk.commit_group;" ::: "memory");
          }
        }
        STAMP(10 + slot);
      }
    }
    if (wtid == 0 && atomicAdd(&g_ticket, 1u) == NCTA + NGATE - 1) { g_ticket = 0; g_epoch = epoch + 1; }
    if (wtid == 64) asm volatile("cp.async.bulk.wait_group.read 0;" ::: "memory");
    STAMP(15);
    return;
  }
  asm volatile("barrier.cluster.arrive.relaxed.aligned;" ::: "memory");

  const int moff = (bid * 4 + (tid >> 7)) * NM + (tid & 63) * 2;
  const int brt = (tid >> 6) & 1;
  const __nv_bfloat16* const* tp = p.t + (brt ? 0 : 6);
  const uint32_t q0 = *(const uint32_t*)(tp[0] + moff), q1 = *(const uint32_t*)(tp[1] + moff);
  const uint32_t q2 = *(const uint32_t*)(tp[2] + moff), q3 = *(const uint32_t*)(tp[3] + moff);
  const uint2 ldt4 = *(const uint2*)(tp[4] + bid * 4);
  const uint32_t q4 = *(const uint32_t*)(tp[brt ? 2 : 5] + moff), q5 = *(const uint32_t*)(tp[brt ? 3 : 6] + moff);

  for (int i = wtid & 63; i < R_BR / 16; i += 64) sts128(cb + R_OFF + br * R_BR + i * 16, 0, 0, 0, 0);
  STAMP(1);

  float acc[5][4];
  float k2048 = 0.f;
  const uint32_t scr = cb + Y0_OFF + wq * SCR_BYTES;
  const uint32_t scr2 = sb + SC2_OFF + warp * 640;
  {
    const uint32_t ldt2 = (ch & 2) ? ldt4.y : ldt4.x;
    const float dt = bf_round(expf((ch & 1) ? bf_hi(ldt2) : bf_lo(ldt2)));
#pragma unroll
    for (int i = 0; i < 5; i++) acc[i][0] = acc[i][1] = acc[i][2] = acc[i][3] = 0.f;
    STAMP(2);
    const uint32_t tb = scr + lane * 16;
    const uint32_t ta = scr + (lane >> 3) * 512 + (lane & 7) * 16;
    const uint32_t tc = ((lane & 8) ? scr2 : scr + 4096) + (lane >> 4) * 128 + (lane & 7) * 16;
    const uint32_t tm = scr2 + 512 + ((lane >> 3) & 1) * 64 + (lane >> 4) * 16;
#pragma unroll 1
    for (int r = 0; r < 2; r++) {
      cf c, z1, z128;
      {
        const uint32_t sh = r ? 0x3244u : 0x1044u;
        float v0 = __uint_as_float(__byte_perm(q0, 0, sh));
        const float v1 = __uint_as_float(__byte_perm(q1, 0, sh)), v2 = __uint_as_float(__byte_perm(q2, 0, sh)), v3 = __uint_as_float(__byte_perm(q3, 0, sh));
        if (br == 0) { c = cmul(cf{v2, v3}, cf{dt * __uint_as_float(__byte_perm(q4, 0, sh)), dt * __uint_as_float(__byte_perm(q5, 0, sh))}); }
        else { v0 = -bf_round(expf(v0)); c = cf{2.f * dt * v2, 2.f * dt * v3}; }
        const float xl = (dt * v0) * 1.4426950408889634f, y = dt * v1;
        z1 = cexp_p(xl, y, 1.f); z128 = cexp_p(xl, y, 128.f);
      }
      const cf z2 = csq(z1), z4 = csq(z2), z8 = csq(z4);
      const cf w8 = {z8.re, -z8.im};
      const cf z16 = csq(w8), z24 = cmul(z16, w8), z32 = csq(z16), z40 = cmul(z32, w8), z48 = csq(z24), z56 = cmul(z32, z24), z64 = csq(z32);
      const cf z256 = csq(z128), z512 = csq(z256), z1024 = csq(z512), z2048 = csq(z1024);
      {
        float kk = fmaf(c.re, z2048.re, -c.im * z2048.im);
#pragma unroll
        for (int o = 16; o; o >>= 1) kk += __shfl_xor_sync(0xffffffffu, kk, o);
        k2048 += kk;
      }
      __syncwarp();
      {
        uint32_t xr[4] = {pack_bf16(1.f, z8.re), pack_bf16(z16.re, z24.re), pack_bf16(z32.re, z40.re), pack_bf16(z48.re, z56.re)};
        uint32_t xi[4] = {pack_bf16(0.f, w8.im), pack_bf16(z16.im, z24.im), pack_bf16(z32.im, z40.im), pack_bf16(z48.im, z56.im)};
        sts128(tb + 0 * 512, xr[0], xr[1], xr[2], xr[3]);
        sts128(tb + 2 * 512, xi[0], xi[1], xi[2], xi[3]);
        const uint32_t yr = pack_bf16(z64.re, z64.re), yi = pack_bf16(z64.im, z64.im), nyi = yi ^ 0x80008000u;
        uint32_t o[4], q[4];
#pragma unroll
        for (int i = 0; i < 4; i++) CMUL2(o[i], q[i], xr[i], xi[i], yr, yi, nyi);
        sts128(tb + 1 * 512, o[0], o[1], o[2], o[3]);
        sts128(tb + 3 * 512, q[0], q[1], q[2], q[3]);
      }
      {
        const cf h1 = cmul(c, z128), h2 = cmul(c, z256), h3 = cmul(h1, z256), h4 = cmul(c, z512), h5 = cmul(h1, z512), h6 = cmul(h2, z512), h7 = cmul(h3, z512);
        const cf e1 = cmul(c, z1), e2 = cmul(c, z2), e3 = cmul(e1, z2), e129 = cmul(h1, z1), e130 = cmul(h1, z2), e131 = cmul(e129, z2);
        const cf e258 = cmul(h2, z2), e386 = cmul(h3, z2);
        const uint32_t pr0 = pack_bf16(c.re, e1.re), pr2 = pack_bf16(h1.re, e129.re), pi0 = pack_bf16(c.im, e1.im), pi2 = pack_bf16(h1.im, e129.im);
        sts128(tb + 4 * 512, pr0, pack_bf16(e2.re, e3.re), pr2, pack_bf16(e130.re, e131.re));
        sts128(tb + 5 * 512, pi0, pack_bf16(e2.im, e3.im), pi2, pack_bf16(e130.im, e131.im));
        uint32_t xr[4] = {pack_bf16(h2.re, e258.re), pack_bf16(h3.re, e386.re), pack_bf16(h4.re, h5.re), pack_bf16(h6.re, h7.re)};
        uint32_t xi[4] = {pack_bf16(h2.im, e258.im), pack_bf16(h3.im, e386.im), pack_bf16(h4.im, h5.im), pack_bf16(h6.im, h7.im)};
        sts128(tb + 6 * 512, xr[0], xr[1], xr[2], xr[3]);
        sts128(tb + 7 * 512, xi[0], xi[1], xi[2], xi[3]);
        xr[1] = __byte_perm(xr[0], xr[1], 0x5410); xi[1] = __byte_perm(xi[0], xi[1], 0x5410);
        xr[0] = __byte_perm(pr0, pr2, 0x5410); xi[0] = __byte_perm(pi0, pi2, 0x5410);
        const uint32_t yr = pack_bf16(z1024.re, z1024.re), yi = pack_bf16(z1024.im, z1024.im), nyi = yi ^ 0x80008000u;
        uint32_t o[4], q[4];
#pragma unroll
        for (int i = 0; i < 4; i++) CMUL2(o[i], q[i], xr[i], xi[i], yr, yi, nyi);
        sts128(tb + 8 * 512, o[0], o[1], o[2], o[3]);
        sts128(scr2 + lane * 16, q[0], q[1], q[2], q[3]);
        const uint32_t m4 = pack_bf16(z4.re, z4.im);
        sts16(scr2 + 512 + lane * 2, m4); sts16(scr2 + 576 + lane * 2, m4 >> 16);
      }
      __syncwarp();
#pragma unroll
      for (int kp = 0; kp < 2; kp++) {
        uint32_t rr[2], ri[2], yr[2], yi[2];
        ldsm4t(tc + kp * 256, rr[0], ri[0], rr[1], ri[1]);
        ldsm4(tm + kp * 32, yr[0], yi[0], yr[1], yi[1]);
#pragma unroll
        for (int k2 = 0; k2 < 2; k2++) {
          const int kk = kp * 2 + k2;
          uint32_t a0, a1, a2, a3, pr, pi, qr, qi, xr, xi;
          ldsm4t(ta + kk * 128, a0, a1, a2, a3);
          ldsm4t(ta + 2048 + kk * 128, pr, pi, qr, qi);
          const uint32_t nyi = yi[k2] ^ 0x80008000u;
          mma16816(acc[0], a0, a1, a2, a3, pr, pi);
          mma16816(acc[2], a0, a1, a2, a3, qr, qi);
          mma16816(acc[4], a0, a1, a2, a3, rr[k2], ri[k2]);
          CMUL2(xr, xi, pr, pi, yr[k2], yi[k2], nyi);
          mma16816(acc[1], a0, a1, a2, a3, xr, xi);
          CMUL2(xr, xi, qr, qi, yr[k2], yi[k2], nyi);
          mma16816(acc[3], a0, a1, a2, a3, xr, xi);
        }
      }
    }
  }
  STAMP(3);
  __syncwarp();
  {
    const uint32_t xs = scr + lane * 16;
#define OTH(i, k) __float_as_uint(hf ? acc[i][k] : acc[i][2 + (k)])
    sts128(xs, OTH(0, 0), OTH(0, 1), OTH(1, 0), OTH(1, 1));
    sts128(xs + 512, OTH(2, 0), OTH(2, 1), OTH(3, 0), OTH(3, 1));
    sts128(xs + 1024, OTH(4, 0), OTH(4, 1), __float_as_uint(k2048), 0);
#undef OTH
  }

  bar_sync(7 + (warp >> 1), 64);
  STAMP(4);
  {
    const uint32_t xo = cb + Y0_OFF + (wq ^ 1) * SCR_BYTES + lane * 16;
    const uint4 o0 = lds128(xo), o1 = lds128(xo + 512), o2 = lds128(xo + 1024);
    const uint32_t rb = cb + R_OFF + br * R_BR;
#define OWN(i, k) (hf ? acc[i][2 + (k)] : acc[i][k])
    const uint32_t vP = pack_bf16(OWN(0, 1) + __uint_as_float(o0.y), OWN(0, 0) + __uint_as_float(o0.x));
    const uint32_t vP4 = pack_bf16(OWN(1, 1) + __uint_as_float(o0.w), OWN(1, 0) + __uint_as_float(o0.z));
    const uint32_t vQ = pack_bf16(OWN(2, 1) + __uint_as_float(o1.y), OWN(2, 0) + __uint_as_float(o1.x));
    const uint32_t vQ4 = pack_bf16(OWN(3, 1) + __uint_as_float(o1.w), OWN(3, 0) + __uint_as_float(o1.z));
    const uint32_t vR = pack_bf16(OWN(4, 1) + __uint_as_float(o2.y), OWN(4, 0) + __uint_as_float(o2.x));
#undef OWN
    const int j = g + 8 * hf;
    {
      const int a = 2 * (t & 1) + 64 * (t & 2) + 8 * j;
      const uint32_t ad = rb + 2 * (RD_X0 - 1 - a);
      const uint32_t a1 = (t & 2) ? ad - 8 : ad, a2 = (t & 2) ? ad : ad - 8;
      const uint32_t w1 = (t & 2) ? vP4 : vP, w2 = (t & 2) ? vP : vP4;
      sts32(a1, w1); sts32(a2, w2);
      sts16(a1 + RD_CS + 2, w1); sts16(a1 + RD_CS + 4, w1 >> 16);
      sts16(a2 + RD_CS + 2, w2); sts16(a2 + RD_CS + 4, w2 >> 16);
    }
    if (t < 2) {
      const int b = 256 + 128 * t + 8 * j;
      const uint32_t ad = rb + 2 * (RD_X0 - 6 - b);
      const uint32_t v22 = __byte_perm(vQ4, 0, 0x3232), v00 = __byte_perm(vQ, 0, 0x3232);
      sts16(ad, vQ4);
      sts64(ad + 2, v22, __byte_perm(vQ4, vQ, 0x5432));
      sts32(ad + 10, v00);
      if (b != 256) { sts16(ad + 14, v00); sts128(ad + RD_CS + 2, vQ4, v22, vQ, v00); }
      else { sts64(ad + RD_CS + 2, vQ4, v22); sts32(ad + RD_CS + 10, vQ); sts16(ad + RD_CS + 14, v00); }
    } else {
      const uint32_t ao = rb + R_O2 + 2 * (159 - (32 * t + j)), ae = ao - (R_O2 - R_E2) + 2;
      sts16(ao, vQ4 >> 16); sts16(ao + RS_CS + 2, vQ4 >> 16); sts16(ao - 32, vQ4); sts16(ao - 32 + RS_CS + 2, vQ4);
      sts16(ae - 32, vQ); sts16(ae - 32 + RS_CS + 2, vQ);
      if (lane != 2 || hf) { sts16(ae, vQ >> 16); sts16(ae + RS_CS + 2, vQ >> 16); }
      else {
        const uint32_t vv = __byte_perm(vQ, 0, 0x3232), ad = rb + 2 * (RD_X0 - 514);
        sts16(ad, vv); sts32(ad + 2, vv); sts16(ad + 6, vv); sts64(ad + RD_CS + 2, vv, vv);
      }
    }
    {
      const uint32_t a = rb + ((g & 1) ? R_O3 : R_E3 + 2) + 2 * (159 - (64 + 16 * t + (j >> 1)));
      const bool p1024 = (lane == 0) && (hf == 0);
      const uint32_t a00 = p1024 ? rb + R_E2 + 2 * (159 - 127) : a;
      sts16(a00, vR >> 16); sts16(a00 + RS_CS + 2, vR >> 16);
      sts16(a - 16, vR); sts16(a - 16 + RS_CS + 2, vR);
      if (p1024) {
        sts32(sb + K1024_OFF + (ch * 2 + br) * 4, __byte_perm(vR, 0, 0x3232));
        const uint32_t kv = pack_bf16(k2048 + __uint_as_float(o2.z), 0.f);
        sts16(rb + R_E3 + 2 * (159 - 127), kv); sts16(rb + R_E3 + 2 * (159 - 127) + RS_CS + 2, kv);
      }
    }
  }
  STAMP(5);
  asm volatile("barrier.cluster.wait.aligned;" ::: "memory");
  bar_sync(7 + (warp >> 1), 64);
  mbar_wait(sb + B_U);
  STAMP(6);

  const uint32_t zz = lds32(cb + R_OFF + br * R_BR);
  conv_dense(sb, cb, zz);
  STAMP(8);
  {
    const int x = (4 + ch) * 128 + wtid, c = x >> 2;
    const uint2 dA = ldg64(p.A_D + bid * 4), dB = ldg64(p.B_D + bid * 4);
    const uint2 gl = gate_ld(x);
    const uint32_t rb = cb + R_OFF + br * R_BR;
    float e48[24], e40[20], e32[16], h32[16], h16[8];
    const int x1 = 159 - (16 * hf + g - 2 * t + 136);
    const uint32_t fs = rb + ((g & 1) ? 2 * x1 : RS_CS + 2 * x1 + 2);
    uint32_t A[2][4][4];
    auto loadA = [&](int buf, uint32_t oe, uint32_t oo, int i0) {
#pragma unroll
      for (int a = 0; a < 2; a++) {
        const uint32_t base = fs + (a ? oo : oe) + i0 * 16;
        uint32_t* k0 = A[buf][2 * a];
        uint32_t* k1 = A[buf][2 * a + 1];
        k0[1] = lds32(base); k0[0] = lds32(base + 16); k0[2] = lds32(base + 32); k1[0] = lds32(base + 48); k1[2] = lds32(base + 64);
        k0[3] = k0[0]; k1[1] = k0[2]; k1[3] = k1[0];
      }
    };
    loadA(0, R_E2, R_O2, 8);
    loadA(1, R_E2, R_O2, 4);
    mbar_wait(sb + B_W);
    const uint64_t d5 = mkdesc(cb + W5_OFF, 144, 576), d3 = mkdesc(cb + W3_OFF, 144, 576);
    const uint64_t d9 = mkdesc(cb + W9_OFF, 144, 576), d7 = mkdesc(cb + W7_OFF, 144, 576);
    const uint32_t y2d = cb + Y2_OFF + br * 3072 + ysw(32 * (5 - (lane >> 4)) + 16 * hf + (lane & 15));
    const uint32_t y3d = cb + Y3_OFF + br * 2048 + ysw(2 * (16 * hf + (lane & 15)) + (lane >> 4));
#define FAR4(N, ACC, BUF, DA, DB, OFF, FIRST)                                                            \
    wg_fence();                                                                                           \
    _Pragma("unroll") for (int k = 0; k < 4; k++) {                                                      \
      const uint32_t* a = A[BUF][k];                                                                      \
      wgmma_rs<N, 1>(ACC, a[0], a[1], a[2], a[3], ((k >> 1) ? DB : DA) + (k & 1) * 18 + (OFF), !(FIRST) || k); \
    }                                                                                                     \
    wg_commit();
    FAR4(48, e48, 0, d5, d3, 0, 1)
    wg_wait0();
    loadA(0, R_E2, R_O2, 0);
    stsm2(y2d - 5 * 512, PK2(e48, 20), PK2(e48, 22));
#pragma unroll
    for (int i = 0; i < 20; i++) e40[i] = FCPY(e48, i);
    stage_done(sb, 2, lane);
    FAR4(40, e40, 1, d5, d3, 36, 0)
    wg_wait0();
    loadA(1, R_E3, R_O3, 8);
    stsm2(y2d - 4 * 512, PK2(e40, 16), PK2(e40, 18));
#pragma unroll
    for (int i = 0; i < 16; i++) e32[i] = FCPY(e40, i);
    stage_done(sb, 3, lane);
    FAR4(32, e32, 0, d5, d3, 72, 0)
    FAR4(32, h32, 1, d9, d7, 0, 1)
    wg_wait1();
    loadA(0, R_E3, R_O3, 4);
    stsm4(y2d, PK2(e32, 0), PK2(e32, 2), PK2(e32, 4), PK2(e32, 6));
    stsm4(y2d - 2 * 512, PK2(e32, 8), PK2(e32, 10), PK2(e32, 12), PK2(e32, 14));
    stage_done(sb, 4, lane);
    STAMP(9);
    wg_wait0();
    stsm4(y3d, PK2(h32, 8), PK2(h32, 10), PK2(h32, 12), PK2(h32, 14));
#pragma unroll
    for (int i = 0; i < 8; i++) h16[i] = FCPY(h32, i);
    stage_done(sb, 5, lane);
    FAR4(16, h16, 0, d9, d7, 72, 0)
#undef FAR4
    const uint32_t yo = sb + CH_OFF + (x & 3) * 4 + ysw(c);
    uint32_t ua[4], ub[4], ya[4], yb[4], a2[4], b2[4], a3[4], b3[4], s2[4];
    skip_terms(ua, ub, sb, x, dA, dB);
    {
      const int xa = x - 514, xb = x - 513, ca = xa >> 2, cb2 = xb >> 2;
      ld4ch(s2, sb + CH_OFF + U_OFF + (xa & 3) * 4 + (ca & 3) * U_CS + (63 - (ca >> 2)) * 16);
      ld4ch(a3, sb + CH_OFF + U_OFF + (xb & 3) * 4 + (cb2 & 3) * U_CS + (63 - (cb2 >> 2)) * 16);
#pragma unroll
      for (int k = 0; k < 4; k++) s2[k] = hadd2(s2[k], __byte_perm(s2[k], a3[k], 0x5432));
    }
    const uint32_t tag = lds32(sb + TAG_OFF);
    wg_wait0();
    stsm4(y3d + 1024, PK2(h16, 0), PK2(h16, 2), PK2(h16, 4), PK2(h16, 6));
    stage_done(sb, 6, lane);
    STAMP(10);
    const uint32_t g2 = gate_fin(p, gl, x, tag);
    mbar_wait(sb + B_ST + 8 * 4);
    const uint4 k0 = lds128(sb + K1024_OFF), k1 = lds128(sb + K1024_OFF + 16);
    const uint32_t kk[8] = {k0.x, k0.y, k0.z, k0.w, k1.x, k1.y, k1.z, k1.w};
    ld4ch(ya, yo + Y0_OFF); ld4ch(yb, yo + Y0_OFF + 4096);
    ld4ch(a2, yo + Y2_OFF - 1024); ld4ch(b2, yo + Y2_OFF - 1024 + 3072);
    mbar_wait(sb + B_ST + 8 * (5 + (ch >> 1)));
    STAMP(12);
    ld4ch(a3, yo + Y3_OFF - 2048); ld4ch(b3, yo + Y3_OFF - 2048 + 2048);
#pragma unroll
    for (int k = 0; k < 4; k++) {
      ya[k] = hadd2(ya[k], hadd2(hfma2(kk[2 * k], s2[k], a2[k]), a3[k]));
      yb[k] = hadd2(yb[k], hadd2(hfma2(kk[2 * k + 1], s2[k], b2[k]), b3[k]));
    }
    const uint4 r = mix(ya, yb, ua, ub, g2);
    if ((uint32_t)(ch & 1) != rank) send_box(sb, 2 + (ch >> 1), wtid, rank, r);
    else merge_box(sb, &tm_out, 2 + (ch >> 1), wtid, rank, oc0, r, 1 + ch);
  }
  STAMP(14);
  if (wtid == 0) asm volatile("cp.async.bulk.wait_group.read 0;" ::: "memory");
  STAMP(15); GT(1);
}

typedef CUresult (*EncodeFn)(CUtensorMap*, CUtensorMapDataType, cuuint32_t, void*, const cuuint64_t*, const cuuint64_t*,
                             const cuuint32_t*, const cuuint32_t*, CUtensorMapInterleave, CUtensorMapSwizzle,
                             CUtensorMapL2promotion, CUtensorMapFloatOOBfill);

}

extern "C" void kernel_launch(void* const* d_in, const int* in_sizes, int n_in, void* d_out, int out_size) {
  (void)in_sizes; (void)n_in; (void)out_size;
  typedef const __nv_bfloat16* bp;
  Params p;
  p.t[0] = (bp)d_in[10]; p.t[1] = (bp)d_in[11]; p.t[2] = (bp)d_in[12]; p.t[3] = (bp)d_in[13]; p.t[4] = (bp)d_in[14]; p.t[5] = nullptr;
  p.t[6] = (bp)d_in[1]; p.t[7] = (bp)d_in[2]; p.t[8] = (bp)d_in[5]; p.t[9] = (bp)d_in[6]; p.t[10] = (bp)d_in[7];
  p.t[11] = (bp)d_in[3]; p.t[12] = (bp)d_in[4]; p.t[13] = nullptr;
  p.u = (bp)d_in[0]; p.gw = (bp)d_in[16]; p.A_D = (bp)d_in[8]; p.B_D = (bp)d_in[15];
  static EncodeFn enc = nullptr;
  if (!enc) {
    cudaDriverEntryPointQueryResult qr;
    cudaGetDriverEntryPoint("cuTensorMapEncodeTiled", (void**)&enc, cudaEnableDefault, &qr);
    cudaFuncSetAttribute(ssm_kernel, cudaFuncAttributeMaxDynamicSharedMemorySize, SMEM_BYTES);
  }
  CUtensorMap tm_in, tm_out;
  {
    cuuint64_t gd[5] = {512, 2, 4, 4, 64};
    cuuint64_t gs[4] = {1024, 8192, 2048, 32768};
    cuuint32_t bx[5] = {8, 2, 4, 4, 32};
    cuuint32_t es[5] = {1, 1, 1, 1, 1};
    enc(&tm_in, CU_TENSOR_MAP_DATA_TYPE_BFLOAT16, 5, d_in[0], gd, gs, bx, es, CU_TENSOR_MAP_INTERLEAVE_NONE,
        CU_TENSOR_MAP_SWIZZLE_NONE, CU_TENSOR_MAP_L2_PROMOTION_NONE, CU_TENSOR_MAP_FLOAT_OOB_FILL_NONE);
  }
  {
    cuuint64_t gd[3] = {512, 1024, 2};
    cuuint64_t gs[2] = {2048, 1024};
    cuuint32_t bx[3] = {8, 128, 2};
    cuuint32_t es[3] = {1, 1, 1};
    enc(&tm_out, CU_TENSOR_MAP_DATA_TYPE_BFLOAT16, 3, d_out, gd, gs, bx, es, CU_TENSOR_MAP_INTERLEAVE_NONE,
        CU_TENSOR_MAP_SWIZZLE_NONE, CU_TENSOR_MAP_L2_PROMOTION_NONE, CU_TENSOR_MAP_FLOAT_OOB_FILL_NONE);
  }
  ssm_kernel<<<NCTA + NGATE, 640, SMEM_BYTES, cudaStreamPerThread>>>(p, tm_in, tm_out);
}
```

```cpp
#include <cuda_runtime.h>
#include <cuda.h>
#include <cuda_bf16.h>
#include <stdint.h>

namespace {
#define FCPY(v, i) (((i) % 3 == 2) ? __uint_as_float(opq(__float_as_uint(v[i]), zz)) : opqf(v[i], zz))

constexpr int L = 2048, D = 512, NM = 128;
constexpr int NCTA = 128;
constexpr int NGATE = 4;

constexpr int RAW_OFF = 0;
constexpr int XIN_OFF = 32768;
constexpr int SC2_OFF = XIN_OFF + 8192;
constexpr int BAR_OFF = SC2_OFF + 10240;
constexpr int CH_OFF = BAR_OFF + 256;
constexpr int U_CS = 1184;
constexpr int U_OFF = 0;
constexpr int R_OFF = 4736;
constexpr int RD_X0 = 565;
constexpr int RD_CS = 1216;
constexpr int RS_CS = 320;
constexpr int R_E2 = 2 * RD_CS, R_O2 = R_E2 + 2 * RS_CS, R_E3 = R_O2 + 2 * RS_CS, R_O3 = R_E3 + 2 * RS_CS;
constexpr int R_BR = R_O3 + 2 * RS_CS;
constexpr int W5_OFF = R_OFF + 2 * R_BR;
constexpr int W3_OFF = W5_OFF + 3456;
constexpr int W9_OFF = W3_OFF + 3456;
constexpr int W7_OFF = W9_OFF + 2304;
constexpr int Y0_OFF = W7_OFF + 2304;
constexpr int Y2_OFF = Y0_OFF + 8192, Y3_OFF = Y2_OFF + 6144;
constexpr int CH_BYTES = Y0_OFF + 18432 + 16;
constexpr int SCR_BYTES = 4608;
constexpr int SMEM_BYTES = CH_OFF + 4 * CH_BYTES;
static_assert(CH_BYTES % 128 == 16, "bank staggering of the channel blocks");
static_assert(SMEM_BYTES <= 232448, "smem");
constexpr int B_RAW = BAR_OFF + 160, B_X = BAR_OFF + 8, B_U = BAR_OFF + 40, B_W = BAR_OFF + 48;
constexpr int TAG_OFF = BAR_OFF + 56;
constexpr int K1024_OFF = BAR_OFF + 64;
constexpr int B_ST = BAR_OFF + 96;

__device__ unsigned int g_gate[L];
__device__ unsigned int g_epoch;
__device__ unsigned int g_ticket;

#define STAMP(k)
#define GT(k)

struct Params {
  const __nv_bfloat16* t[14];
  const __nv_bfloat16 *u, *gw, *A_D, *B_D;
};

template <int N, int TB> __device__ __forceinline__ void wgmma_rs(float* d, uint32_t a0, uint32_t a1, uint32_t a2, uint32_t a3, uint64_t desc, int sc);
template <> __device__ __forceinline__ void wgmma_rs<64, 0>(float* d, uint32_t a0, uint32_t a1, uint32_t a2, uint32_t a3, uint64_t desc, int sc) {
  asm volatile("{\n.reg .pred p;\nsetp.ne.b32 p, %37, 0;\n"
    "wgmma.mma_async.sync.aligned.m64n64k16.f32.bf16.bf16 {%0,%1,%2,%3,%4,%5,%6,%7,%8,%9,%10,%11,%12,%13,%14,%15,%16,%17,%18,%19,%20,%21,%22,%23,%24,%25,%26,%27,%28,%29,%30,%31}, {%32,%33,%34,%35}, %36, p, 1, 1, 0;\n}"
    : "+f"(d[0]), "+f"(d[1]), "+f"(d[2]), "+f"(d[3]), "+f"(d[4]), "+f"(d[5]), "+f"(d[6]), "+f"(d[7]), "+f"(d[8]), "+f"(d[9]), "+f"(d[10]), "+f"(d[11]), "+f"(d[12]), "+f"(d[13]), "+f"(d[14]), "+f"(d[15]), "+f"(d[16]), "+f"(d[17]), "+f"(d[18]), "+f"(d[19]), "+f"(d[20]), "+f"(d[21]), "+f"(d[22]), "+f"(d[23]), "+f"(d[24]), "+f"(d[25]), "+f"(d[26]), "+f"(d[27]), "+f"(d[28]), "+f"(d[29]), "+f"(d[30]), "+f"(d[31]) : "r"(a0), "r"(a1), "r"(a2), "r"(a3), "l"(desc), "r"(sc));
}
template <> __device__ __forceinline__ void wgmma_rs<56, 0>(float* d, uint32_t a0, uint32_t a1, uint32_t a2, uint32_t a3, uint64_t desc, int sc) {
  asm volatile("{\n.reg .pred p;\nsetp.ne.b32 p, %33, 0;\n"
    "wgmma.mma_async.sync.aligned.m64n56k16.f32.bf16.bf16 {%0,%1,%2,%3,%4,%5,%6,%7,%8,%9,%10,%11,%12,%13,%14,%15,%16,%17,%18,%19,%20,%21,%22,%23,%24,%25,%26,%27}, {%28,%29,%30,%31}, %32, p, 1, 1, 0;\n}"
    : "+f"(d[0]), "+f"(d[1]), "+f"(d[2]), "+f"(d[3]), "+f"(d[4]), "+f"(d[5]), "+f"(d[6]), "+f"(d[7]), "+f"(d[8]), "+f"(d[9]), "+f"(d[10]), "+f"(d[11]), "+f"(d[12]), "+f"(d[13]), "+f"(d[14]), "+f"(d[15]), "+f"(d[16]), "+f"(d[17]), "+f"(d[18]), "+f"(d[19]), "+f"(d[20]), "+f"(d[21]), "+f"(d[22]), "+f"(d[23]), "+f"(d[24]), "+f"(d[25]), "+f"(d[26]), "+f"(d[27]) : "r"(a0), "r"(a1), "r"(a2), "r"(a3), "l"(desc), "r"(sc));
}
template <> __device__ __forceinline__ void wgmma_rs<48, 0>(float* d, uint32_t a0, uint32_t a1, uint32_t a2, uint32_t a3, uint64_t desc, int sc) {
  asm volatile("{\n.reg .pred p;\nsetp.ne.b32 p, %29, 0;\n"
    "wgmma.mma_async.sync.aligned.m64n48k16.f32.bf16.bf16 {%0,%1,%2,%3,%4,%5,%6,%7,%8,%9,%10,%11,%12,%13,%14,%15,%16,%17,%18,%19,%20,%21,%22,%23}, {%24,%25,%26,%27}, %28, p, 1, 1, 0;\n}"
    : "+f"(d[0]), "+f"(d[1]), "+f"(d[2]), "+f"(d[3]), "+f"(d[4]), "+f"(d[5]), "+f"(d[6]), "+f"(d[7]), "+f"(d[8]), "+f"(d[9]), "+f"(d[10]), "+f"(d[11]), "+f"(d[12]), "+f"(d[13]), "+f"(d[14]), "+f"(d[15]), "+f"(d[16]), "+f"(d[17]), "+f"(d[18]), "+f"(d[19]), "+f"(d[20]), "+f"(d[21]), "+f"(d[22]), "+f"(d[23]) : "r"(a0), "r"(a1), "r"(a2), "r"(a3), "l"(desc), "r"(sc));
}
template <> __device__ __forceinline__ void wgmma_rs<32, 0>(float* d, uint32_t a0, uint32_t a1, uint32_t a2, uint32_t a3, uint64_t desc, int sc) {
  asm volatile("{\n.reg .pred p;\nsetp.ne.b32 p, %21, 0;\n"
    "wgmma.mma_async.sync.aligned.m64n32k16.f32.bf16.bf16 {%0,%1,%2,%3,%4,%5,%6,%7,%8,%9,%10,%11,%12,%13,%14,%15}, {%16,%17,%18,%19}, %20, p, 1, 1, 0;\n}"
    : "+f"(d[0]), "+f"(d[1]), "+f"(d[2]), "+f"(d[3]), "+f"(d[4]), "+f"(d[5]), "+f"(d[6]), "+f"(d[7]), "+f"(d[8]), "+f"(d[9]), "+f"(d[10]), "+f"(d[11]), "+f"(d[12]), "+f"(d[13]), "+f"(d[14]), "+f"(d[15]) : "r"(a0), "r"(a1), "r"(a2), "r"(a3), "l"(desc), "r"(sc));
}
template <> __device__ __forceinline__ void wgmma_rs<48, 1>(float* d, uint32_t a0, uint32_t a1, uint32_t a2, uint32_t a3, uint64_t desc, int sc) {
  asm volatile("{\n.reg .pred p;\nsetp.ne.b32 p, %29, 0;\n"
    "wgmma.mma_async.sync.aligned.m64n48k16.f32.bf16.bf16 {%0,%1,%2,%3,%4,%5,%6,%7,%8,%9,%10,%11,%12,%13,%14,%15,%16,%17,%18,%19,%20,%21,%22,%23}, {%24,%25,%26,%27}, %28, p, 1, 1, 1;\n}"
    : "+f"(d[0]), "+f"(d[1]), "+f"(d[2]), "+f"(d[3]), "+f"(d[4]), "+f"(d[5]), "+f"(d[6]), "+f"(d[7]), "+f"(d[8]), "+f"(d[9]), "+f"(d[10]), "+f"(d[11]), "+f"(d[12]), "+f"(d[13]), "+f"(d[14]), "+f"(d[15]), "+f"(d[16]), "+f"(d[17]), "+f"(d[18]), "+f"(d[19]), "+f"(d[20]), "+f"(d[21]), "+f"(d[22]), "+f"(d[23]) : "r"(a0), "r"(a1), "r"(a2), "r"(a3), "l"(desc), "r"(sc));
}
template <> __device__ __forceinline__ void wgmma_rs<40, 1>(float* d, uint32_t a0, uint32_t a1, uint32_t a2, uint32_t a3, uint64_t desc, int sc) {
  asm volatile("{\n.reg .pred p;\nsetp.ne.b32 p, %25, 0;\n"
    "wgmma.mma_async.sync.aligned.m64n40k16.f32.bf16.bf16 {%0,%1,%2,%3,%4,%5,%6,%7,%8,%9,%10,%11,%12,%13,%14,%15,%16,%17,%18,%19}, {%20,%21,%22,%23}, %24, p, 1, 1, 1;\n}"
    : "+f"(d[0]), "+f"(d[1]), "+f"(d[2]), "+f"(d[3]), "+f"(d[4]), "+f"(d[5]), "+f"(d[6]), "+f"(d[7]), "+f"(d[8]), "+f"(d[9]), "+f"(d[10]), "+f"(d[11]), "+f"(d[12]), "+f"(d[13]), "+f"(d[14]), "+f"(d[15]), "+f"(d[16]), "+f"(d[17]), "+f"(d[18]), "+f"(d[19]) : "r"(a0), "r"(a1), "r"(a2), "r"(a3), "l"(desc), "r"(sc));
}
template <> __device__ __forceinline__ void wgmma_rs<32, 1>(float* d, uint32_t a0, uint32_t a1, uint32_t a2, uint32_t a3, uint64_t desc, int sc) {
  asm volatile("{\n.reg .pred p;\nsetp.ne.b32 p, %21, 0;\n"
    "wgmma.mma_async.sync.aligned.m64n32k16.f32.bf16.bf16 {%0,%1,%2,%3,%4,%5,%6,%7,%8,%9,%10,%11,%12,%13,%14,%15}, {%16,%17,%18,%19}, %20, p, 1, 1, 1;\n}"
    : "+f"(d[0]), "+f"(d[1]), "+f"(d[2]), "+f"(d[3]), "+f"(d[4]), "+f"(d[5]), "+f"(d[6]), "+f"(d[7]), "+f"(d[8]), "+f"(d[9]), "+f"(d[10]), "+f"(d[11]), "+f"(d[12]), "+f"(d[13]), "+f"(d[14]), "+f"(d[15]) : "r"(a0), "r"(a1), "r"(a2), "r"(a3), "l"(desc), "r"(sc));
}
template <> __device__ __forceinline__ void wgmma_rs<16, 1>(float* d, uint32_t a0, uint32_t a1, uint32_t a2, uint32_t a3, uint64_t desc, int sc) {
  asm volatile("{\n.reg .pred p;\nsetp.ne.b32 p, %13, 0;\n"
    "wgmma.mma_async.sync.aligned.m64n16k16.f32.bf16.bf16 {%0,%1,%2,%3,%4,%5,%6,%7}, {%8,%9,%10,%11}, %12, p, 1, 1, 1;\n}"
    : "+f"(d[0]), "+f"(d[1]), "+f"(d[2]), "+f"(d[3]), "+f"(d[4]), "+f"(d[5]), "+f"(d[6]), "+f"(d[7]) : "r"(a0), "r"(a1), "r"(a2), "r"(a3), "l"(desc), "r"(sc));
}

__device__ __forceinline__ uint32_t pack_bf16(float lo, float hi) {
  uint32_t r; asm("cvt.rn.bf16x2.f32 %0, %1, %2;" : "=r"(r) : "f"(hi), "f"(lo)); return r;
}
__device__ __forceinline__ float bf_lo(uint32_t v) { return __uint_as_float(v << 16); }
__device__ __forceinline__ float bf_hi(uint32_t v) { return __uint_as_float(v & 0xffff0000u); }
__device__ __forceinline__ float bf_round(float x) { return bf_lo(pack_bf16(x, 0.f)); }
__device__ __forceinline__ uint32_t hmul2(uint32_t a, uint32_t b) { uint32_t r; asm("mul.rn.bf16x2 %0, %1, %2;" : "=r"(r) : "r"(a), "r"(b)); return r; }
__device__ __forceinline__ uint32_t hadd2(uint32_t a, uint32_t b) { uint32_t r; asm("add.rn.bf16x2 %0, %1, %2;" : "=r"(r) : "r"(a), "r"(b)); return r; }
__device__ __forceinline__ uint32_t hsub2(uint32_t a, uint32_t b) { uint32_t r; asm("sub.rn.bf16x2 %0, %1, %2;" : "=r"(r) : "r"(a), "r"(b)); return r; }
__device__ __forceinline__ uint32_t hfma2(uint32_t a, uint32_t b, uint32_t c) { uint32_t r; asm("fma.rn.bf16x2 %0, %1, %2, %3;" : "=r"(r) : "r"(a), "r"(b), "r"(c)); return r; }

__device__ __forceinline__ void sts16(uint32_t a, uint32_t v) { asm volatile("st.shared.b16 [%0], %1;" ::"r"(a), "h"((unsigned short)v) : "memory"); }
__device__ __forceinline__ void sts32(uint32_t a, uint32_t v) { asm volatile("st.shared.b32 [%0], %1;" ::"r"(a), "r"(v) : "memory"); }
__device__ __forceinline__ void sts64(uint32_t a, uint32_t x, uint32_t y) { asm volatile("st.shared.v2.b32 [%0], {%1,%2};" ::"r"(a), "r"(x), "r"(y) : "memory"); }
__device__ __forceinline__ void sts128(uint32_t a, uint32_t x, uint32_t y, uint32_t z, uint32_t w) {
  asm volatile("st.shared.v4.b32 [%0], {%1,%2,%3,%4};" ::"r"(a), "r"(x), "r"(y), "r"(z), "r"(w) : "memory");
}
__device__ __forceinline__ uint32_t lds32(uint32_t a) { uint32_t v; asm volatile("ld.shared.b32 %0, [%1];" : "=r"(v) : "r"(a) : "memory"); return v; }
__device__ __forceinline__ uint4 lds128(uint32_t a) {
  uint4 v; asm volatile("ld.shared.v4.b32 {%0,%1,%2,%3}, [%4];" : "=r"(v.x), "=r"(v.y), "=r"(v.z), "=r"(v.w) : "r"(a) : "memory"); return v;
}
__device__ __forceinline__ uint4 ldg128(const void* a) {
  uint4 v; asm volatile("ld.global.nc.v4.b32 {%0,%1,%2,%3}, [%4];" : "=r"(v.x), "=r"(v.y), "=r"(v.z), "=r"(v.w) : "l"(a) : "memory"); return v;
}
__device__ __forceinline__ uint2 ldg64(const void* a) {
  uint2 v; asm volatile("ld.global.nc.v2.b32 {%0,%1}, [%2];" : "=r"(v.x), "=r"(v.y) : "l"(a) : "memory"); return v;
}
__device__ __forceinline__ void ldsm4(uint32_t a, uint32_t& r0, uint32_t& r1, uint32_t& r2, uint32_t& r3) {
  asm volatile("ldmatrix.sync.aligned.m8n8.x4.shared.b16 {%0,%1,%2,%3}, [%4];" : "=r"(r0), "=r"(r1), "=r"(r2), "=r"(r3) : "r"(a) : "memory");
}
__device__ __forceinline__ void ldsm4t(uint32_t a, uint32_t& r0, uint32_t& r1, uint32_t& r2, uint32_t& r3) {
  asm volatile("ldmatrix.sync.aligned.m8n8.x4.trans.shared.b16 {%0,%1,%2,%3}, [%4];" : "=r"(r0), "=r"(r1), "=r"(r2), "=r"(r3) : "r"(a) : "memory");
}
__device__ __forceinline__ void stsm4(uint32_t a, uint32_t r0, uint32_t r1, uint32_t r2, uint32_t r3) {
  asm volatile("stmatrix.sync.aligned.m8n8.x4.shared.b16 [%0], {%1,%2,%3,%4};" ::"r"(a), "r"(r0), "r"(r1), "r"(r2), "r"(r3) : "memory");
}
__device__ __forceinline__ void stsm4t(uint32_t a, uint32_t r0, uint32_t r1, uint32_t r2, uint32_t r3) {
  asm volatile("stmatrix.sync.aligned.m8n8.x4.trans.shared.b16 [%0], {%1,%2,%3,%4};" ::"r"(a), "r"(r0), "r"(r1), "r"(r2), "r"(r3) : "memory");
}
__device__ __forceinline__ void stsm2(uint32_t a, uint32_t r0, uint32_t r1) {
  asm volatile("stmatrix.sync.aligned.m8n8.x2.shared.b16 [%0], {%1,%2};" ::"r"(a), "r"(r0), "r"(r1) : "memory");
}
__device__ __forceinline__ void stsm2t(uint32_t a, uint32_t r0, uint32_t r1) {
  asm volatile("stmatrix.sync.aligned.m8n8.x2.trans.shared.b16 [%0], {%1,%2};" ::"r"(a), "r"(r0), "r"(r1) : "memory");
}
__device__ __forceinline__ void mma16816(float* c, uint32_t a0, uint32_t a1, uint32_t a2, uint32_t a3, uint32_t b0, uint32_t b1) {
  asm("mma.sync.aligned.m16n8k16.row.col.f32.bf16.bf16.f32 {%0,%1,%2,%3}, {%4,%5,%6,%7}, {%8,%9}, {%0,%1,%2,%3};"
      : "+f"(c[0]), "+f"(c[1]), "+f"(c[2]), "+f"(c[3]) : "r"(a0), "r"(a1), "r"(a2), "r"(a3), "r"(b0), "r"(b1));
}
__device__ __forceinline__ void bar_sync(int id, int n) { asm volatile("bar.sync %0, %1;" ::"r"(id), "r"(n) : "memory"); }
__device__ __forceinline__ void wg_fence() { asm volatile("wgmma.fence.sync.aligned;" ::: "memory"); }
__device__ __forceinline__ void wg_commit() { asm volatile("wgmma.commit_group.sync.aligned;" ::: "memory"); }
__device__ __forceinline__ void wg_wait0() { asm volatile("wgmma.wait_group.sync.aligned 0;" ::: "memory"); }
__device__ __forceinline__ void wg_wait1() { asm volatile("wgmma.wait_group.sync.aligned 1;" ::: "memory"); }
__device__ __forceinline__ void fence_async() { asm volatile("fence.proxy.async.shared::cta;" ::: "memory"); }
__device__ __forceinline__ uint32_t opq(uint32_t x, uint32_t z) { uint32_t r; asm volatile("xor.b32 %0, %1, %2;" : "=r"(r) : "r"(x), "r"(z)); return r; }
__device__ __forceinline__ float opqf(float x, uint32_t z) { float r; asm volatile("add.rn.f32 %0, %1, %2;" : "=f"(r) : "f"(x), "f"(__uint_as_float(z))); return r; }
__device__ __forceinline__ uint64_t mkdesc(uint32_t addr, uint32_t lbo, uint32_t sbo) {
  return (uint64_t)((addr & 0x3FFFF) >> 4) | ((uint64_t)(lbo >> 4) << 16) | ((uint64_t)(sbo >> 4) << 32);
}
__device__ __forceinline__ uint32_t mapa(uint32_t a, uint32_t rank) {
  uint32_t r; asm("mapa.shared::cluster.u32 %0, %1, %2;" : "=r"(r) : "r"(a), "r"(rank)); return r;
}
__device__ __forceinline__ void mbar_init_expect(uint32_t bar, uint32_t bytes) {
  asm volatile("mbarrier.init.shared::cta.b64 [%0], 1;" ::"r"(bar) : "memory");
  asm volatile("mbarrier.arrive.expect_tx.shared::cta.b64 _, [%0], %1;" ::"r"(bar), "r"(bytes) : "memory");
}
__device__ __forceinline__ void mbar_wait(uint32_t bar) {
#pragma unroll 1
  for (int it = 0; it < (1 << 22); it++) {
    uint32_t ok;
    asm volatile("{\n.reg .pred p;\nmbarrier.try_wait.parity.acquire.cluster.shared::cta.b64 p, [%1], 0;\nselp.u32 %0, 1, 0, p;\n}"
                 : "=r"(ok) : "r"(bar) : "memory");
    if (ok) return;
  }
  __trap();
}
__device__ __forceinline__ void st_async4(uint32_t a, uint32_t bar, uint32_t x, uint32_t y, uint32_t z, uint32_t w) {
  asm volatile("st.async.weak.shared::cluster.mbarrier::complete_tx::bytes.v4.b32 [%0], {%2,%3,%4,%5}, [%1];"
               ::"r"(a), "r"(bar), "r"(x), "r"(y), "r"(z), "r"(w) : "memory");
}

struct cf { float re, im; };
__device__ __forceinline__ cf cmul(cf a, cf b) { return {fmaf(a.re, b.re, -a.im * b.im), fmaf(a.re, b.im, a.im * b.re)}; }
__device__ __forceinline__ cf csq(cf a) { return {fmaf(a.re, a.re, -a.im * a.im), (a.re + a.re) * a.im}; }
__device__ __forceinline__ cf cexp_p(float xl, float y, float p) {
  float mag; asm("ex2.approx.ftz.f32 %0, %1;" : "=f"(mag) : "f"(xl * p));
  const float th = y * p;
  const float k = __fadd_rn(fmaf(th, 0.15915494309189535f, 12582912.f), -12582912.f);
  float r = fmaf(k, -6.2831854820251465f, th);
  r = fmaf(k, 1.7484555314695172e-07f, r);
  return {mag * __cosf(r), mag * __sinf(r)};
}
__device__ __forceinline__ uint32_t ysw(int c) { return (uint32_t)(c ^ ((c >> 3) & 3)) * 16u; }

#define CMUL2(OR, OI, xr, xi, yr, yi, nyi) do { OR = hfma2(xr, yr, hmul2(xi, nyi)); OI = hfma2(xr, yi, hmul2(xi, yr)); } while (0)

__device__ __forceinline__ uint32_t gate_slow(const __nv_bfloat16* u, const __nv_bfloat16* gw, int row) {
  float s = 0.f;
  const uint32_t* xr = (const uint32_t*)(u + (size_t)row * D);
  const uint32_t* wr = (const uint32_t*)gw;
#pragma unroll 1
  for (int j = 0; j < D / 2; j++) { const uint32_t pr = hmul2(xr[j], wr[j]); s += bf_lo(pr); s += bf_hi(pr); }
  s = bf_round(s);
  return pack_bf16(1.f / (1.f + expf(-s)), 0.f);
}

__device__ __forceinline__ uint2 gate_ld(int x) {
  uint2 gv;
  asm volatile("ld.relaxed.gpu.global.v2.u32 {%0,%1}, [%2];" : "=r"(gv.x), "=r"(gv.y) : "l"(g_gate + x * 2) : "memory");
  return gv;
}
__device__ __noinline__ uint32_t gate_poll(const Params* pp, int x, uint32_t tag) {
  uint2 gv;
#pragma unroll 1
  for (int spins = 0; spins < (1 << 16); spins++) {
    gv = gate_ld(x);
    if ((gv.x >> 16) == tag && (gv.y >> 16) == tag) return __byte_perm(gv.x, gv.y, 0x5410);
  }
  return __byte_perm(gate_slow(pp->u, pp->gw, x * 2), gate_slow(pp->u, pp->gw, x * 2 + 1), 0x5410);
}
__device__ __forceinline__ uint32_t gate_fin(const Params& p, uint2 gv, int x, uint32_t tag) {
  if ((gv.x >> 16) == tag && (gv.y >> 16) == tag) return __byte_perm(gv.x, gv.y, 0x5410);
  return gate_poll(&p, x, tag);
}

__device__ __forceinline__ void ld4ch(uint32_t* v, uint32_t addr) {
#pragma unroll
  for (int k = 0; k < 4; k++) v[k] = lds32(addr + k * CH_BYTES);
}
__device__ __forceinline__ void skip_terms(uint32_t* ua, uint32_t* ub, uint32_t sb, int x, uint2 dA, uint2 dB) {
  const int c = x >> 2;
  uint32_t uu[4];
  ld4ch(uu, sb + CH_OFF + (x & 3) * 4 + U_OFF + (c & 3) * U_CS + (63 - (c >> 2)) * 16);
#pragma unroll
  for (int k = 0; k < 4; k++) {
    ua[k] = hmul2(uu[k], __byte_perm((k & 2) ? dA.y : dA.x, 0, (k & 1) ? 0x3232 : 0x1010));
    ub[k] = hmul2(uu[k], __byte_perm((k & 2) ? dB.y : dB.x, 0, (k & 1) ? 0x3232 : 0x1010));
  }
}
__device__ __forceinline__ uint4 mix(const uint32_t* a, const uint32_t* b, const uint32_t* ua, const uint32_t* ub, uint32_t g2) {
  const uint32_t h2 = hsub2(0x3f803f80u, g2);
  uint32_t o[4];
#pragma unroll
  for (int k = 0; k < 4; k++) o[k] = hadd2(hmul2(g2, hadd2(a[k], ua[k])), hmul2(h2, hadd2(b[k], ub[k])));
  return make_uint4(__byte_perm(o[0], o[1], 0x5410), __byte_perm(o[2], o[3], 0x5410), __byte_perm(o[0], o[1], 0x7632), __byte_perm(o[2], o[3], 0x7632));
}
__device__ __forceinline__ void send_box(uint32_t sb, int slot, int wtid, uint32_t rank, uint4 r) {
  st_async4(mapa(sb + XIN_OFF + slot * 2048 + wtid * 16, rank ^ 1), mapa(sb + B_X + slot * 8, rank ^ 1), r.x, r.y, r.z, r.w);
}
__device__ __forceinline__ void merge_rows(uint32_t st, uint32_t rank, uint4 r, uint4 q) {
  const uint4 lo = rank ? q : r, hi = rank ? r : q;
  sts128(st, lo.x, lo.y, hi.x, hi.y); sts128(st + 2048, lo.z, lo.w, hi.z, hi.w);
}
__device__ __forceinline__ void merge_box(uint32_t sb, const CUtensorMap* tm_out, int slot, int wtid, uint32_t rank, int oc0, uint4 r, int barid) {
  const uint32_t st = sb + RAW_OFF + slot * 4096 + wtid * 16;
  mbar_wait(sb + B_X + slot * 8);
  merge_rows(st, rank, r, lds128(sb + XIN_OFF + slot * 2048 + wtid * 16));
  fence_async();
  bar_sync(barid, 128);
  if (wtid == 0) {
    asm volatile("cp.async.bulk.tensor.3d.global.shared::cta.bulk_group [%0, {%2, %3, %4}], [%1];"
                 ::"l"(tm_out), "r"(sb + RAW_OFF + slot * 4096), "r"(oc0), "r"((2 * slot + (int)rank) * 128), "r"(0) : "memory");
    asm volatile("cp.async.bulk.commit_group;" ::: "memory");
  }
}

__device__ __forceinline__ uint32_t band2(int e, int lo, int hi) {
  uint32_t r = ((uint32_t)(e - lo) <= (uint32_t)(hi - lo) ? 0x3f80u : 0u) | ((uint32_t)(e - 1 - lo) <= (uint32_t)(hi - lo) ? 0x3f800000u : 0u);
  asm volatile("" : "+r"(r));
  return r;
}

__device__ __forceinline__ void stage_done(uint32_t sb, int stage, int lane) {
  __syncwarp();
  if (lane == 0) asm volatile("mbarrier.arrive.shared::cta.b64 _, [%0];" ::"r"(sb + B_ST + 8 * stage) : "memory");
}
#define PK2(v, i) pack_bf16(v[i], v[(i) + 1])

__device__ __forceinline__ void conv_dense(uint32_t sb, uint32_t cb, uint32_t zz) {
  const int lane = threadIdx.x & 31, wq = (threadIdx.x >> 5) & 3, br = wq >> 1, hf = wq & 1, g = lane >> 2, t = lane & 3;
  const uint32_t rb = cb + R_OFF + br * R_BR;
  const int eo = 16 * hf + g - 2 * t;
  const int x0 = RD_X0 - (eo + 536);
  const uint32_t fa = rb + ((g & 1) ? 2 * x0 : RD_CS + 2 * x0 + 2);
  const uint64_t ub = mkdesc(cb + U_OFF, U_CS, 128);
  const uint32_t yd = cb + Y0_OFF + br * 4096 + ysw(4 * (63 - 8 * (lane >> 4) - (lane & 7)) + 2 * hf + ((lane >> 3) & 1));
  uint32_t A[2][4][4];
  float e64[32], e56[28], e48[24];
  auto loadA = [&](int j) {
#pragma unroll
    for (int k = 0; k < 4; k++) {
      const int s = 34 - 4 * j - k;
      if (s >= 0) {
        if (k == 0 && j == 0) A[0][0][2] = lds32(fa + (2 * s + 2) * 16);
        A[j & 1][k][0] = lds32(fa + (2 * s + 1) * 16);
        A[j & 1][k][1] = lds32(fa + (2 * s) * 16);
      }
    }
#pragma unroll
    for (int k = 0; k < 4; k++) {
      if (34 - 4 * j - k >= 0) {
        A[j & 1][k][3] = A[j & 1][k][0];
        if (k) A[j & 1][k][2] = A[j & 1][k - 1][1];
        else if (j) A[j & 1][0][2] = A[(j - 1) & 1][3][1];
      }
    }
  };
  loadA(0); loadA(1);
#pragma unroll
  for (int j = 0; j < 9; j++) {
    if (j == 4) {
      wg_wait0();
      stsm2t(yd - 7 * 512, PK2(e64, 28), PK2(e64, 30));
#pragma unroll
      for (int i = 0; i < 28; i++) e56[i] = FCPY(e64, i);
      stage_done(sb, 0, lane);
    }
    if (j == 8) {
      wg_wait0();
      stsm2t(yd - 6 * 512, PK2(e56, 24), PK2(e56, 26));
#pragma unroll
      for (int i = 0; i < 24; i++) e48[i] = FCPY(e56, i);
      stage_done(sb, 1, lane);
    }
    wg_fence();
#pragma unroll
    for (int k = 0; k < 4; k++) {
      const int s = 34 - 4 * j - k;
      if (s >= 0) {
        const int o = 2 * s - 66 + 128;
        const int cc = o & 3, rs = (o >> 2) - 32;
        const uint64_t desc = ub + (uint64_t)((cc * U_CS - rs * 16) >> 4);
        const uint32_t* a = A[j & 1][k];
        if (j < 4) wgmma_rs<64, 0>(e64, a[0], a[1], a[2], a[3], desc, s != 34);
        else if (j < 8) wgmma_rs<56, 0>(e56, a[0], a[1], a[2], a[3], desc, 1);
        else wgmma_rs<48, 0>(e48, a[0], a[1], a[2], a[3], desc, 1);
      }
    }
    wg_commit();
    if (j >= 1 && j < 8) { wg_wait1(); loadA(j + 1); }
  }
  wg_wait0();
#pragma unroll
  for (int i = 0; i < 6; i += 2) stsm4t(yd - i * 512, PK2(e48, 4 * i), PK2(e48, 4 * i + 2), PK2(e48, 4 * i + 4), PK2(e48, 4 * i + 6));
}

__device__ __noinline__ unsigned int gate_rows(const Params* pp, int grow, int step, int rend) {
  const __nv_bfloat16 *u = pp->u, *gw = pp->gw;
  const int lane = threadIdx.x & 31;
  uint4 gx[4][2], nx[4][2];
#pragma unroll
  for (int i = 0; i < 4; i++) {
    nx[i][0] = ldg128(u + (size_t)(grow + i) * D + lane * 8);
    nx[i][1] = ldg128(u + (size_t)(grow + i) * D + 256 + lane * 8);
  }
  const uint4 gw0 = ldg128(gw + lane * 8), gw1 = ldg128(gw + 256 + lane * 8);
  const uint32_t ws[8] = {gw0.x, gw0.y, gw0.z, gw0.w, gw1.x, gw1.y, gw1.z, gw1.w};
  unsigned int epoch;
  asm volatile("ld.relaxed.gpu.global.u32 %0, [%1];" : "=r"(epoch) : "l"(&g_epoch) : "memory");
#pragma unroll 1
  for (; grow < rend; grow += step) {
#pragma unroll
    for (int i = 0; i < 4; i++) { gx[i][0] = nx[i][0]; gx[i][1] = nx[i][1]; }
    if (grow + step < rend) {
#pragma unroll
      for (int i = 0; i < 4; i++) {
        nx[i][0] = ldg128(u + (size_t)(grow + step + i) * D + lane * 8);
        nx[i][1] = ldg128(u + (size_t)(grow + step + i) * D + 256 + lane * 8);
      }
    }
    float c[2][4];
#pragma unroll
    for (int i = 0; i < 2; i++) {
      const uint4 *x = gx[2 * i], *y = gx[2 * i + 1];
      const uint32_t xs[8] = {x[0].x, x[0].y, x[0].z, x[0].w, x[1].x, x[1].y, x[1].z, x[1].w};
      const uint32_t ys[8] = {y[0].x, y[0].y, y[0].z, y[0].w, y[1].x, y[1].y, y[1].z, y[1].w};
      c[i][0] = c[i][1] = c[i][2] = c[i][3] = 0.f;
#pragma unroll
      for (int j = 0; j < 8; j += 2)
        mma16816(c[i], hmul2(xs[j], ws[j]), hmul2(ys[j], ws[j]), hmul2(xs[j + 1], ws[j + 1]), hmul2(ys[j + 1], ws[j + 1]), 0x3f803f80u, 0x3f803f80u);
    }
    float s = (lane & 2) ? ((lane & 1) ? c[1][2] : c[1][0]) : ((lane & 1) ? c[0][2] : c[0][0]);
#pragma unroll
    for (int o = 4; o < 32; o <<= 1) s += __shfl_xor_sync(0xffffffffu, s, o);
    s = bf_round(s);
    const float gv = 1.f / (1.f + expf(-s));
    const uint32_t w = ((epoch + 1) << 16) | (pack_bf16(gv, 0.f) & 0xffffu);
    if (lane < 4) asm volatile("st.relaxed.gpu.global.u32 [%0], %1;" ::"l"(&g_gate[grow + lane]), "r"(w) : "memory");
  }
  return epoch;
}
#define GW 1
constexpr int GSPLIT = L - 4 * GW * NCTA;
__device__ __noinline__ void gate_cta(const Params* pp) {
  const unsigned int epoch = gate_rows(pp, (blockIdx.x * 20 + (threadIdx.x >> 5)) * 4, 80 * NGATE, GSPLIT);
  __syncthreads();
  if (threadIdx.x == 0 && atomicAdd(&g_ticket, 1u) == NCTA + NGATE - 1) { g_ticket = 0; g_epoch = epoch + 1; }
}

__global__ void __cluster_dims__(2, 1, 1) __launch_bounds__(640, 1)
ssm_kernel(const __grid_constant__ Params p, const __grid_constant__ CUtensorMap tm_in, const __grid_constant__ CUtensorMap tm_out) {
  extern __shared__ __align__(1024) unsigned char smem_raw[];
  const uint32_t sb = (uint32_t)__cvta_generic_to_shared(smem_raw);
  const int tid = threadIdx.x, lane = tid & 31;
  const int warp = __shfl_sync(0xffffffffu, tid >> 5, 0);
  const int ch = warp >> 2, wq = warp & 3, br = wq >> 1, hf = wq & 1;
  const int g = lane >> 2, t = lane & 3;
  if (__builtin_expect(blockIdx.x < NGATE, 0)) { gate_cta(&p); return; }
  const int bid = blockIdx.x - NGATE;
  const uint32_t rank = blockIdx.x & 1;
  const uint32_t cb = sb + CH_OFF + ch * CH_BYTES;
  const int wtid = tid & 127;
  const int oc0 = (bid >> 1) * 8;
  STAMP(0); GT(0);

  if (tid == 512) {
    asm volatile("prefetch.tensormap [%0];" ::"l"(&tm_in) : "memory");
#pragma unroll
    for (int i = 0; i < 4; i++) mbar_init_expect(sb + B_RAW + 8 * i, 8192);
#pragma unroll
    for (int i = 0; i < 4; i++) mbar_init_expect(sb + B_X + 8 * i, 2048);
    asm volatile("mbarrier.init.shared::cta.b64 [%0], 128;" ::"r"(sb + B_U) : "memory");
    asm volatile("mbarrier.init.shared::cta.b64 [%0], 128;" ::"r"(sb + B_W) : "memory");
#pragma unroll
    for (int i = 0; i < 7; i++) asm volatile("mbarrier.init.shared::cta.b64 [%0], 16;" ::"r"(sb + B_ST + 8 * i) : "memory");
    asm volatile("fence.mbarrier_init.release.cluster;" ::: "memory");
    asm volatile("fence.proxy.async.shared::cta;" ::: "memory");
  }
  __syncwarp();
  asm volatile("barrier.cluster.arrive.relaxed.aligned;" ::: "memory");
  if (warp == 16) {
    asm volatile("barrier.cluster.wait.aligned;" ::: "memory");
    if (lane < 4) {
      asm volatile("cp.async.bulk.tensor.5d.shared::cluster.global.mbarrier::complete_tx::bytes.multicast::cluster [%0], [%1, {%3, %4, %4, %4, %5}], [%2], %6;"
                   ::"r"(sb + RAW_OFF + rank * 16384 + lane * 4096), "l"(&tm_in), "r"(sb + B_RAW + 8 * lane), "r"(oc0), "r"(0), "r"((int)rank * 32 + lane * 8),
                     "h"((unsigned short)3) : "memory");
    }
    __syncwarp();
  }

  if (warp >= 16) {
    if (wq >= 4 - GW) gate_rows(&p, GSPLIT + (bid * GW + 3 - wq) * 4, L, L);
    unsigned int epoch;
    asm volatile("ld.relaxed.gpu.global.u32 %0, [%1];" : "=r"(epoch) : "l"(&g_epoch) : "memory");
    if (wq) asm volatile("barrier.cluster.wait.aligned;" ::: "memory");
    sts128(sb + CH_OFF + wq * CH_BYTES + U_OFF + (lane >> 3) * U_CS + (64 + (lane & 7)) * 16, 0, 0, 0, 0);
    const uint2 dA = ldg64(p.A_D + bid * 4), dB = ldg64(p.B_D + bid * 4);
    uint32_t BA[3][4], BB[4][4];
    {
      const int l1 = br ? 3 : 6, h1 = br ? 5 : 10, l2 = br ? 5 : 12, h2 = br ? 11 : 20;
#pragma unroll
      for (int i = 0; i < 4; i++) {
        const int e = 16 * hf + g - 2 * t + 32 - 16 * i;
        BB[i][0] = band2(e, l2, h2); BB[i][1] = band2(e + 8, l2, h2); BB[i][2] = band2(e - 8, l2, h2); BB[i][3] = BB[i][0];
        if (i) { BA[i - 1][0] = band2(e, l1, h1); BA[i - 1][1] = band2(e + 8, l1, h1); BA[i - 1][2] = band2(e - 8, l1, h1); BA[i - 1][3] = BA[i - 1][0]; }
      }
    }
    const uint32_t tag = (epoch + 1) & 0xffffu;
    if (wtid == 0) sts32(sb + TAG_OFF, tag);
    STAMP(3);
    {
      const int x0 = (wq >> 1) * 32 + (wq & 1) * 4;
      const uint32_t dst = sb + CH_OFF + (g & 3) * CH_BYTES + U_OFF + t * U_CS + (63 - x0) * 16;
#pragma unroll 1
      for (int h = 0; h < 4; h++) {
        uint32_t r[4][4];
        mbar_wait(sb + B_RAW + 8 * h);
        if (h == 0) STAMP(4);
#pragma unroll
        for (int i = 0; i < 4; i++) ldsm4t(sb + RAW_OFF + (x0 + h * 8 + i) * 512 + lane * 16, r[i][0], r[i][1], r[i][2], r[i][3]);
        if ((uint32_t)(g >> 2) == rank) {
#pragma unroll
          for (int i = 0; i < 4; i++) sts128(dst - (h * 8 + i) * 16, r[i][0], r[i][1], r[i][2], r[i][3]);
        }
      }
    }
    fence_async();
    asm volatile("mbarrier.arrive.shared::cta.b64 _, [%0];" ::"r"(sb + B_U) : "memory");
    bar_sync(5, 128);
    STAMP(5);
    {
      const int mrow = lane & 7, mi = lane >> 3;
      const uint64_t ub0 = mkdesc(sb + CH_OFF + U_OFF, U_CS, 128);
      uint32_t wa, wb;
      {
        const int c = 4 * (47 - 8 * (mi >> 1) - mrow) + 2 * hf + (mi & 1);
        wa = sb + CH_OFF + (br ? W3_OFF : W5_OFF) + (5 - (c >> 5)) * 576 + ((c & 31) >> 3) * 144 + (c & 7) * 16;
        const int c2 = c - 64, pp = c2 >> 1;
        wb = sb + CH_OFF + (br ? W7_OFF : W9_OFF) + (1 - (pp >> 5)) * 1152 + (c2 & 1) * 576 + ((pp & 31) >> 3) * 144 + (pp & 7) * 16;
      }
      {
        float w1[24];
#pragma unroll
        for (int i = 0; i < 24; i++) w1[i] = 0.f;
#pragma unroll 1
        for (int k = 0; k < 4; k++) {
          wg_fence();
#pragma unroll
          for (int i = 0; i < 3; i++)
            wgmma_rs<48, 0>(w1, BA[i][0], BA[i][1], BA[i][2], BA[i][3],
                            ub0 + (uint64_t)((k * CH_BYTES + ((2 * i + 2) & 3) * U_CS + (16 + (i == 0)) * 16) >> 4), i);
          wg_commit();
          wg_wait0();
#pragma unroll
          for (int i = 0; i < 3; i++) stsm4t(wa + k * CH_BYTES + i * 1152, PK2(w1, 8 * i), PK2(w1, 8 * i + 2), PK2(w1, 8 * i + 4), PK2(w1, 8 * i + 6));
        }
      }
      {
        float w2[2][16];
#pragma unroll
        for (int i = 0; i < 16; i++) { w2[0][i] = 0.f; w2[1][i] = 0.f; }
#pragma unroll 1
        for (int kp = 0; kp < 2; kp++) {
          wg_fence();
#pragma unroll
          for (int k = 0; k < 2; k++)
#pragma unroll
            for (int i = 0; i < 4; i++)
              wgmma_rs<32, 0>(w2[k], BB[i][0], BB[i][1], BB[i][2], BB[i][3],
                              ub0 + (uint64_t)(((2 * kp + k) * CH_BYTES + ((2 * i) & 3) * U_CS + (32 + (i < 2)) * 16) >> 4), i);
          wg_commit();
          wg_wait0();
#pragma unroll
          for (int k = 0; k < 2; k++)
#pragma unroll
            for (int i = 0; i < 2; i++)
              stsm4t(wb + (2 * kp + k) * CH_BYTES + i * 1152, PK2(w2[k], 8 * i), PK2(w2[k], 8 * i + 2), PK2(w2[k], 8 * i + 4), PK2(w2[k], 8 * i + 6));
        }
      }
    }
    fence_async();
    asm volatile("mbarrier.arrive.shared::cta.b64 _, [%0];" ::"r"(sb + B_W) : "memory");
    STAMP(7);
    {
      const int bsel = (int)rank ^ br ^ 1, xl = wtid & 63;
      uint2 gl[4];
      uint32_t ua[4][4], ub[4][4];
#pragma unroll
      for (int i = 0; i < 4; i++) skip_terms(ua[i], ub[i], sb, (2 * (i >> 1) + bsel) * 128 + (i & 1) * 64 + xl, dA, dB);
      const uint32_t yo = sb + CH_OFF + (xl & 3) * 4 + ysw(xl >> 2) + bsel * 512;
#pragma unroll
      for (int i = 0; i < 2; i++) gl[i] = gate_ld(bsel * 128 + i * 64 + xl);
#pragma unroll
      for (int slot = 0; slot < 2; slot++) {
        const int box = 2 * slot + bsel;
        uint32_t g2[2], ya[2][4], yb[2][4];
#pragma unroll
        for (int h = 0; h < 2; h++) g2[h] = gate_fin(p, gl[2 * slot + h], box * 128 + h * 64 + xl, tag);
        mbar_wait(sb + B_ST + 8 * box);
        STAMP(8 + slot);
        if (slot == 0) { gl[2] = gate_ld((2 + bsel) * 128 + xl); gl[3] = gate_ld((2 + bsel) * 128 + 64 + xl); }
#pragma unroll
        for (int h = 0; h < 2; h++) {
          const uint32_t yh = (yo ^ (h * 32)) + h * 256 + slot * 1024;
          ld4ch(ya[h], yh + Y0_OFF); ld4ch(yb[h], yh + Y0_OFF + 4096);
          if (slot) {
            uint32_t a2[4], b2[4];
            ld4ch(a2, yh + Y2_OFF - 1024); ld4ch(b2, yh + Y2_OFF - 1024 + 3072);
#pragma unroll
            for (int k = 0; k < 4; k++) { ya[h][k] = hadd2(ya[h][k], a2[k]); yb[h][k] = hadd2(yb[h][k], b2[k]); }
          }
        }
        const uint4 r0 = mix(ya[0], yb[0], ua[2 * slot], ub[2 * slot], g2[0]), r1 = mix(ya[1], yb[1], ua[2 * slot + 1], ub[2 * slot + 1], g2[1]);
        if (br == 0) { send_box(sb, slot, xl, rank, r0); send_box(sb, slot, xl + 64, rank, r1); }
        else {
          const uint32_t st = sb + RAW_OFF + slot * 4096 + xl * 16, xin = sb + XIN_OFF + slot * 2048 + xl * 16;
          mbar_wait(sb + B_X + slot * 8);
          const uint4 q0 = lds128(xin), q1 = lds128(xin + 1024);
          merge_rows(st, rank, r0, q0); merge_rows(st + 1024, rank, r1, q1);
          fence_async();
          bar_sync(6, 64);
          if (xl == 0) {
            asm volatile("cp.async.bulk.tensor.3d.global.shared::cta.bulk_group [%0, {%2, %3, %4}], [%1];"
                         ::"l"(&tm_out), "r"(sb + RAW_OFF + slot * 4096), "r"(oc0), "r"(box * 128), "r"(0) : "memory");
            asm volatile("cp.async.bulk.commit_group;" ::: "memory");
          }
        }
        STAMP(10 + slot);
      }
    }
    if (wtid == 0 && atomicAdd(&g_ticket, 1u) == NCTA + NGATE - 1) { g_ticket = 0; g_epoch = epoch + 1; }
    if (wtid == 64) asm volatile("cp.async.bulk.wait_group.read 0;" ::: "memory");
    STAMP(15);
    return;
  }

  const int moff = (bid * 4 + (tid >> 7)) * NM + (tid & 63) * 2;
  const int brt = (tid >> 6) & 1;
  const __nv_bfloat16* const* tp = p.t + (brt ? 0 : 6);
  const uint32_t q0 = *(const uint32_t*)(tp[0] + moff), q1 = *(const uint32_t*)(tp[1] + moff);
  const uint32_t q2 = *(const uint32_t*)(tp[2] + moff), q3 = *(const uint32_t*)(tp[3] + moff);
  const uint2 ldt4 = *(const uint2*)(tp[4] + bid * 4);
  const uint32_t q4 = *(const uint32_t*)(tp[brt ? 2 : 5] + moff), q5 = *(const uint32_t*)(tp[brt ? 3 : 6] + moff);

  for (int i = wtid & 63; i < R_BR / 16; i += 64) sts128(cb + R_OFF + br * R_BR + i * 16, 0, 0, 0, 0);
  STAMP(1);

  float acc[5][4];
  float k2048 = 0.f;
  const uint32_t scr = cb + Y0_OFF + wq * SCR_BYTES;
  const uint32_t scr2 = sb + SC2_OFF + warp * 640;
  {
    const uint32_t ldt2 = (ch & 2) ? ldt4.y : ldt4.x;
    const float dt = bf_round(expf((ch & 1) ? bf_hi(ldt2) : bf_lo(ldt2)));
#pragma unroll
    for (int i = 0; i < 5; i++) acc[i][0] = acc[i][1] = acc[i][2] = acc[i][3] = 0.f;
    STAMP(2);
    const uint32_t tb = scr + lane * 16;
    const uint32_t ta = scr + (lane >> 3) * 512 + (lane & 7) * 16;
    const uint32_t tc = ((lane & 8) ? scr2 : scr + 4096) + (lane >> 4) * 128 + (lane & 7) * 16;
    const uint32_t tm = scr2 + 512 + ((lane >> 3) & 1) * 64 + (lane >> 4) * 16;
#pragma unroll 1
    for (int r = 0; r < 2; r++) {
      cf c, z1, z128;
      {
        const uint32_t sh = r ? 0x3244u : 0x1044u;
        float v0 = __uint_as_float(__byte_perm(q0, 0, sh));
        const float v1 = __uint_as_float(__byte_perm(q1, 0, sh)), v2 = __uint_as_float(__byte_perm(q2, 0, sh)), v3 = __uint_as_float(__byte_perm(q3, 0, sh));
        if (br == 0) { c = cmul(cf{v2, v3}, cf{dt * __uint_as_float(__byte_perm(q4, 0, sh)), dt * __uint_as_float(__byte_perm(q5, 0, sh))}); }
        else { v0 = -bf_round(expf(v0)); c = cf{2.f * dt * v2, 2.f * dt * v3}; }
        const float xl = (dt * v0) * 1.4426950408889634f, y = dt * v1;
        z1 = cexp_p(xl, y, 1.f); z128 = cexp_p(xl, y, 128.f);
      }
      const cf z2 = csq(z1), z4 = csq(z2), z8 = csq(z4);
      const cf w8 = {z8.re, -z8.im};
      const cf z16 = csq(w8), z24 = cmul(z16, w8), z32 = csq(z16), z40 = cmul(z32, w8), z48 = csq(z24), z56 = cmul(z32, z24), z64 = csq(z32);
      const cf z256 = csq(z128), z512 = csq(z256), z1024 = csq(z512), z2048 = csq(z1024);
      {
        float kk = fmaf(c.re, z2048.re, -c.im * z2048.im);
#pragma unroll
        for (int o = 16; o; o >>= 1) kk += __shfl_xor_sync(0xffffffffu, kk, o);
        k2048 += kk;
      }
      __syncwarp();
      {
        uint32_t xr[4] = {pack_bf16(1.f, z8.re), pack_bf16(z16.re, z24.re), pack_bf16(z32.re, z40.re), pack_bf16(z48.re, z56.re)};
        uint32_t xi[4] = {pack_bf16(0.f, w8.im), pack_bf16(z16.im, z24.im), pack_bf16(z32.im, z40.im), pack_bf16(z48.im, z56.im)};
        sts128(tb + 0 * 512, xr[0], xr[1], xr[2], xr[3]);
        sts128(tb + 2 * 512, xi[0], xi[1], xi[2], xi[3]);
        const uint32_t yr = pack_bf16(z64.re, z64.re), yi = pack_bf16(z64.im, z64.im), nyi = yi ^ 0x80008000u;
        uint32_t o[4], q[4];
#pragma unroll
        for (int i = 0; i < 4; i++) CMUL2(o[i], q[i], xr[i], xi[i], yr, yi, nyi);
        sts128(tb + 1 * 512, o[0], o[1], o[2], o[3]);
        sts128(tb + 3 * 512, q[0], q[1], q[2], q[3]);
      }
      {
        const cf h1 = cmul(c, z128), h2 = cmul(c, z256), h3 = cmul(h1, z256), h4 = cmul(c, z512), h5 = cmul(h1, z512), h6 = cmul(h2, z512), h7 = cmul(h3, z512);
        const cf e1 = cmul(c, z1), e2 = cmul(c, z2), e3 = cmul(e1, z2), e129 = cmul(h1, z1), e130 = cmul(h1, z2), e131 = cmul(e129, z2);
        const cf e258 = cmul(h2, z2), e386 = cmul(h3, z2);
        const uint32_t pr0 = pack_bf16(c.re, e1.re), pr2 = pack_bf16(h1.re, e129.re), pi0 = pack_bf16(c.im, e1.im), pi2 = pack_bf16(h1.im, e129.im);
        sts128(tb + 4 * 512, pr0, pack_bf16(e2.re, e3.re), pr2, pack_bf16(e130.re, e131.re));
        sts128(tb + 5 * 512, pi0, pack_bf16(e2.im, e3.im), pi2, pack_bf16(e130.im, e131.im));
        uint32_t xr[4] = {pack_bf16(h2.re, e258.re), pack_bf16(h3.re, e386.re), pack_bf16(h4.re, h5.re), pack_bf16(h6.re, h7.re)};
        uint32_t xi[4] = {pack_bf16(h2.im, e258.im), pack_bf16(h3.im, e386.im), pack_bf16(h4.im, h5.im), pack_bf16(h6.im, h7.im)};
        sts128(tb + 6 * 512, xr[0], xr[1], xr[2], xr[3]);
        sts128(tb + 7 * 512, xi[0], xi[1], xi[2], xi[3]);
        xr[1] = __byte_perm(xr[0], xr[1], 0x5410); xi[1] = __byte_perm(xi[0], xi[1], 0x5410);
        xr[0] = __byte_perm(pr0, pr2, 0x5410); xi[0] = __byte_perm(pi0, pi2, 0x5410);
        const uint32_t yr = pack_bf16(z1024.re, z1024.re), yi = pack_bf16(z1024.im, z1024.im), nyi = yi ^ 0x80008000u;
        uint32_t o[4], q[4];
#pragma unroll
        for (int i = 0; i < 4; i++) CMUL2(o[i], q[i], xr[i], xi[i], yr, yi, nyi);
        sts128(tb + 8 * 512, o[0], o[1], o[2], o[3]);
        sts128(scr2 + lane * 16, q[0], q[1], q[2], q[3]);
        const uint32_t m4 = pack_bf16(z4.re, z4.im);
        sts16(scr2 + 512 + lane * 2, m4); sts16(scr2 + 576 + lane * 2, m4 >> 16);
      }
      __syncwarp();
#pragma unroll
      for (int kp = 0; kp < 2; kp++) {
        uint32_t rr[2], ri[2], yr[2], yi[2];
        ldsm4t(tc + kp * 256, rr[0], ri[0], rr[1], ri[1]);
        ldsm4(tm + kp * 32, yr[0], yi[0], yr[1], yi[1]);
#pragma unroll
        for (int k2 = 0; k2 < 2; k2++) {
          const int kk = kp * 2 + k2;
          uint32_t a0, a1, a2, a3, pr, pi, qr, qi, xr, xi;
          ldsm4t(ta + kk * 128, a0, a1, a2, a3);
          ldsm4t(ta + 2048 + kk * 128, pr, pi, qr, qi);
          const uint32_t nyi = yi[k2] ^ 0x80008000u;
          mma16816(acc[0], a0, a1, a2, a3, pr, pi);
          mma16816(acc[2], a0, a1, a2, a3, qr, qi);
          mma16816(acc[4], a0, a1, a2, a3, rr[k2], ri[k2]);
          CMUL2(xr, xi, pr, pi, yr[k2], yi[k2], nyi);
          mma16816(acc[1], a0, a1, a2, a3, xr, xi);
          CMUL2(xr, xi, qr, qi, yr[k2], yi[k2], nyi);
          mma16816(acc[3], a0, a1, a2, a3, xr, xi);
        }
      }
    }
  }
  STAMP(3);
  __syncwarp();
  {
    const uint32_t xs = scr + lane * 16;
#define OTH(i, k) __float_as_uint(hf ? acc[i][k] : acc[i][2 + (k)])
    sts128(xs, OTH(0, 0), OTH(0, 1), OTH(1, 0), OTH(1, 1));
    sts128(xs + 512, OTH(2, 0), OTH(2, 1), OTH(3, 0), OTH(3, 1));
    sts128(xs + 1024, OTH(4, 0), OTH(4, 1), __float_as_uint(k2048), 0);
#undef OTH
  }

  bar_sync(7 + (warp >> 1), 64);
  STAMP(4);
  {
    const uint32_t xo = cb + Y0_OFF + (wq ^ 1) * SCR_BYTES + lane * 16;
    const uint4 o0 = lds128(xo), o1 = lds128(xo + 512), o2 = lds128(xo + 1024);
    const uint32_t rb = cb + R_OFF + br * R_BR;
#define OWN(i, k) (hf ? acc[i][2 + (k)] : acc[i][k])
    const uint32_t vP = pack_bf16(OWN(0, 1) + __uint_as_float(o0.y), OWN(0, 0) + __uint_as_float(o0.x));
    const uint32_t vP4 = pack_bf16(OWN(1, 1) + __uint_as_float(o0.w), OWN(1, 0) + __uint_as_float(o0.z));
    const uint32_t vQ = pack_bf16(OWN(2, 1) + __uint_as_float(o1.y), OWN(2, 0) + __uint_as_float(o1.x));
    const uint32_t vQ4 = pack_bf16(OWN(3, 1) + __uint_as_float(o1.w), OWN(3, 0) + __uint_as_float(o1.z));
    const uint32_t vR = pack_bf16(OWN(4, 1) + __uint_as_float(o2.y), OWN(4, 0) + __uint_as_float(o2.x));
#undef OWN
    const int j = g + 8 * hf;
    {
      const int a = 2 * (t & 1) + 64 * (t & 2) + 8 * j;
      const uint32_t ad = rb + 2 * (RD_X0 - 1 - a);
      const uint32_t a1 = (t & 2) ? ad - 8 : ad, a2 = (t & 2) ? ad : ad - 8;
      const uint32_t w1 = (t & 2) ? vP4 : vP, w2 = (t & 2) ? vP : vP4;
      sts32(a1, w1); sts32(a2, w2);
      sts16(a1 + RD_CS + 2, w1); sts16(a1 + RD_CS + 4, w1 >> 16);
      sts16(a2 + RD_CS + 2, w2); sts16(a2 + RD_CS + 4, w2 >> 16);
    }
    if (t < 2) {
      const int b = 256 + 128 * t + 8 * j;
      const uint32_t ad = rb + 2 * (RD_X0 - 6 - b);
      const uint32_t v22 = __byte_perm(vQ4, 0, 0x3232), v00 = __byte_perm(vQ, 0, 0x3232);
      sts16(ad, vQ4);
      sts64(ad + 2, v22, __byte_perm(vQ4, vQ, 0x5432));
      sts32(ad + 10, v00);
      if (b != 256) { sts16(ad + 14, v00); sts128(ad + RD_CS + 2, vQ4, v22, vQ, v00); }
      else { sts64(ad + RD_CS + 2, vQ4, v22); sts32(ad + RD_CS + 10, vQ); sts16(ad + RD_CS + 14, v00); }
    } else {
      const uint32_t ao = rb + R_O2 + 2 * (159 - (32 * t + j)), ae = ao - (R_O2 - R_E2) + 2;
      sts16(ao, vQ4 >> 16); sts16(ao + RS_CS + 2, vQ4 >> 16); sts16(ao - 32, vQ4); sts16(ao - 32 + RS_CS + 2, vQ4);
      sts16(ae - 32, vQ); sts16(ae - 32 + RS_CS + 2, vQ);
      if (lane != 2 || hf) { sts16(ae, vQ >> 16); sts16(ae + RS_CS + 2, vQ >> 16); }
      else {
        const uint32_t vv = __byte_perm(vQ, 0, 0x3232), ad = rb + 2 * (RD_X0 - 514);
        sts16(ad, vv); sts32(ad + 2, vv); sts16(ad + 6, vv); sts64(ad + RD_CS + 2, vv, vv);
      }
    }
    {
      const uint32_t a = rb + ((g & 1) ? R_O3 : R_E3 + 2) + 2 * (159 - (64 + 16 * t + (j >> 1)));
      const bool p1024 = (lane == 0) && (hf == 0);
      const uint32_t a00 = p1024 ? rb + R_E2 + 2 * (159 - 127) : a;
      sts16(a00, vR >> 16); sts16(a00 + RS_CS + 2, vR >> 16);
      sts16(a - 16, vR); sts16(a - 16 + RS_CS + 2, vR);
      if (p1024) {
        sts32(sb + K1024_OFF + (ch * 2 + br) * 4, __byte_perm(vR, 0, 0x3232));
        const uint32_t kv = pack_bf16(k2048 + __uint_as_float(o2.z), 0.f);
        sts16(rb + R_E3 + 2 * (159 - 127), kv); sts16(rb + R_E3 + 2 * (159 - 127) + RS_CS + 2, kv);
      }
    }
  }
  STAMP(5);
  asm volatile("barrier.cluster.wait.aligned;" ::: "memory");
  bar_sync(7 + (warp >> 1), 64);
  mbar_wait(sb + B_U);
  STAMP(6);

  const uint32_t zz = lds32(cb + R_OFF + br * R_BR);
  conv_dense(sb, cb, zz);
  STAMP(8);
  {
    const int x = (4 + ch) * 128 + wtid, c = x >> 2;
    const uint2 dA = ldg64(p.A_D + bid * 4), dB = ldg64(p.B_D + bid * 4);
    const uint2 gl = gate_ld(x);
    const uint32_t rb = cb + R_OFF + br * R_BR;
    float e48[24], e40[20], e32[16], h32[16], h16[8];
    const int x1 = 159 - (16 * hf + g - 2 * t + 136);
    const uint32_t fs = rb + ((g & 1) ? 2 * x1 : RS_CS + 2 * x1 + 2);
    uint32_t A[2][4][4];
    auto loadA = [&](int buf, uint32_t oe, uint32_t oo, int i0) {
#pragma unroll
      for (int a = 0; a < 2; a++) {
        const uint32_t base = fs + (a ? oo : oe) + i0 * 16;
        uint32_t* k0 = A[buf][2 * a];
        uint32_t* k1 = A[buf][2 * a + 1];
        k0[1] = lds32(base); k0[0] = lds32(base + 16); k0[2] = lds32(base + 32); k1[0] = lds32(base + 48); k1[2] = lds32(base + 64);
        k0[3] = k0[0]; k1[1] = k0[2]; k1[3] = k1[0];
      }
    };
    loadA(0, R_E2, R_O2, 8);
    loadA(1, R_E2, R_O2, 4);
    mbar_wait(sb + B_W);
    const uint64_t d5 = mkdesc(cb + W5_OFF, 144, 576), d3 = mkdesc(cb + W3_OFF, 144, 576);
    const uint64_t d9 = mkdesc(cb + W9_OFF, 144, 576), d7 = mkdesc(cb + W7_OFF, 144, 576);
    const uint32_t y2d = cb + Y2_OFF + br * 3072 + ysw(32 * (5 - (lane >> 4)) + 16 * hf + (lane & 15));
    const uint32_t y3d = cb + Y3_OFF + br * 2048 + ysw(2 * (16 * hf + (lane & 15)) + (lane >> 4));
#define FAR4(N, ACC, BUF, DA, DB, OFF, FIRST)                                                            \
    wg_fence();                                                                                           \
    _Pragma("unroll") for (int k = 0; k < 4; k++) {                                                      \
      const uint32_t* a = A[BUF][k];                                                                      \
      wgmma_rs<N, 1>(ACC, a[0], a[1], a[2], a[3], ((k >> 1) ? DB : DA) + (k & 1) * 18 + (OFF), !(FIRST) || k); \
    }                                                                                                     \
    wg_commit();
    FAR4(48, e48, 0, d5, d3, 0, 1)
    wg_wait0();
    loadA(0, R_E2, R_O2, 0);
    stsm2(y2d - 5 * 512, PK2(e48, 20), PK2(e48, 22));
#pragma unroll
    for (int i = 0; i < 20; i++) e40[i] = FCPY(e48, i);
    stage_done(sb, 2, lane);
    FAR4(40, e40, 1, d5, d3, 36, 0)
    wg_wait0();
    loadA(1, R_E3, R_O3, 8);
    stsm2(y2d - 4 * 512, PK2(e40, 16), PK2(e40, 18));
#pragma unroll
    for (int i = 0; i < 16; i++) e32[i] = FCPY(e40, i);
    stage_done(sb, 3, lane);
    FAR4(32, e32, 0, d5, d3, 72, 0)
    FAR4(32, h32, 1, d9, d7, 0, 1)
    wg_wait1();
    loadA(0, R_E3, R_O3, 4);
    stsm4(y2d, PK2(e32, 0), PK2(e32, 2), PK2(e32, 4), PK2(e32, 6));
    stsm4(y2d - 2 * 512, PK2(e32, 8), PK2(e32, 10), PK2(e32, 12), PK2(e32, 14));
    stage_done(sb, 4, lane);
    STAMP(9);
    wg_wait0();
    stsm4(y3d, PK2(h32, 8), PK2(h32, 10), PK2(h32, 12), PK2(h32, 14));
#pragma unroll
    for (int i = 0; i < 8; i++) h16[i] = FCPY(h32, i);
    stage_done(sb, 5, lane);
    FAR4(16, h16, 0, d9, d7, 72, 0)
#undef FAR4
    const uint32_t yo = sb + CH_OFF + (x & 3) * 4 + ysw(c);
    uint32_t ua[4], ub[4], ya[4], yb[4], a2[4], b2[4], a3[4], b3[4], s2[4];
    skip_terms(ua, ub, sb, x, dA, dB);
    {
      const int xa = x - 514, xb = x - 513, ca = xa >> 2, cb2 = xb >> 2;
      ld4ch(s2, sb + CH_OFF + U_OFF + (xa & 3) * 4 + (ca & 3) * U_CS + (63 - (ca >> 2)) * 16);
      ld4ch(a3, sb + CH_OFF + U_OFF + (xb & 3) * 4 + (cb2 & 3) * U_CS + (63 - (cb2 >> 2)) * 16);
#pragma unroll
      for (int k = 0; k < 4; k++) s2[k] = hadd2(s2[k], __byte_perm(s2[k], a3[k], 0x5432));
    }
    const uint32_t tag = lds32(sb + TAG_OFF);
    wg_wait0();
    stsm4(y3d + 1024, PK2(h16, 0), PK2(h16, 2), PK2(h16, 4), PK2(h16, 6));
    stage_done(sb, 6, lane);
    STAMP(10);
    const uint32_t g2 = gate_fin(p, gl, x, tag);
    mbar_wait(sb + B_ST + 8 * 4);
    const uint4 k0 = lds128(sb + K1024_OFF), k1 = lds128(sb + K1024_OFF + 16);
    const uint32_t kk[8] = {k0.x, k0.y, k0.z, k0.w, k1.x, k1.y, k1.z, k1.w};
    ld4ch(ya, yo + Y0_OFF); ld4ch(yb, yo + Y0_OFF + 4096);
    ld4ch(a2, yo + Y2_OFF - 1024); ld4ch(b2, yo + Y2_OFF - 1024 + 3072);
    mbar_wait(sb + B_ST + 8 * (5 + (ch >> 1)));
    STAMP(12);
    ld4ch(a3, yo + Y3_OFF - 2048); ld4ch(b3, yo + Y3_OFF - 2048 + 2048);
#pragma unroll
    for (int k = 0; k < 4; k++) {
      ya[k] = hadd2(ya[k], hadd2(hfma2(kk[2 * k], s2[k], a2[k]), a3[k]));
      yb[k] = hadd2(yb[k], hadd2(hfma2(kk[2 * k + 1], s2[k], b2[k]), b3[k]));
    }
    const uint4 r = mix(ya, yb, ua, ub, g2);
    if ((uint32_t)(ch & 1) != rank) send_box(sb, 2 + (ch >> 1), wtid, rank, r);
    else merge_box(sb, &tm_out, 2 + (ch >> 1), wtid, rank, oc0, r, 1 + ch);
  }
  STAMP(14);
  if (wtid == 0) asm volatile("cp.async.bulk.wait_group.read 0;" ::: "memory");
  STAMP(15); GT(1);
}

typedef CUresult (*EncodeFn)(CUtensorMap*, CUtensorMapDataType, cuuint32_t, void*, const cuuint64_t*, const cuuint64_t*,
                             const cuuint32_t*, const cuuint32_t*, CUtensorMapInterleave, CUtensorMapSwizzle,
                             CUtensorMapL2promotion, CUtensorMapFloatOOBfill);

}

extern "C" void kernel_launch(void* const* d_in, const int* in_sizes, int n_in, void* d_out, int out_size) {
  (void)in_sizes; (void)n_in; (void)out_size;
  typedef const __nv_bfloat16* bp;
  Params p;
  p.t[0] = (bp)d_in[10]; p.t[1] = (bp)d_in[11]; p.t[2] = (bp)d_in[12]; p.t[3] = (bp)d_in[13]; p.t[4] = (bp)d_in[14]; p.t[5] = nullptr;
  p.t[6] = (bp)d_in[1]; p.t[7] = (bp)d_in[2]; p.t[8] = (bp)d_in[5]; p.t[9] = (bp)d_in[6]; p.t[10] = (bp)d_in[7];
  p.t[11] = (bp)d_in[3]; p.t[12] = (bp)d_in[4]; p.t[13] = nullptr;
  p.u = (bp)d_in[0]; p.gw = (bp)d_in[16]; p.A_D = (bp)d_in[8]; p.B_D = (bp)d_in[15];
  static EncodeFn enc = nullptr;
  if (!enc) {
    cudaDriverEntryPointQueryResult qr;
    cudaGetDriverEntryPoint("cuTensorMapEncodeTiled", (void**)&enc, cudaEnableDefault, &qr);
    cudaFuncSetAttribute(ssm_kernel, cudaFuncAttributeMaxDynamicSharedMemorySize, SMEM_BYTES);
  }
  CUtensorMap tm_in, tm_out;
  {
    cuuint64_t gd[5] = {512, 2, 4, 4, 64};
    cuuint64_t gs[4] = {1024, 8192, 2048, 32768};
    cuuint32_t bx[5] = {8, 2, 4, 4, 8};
    cuuint32_t es[5] = {1, 1, 1, 1, 1};
    enc(&tm_in, CU_TENSOR_MAP_DATA_TYPE_BFLOAT16, 5, d_in[0], gd, gs, bx, es, CU_TENSOR_MAP_INTERLEAVE_NONE,
        CU_TENSOR_MAP_SWIZZLE_NONE, CU_TENSOR_MAP_L2_PROMOTION_NONE, CU_TENSOR_MAP_FLOAT_OOB_FILL_NONE);
  }
  {
    cuuint64_t gd[3] = {512, 1024, 2};
    cuuint64_t gs[2] = {2048, 1024};
    cuuint32_t bx[3] = {8, 128, 2};
    cuuint32_t es[3] = {1, 1, 1};
    enc(&tm_out, CU_TENSOR_MAP_DATA_TYPE_BFLOAT16, 3, d_out, gd, gs, bx, es, CU_TENSOR_MAP_INTERLEAVE_NONE,
        CU_TENSOR_MAP_SWIZZLE_NONE, CU_TENSOR_MAP_L2_PROMOTION_NONE, CU_TENSOR_MAP_FLOAT_OOB_FILL_NONE);
  }
  ssm_kernel<<<NCTA + NGATE, 640, SMEM_BYTES, cudaStreamPerThread>>>(p, tm_in, tm_out);
}
```

```cpp
#include <cuda_runtime.h>
#include <cuda.h>
#include <cuda_bf16.h>
#include <stdint.h>

namespace {
#define FCPY(v, i) (((i) % 3 == 2) ? __uint_as_float(opq(__float_as_uint(v[i]), zz)) : opqf(v[i], zz))

constexpr int L = 2048, D = 512, NM = 128;
constexpr int NCTA = 128;
constexpr int NGATE = 4;

constexpr int RAW_OFF = 0;
constexpr int XIN_OFF = 32768;
constexpr int SC2_OFF = XIN_OFF + 8192;
constexpr int BAR_OFF = SC2_OFF + 10240;
constexpr int CH_OFF = BAR_OFF + 256;
constexpr int U_CS = 1184;
constexpr int U_OFF = 0;
constexpr int R_OFF = 4736;
constexpr int RD_X0 = 565;
constexpr int RD_CS = 1216;
constexpr int RS_CS = 320;
constexpr int R_E2 = 2 * RD_CS, R_O2 = R_E2 + 2 * RS_CS, R_E3 = R_O2 + 2 * RS_CS, R_O3 = R_E3 + 2 * RS_CS;
constexpr int R_BR = R_O3 + 2 * RS_CS;
constexpr int W5_OFF = R_OFF + 2 * R_BR;
constexpr int W3_OFF = W5_OFF + 3456;
constexpr int W9_OFF = W3_OFF + 3456;
constexpr int W7_OFF = W9_OFF + 2304;
constexpr int Y0_OFF = W7_OFF + 2304;
constexpr int Y2_OFF = Y0_OFF + 8192, Y3_OFF = Y2_OFF + 6144;
constexpr int CH_BYTES = Y0_OFF + 18432 + 16;
constexpr int SCR_BYTES = 4608;
constexpr int SMEM_BYTES = CH_OFF + 4 * CH_BYTES;
static_assert(CH_BYTES % 128 == 16, "bank staggering of the channel blocks");
static_assert(SMEM_BYTES <= 232448, "smem");
constexpr int B_RAW = BAR_OFF, B_X = BAR_OFF + 8, B_U = BAR_OFF + 40, B_W = BAR_OFF + 48;
constexpr int TAG_OFF = BAR_OFF + 56;
constexpr int K1024_OFF = BAR_OFF + 64;
constexpr int B_ST = BAR_OFF + 96;

__device__ unsigned int g_gate[L];
__device__ unsigned int g_epoch;
__device__ unsigned int g_ticket;

#define STAMP(k)
#define GT(k)

struct Params {
  const __nv_bfloat16* t[14];
  const __nv_bfloat16 *u, *gw, *A_D, *B_D;
};

template <int N, int TB> __device__ __forceinline__ void wgmma_rs(float* d, uint32_t a0, uint32_t a1, uint32_t a2, uint32_t a3, uint64_t desc, int sc);
template <> __device__ __forceinline__ void wgmma_rs<64, 0>(float* d, uint32_t a0, uint32_t a1, uint32_t a2, uint32_t a3, uint64_t desc, int sc) {
  asm volatile("{\n.reg .pred p;\nsetp.ne.b32 p, %37, 0;\n"
    "wgmma.mma_async.sync.aligned.m64n64k16.f32.bf16.bf16 {%0,%1,%2,%3,%4,%5,%6,%7,%8,%9,%10,%11,%12,%13,%14,%15,%16,%17,%18,%19,%20,%21,%22,%23,%24,%25,%26,%27,%28,%29,%30,%31}, {%32,%33,%34,%35}, %36, p, 1, 1, 0;\n}"
    : "+f"(d[0]), "+f"(d[1]), "+f"(d[2]), "+f"(d[3]), "+f"(d[4]), "+f"(d[5]), "+f"(d[6]), "+f"(d[7]), "+f"(d[8]), "+f"(d[9]), "+f"(d[10]), "+f"(d[11]), "+f"(d[12]), "+f"(d[13]), "+f"(d[14]), "+f"(d[15]), "+f"(d[16]), "+f"(d[17]), "+f"(d[18]), "+f"(d[19]), "+f"(d[20]), "+f"(d[21]), "+f"(d[22]), "+f"(d[23]), "+f"(d[24]), "+f"(d[25]), "+f"(d[26]), "+f"(d[27]), "+f"(d[28]), "+f"(d[29]), "+f"(d[30]), "+f"(d[31]) : "r"(a0), "r"(a1), "r"(a2), "r"(a3), "l"(desc), "r"(sc));
}
template <> __device__ __forceinline__ void wgmma_rs<56, 0>(float* d, uint32_t a0, uint32_t a1, uint32_t a2, uint32_t a3, uint64_t desc, int sc) {
  asm volatile("{\n.reg .pred p;\nsetp.ne.b32 p, %33, 0;\n"
    "wgmma.mma_async.sync.aligned.m64n56k16.f32.bf16.bf16 {%0,%1,%2,%3,%4,%5,%6,%7,%8,%9,%10,%11,%12,%13,%14,%15,%16,%17,%18,%19,%20,%21,%22,%23,%24,%25,%26,%27}, {%28,%29,%30,%31}, %32, p, 1, 1, 0;\n}"
    : "+f"(d[0]), "+f"(d[1]), "+f"(d[2]), "+f"(d[3]), "+f"(d[4]), "+f"(d[5]), "+f"(d[6]), "+f"(d[7]), "+f"(d[8]), "+f"(d[9]), "+f"(d[10]), "+f"(d[11]), "+f"(d[12]), "+f"(d[13]), "+f"(d[14]), "+f"(d[15]), "+f"(d[16]), "+f"(d[17]), "+f"(d[18]), "+f"(d[19]), "+f"(d[20]), "+f"(d[21]), "+f"(d[22]), "+f"(d[23]), "+f"(d[24]), "+f"(d[25]), "+f"(d[26]), "+f"(d[27]) : "r"(a0), "r"(a1), "r"(a2), "r"(a3), "l"(desc), "r"(sc));
}
template <> __device__ __forceinline__ void wgmma_rs<48, 0>(float* d, uint32_t a0, uint32_t a1, uint32_t a2, uint32_t a3, uint64_t desc, int sc) {
  asm volatile("{\n.reg .pred p;\nsetp.ne.b32 p, %29, 0;\n"
    "wgmma.mma_async.sync.aligned.m64n48k16.f32.bf16.bf16 {%0,%1,%2,%3,%4,%5,%6,%7,%8,%9,%10,%11,%12,%13,%14,%15,%16,%17,%18,%19,%20,%21,%22,%23}, {%24,%25,%26,%27}, %28, p, 1, 1, 0;\n}"
    : "+f"(d[0]), "+f"(d[1]), "+f"(d[2]), "+f"(d[3]), "+f"(d[4]), "+f"(d[5]), "+f"(d[6]), "+f"(d[7]), "+f"(d[8]), "+f"(d[9]), "+f"(d[10]), "+f"(d[11]), "+f"(d[12]), "+f"(d[13]), "+f"(d[14]), "+f"(d[15]), "+f"(d[16]), "+f"(d[17]), "+f"(d[18]), "+f"(d[19]), "+f"(d[20]), "+f"(d[21]), "+f"(d[22]), "+f"(d[23]) : "r"(a0), "r"(a1), "r"(a2), "r"(a3), "l"(desc), "r"(sc));
}
template <> __device__ __forceinline__ void wgmma_rs<32, 0>(float* d, uint32_t a0, uint32_t a1, uint32_t a2, uint32_t a3, uint64_t desc, int sc) {
  asm volatile("{\n.reg .pred p;\nsetp.ne.b32 p, %21, 0;\n"
    "wgmma.mma_async.sync.aligned.m64n32k16.f32.bf16.bf16 {%0,%1,%2,%3,%4,%5,%6,%7,%8,%9,%10,%11,%12,%13,%14,%15}, {%16,%17,%18,%19}, %20, p, 1, 1, 0;\n}"
    : "+f"(d[0]), "+f"(d[1]), "+f"(d[2]), "+f"(d[3]), "+f"(d[4]), "+f"(d[5]), "+f"(d[6]), "+f"(d[7]), "+f"(d[8]), "+f"(d[9]), "+f"(d[10]), "+f"(d[11]), "+f"(d[12]), "+f"(d[13]), "+f"(d[14]), "+f"(d[15]) : "r"(a0), "r"(a1), "r"(a2), "r"(a3), "l"(desc), "r"(sc));
}
template <> __device__ __forceinline__ void wgmma_rs<48, 1>(float* d, uint32_t a0, uint32_t a1, uint32_t a2, uint32_t a3, uint64_t desc, int sc) {
  asm volatile("{\n.reg .pred p;\nsetp.ne.b32 p, %29, 0;\n"
    "wgmma.mma_async.sync.aligned.m64n48k16.f32.bf16.bf16 {%0,%1,%2,%3,%4,%5,%6,%7,%8,%9,%10,%11,%12,%13,%14,%15,%16,%17,%18,%19,%20,%21,%22,%23}, {%24,%25,%26,%27}, %28, p, 1, 1, 1;\n}"
    : "+f"(d[0]), "+f"(d[1]), "+f"(d[2]), "+f"(d[3]), "+f"(d[4]), "+f"(d[5]), "+f"(d[6]), "+f"(d[7]), "+f"(d[8]), "+f"(d[9]), "+f"(d[10]), "+f"(d[11]), "+f"(d[12]), "+f"(d[13]), "+f"(d[14]), "+f"(d[15]), "+f"(d[16]), "+f"(d[17]), "+f"(d[18]), "+f"(d[19]), "+f"(d[20]), "+f"(d[21]), "+f"(d[22]), "+f"(d[23]) : "r"(a0), "r"(a1), "r"(a2), "r"(a3), "l"(desc), "r"(sc));
}
template <> __device__ __forceinline__ void wgmma_rs<40, 1>(float* d, uint32_t a0, uint32_t a1, uint32_t a2, uint32_t a3, uint64_t desc, int sc) {
  asm volatile("{\n.reg .pred p;\nsetp.ne.b32 p, %25, 0;\n"
    "wgmma.mma_async.sync.aligned.m64n40k16.f32.bf16.bf16 {%0,%1,%2,%3,%4,%5,%6,%7,%8,%9,%10,%11,%12,%13,%14,%15,%16,%17,%18,%19}, {%20,%21,%22,%23}, %24, p, 1, 1, 1;\n}"
    : "+f"(d[0]), "+f"(d[1]), "+f"(d[2]), "+f"(d[3]), "+f"(d[4]), "+f"(d[5]), "+f"(d[6]), "+f"(d[7]), "+f"(d[8]), "+f"(d[9]), "+f"(d[10]), "+f"(d[11]), "+f"(d[12]), "+f"(d[13]), "+f"(d[14]), "+f"(d[15]), "+f"(d[16]), "+f"(d[17]), "+f"(d[18]), "+f"(d[19]) : "r"(a0), "r"(a1), "r"(a2), "r"(a3), "l"(desc), "r"(sc));
}
template <> __device__ __forceinline__ void wgmma_rs<32, 1>(float* d, uint32_t a0, uint32_t a1, uint32_t a2, uint32_t a3, uint64_t desc, int sc) {
  asm volatile("{\n.reg .pred p;\nsetp.ne.b32 p, %21, 0;\n"
    "wgmma.mma_async.sync.aligned.m64n32k16.f32.bf16.bf16 {%0,%1,%2,%3,%4,%5,%6,%7,%8,%9,%10,%11,%12,%13,%14,%15}, {%16,%17,%18,%19}, %20, p, 1, 1, 1;\n}"
    : "+f"(d[0]), "+f"(d[1]), "+f"(d[2]), "+f"(d[3]), "+f"(d[4]), "+f"(d[5]), "+f"(d[6]), "+f"(d[7]), "+f"(d[8]), "+f"(d[9]), "+f"(d[10]), "+f"(d[11]), "+f"(d[12]), "+f"(d[13]), "+f"(d[14]), "+f"(d[15]) : "r"(a0), "r"(a1), "r"(a2), "r"(a3), "l"(desc), "r"(sc));
}
template <> __device__ __forceinline__ void wgmma_rs<16, 1>(float* d, uint32_t a0, uint32_t a1, uint32_t a2, uint32_t a3, uint64_t desc, int sc) {
  asm volatile("{\n.reg .pred p;\nsetp.ne.b32 p, %13, 0;\n"
    "wgmma.mma_async.sync.aligned.m64n16k16.f32.bf16.bf16 {%0,%1,%2,%3,%4,%5,%6,%7}, {%8,%9,%10,%11}, %12, p, 1, 1, 1;\n}"
    : "+f"(d[0]), "+f"(d[1]), "+f"(d[2]), "+f"(d[3]), "+f"(d[4]), "+f"(d[5]), "+f"(d[6]), "+f"(d[7]) : "r"(a0), "r"(a1), "r"(a2), "r"(a3), "l"(desc), "r"(sc));
}

__device__ __forceinline__ uint32_t pack_bf16(float lo, float hi) {
  uint32_t r; asm("cvt.rn.bf16x2.f32 %0, %1, %2;" : "=r"(r) : "f"(hi), "f"(lo)); return r;
}
__device__ __forceinline__ float bf_lo(uint32_t v) { return __uint_as_float(v << 16); }
__device__ __forceinline__ float bf_hi(uint32_t v) { return __uint_as_float(v & 0xffff0000u); }
__device__ __forceinline__ float bf_round(float x) { return bf_lo(pack_bf16(x, 0.f)); }
__device__ __forceinline__ uint32_t hmul2(uint32_t a, uint32_t b) { uint32_t r; asm("mul.rn.bf16x2 %0, %1, %2;" : "=r"(r) : "r"(a), "r"(b)); return r; }
__device__ __forceinline__ uint32_t hadd2(uint32_t a, uint32_t b) { uint32_t r; asm("add.rn.bf16x2 %0, %1, %2;" : "=r"(r) : "r"(a), "r"(b)); return r; }
__device__ __forceinline__ uint32_t hsub2(uint32_t a, uint32_t b) { uint32_t r; asm("sub.rn.bf16x2 %0, %1, %2;" : "=r"(r) : "r"(a), "r"(b)); return r; }
__device__ __forceinline__ uint32_t hfma2(uint32_t a, uint32_t b, uint32_t c) { uint32_t r; asm("fma.rn.bf16x2 %0, %1, %2, %3;" : "=r"(r) : "r"(a), "r"(b), "r"(c)); return r; }

__device__ __forceinline__ void sts16(uint32_t a, uint32_t v) { asm volatile("st.shared.b16 [%0], %1;" ::"r"(a), "h"((unsigned short)v) : "memory"); }
__device__ __forceinline__ void sts32(uint32_t a, uint32_t v) { asm volatile("st.shared.b32 [%0], %1;" ::"r"(a), "r"(v) : "memory"); }
__device__ __forceinline__ void sts64(uint32_t a, uint32_t x, uint32_t y) { asm volatile("st.shared.v2.b32 [%0], {%1,%2};" ::"r"(a), "r"(x), "r"(y) : "memory"); }
__device__ __forceinline__ void sts128(uint32_t a, uint32_t x, uint32_t y, uint32_t z, uint32_t w) {
  asm volatile("st.shared.v4.b32 [%0], {%1,%2,%3,%4};" ::"r"(a), "r"(x), "r"(y), "r"(z), "r"(w) : "memory");
}
__device__ __forceinline__ uint32_t lds32(uint32_t a) { uint32_t v; asm volatile("ld.shared.b32 %0, [%1];" : "=r"(v) : "r"(a) : "memory"); return v; }
__device__ __forceinline__ uint4 lds128(uint32_t a) {
  uint4 v; asm volatile("ld.shared.v4.b32 {%0,%1,%2,%3}, [%4];" : "=r"(v.x), "=r"(v.y), "=r"(v.z), "=r"(v.w) : "r"(a) : "memory"); return v;
}
__device__ __forceinline__ uint4 ldg128(const void* a) {
  uint4 v; asm volatile("ld.global.nc.v4.b32 {%0,%1,%2,%3}, [%4];" : "=r"(v.x), "=r"(v.y), "=r"(v.z), "=r"(v.w) : "l"(a) : "memory"); return v;
}
__device__ __forceinline__ uint2 ldg64(const void* a) {
  uint2 v; asm volatile("ld.global.nc.v2.b32 {%0,%1}, [%2];" : "=r"(v.x), "=r"(v.y) : "l"(a) : "memory"); return v;
}
__device__ __forceinline__ void ldsm4(uint32_t a, uint32_t& r0, uint32_t& r1, uint32_t& r2, uint32_t& r3) {
  asm volatile("ldmatrix.sync.aligned.m8n8.x4.shared.b16 {%0,%1,%2,%3}, [%4];" : "=r"(r0), "=r"(r1), "=r"(r2), "=r"(r3) : "r"(a) : "memory");
}
__device__ __forceinline__ void ldsm4t(uint32_t a, uint32_t& r0, uint32_t& r1, uint32_t& r2, uint32_t& r3) {
  asm volatile("ldmatrix.sync.aligned.m8n8.x4.trans.shared.b16 {%0,%1,%2,%3}, [%4];" : "=r"(r0), "=r"(r1), "=r"(r2), "=r"(r3) : "r"(a) : "memory");
}
__device__ __forceinline__ void stsm4(uint32_t a, uint32_t r0, uint32_t r1, uint32_t r2, uint32_t r3) {
  asm volatile("stmatrix.sync.aligned.m8n8.x4.shared.b16 [%0], {%1,%2,%3,%4};" ::"r"(a), "r"(r0), "r"(r1), "r"(r2), "r"(r3) : "memory");
}
__device__ __forceinline__ void stsm4t(uint32_t a, uint32_t r0, uint32_t r1, uint32_t r2, uint32_t r3) {
  asm volatile("stmatrix.sync.aligned.m8n8.x4.trans.shared.b16 [%0], {%1,%2,%3,%4};" ::"r"(a), "r"(r0), "r"(r1), "r"(r2), "r"(r3) : "memory");
}
__device__ __forceinline__ void stsm2(uint32_t a, uint32_t r0, uint32_t r1) {
  asm volatile("stmatrix.sync.aligned.m8n8.x2.shared.b16 [%0], {%1,%2};" ::"r"(a), "r"(r0), "r"(r1) : "memory");
}
__device__ __forceinline__ void stsm2t(uint32_t a, uint32_t r0, uint32_t r1) {
  asm volatile("stmatrix.sync.aligned.m8n8.x2.trans.shared.b16 [%0], {%1,%2};" ::"r"(a), "r"(r0), "r"(r1) : "memory");
}
__device__ __forceinline__ void mma16816(float* c, uint32_t a0, uint32_t a1, uint32_t a2, uint32_t a3, uint32_t b0, uint32_t b1) {
  asm("mma.sync.aligned.m16n8k16.row.col.f32.bf16.bf16.f32 {%0,%1,%2,%3}, {%4,%5,%6,%7}, {%8,%9}, {%0,%1,%2,%3};"
      : "+f"(c[0]), "+f"(c[1]), "+f"(c[2]), "+f"(c[3]) : "r"(a0), "r"(a1), "r"(a2), "r"(a3), "r"(b0), "r"(b1));
}
__device__ __forceinline__ void bar_sync(int id, int n) { asm volatile("bar.sync %0, %1;" ::"r"(id), "r"(n) : "memory"); }
__device__ __forceinline__ void wg_fence() { asm volatile("wgmma.fence.sync.aligned;" ::: "memory"); }
__device__ __forceinline__ void wg_commit() { asm volatile("wgmma.commit_group.sync.aligned;" ::: "memory"); }
__device__ __forceinline__ void wg_wait0() { asm volatile("wgmma.wait_group.sync.aligned 0;" ::: "memory"); }
__device__ __forceinline__ void wg_wait1() { asm volatile("wgmma.wait_group.sync.aligned 1;" ::: "memory"); }
__device__ __forceinline__ void fence_async() { asm volatile("fence.proxy.async.shared::cta;" ::: "memory"); }
__device__ __forceinline__ uint32_t opq(uint32_t x, uint32_t z) { uint32_t r; asm volatile("xor.b32 %0, %1, %2;" : "=r"(r) : "r"(x), "r"(z)); return r; }
__device__ __forceinline__ float opqf(float x, uint32_t z) { float r; asm volatile("add.rn.f32 %0, %1, %2;" : "=f"(r) : "f"(x), "f"(__uint_as_float(z))); return r; }
__device__ __forceinline__ uint64_t mkdesc(uint32_t addr, uint32_t lbo, uint32_t sbo) {
  return (uint64_t)((addr & 0x3FFFF) >> 4) | ((uint64_t)(lbo >> 4) << 16) | ((uint64_t)(sbo >> 4) << 32);
}
__device__ __forceinline__ uint32_t mapa(uint32_t a, uint32_t rank) {
  uint32_t r; asm("mapa.shared::cluster.u32 %0, %1, %2;" : "=r"(r) : "r"(a), "r"(rank)); return r;
}
__device__ __forceinline__ void mbar_init_expect(uint32_t bar, uint32_t bytes) {
  asm volatile("mbarrier.init.shared::cta.b64 [%0], 1;" ::"r"(bar) : "memory");
  asm volatile("mbarrier.arrive.expect_tx.shared::cta.b64 _, [%0], %1;" ::"r"(bar), "r"(bytes) : "memory");
}
__device__ __forceinline__ void mbar_wait(uint32_t bar) {
#pragma unroll 1
  for (int it = 0; it < (1 << 22); it++) {
    uint32_t ok;
    asm volatile("{\n.reg .pred p;\nmbarrier.try_wait.parity.acquire.cluster.shared::cta.b64 p, [%1], 0;\nselp.u32 %0, 1, 0, p;\n}"
                 : "=r"(ok) : "r"(bar) : "memory");
    if (ok) return;
  }
  __trap();
}
__device__ __forceinline__ void st_async4(uint32_t a, uint32_t bar, uint32_t x, uint32_t y, uint32_t z, uint32_t w) {
  asm volatile("st.async.weak.shared::cluster.mbarrier::complete_tx::bytes.v4.b32 [%0], {%2,%3,%4,%5}, [%1];"
               ::"r"(a), "r"(bar), "r"(x), "r"(y), "r"(z), "r"(w) : "memory");
}

struct cf { float re, im; };
__device__ __forceinline__ cf cmul(cf a, cf b) { return {fmaf(a.re, b.re, -a.im * b.im), fmaf(a.re, b.im, a.im * b.re)}; }
__device__ __forceinline__ cf csq(cf a) { return {fmaf(a.re, a.re, -a.im * a.im), (a.re + a.re) * a.im}; }
__device__ __forceinline__ cf cexp_p(float xl, float y, float p) {
  float mag; asm("ex2.approx.ftz.f32 %0, %1;" : "=f"(mag) : "f"(xl * p));
  const float th = y * p;
  const float k = __fadd_rn(fmaf(th, 0.15915494309189535f, 12582912.f), -12582912.f);
  float r = fmaf(k, -6.2831854820251465f, th);
  r = fmaf(k, 1.7484555314695172e-07f, r);
  return {mag * __cosf(r), mag * __sinf(r)};
}
__device__ __forceinline__ uint32_t ysw(int c) { return (uint32_t)(c ^ ((c >> 3) & 3)) * 16u; }

#define CMUL2(OR, OI, xr, xi, yr, yi, nyi) do { OR = hfma2(xr, yr, hmul2(xi, nyi)); OI = hfma2(xr, yi, hmul2(xi, yr)); } while (0)

__device__ __forceinline__ uint32_t gate_slow(const __nv_bfloat16* u, const __nv_bfloat16* gw, int row) {
  float s = 0.f;
  const uint32_t* xr = (const uint32_t*)(u + (size_t)row * D);
  const uint32_t* wr = (const uint32_t*)gw;
#pragma unroll 1
  for (int j = 0; j < D / 2; j++) { const uint32_t pr = hmul2(xr[j], wr[j]); s += bf_lo(pr); s += bf_hi(pr); }
  s = bf_round(s);
  return pack_bf16(1.f / (1.f + expf(-s)), 0.f);
}

__device__ __forceinline__ uint2 gate_ld(int x) {
  uint2 gv;
  asm volatile("ld.relaxed.gpu.global.v2.u32 {%0,%1}, [%2];" : "=r"(gv.x), "=r"(gv.y) : "l"(g_gate + x * 2) : "memory");
  return gv;
}
__device__ __noinline__ uint32_t gate_poll(const Params* pp, int x, uint32_t tag) {
  uint2 gv;
#pragma unroll 1
  for (int spins = 0; spins < (1 << 16); spins++) {
    gv = gate_ld(x);
    if ((gv.x >> 16) == tag && (gv.y >> 16) == tag) return __byte_perm(gv.x, gv.y, 0x5410);
  }
  return __byte_perm(gate_slow(pp->u, pp->gw, x * 2), gate_slow(pp->u, pp->gw, x * 2 + 1), 0x5410);
}
__device__ __forceinline__ uint32_t gate_fin(const Params& p, uint2 gv, int x, uint32_t tag) {
  if ((gv.x >> 16) == tag && (gv.y >> 16) == tag) return __byte_perm(gv.x, gv.y, 0x5410);
  return gate_poll(&p, x, tag);
}

__device__ __forceinline__ void ld4ch(uint32_t* v, uint32_t addr) {
#pragma unroll
  for (int k = 0; k < 4; k++) v[k] = lds32(addr + k * CH_BYTES);
}
__device__ __forceinline__ void skip_terms(uint32_t* ua, uint32_t* ub, uint32_t sb, int x, uint2 dA, uint2 dB) {
  const int c = x >> 2;
  uint32_t uu[4];
  ld4ch(uu, sb + CH_OFF + (x & 3) * 4 + U_OFF + (c & 3) * U_CS + (63 - (c >> 2)) * 16);
#pragma unroll
  for (int k = 0; k < 4; k++) {
    ua[k] = hmul2(uu[k], __byte_perm((k & 2) ? dA.y : dA.x, 0, (k & 1) ? 0x3232 : 0x1010));
    ub[k] = hmul2(uu[k], __byte_perm((k & 2) ? dB.y : dB.x, 0, (k & 1) ? 0x3232 : 0x1010));
  }
}
__device__ __forceinline__ uint4 mix(const uint32_t* a, const uint32_t* b, const uint32_t* ua, const uint32_t* ub, uint32_t g2) {
  const uint32_t h2 = hsub2(0x3f803f80u, g2);
  uint32_t o[4];
#pragma unroll
  for (int k = 0; k < 4; k++) o[k] = hadd2(hmul2(g2, hadd2(a[k], ua[k])), hmul2(h2, hadd2(b[k], ub[k])));
  return make_uint4(__byte_perm(o[0], o[1], 0x5410), __byte_perm(o[2], o[3], 0x5410), __byte_perm(o[0], o[1], 0x7632), __byte_perm(o[2], o[3], 0x7632));
}
__device__ __forceinline__ void send_box(uint32_t sb, int slot, int wtid, uint32_t rank, uint4 r) {
  st_async4(mapa(sb + XIN_OFF + slot * 2048 + wtid * 16, rank ^ 1), mapa(sb + B_X + slot * 8, rank ^ 1), r.x, r.y, r.z, r.w);
}
__device__ __forceinline__ void merge_rows(uint32_t st, uint32_t rank, uint4 r, uint4 q) {
  const uint4 lo = rank ? q : r, hi = rank ? r : q;
  sts128(st, lo.x, lo.y, hi.x, hi.y); sts128(st + 2048, lo.z, lo.w, hi.z, hi.w);
}
__device__ __forceinline__ void merge_box(uint32_t sb, const CUtensorMap* tm_out, int slot, int wtid, uint32_t rank, int oc0, uint4 r, int barid) {
  const uint32_t st = sb + RAW_OFF + slot * 4096 + wtid * 16;
  mbar_wait(sb + B_X + slot * 8);
  merge_rows(st, rank, r, lds128(sb + XIN_OFF + slot * 2048 + wtid * 16));
  fence_async();
  bar_sync(barid, 128);
  if (wtid == 0) {
    asm volatile("cp.async.bulk.tensor.3d.global.shared::cta.bulk_group [%0, {%2, %3, %4}], [%1];"
                 ::"l"(tm_out), "r"(sb + RAW_OFF + slot * 4096), "r"(oc0), "r"((2 * slot + (int)rank) * 128), "r"(0) : "memory");
    asm volatile("cp.async.bulk.commit_group;" ::: "memory");
  }
}

__device__ __forceinline__ uint32_t band2(int e, int lo, int hi) {
  uint32_t r = ((uint32_t)(e - lo) <= (uint32_t)(hi - lo) ? 0x3f80u : 0u) | ((uint32_t)(e - 1 - lo) <= (uint32_t)(hi - lo) ? 0x3f800000u : 0u);
  asm volatile("" : "+r"(r));
  return r;
}

__device__ __forceinline__ void stage_done(uint32_t sb, int stage, int lane) {
  __syncwarp();
  if (lane == 0) asm volatile("mbarrier.arrive.shared::cta.b64 _, [%0];" ::"r"(sb + B_ST + 8 * stage) : "memory");
}
#define PK2(v, i) pack_bf16(v[i], v[(i) + 1])

__device__ __forceinline__ void conv_dense(uint32_t sb, uint32_t cb, uint32_t zz) {
  const int lane = threadIdx.x & 31, wq = (threadIdx.x >> 5) & 3, br = wq >> 1, hf = wq & 1, g = lane >> 2, t = lane & 3;
  const uint32_t rb = cb + R_OFF + br * R_BR;
  const int eo = 16 * hf + g - 2 * t;
  const int x0 = RD_X0 - (eo + 536);
  const uint32_t fa = rb + ((g & 1) ? 2 * x0 : RD_CS + 2 * x0 + 2);
  const uint64_t ub = mkdesc(cb + U_OFF, U_CS, 128);
  const uint32_t yd = cb + Y0_OFF + br * 4096 + ysw(4 * (63 - 8 * (lane >> 4) - (lane & 7)) + 2 * hf + ((lane >> 3) & 1));
  uint32_t A[2][4][4];
  float e64[32], e56[28], e48[24];
  auto loadA = [&](int j) {
#pragma unroll
    for (int k = 0; k < 4; k++) {
      const int s = 34 - 4 * j - k;
      if (s >= 0) {
        if (k == 0 && j == 0) A[0][0][2] = lds32(fa + (2 * s + 2) * 16);
        A[j & 1][k][0] = lds32(fa + (2 * s + 1) * 16);
        A[j & 1][k][1] = lds32(fa + (2 * s) * 16);
      }
    }
#pragma unroll
    for (int k = 0; k < 4; k++) {
      if (34 - 4 * j - k >= 0) {
        A[j & 1][k][3] = A[j & 1][k][0];
        if (k) A[j & 1][k][2] = A[j & 1][k - 1][1];
        else if (j) A[j & 1][0][2] = A[(j - 1) & 1][3][1];
      }
    }
  };
  loadA(0); loadA(1);
#pragma unroll
  for (int j = 0; j < 9; j++) {
    if (j == 4) {
      wg_wait0();
      stsm2t(yd - 7 * 512, PK2(e64, 28), PK2(e64, 30));
#pragma unroll
      for (int i = 0; i < 28; i++) e56[i] = FCPY(e64, i);
      stage_done(sb, 0, lane);
    }
    if (j == 8) {
      wg_wait0();
      stsm2t(yd - 6 * 512, PK2(e56, 24), PK2(e56, 26));
#pragma unroll
      for (int i = 0; i < 24; i++) e48[i] = FCPY(e56, i);
      stage_done(sb, 1, lane);
    }
    wg_fence();
#pragma unroll
    for (int k = 0; k < 4; k++) {
      const int s = 34 - 4 * j - k;
      if (s >= 0) {
        const int o = 2 * s - 66 + 128;
        const int cc = o & 3, rs = (o >> 2) - 32;
        const uint64_t desc = ub + (uint64_t)((cc * U_CS - rs * 16) >> 4);
        const uint32_t* a = A[j & 1][k];
        if (j < 4) wgmma_rs<64, 0>(e64, a[0], a[1], a[2], a[3], desc, s != 34);
        else if (j < 8) wgmma_rs<56, 0>(e56, a[0], a[1], a[2], a[3], desc, 1);
        else wgmma_rs<48, 0>(e48, a[0], a[1], a[2], a[3], desc, 1);
      }
    }
    wg_commit();
    if (j >= 1 && j < 8) { wg_wait1(); loadA(j + 1); }
  }
  wg_wait0();
#pragma unroll
  for (int i = 0; i < 6; i += 2) stsm4t(yd - i * 512, PK2(e48, 4 * i), PK2(e48, 4 * i + 2), PK2(e48, 4 * i + 4), PK2(e48, 4 * i + 6));
}

__device__ __noinline__ unsigned int gate_rows(const Params* pp, int grow, int step, int rend) {
  const __nv_bfloat16 *u = pp->u, *gw = pp->gw;
  const int lane = threadIdx.x & 31;
  uint4 gx[4][2], nx[4][2];
#pragma unroll
  for (int i = 0; i < 4; i++) {
    nx[i][0] = ldg128(u + (size_t)(grow + i) * D + lane * 8);
    nx[i][1] = ldg128(u + (size_t)(grow + i) * D + 256 + lane * 8);
  }
  const uint4 gw0 = ldg128(gw + lane * 8), gw1 = ldg128(gw + 256 + lane * 8);
  const uint32_t ws[8] = {gw0.x, gw0.y, gw0.z, gw0.w, gw1.x, gw1.y, gw1.z, gw1.w};
  unsigned int epoch;
  asm volatile("ld.relaxed.gpu.global.u32 %0, [%1];" : "=r"(epoch) : "l"(&g_epoch) : "memory");
#pragma unroll 1
  for (; grow < rend; grow += step) {
#pragma unroll
    for (int i = 0; i < 4; i++) { gx[i][0] = nx[i][0]; gx[i][1] = nx[i][1]; }
    if (grow + step < rend) {
#pragma unroll
      for (int i = 0; i < 4; i++) {
        nx[i][0] = ldg128(u + (size_t)(grow + step + i) * D + lane * 8);
        nx[i][1] = ldg128(u + (size_t)(grow + step + i) * D + 256 + lane * 8);
      }
    }
    float c[2][4];
#pragma unroll
    for (int i = 0; i < 2; i++) {
      const uint4 *x = gx[2 * i], *y = gx[2 * i + 1];
      const uint32_t xs[8] = {x[0].x, x[0].y, x[0].z, x[0].w, x[1].x, x[1].y, x[1].z, x[1].w};
      const uint32_t ys[8] = {y[0].x, y[0].y, y[0].z, y[0].w, y[1].x, y[1].y, y[1].z, y[1].w};
      c[i][0] = c[i][1] = c[i][2] = c[i][3] = 0.f;
#pragma unroll
      for (int j = 0; j < 8; j += 2)
        mma16816(c[i], hmul2(xs[j], ws[j]), hmul2(ys[j], ws[j]), hmul2(xs[j + 1], ws[j + 1]), hmul2(ys[j + 1], ws[j + 1]), 0x3f803f80u, 0x3f803f80u);
    }
    float s = (lane & 2) ? ((lane & 1) ? c[1][2] : c[1][0]) : ((lane & 1) ? c[0][2] : c[0][0]);
#pragma unroll
    for (int o = 4; o < 32; o <<= 1) s += __shfl_xor_sync(0xffffffffu, s, o);
    s = bf_round(s);
    const float gv = 1.f / (1.f + expf(-s));
    const uint32_t w = ((epoch + 1) << 16) | (pack_bf16(gv, 0.f) & 0xffffu);
    if (lane < 4) asm volatile("st.relaxed.gpu.global.u32 [%0], %1;" ::"l"(&g_gate[grow + lane]), "r"(w) : "memory");
  }
  return epoch;
}
#define GW 1
constexpr int GSPLIT = L - 4 * GW * NCTA;
__device__ __noinline__ void gate_cta(const Params* pp) {
  const unsigned int epoch = gate_rows(pp, (blockIdx.x * 20 + (threadIdx.x >> 5)) * 4, 80 * NGATE, GSPLIT);
  __syncthreads();
  if (threadIdx.x == 0 && atomicAdd(&g_ticket, 1u) == NCTA + NGATE - 1) { g_ticket = 0; g_epoch = epoch + 1; }
}

__global__ void __cluster_dims__(2, 1, 1) __launch_bounds__(640, 1)
ssm_kernel(const __grid_constant__ Params p, const __grid_constant__ CUtensorMap tm_in, const __grid_constant__ CUtensorMap tm_out) {
  extern __shared__ __align__(1024) unsigned char smem_raw[];
  const uint32_t sb = (uint32_t)__cvta_generic_to_shared(smem_raw);
  const int tid = threadIdx.x, lane = tid & 31;
  const int warp = __shfl_sync(0xffffffffu, tid >> 5, 0);
  const int ch = warp >> 2, wq = warp & 3, br = wq >> 1, hf = wq & 1;
  const int g = lane >> 2, t = lane & 3;
  if (__builtin_expect(blockIdx.x < NGATE, 0)) { gate_cta(&p); return; }
  const int bid = blockIdx.x - NGATE;
  const uint32_t rank = blockIdx.x & 1;
  const uint32_t cb = sb + CH_OFF + ch * CH_BYTES;
  const int wtid = tid & 127;
  const int oc0 = (bid >> 1) * 8;
  STAMP(0); GT(0);

  if (warp >= 16) {
    if (wtid == 0) {
      mbar_init_expect(sb + B_RAW, 32768);
#pragma unroll
      for (int i = 0; i < 4; i++) mbar_init_expect(sb + B_X + 8 * i, 2048);
      asm volatile("mbarrier.init.shared::cta.b64 [%0], 128;" ::"r"(sb + B_U) : "memory");
      asm volatile("mbarrier.init.shared::cta.b64 [%0], 128;" ::"r"(sb + B_W) : "memory");
#pragma unroll
      for (int i = 0; i < 7; i++) asm volatile("mbarrier.init.shared::cta.b64 [%0], 16;" ::"r"(sb + B_ST + 8 * i) : "memory");
      asm volatile("fence.mbarrier_init.release.cluster;" ::: "memory");
      asm volatile("fence.proxy.async.shared::cta;" ::: "memory");
    }
    __syncwarp();
    asm volatile("barrier.cluster.arrive.relaxed.aligned;" ::: "memory");
    if (wq >= 4 - GW) gate_rows(&p, GSPLIT + (bid * GW + 3 - wq) * 4, L, L);
    unsigned int epoch;
    asm volatile("ld.relaxed.gpu.global.u32 %0, [%1];" : "=r"(epoch) : "l"(&g_epoch) : "memory");
    asm volatile("barrier.cluster.wait.aligned;" ::: "memory");
    if (wtid == 0) {
      asm volatile("cp.async.bulk.tensor.5d.shared::cluster.global.mbarrier::complete_tx::bytes.multicast::cluster [%0], [%1, {%3, %4, %4, %4, %5}], [%2], %6;"
                   ::"r"(sb + RAW_OFF + rank * 16384), "l"(&tm_in), "r"(sb + B_RAW), "r"(oc0), "r"(0), "r"((int)rank * 32), "h"((unsigned short)3) : "memory");
    }
    sts128(sb + CH_OFF + wq * CH_BYTES + U_OFF + (lane >> 3) * U_CS + (64 + (lane & 7)) * 16, 0, 0, 0, 0);
    const uint2 dA = ldg64(p.A_D + bid * 4), dB = ldg64(p.B_D + bid * 4);
    uint32_t BA[3][4], BB[4][4];
    {
      const int l1 = br ? 3 : 6, h1 = br ? 5 : 10, l2 = br ? 5 : 12, h2 = br ? 11 : 20;
#pragma unroll
      for (int i = 0; i < 4; i++) {
        const int e = 16 * hf + g - 2 * t + 32 - 16 * i;
        BB[i][0] = band2(e, l2, h2); BB[i][1] = band2(e + 8, l2, h2); BB[i][2] = band2(e - 8, l2, h2); BB[i][3] = BB[i][0];
        if (i) { BA[i - 1][0] = band2(e, l1, h1); BA[i - 1][1] = band2(e + 8, l1, h1); BA[i - 1][2] = band2(e - 8, l1, h1); BA[i - 1][3] = BA[i - 1][0]; }
      }
    }
    const uint32_t tag = (epoch + 1) & 0xffffu;
    if (wtid == 0) sts32(sb + TAG_OFF, tag);
    STAMP(3);
    mbar_wait(sb + B_RAW);
    STAMP(4);
    {
      const uint32_t dst = sb + CH_OFF + (g & 3) * CH_BYTES + U_OFF + t * U_CS + (63 - wq * 16) * 16;
#pragma unroll
      for (int h = 0; h < 2; h++) {
        uint32_t r[8][4];
#pragma unroll
        for (int i = 0; i < 8; i++) ldsm4t(sb + RAW_OFF + (wq * 16 + h * 8 + i) * 512 + lane * 16, r[i][0], r[i][1], r[i][2], r[i][3]);
        if ((uint32_t)(g >> 2) == rank) {
#pragma unroll
          for (int i = 0; i < 8; i++) sts128(dst - (h * 8 + i) * 16, r[i][0], r[i][1], r[i][2], r[i][3]);
        }
      }
    }
    fence_async();
    asm volatile("mbarrier.arrive.shared::cta.b64 _, [%0];" ::"r"(sb + B_U) : "memory");
    bar_sync(5, 128);
    STAMP(5);
    {
      const int mrow = lane & 7, mi = lane >> 3;
      const uint64_t ub0 = mkdesc(sb + CH_OFF + U_OFF, U_CS, 128);
      uint32_t wa, wb;
      {
        const int c = 4 * (47 - 8 * (mi >> 1) - mrow) + 2 * hf + (mi & 1);
        wa = sb + CH_OFF + (br ? W3_OFF : W5_OFF) + (5 - (c >> 5)) * 576 + ((c & 31) >> 3) * 144 + (c & 7) * 16;
        const int c2 = c - 64, pp = c2 >> 1;
        wb = sb + CH_OFF + (br ? W7_OFF : W9_OFF) + (1 - (pp >> 5)) * 1152 + (c2 & 1) * 576 + ((pp & 31) >> 3) * 144 + (pp & 7) * 16;
      }
      {
        float w1[24];
#pragma unroll
        for (int i = 0; i < 24; i++) w1[i] = 0.f;
#pragma unroll 1
        for (int k = 0; k < 4; k++) {
          wg_fence();
#pragma unroll
          for (int i = 0; i < 3; i++)
            wgmma_rs<48, 0>(w1, BA[i][0], BA[i][1], BA[i][2], BA[i][3],
                            ub0 + (uint64_t)((k * CH_BYTES + ((2 * i + 2) & 3) * U_CS + (16 + (i == 0)) * 16) >> 4), i);
          wg_commit();
          wg_wait0();
#pragma unroll
          for (int i = 0; i < 3; i++) stsm4t(wa + k * CH_BYTES + i * 1152, PK2(w1, 8 * i), PK2(w1, 8 * i + 2), PK2(w1, 8 * i + 4), PK2(w1, 8 * i + 6));
        }
      }
      {
        float w2[2][16];
#pragma unroll
        for (int i = 0; i < 16; i++) { w2[0][i] = 0.f; w2[1][i] = 0.f; }
#pragma unroll 1
        for (int kp = 0; kp < 2; kp++) {
          wg_fence();
#pragma unroll
          for (int k = 0; k < 2; k++)
#pragma unroll
            for (int i = 0; i < 4; i++)
              wgmma_rs<32, 0>(w2[k], BB[i][0], BB[i][1], BB[i][2], BB[i][3],
                              ub0 + (uint64_t)(((2 * kp + k) * CH_BYTES + ((2 * i) & 3) * U_CS + (32 + (i < 2)) * 16) >> 4), i);
          wg_commit();
          wg_wait0();
#pragma unroll
          for (int k = 0; k < 2; k++)
#pragma unroll
            for (int i = 0; i < 2; i++)
              stsm4t(wb + (2 * kp + k) * CH_BYTES + i * 1152, PK2(w2[k], 8 * i), PK2(w2[k], 8 * i + 2), PK2(w2[k], 8 * i + 4), PK2(w2[k], 8 * i + 6));
        }
      }
    }
    fence_async();
    asm volatile("mbarrier.arrive.shared::cta.b64 _, [%0];" ::"r"(sb + B_W) : "memory");
    STAMP(7);
    {
      const int bsel = (int)rank ^ br ^ 1, xl = wtid & 63;
      uint2 gl[4];
      uint32_t ua[4][4], ub[4][4];
#pragma unroll
      for (int i = 0; i < 4; i++) skip_terms(ua[i], ub[i], sb, (2 * (i >> 1) + bsel) * 128 + (i & 1) * 64 + xl, dA, dB);
      const uint32_t yo = sb + CH_OFF + (xl & 3) * 4 + ysw(xl >> 2) + bsel * 512;
#pragma unroll
      for (int i = 0; i < 2; i++) gl[i] = gate_ld(bsel * 128 + i * 64 + xl);
#pragma unroll
      for (int slot = 0; slot < 2; slot++) {
        const int box = 2 * slot + bsel;
        uint32_t g2[2], ya[2][4], yb[2][4];
#pragma unroll
        for (int h = 0; h < 2; h++) g2[h] = gate_fin(p, gl[2 * slot + h], box * 128 + h * 64 + xl, tag);
        mbar_wait(sb + B_ST + 8 * box);
        STAMP(8 + slot);
        if (slot == 0) { gl[2] = gate_ld((2 + bsel) * 128 + xl); gl[3] = gate_ld((2 + bsel) * 128 + 64 + xl); }
#pragma unroll
        for (int h = 0; h < 2; h++) {
          const uint32_t yh = (yo ^ (h * 32)) + h * 256 + slot * 1024;
          ld4ch(ya[h], yh + Y0_OFF); ld4ch(yb[h], yh + Y0_OFF + 4096);
          if (slot) {
            uint32_t a2[4], b2[4];
            ld4ch(a2, yh + Y2_OFF - 1024); ld4ch(b2, yh + Y2_OFF - 1024 + 3072);
#pragma unroll
            for (int k = 0; k < 4; k++) { ya[h][k] = hadd2(ya[h][k], a2[k]); yb[h][k] = hadd2(yb[h][k], b2[k]); }
          }
        }
        const uint4 r0 = mix(ya[0], yb[0], ua[2 * slot], ub[2 * slot], g2[0]), r1 = mix(ya[1], yb[1], ua[2 * slot + 1], ub[2 * slot + 1], g2[1]);
        if (br == 0) { send_box(sb, slot, xl, rank, r0); send_box(sb, slot, xl + 64, rank, r1); }
        else {
          const uint32_t st = sb + RAW_OFF + slot * 4096 + xl * 16, xin = sb + XIN_OFF + slot * 2048 + xl * 16;
          mbar_wait(sb + B_X + slot * 8);
          const uint4 q0 = lds128(xin), q1 = lds128(xin + 1024);
          merge_rows(st, rank, r0, q0); merge_rows(st + 1024, rank, r1, q1);
          fence_async();
          bar_sync(6, 64);
          if (xl == 0) {
            asm volatile("cp.async.bulk.tensor.3d.global.shared::cta.bulk_group [%0, {%2, %3, %4}], [%1];"
                         ::"l"(&tm_out), "r"(sb + RAW_OFF + slot * 4096), "r"(oc0), "r"(box * 128), "r"(0) : "memory");
            asm volatile("cp.async.bulk.commit_group;" ::: "memory");
          }
        }
        STAMP(10 + slot);
      }
    }
    if (wtid == 0 && atomicAdd(&g_ticket, 1u) == NCTA + NGATE - 1) { g_ticket = 0; g_epoch = epoch + 1; }
    if (wtid == 64) asm volatile("cp.async.bulk.wait_group.read 0;" ::: "memory");
    STAMP(15);
    return;
  }
  asm volatile("barrier.cluster.arrive.relaxed.aligned;" ::: "memory");

  const int moff = (bid * 4 + (tid >> 7)) * NM + (tid & 63) * 2;
  const int brt = (tid >> 6) & 1;
  const __nv_bfloat16* const* tp = p.t + (brt ? 0 : 6);
  const uint32_t q0 = *(const uint32_t*)(tp[0] + moff), q1 = *(const uint32_t*)(tp[1] + moff);
  const uint32_t q2 = *(const uint32_t*)(tp[2] + moff), q3 = *(const uint32_t*)(tp[3] + moff);
  const uint2 ldt4 = *(const uint2*)(tp[4] + bid * 4);
  const uint32_t q4 = *(const uint32_t*)(tp[brt ? 2 : 5] + moff), q5 = *(const uint32_t*)(tp[brt ? 3 : 6] + moff);

  for (int i = wtid & 63; i < R_BR / 16; i += 64) sts128(cb + R_OFF + br * R_BR + i * 16, 0, 0, 0, 0);
  STAMP(1);

  float acc[5][4];
  float k2048 = 0.f;
  const uint32_t scr = cb + Y0_OFF + wq * SCR_BYTES;
  const uint32_t scr2 = sb + SC2_OFF + warp * 640;
  {
    const uint32_t ldt2 = (ch & 2) ? ldt4.y : ldt4.x;
    const float dt = bf_round(expf((ch & 1) ? bf_hi(ldt2) : bf_lo(ldt2)));
#pragma unroll
    for (int i = 0; i < 5; i++) acc[i][0] = acc[i][1] = acc[i][2] = acc[i][3] = 0.f;
    STAMP(2);
    const uint32_t tb = scr + lane * 16;
    const uint32_t tb1 = tb + hf * 512, tb2 = tb + (hf ^ 1) * 512;
    const uint32_t ta = scr + (lane >> 3) * 512 + (lane & 7) * 16;
    const uint32_t tc = ((lane & 8) ? scr2 : scr + 4096) + (lane >> 4) * 128 + (lane & 7) * 16;
    const uint32_t tm = scr2 + 512 + ((lane >> 3) & 1) * 64 + (lane >> 4) * 16;
#pragma unroll 1
    for (int r = 0; r < 2; r++) {
      cf c, z1, z128;
      {
        const uint32_t sh = r ? 0x3244u : 0x1044u;
        float v0 = __uint_as_float(__byte_perm(q0, 0, sh));
        const float v1 = __uint_as_float(__byte_perm(q1, 0, sh)), v2 = __uint_as_float(__byte_perm(q2, 0, sh)), v3 = __uint_as_float(__byte_perm(q3, 0, sh));
        if (br == 0) { c = cmul(cf{v2, v3}, cf{dt * __uint_as_float(__byte_perm(q4, 0, sh)), dt * __uint_as_float(__byte_perm(q5, 0, sh))}); }
        else { v0 = -bf_round(expf(v0)); c = cf{2.f * dt * v2, 2.f * dt * v3}; }
        const float xl = (dt * v0) * 1.4426950408889634f, y = dt * v1;
        z1 = cexp_p(xl, y, 1.f); z128 = cexp_p(xl, y, 128.f);
      }
      const cf z2 = csq(z1), z4 = csq(z2), z8 = csq(z4);
      const cf w8 = {z8.re, -z8.im};
      const cf z16 = csq(w8), z24 = cmul(z16, w8), z32 = csq(z16), z40 = cmul(z32, w8), z48 = csq(z24), z56 = cmul(z32, z24), z64 = csq(z32);
      const cf z256 = csq(z128), z512 = csq(z256), z1024 = csq(z512), z2048 = csq(z1024);
      {
        float kk = fmaf(c.re, z2048.re, -c.im * z2048.im);
#pragma unroll
        for (int o = 16; o; o >>= 1) kk += __shfl_xor_sync(0xffffffffu, kk, o);
        k2048 += kk;
      }
      __syncwarp();
      {
        uint32_t xr[4] = {pack_bf16(1.f, z8.re), pack_bf16(z16.re, z24.re), pack_bf16(z32.re, z40.re), pack_bf16(z48.re, z56.re)};
        uint32_t xi[4] = {pack_bf16(0.f, w8.im), pack_bf16(z16.im, z24.im), pack_bf16(z32.im, z40.im), pack_bf16(z48.im, z56.im)};
        sts128(tb1, xr[0], xr[1], xr[2], xr[3]);
        sts128(tb1 + 1024, xi[0], xi[1], xi[2], xi[3]);
        const uint32_t yr = pack_bf16(z64.re, z64.re), yi = pack_bf16(z64.im, z64.im), nyi = yi ^ 0x80008000u;
        uint32_t o[4], q[4];
#pragma unroll
        for (int i = 0; i < 4; i++) CMUL2(o[i], q[i], xr[i], xi[i], yr, yi, nyi);
        sts128(tb2, o[0], o[1], o[2], o[3]);
        sts128(tb2 + 1024, q[0], q[1], q[2], q[3]);
      }
      {
        const cf h1 = cmul(c, z128), h2 = cmul(c, z256), h3 = cmul(h1, z256), h4 = cmul(c, z512), h5 = cmul(h1, z512), h6 = cmul(h2, z512), h7 = cmul(h3, z512);
        const cf e1 = cmul(c, z1), e2 = cmul(c, z2), e3 = cmul(e1, z2), e129 = cmul(h1, z1), e130 = cmul(h1, z2), e131 = cmul(e129, z2);
        const cf e258 = cmul(h2, z2), e386 = cmul(h3, z2);
        const uint32_t pr0 = pack_bf16(c.re, e1.re), pr2 = pack_bf16(h1.re, e129.re), pi0 = pack_bf16(c.im, e1.im), pi2 = pack_bf16(h1.im, e129.im);
        sts128(tb + 4 * 512, pr0, pack_bf16(e2.re, e3.re), pr2, pack_bf16(e130.re, e131.re));
        sts128(tb + 5 * 512, pi0, pack_bf16(e2.im, e3.im), pi2, pack_bf16(e130.im, e131.im));
        uint32_t xr[4] = {pack_bf16(h2.re, e258.re), pack_bf16(h3.re, e386.re), pack_bf16(h4.re, h5.re), pack_bf16(h6.re, h7.re)};
        uint32_t xi[4] = {pack_bf16(h2.im, e258.im), pack_bf16(h3.im, e386.im), pack_bf16(h4.im, h5.im), pack_bf16(h6.im, h7.im)};
        sts128(tb + 6 * 512, xr[0], xr[1], xr[2], xr[3]);
        sts128(tb + 7 * 512, xi[0], xi[1], xi[2], xi[3]);
        xr[1] = __byte_perm(xr[0], xr[1], 0x5410); xi[1] = __byte_perm(xi[0], xi[1], 0x5410);
        xr[0] = __byte_perm(pr0, pr2, 0x5410); xi[0] = __byte_perm(pi0, pi2, 0x5410);
        const uint32_t yr = pack_bf16(z1024.re, z1024.re), yi = pack_bf16(z1024.im, z1024.im), nyi = yi ^ 0x80008000u;
        uint32_t o[4], q[4];
#pragma unroll
        for (int i = 0; i < 4; i++) CMUL2(o[i], q[i], xr[i], xi[i], yr, yi, nyi);
        sts128(tb + 8 * 512, o[0], o[1], o[2], o[3]);
        sts128(scr2 + lane * 16, q[0], q[1], q[2], q[3]);
        const uint32_t m4 = pack_bf16(z4.re, z4.im);
        sts16(scr2 + 512 + lane * 2, m4); sts16(scr2 + 576 + lane * 2, m4 >> 16);
      }
      __syncwarp();
#pragma unroll
      for (int kp = 0; kp < 2; kp++) {
        uint32_t rr[2], ri[2], yr[2], yi[2];
        ldsm4t(tc + kp * 256, rr[0], ri[0], rr[1], ri[1]);
        ldsm4(tm + kp * 32, yr[0], yi[0], yr[1], yi[1]);
#pragma unroll
        for (int k2 = 0; k2 < 2; k2++) {
          const int kk = kp * 2 + k2;
          uint32_t a0, a1, a2, a3, pr, pi, qr, qi, xr, xi;
          ldsm4t(ta + kk * 128, a0, a1, a2, a3);
          ldsm4t(ta + 2048 + kk * 128, pr, pi, qr, qi);
          const uint32_t nyi = yi[k2] ^ 0x80008000u;
          mma16816(acc[0], a0, a1, a2, a3, pr, pi);
          mma16816(acc[2], a0, a1, a2, a3, qr, qi);
          mma16816(acc[4], a0, a1, a2, a3, rr[k2], ri[k2]);
          CMUL2(xr, xi, pr, pi, yr[k2], yi[k2], nyi);
          mma16816(acc[1], a0, a1, a2, a3, xr, xi);
          CMUL2(xr, xi, qr, qi, yr[k2], yi[k2], nyi);
          mma16816(acc[3], a0, a1, a2, a3, xr, xi);
        }
      }
    }
  }
  STAMP(3);
  __syncwarp();
  {
    const uint32_t xs = scr + lane * 16;
#define OTH(i, k) __float_as_uint(acc[i][2 + (k)])
    sts128(xs, OTH(0, 0), OTH(0, 1), OTH(1, 0), OTH(1, 1));
    sts128(xs + 512, OTH(2, 0), OTH(2, 1), OTH(3, 0), OTH(3, 1));
    sts128(xs + 1024, OTH(4, 0), OTH(4, 1), __float_as_uint(k2048), 0);
#undef OTH
  }

  bar_sync(7 + (warp >> 1), 64);
  STAMP(4);
  {
    const uint32_t xo = cb + Y0_OFF + (wq ^ 1) * SCR_BYTES + lane * 16;
    const uint4 o0 = lds128(xo), o1 = lds128(xo + 512), o2 = lds128(xo + 1024);
    const uint32_t rb = cb + R_OFF + br * R_BR;
#define OWN(i, k) acc[i][k]
    const uint32_t vP = pack_bf16(OWN(0, 1) + __uint_as_float(o0.y), OWN(0, 0) + __uint_as_float(o0.x));
    const uint32_t vP4 = pack_bf16(OWN(1, 1) + __uint_as_float(o0.w), OWN(1, 0) + __uint_as_float(o0.z));
    const uint32_t vQ = pack_bf16(OWN(2, 1) + __uint_as_float(o1.y), OWN(2, 0) + __uint_as_float(o1.x));
    const uint32_t vQ4 = pack_bf16(OWN(3, 1) + __uint_as_float(o1.w), OWN(3, 0) + __uint_as_float(o1.z));
    const uint32_t vR = pack_bf16(OWN(4, 1) + __uint_as_float(o2.y), OWN(4, 0) + __uint_as_float(o2.x));
#undef OWN
    const int j = g + 8 * hf;
    {
      const int a = 2 * (t & 1) + 64 * (t & 2) + 8 * j;
      const uint32_t ad = rb + 2 * (RD_X0 - 1 - a);
      const uint32_t a1 = (t & 2) ? ad - 8 : ad, a2 = (t & 2) ? ad : ad - 8;
      const uint32_t w1 = (t & 2) ? vP4 : vP, w2 = (t & 2) ? vP : vP4;
      sts32(a1, w1); sts32(a2, w2);
      sts16(a1 + RD_CS + 2, w1); sts16(a1 + RD_CS + 4, w1 >> 16);
      sts16(a2 + RD_CS + 2, w2); sts16(a2 + RD_CS + 4, w2 >> 16);
    }
    if (t < 2) {
      const int b = 256 + 128 * t + 8 * j;
      const uint32_t ad = rb + 2 * (RD_X0 - 6 - b);
      const uint32_t v22 = __byte_perm(vQ4, 0, 0x3232), v00 = __byte_perm(vQ, 0, 0x3232);
      sts16(ad, vQ4);
      sts64(ad + 2, v22, __byte_perm(vQ4, vQ, 0x5432));
      sts32(ad + 10, v00);
      if (b != 256) { sts16(ad + 14, v00); sts128(ad + RD_CS + 2, vQ4, v22, vQ, v00); }
      else { sts64(ad + RD_CS + 2, vQ4, v22); sts32(ad + RD_CS + 10, vQ); sts16(ad + RD_CS + 14, v00); }
    } else {
      const uint32_t ao = rb + R_O2 + 2 * (159 - (32 * t + j)), ae = ao - (R_O2 - R_E2) + 2;
      sts16(ao, vQ4 >> 16); sts16(ao + RS_CS + 2, vQ4 >> 16); sts16(ao - 32, vQ4); sts16(ao - 32 + RS_CS + 2, vQ4);
      sts16(ae - 32, vQ); sts16(ae - 32 + RS_CS + 2, vQ);
      if (lane != 2 || hf) { sts16(ae, vQ >> 16); sts16(ae + RS_CS + 2, vQ >> 16); }
      else {
        const uint32_t vv = __byte_perm(vQ, 0, 0x3232), ad = rb + 2 * (RD_X0 - 514);
        sts16(ad, vv); sts32(ad + 2, vv); sts16(ad + 6, vv); sts64(ad + RD_CS + 2, vv, vv);
      }
    }
    {
      const uint32_t a = rb + ((g & 1) ? R_O3 : R_E3 + 2) + 2 * (159 - (64 + 16 * t + (j >> 1)));
      const bool p1024 = (lane == 0) && (hf == 0);
      const uint32_t a00 = p1024 ? rb + R_E2 + 2 * (159 - 127) : a;
      sts16(a00, vR >> 16); sts16(a00 + RS_CS + 2, vR >> 16);
      sts16(a - 16, vR); sts16(a - 16 + RS_CS + 2, vR);
      if (p1024) {
        sts32(sb + K1024_OFF + (ch * 2 + br) * 4, __byte_perm(vR, 0, 0x3232));
        const uint32_t kv = pack_bf16(k2048 + __uint_as_float(o2.z), 0.f);
        sts16(rb + R_E3 + 2 * (159 - 127), kv); sts16(rb + R_E3 + 2 * (159 - 127) + RS_CS + 2, kv);
      }
    }
  }
  STAMP(5);
  asm volatile("barrier.cluster.wait.aligned;" ::: "memory");
  bar_sync(7 + (warp >> 1), 64);
  mbar_wait(sb + B_U);
  STAMP(6);

  const uint32_t zz = lds32(cb + R_OFF + br * R_BR);
  conv_dense(sb, cb, zz);
  STAMP(8);
  {
    const int x = (4 + ch) * 128 + wtid, c = x >> 2;
    const uint2 dA = ldg64(p.A_D + bid * 4), dB = ldg64(p.B_D + bid * 4);
    const uint2 gl = gate_ld(x);
    const uint32_t rb = cb + R_OFF + br * R_BR;
    float e48[24], e40[20], e32[16], h32[16], h16[8];
    const int x1 = 159 - (16 * hf + g - 2 * t + 136);
    const uint32_t fs = rb + ((g & 1) ? 2 * x1 : RS_CS + 2 * x1 + 2);
    uint32_t A[2][4][4];
    auto loadA = [&](int buf, uint32_t oe, uint32_t oo, int i0) {
#pragma unroll
      for (int a = 0; a < 2; a++) {
        const uint32_t base = fs + (a ? oo : oe) + i0 * 16;
        uint32_t* k0 = A[buf][2 * a];
        uint32_t* k1 = A[buf][2 * a + 1];
        k0[1] = lds32(base); k0[0] = lds32(base + 16); k0[2] = lds32(base + 32); k1[0] = lds32(base + 48); k1[2] = lds32(base + 64);
        k0[3] = k0[0]; k1[1] = k0[2]; k1[3] = k1[0];
      }
    };
    loadA(0, R_E2, R_O2, 8);
    loadA(1, R_E2, R_O2, 4);
    mbar_wait(sb + B_W);
    const uint64_t d5 = mkdesc(cb + W5_OFF, 144, 576), d3 = mkdesc(cb + W3_OFF, 144, 576);
    const uint64_t d9 = mkdesc(cb + W9_OFF, 144, 576), d7 = mkdesc(cb + W7_OFF, 144, 576);
    const uint32_t y2d = cb + Y2_OFF + br * 3072 + ysw(32 * (5 - (lane >> 4)) + 16 * hf + (lane & 15));
    const uint32_t y3d = cb + Y3_OFF + br * 2048 + ysw(2 * (16 * hf + (lane & 15)) + (lane >> 4));
#define FAR4(N, ACC, BUF, DA, DB, OFF, FIRST)                                                            \
    wg_fence();                                                                                           \
    _Pragma("unroll") for (int k = 0; k < 4; k++) {                                                      \
      const uint32_t* a = A[BUF][k];                                                                      \
      wgmma_rs<N, 1>(ACC, a[0], a[1], a[2], a[3], ((k >> 1) ? DB : DA) + (k & 1) * 18 + (OFF), !(FIRST) || k); \
    }                                                                                                     \
    wg_commit();
    FAR4(48, e48, 0, d5, d3, 0, 1)
    wg_wait0();
    loadA(0, R_E2, R_O2, 0);
    stsm2(y2d - 5 * 512, PK2(e48, 20), PK2(e48, 22));
#pragma unroll
    for (int i = 0; i < 20; i++) e40[i] = FCPY(e48, i);
    stage_done(sb, 2, lane);
    FAR4(40, e40, 1, d5, d3, 36, 0)
    wg_wait0();
    loadA(1, R_E3, R_O3, 8);
    stsm2(y2d - 4 * 512, PK2(e40, 16), PK2(e40, 18));
#pragma unroll
    for (int i = 0; i < 16; i++) e32[i] = FCPY(e40, i);
    stage_done(sb, 3, lane);
    FAR4(32, e32, 0, d5, d3, 72, 0)
    FAR4(32, h32, 1, d9, d7, 0, 1)
    wg_wait1();
    loadA(0, R_E3, R_O3, 4);
    stsm4(y2d, PK2(e32, 0), PK2(e32, 2), PK2(e32, 4), PK2(e32, 6));
    stsm4(y2d - 2 * 512, PK2(e32, 8), PK2(e32, 10), PK2(e32, 12), PK2(e32, 14));
    stage_done(sb, 4, lane);
    STAMP(9);
    wg_wait0();
    stsm4(y3d, PK2(h32, 8), PK2(h32, 10), PK2(h32, 12), PK2(h32, 14));
#pragma unroll
    for (int i = 0; i < 8; i++) h16[i] = FCPY(h32, i);
    stage_done(sb, 5, lane);
    FAR4(16, h16, 0, d9, d7, 72, 0)
#undef FAR4
    const uint32_t yo = sb + CH_OFF + (x & 3) * 4 + ysw(c);
    uint32_t ua[4], ub[4], ya[4], yb[4], a2[4], b2[4], a3[4], b3[4], s2[4];
    skip_terms(ua, ub, sb, x, dA, dB);
    {
      const int xa = x - 514, xb = x - 513, ca = xa >> 2, cb2 = xb >> 2;
      ld4ch(s2, sb + CH_OFF + U_OFF + (xa & 3) * 4 + (ca & 3) * U_CS + (63 - (ca >> 2)) * 16);
      ld4ch(a3, sb + CH_OFF + U_OFF + (xb & 3) * 4 + (cb2 & 3) * U_CS + (63 - (cb2 >> 2)) * 16);
#pragma unroll
      for (int k = 0; k < 4; k++) s2[k] = hadd2(s2[k], __byte_perm(s2[k], a3[k], 0x5432));
    }
    const uint32_t tag = lds32(sb + TAG_OFF);
    wg_wait0();
    stsm4(y3d + 1024, PK2(h16, 0), PK2(h16, 2), PK2(h16, 4), PK2(h16, 6));
    stage_done(sb, 6, lane);
    STAMP(10);
    const uint32_t g2 = gate_fin(p, gl, x, tag);
    mbar_wait(sb + B_ST + 8 * 4);
    const uint4 k0 = lds128(sb + K1024_OFF), k1 = lds128(sb + K1024_OFF + 16);
    const uint32_t kk[8] = {k0.x, k0.y, k0.z, k0.w, k1.x, k1.y, k1.z, k1.w};
    ld4ch(ya, yo + Y0_OFF); ld4ch(yb, yo + Y0_OFF + 4096);
    ld4ch(a2, yo + Y2_OFF - 1024); ld4ch(b2, yo + Y2_OFF - 1024 + 3072);
    mbar_wait(sb + B_ST + 8 * (5 + (ch >> 1)));
    STAMP(12);
    ld4ch(a3, yo + Y3_OFF - 2048); ld4ch(b3, yo + Y3_OFF - 2048 + 2048);
#pragma unroll
    for (int k = 0; k < 4; k++) {
      ya[k] = hadd2(ya[k], hadd2(hfma2(kk[2 * k], s2[k], a2[k]), a3[k]));
      yb[k] = hadd2(yb[k], hadd2(hfma2(kk[2 * k + 1], s2[k], b2[k]), b3[k]));
    }
    const uint4 r = mix(ya, yb, ua, ub, g2);
    if ((uint32_t)(ch & 1) != rank) send_box(sb, 2 + (ch >> 1), wtid, rank, r);
    else merge_box(sb, &tm_out, 2 + (ch >> 1), wtid, rank, oc0, r, 1 + ch);
  }
  STAMP(14);
  if (wtid == 0) asm volatile("cp.async.bulk.wait_group.read 0;" ::: "memory");
  STAMP(15); GT(1);
}

typedef CUresult (*EncodeFn)(CUtensorMap*, CUtensorMapDataType, cuuint32_t, void*, const cuuint64_t*, const cuuint64_t*,
                             const cuuint32_t*, const cuuint32_t*, CUtensorMapInterleave, CUtensorMapSwizzle,
                             CUtensorMapL2promotion, CUtensorMapFloatOOBfill);

}

extern "C" void kernel_launch(void* const* d_in, const int* in_sizes, int n_in, void* d_out, int out_size) {
  (void)in_sizes; (void)n_in; (void)out_size;
  typedef const __nv_bfloat16* bp;
  Params p;
  p.t[0] = (bp)d_in[10]; p.t[1] = (bp)d_in[11]; p.t[2] = (bp)d_in[12]; p.t[3] = (bp)d_in[13]; p.t[4] = (bp)d_in[14]; p.t[5] = nullptr;
  p.t[6] = (bp)d_in[1]; p.t[7] = (bp)d_in[2]; p.t[8] = (bp)d_in[5]; p.t[9] = (bp)d_in[6]; p.t[10] = (bp)d_in[7];
  p.t[11] = (bp)d_in[3]; p.t[12] = (bp)d_in[4]; p.t[13] = nullptr;
  p.u = (bp)d_in[0]; p.gw = (bp)d_in[16]; p.A_D = (bp)d_in[8]; p.B_D = (bp)d_in[15];
  static EncodeFn enc = nullptr;
  if (!enc) {
    cudaDriverEntryPointQueryResult qr;
    cudaGetDriverEntryPoint("cuTensorMapEncodeTiled", (void**)&enc, cudaEnableDefault, &qr);
    cudaFuncSetAttribute(ssm_kernel, cudaFuncAttributeMaxDynamicSharedMemorySize, SMEM_BYTES);
  }
  CUtensorMap tm_in, tm_out;
  {
    cuuint64_t gd[5] = {512, 2, 4, 4, 64};
    cuuint64_t gs[4] = {1024, 8192, 2048, 32768};
    cuuint32_t bx[5] = {8, 2, 4, 4, 32};
    cuuint32_t es[5] = {1, 1, 1, 1, 1};
    enc(&tm_in, CU_TENSOR_MAP_DATA_TYPE_BFLOAT16, 5, d_in[0], gd, gs, bx, es, CU_TENSOR_MAP_INTERLEAVE_NONE,
        CU_TENSOR_MAP_SWIZZLE_NONE, CU_TENSOR_MAP_L2_PROMOTION_NONE, CU_TENSOR_MAP_FLOAT_OOB_FILL_NONE);
  }
  {
    cuuint64_t gd[3] = {512, 1024, 2};
    cuuint64_t gs[2] = {2048, 1024};
    cuuint32_t bx[3] = {8, 128, 2};
    cuuint32_t es[3] = {1, 1, 1};
    enc(&tm_out, CU_TENSOR_MAP_DATA_TYPE_BFLOAT16, 3, d_out, gd, gs, bx, es, CU_TENSOR_MAP_INTERLEAVE_NONE,
        CU_TENSOR_MAP_SWIZZLE_NONE, CU_TENSOR_MAP_L2_PROMOTION_NONE, CU_TENSOR_MAP_FLOAT_OOB_FILL_NONE);
  }
  ssm_kernel<<<NCTA + NGATE, 640, SMEM_BYTES, cudaStreamPerThread>>>(p, tm_in, tm_out);
}
```

```cpp
#include <cuda_runtime.h>
#include <cuda.h>
#include <cuda_bf16.h>
#include <stdint.h>

namespace {
#define PREDLD 1
#define FCPY(v, i) (((i) % 3 == 2) ? __uint_as_float(opq(__float_as_uint(v[i]), zz)) : opqf(v[i], zz))

constexpr int L = 2048, D = 512, NM = 128;
constexpr int NCTA = 128;
constexpr int NGATE = 4;

constexpr int RAW_OFF = 0;
constexpr int XIN_OFF = 32768;
constexpr int SC2_OFF = XIN_OFF + 8192;
constexpr int BAR_OFF = SC2_OFF + 10240;
constexpr int CH_OFF = BAR_OFF + 256;
constexpr int U_CS = 1184;
constexpr int U_OFF = 0;
constexpr int R_OFF = 4736;
constexpr int RD_X0 = 565;
constexpr int RD_CS = 1216;
constexpr int RS_CS = 320;
constexpr int R_E2 = 2 * RD_CS, R_O2 = R_E2 + 2 * RS_CS, R_E3 = R_O2 + 2 * RS_CS, R_O3 = R_E3 + 2 * RS_CS;
constexpr int R_BR = R_O3 + 2 * RS_CS;
constexpr int W5_OFF = R_OFF + 2 * R_BR;
constexpr int W3_OFF = W5_OFF + 3456;
constexpr int W9_OFF = W3_OFF + 3456;
constexpr int W7_OFF = W9_OFF + 2304;
constexpr int Y0_OFF = W7_OFF + 2304;
constexpr int Y2_OFF = Y0_OFF + 8192, Y3_OFF = Y2_OFF + 6144;
constexpr int CH_BYTES = Y0_OFF + 18432 + 16;
constexpr int SCR_BYTES = 4608;
constexpr int SMEM_BYTES = CH_OFF + 4 * CH_BYTES;
static_assert(CH_BYTES % 128 == 16, "bank staggering of the channel blocks");
static_assert(SMEM_BYTES <= 232448, "smem");
constexpr int B_RAW = BAR_OFF, B_X = BAR_OFF + 8, B_U = BAR_OFF + 40, B_W = BAR_OFF + 48;
constexpr int TAG_OFF = BAR_OFF + 56;
constexpr int K1024_OFF = BAR_OFF + 64;
constexpr int B_ST = BAR_OFF + 96;

__device__ unsigned int g_gate[L];
__device__ unsigned int g_epoch;
__device__ unsigned int g_ticket;

#define STAMP(k)
#define GT(k)

struct Params {
  const __nv_bfloat16* t[14];
  const __nv_bfloat16 *u, *gw, *A_D, *B_D;
};

template <int N, int TB> __device__ __forceinline__ void wgmma_rs(float* d, uint32_t a0, uint32_t a1, uint32_t a2, uint32_t a3, uint64_t desc, int sc);
template <> __device__ __forceinline__ void wgmma_rs<64, 0>(float* d, uint32_t a0, uint32_t a1, uint32_t a2, uint32_t a3, uint64_t desc, int sc) {
  asm volatile("{\n.reg .pred p;\nsetp.ne.b32 p, %37, 0;\n"
    "wgmma.mma_async.sync.aligned.m64n64k16.f32.bf16.bf16 {%0,%1,%2,%3,%4,%5,%6,%7,%8,%9,%10,%11,%12,%13,%14,%15,%16,%17,%18,%19,%20,%21,%22,%23,%24,%25,%26,%27,%28,%29,%30,%31}, {%32,%33,%34,%35}, %36, p, 1, 1, 0;\n}"
    : "+f"(d[0]), "+f"(d[1]), "+f"(d[2]), "+f"(d[3]), "+f"(d[4]), "+f"(d[5]), "+f"(d[6]), "+f"(d[7]), "+f"(d[8]), "+f"(d[9]), "+f"(d[10]), "+f"(d[11]), "+f"(d[12]), "+f"(d[13]), "+f"(d[14]), "+f"(d[15]), "+f"(d[16]), "+f"(d[17]), "+f"(d[18]), "+f"(d[19]), "+f"(d[20]), "+f"(d[21]), "+f"(d[22]), "+f"(d[23]), "+f"(d[24]), "+f"(d[25]), "+f"(d[26]), "+f"(d[27]), "+f"(d[28]), "+f"(d[29]), "+f"(d[30]), "+f"(d[31]) : "r"(a0), "r"(a1), "r"(a2), "r"(a3), "l"(desc), "r"(sc));
}
template <> __device__ __forceinline__ void wgmma_rs<56, 0>(float* d, uint32_t a0, uint32_t a1, uint32_t a2, uint32_t a3, uint64_t desc, int sc) {
  asm volatile("{\n.reg .pred p;\nsetp.ne.b32 p, %33, 0;\n"
    "wgmma.mma_async.sync.aligned.m64n56k16.f32.bf16.bf16 {%0,%1,%2,%3,%4,%5,%6,%7,%8,%9,%10,%11,%12,%13,%14,%15,%16,%17,%18,%19,%20,%21,%22,%23,%24,%25,%26,%27}, {%28,%29,%30,%31}, %32, p, 1, 1, 0;\n}"
    : "+f"(d[0]), "+f"(d[1]), "+f"(d[2]), "+f"(d[3]), "+f"(d[4]), "+f"(d[5]), "+f"(d[6]), "+f"(d[7]), "+f"(d[8]), "+f"(d[9]), "+f"(d[10]), "+f"(d[11]), "+f"(d[12]), "+f"(d[13]), "+f"(d[14]), "+f"(d[15]), "+f"(d[16]), "+f"(d[17]), "+f"(d[18]), "+f"(d[19]), "+f"(d[20]), "+f"(d[21]), "+f"(d[22]), "+f"(d[23]), "+f"(d[24]), "+f"(d[25]), "+f"(d[26]), "+f"(d[27]) : "r"(a0), "r"(a1), "r"(a2), "r"(a3), "l"(desc), "r"(sc));
}
template <> __device__ __forceinline__ void wgmma_rs<48, 0>(float* d, uint32_t a0, uint32_t a1, uint32_t a2, uint32_t a3, uint64_t desc, int sc) {
  asm volatile("{\n.reg .pred p;\nsetp.ne.b32 p, %29, 0;\n"
    "wgmma.mma_async.sync.aligned.m64n48k16.f32.bf16.bf16 {%0,%1,%2,%3,%4,%5,%6,%7,%8,%9,%10,%11,%12,%13,%14,%15,%16,%17,%18,%19,%20,%21,%22,%23}, {%24,%25,%26,%27}, %28, p, 1, 1, 0;\n}"
    : "+f"(d[0]), "+f"(d[1]), "+f"(d[2]), "+f"(d[3]), "+f"(d[4]), "+f"(d[5]), "+f"(d[6]), "+f"(d[7]), "+f"(d[8]), "+f"(d[9]), "+f"(d[10]), "+f"(d[11]), "+f"(d[12]), "+f"(d[13]), "+f"(d[14]), "+f"(d[15]), "+f"(d[16]), "+f"(d[17]), "+f"(d[18]), "+f"(d[19]), "+f"(d[20]), "+f"(d[21]), "+f"(d[22]), "+f"(d[23]) : "r"(a0), "r"(a1), "r"(a2), "r"(a3), "l"(desc), "r"(sc));
}
template <> __device__ __forceinline__ void wgmma_rs<32, 0>(float* d, uint32_t a0, uint32_t a1, uint32_t a2, uint32_t a3, uint64_t desc, int sc) {
  asm volatile("{\n.reg .pred p;\nsetp.ne.b32 p, %21, 0;\n"
    "wgmma.mma_async.sync.aligned.m64n32k16.f32.bf16.bf16 {%0,%1,%2,%3,%4,%5,%6,%7,%8,%9,%10,%11,%12,%13,%14,%15}, {%16,%17,%18,%19}, %20, p, 1, 1, 0;\n}"
    : "+f"(d[0]), "+f"(d[1]), "+f"(d[2]), "+f"(d[3]), "+f"(d[4]), "+f"(d[5]), "+f"(d[6]), "+f"(d[7]), "+f"(d[8]), "+f"(d[9]), "+f"(d[10]), "+f"(d[11]), "+f"(d[12]), "+f"(d[13]), "+f"(d[14]), "+f"(d[15]) : "r"(a0), "r"(a1), "r"(a2), "r"(a3), "l"(desc), "r"(sc));
}
template <> __device__ __forceinline__ void wgmma_rs<48, 1>(float* d, uint32_t a0, uint32_t a1, uint32_t a2, uint32_t a3, uint64_t desc, int sc) {
  asm volatile("{\n.reg .pred p;\nsetp.ne.b32 p, %29, 0;\n"
    "wgmma.mma_async.sync.aligned.m64n48k16.f32.bf16.bf16 {%0,%1,%2,%3,%4,%5,%6,%7,%8,%9,%10,%11,%12,%13,%14,%15,%16,%17,%18,%19,%20,%21,%22,%23}, {%24,%25,%26,%27}, %28, p, 1, 1, 1;\n}"
    : "+f"(d[0]), "+f"(d[1]), "+f"(d[2]), "+f"(d[3]), "+f"(d[4]), "+f"(d[5]), "+f"(d[6]), "+f"(d[7]), "+f"(d[8]), "+f"(d[9]), "+f"(d[10]), "+f"(d[11]), "+f"(d[12]), "+f"(d[13]), "+f"(d[14]), "+f"(d[15]), "+f"(d[16]), "+f"(d[17]), "+f"(d[18]), "+f"(d[19]), "+f"(d[20]), "+f"(d[21]), "+f"(d[22]), "+f"(d[23]) : "r"(a0), "r"(a1), "r"(a2), "r"(a3), "l"(desc), "r"(sc));
}
template <> __device__ __forceinline__ void wgmma_rs<40, 1>(float* d, uint32_t a0, uint32_t a1, uint32_t a2, uint32_t a3, uint64_t desc, int sc) {
  asm volatile("{\n.reg .pred p;\nsetp.ne.b32 p, %25, 0;\n"
    "wgmma.mma_async.sync.aligned.m64n40k16.f32.bf16.bf16 {%0,%1,%2,%3,%4,%5,%6,%7,%8,%9,%10,%11,%12,%13,%14,%15,%16,%17,%18,%19}, {%20,%21,%22,%23}, %24, p, 1, 1, 1;\n}"
    : "+f"(d[0]), "+f"(d[1]), "+f"(d[2]), "+f"(d[3]), "+f"(d[4]), "+f"(d[5]), "+f"(d[6]), "+f"(d[7]), "+f"(d[8]), "+f"(d[9]), "+f"(d[10]), "+f"(d[11]), "+f"(d[12]), "+f"(d[13]), "+f"(d[14]), "+f"(d[15]), "+f"(d[16]), "+f"(d[17]), "+f"(d[18]), "+f"(d[19]) : "r"(a0), "r"(a1), "r"(a2), "r"(a3), "l"(desc), "r"(sc));
}
template <> __device__ __forceinline__ void wgmma_rs<32, 1>(float* d, uint32_t a0, uint32_t a1, uint32_t a2, uint32_t a3, uint64_t desc, int sc) {
  asm volatile("{\n.reg .pred p;\nsetp.ne.b32 p, %21, 0;\n"
    "wgmma.mma_async.sync.aligned.m64n32k16.f32.bf16.bf16 {%0,%1,%2,%3,%4,%5,%6,%7,%8,%9,%10,%11,%12,%13,%14,%15}, {%16,%17,%18,%19}, %20, p, 1, 1, 1;\n}"
    : "+f"(d[0]), "+f"(d[1]), "+f"(d[2]), "+f"(d[3]), "+f"(d[4]), "+f"(d[5]), "+f"(d[6]), "+f"(d[7]), "+f"(d[8]), "+f"(d[9]), "+f"(d[10]), "+f"(d[11]), "+f"(d[12]), "+f"(d[13]), "+f"(d[14]), "+f"(d[15]) : "r"(a0), "r"(a1), "r"(a2), "r"(a3), "l"(desc), "r"(sc));
}
template <> __device__ __forceinline__ void wgmma_rs<16, 1>(float* d, uint32_t a0, uint32_t a1, uint32_t a2, uint32_t a3, uint64_t desc, int sc) {
  asm volatile("{\n.reg .pred p;\nsetp.ne.b32 p, %13, 0;\n"
    "wgmma.mma_async.sync.aligned.m64n16k16.f32.bf16.bf16 {%0,%1,%2,%3,%4,%5,%6,%7}, {%8,%9,%10,%11}, %12, p, 1, 1, 1;\n}"
    : "+f"(d[0]), "+f"(d[1]), "+f"(d[2]), "+f"(d[3]), "+f"(d[4]), "+f"(d[5]), "+f"(d[6]), "+f"(d[7]) : "r"(a0), "r"(a1), "r"(a2), "r"(a3), "l"(desc), "r"(sc));
}

__device__ __forceinline__ uint32_t pack_bf16(float lo, float hi) {
  uint32_t r; asm("cvt.rn.bf16x2.f32 %0, %1, %2;" : "=r"(r) : "f"(hi), "f"(lo)); return r;
}
__device__ __forceinline__ float bf_lo(uint32_t v) { return __uint_as_float(v << 16); }
__device__ __forceinline__ float bf_hi(uint32_t v) { return __uint_as_float(v & 0xffff0000u); }
__device__ __forceinline__ float bf_round(float x) { return bf_lo(pack_bf16(x, 0.f)); }
__device__ __forceinline__ uint32_t hmul2(uint32_t a, uint32_t b) { uint32_t r; asm("mul.rn.bf16x2 %0, %1, %2;" : "=r"(r) : "r"(a), "r"(b)); return r; }
__device__ __forceinline__ uint32_t hadd2(uint32_t a, uint32_t b) { uint32_t r; asm("add.rn.bf16x2 %0, %1, %2;" : "=r"(r) : "r"(a), "r"(b)); return r; }
__device__ __forceinline__ uint32_t hsub2(uint32_t a, uint32_t b) { uint32_t r; asm("sub.rn.bf16x2 %0, %1, %2;" : "=r"(r) : "r"(a), "r"(b)); return r; }
__device__ __forceinline__ uint32_t hfma2(uint32_t a, uint32_t b, uint32_t c) { uint32_t r; asm("fma.rn.bf16x2 %0, %1, %2, %3;" : "=r"(r) : "r"(a), "r"(b), "r"(c)); return r; }

__device__ __forceinline__ void sts16(uint32_t a, uint32_t v) { asm volatile("st.shared.b16 [%0], %1;" ::"r"(a), "h"((unsigned short)v) : "memory"); }
__device__ __forceinline__ void sts32(uint32_t a, uint32_t v) { asm volatile("st.shared.b32 [%0], %1;" ::"r"(a), "r"(v) : "memory"); }
__device__ __forceinline__ void sts64(uint32_t a, uint32_t x, uint32_t y) { asm volatile("st.shared.v2.b32 [%0], {%1,%2};" ::"r"(a), "r"(x), "r"(y) : "memory"); }
__device__ __forceinline__ void sts128(uint32_t a, uint32_t x, uint32_t y, uint32_t z, uint32_t w) {
  asm volatile("st.shared.v4.b32 [%0], {%1,%2,%3,%4};" ::"r"(a), "r"(x), "r"(y), "r"(z), "r"(w) : "memory");
}
__device__ __forceinline__ uint32_t lds32(uint32_t a) { uint32_t v; asm volatile("ld.shared.b32 %0, [%1];" : "=r"(v) : "r"(a) : "memory"); return v; }
__device__ __forceinline__ uint32_t ldf(uint32_t base, int i, int lo0, int hi0, int hf) {
  if (i < lo0 || i > hi0 + 2) return 0u;
  if (i < lo0 + 2 || i > hi0) {
    uint32_t v;
    asm volatile("{\n.reg .pred p;\nsetp.eq.b32 p, %2, %3;\nmov.b32 %0, 0;\n@p ld.shared.b32 %0, [%1];\n}" : "=r"(v) : "r"(base + i * 16), "r"(hf), "r"(i > hi0 ? 1 : 0) : "memory");
    return v;
  }
  return lds32(base + i * 16);
}
__device__ __forceinline__ uint4 lds128(uint32_t a) {
  uint4 v; asm volatile("ld.shared.v4.b32 {%0,%1,%2,%3}, [%4];" : "=r"(v.x), "=r"(v.y), "=r"(v.z), "=r"(v.w) : "r"(a) : "memory"); return v;
}
__device__ __forceinline__ uint4 ldg128(const void* a) {
  uint4 v; asm volatile("ld.global.nc.v4.b32 {%0,%1,%2,%3}, [%4];" : "=r"(v.x), "=r"(v.y), "=r"(v.z), "=r"(v.w) : "l"(a) : "memory"); return v;
}
__device__ __forceinline__ uint2 ldg64(const void* a) {
  uint2 v; asm volatile("ld.global.nc.v2.b32 {%0,%1}, [%2];" : "=r"(v.x), "=r"(v.y) : "l"(a) : "memory"); return v;
}
__device__ __forceinline__ void ldsm4(uint32_t a, uint32_t& r0, uint32_t& r1, uint32_t& r2, uint32_t& r3) {
  asm volatile("ldmatrix.sync.aligned.m8n8.x4.shared.b16 {%0,%1,%2,%3}, [%4];" : "=r"(r0), "=r"(r1), "=r"(r2), "=r"(r3) : "r"(a) : "memory");
}
__device__ __forceinline__ void ldsm4t(uint32_t a, uint32_t& r0, uint32_t& r1, uint32_t& r2, uint32_t& r3) {
  asm volatile("ldmatrix.sync.aligned.m8n8.x4.trans.shared.b16 {%0,%1,%2,%3}, [%4];" : "=r"(r0), "=r"(r1), "=r"(r2), "=r"(r3) : "r"(a) : "memory");
}
__device__ __forceinline__ void stsm4(uint32_t a, uint32_t r0, uint32_t r1, uint32_t r2, uint32_t r3) {
  asm volatile("stmatrix.sync.aligned.m8n8.x4.shared.b16 [%0], {%1,%2,%3,%4};" ::"r"(a), "r"(r0), "r"(r1), "r"(r2), "r"(r3) : "memory");
}
__device__ __forceinline__ void stsm4t(uint32_t a, uint32_t r0, uint32_t r1, uint32_t r2, uint32_t r3) {
  asm volatile("stmatrix.sync.aligned.m8n8.x4.trans.shared.b16 [%0], {%1,%2,%3,%4};" ::"r"(a), "r"(r0), "r"(r1), "r"(r2), "r"(r3) : "memory");
}
__device__ __forceinline__ void stsm2(uint32_t a, uint32_t r0, uint32_t r1) {
  asm volatile("stmatrix.sync.aligned.m8n8.x2.shared.b16 [%0], {%1,%2};" ::"r"(a), "r"(r0), "r"(r1) : "memory");
}
__device__ __forceinline__ void stsm2t(uint32_t a, uint32_t r0, uint32_t r1) {
  asm volatile("stmatrix.sync.aligned.m8n8.x2.trans.shared.b16 [%0], {%1,%2};" ::"r"(a), "r"(r0), "r"(r1) : "memory");
}
__device__ __forceinline__ void mma16816(float* c, uint32_t a0, uint32_t a1, uint32_t a2, uint32_t a3, uint32_t b0, uint32_t b1) {
  asm("mma.sync.aligned.m16n8k16.row.col.f32.bf16.bf16.f32 {%0,%1,%2,%3}, {%4,%5,%6,%7}, {%8,%9}, {%0,%1,%2,%3};"
      : "+f"(c[0]), "+f"(c[1]), "+f"(c[2]), "+f"(c[3]) : "r"(a0), "r"(a1), "r"(a2), "r"(a3), "r"(b0), "r"(b1));
}
__device__ __forceinline__ void bar_sync(int id, int n) { asm volatile("bar.sync %0, %1;" ::"r"(id), "r"(n) : "memory"); }
__device__ __forceinline__ void wg_fence() { asm volatile("wgmma.fence.sync.aligned;" ::: "memory"); }
__device__ __forceinline__ void wg_commit() { asm volatile("wgmma.commit_group.sync.aligned;" ::: "memory"); }
__device__ __forceinline__ void wg_wait0() { asm volatile("wgmma.wait_group.sync.aligned 0;" ::: "memory"); }
__device__ __forceinline__ void wg_wait1() { asm volatile("wgmma.wait_group.sync.aligned 1;" ::: "memory"); }
__device__ __forceinline__ void fence_async() { asm volatile("fence.proxy.async.shared::cta;" ::: "memory"); }
__device__ __forceinline__ uint32_t opq(uint32_t x, uint32_t z) { uint32_t r; asm volatile("xor.b32 %0, %1, %2;" : "=r"(r) : "r"(x), "r"(z)); return r; }
__device__ __forceinline__ float opqf(float x, uint32_t z) { float r; asm volatile("add.rn.f32 %0, %1, %2;" : "=f"(r) : "f"(x), "f"(__uint_as_float(z))); return r; }
__device__ __forceinline__ uint64_t mkdesc(uint32_t addr, uint32_t lbo, uint32_t sbo) {
  return (uint64_t)((addr & 0x3FFFF) >> 4) | ((uint64_t)(lbo >> 4) << 16) | ((uint64_t)(sbo >> 4) << 32);
}
__device__ __forceinline__ uint32_t mapa(uint32_t a, uint32_t rank) {
  uint32_t r; asm("mapa.shared::cluster.u32 %0, %1, %2;" : "=r"(r) : "r"(a), "r"(rank)); return r;
}
__device__ __forceinline__ void mbar_init_expect(uint32_t bar, uint32_t bytes) {
  asm volatile("mbarrier.init.shared::cta.b64 [%0], 1;" ::"r"(bar) : "memory");
  asm volatile("mbarrier.arrive.expect_tx.shared::cta.b64 _, [%0], %1;" ::"r"(bar), "r"(bytes) : "memory");
}
__device__ __forceinline__ void mbar_wait(uint32_t bar) {
#pragma unroll 1
  for (int it = 0; it < (1 << 22); it++) {
    uint32_t ok;
    asm volatile("{\n.reg .pred p;\nmbarrier.try_wait.parity.acquire.cluster.shared::cta.b64 p, [%1], 0;\nselp.u32 %0, 1, 0, p;\n}"
                 : "=r"(ok) : "r"(bar) : "memory");
    if (ok) return;
  }
  __trap();
}
__device__ __forceinline__ void st_async4(uint32_t a, uint32_t bar, uint32_t x, uint32_t y, uint32_t z, uint32_t w) {
  asm volatile("st.async.weak.shared::cluster.mbarrier::complete_tx::bytes.v4.b32 [%0], {%2,%3,%4,%5}, [%1];"
               ::"r"(a), "r"(bar), "r"(x), "r"(y), "r"(z), "r"(w) : "memory");
}

struct cf { float re, im; };
__device__ __forceinline__ cf cmul(cf a, cf b) { return {fmaf(a.re, b.re, -a.im * b.im), fmaf(a.re, b.im, a.im * b.re)}; }
__device__ __forceinline__ cf csq(cf a) { return {fmaf(a.re, a.re, -a.im * a.im), (a.re + a.re) * a.im}; }
__device__ __forceinline__ cf cexp_p(float xl, float y, float p) {
  float mag; asm("ex2.approx.ftz.f32 %0, %1;" : "=f"(mag) : "f"(xl * p));
  const float th = y * p;
  const float k = __fadd_rn(fmaf(th, 0.15915494309189535f, 12582912.f), -12582912.f);
  float r = fmaf(k, -6.2831854820251465f, th);
  r = fmaf(k, 1.7484555314695172e-07f, r);
  return {mag * __cosf(r), mag * __sinf(r)};
}
__device__ __forceinline__ uint32_t ysw(int c) { return (uint32_t)(c ^ ((c >> 3) & 3)) * 16u; }

#define CMUL2(OR, OI, xr, xi, yr, yi, nyi) do { OR = hfma2(xr, yr, hmul2(xi, nyi)); OI = hfma2(xr, yi, hmul2(xi, yr)); } while (0)

__device__ __forceinline__ uint32_t gate_slow(const __nv_bfloat16* u, const __nv_bfloat16* gw, int row) {
  float s = 0.f;
  const uint32_t* xr = (const uint32_t*)(u + (size_t)row * D);
  const uint32_t* wr = (const uint32_t*)gw;
#pragma unroll 1
  for (int j = 0; j < D / 2; j++) { const uint32_t pr = hmul2(xr[j], wr[j]); s += bf_lo(pr); s += bf_hi(pr); }
  s = bf_round(s);
  return pack_bf16(1.f / (1.f + expf(-s)), 0.f);
}

__device__ __forceinline__ uint2 gate_ld(int x) {
  uint2 gv;
  asm volatile("ld.relaxed.gpu.global.v2.u32 {%0,%1}, [%2];" : "=r"(gv.x), "=r"(gv.y) : "l"(g_gate + x * 2) : "memory");
  return gv;
}
__device__ __noinline__ uint32_t gate_poll(const Params* pp, int x, uint32_t tag) {
  uint2 gv;
#pragma unroll 1
  for (int spins = 0; spins < (1 << 16); spins++) {
    gv = gate_ld(x);
    if ((gv.x >> 16) == tag && (gv.y >> 16) == tag) return __byte_perm(gv.x, gv.y, 0x5410);
  }
  return __byte_perm(gate_slow(pp->u, pp->gw, x * 2), gate_slow(pp->u, pp->gw, x * 2 + 1), 0x5410);
}
__device__ __forceinline__ uint32_t gate_fin(const Params& p, uint2 gv, int x, uint32_t tag) {
  if ((gv.x >> 16) == tag && (gv.y >> 16) == tag) return __byte_perm(gv.x, gv.y, 0x5410);
  return gate_poll(&p, x, tag);
}

__device__ __forceinline__ void ld4ch(uint32_t* v, uint32_t addr) {
#pragma unroll
  for (int k = 0; k < 4; k++) v[k] = lds32(addr + k * CH_BYTES);
}
__device__ __forceinline__ void skip_terms(uint32_t* ua, uint32_t* ub, uint32_t sb, int x, uint2 dA, uint2 dB) {
  const int c = x >> 2;
  uint32_t uu[4];
  ld4ch(uu, sb + CH_OFF + (x & 3) * 4 + U_OFF + (c & 3) * U_CS + (63 - (c >> 2)) * 16);
#pragma unroll
  for (int k = 0; k < 4; k++) {
    ua[k] = hmul2(uu[k], __byte_perm((k & 2) ? dA.y : dA.x, 0, (k & 1) ? 0x3232 : 0x1010));
    ub[k] = hmul2(uu[k], __byte_perm((k & 2) ? dB.y : dB.x, 0, (k & 1) ? 0x3232 : 0x1010));
  }
}
__device__ __forceinline__ uint4 mix(const uint32_t* a, const uint32_t* b, const uint32_t* ua, const uint32_t* ub, uint32_t g2) {
  const uint32_t h2 = hsub2(0x3f803f80u, g2);
  uint32_t o[4];
#pragma unroll
  for (int k = 0; k < 4; k++) o[k] = hadd2(hmul2(g2, hadd2(a[k], ua[k])), hmul2(h2, hadd2(b[k], ub[k])));
  return make_uint4(__byte_perm(o[0], o[1], 0x5410), __byte_perm(o[2], o[3], 0x5410), __byte_perm(o[0], o[1], 0x7632), __byte_perm(o[2], o[3], 0x7632));
}
__device__ __forceinline__ void send_box(uint32_t sb, int slot, int wtid, uint32_t rank, uint4 r) {
  st_async4(mapa(sb + XIN_OFF + slot * 2048 + wtid * 16, rank ^ 1), mapa(sb + B_X + slot * 8, rank ^ 1), r.x, r.y, r.z, r.w);
}
__device__ __forceinline__ void merge_rows(uint32_t st, uint32_t rank, uint4 r, uint4 q) {
  const uint4 lo = rank ? q : r, hi = rank ? r : q;
  sts128(st, lo.x, lo.y, hi.x, hi.y); sts128(st + 2048, lo.z, lo.w, hi.z, hi.w);
}
__device__ __forceinline__ void merge_box(uint32_t sb, const CUtensorMap* tm_out, int slot, int wtid, uint32_t rank, int oc0, uint4 r, int barid) {
  const uint32_t st = sb + RAW_OFF + slot * 4096 + wtid * 16;
  mbar_wait(sb + B_X + slot * 8);
  merge_rows(st, rank, r, lds128(sb + XIN_OFF + slot * 2048 + wtid * 16));
  fence_async();
  bar_sync(barid, 128);
  if (wtid == 0) {
    asm volatile("cp.async.bulk.tensor.3d.global.shared::cta.bulk_group [%0, {%2, %3, %4}], [%1];"
                 ::"l"(tm_out), "r"(sb + RAW_OFF + slot * 4096), "r"(oc0), "r"((2 * slot + (int)rank) * 128), "r"(0) : "memory");
    asm volatile("cp.async.bulk.commit_group;" ::: "memory");
  }
}

__device__ __forceinline__ uint32_t band2(int e, int lo, int hi) {
  uint32_t r = ((uint32_t)(e - lo) <= (uint32_t)(hi - lo) ? 0x3f80u : 0u) | ((uint32_t)(e - 1 - lo) <= (uint32_t)(hi - lo) ? 0x3f800000u : 0u);
  asm volatile("" : "+r"(r));
  return r;
}

__device__ __forceinline__ void stage_done(uint32_t sb, int stage, int lane) {
  __syncwarp();
  if (lane == 0) asm volatile("mbarrier.arrive.shared::cta.b64 _, [%0];" ::"r"(sb + B_ST + 8 * stage) : "memory");
}
#define PK2(v, i) pack_bf16(v[i], v[(i) + 1])

__device__ __forceinline__ void conv_dense(uint32_t sb, uint32_t cb, uint32_t zz) {
  const int lane = threadIdx.x & 31, wq = (threadIdx.x >> 5) & 3, br = wq >> 1, hf = wq & 1, g = lane >> 2, t = lane & 3;
  const uint32_t rb = cb + R_OFF + br * R_BR;
  const int eo = 16 * hf + g - 2 * t;
  const int x0 = RD_X0 - (eo + 536);
  const uint32_t fa = rb + ((g & 1) ? 2 * x0 : RD_CS + 2 * x0 + 2);
  const uint64_t ub = mkdesc(cb + U_OFF, U_CS, 128);
  const uint32_t yd = cb + Y0_OFF + br * 4096 + ysw(4 * (63 - 8 * (lane >> 4) - (lane & 7)) + 2 * hf + ((lane >> 3) & 1));
  uint32_t A[2][4][4];
  float e64[32], e56[28], e48[24];
  auto loadA = [&](int j) {
#pragma unroll
    for (int k = 0; k < 4; k++) {
      const int s = 34 - 4 * j - k;
      if (s >= 0) {
        if (k == 0 && j == 0) A[0][0][2] = ldf(fa, 2 * s + 2, 2, 67, hf);
        A[j & 1][k][0] = ldf(fa, 2 * s + 1, 2, 67, hf);
        A[j & 1][k][1] = ldf(fa, 2 * s, 2, 67, hf);
      }
    }
#pragma unroll
    for (int k = 0; k < 4; k++) {
      if (34 - 4 * j - k >= 0) {
        A[j & 1][k][3] = A[j & 1][k][0];
        if (k) A[j & 1][k][2] = A[j & 1][k - 1][1];
        else if (j) A[j & 1][0][2] = A[(j - 1) & 1][3][1];
      }
    }
  };
  loadA(0); loadA(1);
#pragma unroll
  for (int j = 0; j < 9; j++) {
    if (j == 4) {
      wg_wait0();
      stsm2t(yd - 7 * 512, PK2(e64, 28), PK2(e64, 30));
#pragma unroll
      for (int i = 0; i < 28; i++) e56[i] = FCPY(e64, i);
      stage_done(sb, 0, lane);
    }
    if (j == 8) {
      wg_wait0();
      stsm2t(yd - 6 * 512, PK2(e56, 24), PK2(e56, 26));
#pragma unroll
      for (int i = 0; i < 24; i++) e48[i] = FCPY(e56, i);
      stage_done(sb, 1, lane);
    }
    wg_fence();
#pragma unroll
    for (int k = 0; k < 4; k++) {
      const int s = 34 - 4 * j - k;
      if (s >= 0) {
        const int o = 2 * s - 66 + 128;
        const int cc = o & 3, rs = (o >> 2) - 32;
        const uint64_t desc = ub + (uint64_t)((cc * U_CS - rs * 16) >> 4);
        const uint32_t* a = A[j & 1][k];
        if (j < 4) wgmma_rs<64, 0>(e64, a[0], a[1], a[2], a[3], desc, s != 34);
        else if (j < 8) wgmma_rs<56, 0>(e56, a[0], a[1], a[2], a[3], desc, 1);
        else wgmma_rs<48, 0>(e48, a[0], a[1], a[2], a[3], desc, 1);
      }
    }
    wg_commit();
    if (j >= 1 && j < 8) { wg_wait1(); loadA(j + 1); }
  }
  wg_wait0();
#pragma unroll
  for (int i = 0; i < 6; i += 2) stsm4t(yd - i * 512, PK2(e48, 4 * i), PK2(e48, 4 * i + 2), PK2(e48, 4 * i + 4), PK2(e48, 4 * i + 6));
}

__device__ __noinline__ unsigned int gate_rows(const Params* pp, int grow, int step, int rend) {
  const __nv_bfloat16 *u = pp->u, *gw = pp->gw;
  const int lane = threadIdx.x & 31;
  uint4 gx[4][2], nx[4][2];
#pragma unroll
  for (int i = 0; i < 4; i++) {
    nx[i][0] = ldg128(u + (size_t)(grow + i) * D + lane * 8);
    nx[i][1] = ldg128(u + (size_t)(grow + i) * D + 256 + lane * 8);
  }
  const uint4 gw0 = ldg128(gw + lane * 8), gw1 = ldg128(gw + 256 + lane * 8);
  const uint32_t ws[8] = {gw0.x, gw0.y, gw0.z, gw0.w, gw1.x, gw1.y, gw1.z, gw1.w};
  unsigned int epoch;
  asm volatile("ld.relaxed.gpu.global.u32 %0, [%1];" : "=r"(epoch) : "l"(&g_epoch) : "memory");
#pragma unroll 1
  for (; grow < rend; grow += step) {
#pragma unroll
    for (int i = 0; i < 4; i++) { gx[i][0] = nx[i][0]; gx[i][1] = nx[i][1]; }
    if (grow + step < rend) {
#pragma unroll
      for (int i = 0; i < 4; i++) {
        nx[i][0] = ldg128(u + (size_t)(grow + step + i) * D + lane * 8);
        nx[i][1] = ldg128(u + (size_t)(grow + step + i) * D + 256 + lane * 8);
      }
    }
    float c[2][4];
#pragma unroll
    for (int i = 0; i < 2; i++) {
      const uint4 *x = gx[2 * i], *y = gx[2 * i + 1];
      const uint32_t xs[8] = {x[0].x, x[0].y, x[0].z, x[0].w, x[1].x, x[1].y, x[1].z, x[1].w};
      const uint32_t ys[8] = {y[0].x, y[0].y, y[0].z, y[0].w, y[1].x, y[1].y, y[1].z, y[1].w};
      c[i][0] = c[i][1] = c[i][2] = c[i][3] = 0.f;
#pragma unroll
      for (int j = 0; j < 8; j += 2)
        mma16816(c[i], hmul2(xs[j], ws[j]), hmul2(ys[j], ws[j]), hmul2(xs[j + 1], ws[j + 1]), hmul2(ys[j + 1], ws[j + 1]), 0x3f803f80u, 0x3f803f80u);
    }
    float s = (lane & 2) ? ((lane & 1) ? c[1][2] : c[1][0]) : ((lane & 1) ? c[0][2] : c[0][0]);
#pragma unroll
    for (int o = 4; o < 32; o <<= 1) s += __shfl_xor_sync(0xffffffffu, s, o);
    s = bf_round(s);
    const float gv = 1.f / (1.f + expf(-s));
    const uint32_t w = ((epoch + 1) << 16) | (pack_bf16(gv, 0.f) & 0xffffu);
    if (lane < 4) asm volatile("st.relaxed.gpu.global.u32 [%0], %1;" ::"l"(&g_gate[grow + lane]), "r"(w) : "memory");
  }
  return epoch;
}
#define GW 1
constexpr int GSPLIT = L - 4 * GW * NCTA;
__device__ __noinline__ void gate_cta(const Params* pp) {
  const unsigned int epoch = gate_rows(pp, (blockIdx.x * 20 + (threadIdx.x >> 5)) * 4, 80 * NGATE, GSPLIT);
  __syncthreads();
  if (threadIdx.x == 0 && atomicAdd(&g_ticket, 1u) == NCTA + NGATE - 1) { g_ticket = 0; g_epoch = epoch + 1; }
}

__global__ void __cluster_dims__(2, 1, 1) __launch_bounds__(640, 1)
ssm_kernel(const __grid_constant__ Params p, const __grid_constant__ CUtensorMap tm_in, const __grid_constant__ CUtensorMap tm_out) {
  extern __shared__ __align__(1024) unsigned char smem_raw[];
  const uint32_t sb = (uint32_t)__cvta_generic_to_shared(smem_raw);
  const int tid = threadIdx.x, lane = tid & 31;
  const int warp = __shfl_sync(0xffffffffu, tid >> 5, 0);
  const int ch = warp >> 2, wq = warp & 3, br = wq >> 1, hf = wq & 1;
  const int g = lane >> 2, t = lane & 3;
  if (__builtin_expect(blockIdx.x < NGATE, 0)) { gate_cta(&p); return; }
  const int bid = blockIdx.x - NGATE;
  const uint32_t rank = blockIdx.x & 1;
  const uint32_t cb = sb + CH_OFF + ch * CH_BYTES;
  const int wtid = tid & 127;
  const int oc0 = (bid >> 1) * 8;
  STAMP(0); GT(0);

  if (warp >= 16) {
    if (wtid == 0) {
      mbar_init_expect(sb + B_RAW, 32768);
#pragma unroll
      for (int i = 0; i < 4; i++) mbar_init_expect(sb + B_X + 8 * i, 2048);
      asm volatile("mbarrier.init.shared::cta.b64 [%0], 128;" ::"r"(sb + B_U) : "memory");
      asm volatile("mbarrier.init.shared::cta.b64 [%0], 128;" ::"r"(sb + B_W) : "memory");
#pragma unroll
      for (int i = 0; i < 7; i++) asm volatile("mbarrier.init.shared::cta.b64 [%0], 16;" ::"r"(sb + B_ST + 8 * i) : "memory");
      asm volatile("fence.mbarrier_init.release.cluster;" ::: "memory");
      asm volatile("fence.proxy.async.shared::cta;" ::: "memory");
    }
    __syncwarp();
    asm volatile("barrier.cluster.arrive.relaxed.aligned;" ::: "memory");
    if (wq >= 4 - GW) gate_rows(&p, GSPLIT + (bid * GW + 3 - wq) * 4, L, L);
    unsigned int epoch;
    asm volatile("ld.relaxed.gpu.global.u32 %0, [%1];" : "=r"(epoch) : "l"(&g_epoch) : "memory");
    asm volatile("barrier.cluster.wait.aligned;" ::: "memory");
    if (wtid == 0) {
      asm volatile("cp.async.bulk.tensor.5d.shared::cluster.global.mbarrier::complete_tx::bytes.multicast::cluster [%0], [%1, {%3, %4, %4, %4, %5}], [%2], %6;"
                   ::"r"(sb + RAW_OFF + rank * 16384), "l"(&tm_in), "r"(sb + B_RAW), "r"(oc0), "r"(0), "r"((int)rank * 32), "h"((unsigned short)3) : "memory");
    }
    sts128(sb + CH_OFF + wq * CH_BYTES + U_OFF + (lane >> 3) * U_CS + (64 + (lane & 7)) * 16, 0, 0, 0, 0);
    const uint2 dA = ldg64(p.A_D + bid * 4), dB = ldg64(p.B_D + bid * 4);
    uint32_t BA[3][4], BB[4][4];
    {
      const int l1 = br ? 3 : 6, h1 = br ? 5 : 10, l2 = br ? 5 : 12, h2 = br ? 11 : 20;
#pragma unroll
      for (int i = 0; i < 4; i++) {
        const int e = 16 * hf + g - 2 * t + 32 - 16 * i;
        BB[i][0] = band2(e, l2, h2); BB[i][1] = band2(e + 8, l2, h2); BB[i][2] = band2(e - 8, l2, h2); BB[i][3] = BB[i][0];
        if (i) { BA[i - 1][0] = band2(e, l1, h1); BA[i - 1][1] = band2(e + 8, l1, h1); BA[i - 1][2] = band2(e - 8, l1, h1); BA[i - 1][3] = BA[i - 1][0]; }
      }
    }
    const uint32_t tag = (epoch + 1) & 0xffffu;
    if (wtid == 0) sts32(sb + TAG_OFF, tag);
    STAMP(3);
    mbar_wait(sb + B_RAW);
    STAMP(4);
    {
      const uint32_t dst = sb + CH_OFF + (g & 3) * CH_BYTES + U_OFF + t * U_CS + (63 - wq * 16) * 16;
#pragma unroll
      for (int h = 0; h < 2; h++) {
        uint32_t r[8][4];
#pragma unroll
        for (int i = 0; i < 8; i++) ldsm4t(sb + RAW_OFF + (wq * 16 + h * 8 + i) * 512 + lane * 16, r[i][0], r[i][1], r[i][2], r[i][3]);
        if ((uint32_t)(g >> 2) == rank) {
#pragma unroll
          for (int i = 0; i < 8; i++) sts128(dst - (h * 8 + i) * 16, r[i][0], r[i][1], r[i][2], r[i][3]);
        }
      }
    }
    fence_async();
    asm volatile("mbarrier.arrive.shared::cta.b64 _, [%0];" ::"r"(sb + B_U) : "memory");
    bar_sync(5, 128);
    STAMP(5);
    {
      const int mrow = lane & 7, mi = lane >> 3;
      const uint64_t ub0 = mkdesc(sb + CH_OFF + U_OFF, U_CS, 128);
      uint32_t wa, wb;
      {
        const int c = 4 * (47 - 8 * (mi >> 1) - mrow) + 2 * hf + (mi & 1);
        wa = sb + CH_OFF + (br ? W3_OFF : W5_OFF) + (5 - (c >> 5)) * 576 + ((c & 31) >> 3) * 144 + (c & 7) * 16;
        const int c2 = c - 64, pp = c2 >> 1;
        wb = sb + CH_OFF + (br ? W7_OFF : W9_OFF) + (1 - (pp >> 5)) * 1152 + (c2 & 1) * 576 + ((pp & 31) >> 3) * 144 + (pp & 7) * 16;
      }
      {
        float w1[24];
#pragma unroll
        for (int i = 0; i < 24; i++) w1[i] = 0.f;
#pragma unroll 1
        for (int k = 0; k < 4; k++) {
          wg_fence();
#pragma unroll
          for (int i = 0; i < 3; i++)
            wgmma_rs<48, 0>(w1, BA[i][0], BA[i][1], BA[i][2], BA[i][3],
                            ub0 + (uint64_t)((k * CH_BYTES + ((2 * i + 2) & 3) * U_CS + (16 + (i == 0)) * 16) >> 4), i);
          wg_commit();
          wg_wait0();
#pragma unroll
          for (int i = 0; i < 3; i++) stsm4t(wa + k * CH_BYTES + i * 1152, PK2(w1, 8 * i), PK2(w1, 8 * i + 2), PK2(w1, 8 * i + 4), PK2(w1, 8 * i + 6));
        }
      }
      {
        float w2[2][16];
#pragma unroll
        for (int i = 0; i < 16; i++) { w2[0][i] = 0.f; w2[1][i] = 0.f; }
#pragma unroll 1
        for (int kp = 0; kp < 2; kp++) {
          wg_fence();
#pragma unroll
          for (int k = 0; k < 2; k++)
#pragma unroll
            for (int i = 0; i < 4; i++)
              wgmma_rs<32, 0>(w2[k], BB[i][0], BB[i][1], BB[i][2], BB[i][3],
                              ub0 + (uint64_t)(((2 * kp + k) * CH_BYTES + ((2 * i) & 3) * U_CS + (32 + (i < 2)) * 16) >> 4), i);
          wg_commit();
          wg_wait0();
#pragma unroll
          for (int k = 0; k < 2; k++)
#pragma unroll
            for (int i = 0; i < 2; i++)
              stsm4t(wb + (2 * kp + k) * CH_BYTES + i * 1152, PK2(w2[k], 8 * i), PK2(w2[k], 8 * i + 2), PK2(w2[k], 8 * i + 4), PK2(w2[k], 8 * i + 6));
        }
      }
    }
    fence_async();
    asm volatile("mbarrier.arrive.shared::cta.b64 _, [%0];" ::"r"(sb + B_W) : "memory");
    STAMP(7);
    {
      const int bsel = (int)rank ^ br ^ 1, xl = wtid & 63;
      uint2 gl[4];
      uint32_t ua[4][4], ub[4][4];
#pragma unroll
      for (int i = 0; i < 4; i++) skip_terms(ua[i], ub[i], sb, (2 * (i >> 1) + bsel) * 128 + (i & 1) * 64 + xl, dA, dB);
      const uint32_t yo = sb + CH_OFF + (xl & 3) * 4 + ysw(xl >> 2) + bsel * 512;
#pragma unroll
      for (int i = 0; i < 2; i++) gl[i] = gate_ld(bsel * 128 + i * 64 + xl);
#pragma unroll
      for (int slot = 0; slot < 2; slot++) {
        const int box = 2 * slot + bsel;
        uint32_t g2[2], ya[2][4], yb[2][4];
#pragma unroll
        for (int h = 0; h < 2; h++) g2[h] = gate_fin(p, gl[2 * slot + h], box * 128 + h * 64 + xl, tag);
        mbar_wait(sb + B_ST + 8 * box);
        STAMP(8 + slot);
        if (slot == 0) { gl[2] = gate_ld((2 + bsel) * 128 + xl); gl[3] = gate_ld((2 + bsel) * 128 + 64 + xl); }
#pragma unroll
        for (int h = 0; h < 2; h++) {
          const uint32_t yh = (yo ^ (h * 32)) + h * 256 + slot * 1024;
          ld4ch(ya[h], yh + Y0_OFF); ld4ch(yb[h], yh + Y0_OFF + 4096);
          if (slot) {
            uint32_t a2[4], b2[4];
            ld4ch(a2, yh + Y2_OFF - 1024); ld4ch(b2, yh + Y2_OFF - 1024 + 3072);
#pragma unroll
            for (int k = 0; k < 4; k++) { ya[h][k] = hadd2(ya[h][k], a2[k]); yb[h][k] = hadd2(yb[h][k], b2[k]); }
          }
        }
        const uint4 r0 = mix(ya[0], yb[0], ua[2 * slot], ub[2 * slot], g2[0]), r1 = mix(ya[1], yb[1], ua[2 * slot + 1], ub[2 * slot + 1], g2[1]);
        if (br == 0) { send_box(sb, slot, xl, rank, r0); send_box(sb, slot, xl + 64, rank, r1); }
        else {
          const uint32_t st = sb + RAW_OFF + slot * 4096 + xl * 16, xin = sb + XIN_OFF + slot * 2048 + xl * 16;
          mbar_wait(sb + B_X + slot * 8);
          const uint4 q0 = lds128(xin), q1 = lds128(xin + 1024);
          merge_rows(st, rank, r0, q0); merge_rows(st + 1024, rank, r1, q1);
          fence_async();
          bar_sync(6, 64);
          if (xl == 0) {
            asm volatile("cp.async.bulk.tensor.3d.global.shared::cta.bulk_group [%0, {%2, %3, %4}], [%1];"
                         ::"l"(&tm_out), "r"(sb + RAW_OFF + slot * 4096), "r"(oc0), "r"(box * 128), "r"(0) : "memory");
            asm volatile("cp.async.bulk.commit_group;" ::: "memory");
          }
        }
        STAMP(10 + slot);
      }
    }
    if (wtid == 0 && atomicAdd(&g_ticket, 1u) == NCTA + NGATE - 1) { g_ticket = 0; g_epoch = epoch + 1; }
    if (wtid == 64) asm volatile("cp.async.bulk.wait_group.read 0;" ::: "memory");
    STAMP(15);
    return;
  }
  asm volatile("barrier.cluster.arrive.relaxed.aligned;" ::: "memory");

  const int moff = (bid * 4 + (tid >> 7)) * NM + (tid & 63) * 2;
  const int brt = (tid >> 6) & 1;
  const __nv_bfloat16* const* tp = p.t + (brt ? 0 : 6);
  const uint32_t q0 = *(const uint32_t*)(tp[0] + moff), q1 = *(const uint32_t*)(tp[1] + moff);
  const uint32_t q2 = *(const uint32_t*)(tp[2] + moff), q3 = *(const uint32_t*)(tp[3] + moff);
  const uint2 ldt4 = *(const uint2*)(tp[4] + bid * 4);
  const uint32_t q4 = *(const uint32_t*)(tp[brt ? 2 : 5] + moff), q5 = *(const uint32_t*)(tp[brt ? 3 : 6] + moff);

  for (int i = wtid & 63; i < R_BR / 16; i += 64) sts128(cb + R_OFF + br * R_BR + i * 16, 0, 0, 0, 0);
  STAMP(1);

  float acc[5][4];
  float k2048 = 0.f;
  const uint32_t scr = cb + Y0_OFF + wq * SCR_BYTES;
  const uint32_t scr2 = sb + SC2_OFF + warp * 640;
  {
    const uint32_t ldt2 = (ch & 2) ? ldt4.y : ldt4.x;
    const float dt = bf_round(expf((ch & 1) ? bf_hi(ldt2) : bf_lo(ldt2)));
#pragma unroll
    for (int i = 0; i < 5; i++) acc[i][0] = acc[i][1] = acc[i][2] = acc[i][3] = 0.f;
    STAMP(2);
    const uint32_t tb = scr + lane * 16;
    const uint32_t tb1 = tb + hf * 512, tb2 = tb + (hf ^ 1) * 512;
    const uint32_t ta = scr + (lane >> 3) * 512 + (lane & 7) * 16;
    const uint32_t tc = ((lane & 8) ? scr2 : scr + 4096) + (lane >> 4) * 128 + (lane & 7) * 16;
    const uint32_t tm = scr2 + 512 + ((lane >> 3) & 1) * 64 + (lane >> 4) * 16;
#pragma unroll 1
    for (int r = 0; r < 2; r++) {
      cf c, z1, z128;
      {
        const uint32_t sh = r ? 0x3244u : 0x1044u;
        float v0 = __uint_as_float(__byte_perm(q0, 0, sh));
        const float v1 = __uint_as_float(__byte_perm(q1, 0, sh)), v2 = __uint_as_float(__byte_perm(q2, 0, sh)), v3 = __uint_as_float(__byte_perm(q3, 0, sh));
        if (br == 0) { c = cmul(cf{v2, v3}, cf{dt * __uint_as_float(__byte_perm(q4, 0, sh)), dt * __uint_as_float(__byte_perm(q5, 0, sh))}); }
        else { v0 = -bf_round(expf(v0)); c = cf{2.f * dt * v2, 2.f * dt * v3}; }
        const float xl = (dt * v0) * 1.4426950408889634f, y = dt * v1;
        z1 = cexp_p(xl, y, 1.f); z128 = cexp_p(xl, y, 128.f);
      }
      const cf z2 = csq(z1), z4 = csq(z2), z8 = csq(z4);
      const cf w8 = {z8.re, -z8.im};
      const cf z16 = csq(w8), z24 = cmul(z16, w8), z32 = csq(z16), z40 = cmul(z32, w8), z48 = csq(z24), z56 = cmul(z32, z24), z64 = csq(z32);
      const cf z256 = csq(z128), z512 = csq(z256), z1024 = csq(z512), z2048 = csq(z1024);
      {
        float kk = fmaf(c.re, z2048.re, -c.im * z2048.im);
#pragma unroll
        for (int o = 16; o; o >>= 1) kk += __shfl_xor_sync(0xffffffffu, kk, o);
        k2048 += kk;
      }
      __syncwarp();
      {
        uint32_t xr[4] = {pack_bf16(1.f, z8.re), pack_bf16(z16.re, z24.re), pack_bf16(z32.re, z40.re), pack_bf16(z48.re, z56.re)};
        uint32_t xi[4] = {pack_bf16(0.f, w8.im), pack_bf16(z16.im, z24.im), pack_bf16(z32.im, z40.im), pack_bf16(z48.im, z56.im)};
        sts128(tb1, xr[0], xr[1], xr[2], xr[3]);
        sts128(tb1 + 1024, xi[0], xi[1], xi[2], xi[3]);
        const uint32_t yr = pack_bf16(z64.re, z64.re), yi = pack_bf16(z64.im, z64.im), nyi = yi ^ 0x80008000u;
        uint32_t o[4], q[4];
#pragma unroll
        for (int i = 0; i < 4; i++) CMUL2(o[i], q[i], xr[i], xi[i], yr, yi, nyi);
        sts128(tb2, o[0], o[1], o[2], o[3]);
        sts128(tb2 + 1024, q[0], q[1], q[2], q[3]);
      }
      {
        const cf h1 = cmul(c, z128), h2 = cmul(c, z256), h3 = cmul(h1, z256), h4 = cmul(c, z512), h5 = cmul(h1, z512), h6 = cmul(h2, z512), h7 = cmul(h3, z512);
        const cf e1 = cmul(c, z1), e2 = cmul(c, z2), e3 = cmul(e1, z2), e129 = cmul(h1, z1), e130 = cmul(h1, z2), e131 = cmul(e129, z2);
        const cf e258 = cmul(h2, z2), e386 = cmul(h3, z2);
        const uint32_t pr0 = pack_bf16(c.re, e1.re), pr2 = pack_bf16(h1.re, e129.re), pi0 = pack_bf16(c.im, e1.im), pi2 = pack_bf16(h1.im, e129.im);
        sts128(tb + 4 * 512, pr0, pack_bf16(e2.re, e3.re), pr2, pack_bf16(e130.re, e131.re));
        sts128(tb + 5 * 512, pi0, pack_bf16(e2.im, e3.im), pi2, pack_bf16(e130.im, e131.im));
        uint32_t xr[4] = {pack_bf16(h2.re, e258.re), pack_bf16(h3.re, e386.re), pack_bf16(h4.re, h5.re), pack_bf16(h6.re, h7.re)};
        uint32_t xi[4] = {pack_bf16(h2.im, e258.im), pack_bf16(h3.im, e386.im), pack_bf16(h4.im, h5.im), pack_bf16(h6.im, h7.im)};
        sts128(tb + 6 * 512, xr[0], xr[1], xr[2], xr[3]);
        sts128(tb + 7 * 512, xi[0], xi[1], xi[2], xi[3]);
        xr[1] = __byte_perm(xr[0], xr[1], 0x5410); xi[1] = __byte_perm(xi[0], xi[1], 0x5410);
        xr[0] = __byte_perm(pr0, pr2, 0x5410); xi[0] = __byte_perm(pi0, pi2, 0x5410);
        const uint32_t yr = pack_bf16(z1024.re, z1024.re), yi = pack_bf16(z1024.im, z1024.im), nyi = yi ^ 0x80008000u;
        uint32_t o[4], q[4];
#pragma unroll
        for (int i = 0; i < 4; i++) CMUL2(o[i], q[i], xr[i], xi[i], yr, yi, nyi);
        sts128(tb + 8 * 512, o[0], o[1], o[2], o[3]);
        sts128(scr2 + lane * 16, q[0], q[1], q[2], q[3]);
        const uint32_t m4 = pack_bf16(z4.re, z4.im);
        sts16(scr2 + 512 + lane * 2, m4); sts16(scr2 + 576 + lane * 2, m4 >> 16);
      }
      __syncwarp();
#pragma unroll
      for (int kp = 0; kp < 2; kp++) {
        uint32_t rr[2], ri[2], yr[2], yi[2];
        ldsm4t(tc + kp * 256, rr[0], ri[0], rr[1], ri[1]);
        ldsm4(tm + kp * 32, yr[0], yi[0], yr[1], yi[1]);
#pragma unroll
        for (int k2 = 0; k2 < 2; k2++) {
          const int kk = kp * 2 + k2;
          uint32_t a0, a1, a2, a3, pr, pi, qr, qi, xr, xi;
          ldsm4t(ta + kk * 128, a0, a1, a2, a3);
          ldsm4t(ta + 2048 + kk * 128, pr, pi, qr, qi);
          const uint32_t nyi = yi[k2] ^ 0x80008000u;
          mma16816(acc[0], a0, a1, a2, a3, pr, pi);
          mma16816(acc[2], a0, a1, a2, a3, qr, qi);
          mma16816(acc[4], a0, a1, a2, a3, rr[k2], ri[k2]);
          CMUL2(xr, xi, pr, pi, yr[k2], yi[k2], nyi);
          mma16816(acc[1], a0, a1, a2, a3, xr, xi);
          CMUL2(xr, xi, qr, qi, yr[k2], yi[k2], nyi);
          mma16816(acc[3], a0, a1, a2, a3, xr, xi);
        }
      }
    }
  }
  STAMP(3);
  __syncwarp();
  {
    const uint32_t xs = scr + lane * 16;
#define OTH(i, k) __float_as_uint(acc[i][2 + (k)])
    sts128(xs, OTH(0, 0), OTH(0, 1), OTH(1, 0), OTH(1, 1));
    sts128(xs + 512, OTH(2, 0), OTH(2, 1), OTH(3, 0), OTH(3, 1));
    sts128(xs + 1024, OTH(4, 0), OTH(4, 1), __float_as_uint(k2048), 0);
#undef OTH
  }

  bar_sync(7 + (warp >> 1), 64);
  STAMP(4);
  {
    const uint32_t xo = cb + Y0_OFF + (wq ^ 1) * SCR_BYTES + lane * 16;
    const uint4 o0 = lds128(xo), o1 = lds128(xo + 512), o2 = lds128(xo + 1024);
    const uint32_t rb = cb + R_OFF + br * R_BR;
#define OWN(i, k) acc[i][k]
    const uint32_t vP = pack_bf16(OWN(0, 1) + __uint_as_float(o0.y), OWN(0, 0) + __uint_as_float(o0.x));
    const uint32_t vP4 = pack_bf16(OWN(1, 1) + __uint_as_float(o0.w), OWN(1, 0) + __uint_as_float(o0.z));
    const uint32_t vQ = pack_bf16(OWN(2, 1) + __uint_as_float(o1.y), OWN(2, 0) + __uint_as_float(o1.x));
    const uint32_t vQ4 = pack_bf16(OWN(3, 1) + __uint_as_float(o1.w), OWN(3, 0) + __uint_as_float(o1.z));
    const uint32_t vR = pack_bf16(OWN(4, 1) + __uint_as_float(o2.y), OWN(4, 0) + __uint_as_float(o2.x));
#undef OWN
    const int j = g + 8 * hf;
    {
      const int a = 2 * (t & 1) + 64 * (t & 2) + 8 * j;
      const uint32_t ad = rb + 2 * (RD_X0 - 1 - a);
      const uint32_t a1 = (t & 2) ? ad - 8 : ad, a2 = (t & 2) ? ad : ad - 8;
      const uint32_t w1 = (t & 2) ? vP4 : vP, w2 = (t & 2) ? vP : vP4;
      sts32(a1, w1); sts32(a2, w2);
      sts16(a1 + RD_CS + 2, w1); sts16(a1 + RD_CS + 4, w1 >> 16);
      sts16(a2 + RD_CS + 2, w2); sts16(a2 + RD_CS + 4, w2 >> 16);
    }
    if (t < 2) {
      const int b = 256 + 128 * t + 8 * j;
      const uint32_t ad = rb + 2 * (RD_X0 - 6 - b);
      const uint32_t v22 = __byte_perm(vQ4, 0, 0x3232), v00 = __byte_perm(vQ, 0, 0x3232);
      sts16(ad, vQ4);
      sts64(ad + 2, v22, __byte_perm(vQ4, vQ, 0x5432));
      sts32(ad + 10, v00);
      if (b != 256) { sts16(ad + 14, v00); sts128(ad + RD_CS + 2, vQ4, v22, vQ, v00); }
      else { sts64(ad + RD_CS + 2, vQ4, v22); sts32(ad + RD_CS + 10, vQ); sts16(ad + RD_CS + 14, v00); }
    } else {
      const uint32_t ao = rb + R_O2 + 2 * (159 - (32 * t + j)), ae = ao - (R_O2 - R_E2) + 2;
      sts16(ao, vQ4 >> 16); sts16(ao + RS_CS + 2, vQ4 >> 16); sts16(ao - 32, vQ4); sts16(ao - 32 + RS_CS + 2, vQ4);
      sts16(ae - 32, vQ); sts16(ae - 32 + RS_CS + 2, vQ);
      if (lane != 2 || hf) { sts16(ae, vQ >> 16); sts16(ae + RS_CS + 2, vQ >> 16); }
      else {
        const uint32_t vv = __byte_perm(vQ, 0, 0x3232), ad = rb + 2 * (RD_X0 - 514);
        sts16(ad, vv); sts32(ad + 2, vv); sts16(ad + 6, vv); sts64(ad + RD_CS + 2, vv, vv);
      }
    }
    {
      const uint32_t a = rb + ((g & 1) ? R_O3 : R_E3 + 2) + 2 * (159 - (64 + 16 * t + (j >> 1)));
      const bool p1024 = (lane == 0) && (hf == 0);
      const uint32_t a00 = p1024 ? rb + R_E2 + 2 * (159 - 127) : a;
      sts16(a00, vR >> 16); sts16(a00 + RS_CS + 2, vR >> 16);
      sts16(a - 16, vR); sts16(a - 16 + RS_CS + 2, vR);
      if (p1024) {
        sts32(sb + K1024_OFF + (ch * 2 + br) * 4, __byte_perm(vR, 0, 0x3232));
        const uint32_t kv = pack_bf16(k2048 + __uint_as_float(o2.z), 0.f);
        sts16(rb + R_E3 + 2 * (159 - 127), kv); sts16(rb + R_E3 + 2 * (159 - 127) + RS_CS + 2, kv);
      }
    }
  }
  STAMP(5);
  asm volatile("barrier.cluster.wait.aligned;" ::: "memory");
  bar_sync(7 + (warp >> 1), 64);
  mbar_wait(sb + B_U);
  STAMP(6);

  const uint32_t zz = lds32(cb + R_OFF + br * R_BR);
  conv_dense(sb, cb, zz);
  STAMP(8);
  {
    const int x = (4 + ch) * 128 + wtid, c = x >> 2;
    const uint2 dA = ldg64(p.A_D + bid * 4), dB = ldg64(p.B_D + bid * 4);
    const uint2 gl = gate_ld(x);
    const uint32_t rb = cb + R_OFF + br * R_BR;
    float e48[24], e40[20], e32[16], h32[16], h16[8];
    const int x1 = 159 - (16 * hf + g - 2 * t + 136);
    const uint32_t fs = rb + ((g & 1) ? 2 * x1 : RS_CS + 2 * x1 + 2);
    uint32_t A[2][4][4];
    auto loadA = [&](int buf, uint32_t oe, uint32_t oo, int i0) {
#pragma unroll
      for (int a = 0; a < 2; a++) {
        const uint32_t base = fs + (a ? oo : oe);
        uint32_t* k0 = A[buf][2 * a];
        uint32_t* k1 = A[buf][2 * a + 1];
        k0[1] = ldf(base, i0, 1, 9, hf); k0[0] = ldf(base, i0 + 1, 1, 9, hf); k0[2] = ldf(base, i0 + 2, 1, 9, hf);
        k1[0] = ldf(base, i0 + 3, 1, 9, hf); k1[2] = ldf(base, i0 + 4, 1, 9, hf);
        k0[3] = k0[0]; k1[1] = k0[2]; k1[3] = k1[0];
      }
    };
    loadA(0, R_E2, R_O2, 8);
    loadA(1, R_E2, R_O2, 4);
    mbar_wait(sb + B_W);
    const uint64_t d5 = mkdesc(cb + W5_OFF, 144, 576), d3 = mkdesc(cb + W3_OFF, 144, 576);
    const uint64_t d9 = mkdesc(cb + W9_OFF, 144, 576), d7 = mkdesc(cb + W7_OFF, 144, 576);
    const uint32_t y2d = cb + Y2_OFF + br * 3072 + ysw(32 * (5 - (lane >> 4)) + 16 * hf + (lane & 15));
    const uint32_t y3d = cb + Y3_OFF + br * 2048 + ysw(2 * (16 * hf + (lane & 15)) + (lane >> 4));
#define FAR4(N, ACC, BUF, DA, DB, OFF, FIRST)                                                            \
    wg_fence();                                                                                           \
    _Pragma("unroll") for (int k = 0; k < 4; k++) {                                                      \
      const uint32_t* a = A[BUF][k];                                                                      \
      wgmma_rs<N, 1>(ACC, a[0], a[1], a[2], a[3], ((k >> 1) ? DB : DA) + (k & 1) * 18 + (OFF), !(FIRST) || k); \
    }                                                                                                     \
    wg_commit();
    FAR4(48, e48, 0, d5, d3, 0, 1)
    wg_wait0();
    loadA(0, R_E2, R_O2, 0);
    stsm2(y2d - 5 * 512, PK2(e48, 20), PK2(e48, 22));
#pragma unroll
    for (int i = 0; i < 20; i++) e40[i] = FCPY(e48, i);
    stage_done(sb, 2, lane);
    FAR4(40, e40, 1, d5, d3, 36, 0)
    wg_wait0();
    loadA(1, R_E3, R_O3, 8);
    stsm2(y2d - 4 * 512, PK2(e40, 16), PK2(e40, 18));
#pragma unroll
    for (int i = 0; i < 16; i++) e32[i] = FCPY(e40, i);
    stage_done(sb, 3, lane);
    FAR4(32, e32, 0, d5, d3, 72, 0)
    FAR4(32, h32, 1, d9, d7, 0, 1)
    wg_wait1();
    loadA(0, R_E3, R_O3, 4);
    stsm4(y2d, PK2(e32, 0), PK2(e32, 2), PK2(e32, 4), PK2(e32, 6));
    stsm4(y2d - 2 * 512, PK2(e32, 8), PK2(e32, 10), PK2(e32, 12), PK2(e32, 14));
    stage_done(sb, 4, lane);
    STAMP(9);
    wg_wait0();
    stsm4(y3d, PK2(h32, 8), PK2(h32, 10), PK2(h32, 12), PK2(h32, 14));
#pragma unroll
    for (int i = 0; i < 8; i++) h16[i] = FCPY(h32, i);
    stage_done(sb, 5, lane);
    FAR4(16, h16, 0, d9, d7, 72, 0)
#undef FAR4
    const uint32_t yo = sb + CH_OFF + (x & 3) * 4 + ysw(c);
    uint32_t ua[4], ub[4], ya[4], yb[4], a2[4], b2[4], a3[4], b3[4], s2[4];
    skip_terms(ua, ub, sb, x, dA, dB);
    {
      const int xa = x - 514, xb = x - 513, ca = xa >> 2, cb2 = xb >> 2;
      ld4ch(s2, sb + CH_OFF + U_OFF + (xa & 3) * 4 + (ca & 3) * U_CS + (63 - (ca >> 2)) * 16);
      ld4ch(a3, sb + CH_OFF + U_OFF + (xb & 3) * 4 + (cb2 & 3) * U_CS + (63 - (cb2 >> 2)) * 16);
#pragma unroll
      for (int k = 0; k < 4; k++) s2[k] = hadd2(s2[k], __byte_perm(s2[k], a3[k], 0x5432));
    }
    const uint32_t tag = lds32(sb + TAG_OFF);
    wg_wait0();
    stsm4(y3d + 1024, PK2(h16, 0), PK2(h16, 2), PK2(h16, 4), PK2(h16, 6));
    stage_done(sb, 6, lane);
    STAMP(10);
    const uint32_t g2 = gate_fin(p, gl, x, tag);
    mbar_wait(sb + B_ST + 8 * 4);
    const uint4 k0 = lds128(sb + K1024_OFF), k1 = lds128(sb + K1024_OFF + 16);
    const uint32_t kk[8] = {k0.x, k0.y, k0.z, k0.w, k1.x, k1.y, k1.z, k1.w};
    ld4ch(ya, yo + Y0_OFF); ld4ch(yb, yo + Y0_OFF + 4096);
    ld4ch(a2, yo + Y2_OFF - 1024); ld4ch(b2, yo + Y2_OFF - 1024 + 3072);
    mbar_wait(sb + B_ST + 8 * (5 + (ch >> 1)));
    STAMP(12);
    ld4ch(a3, yo + Y3_OFF - 2048); ld4ch(b3, yo + Y3_OFF - 2048 + 2048);
#pragma unroll
    for (int k = 0; k < 4; k++) {
      ya[k] = hadd2(ya[k], hadd2(hfma2(kk[2 * k], s2[k], a2[k]), a3[k]));
      yb[k] = hadd2(yb[k], hadd2(hfma2(kk[2 * k + 1], s2[k], b2[k]), b3[k]));
    }
    const uint4 r = mix(ya, yb, ua, ub, g2);
    if ((uint32_t)(ch & 1) != rank) send_box(sb, 2 + (ch >> 1), wtid, rank, r);
    else merge_box(sb, &tm_out, 2 + (ch >> 1), wtid, rank, oc0, r, 1 + ch);
  }
  STAMP(14);
  if (wtid == 0) asm volatile("cp.async.bulk.wait_group.read 0;" ::: "memory");
  STAMP(15); GT(1);
}

typedef CUresult (*EncodeFn)(CUtensorMap*, CUtensorMapDataType, cuuint32_t, void*, const cuuint64_t*, const cuuint64_t*,
                             const cuuint32_t*, const cuuint32_t*, CUtensorMapInterleave, CUtensorMapSwizzle,
                             CUtensorMapL2promotion, CUtensorMapFloatOOBfill);

}

extern "C" void kernel_launch(void* const* d_in, const int* in_sizes, int n_in, void* d_out, int out_size) {
  (void)in_sizes; (void)n_in; (void)out_size;
  typedef const __nv_bfloat16* bp;
  Params p;
  p.t[0] = (bp)d_in[10]; p.t[1] = (bp)d_in[11]; p.t[2] = (bp)d_in[12]; p.t[3] = (bp)d_in[13]; p.t[4] = (bp)d_in[14]; p.t[5] = nullptr;
  p.t[6] = (bp)d_in[1]; p.t[7] = (bp)d_in[2]; p.t[8] = (bp)d_in[5]; p.t[9] = (bp)d_in[6]; p.t[10] = (bp)d_in[7];
  p.t[11] = (bp)d_in[3]; p.t[12] = (bp)d_in[4]; p.t[13] = nullptr;
  p.u = (bp)d_in[0]; p.gw = (bp)d_in[16]; p.A_D = (bp)d_in[8]; p.B_D = (bp)d_in[15];
  static EncodeFn enc = nullptr;
  if (!enc) {
    cudaDriverEntryPointQueryResult qr;
    cudaGetDriverEntryPoint("cuTensorMapEncodeTiled", (void**)&enc, cudaEnableDefault, &qr);
    cudaFuncSetAttribute(ssm_kernel, cudaFuncAttributeMaxDynamicSharedMemorySize, SMEM_BYTES);
  }
  CUtensorMap tm_in, tm_out;
  {
    cuuint64_t gd[5] = {512, 2, 4, 4, 64};
    cuuint64_t gs[4] = {1024, 8192, 2048, 32768};
    cuuint32_t bx[5] = {8, 2, 4, 4, 32};
    cuuint32_t es[5] = {1, 1, 1, 1, 1};
    enc(&tm_in, CU_TENSOR_MAP_DATA_TYPE_BFLOAT16, 5, d_in[0], gd, gs, bx, es, CU_TENSOR_MAP_INTERLEAVE_NONE,
        CU_TENSOR_MAP_SWIZZLE_NONE, CU_TENSOR_MAP_L2_PROMOTION_NONE, CU_TENSOR_MAP_FLOAT_OOB_FILL_NONE);
  }
  {
    cuuint64_t gd[3] = {512, 1024, 2};
    cuuint64_t gs[2] = {2048, 1024};
    cuuint32_t bx[3] = {8, 128, 2};
    cuuint32_t es[3] = {1, 1, 1};
    enc(&tm_out, CU_TENSOR_MAP_DATA_TYPE_BFLOAT16, 3, d_out, gd, gs, bx, es, CU_TENSOR_MAP_INTERLEAVE_NONE,
        CU_TENSOR_MAP_SWIZZLE_NONE, CU_TENSOR_MAP_L2_PROMOTION_NONE, CU_TENSOR_MAP_FLOAT_OOB_FILL_NONE);
  }
  ssm_kernel<<<NCTA + NGATE, 640, SMEM_BYTES, cudaStreamPerThread>>>(p, tm_in, tm_out);
}
```

```cpp
#include <cuda_runtime.h>
#include <cuda.h>
#include <cuda_bf16.h>
#include <stdint.h>

namespace {
#define PREDLD 1
#define FCPY(v, i) (((i) % 3 == 2) ? __uint_as_float(opq(__float_as_uint(v[i]), zz)) : opqf(v[i], zz))

constexpr int L = 2048, D = 512, NM = 128;
constexpr int NCTA = 128;
constexpr int NGATE = 4;

constexpr int RAW_OFF = 0;
constexpr int XIN_OFF = 32768;
constexpr int SC2_OFF = XIN_OFF + 8192;
constexpr int BAR_OFF = SC2_OFF + 10240;
constexpr int CH_OFF = BAR_OFF + 256;
constexpr int U_CS = 1184;
constexpr int U_OFF = 0;
constexpr int R_OFF = 4736;
constexpr int RD_X0 = 565;
constexpr int RD_CS = 1216;
constexpr int RS_CS = 320;
constexpr int R_E2 = 2 * RD_CS, R_O2 = R_E2 + 2 * RS_CS, R_E3 = R_O2 + 2 * RS_CS, R_O3 = R_E3 + 2 * RS_CS + 16;
constexpr int R_BR = R_O3 + 2 * RS_CS - 16;
constexpr int W5_OFF = R_OFF + 2 * R_BR;
constexpr int W3_OFF = W5_OFF + 3456;
constexpr int W9_OFF = W3_OFF + 3456;
constexpr int W7_OFF = W9_OFF + 2304;
constexpr int Y0_OFF = W7_OFF + 2304;
constexpr int Y2_OFF = Y0_OFF + 8192, Y3_OFF = Y2_OFF + 6144;
constexpr int CH_BYTES = Y0_OFF + 18432 + 16;
constexpr int SCR_BYTES = 4608;
constexpr int SMEM_BYTES = CH_OFF + 4 * CH_BYTES;
static_assert(CH_BYTES % 128 == 16, "bank staggering of the channel blocks");
static_assert(SMEM_BYTES <= 232448, "smem");
constexpr int B_RAW = BAR_OFF, B_X = BAR_OFF + 8, B_U = BAR_OFF + 40, B_W = BAR_OFF + 48;
constexpr int TAG_OFF = BAR_OFF + 56;
constexpr int K1024_OFF = BAR_OFF + 64;
constexpr int DSK_OFF = BAR_OFF + 160;
constexpr int B_ST = BAR_OFF + 96;

__device__ unsigned int g_gate[L];
__device__ unsigned int g_epoch;
__device__ unsigned int g_ticket;

#define STAMP(k)
#define GT(k)

struct Params {
  const __nv_bfloat16* t[14];
  const __nv_bfloat16 *u, *gw, *A_D, *B_D;
};

template <int N, int TB> __device__ __forceinline__ void wgmma_rs(float* d, uint32_t a0, uint32_t a1, uint32_t a2, uint32_t a3, uint64_t desc, int sc);
template <> __device__ __forceinline__ void wgmma_rs<64, 0>(float* d, uint32_t a0, uint32_t a1, uint32_t a2, uint32_t a3, uint64_t desc, int sc) {
  asm volatile("{\n.reg .pred p;\nsetp.ne.b32 p, %37, 0;\n"
    "wgmma.mma_async.sync.aligned.m64n64k16.f32.bf16.bf16 {%0,%1,%2,%3,%4,%5,%6,%7,%8,%9,%10,%11,%12,%13,%14,%15,%16,%17,%18,%19,%20,%21,%22,%23,%24,%25,%26,%27,%28,%29,%30,%31}, {%32,%33,%34,%35}, %36, p, 1, 1, 0;\n}"
    : "+f"(d[0]), "+f"(d[1]), "+f"(d[2]), "+f"(d[3]), "+f"(d[4]), "+f"(d[5]), "+f"(d[6]), "+f"(d[7]), "+f"(d[8]), "+f"(d[9]), "+f"(d[10]), "+f"(d[11]), "+f"(d[12]), "+f"(d[13]), "+f"(d[14]), "+f"(d[15]), "+f"(d[16]), "+f"(d[17]), "+f"(d[18]), "+f"(d[19]), "+f"(d[20]), "+f"(d[21]), "+f"(d[22]), "+f"(d[23]), "+f"(d[24]), "+f"(d[25]), "+f"(d[26]), "+f"(d[27]), "+f"(d[28]), "+f"(d[29]), "+f"(d[30]), "+f"(d[31]) : "r"(a0), "r"(a1), "r"(a2), "r"(a3), "l"(desc), "r"(sc));
}
template <> __device__ __forceinline__ void wgmma_rs<56, 0>(float* d, uint32_t a0, uint32_t a1, uint32_t a2, uint32_t a3, uint64_t desc, int sc) {
  asm volatile("{\n.reg .pred p;\nsetp.ne.b32 p, %33, 0;\n"
    "wgmma.mma_async.sync.aligned.m64n56k16.f32.bf16.bf16 {%0,%1,%2,%3,%4,%5,%6,%7,%8,%9,%10,%11,%12,%13,%14,%15,%16,%17,%18,%19,%20,%21,%22,%23,%24,%25,%26,%27}, {%28,%29,%30,%31}, %32, p, 1, 1, 0;\n}"
    : "+f"(d[0]), "+f"(d[1]), "+f"(d[2]), "+f"(d[3]), "+f"(d[4]), "+f"(d[5]), "+f"(d[6]), "+f"(d[7]), "+f"(d[8]), "+f"(d[9]), "+f"(d[10]), "+f"(d[11]), "+f"(d[12]), "+f"(d[13]), "+f"(d[14]), "+f"(d[15]), "+f"(d[16]), "+f"(d[17]), "+f"(d[18]), "+f"(d[19]), "+f"(d[20]), "+f"(d[21]), "+f"(d[22]), "+f"(d[23]), "+f"(d[24]), "+f"(d[25]), "+f"(d[26]), "+f"(d[27]) : "r"(a0), "r"(a1), "r"(a2), "r"(a3), "l"(desc), "r"(sc));
}
template <> __device__ __forceinline__ void wgmma_rs<48, 0>(float* d, uint32_t a0, uint32_t a1, uint32_t a2, uint32_t a3, uint64_t desc, int sc) {
  asm volatile("{\n.reg .pred p;\nsetp.ne.b32 p, %29, 0;\n"
    "wgmma.mma_async.sync.aligned.m64n48k16.f32.bf16.bf16 {%0,%1,%2,%3,%4,%5,%6,%7,%8,%9,%10,%11,%12,%13,%14,%15,%16,%17,%18,%19,%20,%21,%22,%23}, {%24,%25,%26,%27}, %28, p, 1, 1, 0;\n}"
    : "+f"(d[0]), "+f"(d[1]), "+f"(d[2]), "+f"(d[3]), "+f"(d[4]), "+f"(d[5]), "+f"(d[6]), "+f"(d[7]), "+f"(d[8]), "+f"(d[9]), "+f"(d[10]), "+f"(d[11]), "+f"(d[12]), "+f"(d[13]), "+f"(d[14]), "+f"(d[15]), "+f"(d[16]), "+f"(d[17]), "+f"(d[18]), "+f"(d[19]), "+f"(d[20]), "+f"(d[21]), "+f"(d[22]), "+f"(d[23]) : "r"(a0), "r"(a1), "r"(a2), "r"(a3), "l"(desc), "r"(sc));
}
template <> __device__ __forceinline__ void wgmma_rs<32, 0>(float* d, uint32_t a0, uint32_t a1, uint32_t a2, uint32_t a3, uint64_t desc, int sc) {
  asm volatile("{\n.reg .pred p;\nsetp.ne.b32 p, %21, 0;\n"
    "wgmma.mma_async.sync.aligned.m64n32k16.f32.bf16.bf16 {%0,%1,%2,%3,%4,%5,%6,%7,%8,%9,%10,%11,%12,%13,%14,%15}, {%16,%17,%18,%19}, %20, p, 1, 1, 0;\n}"
    : "+f"(d[0]), "+f"(d[1]), "+f"(d[2]), "+f"(d[3]), "+f"(d[4]), "+f"(d[5]), "+f"(d[6]), "+f"(d[7]), "+f"(d[8]), "+f"(d[9]), "+f"(d[10]), "+f"(d[11]), "+f"(d[12]), "+f"(d[13]), "+f"(d[14]), "+f"(d[15]) : "r"(a0), "r"(a1), "r"(a2), "r"(a3), "l"(desc), "r"(sc));
}
template <> __device__ __forceinline__ void wgmma_rs<48, 1>(float* d, uint32_t a0, uint32_t a1, uint32_t a2, uint32_t a3, uint64_t desc, int sc) {
  asm volatile("{\n.reg .pred p;\nsetp.ne.b32 p, %29, 0;\n"
    "wgmma.mma_async.sync.aligned.m64n48k16.f32.bf16.bf16 {%0,%1,%2,%3,%4,%5,%6,%7,%8,%9,%10,%11,%12,%13,%14,%15,%16,%17,%18,%19,%20,%21,%22,%23}, {%24,%25,%26,%27}, %28, p, 1, 1, 1;\n}"
    : "+f"(d[0]), "+f"(d[1]), "+f"(d[2]), "+f"(d[3]), "+f"(d[4]), "+f"(d[5]), "+f"(d[6]), "+f"(d[7]), "+f"(d[8]), "+f"(d[9]), "+f"(d[10]), "+f"(d[11]), "+f"(d[12]), "+f"(d[13]), "+f"(d[14]), "+f"(d[15]), "+f"(d[16]), "+f"(d[17]), "+f"(d[18]), "+f"(d[19]), "+f"(d[20]), "+f"(d[21]), "+f"(d[22]), "+f"(d[23]) : "r"(a0), "r"(a1), "r"(a2), "r"(a3), "l"(desc), "r"(sc));
}
template <> __device__ __forceinline__ void wgmma_rs<40, 1>(float* d, uint32_t a0, uint32_t a1, uint32_t a2, uint32_t a3, uint64_t desc, int sc) {
  asm volatile("{\n.reg .pred p;\nsetp.ne.b32 p, %25, 0;\n"
    "wgmma.mma_async.sync.aligned.m64n40k16.f32.bf16.bf16 {%0,%1,%2,%3,%4,%5,%6,%7,%8,%9,%10,%11,%12,%13,%14,%15,%16,%17,%18,%19}, {%20,%21,%22,%23}, %24, p, 1, 1, 1;\n}"
    : "+f"(d[0]), "+f"(d[1]), "+f"(d[2]), "+f"(d[3]), "+f"(d[4]), "+f"(d[5]), "+f"(d[6]), "+f"(d[7]), "+f"(d[8]), "+f"(d[9]), "+f"(d[10]), "+f"(d[11]), "+f"(d[12]), "+f"(d[13]), "+f"(d[14]), "+f"(d[15]), "+f"(d[16]), "+f"(d[17]), "+f"(d[18]), "+f"(d[19]) : "r"(a0), "r"(a1), "r"(a2), "r"(a3), "l"(desc), "r"(sc));
}
template <> __device__ __forceinline__ void wgmma_rs<32, 1>(float* d, uint32_t a0, uint32_t a1, uint32_t a2, uint32_t a3, uint64_t desc, int sc) {
  asm volatile("{\n.reg .pred p;\nsetp.ne.b32 p, %21, 0;\n"
    "wgmma.mma_async.sync.aligned.m64n32k16.f32.bf16.bf16 {%0,%1,%2,%3,%4,%5,%6,%7,%8,%9,%10,%11,%12,%13,%14,%15}, {%16,%17,%18,%19}, %20, p, 1, 1, 1;\n}"
    : "+f"(d[0]), "+f"(d[1]), "+f"(d[2]), "+f"(d[3]), "+f"(d[4]), "+f"(d[5]), "+f"(d[6]), "+f"(d[7]), "+f"(d[8]), "+f"(d[9]), "+f"(d[10]), "+f"(d[11]), "+f"(d[12]), "+f"(d[13]), "+f"(d[14]), "+f"(d[15]) : "r"(a0), "r"(a1), "r"(a2), "r"(a3), "l"(desc), "r"(sc));
}
template <> __device__ __forceinline__ void wgmma_rs<16, 1>(float* d, uint32_t a0, uint32_t a1, uint32_t a2, uint32_t a3, uint64_t desc, int sc) {
  asm volatile("{\n.reg .pred p;\nsetp.ne.b32 p, %13, 0;\n"
    "wgmma.mma_async.sync.aligned.m64n16k16.f32.bf16.bf16 {%0,%1,%2,%3,%4,%5,%6,%7}, {%8,%9,%10,%11}, %12, p, 1, 1, 1;\n}"
    : "+f"(d[0]), "+f"(d[1]), "+f"(d[2]), "+f"(d[3]), "+f"(d[4]), "+f"(d[5]), "+f"(d[6]), "+f"(d[7]) : "r"(a0), "r"(a1), "r"(a2), "r"(a3), "l"(desc), "r"(sc));
}

__device__ __forceinline__ uint32_t pack_bf16(float lo, float hi) {
  uint32_t r; asm("cvt.rn.bf16x2.f32 %0, %1, %2;" : "=r"(r) : "f"(hi), "f"(lo)); return r;
}
__device__ __forceinline__ float bf_lo(uint32_t v) { return __uint_as_float(v << 16); }
__device__ __forceinline__ float bf_hi(uint32_t v) { return __uint_as_float(v & 0xffff0000u); }
__device__ __forceinline__ float bf_round(float x) { return bf_lo(pack_bf16(x, 0.f)); }
__device__ __forceinline__ uint32_t hmul2(uint32_t a, uint32_t b) { uint32_t r; asm("mul.rn.bf16x2 %0, %1, %2;" : "=r"(r) : "r"(a), "r"(b)); return r; }
__device__ __forceinline__ uint32_t hadd2(uint32_t a, uint32_t b) { uint32_t r; asm("add.rn.bf16x2 %0, %1, %2;" : "=r"(r) : "r"(a), "r"(b)); return r; }
__device__ __forceinline__ uint32_t hsub2(uint32_t a, uint32_t b) { uint32_t r; asm("sub.rn.bf16x2 %0, %1, %2;" : "=r"(r) : "r"(a), "r"(b)); return r; }
__device__ __forceinline__ uint32_t hfma2(uint32_t a, uint32_t b, uint32_t c) { uint32_t r; asm("fma.rn.bf16x2 %0, %1, %2, %3;" : "=r"(r) : "r"(a), "r"(b), "r"(c)); return r; }

__device__ __forceinline__ void sts16(uint32_t a, uint32_t v) { asm volatile("st.shared.b16 [%0], %1;" ::"r"(a), "h"((unsigned short)v) : "memory"); }
__device__ __forceinline__ void sts32(uint32_t a, uint32_t v) { asm volatile("st.shared.b32 [%0], %1;" ::"r"(a), "r"(v) : "memory"); }
__device__ __forceinline__ void sts64(uint32_t a, uint32_t x, uint32_t y) { asm volatile("st.shared.v2.b32 [%0], {%1,%2};" ::"r"(a), "r"(x), "r"(y) : "memory"); }
__device__ __forceinline__ void sts128(uint32_t a, uint32_t x, uint32_t y, uint32_t z, uint32_t w) {
  asm volatile("st.shared.v4.b32 [%0], {%1,%2,%3,%4};" ::"r"(a), "r"(x), "r"(y), "r"(z), "r"(w) : "memory");
}
__device__ __forceinline__ uint32_t lds32(uint32_t a) { uint32_t v; asm volatile("ld.shared.b32 %0, [%1];" : "=r"(v) : "r"(a) : "memory"); return v; }
__device__ __forceinline__ uint32_t ldf(uint32_t base, int i, int lo0, int hi0, int hf) {
  if (i < lo0 || i > hi0 + 2) return 0u;
  if (i < lo0 + 2 || i > hi0) {
    uint32_t v;
    asm volatile("{\n.reg .pred p;\nsetp.eq.b32 p, %2, %3;\nmov.b32 %0, 0;\n@p ld.shared.b32 %0, [%1];\n}" : "=r"(v) : "r"(base + i * 16), "r"(hf), "r"(i > hi0 ? 1 : 0) : "memory");
    return v;
  }
  return lds32(base + i * 16);
}
__device__ __forceinline__ uint2 lds64(uint32_t a) { uint2 v; asm volatile("ld.shared.v2.b32 {%0,%1}, [%2];" : "=r"(v.x), "=r"(v.y) : "r"(a) : "memory"); return v; }
__device__ __forceinline__ uint4 lds128(uint32_t a) {
  uint4 v; asm volatile("ld.shared.v4.b32 {%0,%1,%2,%3}, [%4];" : "=r"(v.x), "=r"(v.y), "=r"(v.z), "=r"(v.w) : "r"(a) : "memory"); return v;
}
__device__ __forceinline__ uint4 ldg128(const void* a) {
  uint4 v; asm volatile("ld.global.nc.v4.b32 {%0,%1,%2,%3}, [%4];" : "=r"(v.x), "=r"(v.y), "=r"(v.z), "=r"(v.w) : "l"(a) : "memory"); return v;
}
__device__ __forceinline__ uint2 ldg64(const void* a) {
  uint2 v; asm volatile("ld.global.nc.v2.b32 {%0,%1}, [%2];" : "=r"(v.x), "=r"(v.y) : "l"(a) : "memory"); return v;
}
__device__ __forceinline__ void ldsm4(uint32_t a, uint32_t& r0, uint32_t& r1, uint32_t& r2, uint32_t& r3) {
  asm volatile("ldmatrix.sync.aligned.m8n8.x4.shared.b16 {%0,%1,%2,%3}, [%4];" : "=r"(r0), "=r"(r1), "=r"(r2), "=r"(r3) : "r"(a) : "memory");
}
__device__ __forceinline__ void ldsm4t(uint32_t a, uint32_t& r0, uint32_t& r1, uint32_t& r2, uint32_t& r3) {
  asm volatile("ldmatrix.sync.aligned.m8n8.x4.trans.shared.b16 {%0,%1,%2,%3}, [%4];" : "=r"(r0), "=r"(r1), "=r"(r2), "=r"(r3) : "r"(a) : "memory");
}
__device__ __forceinline__ void stsm4(uint32_t a, uint32_t r0, uint32_t r1, uint32_t r2, uint32_t r3) {
  asm volatile("stmatrix.sync.aligned.m8n8.x4.shared.b16 [%0], {%1,%2,%3,%4};" ::"r"(a), "r"(r0), "r"(r1), "r"(r2), "r"(r3) : "memory");
}
__device__ __forceinline__ void stsm4t(uint32_t a, uint32_t r0, uint32_t r1, uint32_t r2, uint32_t r3) {
  asm volatile("stmatrix.sync.aligned.m8n8.x4.trans.shared.b16 [%0], {%1,%2,%3,%4};" ::"r"(a), "r"(r0), "r"(r1), "r"(r2), "r"(r3) : "memory");
}
__device__ __forceinline__ void stsm2(uint32_t a, uint32_t r0, uint32_t r1) {
  asm volatile("stmatrix.sync.aligned.m8n8.x2.shared.b16 [%0], {%1,%2};" ::"r"(a), "r"(r0), "r"(r1) : "memory");
}
__device__ __forceinline__ void stsm2t(uint32_t a, uint32_t r0, uint32_t r1) {
  asm volatile("stmatrix.sync.aligned.m8n8.x2.trans.shared.b16 [%0], {%1,%2};" ::"r"(a), "r"(r0), "r"(r1) : "memory");
}
__device__ __forceinline__ void mma16816(float* c, uint32_t a0, uint32_t a1, uint32_t a2, uint32_t a3, uint32_t b0, uint32_t b1) {
  asm("mma.sync.aligned.m16n8k16.row.col.f32.bf16.bf16.f32 {%0,%1,%2,%3}, {%4,%5,%6,%7}, {%8,%9}, {%0,%1,%2,%3};"
      : "+f"(c[0]), "+f"(c[1]), "+f"(c[2]), "+f"(c[3]) : "r"(a0), "r"(a1), "r"(a2), "r"(a3), "r"(b0), "r"(b1));
}
__device__ __forceinline__ void bar_sync(int id, int n) { asm volatile("bar.sync %0, %1;" ::"r"(id), "r"(n) : "memory"); }
__device__ __forceinline__ void wg_fence() { asm volatile("wgmma.fence.sync.aligned;" ::: "memory"); }
__device__ __forceinline__ void wg_commit() { asm volatile("wgmma.commit_group.sync.aligned;" ::: "memory"); }
__device__ __forceinline__ void wg_wait0() { asm volatile("wgmma.wait_group.sync.aligned 0;" ::: "memory"); }
__device__ __forceinline__ void wg_wait1() { asm volatile("wgmma.wait_group.sync.aligned 1;" ::: "memory"); }
__device__ __forceinline__ void fence_async() { asm volatile("fence.proxy.async.shared::cta;" ::: "memory"); }
__device__ __forceinline__ uint32_t opq(uint32_t x, uint32_t z) { uint32_t r; asm volatile("xor.b32 %0, %1, %2;" : "=r"(r) : "r"(x), "r"(z)); return r; }
__device__ __forceinline__ float opqf(float x, uint32_t z) { float r; asm volatile("add.rn.f32 %0, %1, %2;" : "=f"(r) : "f"(x), "f"(__uint_as_float(z))); return r; }
__device__ __forceinline__ uint64_t mkdesc(uint32_t addr, uint32_t lbo, uint32_t sbo) {
  return (uint64_t)((addr & 0x3FFFF) >> 4) | ((uint64_t)(lbo >> 4) << 16) | ((uint64_t)(sbo >> 4) << 32);
}
__device__ __forceinline__ uint32_t mapa(uint32_t a, uint32_t rank) {
  uint32_t r; asm("mapa.shared::cluster.u32 %0, %1, %2;" : "=r"(r) : "r"(a), "r"(rank)); return r;
}
__device__ __forceinline__ void mbar_init_expect(uint32_t bar, uint32_t bytes) {
  asm volatile("mbarrier.init.shared::cta.b64 [%0], 1;" ::"r"(bar) : "memory");
  asm volatile("mbarrier.arrive.expect_tx.shared::cta.b64 _, [%0], %1;" ::"r"(bar), "r"(bytes) : "memory");
}
__device__ __forceinline__ void mbar_wait(uint32_t bar) {
#pragma unroll 1
  for (int it = 0; it < (1 << 22); it++) {
    uint32_t ok;
    asm volatile("{\n.reg .pred p;\nmbarrier.try_wait.parity.acquire.cluster.shared::cta.b64 p, [%1], 0;\nselp.u32 %0, 1, 0, p;\n}"
                 : "=r"(ok) : "r"(bar) : "memory");
    if (ok) return;
  }
  __trap();
}
__device__ __forceinline__ void st_async4(uint32_t a, uint32_t bar, uint32_t x, uint32_t y, uint32_t z, uint32_t w) {
  asm volatile("st.async.weak.shared::cluster.mbarrier::complete_tx::bytes.v4.b32 [%0], {%2,%3,%4,%5}, [%1];"
               ::"r"(a), "r"(bar), "r"(x), "r"(y), "r"(z), "r"(w) : "memory");
}

struct cf { float re, im; };
__device__ __forceinline__ cf cmul(cf a, cf b) { return {fmaf(a.re, b.re, -a.im * b.im), fmaf(a.re, b.im, a.im * b.re)}; }
__device__ __forceinline__ cf csq(cf a) { return {fmaf(a.re, a.re, -a.im * a.im), (a.re + a.re) * a.im}; }
__device__ __forceinline__ cf cexp_p(float xl, float y, float p) {
  float mag; asm("ex2.approx.ftz.f32 %0, %1;" : "=f"(mag) : "f"(xl * p));
  const float th = y * p;
  const float k = __fadd_rn(fmaf(th, 0.15915494309189535f, 12582912.f), -12582912.f);
  float r = fmaf(k, -6.2831854820251465f, th);
  r = fmaf(k, 1.7484555314695172e-07f, r);
  return {mag * __cosf(r), mag * __sinf(r)};
}
__device__ __forceinline__ uint32_t ysw(int c) { return (uint32_t)(c ^ ((c >> 3) & 3)) * 16u; }

#define CMUL2(OR, OI, xr, xi, yr, yi, nyi) do { OR = hfma2(xr, yr, hmul2(xi, nyi)); OI = hfma2(xr, yi, hmul2(xi, yr)); } while (0)

__device__ __forceinline__ uint32_t gate_slow(const __nv_bfloat16* u, const __nv_bfloat16* gw, int row) {
  float s = 0.f;
  const uint32_t* xr = (const uint32_t*)(u + (size_t)row * D);
  const uint32_t* wr = (const uint32_t*)gw;
#pragma unroll 1
  for (int j = 0; j < D / 2; j++) { const uint32_t pr = hmul2(xr[j], wr[j]); s += bf_lo(pr); s += bf_hi(pr); }
  s = bf_round(s);
  return pack_bf16(1.f / (1.f + expf(-s)), 0.f);
}

__device__ __forceinline__ uint2 gate_ld(int x) {
  uint2 gv;
  asm volatile("ld.relaxed.gpu.global.v2.u32 {%0,%1}, [%2];" : "=r"(gv.x), "=r"(gv.y) : "l"(g_gate + x * 2) : "memory");
  return gv;
}
__device__ __noinline__ uint32_t gate_poll(const Params* pp, int x, uint32_t tag) {
  uint2 gv;
#pragma unroll 1
  for (int spins = 0; spins < (1 << 16); spins++) {
    gv = gate_ld(x);
    if ((gv.x >> 16) == tag && (gv.y >> 16) == tag) return __byte_perm(gv.x, gv.y, 0x5410);
  }
  return __byte_perm(gate_slow(pp->u, pp->gw, x * 2), gate_slow(pp->u, pp->gw, x * 2 + 1), 0x5410);
}
__device__ __forceinline__ uint32_t gate_fin(const Params& p, uint2 gv, int x, uint32_t tag) {
  if ((gv.x >> 16) == tag && (gv.y >> 16) == tag) return __byte_perm(gv.x, gv.y, 0x5410);
  return gate_poll(&p, x, tag);
}

__device__ __forceinline__ void ld4ch(uint32_t* v, uint32_t addr) {
#pragma unroll
  for (int k = 0; k < 4; k++) v[k] = lds32(addr + k * CH_BYTES);
}
__device__ __forceinline__ void skip_terms(uint32_t* ua, uint32_t* ub, uint32_t sb, int x, uint2 dA, uint2 dB) {
  const int c = x >> 2;
  uint32_t uu[4];
  ld4ch(uu, sb + CH_OFF + (x & 3) * 4 + U_OFF + (c & 3) * U_CS + (63 - (c >> 2)) * 16);
#pragma unroll
  for (int k = 0; k < 4; k++) {
    ua[k] = hmul2(uu[k], __byte_perm((k & 2) ? dA.y : dA.x, 0, (k & 1) ? 0x3232 : 0x1010));
    ub[k] = hmul2(uu[k], __byte_perm((k & 2) ? dB.y : dB.x, 0, (k & 1) ? 0x3232 : 0x1010));
  }
}
__device__ __forceinline__ uint4 mix(const uint32_t* a, const uint32_t* b, const uint32_t* ua, const uint32_t* ub, uint32_t g2) {
  const uint32_t h2 = hsub2(0x3f803f80u, g2);
  uint32_t o[4];
#pragma unroll
  for (int k = 0; k < 4; k++) o[k] = hadd2(hmul2(g2, hadd2(a[k], ua[k])), hmul2(h2, hadd2(b[k], ub[k])));
  return make_uint4(__byte_perm(o[0], o[1], 0x5410), __byte_perm(o[2], o[3], 0x5410), __byte_perm(o[0], o[1], 0x7632), __byte_perm(o[2], o[3], 0x7632));
}
__device__ __forceinline__ void send_box(uint32_t sb, int slot, int wtid, uint32_t rank, uint4 r) {
  st_async4(mapa(sb + XIN_OFF + slot * 2048 + wtid * 16, rank ^ 1), mapa(sb + B_X + slot * 8, rank ^ 1), r.x, r.y, r.z, r.w);
}
__device__ __forceinline__ void merge_rows(uint32_t st, uint32_t rank, uint4 r, uint4 q) {
  const uint4 lo = rank ? q : r, hi = rank ? r : q;
  sts128(st, lo.x, lo.y, hi.x, hi.y); sts128(st + 2048, lo.z, lo.w, hi.z, hi.w);
}
__device__ __forceinline__ void merge_box(uint32_t sb, const CUtensorMap* tm_out, int slot, int wtid, uint32_t rank, int oc0, uint4 r, int barid) {
  const uint32_t st = sb + RAW_OFF + slot * 4096 + wtid * 16;
  mbar_wait(sb + B_X + slot * 8);
  merge_rows(st, rank, r, lds128(sb + XIN_OFF + slot * 2048 + wtid * 16));
  fence_async();
  bar_sync(barid, 128);
  if (wtid == 0) {
    asm volatile("cp.async.bulk.tensor.3d.global.shared::cta.bulk_group [%0, {%2, %3, %4}], [%1];"
                 ::"l"(tm_out), "r"(sb + RAW_OFF + slot * 4096), "r"(oc0), "r"((2 * slot + (int)rank) * 128), "r"(0) : "memory");
    asm volatile("cp.async.bulk.commit_group;" ::: "memory");
  }
}

__device__ __forceinline__ uint32_t band2(int e, int lo, int hi) {
  uint32_t r = ((uint32_t)(e - lo) <= (uint32_t)(hi - lo) ? 0x3f80u : 0u) | ((uint32_t)(e - 1 - lo) <= (uint32_t)(hi - lo) ? 0x3f800000u : 0u);
  asm volatile("" : "+r"(r));
  return r;
}

__device__ __forceinline__ void stage_done(uint32_t sb, int stage, int lane) {
  __syncwarp();
  if (lane == 0) asm volatile("mbarrier.arrive.shared::cta.b64 _, [%0];" ::"r"(sb + B_ST + 8 * stage) : "memory");
}
#define PK2(v, i) pack_bf16(v[i], v[(i) + 1])

__device__ __forceinline__ void conv_dense(uint32_t sb, uint32_t cb, uint32_t zz) {
  const int lane = threadIdx.x & 31, wq = (threadIdx.x >> 5) & 3, br = wq >> 1, hf = wq & 1, g = lane >> 2, t = lane & 3;
  const uint32_t rb = cb + R_OFF + br * R_BR;
  const int eo = 16 * hf + g - 2 * t;
  const int x0 = RD_X0 - (eo + 536);
  const uint32_t fa = rb + ((g & 1) ? 2 * x0 : RD_CS + 2 * x0 + 2);
  const uint64_t ub = mkdesc(cb + U_OFF, U_CS, 128);
  const uint32_t yd = cb + Y0_OFF + br * 4096 + ysw(4 * (63 - 8 * (lane >> 4) - (lane & 7)) + 2 * hf + ((lane >> 3) & 1));
  uint32_t A[2][4][4];
  float e64[32], e56[28], e48[24];
  auto loadA = [&](int j) {
#pragma unroll
    for (int k = 0; k < 4; k++) {
      const int s = 34 - 4 * j - k;
      if (s >= 0) {
        if (k == 0 && j == 0) A[0][0][2] = ldf(fa, 2 * s + 2, 2, 67, hf);
        A[j & 1][k][0] = ldf(fa, 2 * s + 1, 2, 67, hf);
        A[j & 1][k][1] = ldf(fa, 2 * s, 2, 67, hf);
      }
    }
#pragma unroll
    for (int k = 0; k < 4; k++) {
      if (34 - 4 * j - k >= 0) {
        A[j & 1][k][3] = A[j & 1][k][0];
        if (k) A[j & 1][k][2] = A[j & 1][k - 1][1];
        else if (j) A[j & 1][0][2] = A[(j - 1) & 1][3][1];
      }
    }
  };
  loadA(0); loadA(1);
#pragma unroll
  for (int j = 0; j < 9; j++) {
    if (j == 4) {
      wg_wait0();
      stsm2t(yd - 7 * 512, PK2(e64, 28), PK2(e64, 30));
#pragma unroll
      for (int i = 0; i < 28; i++) e56[i] = FCPY(e64, i);
      stage_done(sb, 0, lane);
    }
    if (j == 8) {
      wg_wait0();
      stsm2t(yd - 6 * 512, PK2(e56, 24), PK2(e56, 26));
#pragma unroll
      for (int i = 0; i < 24; i++) e48[i] = FCPY(e56, i);
      stage_done(sb, 1, lane);
    }
    wg_fence();
#pragma unroll
    for (int k = 0; k < 4; k++) {
      const int s = 34 - 4 * j - k;
      if (s >= 0) {
        const int o = 2 * s - 66 + 128;
        const int cc = o & 3, rs = (o >> 2) - 32;
        const uint64_t desc = ub + (uint64_t)((cc * U_CS - rs * 16) >> 4);
        const uint32_t* a = A[j & 1][k];
        if (j < 4) wgmma_rs<64, 0>(e64, a[0], a[1], a[2], a[3], desc, s != 34);
        else if (j < 8) wgmma_rs<56, 0>(e56, a[0], a[1], a[2], a[3], desc, 1);
        else wgmma_rs<48, 0>(e48, a[0], a[1], a[2], a[3], desc, 1);
      }
    }
    wg_commit();
    if (j >= 1 && j < 8) { wg_wait1(); loadA(j + 1); }
  }
  wg_wait0();
#pragma unroll
  for (int i = 0; i < 6; i += 2) stsm4t(yd - i * 512, PK2(e48, 4 * i), PK2(e48, 4 * i + 2), PK2(e48, 4 * i + 4), PK2(e48, 4 * i + 6));
}

__device__ __noinline__ unsigned int gate_rows(const Params* pp, int grow, int step, int rend) {
  const __nv_bfloat16 *u = pp->u, *gw = pp->gw;
  const int lane = threadIdx.x & 31;
  uint4 gx[4][2], nx[4][2];
#pragma unroll
  for (int i = 0; i < 4; i++) {
    nx[i][0] = ldg128(u + (size_t)(grow + i) * D + lane * 8);
    nx[i][1] = ldg128(u + (size_t)(grow + i) * D + 256 + lane * 8);
  }
  const uint4 gw0 = ldg128(gw + lane * 8), gw1 = ldg128(gw + 256 + lane * 8);
  const uint32_t ws[8] = {gw0.x, gw0.y, gw0.z, gw0.w, gw1.x, gw1.y, gw1.z, gw1.w};
  unsigned int epoch;
  asm volatile("ld.relaxed.gpu.global.u32 %0, [%1];" : "=r"(epoch) : "l"(&g_epoch) : "memory");
#pragma unroll 1
  for (; grow < rend; grow += step) {
#pragma unroll
    for (int i = 0; i < 4; i++) { gx[i][0] = nx[i][0]; gx[i][1] = nx[i][1]; }
    if (grow + step < rend) {
#pragma unroll
      for (int i = 0; i < 4; i++) {
        nx[i][0] = ldg128(u + (size_t)(grow + step + i) * D + lane * 8);
        nx[i][1] = ldg128(u + (size_t)(grow + step + i) * D + 256 + lane * 8);
      }
    }
    float c[2][4];
#pragma unroll
    for (int i = 0; i < 2; i++) {
      const uint4 *x = gx[2 * i], *y = gx[2 * i + 1];
      const uint32_t xs[8] = {x[0].x, x[0].y, x[0].z, x[0].w, x[1].x, x[1].y, x[1].z, x[1].w};
      const uint32_t ys[8] = {y[0].x, y[0].y, y[0].z, y[0].w, y[1].x, y[1].y, y[1].z, y[1].w};
      c[i][0] = c[i][1] = c[i][2] = c[i][3] = 0.f;
#pragma unroll
      for (int j = 0; j < 8; j += 2)
        mma16816(c[i], hmul2(xs[j], ws[j]), hmul2(ys[j], ws[j]), hmul2(xs[j + 1], ws[j + 1]), hmul2(ys[j + 1], ws[j + 1]), 0x3f803f80u, 0x3f803f80u);
    }
    float s = (lane & 2) ? ((lane & 1) ? c[1][2] : c[1][0]) : ((lane & 1) ? c[0][2] : c[0][0]);
#pragma unroll
    for (int o = 4; o < 32; o <<= 1) s += __shfl_xor_sync(0xffffffffu, s, o);
    s = bf_round(s);
    const float gv = 1.f / (1.f + expf(-s));
    const uint32_t w = ((epoch + 1) << 16) | (pack_bf16(gv, 0.f) & 0xffffu);
    if (lane < 4) asm volatile("st.relaxed.gpu.global.u32 [%0], %1;" ::"l"(&g_gate[grow + lane]), "r"(w) : "memory");
  }
  return epoch;
}
#define GW 1
constexpr int GSPLIT = L - 4 * GW * NCTA;
__device__ __noinline__ void gate_cta(const Params* pp) {
  const unsigned int epoch = gate_rows(pp, (blockIdx.x * 20 + (threadIdx.x >> 5)) * 4, 80 * NGATE, GSPLIT);
  __syncthreads();
  if (threadIdx.x == 0 && atomicAdd(&g_ticket, 1u) == NCTA + NGATE - 1) { g_ticket = 0; g_epoch = epoch + 1; }
}

__global__ void __cluster_dims__(2, 1, 1) __launch_bounds__(640, 1)
ssm_kernel(const __grid_constant__ Params p, const __grid_constant__ CUtensorMap tm_in, const __grid_constant__ CUtensorMap tm_out) {
  extern __shared__ __align__(1024) unsigned char smem_raw[];
  const uint32_t sb = (uint32_t)__cvta_generic_to_shared(smem_raw);
  const int tid = threadIdx.x, lane = tid & 31;
  const int warp = __shfl_sync(0xffffffffu, tid >> 5, 0);
  const int ch = warp >> 2, wq = warp & 3, br = wq >> 1, hf = wq & 1;
  const int g = lane >> 2, t = lane & 3;
  if (__builtin_expect(blockIdx.x < NGATE, 0)) { gate_cta(&p); return; }
  const int bid = blockIdx.x - NGATE;
  const uint32_t rank = blockIdx.x & 1;
  const uint32_t cb = sb + CH_OFF + ch * CH_BYTES;
  const int wtid = tid & 127;
  const int oc0 = (bid >> 1) * 8;
  STAMP(0); GT(0);

  if (warp >= 16) {
    if (wtid == 0) {
      mbar_init_expect(sb + B_RAW, 32768);
#pragma unroll
      for (int i = 0; i < 4; i++) mbar_init_expect(sb + B_X + 8 * i, 2048);
      asm volatile("mbarrier.init.shared::cta.b64 [%0], 128;" ::"r"(sb + B_U) : "memory");
      asm volatile("mbarrier.init.shared::cta.b64 [%0], 128;" ::"r"(sb + B_W) : "memory");
#pragma unroll
      for (int i = 0; i < 7; i++) asm volatile("mbarrier.init.shared::cta.b64 [%0], 16;" ::"r"(sb + B_ST + 8 * i) : "memory");
      asm volatile("fence.mbarrier_init.release.cluster;" ::: "memory");
      asm volatile("fence.proxy.async.shared::cta;" ::: "memory");
    }
    __syncwarp();
    asm volatile("barrier.cluster.arrive.relaxed.aligned;" ::: "memory");
    if (wq >= 4 - GW) gate_rows(&p, GSPLIT + (bid * GW + 3 - wq) * 4, L, L);
    unsigned int epoch;
    asm volatile("ld.relaxed.gpu.global.u32 %0, [%1];" : "=r"(epoch) : "l"(&g_epoch) : "memory");
    asm volatile("barrier.cluster.wait.aligned;" ::: "memory");
    if (wtid == 0) {
      asm volatile("cp.async.bulk.tensor.5d.shared::cluster.global.mbarrier::complete_tx::bytes.multicast::cluster [%0], [%1, {%3, %4, %4, %4, %5}], [%2], %6;"
                   ::"r"(sb + RAW_OFF + rank * 16384), "l"(&tm_in), "r"(sb + B_RAW), "r"(oc0), "r"(0), "r"((int)rank * 32), "h"((unsigned short)3) : "memory");
    }
    sts128(sb + CH_OFF + wq * CH_BYTES + U_OFF + (lane >> 3) * U_CS + (64 + (lane & 7)) * 16, 0, 0, 0, 0);
    const uint2 dA = ldg64(p.A_D + bid * 4), dB = ldg64(p.B_D + bid * 4);
    uint32_t BA[3][4], BB[4][4];
    {
      const int l1 = br ? 3 : 6, h1 = br ? 5 : 10, l2 = br ? 5 : 12, h2 = br ? 11 : 20;
#pragma unroll
      for (int i = 0; i < 4; i++) {
        const int e = 16 * hf + g - 2 * t + 32 - 16 * i;
        BB[i][0] = band2(e, l2, h2); BB[i][1] = band2(e + 8, l2, h2); BB[i][2] = band2(e - 8, l2, h2); BB[i][3] = BB[i][0];
        if (i) { BA[i - 1][0] = band2(e, l1, h1); BA[i - 1][1] = band2(e + 8, l1, h1); BA[i - 1][2] = band2(e - 8, l1, h1); BA[i - 1][3] = BA[i - 1][0]; }
      }
    }
    const uint32_t tag = (epoch + 1) & 0xffffu;
    if (wtid == 0) { sts32(sb + TAG_OFF, tag); sts128(sb + DSK_OFF, dA.x, dA.y, dB.x, dB.y); }
    STAMP(3);
    mbar_wait(sb + B_RAW);
    STAMP(4);
    {
      const uint32_t dst = sb + CH_OFF + (g & 3) * CH_BYTES + U_OFF + t * U_CS + (63 - wq * 16) * 16;
#pragma unroll
      for (int h = 0; h < 2; h++) {
        uint32_t r[8][4];
#pragma unroll
        for (int i = 0; i < 8; i++) ldsm4t(sb + RAW_OFF + (wq * 16 + h * 8 + i) * 512 + lane * 16, r[i][0], r[i][1], r[i][2], r[i][3]);
        if ((uint32_t)(g >> 2) == rank) {
#pragma unroll
          for (int i = 0; i < 8; i++) sts128(dst - (h * 8 + i) * 16, r[i][0], r[i][1], r[i][2], r[i][3]);
        }
      }
    }
    fence_async();
    asm volatile("mbarrier.arrive.shared::cta.b64 _, [%0];" ::"r"(sb + B_U) : "memory");
    bar_sync(5, 128);
    STAMP(5);
    {
      const int mrow = lane & 7, mi = lane >> 3;
      const uint64_t ub0 = mkdesc(sb + CH_OFF + U_OFF, U_CS, 128);
      uint32_t wa, wb;
      {
        const int c = 4 * (47 - 8 * (mi >> 1) - mrow) + 2 * hf + (mi & 1);
        wa = sb + CH_OFF + (br ? W3_OFF : W5_OFF) + (5 - (c >> 5)) * 576 + ((c & 31) >> 3) * 144 + (c & 7) * 16;
        const int c2 = c - 64, pp = c2 >> 1;
        wb = sb + CH_OFF + (br ? W7_OFF : W9_OFF) + (1 - (pp >> 5)) * 1152 + (c2 & 1) * 576 + ((pp & 31) >> 3) * 144 + (pp & 7) * 16;
      }
      {
        float w1[24];
#pragma unroll
        for (int i = 0; i < 24; i++) w1[i] = 0.f;
#pragma unroll 1
        for (int k = 0; k < 4; k++) {
          wg_fence();
#pragma unroll
          for (int i = 0; i < 3; i++)
            wgmma_rs<48, 0>(w1, BA[i][0], BA[i][1], BA[i][2], BA[i][3],
                            ub0 + (uint64_t)((k * CH_BYTES + ((2 * i + 2) & 3) * U_CS + (16 + (i == 0)) * 16) >> 4), i);
          wg_commit();
          wg_wait0();
#pragma unroll
          for (int i = 0; i < 3; i++) stsm4t(wa + k * CH_BYTES + i * 1152, PK2(w1, 8 * i), PK2(w1, 8 * i + 2), PK2(w1, 8 * i + 4), PK2(w1, 8 * i + 6));
        }
      }
      {
        float w2[2][16];
#pragma unroll
        for (int i = 0; i < 16; i++) { w2[0][i] = 0.f; w2[1][i] = 0.f; }
#pragma unroll 1
        for (int kp = 0; kp < 2; kp++) {
          wg_fence();
#pragma unroll
          for (int k = 0; k < 2; k++)
#pragma unroll
            for (int i = 0; i < 4; i++)
              wgmma_rs<32, 0>(w2[k], BB[i][0], BB[i][1], BB[i][2], BB[i][3],
                              ub0 + (uint64_t)(((2 * kp + k) * CH_BYTES + ((2 * i) & 3) * U_CS + (32 + (i < 2)) * 16) >> 4), i);
          wg_commit();
          wg_wait0();
#pragma unroll
          for (int k = 0; k < 2; k++)
#pragma unroll
            for (int i = 0; i < 2; i++)
              stsm4t(wb + (2 * kp + k) * CH_BYTES + i * 1152, PK2(w2[k], 8 * i), PK2(w2[k], 8 * i + 2), PK2(w2[k], 8 * i + 4), PK2(w2[k], 8 * i + 6));
        }
      }
    }
    fence_async();
    asm volatile("mbarrier.arrive.shared::cta.b64 _, [%0];" ::"r"(sb + B_W) : "memory");
    STAMP(7);
    {
      const int bsel = (int)rank ^ br ^ 1, xl = wtid & 63;
      uint2 gl[4];
      uint32_t ua[4][4], ub[4][4];
#pragma unroll
      for (int i = 0; i < 4; i++) skip_terms(ua[i], ub[i], sb, (2 * (i >> 1) + bsel) * 128 + (i & 1) * 64 + xl, dA, dB);
      const uint32_t yo = sb + CH_OFF + (xl & 3) * 4 + ysw(xl >> 2) + bsel * 512;
#pragma unroll
      for (int i = 0; i < 2; i++) gl[i] = gate_ld(bsel * 128 + i * 64 + xl);
#pragma unroll
      for (int slot = 0; slot < 2; slot++) {
        const int box = 2 * slot + bsel;
        uint32_t g2[2], ya[2][4], yb[2][4];
#pragma unroll
        for (int h = 0; h < 2; h++) g2[h] = gate_fin(p, gl[2 * slot + h], box * 128 + h * 64 + xl, tag);
        mbar_wait(sb + B_ST + 8 * box);
        STAMP(8 + slot);
        if (slot == 0) { gl[2] = gate_ld((2 + bsel) * 128 + xl); gl[3] = gate_ld((2 + bsel) * 128 + 64 + xl); }
#pragma unroll
        for (int h = 0; h < 2; h++) {
          const uint32_t yh = (yo ^ (h * 32)) + h * 256 + slot * 1024;
          ld4ch(ya[h], yh + Y0_OFF); ld4ch(yb[h], yh + Y0_OFF + 4096);
          if (slot) {
            uint32_t a2[4], b2[4];
            ld4ch(a2, yh + Y2_OFF - 1024); ld4ch(b2, yh + Y2_OFF - 1024 + 3072);
#pragma unroll
            for (int k = 0; k < 4; k++) { ya[h][k] = hadd2(ya[h][k], a2[k]); yb[h][k] = hadd2(yb[h][k], b2[k]); }
          }
        }
        const uint4 r0 = mix(ya[0], yb[0], ua[2 * slot], ub[2 * slot], g2[0]), r1 = mix(ya[1], yb[1], ua[2 * slot + 1], ub[2 * slot + 1], g2[1]);
        if (br == 0) { send_box(sb, slot, xl, rank, r0); send_box(sb, slot, xl + 64, rank, r1); }
        else {
          const uint32_t st = sb + RAW_OFF + slot * 4096 + xl * 16, xin = sb + XIN_OFF + slot * 2048 + xl * 16;
          mbar_wait(sb + B_X + slot * 8);
          const uint4 q0 = lds128(xin), q1 = lds128(xin + 1024);
          merge_rows(st, rank, r0, q0); merge_rows(st + 1024, rank, r1, q1);
          fence_async();
          bar_sync(6, 64);
          if (xl == 0) {
            asm volatile("cp.async.bulk.tensor.3d.global.shared::cta.bulk_group [%0, {%2, %3, %4}], [%1];"
                         ::"l"(&tm_out), "r"(sb + RAW_OFF + slot * 4096), "r"(oc0), "r"(box * 128), "r"(0) : "memory");
            asm volatile("cp.async.bulk.commit_group;" ::: "memory");
          }
        }
        STAMP(10 + slot);
      }
    }
    if (wtid == 0 && atomicAdd(&g_ticket, 1u) == NCTA + NGATE - 1) { g_ticket = 0; g_epoch = epoch + 1; }
    if (wtid == 64) asm volatile("cp.async.bulk.wait_group.read 0;" ::: "memory");
    STAMP(15);
    return;
  }
  asm volatile("barrier.cluster.arrive.relaxed.aligned;" ::: "memory");

  const int moff = (bid * 4 + (tid >> 7)) * NM + (tid & 63) * 2;
  const int brt = (tid >> 6) & 1;
  const __nv_bfloat16* const* tp = p.t + (brt ? 0 : 6);
  const uint32_t q0 = *(const uint32_t*)(tp[0] + moff), q1 = *(const uint32_t*)(tp[1] + moff);
  const uint32_t q2 = *(const uint32_t*)(tp[2] + moff), q3 = *(const uint32_t*)(tp[3] + moff);
  const uint2 ldt4 = *(const uint2*)(tp[4] + bid * 4);
  const uint32_t q4 = *(const uint32_t*)(tp[brt ? 2 : 5] + moff), q5 = *(const uint32_t*)(tp[brt ? 3 : 6] + moff);

  for (int i = wtid & 63; i < R_BR / 16; i += 64) sts128(cb + R_OFF + br * R_BR + i * 16, 0, 0, 0, 0);
  STAMP(1);

  float acc[5][4];
  float k2048 = 0.f;
  const uint32_t scr = cb + Y0_OFF + wq * SCR_BYTES;
  const uint32_t scr2 = sb + SC2_OFF + warp * 640;
  {
    const uint32_t ldt2 = (ch & 2) ? ldt4.y : ldt4.x;
    const float dt = bf_round(expf((ch & 1) ? bf_hi(ldt2) : bf_lo(ldt2)));
#pragma unroll
    for (int i = 0; i < 5; i++) acc[i][0] = acc[i][1] = acc[i][2] = acc[i][3] = 0.f;
    STAMP(2);
    const uint32_t tb = scr + lane * 16;
    const uint32_t tb1 = tb + hf * 512, tb2 = tb + (hf ^ 1) * 512;
    const uint32_t ta = scr + (lane >> 3) * 512 + (lane & 7) * 16;
    const uint32_t tc = ((lane & 8) ? scr2 : scr + 4096) + (lane >> 4) * 128 + (lane & 7) * 16;
    const uint32_t tm = scr2 + 512 + ((lane >> 3) & 1) * 64 + (lane >> 4) * 16;
#pragma unroll 1
    for (int r = 0; r < 2; r++) {
      cf c, z1, z128;
      {
        const uint32_t sh = r ? 0x3244u : 0x1044u;
        float v0 = __uint_as_float(__byte_perm(q0, 0, sh));
        const float v1 = __uint_as_float(__byte_perm(q1, 0, sh)), v2 = __uint_as_float(__byte_perm(q2, 0, sh)), v3 = __uint_as_float(__byte_perm(q3, 0, sh));
        if (br == 0) { c = cmul(cf{v2, v3}, cf{dt * __uint_as_float(__byte_perm(q4, 0, sh)), dt * __uint_as_float(__byte_perm(q5, 0, sh))}); }
        else { v0 = -bf_round(expf(v0)); c = cf{2.f * dt * v2, 2.f * dt * v3}; }
        const float xl = (dt * v0) * 1.4426950408889634f, y = dt * v1;
        z1 = cexp_p(xl, y, 1.f); z128 = cexp_p(xl, y, 128.f);
      }
      const cf z2 = csq(z1), z4 = csq(z2), z8 = csq(z4);
      const cf w8 = {z8.re, -z8.im};
      const cf z16 = csq(w8), z24 = cmul(z16, w8), z32 = csq(z16), z40 = cmul(z32, w8), z48 = csq(z24), z56 = cmul(z32, z24), z64 = csq(z32);
      const cf z256 = csq(z128), z512 = csq(z256), z1024 = csq(z512), z2048 = csq(z1024);
      {
        k2048 += fmaf(c.re, z2048.re, -c.im * z2048.im);
        if (r) {
#pragma unroll
          for (int o = 16; o; o >>= 1) k2048 += __shfl_xor_sync(0xffffffffu, k2048, o);
        }
      }
      __syncwarp();
      {
        uint32_t xr[4] = {pack_bf16(1.f, z8.re), pack_bf16(z16.re, z24.re), pack_bf16(z32.re, z40.re), pack_bf16(z48.re, z56.re)};
        uint32_t xi[4] = {pack_bf16(0.f, w8.im), pack_bf16(z16.im, z24.im), pack_bf16(z32.im, z40.im), pack_bf16(z48.im, z56.im)};
        sts128(tb1, xr[0], xr[1], xr[2], xr[3]);
        sts128(tb1 + 1024, xi[0], xi[1], xi[2], xi[3]);
        const uint32_t yr = pack_bf16(z64.re, z64.re), yi = pack_bf16(z64.im, z64.im), nyi = yi ^ 0x80008000u;
        uint32_t o[4], q[4];
#pragma unroll
        for (int i = 0; i < 4; i++) CMUL2(o[i], q[i], xr[i], xi[i], yr, yi, nyi);
        sts128(tb2, o[0], o[1], o[2], o[3]);
        sts128(tb2 + 1024, q[0], q[1], q[2], q[3]);
      }
      {
        const cf h1 = cmul(c, z128), h2 = cmul(c, z256), h3 = cmul(h1, z256), h4 = cmul(c, z512), h5 = cmul(h1, z512), h6 = cmul(h2, z512), h7 = cmul(h3, z512);
        const cf e1 = cmul(c, z1), e2 = cmul(c, z2), e3 = cmul(e1, z2), e129 = cmul(h1, z1), e130 = cmul(h1, z2), e131 = cmul(e129, z2);
        const cf e258 = cmul(h2, z2), e386 = cmul(h3, z2);
        const uint32_t pr0 = pack_bf16(c.re, e1.re), pr2 = pack_bf16(h1.re, e129.re), pi0 = pack_bf16(c.im, e1.im), pi2 = pack_bf16(h1.im, e129.im);
        sts128(tb + 4 * 512, pr0, pack_bf16(e2.re, e3.re), pr2, pack_bf16(e130.re, e131.re));
        sts128(tb + 5 * 512, pi0, pack_bf16(e2.im, e3.im), pi2, pack_bf16(e130.im, e131.im));
        uint32_t xr[4] = {pack_bf16(h2.re, e258.re), pack_bf16(h3.re, e386.re), pack_bf16(h4.re, h5.re), pack_bf16(h6.re, h7.re)};
        uint32_t xi[4] = {pack_bf16(h2.im, e258.im), pack_bf16(h3.im, e386.im), pack_bf16(h4.im, h5.im), pack_bf16(h6.im, h7.im)};
        sts128(tb + 6 * 512, xr[0], xr[1], xr[2], xr[3]);
        sts128(tb + 7 * 512, xi[0], xi[1], xi[2], xi[3]);
        xr[1] = __byte_perm(xr[0], xr[1], 0x5410); xi[1] = __byte_perm(xi[0], xi[1], 0x5410);
        xr[0] = __byte_perm(pr0, pr2, 0x5410); xi[0] = __byte_perm(pi0, pi2, 0x5410);
        const uint32_t yr = pack_bf16(z1024.re, z1024.re), yi = pack_bf16(z1024.im, z1024.im), nyi = yi ^ 0x80008000u;
        uint32_t o[4], q[4];
#pragma unroll
        for (int i = 0; i < 4; i++) CMUL2(o[i], q[i], xr[i], xi[i], yr, yi, nyi);
        sts128(tb + 8 * 512, o[0], o[1], o[2], o[3]);
        sts128(scr2 + lane * 16, q[0], q[1], q[2], q[3]);
        const uint32_t m4 = pack_bf16(z4.re, z4.im);
        sts16(scr2 + 512 + lane * 2, m4); sts16(scr2 + 576 + lane * 2, m4 >> 16);
      }
      __syncwarp();
#pragma unroll
      for (int kp = 0; kp < 2; kp++) {
        uint32_t rr[2], ri[2], yr[2], yi[2];
        ldsm4t(tc + kp * 256, rr[0], ri[0], rr[1], ri[1]);
        ldsm4(tm + kp * 32, yr[0], yi[0], yr[1], yi[1]);
#pragma unroll
        for (int k2 = 0; k2 < 2; k2++) {
          const int kk = kp * 2 + k2;
          uint32_t a0, a1, a2, a3, pr, pi, qr, qi, xr, xi;
          ldsm4t(ta + kk * 128, a0, a1, a2, a3);
          ldsm4t(ta + 2048 + kk * 128, pr, pi, qr, qi);
          const uint32_t nyi = yi[k2] ^ 0x80008000u;
          mma16816(acc[0], a0, a1, a2, a3, pr, pi);
          mma16816(acc[2], a0, a1, a2, a3, qr, qi);
          mma16816(acc[4], a0, a1, a2, a3, rr[k2], ri[k2]);
          CMUL2(xr, xi, pr, pi, yr[k2], yi[k2], nyi);
          mma16816(acc[1], a0, a1, a2, a3, xr, xi);
          CMUL2(xr, xi, qr, qi, yr[k2], yi[k2], nyi);
          mma16816(acc[3], a0, a1, a2, a3, xr, xi);
        }
      }
    }
  }
  STAMP(3);
  __syncwarp();
  {
    const uint32_t xs = scr + lane * 16;
#define OTH(i, k) __float_as_uint(acc[i][2 + (k)])
    sts128(xs, OTH(0, 0), OTH(0, 1), OTH(1, 0), OTH(1, 1));
    sts128(xs + 512, OTH(2, 0), OTH(2, 1), OTH(3, 0), OTH(3, 1));
    sts64(scr + 1024 + lane * 8, OTH(4, 0), OTH(4, 1));
    if (lane == 0) sts32(scr + 1280, __float_as_uint(k2048));
#undef OTH
  }

  bar_sync(7 + (warp >> 1), 64);
  STAMP(4);
  {
    const uint32_t xo = cb + Y0_OFF + (wq ^ 1) * SCR_BYTES + lane * 16;
    const uint4 o0 = lds128(xo), o1 = lds128(xo + 512);
    const uint2 o2 = lds64(xo + 1024 - lane * 8);
    const uint32_t rb = cb + R_OFF + br * R_BR;
#define OWN(i, k) acc[i][k]
    const uint32_t vP = pack_bf16(OWN(0, 1) + __uint_as_float(o0.y), OWN(0, 0) + __uint_as_float(o0.x));
    const uint32_t vP4 = pack_bf16(OWN(1, 1) + __uint_as_float(o0.w), OWN(1, 0) + __uint_as_float(o0.z));
    const uint32_t vQ = pack_bf16(OWN(2, 1) + __uint_as_float(o1.y), OWN(2, 0) + __uint_as_float(o1.x));
    const uint32_t vQ4 = pack_bf16(OWN(3, 1) + __uint_as_float(o1.w), OWN(3, 0) + __uint_as_float(o1.z));
    const uint32_t vR = pack_bf16(OWN(4, 1) + __uint_as_float(o2.y), OWN(4, 0) + __uint_as_float(o2.x));
#undef OWN
    const int j = g + 8 * hf;
    {
      const int a = 2 * (t & 1) + 64 * (t & 2) + 8 * j;
      const uint32_t ad = rb + 2 * (RD_X0 - 1 - a);
      const uint32_t a1 = (t & 2) ? ad - 8 : ad, a2 = (t & 2) ? ad : ad - 8;
      const uint32_t w1 = (t & 2) ? vP4 : vP, w2 = (t & 2) ? vP : vP4;
      sts32(a1, w1); sts32(a2, w2);
      sts16(a1 + RD_CS + 2, w1); sts16(a1 + RD_CS + 4, w1 >> 16);
      sts16(a2 + RD_CS + 2, w2); sts16(a2 + RD_CS + 4, w2 >> 16);
    }
    if (t < 2) {
      const int b = 256 + 128 * t + 8 * j;
      const uint32_t ad = rb + 2 * (RD_X0 - 6 - b);
      const uint32_t v22 = __byte_perm(vQ4, 0, 0x3232), v00 = __byte_perm(vQ, 0, 0x3232);
      sts16(ad, vQ4);
      sts64(ad + 2, v22, __byte_perm(vQ4, vQ, 0x5432));
      sts32(ad + 10, v00);
      if (b != 256) { sts16(ad + 14, v00); sts128(ad + RD_CS + 2, vQ4, v22, vQ, v00); }
      else { sts64(ad + RD_CS + 2, vQ4, v22); sts32(ad + RD_CS + 10, vQ); sts16(ad + RD_CS + 14, v00); }
    } else {
      const uint32_t ao = rb + R_O2 + 2 * (159 - (32 * t + j)), ae = ao - (R_O2 - R_E2) + 2;
      sts16(ao, vQ4 >> 16); sts16(ao + RS_CS + 2, vQ4 >> 16); sts16(ao - 32, vQ4); sts16(ao - 32 + RS_CS + 2, vQ4);
      sts16(ae - 32, vQ); sts16(ae - 32 + RS_CS + 2, vQ);
      if (lane != 2 || hf) { sts16(ae, vQ >> 16); sts16(ae + RS_CS + 2, vQ >> 16); }
      else {
        const uint32_t vv = __byte_perm(vQ, 0, 0x3232), ad = rb + 2 * (RD_X0 - 514);
        sts16(ad, vv); sts32(ad + 2, vv); sts16(ad + 6, vv); sts64(ad + RD_CS + 2, vv, vv);
      }
    }
    {
      const uint32_t a = rb + ((g & 1) ? R_O3 : R_E3 + 2) + 2 * (159 - (64 + 16 * t + (j >> 1)));
      const bool p1024 = (lane == 0) && (hf == 0);
      const uint32_t a00 = p1024 ? rb + R_E2 + 2 * (159 - 127) : a;
      sts16(a00, vR >> 16); sts16(a00 + RS_CS + 2, vR >> 16);
      sts16(a - 16, vR); sts16(a - 16 + RS_CS + 2, vR);
      if (p1024) {
        sts32(sb + K1024_OFF + (ch * 2 + br) * 4, __byte_perm(vR, 0, 0x3232));
        const uint32_t kv = pack_bf16(k2048 + __uint_as_float(lds32(xo + 1280)), 0.f);
        sts16(rb + R_E3 + 2 * (159 - 127), kv); sts16(rb + R_E3 + 2 * (159 - 127) + RS_CS + 2, kv);
      }
    }
  }
  STAMP(5);
  asm volatile("barrier.cluster.wait.aligned;" ::: "memory");
  bar_sync(7 + (warp >> 1), 64);
  mbar_wait(sb + B_U);
  STAMP(6);

  const uint32_t zz = lds32(cb + R_OFF + br * R_BR);
  conv_dense(sb, cb, zz);
  STAMP(8);
  {
    const int x = (4 + ch) * 128 + wtid, c = x >> 2;
    const uint32_t rb = cb + R_OFF + br * R_BR;
    float e48[24], e40[20], e32[16], h32[16], h16[8];
    const int x1 = 159 - (16 * hf + g - 2 * t + 136);
    const uint32_t fs = rb + ((g & 1) ? 2 * x1 : RS_CS + 2 * x1 + 2);
    uint32_t A[2][4][4];
    auto loadA = [&](int buf, uint32_t oe, uint32_t oo, int i0) {
#pragma unroll
      for (int a = 0; a < 2; a++) {
        const uint32_t base = fs + (a ? oo : oe);
        uint32_t* k0 = A[buf][2 * a];
        uint32_t* k1 = A[buf][2 * a + 1];
        k0[1] = ldf(base, i0, 1, 9, hf); k0[0] = ldf(base, i0 + 1, 1, 9, hf); k0[2] = ldf(base, i0 + 2, 1, 9, hf);
        k1[0] = ldf(base, i0 + 3, 1, 9, hf); k1[2] = (i0 == 8) ? 0u : A[buf ^ 1][2 * a][1];
        k0[3] = k0[0]; k1[1] = k0[2]; k1[3] = k1[0];
      }
    };
    loadA(0, R_E2, R_O2, 8);
    loadA(1, R_E2, R_O2, 4);
    mbar_wait(sb + B_W);
    const uint64_t d5 = mkdesc(cb + W5_OFF, 144, 576), d3 = mkdesc(cb + W3_OFF, 144, 576);
    const uint64_t d9 = mkdesc(cb + W9_OFF, 144, 576), d7 = mkdesc(cb + W7_OFF, 144, 576);
    const uint32_t y2d = cb + Y2_OFF + br * 3072 + ysw(32 * (5 - (lane >> 4)) + 16 * hf + (lane & 15));
    const uint32_t y3d = cb + Y3_OFF + br * 2048 + ysw(2 * (16 * hf + (lane & 15)) + (lane >> 4));
#define FAR4(N, ACC, BUF, DA, DB, OFF, FIRST)                                                            \
    wg_fence();                                                                                           \
    _Pragma("unroll") for (int k = 0; k < 4; k++) {                                                      \
      const uint32_t* a = A[BUF][k];                                                                      \
      wgmma_rs<N, 1>(ACC, a[0], a[1], a[2], a[3], ((k >> 1) ? DB : DA) + (k & 1) * 18 + (OFF), !(FIRST) || k); \
    }                                                                                                     \
    wg_commit();
    FAR4(48, e48, 0, d5, d3, 0, 1)
    wg_wait0();
    loadA(0, R_E2, R_O2, 0);
    stsm2(y2d - 5 * 512, PK2(e48, 20), PK2(e48, 22));
#pragma unroll
    for (int i = 0; i < 20; i++) e40[i] = FCPY(e48, i);
    stage_done(sb, 2, lane);
    FAR4(40, e40, 1, d5, d3, 36, 0)
    wg_wait0();
    loadA(1, R_E3, R_O3, 8);
    stsm2(y2d - 4 * 512, PK2(e40, 16), PK2(e40, 18));
#pragma unroll
    for (int i = 0; i < 16; i++) e32[i] = FCPY(e40, i);
    stage_done(sb, 3, lane);
    FAR4(32, e32, 0, d5, d3, 72, 0)
    FAR4(32, h32, 1, d9, d7, 0, 1)
    wg_wait1();
    loadA(0, R_E3, R_O3, 4);
    stsm4(y2d, PK2(e32, 0), PK2(e32, 2), PK2(e32, 4), PK2(e32, 6));
    stsm4(y2d - 2 * 512, PK2(e32, 8), PK2(e32, 10), PK2(e32, 12), PK2(e32, 14));
    stage_done(sb, 4, lane);
    const uint2 gl = gate_ld(x);
    STAMP(9);
    wg_wait0();
    stsm4(y3d, PK2(h32, 8), PK2(h32, 10), PK2(h32, 12), PK2(h32, 14));
#pragma unroll
    for (int i = 0; i < 8; i++) h16[i] = FCPY(h32, i);
    stage_done(sb, 5, lane);
    FAR4(16, h16, 0, d9, d7, 72, 0)
#undef FAR4
    const uint32_t yo = sb + CH_OFF + (x & 3) * 4 + ysw(c);
    uint32_t ua[4], ub[4], ya[4], yb[4], a2[4], b2[4], a3[4], b3[4], s2[4];
    const uint4 dd = lds128(sb + DSK_OFF);
    skip_terms(ua, ub, sb, x, make_uint2(dd.x, dd.y), make_uint2(dd.z, dd.w));
    {
      const int xa = x - 514, xb = x - 513, ca = xa >> 2, cb2 = xb >> 2;
      ld4ch(s2, sb + CH_OFF + U_OFF + (xa & 3) * 4 + (ca & 3) * U_CS + (63 - (ca >> 2)) * 16);
      ld4ch(a3, sb + CH_OFF + U_OFF + (xb & 3) * 4 + (cb2 & 3) * U_CS + (63 - (cb2 >> 2)) * 16);
#pragma unroll
      for (int k = 0; k < 4; k++) s2[k] = hadd2(s2[k], __byte_perm(s2[k], a3[k], 0x5432));
    }
    const uint32_t tag = lds32(sb + TAG_OFF);
    wg_wait0();
    stsm4(y3d + 1024, PK2(h16, 0), PK2(h16, 2), PK2(h16, 4), PK2(h16, 6));
    stage_done(sb, 6, lane);
    STAMP(10);
    const uint32_t g2 = gate_fin(p, gl, x, tag);
    mbar_wait(sb + B_ST + 8 * 4);
    const uint4 k0 = lds128(sb + K1024_OFF), k1 = lds128(sb + K1024_OFF + 16);
    const uint32_t kk[8] = {k0.x, k0.y, k0.z, k0.w, k1.x, k1.y, k1.z, k1.w};
    ld4ch(ya, yo + Y0_OFF); ld4ch(yb, yo + Y0_OFF + 4096);
    ld4ch(a2, yo + Y2_OFF - 1024); ld4ch(b2, yo + Y2_OFF - 1024 + 3072);
    mbar_wait(sb + B_ST + 8 * (5 + (ch >> 1)));
    STAMP(12);
    ld4ch(a3, yo + Y3_OFF - 2048); ld4ch(b3, yo + Y3_OFF - 2048 + 2048);
#pragma unroll
    for (int k = 0; k < 4; k++) {
      ya[k] = hadd2(ya[k], hadd2(hfma2(kk[2 * k], s2[k], a2[k]), a3[k]));
      yb[k] = hadd2(yb[k], hadd2(hfma2(kk[2 * k + 1], s2[k], b2[k]), b3[k]));
    }
    const uint4 r = mix(ya, yb, ua, ub, g2);
    if ((uint32_t)(ch & 1) != rank) send_box(sb, 2 + (ch >> 1), wtid, rank, r);
    else merge_box(sb, &tm_out, 2 + (ch >> 1), wtid, rank, oc0, r, 1 + ch);
  }
  STAMP(14);
  if (wtid == 0) asm volatile("cp.async.bulk.wait_group.read 0;" ::: "memory");
  STAMP(15); GT(1);
}

typedef CUresult (*EncodeFn)(CUtensorMap*, CUtensorMapDataType, cuuint32_t, void*, const cuuint64_t*, const cuuint64_t*,
                             const cuuint32_t*, const cuuint32_t*, CUtensorMapInterleave, CUtensorMapSwizzle,
                             CUtensorMapL2promotion, CUtensorMapFloatOOBfill);

}

extern "C" void kernel_launch(void* const* d_in, const int* in_sizes, int n_in, void* d_out, int out_size) {
  (void)in_sizes; (void)n_in; (void)out_size;
  typedef const __nv_bfloat16* bp;
  Params p;
  p.t[0] = (bp)d_in[10]; p.t[1] = (bp)d_in[11]; p.t[2] = (bp)d_in[12]; p.t[3] = (bp)d_in[13]; p.t[4] = (bp)d_in[14]; p.t[5] = nullptr;
  p.t[6] = (bp)d_in[1]; p.t[7] = (bp)d_in[2]; p.t[8] = (bp)d_in[5]; p.t[9] = (bp)d_in[6]; p.t[10] = (bp)d_in[7];
  p.t[11] = (bp)d_in[3]; p.t[12] = (bp)d_in[4]; p.t[13] = nullptr;
  p.u = (bp)d_in[0]; p.gw = (bp)d_in[16]; p.A_D = (bp)d_in[8]; p.B_D = (bp)d_in[15];
  static EncodeFn enc = nullptr;
  if (!enc) {
    cudaDriverEntryPointQueryResult qr;
    cudaGetDriverEntryPoint("cuTensorMapEncodeTiled", (void**)&enc, cudaEnableDefault, &qr);
    cudaFuncSetAttribute(ssm_kernel, cudaFuncAttributeMaxDynamicSharedMemorySize, SMEM_BYTES);
  }
  CUtensorMap tm_in, tm_out;
  {
    cuuint64_t gd[5] = {512, 2, 4, 4, 64};
    cuuint64_t gs[4] = {1024, 8192, 2048, 32768};
    cuuint32_t bx[5] = {8, 2, 4, 4, 32};
    cuuint32_t es[5] = {1, 1, 1, 1, 1};
    enc(&tm_in, CU_TENSOR_MAP_DATA_TYPE_BFLOAT16, 5, d_in[0], gd, gs, bx, es, CU_TENSOR_MAP_INTERLEAVE_NONE,
        CU_TENSOR_MAP_SWIZZLE_NONE, CU_TENSOR_MAP_L2_PROMOTION_NONE, CU_TENSOR_MAP_FLOAT_OOB_FILL_NONE);
  }
  {
    cuuint64_t gd[3] = {512, 1024, 2};
    cuuint64_t gs[2] = {2048, 1024};
    cuuint32_t bx[3] = {8, 128, 2};
    cuuint32_t es[3] = {1, 1, 1};
    enc(&tm_out, CU_TENSOR_MAP_DATA_TYPE_BFLOAT16, 3, d_out, gd, gs, bx, es, CU_TENSOR_MAP_INTERLEAVE_NONE,
        CU_TENSOR_MAP_SWIZZLE_NONE, CU_TENSOR_MAP_L2_PROMOTION_NONE, CU_TENSOR_MAP_FLOAT_OOB_FILL_NONE);
  }
  ssm_kernel<<<NCTA + NGATE, 640, SMEM_BYTES, cudaStreamPerThread>>>(p, tm_in, tm_out);
}
```

```cpp
#include <cuda_runtime.h>
#include <cuda.h>
#include <cuda_bf16.h>
#include <stdint.h>

namespace {
#define PREDLD 1
#define FCPY(v, i) (((i) % 3 == 2) ? __uint_as_float(opq(__float_as_uint(v[i]), zz)) : opqf(v[i], zz))

constexpr int L = 2048, D = 512, NM = 128;
constexpr int NCTA = 128;
constexpr int NGATE = 4;

constexpr int RAW_OFF = 0;
constexpr int XIN_OFF = 32768;
constexpr int SC2_OFF = XIN_OFF + 8192;
constexpr int BAR_OFF = SC2_OFF + 10240;
constexpr int CH_OFF = BAR_OFF + 256;
constexpr int U_CS = 1184;
constexpr int U_OFF = 0;
constexpr int R_OFF = 4736;
constexpr int RD_X0 = 565;
constexpr int RD_CS = 1216;
constexpr int RS_CS = 320;
constexpr int R_E2 = 2 * RD_CS, R_O2 = R_E2 + 2 * RS_CS, R_E3 = R_O2 + 2 * RS_CS, R_O3 = R_E3 + 2 * RS_CS;
constexpr int R_BR = R_O3 + 2 * RS_CS;
constexpr int W5_OFF = R_OFF + 2 * R_BR;
constexpr int W3_OFF = W5_OFF + 3456;
constexpr int W9_OFF = W3_OFF + 3456;
constexpr int W7_OFF = W9_OFF + 2304;
constexpr int Y0_OFF = W7_OFF + 2304;
constexpr int Y2_OFF = Y0_OFF + 8192, Y3_OFF = Y2_OFF + 6144;
constexpr int CH_BYTES = Y0_OFF + 18432 + 16;
constexpr int SCR_BYTES = 4608;
constexpr int SMEM_BYTES = CH_OFF + 4 * CH_BYTES;
static_assert(CH_BYTES % 128 == 16, "bank staggering of the channel blocks");
static_assert(SMEM_BYTES <= 232448, "smem");
constexpr int B_RAW = BAR_OFF, B_X = BAR_OFF + 8, B_U = BAR_OFF + 40, B_W = BAR_OFF + 48;
constexpr int TAG_OFF = BAR_OFF + 56;
constexpr int K1024_OFF = BAR_OFF + 64;
constexpr int DSK_OFF = BAR_OFF + 160;
constexpr int B_ST = BAR_OFF + 96;

__device__ unsigned int g_gate[L];
__device__ unsigned int g_epoch;
__device__ unsigned int g_ticket;

#define STAMP(k)
#define GT(k)

struct Params {
  const __nv_bfloat16* t[14];
  const __nv_bfloat16 *u, *gw, *A_D, *B_D;
};

template <int N, int TB> __device__ __forceinline__ void wgmma_rs(float* d, uint32_t a0, uint32_t a1, uint32_t a2, uint32_t a3, uint64_t desc, int sc);
template <> __device__ __forceinline__ void wgmma_rs<64, 0>(float* d, uint32_t a0, uint32_t a1, uint32_t a2, uint32_t a3, uint64_t desc, int sc) {
  asm volatile("{\n.reg .pred p;\nsetp.ne.b32 p, %37, 0;\n"
    "wgmma.mma_async.sync.aligned.m64n64k16.f32.bf16.bf16 {%0,%1,%2,%3,%4,%5,%6,%7,%8,%9,%10,%11,%12,%13,%14,%15,%16,%17,%18,%19,%20,%21,%22,%23,%24,%25,%26,%27,%28,%29,%30,%31}, {%32,%33,%34,%35}, %36, p, 1, 1, 0;\n}"
    : "+f"(d[0]), "+f"(d[1]), "+f"(d[2]), "+f"(d[3]), "+f"(d[4]), "+f"(d[5]), "+f"(d[6]), "+f"(d[7]), "+f"(d[8]), "+f"(d[9]), "+f"(d[10]), "+f"(d[11]), "+f"(d[12]), "+f"(d[13]), "+f"(d[14]), "+f"(d[15]), "+f"(d[16]), "+f"(d[17]), "+f"(d[18]), "+f"(d[19]), "+f"(d[20]), "+f"(d[21]), "+f"(d[22]), "+f"(d[23]), "+f"(d[24]), "+f"(d[25]), "+f"(d[26]), "+f"(d[27]), "+f"(d[28]), "+f"(d[29]), "+f"(d[30]), "+f"(d[31]) : "r"(a0), "r"(a1), "r"(a2), "r"(a3), "l"(desc), "r"(sc));
}
template <> __device__ __forceinline__ void wgmma_rs<56, 0>(float* d, uint32_t a0, uint32_t a1, uint32_t a2, uint32_t a3, uint64_t desc, int sc) {
  asm volatile("{\n.reg .pred p;\nsetp.ne.b32 p, %33, 0;\n"
    "wgmma.mma_async.sync.aligned.m64n56k16.f32.bf16.bf16 {%0,%1,%2,%3,%4,%5,%6,%7,%8,%9,%10,%11,%12,%13,%14,%15,%16,%17,%18,%19,%20,%21,%22,%23,%24,%25,%26,%27}, {%28,%29,%30,%31}, %32, p, 1, 1, 0;\n}"
    : "+f"(d[0]), "+f"(d[1]), "+f"(d[2]), "+f"(d[3]), "+f"(d[4]), "+f"(d[5]), "+f"(d[6]), "+f"(d[7]), "+f"(d[8]), "+f"(d[9]), "+f"(d[10]), "+f"(d[11]), "+f"(d[12]), "+f"(d[13]), "+f"(d[14]), "+f"(d[15]), "+f"(d[16]), "+f"(d[17]), "+f"(d[18]), "+f"(d[19]), "+f"(d[20]), "+f"(d[21]), "+f"(d[22]), "+f"(d[23]), "+f"(d[24]), "+f"(d[25]), "+f"(d[26]), "+f"(d[27]) : "r"(a0), "r"(a1), "r"(a2), "r"(a3), "l"(desc), "r"(sc));
}
template <> __device__ __forceinline__ void wgmma_rs<48, 0>(float* d, uint32_t a0, uint32_t a1, uint32_t a2, uint32_t a3, uint64_t desc, int sc) {
  asm volatile("{\n.reg .pred p;\nsetp.ne.b32 p, %29, 0;\n"
    "wgmma.mma_async.sync.aligned.m64n48k16.f32.bf16.bf16 {%0,%1,%2,%3,%4,%5,%6,%7,%8,%9,%10,%11,%12,%13,%14,%15,%16,%17,%18,%19,%20,%21,%22,%23}, {%24,%25,%26,%27}, %28, p, 1, 1, 0;\n}"
    : "+f"(d[0]), "+f"(d[1]), "+f"(d[2]), "+f"(d[3]), "+f"(d[4]), "+f"(d[5]), "+f"(d[6]), "+f"(d[7]), "+f"(d[8]), "+f"(d[9]), "+f"(d[10]), "+f"(d[11]), "+f"(d[12]), "+f"(d[13]), "+f"(d[14]), "+f"(d[15]), "+f"(d[16]), "+f"(d[17]), "+f"(d[18]), "+f"(d[19]), "+f"(d[20]), "+f"(d[21]), "+f"(d[22]), "+f"(d[23]) : "r"(a0), "r"(a1), "r"(a2), "r"(a3), "l"(desc), "r"(sc));
}
template <> __device__ __forceinline__ void wgmma_rs<32, 0>(float* d, uint32_t a0, uint32_t a1, uint32_t a2, uint32_t a3, uint64_t desc, int sc) {
  asm volatile("{\n.reg .pred p;\nsetp.ne.b32 p, %21, 0;\n"
    "wgmma.mma_async.sync.aligned.m64n32k16.f32.bf16.bf16 {%0,%1,%2,%3,%4,%5,%6,%7,%8,%9,%10,%11,%12,%13,%14,%15}, {%16,%17,%18,%19}, %20, p, 1, 1, 0;\n}"
    : "+f"(d[0]), "+f"(d[1]), "+f"(d[2]), "+f"(d[3]), "+f"(d[4]), "+f"(d[5]), "+f"(d[6]), "+f"(d[7]), "+f"(d[8]), "+f"(d[9]), "+f"(d[10]), "+f"(d[11]), "+f"(d[12]), "+f"(d[13]), "+f"(d[14]), "+f"(d[15]) : "r"(a0), "r"(a1), "r"(a2), "r"(a3), "l"(desc), "r"(sc));
}
template <> __device__ __forceinline__ void wgmma_rs<48, 1>(float* d, uint32_t a0, uint32_t a1, uint32_t a2, uint32_t a3, uint64_t desc, int sc) {
  asm volatile("{\n.reg .pred p;\nsetp.ne.b32 p, %29, 0;\n"
    "wgmma.mma_async.sync.aligned.m64n48k16.f32.bf16.bf16 {%0,%1,%2,%3,%4,%5,%6,%7,%8,%9,%10,%11,%12,%13,%14,%15,%16,%17,%18,%19,%20,%21,%22,%23}, {%24,%25,%26,%27}, %28, p, 1, 1, 1;\n}"
    : "+f"(d[0]), "+f"(d[1]), "+f"(d[2]), "+f"(d[3]), "+f"(d[4]), "+f"(d[5]), "+f"(d[6]), "+f"(d[7]), "+f"(d[8]), "+f"(d[9]), "+f"(d[10]), "+f"(d[11]), "+f"(d[12]), "+f"(d[13]), "+f"(d[14]), "+f"(d[15]), "+f"(d[16]), "+f"(d[17]), "+f"(d[18]), "+f"(d[19]), "+f"(d[20]), "+f"(d[21]), "+f"(d[22]), "+f"(d[23]) : "r"(a0), "r"(a1), "r"(a2), "r"(a3), "l"(desc), "r"(sc));
}
template <> __device__ __forceinline__ void wgmma_rs<40, 1>(float* d, uint32_t a0, uint32_t a1, uint32_t a2, uint32_t a3, uint64_t desc, int sc) {
  asm volatile("{\n.reg .pred p;\nsetp.ne.b32 p, %25, 0;\n"
    "wgmma.mma_async.sync.aligned.m64n40k16.f32.bf16.bf16 {%0,%1,%2,%3,%4,%5,%6,%7,%8,%9,%10,%11,%12,%13,%14,%15,%16,%17,%18,%19}, {%20,%21,%22,%23}, %24, p, 1, 1, 1;\n}"
    : "+f"(d[0]), "+f"(d[1]), "+f"(d[2]), "+f"(d[3]), "+f"(d[4]), "+f"(d[5]), "+f"(d[6]), "+f"(d[7]), "+f"(d[8]), "+f"(d[9]), "+f"(d[10]), "+f"(d[11]), "+f"(d[12]), "+f"(d[13]), "+f"(d[14]), "+f"(d[15]), "+f"(d[16]), "+f"(d[17]), "+f"(d[18]), "+f"(d[19]) : "r"(a0), "r"(a1), "r"(a2), "r"(a3), "l"(desc), "r"(sc));
}
template <> __device__ __forceinline__ void wgmma_rs<32, 1>(float* d, uint32_t a0, uint32_t a1, uint32_t a2, uint32_t a3, uint64_t desc, int sc) {
  asm volatile("{\n.reg .pred p;\nsetp.ne.b32 p, %21, 0;\n"
    "wgmma.mma_async.sync.aligned.m64n32k16.f32.bf16.bf16 {%0,%1,%2,%3,%4,%5,%6,%7,%8,%9,%10,%11,%12,%13,%14,%15}, {%16,%17,%18,%19}, %20, p, 1, 1, 1;\n}"
    : "+f"(d[0]), "+f"(d[1]), "+f"(d[2]), "+f"(d[3]), "+f"(d[4]), "+f"(d[5]), "+f"(d[6]), "+f"(d[7]), "+f"(d[8]), "+f"(d[9]), "+f"(d[10]), "+f"(d[11]), "+f"(d[12]), "+f"(d[13]), "+f"(d[14]), "+f"(d[15]) : "r"(a0), "r"(a1), "r"(a2), "r"(a3), "l"(desc), "r"(sc));
}
template <> __device__ __forceinline__ void wgmma_rs<16, 1>(float* d, uint32_t a0, uint32_t a1, uint32_t a2, uint32_t a3, uint64_t desc, int sc) {
  asm volatile("{\n.reg .pred p;\nsetp.ne.b32 p, %13, 0;\n"
    "wgmma.mma_async.sync.aligned.m64n16k16.f32.bf16.bf16 {%0,%1,%2,%3,%4,%5,%6,%7}, {%8,%9,%10,%11}, %12, p, 1, 1, 1;\n}"
    : "+f"(d[0]), "+f"(d[1]), "+f"(d[2]), "+f"(d[3]), "+f"(d[4]), "+f"(d[5]), "+f"(d[6]), "+f"(d[7]) : "r"(a0), "r"(a1), "r"(a2), "r"(a3), "l"(desc), "r"(sc));
}

__device__ __forceinline__ uint32_t pack_bf16(float lo, float hi) {
  uint32_t r; asm("cvt.rn.bf16x2.f32 %0, %1, %2;" : "=r"(r) : "f"(hi), "f"(lo)); return r;
}
__device__ __forceinline__ float bf_lo(uint32_t v) { return __uint_as_float(v << 16); }
__device__ __forceinline__ float bf_hi(uint32_t v) { return __uint_as_float(v & 0xffff0000u); }
__device__ __forceinline__ float bf_round(float x) { return bf_lo(pack_bf16(x, 0.f)); }
__device__ __forceinline__ uint32_t hmul2(uint32_t a, uint32_t b) { uint32_t r; asm("mul.rn.bf16x2 %0, %1, %2;" : "=r"(r) : "r"(a), "r"(b)); return r; }
__device__ __forceinline__ uint32_t hadd2(uint32_t a, uint32_t b) { uint32_t r; asm("add.rn.bf16x2 %0, %1, %2;" : "=r"(r) : "r"(a), "r"(b)); return r; }
__device__ __forceinline__ uint32_t hsub2(uint32_t a, uint32_t b) { uint32_t r; asm("sub.rn.bf16x2 %0, %1, %2;" : "=r"(r) : "r"(a), "r"(b)); return r; }
__device__ __forceinline__ uint32_t hfma2(uint32_t a, uint32_t b, uint32_t c) { uint32_t r; asm("fma.rn.bf16x2 %0, %1, %2, %3;" : "=r"(r) : "r"(a), "r"(b), "r"(c)); return r; }

__device__ __forceinline__ void sts16(uint32_t a, uint32_t v) { asm volatile("st.shared.b16 [%0], %1;" ::"r"(a), "h"((unsigned short)v) : "memory"); }
__device__ __forceinline__ void sts32(uint32_t a, uint32_t v) { asm volatile("st.shared.b32 [%0], %1;" ::"r"(a), "r"(v) : "memory"); }
__device__ __forceinline__ void sts64(uint32_t a, uint32_t x, uint32_t y) { asm volatile("st.shared.v2.b32 [%0], {%1,%2};" ::"r"(a), "r"(x), "r"(y) : "memory"); }
__device__ __forceinline__ void sts128(uint32_t a, uint32_t x, uint32_t y, uint32_t z, uint32_t w) {
  asm volatile("st.shared.v4.b32 [%0], {%1,%2,%3,%4};" ::"r"(a), "r"(x), "r"(y), "r"(z), "r"(w) : "memory");
}
__device__ __forceinline__ uint32_t lds32(uint32_t a) { uint32_t v; asm volatile("ld.shared.b32 %0, [%1];" : "=r"(v) : "r"(a) : "memory"); return v; }
__device__ __forceinline__ uint32_t ldf(uint32_t base, int i, int lo0, int hi0, int hf) {
  if (i < lo0 || i > hi0 + 2) return 0u;
  if (i < lo0 + 2 || i > hi0) {
    uint32_t v;
    asm volatile("{\n.reg .pred p;\nsetp.eq.b32 p, %2, %3;\nmov.b32 %0, 0;\n@p ld.shared.b32 %0, [%1];\n}" : "=r"(v) : "r"(base + i * 16), "r"(hf), "r"(i > hi0 ? 1 : 0) : "memory");
    return v;
  }
  return lds32(base + i * 16);
}
__device__ __forceinline__ uint4 lds128(uint32_t a) {
  uint4 v; asm volatile("ld.shared.v4.b32 {%0,%1,%2,%3}, [%4];" : "=r"(v.x), "=r"(v.y), "=r"(v.z), "=r"(v.w) : "r"(a) : "memory"); return v;
}
__device__ __forceinline__ uint4 ldg128(const void* a) {
  uint4 v; asm volatile("ld.global.nc.v4.b32 {%0,%1,%2,%3}, [%4];" : "=r"(v.x), "=r"(v.y), "=r"(v.z), "=r"(v.w) : "l"(a) : "memory"); return v;
}
__device__ __forceinline__ uint2 ldg64(const void* a) {
  uint2 v; asm volatile("ld.global.nc.v2.b32 {%0,%1}, [%2];" : "=r"(v.x), "=r"(v.y) : "l"(a) : "memory"); return v;
}
__device__ __forceinline__ void ldsm4(uint32_t a, uint32_t& r0, uint32_t& r1, uint32_t& r2, uint32_t& r3) {
  asm volatile("ldmatrix.sync.aligned.m8n8.x4.shared.b16 {%0,%1,%2,%3}, [%4];" : "=r"(r0), "=r"(r1), "=r"(r2), "=r"(r3) : "r"(a) : "memory");
}
__device__ __forceinline__ void ldsm4t(uint32_t a, uint32_t& r0, uint32_t& r1, uint32_t& r2, uint32_t& r3) {
  asm volatile("ldmatrix.sync.aligned.m8n8.x4.trans.shared.b16 {%0,%1,%2,%3}, [%4];" : "=r"(r0), "=r"(r1), "=r"(r2), "=r"(r3) : "r"(a) : "memory");
}
__device__ __forceinline__ void stsm4(uint32_t a, uint32_t r0, uint32_t r1, uint32_t r2, uint32_t r3) {
  asm volatile("stmatrix.sync.aligned.m8n8.x4.shared.b16 [%0], {%1,%2,%3,%4};" ::"r"(a), "r"(r0), "r"(r1), "r"(r2), "r"(r3) : "memory");
}
__device__ __forceinline__ void stsm4t(uint32_t a, uint32_t r0, uint32_t r1, uint32_t r2, uint32_t r3) {
  asm volatile("stmatrix.sync.aligned.m8n8.x4.trans.shared.b16 [%0], {%1,%2,%3,%4};" ::"r"(a), "r"(r0), "r"(r1), "r"(r2), "r"(r3) : "memory");
}
__device__ __forceinline__ void stsm2(uint32_t a, uint32_t r0, uint32_t r1) {
  asm volatile("stmatrix.sync.aligned.m8n8.x2.shared.b16 [%0], {%1,%2};" ::"r"(a), "r"(r0), "r"(r1) : "memory");
}
__device__ __forceinline__ void stsm2t(uint32_t a, uint32_t r0, uint32_t r1) {
  asm volatile("stmatrix.sync.aligned.m8n8.x2.trans.shared.b16 [%0], {%1,%2};" ::"r"(a), "r"(r0), "r"(r1) : "memory");
}
__device__ __forceinline__ void mma16816(float* c, uint32_t a0, uint32_t a1, uint32_t a2, uint32_t a3, uint32_t b0, uint32_t b1) {
  asm("mma.sync.aligned.m16n8k16.row.col.f32.bf16.bf16.f32 {%0,%1,%2,%3}, {%4,%5,%6,%7}, {%8,%9}, {%0,%1,%2,%3};"
      : "+f"(c[0]), "+f"(c[1]), "+f"(c[2]), "+f"(c[3]) : "r"(a0), "r"(a1), "r"(a2), "r"(a3), "r"(b0), "r"(b1));
}
__device__ __forceinline__ void bar_sync(int id, int n) { asm volatile("bar.sync %0, %1;" ::"r"(id), "r"(n) : "memory"); }
__device__ __forceinline__ void wg_fence() { asm volatile("wgmma.fence.sync.aligned;" ::: "memory"); }
__device__ __forceinline__ void wg_commit() { asm volatile("wgmma.commit_group.sync.aligned;" ::: "memory"); }
__device__ __forceinline__ void wg_wait0() { asm volatile("wgmma.wait_group.sync.aligned 0;" ::: "memory"); }
__device__ __forceinline__ void wg_wait1() { asm volatile("wgmma.wait_group.sync.aligned 1;" ::: "memory"); }
__device__ __forceinline__ void fence_async() { asm volatile("fence.proxy.async.shared::cta;" ::: "memory"); }
__device__ __forceinline__ uint32_t opq(uint32_t x, uint32_t z) { uint32_t r; asm volatile("xor.b32 %0, %1, %2;" : "=r"(r) : "r"(x), "r"(z)); return r; }
__device__ __forceinline__ float opqf(float x, uint32_t z) { float r; asm volatile("add.rn.f32 %0, %1, %2;" : "=f"(r) : "f"(x), "f"(__uint_as_float(z))); return r; }
__device__ __forceinline__ uint64_t mkdesc(uint32_t addr, uint32_t lbo, uint32_t sbo) {
  return (uint64_t)((addr & 0x3FFFF) >> 4) | ((uint64_t)(lbo >> 4) << 16) | ((uint64_t)(sbo >> 4) << 32);
}
__device__ __forceinline__ uint32_t mapa(uint32_t a, uint32_t rank) {
  uint32_t r; asm("mapa.shared::cluster.u32 %0, %1, %2;" : "=r"(r) : "r"(a), "r"(rank)); return r;
}
__device__ __forceinline__ void mbar_init_expect(uint32_t bar, uint32_t bytes) {
  asm volatile("mbarrier.init.shared::cta.b64 [%0], 1;" ::"r"(bar) : "memory");
  asm volatile("mbarrier.arrive.expect_tx.shared::cta.b64 _, [%0], %1;" ::"r"(bar), "r"(bytes) : "memory");
}
__device__ __forceinline__ void mbar_wait(uint32_t bar) {
#pragma unroll 1
  for (int it = 0; it < (1 << 22); it++) {
    uint32_t ok;
    asm volatile("{\n.reg .pred p;\nmbarrier.try_wait.parity.acquire.cluster.shared::cta.b64 p, [%1], 0;\nselp.u32 %0, 1, 0, p;\n}"
                 : "=r"(ok) : "r"(bar) : "memory");
    if (ok) return;
  }
  __trap();
}
__device__ __forceinline__ void st_async4(uint32_t a, uint32_t bar, uint32_t x, uint32_t y, uint32_t z, uint32_t w) {
  asm volatile("st.async.weak.shared::cluster.mbarrier::complete_tx::bytes.v4.b32 [%0], {%2,%3,%4,%5}, [%1];"
               ::"r"(a), "r"(bar), "r"(x), "r"(y), "r"(z), "r"(w) : "memory");
}

struct cf { float re, im; };
__device__ __forceinline__ cf cmul(cf a, cf b) { return {fmaf(a.re, b.re, -a.im * b.im), fmaf(a.re, b.im, a.im * b.re)}; }
__device__ __forceinline__ cf csq(cf a) { return {fmaf(a.re, a.re, -a.im * a.im), (a.re + a.re) * a.im}; }
__device__ __forceinline__ cf cexp_p(float xl, float y, float p) {
  float mag; asm("ex2.approx.ftz.f32 %0, %1;" : "=f"(mag) : "f"(xl * p));
  const float th = y * p;
  const float k = __fadd_rn(fmaf(th, 0.15915494309189535f, 12582912.f), -12582912.f);
  float r = fmaf(k, -6.2831854820251465f, th);
  r = fmaf(k, 1.7484555314695172e-07f, r);
  return {mag * __cosf(r), mag * __sinf(r)};
}
__device__ __forceinline__ uint32_t ysw(int c) { return (uint32_t)(c ^ ((c >> 3) & 3)) * 16u; }

#define CMUL2(OR, OI, xr, xi, yr, yi, nyi) do { OR = hfma2(xr, yr, hmul2(xi, nyi)); OI = hfma2(xr, yi, hmul2(xi, yr)); } while (0)

__device__ __forceinline__ uint32_t gate_slow(const __nv_bfloat16* u, const __nv_bfloat16* gw, int row) {
  float s = 0.f;
  const uint32_t* xr = (const uint32_t*)(u + (size_t)row * D);
  const uint32_t* wr = (const uint32_t*)gw;
#pragma unroll 1
  for (int j = 0; j < D / 2; j++) { const uint32_t pr = hmul2(xr[j], wr[j]); s += bf_lo(pr); s += bf_hi(pr); }
  s = bf_round(s);
  return pack_bf16(1.f / (1.f + expf(-s)), 0.f);
}

__device__ __forceinline__ uint2 gate_ld(int x) {
  uint2 gv;
  asm volatile("ld.relaxed.gpu.global.v2.u32 {%0,%1}, [%2];" : "=r"(gv.x), "=r"(gv.y) : "l"(g_gate + x * 2) : "memory");
  return gv;
}
__device__ __noinline__ uint32_t gate_poll(const Params* pp, int x, uint32_t tag) {
  uint2 gv;
#pragma unroll 1
  for (int spins = 0; spins < (1 << 16); spins++) {
    gv = gate_ld(x);
    if ((gv.x >> 16) == tag && (gv.y >> 16) == tag) return __byte_perm(gv.x, gv.y, 0x5410);
  }
  return __byte_perm(gate_slow(pp->u, pp->gw, x * 2), gate_slow(pp->u, pp->gw, x * 2 + 1), 0x5410);
}
__device__ __forceinline__ uint32_t gate_fin(const Params& p, uint2 gv, int x, uint32_t tag) {
  if ((gv.x >> 16) == tag && (gv.y >> 16) == tag) return __byte_perm(gv.x, gv.y, 0x5410);
  return gate_poll(&p, x, tag);
}

__device__ __forceinline__ void ld4ch(uint32_t* v, uint32_t addr) {
#pragma unroll
  for (int k = 0; k < 4; k++) v[k] = lds32(addr + k * CH_BYTES);
}
__device__ __forceinline__ void skip_terms(uint32_t* ua, uint32_t* ub, uint32_t sb, int x, uint2 dA, uint2 dB) {
  const int c = x >> 2;
  uint32_t uu[4];
  ld4ch(uu, sb + CH_OFF + (x & 3) * 4 + U_OFF + (c & 3) * U_CS + (63 - (c >> 2)) * 16);
#pragma unroll
  for (int k = 0; k < 4; k++) {
    ua[k] = hmul2(uu[k], __byte_perm((k & 2) ? dA.y : dA.x, 0, (k & 1) ? 0x3232 : 0x1010));
    ub[k] = hmul2(uu[k], __byte_perm((k & 2) ? dB.y : dB.x, 0, (k & 1) ? 0x3232 : 0x1010));
  }
}
__device__ __forceinline__ uint4 mix(const uint32_t* a, const uint32_t* b, const uint32_t* ua, const uint32_t* ub, uint32_t g2) {
  const uint32_t h2 = hsub2(0x3f803f80u, g2);
  uint32_t o[4];
#pragma unroll
  for (int k = 0; k < 4; k++) o[k] = hadd2(hmul2(g2, hadd2(a[k], ua[k])), hmul2(h2, hadd2(b[k], ub[k])));
  return make_uint4(__byte_perm(o[0], o[1], 0x5410), __byte_perm(o[2], o[3], 0x5410), __byte_perm(o[0], o[1], 0x7632), __byte_perm(o[2], o[3], 0x7632));
}
__device__ __forceinline__ void send_box(uint32_t sb, int slot, int wtid, uint32_t rank, uint4 r) {
  st_async4(mapa(sb + XIN_OFF + slot * 2048 + wtid * 16, rank ^ 1), mapa(sb + B_X + slot * 8, rank ^ 1), r.x, r.y, r.z, r.w);
}
__device__ __forceinline__ void merge_rows(uint32_t st, uint32_t rank, uint4 r, uint4 q) {
  const uint4 lo = rank ? q : r, hi = rank ? r : q;
  sts128(st, lo.x, lo.y, hi.x, hi.y); sts128(st + 2048, lo.z, lo.w, hi.z, hi.w);
}
__device__ __forceinline__ void merge_box(uint32_t sb, const CUtensorMap* tm_out, int slot, int wtid, uint32_t rank, int oc0, uint4 r, int barid) {
  const uint32_t st = sb + RAW_OFF + slot * 4096 + wtid * 16;
  mbar_wait(sb + B_X + slot * 8);
  merge_rows(st, rank, r, lds128(sb + XIN_OFF + slot * 2048 + wtid * 16));
  fence_async();
  bar_sync(barid, 128);
  if (wtid == 0) {
    asm volatile("cp.async.bulk.tensor.3d.global.shared::cta.bulk_group [%0, {%2, %3, %4}], [%1];"
                 ::"l"(tm_out), "r"(sb + RAW_OFF + slot * 4096), "r"(oc0), "r"((2 * slot + (int)rank) * 128), "r"(0) : "memory");
    asm volatile("cp.async.bulk.commit_group;" ::: "memory");
  }
}

__device__ __forceinline__ uint32_t band2(int e, int lo, int hi) {
  uint32_t r = ((uint32_t)(e - lo) <= (uint32_t)(hi - lo) ? 0x3f80u : 0u) | ((uint32_t)(e - 1 - lo) <= (uint32_t)(hi - lo) ? 0x3f800000u : 0u);
  asm volatile("" : "+r"(r));
  return r;
}

__device__ __forceinline__ void stage_done(uint32_t sb, int stage, int lane) {
  __syncwarp();
  if (lane == 0) asm volatile("mbarrier.arrive.shared::cta.b64 _, [%0];" ::"r"(sb + B_ST + 8 * stage) : "memory");
}
#define PK2(v, i) pack_bf16(v[i], v[(i) + 1])

__device__ __forceinline__ void conv_dense(uint32_t sb, uint32_t cb, uint32_t zz) {
  const int lane = threadIdx.x & 31, wq = (threadIdx.x >> 5) & 3, br = wq >> 1, hf = wq & 1, g = lane >> 2, t = lane & 3;
  const uint32_t rb = cb + R_OFF + br * R_BR;
  const int eo = 16 * hf + g - 2 * t;
  const int x0 = RD_X0 - (eo + 536);
  const uint32_t fa = rb + ((g & 1) ? 2 * x0 : RD_CS + 2 * x0 + 2);
  const uint64_t ub = mkdesc(cb + U_OFF, U_CS, 128);
  const uint32_t yd = cb + Y0_OFF + br * 4096 + ysw(4 * (63 - 8 * (lane >> 4) - (lane & 7)) + 2 * hf + ((lane >> 3) & 1));
  uint32_t A[2][4][4];
  float e64[32], e56[28], e48[24];
  auto loadA = [&](int j) {
#pragma unroll
    for (int k = 0; k < 4; k++) {
      const int s = 34 - 4 * j - k;
      if (s >= 0) {
        if (k == 0 && j == 0) A[0][0][2] = ldf(fa, 2 * s + 2, 2, 67, hf);
        A[j & 1][k][0] = ldf(fa, 2 * s + 1, 2, 67, hf);
        A[j & 1][k][1] = ldf(fa, 2 * s, 2, 67, hf);
      }
    }
#pragma unroll
    for (int k = 0; k < 4; k++) {
      if (34 - 4 * j - k >= 0) {
        A[j & 1][k][3] = A[j & 1][k][0];
        if (k) A[j & 1][k][2] = A[j & 1][k - 1][1];
        else if (j) A[j & 1][0][2] = A[(j - 1) & 1][3][1];
      }
    }
  };
  loadA(0); loadA(1);
#pragma unroll
  for (int j = 0; j < 9; j++) {
    if (j == 4) {
      wg_wait0();
      stsm2t(yd - 7 * 512, PK2(e64, 28), PK2(e64, 30));
#pragma unroll
      for (int i = 0; i < 28; i++) e56[i] = FCPY(e64, i);
      stage_done(sb, 0, lane);
    }
    if (j == 8) {
      wg_wait0();
      stsm2t(yd - 6 * 512, PK2(e56, 24), PK2(e56, 26));
#pragma unroll
      for (int i = 0; i < 24; i++) e48[i] = FCPY(e56, i);
      stage_done(sb, 1, lane);
    }
    wg_fence();
#pragma unroll
    for (int k = 0; k < 4; k++) {
      const int s = 34 - 4 * j - k;
      if (s >= 0) {
        const int o = 2 * s - 66 + 128;
        const int cc = o & 3, rs = (o >> 2) - 32;
        const uint64_t desc = ub + (uint64_t)((cc * U_CS - rs * 16) >> 4);
        const uint32_t* a = A[j & 1][k];
        if (j < 4) wgmma_rs<64, 0>(e64, a[0], a[1], a[2], a[3], desc, s != 34);
        else if (j < 8) wgmma_rs<56, 0>(e56, a[0], a[1], a[2], a[3], desc, 1);
        else wgmma_rs<48, 0>(e48, a[0], a[1], a[2], a[3], desc, 1);
      }
    }
    wg_commit();
    if (j >= 1 && j < 8) { wg_wait1(); loadA(j + 1); }
  }
  wg_wait0();
#pragma unroll
  for (int i = 0; i < 6; i += 2) stsm4t(yd - i * 512, PK2(e48, 4 * i), PK2(e48, 4 * i + 2), PK2(e48, 4 * i + 4), PK2(e48, 4 * i + 6));
}

__device__ __noinline__ unsigned int gate_rows(const Params* pp, int grow, int step, int rend) {
  const __nv_bfloat16 *u = pp->u, *gw = pp->gw;
  const int lane = threadIdx.x & 31;
  uint4 gx[4][2], nx[4][2];
#pragma unroll
  for (int i = 0; i < 4; i++) {
    nx[i][0] = ldg128(u + (size_t)(grow + i) * D + lane * 8);
    nx[i][1] = ldg128(u + (size_t)(grow + i) * D + 256 + lane * 8);
  }
  const uint4 gw0 = ldg128(gw + lane * 8), gw1 = ldg128(gw + 256 + lane * 8);
  const uint32_t ws[8] = {gw0.x, gw0.y, gw0.z, gw0.w, gw1.x, gw1.y, gw1.z, gw1.w};
  unsigned int epoch;
  asm volatile("ld.relaxed.gpu.global.u32 %0, [%1];" : "=r"(epoch) : "l"(&g_epoch) : "memory");
#pragma unroll 1
  for (; grow < rend; grow += step) {
#pragma unroll
    for (int i = 0; i < 4; i++) { gx[i][0] = nx[i][0]; gx[i][1] = nx[i][1]; }
    if (grow + step < rend) {
#pragma unroll
      for (int i = 0; i < 4; i++) {
        nx[i][0] = ldg128(u + (size_t)(grow + step + i) * D + lane * 8);
        nx[i][1] = ldg128(u + (size_t)(grow + step + i) * D + 256 + lane * 8);
      }
    }
    float c[2][4];
#pragma unroll
    for (int i = 0; i < 2; i++) {
      const uint4 *x = gx[2 * i], *y = gx[2 * i + 1];
      const uint32_t xs[8] = {x[0].x, x[0].y, x[0].z, x[0].w, x[1].x, x[1].y, x[1].z, x[1].w};
      const uint32_t ys[8] = {y[0].x, y[0].y, y[0].z, y[0].w, y[1].x, y[1].y, y[1].z, y[1].w};
      c[i][0] = c[i][1] = c[i][2] = c[i][3] = 0.f;
#pragma unroll
      for (int j = 0; j < 8; j += 2)
        mma16816(c[i], hmul2(xs[j], ws[j]), hmul2(ys[j], ws[j]), hmul2(xs[j + 1], ws[j + 1]), hmul2(ys[j + 1], ws[j + 1]), 0x3f803f80u, 0x3f803f80u);
    }
    float s = (lane & 2) ? ((lane & 1) ? c[1][2] : c[1][0]) : ((lane & 1) ? c[0][2] : c[0][0]);
#pragma unroll
    for (int o = 4; o < 32; o <<= 1) s += __shfl_xor_sync(0xffffffffu, s, o);
    s = bf_round(s);
    const float gv = 1.f / (1.f + expf(-s));
    const uint32_t w = ((epoch + 1) << 16) | (pack_bf16(gv, 0.f) & 0xffffu);
    if (lane < 4) asm volatile("st.relaxed.gpu.global.u32 [%0], %1;" ::"l"(&g_gate[grow + lane]), "r"(w) : "memory");
  }
  return epoch;
}
#define GW 1
constexpr int GSPLIT = L - 4 * GW * NCTA;
__device__ __noinline__ void gate_cta(const Params* pp) {
  const unsigned int epoch = gate_rows(pp, (blockIdx.x * 20 + (threadIdx.x >> 5)) * 4, 80 * NGATE, GSPLIT);
  __syncthreads();
  if (threadIdx.x == 0 && atomicAdd(&g_ticket, 1u) == NCTA + NGATE - 1) { g_ticket = 0; g_epoch = epoch + 1; }
}

__global__ void __cluster_dims__(2, 1, 1) __launch_bounds__(640, 1)
ssm_kernel(const __grid_constant__ Params p, const __grid_constant__ CUtensorMap tm_in, const __grid_constant__ CUtensorMap tm_out) {
  extern __shared__ __align__(1024) unsigned char smem_raw[];
  const uint32_t sb = (uint32_t)__cvta_generic_to_shared(smem_raw);
  const int tid = threadIdx.x, lane = tid & 31;
  const int warp = __shfl_sync(0xffffffffu, tid >> 5, 0);
  const int ch = warp >> 2, wq = warp & 3, br = wq >> 1, hf = wq & 1;
  const int g = lane >> 2, t = lane & 3;
  if (__builtin_expect(blockIdx.x < NGATE, 0)) { gate_cta(&p); return; }
  const int bid = blockIdx.x - NGATE;
  const uint32_t rank = blockIdx.x & 1;
  const uint32_t cb = sb + CH_OFF + ch * CH_BYTES;
  const int wtid = tid & 127;
  const int oc0 = (bid >> 1) * 8;
  STAMP(0); GT(0);

  if (warp >= 16) {
    if (wtid == 0) {
      mbar_init_expect(sb + B_RAW, 32768);
#pragma unroll
      for (int i = 0; i < 4; i++) mbar_init_expect(sb + B_X + 8 * i, 2048);
      asm volatile("mbarrier.init.shared::cta.b64 [%0], 128;" ::"r"(sb + B_U) : "memory");
      asm volatile("mbarrier.init.shared::cta.b64 [%0], 128;" ::"r"(sb + B_W) : "memory");
#pragma unroll
      for (int i = 0; i < 7; i++) asm volatile("mbarrier.init.shared::cta.b64 [%0], 16;" ::"r"(sb + B_ST + 8 * i) : "memory");
      asm volatile("fence.mbarrier_init.release.cluster;" ::: "memory");
      asm volatile("fence.proxy.async.shared::cta;" ::: "memory");
    }
    __syncwarp();
    asm volatile("barrier.cluster.arrive.relaxed.aligned;" ::: "memory");
    if (wq >= 4 - GW) gate_rows(&p, GSPLIT + (bid * GW + 3 - wq) * 4, L, L);
    unsigned int epoch;
    asm volatile("ld.relaxed.gpu.global.u32 %0, [%1];" : "=r"(epoch) : "l"(&g_epoch) : "memory");
    asm volatile("barrier.cluster.wait.aligned;" ::: "memory");
    if (wtid == 0) {
      asm volatile("cp.async.bulk.tensor.5d.shared::cluster.global.mbarrier::complete_tx::bytes.multicast::cluster [%0], [%1, {%3, %4, %4, %4, %5}], [%2], %6;"
                   ::"r"(sb + RAW_OFF + rank * 16384), "l"(&tm_in), "r"(sb + B_RAW), "r"(oc0), "r"(0), "r"((int)rank * 32), "h"((unsigned short)3) : "memory");
    }
    sts128(sb + CH_OFF + wq * CH_BYTES + U_OFF + (lane >> 3) * U_CS + (64 + (lane & 7)) * 16, 0, 0, 0, 0);
    const uint2 dA = ldg64(p.A_D + bid * 4), dB = ldg64(p.B_D + bid * 4);
    uint32_t BA[3][4], BB[4][4];
    {
      const int l1 = br ? 3 : 6, h1 = br ? 5 : 10, l2 = br ? 5 : 12, h2 = br ? 11 : 20;
#pragma unroll
      for (int i = 0; i < 4; i++) {
        const int e = 16 * hf + g - 2 * t + 32 - 16 * i;
        BB[i][0] = band2(e, l2, h2); BB[i][1] = band2(e + 8, l2, h2); BB[i][2] = band2(e - 8, l2, h2); BB[i][3] = BB[i][0];
        if (i) { BA[i - 1][0] = band2(e, l1, h1); BA[i - 1][1] = band2(e + 8, l1, h1); BA[i - 1][2] = band2(e - 8, l1, h1); BA[i - 1][3] = BA[i - 1][0]; }
      }
    }
    const uint32_t tag = (epoch + 1) & 0xffffu;
    if (wtid == 0) { sts32(sb + TAG_OFF, tag); sts128(sb + DSK_OFF, dA.x, dA.y, dB.x, dB.y); }
    STAMP(3);
    mbar_wait(sb + B_RAW);
    STAMP(4);
    {
      const uint32_t dst = sb + CH_OFF + (g & 3) * CH_BYTES + U_OFF + t * U_CS + (63 - wq * 16) * 16;
#pragma unroll
      for (int h = 0; h < 2; h++) {
        uint32_t r[8][4];
#pragma unroll
        for (int i = 0; i < 8; i++) ldsm4t(sb + RAW_OFF + (wq * 16 + h * 8 + i) * 512 + lane * 16, r[i][0], r[i][1], r[i][2], r[i][3]);
        if ((uint32_t)(g >> 2) == rank) {
#pragma unroll
          for (int i = 0; i < 8; i++) sts128(dst - (h * 8 + i) * 16, r[i][0], r[i][1], r[i][2], r[i][3]);
        }
      }
    }
    fence_async();
    asm volatile("mbarrier.arrive.shared::cta.b64 _, [%0];" ::"r"(sb + B_U) : "memory");
    bar_sync(5, 128);
    STAMP(5);
    {
      const int mrow = lane & 7, mi = lane >> 3;
      const uint64_t ub0 = mkdesc(sb + CH_OFF + U_OFF, U_CS, 128);
      uint32_t wa, wb;
      {
        const int c = 4 * (47 - 8 * (mi >> 1) - mrow) + 2 * hf + (mi & 1);
        wa = sb + CH_OFF + (br ? W3_OFF : W5_OFF) + (5 - (c >> 5)) * 576 + ((c & 31) >> 3) * 144 + (c & 7) * 16;
        const int c2 = c - 64, pp = c2 >> 1;
        wb = sb + CH_OFF + (br ? W7_OFF : W9_OFF) + (1 - (pp >> 5)) * 1152 + (c2 & 1) * 576 + ((pp & 31) >> 3) * 144 + (pp & 7) * 16;
      }
      {
        float w1[24];
#pragma unroll
        for (int i = 0; i < 24; i++) w1[i] = 0.f;
#pragma unroll 1
        for (int k = 0; k < 4; k++) {
          wg_fence();
#pragma unroll
          for (int i = 0; i < 3; i++)
            wgmma_rs<48, 0>(w1, BA[i][0], BA[i][1], BA[i][2], BA[i][3],
                            ub0 + (uint64_t)((k * CH_BYTES + ((2 * i + 2) & 3) * U_CS + (16 + (i == 0)) * 16) >> 4), i);
          wg_commit();
          wg_wait0();
#pragma unroll
          for (int i = 0; i < 3; i++) stsm4t(wa + k * CH_BYTES + i * 1152, PK2(w1, 8 * i), PK2(w1, 8 * i + 2), PK2(w1, 8 * i + 4), PK2(w1, 8 * i + 6));
        }
      }
      {
        float w2[2][16];
#pragma unroll
        for (int i = 0; i < 16; i++) { w2[0][i] = 0.f; w2[1][i] = 0.f; }
#pragma unroll 1
        for (int kp = 0; kp < 2; kp++) {
          wg_fence();
#pragma unroll
          for (int k = 0; k < 2; k++)
#pragma unroll
            for (int i = 0; i < 4; i++)
              wgmma_rs<32, 0>(w2[k], BB[i][0], BB[i][1], BB[i][2], BB[i][3],
                              ub0 + (uint64_t)(((2 * kp + k) * CH_BYTES + ((2 * i) & 3) * U_CS + (32 + (i < 2)) * 16) >> 4), i);
          wg_commit();
          wg_wait0();
#pragma unroll
          for (int k = 0; k < 2; k++)
#pragma unroll
            for (int i = 0; i < 2; i++)
              stsm4t(wb + (2 * kp + k) * CH_BYTES + i * 1152, PK2(w2[k], 8 * i), PK2(w2[k], 8 * i + 2), PK2(w2[k], 8 * i + 4), PK2(w2[k], 8 * i + 6));
        }
      }
    }
    fence_async();
    asm volatile("mbarrier.arrive.shared::cta.b64 _, [%0];" ::"r"(sb + B_W) : "memory");
    STAMP(7);
    {
      const int bsel = (int)rank ^ br ^ 1, xl = wtid & 63;
      uint2 gl[4];
      uint32_t ua[4][4], ub[4][4];
#pragma unroll
      for (int i = 0; i < 4; i++) skip_terms(ua[i], ub[i], sb, (2 * (i >> 1) + bsel) * 128 + (i & 1) * 64 + xl, dA, dB);
      const uint32_t yo = sb + CH_OFF + (xl & 3) * 4 + ysw(xl >> 2) + bsel * 512;
#pragma unroll
      for (int i = 0; i < 2; i++) gl[i] = gate_ld(bsel * 128 + i * 64 + xl);
#pragma unroll
      for (int slot = 0; slot < 2; slot++) {
        const int box = 2 * slot + bsel;
        uint32_t g2[2], ya[2][4], yb[2][4];
#pragma unroll
        for (int h = 0; h < 2; h++) g2[h] = gate_fin(p, gl[2 * slot + h], box * 128 + h * 64 + xl, tag);
        mbar_wait(sb + B_ST + 8 * box);
        STAMP(8 + slot);
        if (slot == 0) { gl[2] = gate_ld((2 + bsel) * 128 + xl); gl[3] = gate_ld((2 + bsel) * 128 + 64 + xl); }
#pragma unroll
        for (int h = 0; h < 2; h++) {
          const uint32_t yh = (yo ^ (h * 32)) + h * 256 + slot * 1024;
          ld4ch(ya[h], yh + Y0_OFF); ld4ch(yb[h], yh + Y0_OFF + 4096);
          if (slot) {
            uint32_t a2[4], b2[4];
            ld4ch(a2, yh + Y2_OFF - 1024); ld4ch(b2, yh + Y2_OFF - 1024 + 3072);
#pragma unroll
            for (int k = 0; k < 4; k++) { ya[h][k] = hadd2(ya[h][k], a2[k]); yb[h][k] = hadd2(yb[h][k], b2[k]); }
          }
        }
        const uint4 r0 = mix(ya[0], yb[0], ua[2 * slot], ub[2 * slot], g2[0]), r1 = mix(ya[1], yb[1], ua[2 * slot + 1], ub[2 * slot + 1], g2[1]);
        if (br == 0) { send_box(sb, slot, xl, rank, r0); send_box(sb, slot, xl + 64, rank, r1); }
        else {
          const uint32_t st = sb + RAW_OFF + slot * 4096 + xl * 16, xin = sb + XIN_OFF + slot * 2048 + xl * 16;
          mbar_wait(sb + B_X + slot * 8);
          const uint4 q0 = lds128(xin), q1 = lds128(xin + 1024);
          merge_rows(st, rank, r0, q0); merge_rows(st + 1024, rank, r1, q1);
          fence_async();
          bar_sync(6, 64);
          if (xl == 0) {
            asm volatile("cp.async.bulk.tensor.3d.global.shared::cta.bulk_group [%0, {%2, %3, %4}], [%1];"
                         ::"l"(&tm_out), "r"(sb + RAW_OFF + slot * 4096), "r"(oc0), "r"(box * 128), "r"(0) : "memory");
            asm volatile("cp.async.bulk.commit_group;" ::: "memory");
          }
        }
        STAMP(10 + slot);
      }
    }
    if (wtid == 0 && atomicAdd(&g_ticket, 1u) == NCTA + NGATE - 1) { g_ticket = 0; g_epoch = epoch + 1; }
    if (wtid == 64) asm volatile("cp.async.bulk.wait_group.read 0;" ::: "memory");
    STAMP(15);
    return;
  }
  asm volatile("barrier.cluster.arrive.relaxed.aligned;" ::: "memory");

  const int moff = (bid * 4 + (tid >> 7)) * NM + (tid & 63) * 2;
  const int brt = (tid >> 6) & 1;
  const __nv_bfloat16* const* tp = p.t + (brt ? 0 : 6);
  const uint32_t q0 = *(const uint32_t*)(tp[0] + moff), q1 = *(const uint32_t*)(tp[1] + moff);
  const uint32_t q2 = *(const uint32_t*)(tp[2] + moff), q3 = *(const uint32_t*)(tp[3] + moff);
  const uint2 ldt4 = *(const uint2*)(tp[4] + bid * 4);
  const uint32_t q4 = *(const uint32_t*)(tp[brt ? 2 : 5] + moff), q5 = *(const uint32_t*)(tp[brt ? 3 : 6] + moff);

  for (int i = wtid & 63; i < R_BR / 16; i += 64) sts128(cb + R_OFF + br * R_BR + i * 16, 0, 0, 0, 0);
  STAMP(1);

  float acc[5][4];
  float k2048 = 0.f;
  const uint32_t scr = cb + Y0_OFF + wq * SCR_BYTES;
  const uint32_t scr2 = sb + SC2_OFF + warp * 640;
  {
    const uint32_t ldt2 = (ch & 2) ? ldt4.y : ldt4.x;
    const float dt = bf_round(expf((ch & 1) ? bf_hi(ldt2) : bf_lo(ldt2)));
#pragma unroll
    for (int i = 0; i < 5; i++) acc[i][0] = acc[i][1] = acc[i][2] = acc[i][3] = 0.f;
    STAMP(2);
    const uint32_t tb = scr + lane * 16;
    const uint32_t tb1 = tb + hf * 512, tb2 = tb + (hf ^ 1) * 512;
    const uint32_t ta = scr + (lane >> 3) * 512 + (lane & 7) * 16;
    const uint32_t tc = ((lane & 8) ? scr2 : scr + 4096) + (lane >> 4) * 128 + (lane & 7) * 16;
    const uint32_t tm = scr2 + 512 + ((lane >> 3) & 1) * 64 + (lane >> 4) * 16;
#pragma unroll 1
    for (int r = 0; r < 2; r++) {
      cf c, z1, z128;
      {
        const uint32_t sh = r ? 0x3244u : 0x1044u;
        float v0 = __uint_as_float(__byte_perm(q0, 0, sh));
        const float v1 = __uint_as_float(__byte_perm(q1, 0, sh)), v2 = __uint_as_float(__byte_perm(q2, 0, sh)), v3 = __uint_as_float(__byte_perm(q3, 0, sh));
        if (br == 0) { c = cmul(cf{v2, v3}, cf{dt * __uint_as_float(__byte_perm(q4, 0, sh)), dt * __uint_as_float(__byte_perm(q5, 0, sh))}); }
        else { v0 = -bf_round(expf(v0)); c = cf{2.f * dt * v2, 2.f * dt * v3}; }
        const float xl = (dt * v0) * 1.4426950408889634f, y = dt * v1;
        z1 = cexp_p(xl, y, 1.f); z128 = cexp_p(xl, y, 128.f);
      }
      const cf z2 = csq(z1), z4 = csq(z2), z8 = csq(z4);
      const cf w8 = {z8.re, -z8.im};
      const cf z16 = csq(w8), z24 = cmul(z16, w8), z32 = csq(z16), z40 = cmul(z32, w8), z48 = csq(z24), z56 = cmul(z32, z24), z64 = csq(z32);
      const cf z256 = csq(z128), z512 = csq(z256), z1024 = csq(z512), z2048 = csq(z1024);
      {
        float kk = fmaf(c.re, z2048.re, -c.im * z2048.im);
#pragma unroll
        for (int o = 16; o; o >>= 1) kk += __shfl_xor_sync(0xffffffffu, kk, o);
        k2048 += kk;
      }
      __syncwarp();
      {
        uint32_t xr[4] = {pack_bf16(1.f, z8.re), pack_bf16(z16.re, z24.re), pack_bf16(z32.re, z40.re), pack_bf16(z48.re, z56.re)};
        uint32_t xi[4] = {pack_bf16(0.f, w8.im), pack_bf16(z16.im, z24.im), pack_bf16(z32.im, z40.im), pack_bf16(z48.im, z56.im)};
        sts128(tb1, xr[0], xr[1], xr[2], xr[3]);
        sts128(tb1 + 1024, xi[0], xi[1], xi[2], xi[3]);
        const uint32_t yr = pack_bf16(z64.re, z64.re), yi = pack_bf16(z64.im, z64.im), nyi = yi ^ 0x80008000u;
        uint32_t o[4], q[4];
#pragma unroll
        for (int i = 0; i < 4; i++) CMUL2(o[i], q[i], xr[i], xi[i], yr, yi, nyi);
        sts128(tb2, o[0], o[1], o[2], o[3]);
        sts128(tb2 + 1024, q[0], q[1], q[2], q[3]);
      }
      {
        const cf h1 = cmul(c, z128), h2 = cmul(c, z256), h3 = cmul(h1, z256), h4 = cmul(c, z512), h5 = cmul(h1, z512), h6 = cmul(h2, z512), h7 = cmul(h3, z512);
        const cf e1 = cmul(c, z1), e2 = cmul(c, z2), e3 = cmul(e1, z2), e129 = cmul(h1, z1), e130 = cmul(h1, z2), e131 = cmul(e129, z2);
        const cf e258 = cmul(h2, z2), e386 = cmul(h3, z2);
        const uint32_t pr0 = pack_bf16(c.re, e1.re), pr2 = pack_bf16(h1.re, e129.re), pi0 = pack_bf16(c.im, e1.im), pi2 = pack_bf16(h1.im, e129.im);
        sts128(tb + 4 * 512, pr0, pack_bf16(e2.re, e3.re), pr2, pack_bf16(e130.re, e131.re));
        sts128(tb + 5 * 512, pi0, pack_bf16(e2.im, e3.im), pi2, pack_bf16(e130.im, e131.im));
        uint32_t xr[4] = {pack_bf16(h2.re, e258.re), pack_bf16(h3.re, e386.re), pack_bf16(h4.re, h5.re), pack_bf16(h6.re, h7.re)};
        uint32_t xi[4] = {pack_bf16(h2.im, e258.im), pack_bf16(h3.im, e386.im), pack_bf16(h4.im, h5.im), pack_bf16(h6.im, h7.im)};
        sts128(tb + 6 * 512, xr[0], xr[1], xr[2], xr[3]);
        sts128(tb + 7 * 512, xi[0], xi[1], xi[2], xi[3]);
        xr[1] = __byte_perm(xr[0], xr[1], 0x5410); xi[1] = __byte_perm(xi[0], xi[1], 0x5410);
        xr[0] = __byte_perm(pr0, pr2, 0x5410); xi[0] = __byte_perm(pi0, pi2, 0x5410);
        const uint32_t yr = pack_bf16(z1024.re, z1024.re), yi = pack_bf16(z1024.im, z1024.im), nyi = yi ^ 0x80008000u;
        uint32_t o[4], q[4];
#pragma unroll
        for (int i = 0; i < 4; i++) CMUL2(o[i], q[i], xr[i], xi[i], yr, yi, nyi);
        sts128(tb + 8 * 512, o[0], o[1], o[2], o[3]);
        sts128(scr2 + lane * 16, q[0], q[1], q[2], q[3]);
        const uint32_t m4 = pack_bf16(z4.re, z4.im);
        sts16(scr2 + 512 + lane * 2, m4); sts16(scr2 + 576 + lane * 2, m4 >> 16);
      }
      __syncwarp();
#pragma unroll
      for (int kp = 0; kp < 2; kp++) {
        uint32_t rr[2], ri[2], yr[2], yi[2];
        ldsm4t(tc + kp * 256, rr[0], ri[0], rr[1], ri[1]);
        ldsm4(tm + kp * 32, yr[0], yi[0], yr[1], yi[1]);
#pragma unroll
        for (int k2 = 0; k2 < 2; k2++) {
          const int kk = kp * 2 + k2;
          uint32_t a0, a1, a2, a3, pr, pi, qr, qi, xr, xi;
          ldsm4t(ta + kk * 128, a0, a1, a2, a3);
          ldsm4t(ta + 2048 + kk * 128, pr, pi, qr, qi);
          const uint32_t nyi = yi[k2] ^ 0x80008000u;
          mma16816(acc[0], a0, a1, a2, a3, pr, pi);
          mma16816(acc[2], a0, a1, a2, a3, qr, qi);
          mma16816(acc[4], a0, a1, a2, a3, rr[k2], ri[k2]);
          CMUL2(xr, xi, pr, pi, yr[k2], yi[k2], nyi);
          mma16816(acc[1], a0, a1, a2, a3, xr, xi);
          CMUL2(xr, xi, qr, qi, yr[k2], yi[k2], nyi);
          mma16816(acc[3], a0, a1, a2, a3, xr, xi);
        }
      }
    }
  }
  STAMP(3);
  __syncwarp();
  {
    const uint32_t xs = scr + lane * 16;
#define OTH(i, k) __float_as_uint(acc[i][2 + (k)])
    sts128(xs, OTH(0, 0), OTH(0, 1), OTH(1, 0), OTH(1, 1));
    sts128(xs + 512, OTH(2, 0), OTH(2, 1), OTH(3, 0), OTH(3, 1));
    sts128(xs + 1024, OTH(4, 0), OTH(4, 1), __float_as_uint(k2048), 0);
#undef OTH
  }

  bar_sync(7 + (warp >> 1), 64);
  STAMP(4);
  {
    const uint32_t xo = cb + Y0_OFF + (wq ^ 1) * SCR_BYTES + lane * 16;
    const uint4 o0 = lds128(xo), o1 = lds128(xo + 512), o2 = lds128(xo + 1024);
    const uint32_t rb = cb + R_OFF + br * R_BR;
#define OWN(i, k) acc[i][k]
    const uint32_t vP = pack_bf16(OWN(0, 1) + __uint_as_float(o0.y), OWN(0, 0) + __uint_as_float(o0.x));
    const uint32_t vP4 = pack_bf16(OWN(1, 1) + __uint_as_float(o0.w), OWN(1, 0) + __uint_as_float(o0.z));
    const uint32_t vQ = pack_bf16(OWN(2, 1) + __uint_as_float(o1.y), OWN(2, 0) + __uint_as_float(o1.x));
    const uint32_t vQ4 = pack_bf16(OWN(3, 1) + __uint_as_float(o1.w), OWN(3, 0) + __uint_as_float(o1.z));
    const uint32_t vR = pack_bf16(OWN(4, 1) + __uint_as_float(o2.y), OWN(4, 0) + __uint_as_float(o2.x));
#undef OWN
    const int j = g + 8 * hf;
    {
      const int a = 2 * (t & 1) + 64 * (t & 2) + 8 * j;
      const uint32_t ad = rb + 2 * (RD_X0 - 1 - a);
      const uint32_t a1 = (t & 2) ? ad - 8 : ad, a2 = (t & 2) ? ad : ad - 8;
      const uint32_t w1 = (t & 2) ? vP4 : vP, w2 = (t & 2) ? vP : vP4;
      sts32(a1, w1); sts32(a2, w2);
      sts16(a1 + RD_CS + 2, w1); sts16(a1 + RD_CS + 4, w1 >> 16);
      sts16(a2 + RD_CS + 2, w2); sts16(a2 + RD_CS + 4, w2 >> 16);
    }
    if (t < 2) {
      const int b = 256 + 128 * t + 8 * j;
      const uint32_t ad = rb + 2 * (RD_X0 - 6 - b);
      const uint32_t v22 = __byte_perm(vQ4, 0, 0x3232), v00 = __byte_perm(vQ, 0, 0x3232);
      sts16(ad, vQ4);
      sts64(ad + 2, v22, __byte_perm(vQ4, vQ, 0x5432));
      sts32(ad + 10, v00);
      if (b != 256) { sts16(ad + 14, v00); sts128(ad + RD_CS + 2, vQ4, v22, vQ, v00); }
      else { sts64(ad + RD_CS + 2, vQ4, v22); sts32(ad + RD_CS + 10, vQ); sts16(ad + RD_CS + 14, v00); }
    } else {
      const uint32_t ao = rb + R_O2 + 2 * (159 - (32 * t + j)), ae = ao - (R_O2 - R_E2) + 2;
      sts16(ao, vQ4 >> 16); sts16(ao + RS_CS + 2, vQ4 >> 16); sts16(ao - 32, vQ4); sts16(ao - 32 + RS_CS + 2, vQ4);
      sts16(ae - 32, vQ); sts16(ae - 32 + RS_CS + 2, vQ);
      if (lane != 2 || hf) { sts16(ae, vQ >> 16); sts16(ae + RS_CS + 2, vQ >> 16); }
      else {
        const uint32_t vv = __byte_perm(vQ, 0, 0x3232), ad = rb + 2 * (RD_X0 - 514);
        sts16(ad, vv); sts32(ad + 2, vv); sts16(ad + 6, vv); sts64(ad + RD_CS + 2, vv, vv);
      }
    }
    {
      const uint32_t a = rb + ((g & 1) ? R_O3 : R_E3 + 2) + 2 * (159 - (64 + 16 * t + (j >> 1)));
      const bool p1024 = (lane == 0) && (hf == 0);
      const uint32_t a00 = p1024 ? rb + R_E2 + 2 * (159 - 127) : a;
      sts16(a00, vR >> 16); sts16(a00 + RS_CS + 2, vR >> 16);
      sts16(a - 16, vR); sts16(a - 16 + RS_CS + 2, vR);
      if (p1024) {
        sts32(sb + K1024_OFF + (ch * 2 + br) * 4, __byte_perm(vR, 0, 0x3232));
        const uint32_t kv = pack_bf16(k2048 + __uint_as_float(o2.z), 0.f);
        sts16(rb + R_E3 + 2 * (159 - 127), kv); sts16(rb + R_E3 + 2 * (159 - 127) + RS_CS + 2, kv);
      }
    }
  }
  STAMP(5);
  asm volatile("barrier.cluster.wait.aligned;" ::: "memory");
  bar_sync(7 + (warp >> 1), 64);
  mbar_wait(sb + B_U);
  STAMP(6);

  const uint32_t zz = lds32(cb + R_OFF + br * R_BR);
  conv_dense(sb, cb, zz);
  STAMP(8);
  {
    const int x = (4 + ch) * 128 + wtid, c = x >> 2;
    const uint32_t rb = cb + R_OFF + br * R_BR;
    float e48[24], e40[20], e32[16], h32[16], h16[8];
    const int x1 = 159 - (16 * hf + g - 2 * t + 136);
    const uint32_t fs = rb + ((g & 1) ? 2 * x1 : RS_CS + 2 * x1 + 2);
    uint32_t A[2][4][4];
    auto loadA = [&](int buf, uint32_t oe, uint32_t oo, int i0) {
#pragma unroll
      for (int a = 0; a < 2; a++) {
        const uint32_t base = fs + (a ? oo : oe);
        uint32_t* k0 = A[buf][2 * a];
        uint32_t* k1 = A[buf][2 * a + 1];
        k0[1] = ldf(base, i0, 1, 9, hf); k0[0] = ldf(base, i0 + 1, 1, 9, hf); k0[2] = ldf(base, i0 + 2, 1, 9, hf);
        k1[0] = ldf(base, i0 + 3, 1, 9, hf); k1[2] = (i0 == 8) ? 0u : A[buf ^ 1][2 * a][1];
        k0[3] = k0[0]; k1[1] = k0[2]; k1[3] = k1[0];
      }
    };
    loadA(0, R_E2, R_O2, 8);
    loadA(1, R_E2, R_O2, 4);
    mbar_wait(sb + B_W);
    const uint64_t d5 = mkdesc(cb + W5_OFF, 144, 576), d3 = mkdesc(cb + W3_OFF, 144, 576);
    const uint64_t d9 = mkdesc(cb + W9_OFF, 144, 576), d7 = mkdesc(cb + W7_OFF, 144, 576);
    const uint32_t y2d = cb + Y2_OFF + br * 3072 + ysw(32 * (5 - (lane >> 4)) + 16 * hf + (lane & 15));
    const uint32_t y3d = cb + Y3_OFF + br * 2048 + ysw(2 * (16 * hf + (lane & 15)) + (lane >> 4));
#define FAR4(N, ACC, BUF, DA, DB, OFF, FIRST)                                                            \
    wg_fence();                                                                                           \
    _Pragma("unroll") for (int k = 0; k < 4; k++) {                                                      \
      const uint32_t* a = A[BUF][k];                                                                      \
      wgmma_rs<N, 1>(ACC, a[0], a[1], a[2], a[3], ((k >> 1) ? DB : DA) + (k & 1) * 18 + (OFF), !(FIRST) || k); \
    }                                                                                                     \
    wg_commit();
    FAR4(48, e48, 0, d5, d3, 0, 1)
    wg_wait0();
    loadA(0, R_E2, R_O2, 0);
    stsm2(y2d - 5 * 512, PK2(e48, 20), PK2(e48, 22));
#pragma unroll
    for (int i = 0; i < 20; i++) e40[i] = FCPY(e48, i);
    stage_done(sb, 2, lane);
    FAR4(40, e40, 1, d5, d3, 36, 0)
    wg_wait0();
    loadA(1, R_E3, R_O3, 8);
    stsm2(y2d - 4 * 512, PK2(e40, 16), PK2(e40, 18));
#pragma unroll
    for (int i = 0; i < 16; i++) e32[i] = FCPY(e40, i);
    stage_done(sb, 3, lane);
    FAR4(32, e32, 0, d5, d3, 72, 0)
    FAR4(32, h32, 1, d9, d7, 0, 1)
    wg_wait1();
    loadA(0, R_E3, R_O3, 4);
    stsm4(y2d, PK2(e32, 0), PK2(e32, 2), PK2(e32, 4), PK2(e32, 6));
    stsm4(y2d - 2 * 512, PK2(e32, 8), PK2(e32, 10), PK2(e32, 12), PK2(e32, 14));
    stage_done(sb, 4, lane);
    const uint2 gl = gate_ld(x);
    STAMP(9);
    wg_wait0();
    stsm4(y3d, PK2(h32, 8), PK2(h32, 10), PK2(h32, 12), PK2(h32, 14));
#pragma unroll
    for (int i = 0; i < 8; i++) h16[i] = FCPY(h32, i);
    stage_done(sb, 5, lane);
    FAR4(16, h16, 0, d9, d7, 72, 0)
#undef FAR4
    const uint32_t yo = sb + CH_OFF + (x & 3) * 4 + ysw(c);
    uint32_t ua[4], ub[4], ya[4], yb[4], a2[4], b2[4], a3[4], b3[4], s2[4];
    const uint4 dd = lds128(sb + DSK_OFF);
    skip_terms(ua, ub, sb, x, make_uint2(dd.x, dd.y), make_uint2(dd.z, dd.w));
    {
      const int xa = x - 514, xb = x - 513, ca = xa >> 2, cb2 = xb >> 2;
      ld4ch(s2, sb + CH_OFF + U_OFF + (xa & 3) * 4 + (ca & 3) * U_CS + (63 - (ca >> 2)) * 16);
      ld4ch(a3, sb + CH_OFF + U_OFF + (xb & 3) * 4 + (cb2 & 3) * U_CS + (63 - (cb2 >> 2)) * 16);
#pragma unroll
      for (int k = 0; k < 4; k++) s2[k] = hadd2(s2[k], __byte_perm(s2[k], a3[k], 0x5432));
    }
    const uint32_t tag = lds32(sb + TAG_OFF);
    wg_wait0();
    stsm4(y3d + 1024, PK2(h16, 0), PK2(h16, 2), PK2(h16, 4), PK2(h16, 6));
    stage_done(sb, 6, lane);
    STAMP(10);
    const uint32_t g2 = gate_fin(p, gl, x, tag);
    mbar_wait(sb + B_ST + 8 * 4);
    const uint4 k0 = lds128(sb + K1024_OFF), k1 = lds128(sb + K1024_OFF + 16);
    const uint32_t kk[8] = {k0.x, k0.y, k0.z, k0.w, k1.x, k1.y, k1.z, k1.w};
    ld4ch(ya, yo + Y0_OFF); ld4ch(yb, yo + Y0_OFF + 4096);
    ld4ch(a2, yo + Y2_OFF - 1024); ld4ch(b2, yo + Y2_OFF - 1024 + 3072);
    mbar_wait(sb + B_ST + 8 * (5 + (ch >> 1)));
    STAMP(12);
    ld4ch(a3, yo + Y3_OFF - 2048); ld4ch(b3, yo + Y3_OFF - 2048 + 2048);
#pragma unroll
    for (int k = 0; k < 4; k++) {
      ya[k] = hadd2(ya[k], hadd2(hfma2(kk[2 * k], s2[k], a2[k]), a3[k]));
      yb[k] = hadd2(yb[k], hadd2(hfma2(kk[2 * k + 1], s2[k], b2[k]), b3[k]));
    }
    const uint4 r = mix(ya, yb, ua, ub, g2);
    if ((uint32_t)(ch & 1) != rank) send_box(sb, 2 + (ch >> 1), wtid, rank, r);
    else merge_box(sb, &tm_out, 2 + (ch >> 1), wtid, rank, oc0, r, 1 + ch);
  }
  STAMP(14);
  if (wtid == 0) asm volatile("cp.async.bulk.wait_group.read 0;" ::: "memory");
  STAMP(15); GT(1);
}

typedef CUresult (*EncodeFn)(CUtensorMap*, CUtensorMapDataType, cuuint32_t, void*, const cuuint64_t*, const cuuint64_t*,
                             const cuuint32_t*, const cuuint32_t*, CUtensorMapInterleave, CUtensorMapSwizzle,
                             CUtensorMapL2promotion, CUtensorMapFloatOOBfill);

}

extern "C" void kernel_launch(void* const* d_in, const int* in_sizes, int n_in, void* d_out, int out_size) {
  (void)in_sizes; (void)n_in; (void)out_size;
  typedef const __nv_bfloat16* bp;
  Params p;
  p.t[0] = (bp)d_in[10]; p.t[1] = (bp)d_in[11]; p.t[2] = (bp)d_in[12]; p.t[3] = (bp)d_in[13]; p.t[4] = (bp)d_in[14]; p.t[5] = nullptr;
  p.t[6] = (bp)d_in[1]; p.t[7] = (bp)d_in[2]; p.t[8] = (bp)d_in[5]; p.t[9] = (bp)d_in[6]; p.t[10] = (bp)d_in[7];
  p.t[11] = (bp)d_in[3]; p.t[12] = (bp)d_in[4]; p.t[13] = nullptr;
  p.u = (bp)d_in[0]; p.gw = (bp)d_in[16]; p.A_D = (bp)d_in[8]; p.B_D = (bp)d_in[15];
  static EncodeFn enc = nullptr;
  if (!enc) {
    cudaDriverEntryPointQueryResult qr;
    cudaGetDriverEntryPoint("cuTensorMapEncodeTiled", (void**)&enc, cudaEnableDefault, &qr);
    cudaFuncSetAttribute(ssm_kernel, cudaFuncAttributeMaxDynamicSharedMemorySize, SMEM_BYTES);
  }
  CUtensorMap tm_in, tm_out;
  {
    cuuint64_t gd[5] = {512, 2, 4, 4, 64};
    cuuint64_t gs[4] = {1024, 8192, 2048, 32768};
    cuuint32_t bx[5] = {8, 2, 4, 4, 32};
    cuuint32_t es[5] = {1, 1, 1, 1, 1};
    enc(&tm_in, CU_TENSOR_MAP_DATA_TYPE_BFLOAT16, 5, d_in[0], gd, gs, bx, es, CU_TENSOR_MAP_INTERLEAVE_NONE,
        CU_TENSOR_MAP_SWIZZLE_NONE, CU_TENSOR_MAP_L2_PROMOTION_NONE, CU_TENSOR_MAP_FLOAT_OOB_FILL_NONE);
  }
  {
    cuuint64_t gd[3] = {512, 1024, 2};
    cuuint64_t gs[2] = {2048, 1024};
    cuuint32_t bx[3] = {8, 128, 2};
    cuuint32_t es[3] = {1, 1, 1};
    enc(&tm_out, CU_TENSOR_MAP_DATA_TYPE_BFLOAT16, 3, d_out, gd, gs, bx, es, CU_TENSOR_MAP_INTERLEAVE_NONE,
        CU_TENSOR_MAP_SWIZZLE_NONE, CU_TENSOR_MAP_L2_PROMOTION_NONE, CU_TENSOR_MAP_FLOAT_OOB_FILL_NONE);
  }
  ssm_kernel<<<NCTA + NGATE, 640, SMEM_BYTES, cudaStreamPerThread>>>(p, tm_in, tm_out);
}
```

```cpp
#include <cuda_runtime.h>
#include <cuda.h>
#include <cuda_bf16.h>
#include <stdint.h>

namespace {
#define PREDLD 1
#define FCPY(v, i) (((i) % 3 == 2) ? __uint_as_float(opq(__float_as_uint(v[i]), zz)) : opqf(v[i], zz))

constexpr int L = 2048, D = 512, NM = 128;
constexpr int NCTA = 128;
constexpr int NGATE = 4;

constexpr int RAW_OFF = 0;
constexpr int XIN_OFF = 32768;
constexpr int SC2_OFF = XIN_OFF + 8192;
constexpr int BAR_OFF = SC2_OFF + 10240;
constexpr int CH_OFF = BAR_OFF + 256;
constexpr int U_CS = 1184;
constexpr int U_OFF = 0;
constexpr int R_OFF = 4736;
constexpr int RD_X0 = 565;
constexpr int RD_CS = 1216;
constexpr int RS_CS = 320;
constexpr int R_E2 = 2 * RD_CS, R_O2 = R_E2 + 2 * RS_CS, R_E3 = R_O2 + 2 * RS_CS, R_O3 = R_E3 + 2 * RS_CS + 16;
constexpr int R_BR = R_O3 + 2 * RS_CS - 16;
constexpr int W5_OFF = R_OFF + 2 * R_BR;
constexpr int W3_OFF = W5_OFF + 3456;
constexpr int W9_OFF = W3_OFF + 3456;
constexpr int W7_OFF = W9_OFF + 2304;
constexpr int Y0_OFF = W7_OFF + 2304;
constexpr int Y2_OFF = Y0_OFF + 8192, Y3_OFF = Y2_OFF + 6144;
constexpr int CH_BYTES = Y0_OFF + 18432 + 16;
constexpr int SCR_BYTES = 4608;
constexpr int SMEM_BYTES = CH_OFF + 4 * CH_BYTES;
static_assert(CH_BYTES % 128 == 16, "bank staggering of the channel blocks");
static_assert(SMEM_BYTES <= 232448, "smem");
constexpr int B_RAW = BAR_OFF, B_X = BAR_OFF + 8, B_U = BAR_OFF + 40, B_W = BAR_OFF + 48;
constexpr int TAG_OFF = BAR_OFF + 56;
constexpr int K1024_OFF = BAR_OFF + 64;
constexpr int DSK_OFF = BAR_OFF + 160;
constexpr int B_ST = BAR_OFF + 96;

__device__ unsigned int g_gate[L];
__device__ unsigned int g_epoch;
__device__ unsigned int g_ticket;

#define STAMP(k)
#define GT(k)

struct Params {
  const __nv_bfloat16* t[14];
  const __nv_bfloat16 *u, *gw, *A_D, *B_D;
};

template <int N, int TB> __device__ __forceinline__ void wgmma_rs(float* d, uint32_t a0, uint32_t a1, uint32_t a2, uint32_t a3, uint64_t desc, int sc);
template <> __device__ __forceinline__ void wgmma_rs<64, 0>(float* d, uint32_t a0, uint32_t a1, uint32_t a2, uint32_t a3, uint64_t desc, int sc) {
  asm volatile("{\n.reg .pred p;\nsetp.ne.b32 p, %37, 0;\n"
    "wgmma.mma_async.sync.aligned.m64n64k16.f32.bf16.bf16 {%0,%1,%2,%3,%4,%5,%6,%7,%8,%9,%10,%11,%12,%13,%14,%15,%16,%17,%18,%19,%20,%21,%22,%23,%24,%25,%26,%27,%28,%29,%30,%31}, {%32,%33,%34,%35}, %36, p, 1, 1, 0;\n}"
    : "+f"(d[0]), "+f"(d[1]), "+f"(d[2]), "+f"(d[3]), "+f"(d[4]), "+f"(d[5]), "+f"(d[6]), "+f"(d[7]), "+f"(d[8]), "+f"(d[9]), "+f"(d[10]), "+f"(d[11]), "+f"(d[12]), "+f"(d[13]), "+f"(d[14]), "+f"(d[15]), "+f"(d[16]), "+f"(d[17]), "+f"(d[18]), "+f"(d[19]), "+f"(d[20]), "+f"(d[21]), "+f"(d[22]), "+f"(d[23]), "+f"(d[24]), "+f"(d[25]), "+f"(d[26]), "+f"(d[27]), "+f"(d[28]), "+f"(d[29]), "+f"(d[30]), "+f"(d[31]) : "r"(a0), "r"(a1), "r"(a2), "r"(a3), "l"(desc), "r"(sc));
}
template <> __device__ __forceinline__ void wgmma_rs<56, 0>(float* d, uint32_t a0, uint32_t a1, uint32_t a2, uint32_t a3, uint64_t desc, int sc) {
  asm volatile("{\n.reg .pred p;\nsetp.ne.b32 p, %33, 0;\n"
    "wgmma.mma_async.sync.aligned.m64n56k16.f32.bf16.bf16 {%0,%1,%2,%3,%4,%5,%6,%7,%8,%9,%10,%11,%12,%13,%14,%15,%16,%17,%18,%19,%20,%21,%22,%23,%24,%25,%26,%27}, {%28,%29,%30,%31}, %32, p, 1, 1, 0;\n}"
    : "+f"(d[0]), "+f"(d[1]), "+f"(d[2]), "+f"(d[3]), "+f"(d[4]), "+f"(d[5]), "+f"(d[6]), "+f"(d[7]), "+f"(d[8]), "+f"(d[9]), "+f"(d[10]), "+f"(d[11]), "+f"(d[12]), "+f"(d[13]), "+f"(d[14]), "+f"(d[15]), "+f"(d[16]), "+f"(d[17]), "+f"(d[18]), "+f"(d[19]), "+f"(d[20]), "+f"(d[21]), "+f"(d[22]), "+f"(d[23]), "+f"(d[24]), "+f"(d[25]), "+f"(d[26]), "+f"(d[27]) : "r"(a0), "r"(a1), "r"(a2), "r"(a3), "l"(desc), "r"(sc));
}
template <> __device__ __forceinline__ void wgmma_rs<48, 0>(float* d, uint32_t a0, uint32_t a1, uint32_t a2, uint32_t a3, uint64_t desc, int sc) {
  asm volatile("{\n.reg .pred p;\nsetp.ne.b32 p, %29, 0;\n"
    "wgmma.mma_async.sync.aligned.m64n48k16.f32.bf16.bf16 {%0,%1,%2,%3,%4,%5,%6,%7,%8,%9,%10,%11,%12,%13,%14,%15,%16,%17,%18,%19,%20,%21,%22,%23}, {%24,%25,%26,%27}, %28, p, 1, 1, 0;\n}"
    : "+f"(d[0]), "+f"(d[1]), "+f"(d[2]), "+f"(d[3]), "+f"(d[4]), "+f"(d[5]), "+f"(d[6]), "+f"(d[7]), "+f"(d[8]), "+f"(d[9]), "+f"(d[10]), "+f"(d[11]), "+f"(d[12]), "+f"(d[13]), "+f"(d[14]), "+f"(d[15]), "+f"(d[16]), "+f"(d[17]), "+f"(d[18]), "+f"(d[19]), "+f"(d[20]), "+f"(d[21]), "+f"(d[22]), "+f"(d[23]) : "r"(a0), "r"(a1), "r"(a2), "r"(a3), "l"(desc), "r"(sc));
}
template <> __device__ __forceinline__ void wgmma_rs<32, 0>(float* d, uint32_t a0, uint32_t a1, uint32_t a2, uint32_t a3, uint64_t desc, int sc) {
  asm volatile("{\n.reg .pred p;\nsetp.ne.b32 p, %21, 0;\n"
    "wgmma.mma_async.sync.aligned.m64n32k16.f32.bf16.bf16 {%0,%1,%2,%3,%4,%5,%6,%7,%8,%9,%10,%11,%12,%13,%14,%15}, {%16,%17,%18,%19}, %20, p, 1, 1, 0;\n}"
    : "+f"(d[0]), "+f"(d[1]), "+f"(d[2]), "+f"(d[3]), "+f"(d[4]), "+f"(d[5]), "+f"(d[6]), "+f"(d[7]), "+f"(d[8]), "+f"(d[9]), "+f"(d[10]), "+f"(d[11]), "+f"(d[12]), "+f"(d[13]), "+f"(d[14]), "+f"(d[15]) : "r"(a0), "r"(a1), "r"(a2), "r"(a3), "l"(desc), "r"(sc));
}
template <> __device__ __forceinline__ void wgmma_rs<48, 1>(float* d, uint32_t a0, uint32_t a1, uint32_t a2, uint32_t a3, uint64_t desc, int sc) {
  asm volatile("{\n.reg .pred p;\nsetp.ne.b32 p, %29, 0;\n"
    "wgmma.mma_async.sync.aligned.m64n48k16.f32.bf16.bf16 {%0,%1,%2,%3,%4,%5,%6,%7,%8,%9,%10,%11,%12,%13,%14,%15,%16,%17,%18,%19,%20,%21,%22,%23}, {%24,%25,%26,%27}, %28, p, 1, 1, 1;\n}"
    : "+f"(d[0]), "+f"(d[1]), "+f"(d[2]), "+f"(d[3]), "+f"(d[4]), "+f"(d[5]), "+f"(d[6]), "+f"(d[7]), "+f"(d[8]), "+f"(d[9]), "+f"(d[10]), "+f"(d[11]), "+f"(d[12]), "+f"(d[13]), "+f"(d[14]), "+f"(d[15]), "+f"(d[16]), "+f"(d[17]), "+f"(d[18]), "+f"(d[19]), "+f"(d[20]), "+f"(d[21]), "+f"(d[22]), "+f"(d[23]) : "r"(a0), "r"(a1), "r"(a2), "r"(a3), "l"(desc), "r"(sc));
}
template <> __device__ __forceinline__ void wgmma_rs<40, 1>(float* d, uint32_t a0, uint32_t a1, uint32_t a2, uint32_t a3, uint64_t desc, int sc) {
  asm volatile("{\n.reg .pred p;\nsetp.ne.b32 p, %25, 0;\n"
    "wgmma.mma_async.sync.aligned.m64n40k16.f32.bf16.bf16 {%0,%1,%2,%3,%4,%5,%6,%7,%8,%9,%10,%11,%12,%13,%14,%15,%16,%17,%18,%19}, {%20,%21,%22,%23}, %24, p, 1, 1, 1;\n}"
    : "+f"(d[0]), "+f"(d[1]), "+f"(d[2]), "+f"(d[3]), "+f"(d[4]), "+f"(d[5]), "+f"(d[6]), "+f"(d[7]), "+f"(d[8]), "+f"(d[9]), "+f"(d[10]), "+f"(d[11]), "+f"(d[12]), "+f"(d[13]), "+f"(d[14]), "+f"(d[15]), "+f"(d[16]), "+f"(d[17]), "+f"(d[18]), "+f"(d[19]) : "r"(a0), "r"(a1), "r"(a2), "r"(a3), "l"(desc), "r"(sc));
}
template <> __device__ __forceinline__ void wgmma_rs<32, 1>(float* d, uint32_t a0, uint32_t a1, uint32_t a2, uint32_t a3, uint64_t desc, int sc) {
  asm volatile("{\n.reg .pred p;\nsetp.ne.b32 p, %21, 0;\n"
    "wgmma.mma_async.sync.aligned.m64n32k16.f32.bf16.bf16 {%0,%1,%2,%3,%4,%5,%6,%7,%8,%9,%10,%11,%12,%13,%14,%15}, {%16,%17,%18,%19}, %20, p, 1, 1, 1;\n}"
    : "+f"(d[0]), "+f"(d[1]), "+f"(d[2]), "+f"(d[3]), "+f"(d[4]), "+f"(d[5]), "+f"(d[6]), "+f"(d[7]), "+f"(d[8]), "+f"(d[9]), "+f"(d[10]), "+f"(d[11]), "+f"(d[12]), "+f"(d[13]), "+f"(d[14]), "+f"(d[15]) : "r"(a0), "r"(a1), "r"(a2), "r"(a3), "l"(desc), "r"(sc));
}
template <> __device__ __forceinline__ void wgmma_rs<16, 1>(float* d, uint32_t a0, uint32_t a1, uint32_t a2, uint32_t a3, uint64_t desc, int sc) {
  asm volatile("{\n.reg .pred p;\nsetp.ne.b32 p, %13, 0;\n"
    "wgmma.mma_async.sync.aligned.m64n16k16.f32.bf16.bf16 {%0,%1,%2,%3,%4,%5,%6,%7}, {%8,%9,%10,%11}, %12, p, 1, 1, 1;\n}"
    : "+f"(d[0]), "+f"(d[1]), "+f"(d[2]), "+f"(d[3]), "+f"(d[4]), "+f"(d[5]), "+f"(d[6]), "+f"(d[7]) : "r"(a0), "r"(a1), "r"(a2), "r"(a3), "l"(desc), "r"(sc));
}

__device__ __forceinline__ uint32_t pack_bf16(float lo, float hi) {
  uint32_t r; asm("cvt.rn.bf16x2.f32 %0, %1, %2;" : "=r"(r) : "f"(hi), "f"(lo)); return r;
}
__device__ __forceinline__ float bf_lo(uint32_t v) { return __uint_as_float(v << 16); }
__device__ __forceinline__ float bf_hi(uint32_t v) { return __uint_as_float(v & 0xffff0000u); }
__device__ __forceinline__ float bf_round(float x) { return bf_lo(pack_bf16(x, 0.f)); }
__device__ __forceinline__ uint32_t hmul2(uint32_t a, uint32_t b) { uint32_t r; asm("mul.rn.bf16x2 %0, %1, %2;" : "=r"(r) : "r"(a), "r"(b)); return r; }
__device__ __forceinline__ uint32_t hadd2(uint32_t a, uint32_t b) { uint32_t r; asm("add.rn.bf16x2 %0, %1, %2;" : "=r"(r) : "r"(a), "r"(b)); return r; }
__device__ __forceinline__ uint32_t hsub2(uint32_t a, uint32_t b) { uint32_t r; asm("sub.rn.bf16x2 %0, %1, %2;" : "=r"(r) : "r"(a), "r"(b)); return r; }
__device__ __forceinline__ uint32_t hfma2(uint32_t a, uint32_t b, uint32_t c) { uint32_t r; asm("fma.rn.bf16x2 %0, %1, %2, %3;" : "=r"(r) : "r"(a), "r"(b), "r"(c)); return r; }

__device__ __forceinline__ void sts16(uint32_t a, uint32_t v) { asm volatile("st.shared.b16 [%0], %1;" ::"r"(a), "h"((unsigned short)v) : "memory"); }
__device__ __forceinline__ void sts32(uint32_t a, uint32_t v) { asm volatile("st.shared.b32 [%0], %1;" ::"r"(a), "r"(v) : "memory"); }
__device__ __forceinline__ void sts64(uint32_t a, uint32_t x, uint32_t y) { asm volatile("st.shared.v2.b32 [%0], {%1,%2};" ::"r"(a), "r"(x), "r"(y) : "memory"); }
__device__ __forceinline__ void sts128(uint32_t a, uint32_t x, uint32_t y, uint32_t z, uint32_t w) {
  asm volatile("st.shared.v4.b32 [%0], {%1,%2,%3,%4};" ::"r"(a), "r"(x), "r"(y), "r"(z), "r"(w) : "memory");
}
__device__ __forceinline__ uint32_t lds32(uint32_t a) { uint32_t v; asm volatile("ld.shared.b32 %0, [%1];" : "=r"(v) : "r"(a) : "memory"); return v; }
__device__ __forceinline__ uint32_t ldf(uint32_t base, int i, int lo0, int hi0, int hf) {
  if (i < lo0 || i > hi0 + 2) return 0u;
  if (i < lo0 + 2 || i > hi0) {
    uint32_t v;
    asm volatile("{\n.reg .pred p;\nsetp.eq.b32 p, %2, %3;\nmov.b32 %0, 0;\n@p ld.shared.b32 %0, [%1];\n}" : "=r"(v) : "r"(base + i * 16), "r"(hf), "r"(i > hi0 ? 1 : 0) : "memory");
    return v;
  }
  return lds32(base + i * 16);
}
__device__ __forceinline__ uint2 lds64(uint32_t a) { uint2 v; asm volatile("ld.shared.v2.b32 {%0,%1}, [%2];" : "=r"(v.x), "=r"(v.y) : "r"(a) : "memory"); return v; }
__device__ __forceinline__ uint4 lds128(uint32_t a) {
  uint4 v; asm volatile("ld.shared.v4.b32 {%0,%1,%2,%3}, [%4];" : "=r"(v.x), "=r"(v.y), "=r"(v.z), "=r"(v.w) : "r"(a) : "memory"); return v;
}
__device__ __forceinline__ uint4 ldg128(const void* a) {
  uint4 v; asm volatile("ld.global.nc.v4.b32 {%0,%1,%2,%3}, [%4];" : "=r"(v.x), "=r"(v.y), "=r"(v.z), "=r"(v.w) : "l"(a) : "memory"); return v;
}
__device__ __forceinline__ uint2 ldg64(const void* a) {
  uint2 v; asm volatile("ld.global.nc.v2.b32 {%0,%1}, [%2];" : "=r"(v.x), "=r"(v.y) : "l"(a) : "memory"); return v;
}
__device__ __forceinline__ void ldsm4(uint32_t a, uint32_t& r0, uint32_t& r1, uint32_t& r2, uint32_t& r3) {
  asm volatile("ldmatrix.sync.aligned.m8n8.x4.shared.b16 {%0,%1,%2,%3}, [%4];" : "=r"(r0), "=r"(r1), "=r"(r2), "=r"(r3) : "r"(a) : "memory");
}
__device__ __forceinline__ void ldsm4t(uint32_t a, uint32_t& r0, uint32_t& r1, uint32_t& r2, uint32_t& r3) {
  asm volatile("ldmatrix.sync.aligned.m8n8.x4.trans.shared.b16 {%0,%1,%2,%3}, [%4];" : "=r"(r0), "=r"(r1), "=r"(r2), "=r"(r3) : "r"(a) : "memory");
}
__device__ __forceinline__ void stsm4(uint32_t a, uint32_t r0, uint32_t r1, uint32_t r2, uint32_t r3) {
  asm volatile("stmatrix.sync.aligned.m8n8.x4.shared.b16 [%0], {%1,%2,%3,%4};" ::"r"(a), "r"(r0), "r"(r1), "r"(r2), "r"(r3) : "memory");
}
__device__ __forceinline__ void stsm4t(uint32_t a, uint32_t r0, uint32_t r1, uint32_t r2, uint32_t r3) {
  asm volatile("stmatrix.sync.aligned.m8n8.x4.trans.shared.b16 [%0], {%1,%2,%3,%4};" ::"r"(a), "r"(r0), "r"(r1), "r"(r2), "r"(r3) : "memory");
}
__device__ __forceinline__ void stsm2(uint32_t a, uint32_t r0, uint32_t r1) {
  asm volatile("stmatrix.sync.aligned.m8n8.x2.shared.b16 [%0], {%1,%2};" ::"r"(a), "r"(r0), "r"(r1) : "memory");
}
__device__ __forceinline__ void stsm2t(uint32_t a, uint32_t r0, uint32_t r1) {
  asm volatile("stmatrix.sync.aligned.m8n8.x2.trans.shared.b16 [%0], {%1,%2};" ::"r"(a), "r"(r0), "r"(r1) : "memory");
}
__device__ __forceinline__ void mma16816(float* c, uint32_t a0, uint32_t a1, uint32_t a2, uint32_t a3, uint32_t b0, uint32_t b1) {
  asm("mma.sync.aligned.m16n8k16.row.col.f32.bf16.bf16.f32 {%0,%1,%2,%3}, {%4,%5,%6,%7}, {%8,%9}, {%0,%1,%2,%3};"
      : "+f"(c[0]), "+f"(c[1]), "+f"(c[2]), "+f"(c[3]) : "r"(a0), "r"(a1), "r"(a2), "r"(a3), "r"(b0), "r"(b1));
}
__device__ __forceinline__ void bar_sync(int id, int n) { asm volatile("bar.sync %0, %1;" ::"r"(id), "r"(n) : "memory"); }
__device__ __forceinline__ void wg_fence() { asm volatile("wgmma.fence.sync.aligned;" ::: "memory"); }
__device__ __forceinline__ void wg_commit() { asm volatile("wgmma.commit_group.sync.aligned;" ::: "memory"); }
__device__ __forceinline__ void wg_wait0() { asm volatile("wgmma.wait_group.sync.aligned 0;" ::: "memory"); }
__device__ __forceinline__ void wg_wait1() { asm volatile("wgmma.wait_group.sync.aligned 1;" ::: "memory"); }
__device__ __forceinline__ void fence_async() { asm volatile("fence.proxy.async.shared::cta;" ::: "memory"); }
__device__ __forceinline__ uint32_t opq(uint32_t x, uint32_t z) { uint32_t r; asm volatile("xor.b32 %0, %1, %2;" : "=r"(r) : "r"(x), "r"(z)); return r; }
__device__ __forceinline__ float opqf(float x, uint32_t z) { float r; asm volatile("add.rn.f32 %0, %1, %2;" : "=f"(r) : "f"(x), "f"(__uint_as_float(z))); return r; }
__device__ __forceinline__ uint64_t mkdesc(uint32_t addr, uint32_t lbo, uint32_t sbo) {
  return (uint64_t)((addr & 0x3FFFF) >> 4) | ((uint64_t)(lbo >> 4) << 16) | ((uint64_t)(sbo >> 4) << 32);
}
__device__ __forceinline__ uint32_t mapa(uint32_t a, uint32_t rank) {
  uint32_t r; asm("mapa.shared::cluster.u32 %0, %1, %2;" : "=r"(r) : "r"(a), "r"(rank)); return r;
}
__device__ __forceinline__ void mbar_init_expect(uint32_t bar, uint32_t bytes) {
  asm volatile("mbarrier.init.shared::cta.b64 [%0], 1;" ::"r"(bar) : "memory");
  asm volatile("mbarrier.arrive.expect_tx.shared::cta.b64 _, [%0], %1;" ::"r"(bar), "r"(bytes) : "memory");
}
__device__ __forceinline__ void mbar_wait(uint32_t bar) {
#pragma unroll 1
  for (int it = 0; it < (1 << 22); it++) {
    uint32_t ok;
    asm volatile("{\n.reg .pred p;\nmbarrier.try_wait.parity.acquire.cluster.shared::cta.b64 p, [%1], 0;\nselp.u32 %0, 1, 0, p;\n}"
                 : "=r"(ok) : "r"(bar) : "memory");
    if (ok) return;
  }
  __trap();
}
__device__ __forceinline__ void st_async4(uint32_t a, uint32_t bar, uint32_t x, uint32_t y, uint32_t z, uint32_t w) {
  asm volatile("st.async.weak.shared::cluster.mbarrier::complete_tx::bytes.v4.b32 [%0], {%2,%3,%4,%5}, [%1];"
               ::"r"(a), "r"(bar), "r"(x), "r"(y), "r"(z), "r"(w) : "memory");
}

struct cf { float re, im; };
__device__ __forceinline__ cf cmul(cf a, cf b) { return {fmaf(a.re, b.re, -a.im * b.im), fmaf(a.re, b.im, a.im * b.re)}; }
__device__ __forceinline__ cf csq(cf a) { return {fmaf(a.re, a.re, -a.im * a.im), (a.re + a.re) * a.im}; }
__device__ __forceinline__ cf cexp_p(float xl, float y, float p) {
  float mag; asm("ex2.approx.ftz.f32 %0, %1;" : "=f"(mag) : "f"(xl * p));
  const float th = y * p;
  const float k = __fadd_rn(fmaf(th, 0.15915494309189535f, 12582912.f), -12582912.f);
  float r = fmaf(k, -6.2831854820251465f, th);
  r = fmaf(k, 1.7484555314695172e-07f, r);
  return {mag * __cosf(r), mag * __sinf(r)};
}
__device__ __forceinline__ uint32_t ysw(int c) { return (uint32_t)(c ^ ((c >> 3) & 3)) * 16u; }

#define CMUL2(OR, OI, xr, xi, yr, yi, nyi) do { OR = hfma2(xr, yr, hmul2(xi, nyi)); OI = hfma2(xr, yi, hmul2(xi, yr)); } while (0)

__device__ __forceinline__ uint32_t gate_slow(const __nv_bfloat16* u, const __nv_bfloat16* gw, int row) {
  float s = 0.f;
  const uint32_t* xr = (const uint32_t*)(u + (size_t)row * D);
  const uint32_t* wr = (const uint32_t*)gw;
#pragma unroll 1
  for (int j = 0; j < D / 2; j++) { const uint32_t pr = hmul2(xr[j], wr[j]); s += bf_lo(pr); s += bf_hi(pr); }
  s = bf_round(s);
  return pack_bf16(1.f / (1.f + expf(-s)), 0.f);
}

__device__ __forceinline__ uint2 gate_ld(int x) {
  uint2 gv;
  asm volatile("ld.relaxed.gpu.global.v2.u32 {%0,%1}, [%2];" : "=r"(gv.x), "=r"(gv.y) : "l"(g_gate + x * 2) : "memory");
  return gv;
}
__device__ __noinline__ uint32_t gate_poll(const Params* pp, int x, uint32_t tag) {
  uint2 gv;
#pragma unroll 1
  for (int spins = 0; spins < (1 << 16); spins++) {
    gv = gate_ld(x);
    if ((gv.x >> 16) == tag && (gv.y >> 16) == tag) return __byte_perm(gv.x, gv.y, 0x5410);
  }
  return __byte_perm(gate_slow(pp->u, pp->gw, x * 2), gate_slow(pp->u, pp->gw, x * 2 + 1), 0x5410);
}
__device__ __forceinline__ uint32_t gate_fin(const Params& p, uint2 gv, int x, uint32_t tag) {
  if ((gv.x >> 16) == tag && (gv.y >> 16) == tag) return __byte_perm(gv.x, gv.y, 0x5410);
  return gate_poll(&p, x, tag);
}

__device__ __forceinline__ void ld4ch(uint32_t* v, uint32_t addr) {
#pragma unroll
  for (int k = 0; k < 4; k++) v[k] = lds32(addr + k * CH_BYTES);
}
__device__ __forceinline__ void skip_terms(uint32_t* ua, uint32_t* ub, uint32_t sb, int x, uint2 dA, uint2 dB) {
  const int c = x >> 2;
  uint32_t uu[4];
  ld4ch(uu, sb + CH_OFF + (x & 3) * 4 + U_OFF + (c & 3) * U_CS + (63 - (c >> 2)) * 16);
#pragma unroll
  for (int k = 0; k < 4; k++) {
    ua[k] = hmul2(uu[k], __byte_perm((k & 2) ? dA.y : dA.x, 0, (k & 1) ? 0x3232 : 0x1010));
    ub[k] = hmul2(uu[k], __byte_perm((k & 2) ? dB.y : dB.x, 0, (k & 1) ? 0x3232 : 0x1010));
  }
}
__device__ __forceinline__ uint4 mix(const uint32_t* a, const uint32_t* b, const uint32_t* ua, const uint32_t* ub, uint32_t g2) {
  const uint32_t h2 = hsub2(0x3f803f80u, g2);
  uint32_t o[4];
#pragma unroll
  for (int k = 0; k < 4; k++) o[k] = hadd2(hmul2(g2, hadd2(a[k], ua[k])), hmul2(h2, hadd2(b[k], ub[k])));
  return make_uint4(__byte_perm(o[0], o[1], 0x5410), __byte_perm(o[2], o[3], 0x5410), __byte_perm(o[0], o[1], 0x7632), __byte_perm(o[2], o[3], 0x7632));
}
__device__ __forceinline__ void send_box(uint32_t sb, int slot, int wtid, uint32_t rank, uint4 r) {
  st_async4(mapa(sb + XIN_OFF + slot * 2048 + wtid * 16, rank ^ 1), mapa(sb + B_X + slot * 8, rank ^ 1), r.x, r.y, r.z, r.w);
}
__device__ __forceinline__ void merge_rows(uint32_t st, uint32_t rank, uint4 r, uint4 q) {
  const uint4 lo = rank ? q : r, hi = rank ? r : q;
  sts128(st, lo.x, lo.y, hi.x, hi.y); sts128(st + 2048, lo.z, lo.w, hi.z, hi.w);
}
__device__ __forceinline__ void merge_box(uint32_t sb, const CUtensorMap* tm_out, int slot, int wtid, uint32_t rank, int oc0, uint4 r, int barid) {
  const uint32_t st = sb + RAW_OFF + slot * 4096 + wtid * 16;
  mbar_wait(sb + B_X + slot * 8);
  merge_rows(st, rank, r, lds128(sb + XIN_OFF + slot * 2048 + wtid * 16));
  fence_async();
  bar_sync(barid, 128);
  if (wtid == 0) {
    asm volatile("cp.async.bulk.tensor.3d.global.shared::cta.bulk_group [%0, {%2, %3, %4}], [%1];"
                 ::"l"(tm_out), "r"(sb + RAW_OFF + slot * 4096), "r"(oc0), "r"((2 * slot + (int)rank) * 128), "r"(0) : "memory");
    asm volatile("cp.async.bulk.commit_group;" ::: "memory");
  }
}

__device__ __forceinline__ uint32_t band2(int e, int lo, int hi) {
  uint32_t r = ((uint32_t)(e - lo) <= (uint32_t)(hi - lo) ? 0x3f80u : 0u) | ((uint32_t)(e - 1 - lo) <= (uint32_t)(hi - lo) ? 0x3f800000u : 0u);
  asm volatile("" : "+r"(r));
  return r;
}

__device__ __forceinline__ void stage_done(uint32_t sb, int stage, int lane) {
  __syncwarp();
  if (lane == 0) asm volatile("mbarrier.arrive.shared::cta.b64 _, [%0];" ::"r"(sb + B_ST + 8 * stage) : "memory");
}
#define PK2(v, i) pack_bf16(v[i], v[(i) + 1])

__device__ __forceinline__ void conv_dense(uint32_t sb, uint32_t cb, uint32_t zz) {
  const int lane = threadIdx.x & 31, wq = (threadIdx.x >> 5) & 3, br = wq >> 1, hf = wq & 1, g = lane >> 2, t = lane & 3;
  const uint32_t rb = cb + R_OFF + br * R_BR;
  const int eo = 16 * hf + g - 2 * t;
  const int x0 = RD_X0 - (eo + 536);
  const uint32_t fa = rb + ((g & 1) ? 2 * x0 : RD_CS + 2 * x0 + 2);
  const uint64_t ub = mkdesc(cb + U_OFF, U_CS, 128);
  const uint32_t yd = cb + Y0_OFF + br * 4096 + ysw(4 * (63 - 8 * (lane >> 4) - (lane & 7)) + 2 * hf + ((lane >> 3) & 1));
  uint32_t A[2][4][4];
  float e64[32], e56[28], e48[24];
  auto loadA = [&](int j) {
#pragma unroll
    for (int k = 0; k < 4; k++) {
      const int s = 34 - 4 * j - k;
      if (s >= 0) {
        if (k == 0 && j == 0) A[0][0][2] = ldf(fa, 2 * s + 2, 2, 67, hf);
        A[j & 1][k][0] = ldf(fa, 2 * s + 1, 2, 67, hf);
        A[j & 1][k][1] = ldf(fa, 2 * s, 2, 67, hf);
      }
    }
#pragma unroll
    for (int k = 0; k < 4; k++) {
      if (34 - 4 * j - k >= 0) {
        A[j & 1][k][3] = A[j & 1][k][0];
        if (k) A[j & 1][k][2] = A[j & 1][k - 1][1];
        else if (j) A[j & 1][0][2] = A[(j - 1) & 1][3][1];
      }
    }
  };
  loadA(0); loadA(1);
#pragma unroll
  for (int j = 0; j < 9; j++) {
    if (j == 4) {
      wg_wait0();
      stsm2t(yd - 7 * 512, PK2(e64, 28), PK2(e64, 30));
#pragma unroll
      for (int i = 0; i < 28; i++) e56[i] = FCPY(e64, i);
      stage_done(sb, 0, lane);
    }
    if (j == 8) {
      wg_wait0();
      stsm2t(yd - 6 * 512, PK2(e56, 24), PK2(e56, 26));
#pragma unroll
      for (int i = 0; i < 24; i++) e48[i] = FCPY(e56, i);
      stage_done(sb, 1, lane);
    }
    wg_fence();
#pragma unroll
    for (int k = 0; k < 4; k++) {
      const int s = 34 - 4 * j - k;
      if (s >= 0) {
        const int o = 2 * s - 66 + 128;
        const int cc = o & 3, rs = (o >> 2) - 32;
        const uint64_t desc = ub + (uint64_t)((cc * U_CS - rs * 16) >> 4);
        const uint32_t* a = A[j & 1][k];
        if (j < 4) wgmma_rs<64, 0>(e64, a[0], a[1], a[2], a[3], desc, s != 34);
        else if (j < 8) wgmma_rs<56, 0>(e56, a[0], a[1], a[2], a[3], desc, 1);
        else wgmma_rs<48, 0>(e48, a[0], a[1], a[2], a[3], desc, 1);
      }
    }
    wg_commit();
    if (j >= 1 && j < 8) { wg_wait1(); loadA(j + 1); }
  }
  wg_wait0();
#pragma unroll
  for (int i = 0; i < 6; i += 2) stsm4t(yd - i * 512, PK2(e48, 4 * i), PK2(e48, 4 * i + 2), PK2(e48, 4 * i + 4), PK2(e48, 4 * i + 6));
}

__device__ __noinline__ unsigned int gate_rows(const Params* pp, int grow, int step, int rend) {
  const __nv_bfloat16 *u = pp->u, *gw = pp->gw;
  const int lane = threadIdx.x & 31;
  uint4 nx[4][2];
#pragma unroll
  for (int i = 0; i < 4; i++) {
    nx[i][0] = ldg128(u + (size_t)(grow + i) * D + lane * 8);
    nx[i][1] = ldg128(u + (size_t)(grow + i) * D + 256 + lane * 8);
  }
  const uint4 gw0 = ldg128(gw + lane * 8), gw1 = ldg128(gw + 256 + lane * 8);
  const uint32_t ws[8] = {gw0.x, gw0.y, gw0.z, gw0.w, gw1.x, gw1.y, gw1.z, gw1.w};
  unsigned int epoch;
  asm volatile("ld.relaxed.gpu.global.u32 %0, [%1];" : "=r"(epoch) : "l"(&g_epoch) : "memory");
#pragma unroll 1
  for (; grow < rend; grow += step) {
    const int nrow = (grow + step < rend) ? grow + step : grow;
    float c[2][4];
#pragma unroll
    for (int i = 0; i < 2; i++) {
      const uint4 *x = nx[2 * i], *y = nx[2 * i + 1];
      const uint32_t xs[8] = {x[0].x, x[0].y, x[0].z, x[0].w, x[1].x, x[1].y, x[1].z, x[1].w};
      const uint32_t ys[8] = {y[0].x, y[0].y, y[0].z, y[0].w, y[1].x, y[1].y, y[1].z, y[1].w};
      uint32_t px[8], py[8];
#pragma unroll
      for (int j = 0; j < 8; j++) { px[j] = hmul2(xs[j], ws[j]); py[j] = hmul2(ys[j], ws[j]); }
      if (nrow != grow) {
#pragma unroll
        for (int k = 2 * i; k < 2 * i + 2; k++) {
          nx[k][0] = ldg128(u + (size_t)(nrow + k) * D + lane * 8);
          nx[k][1] = ldg128(u + (size_t)(nrow + k) * D + 256 + lane * 8);
        }
      }
      c[i][0] = c[i][1] = c[i][2] = c[i][3] = 0.f;
#pragma unroll
      for (int j = 0; j < 8; j += 2) mma16816(c[i], px[j], py[j], px[j + 1], py[j + 1], 0x3f803f80u, 0x3f803f80u);
    }
    float s = (lane & 2) ? ((lane & 1) ? c[1][2] : c[1][0]) : ((lane & 1) ? c[0][2] : c[0][0]);
#pragma unroll
    for (int o = 4; o < 32; o <<= 1) s += __shfl_xor_sync(0xffffffffu, s, o);
    s = bf_round(s);
    const float gv = 1.f / (1.f + expf(-s));
    const uint32_t w = ((epoch + 1) << 16) | (pack_bf16(gv, 0.f) & 0xffffu);
    if (lane < 4) asm volatile("st.relaxed.gpu.global.u32 [%0], %1;" ::"l"(&g_gate[grow + lane]), "r"(w) : "memory");
  }
  return epoch;
}
#define GW 1
constexpr int GSPLIT = L - 4 * GW * NCTA;
__device__ __noinline__ void gate_cta(const Params* pp) {
  const unsigned int epoch = gate_rows(pp, (blockIdx.x * 20 + (threadIdx.x >> 5)) * 4, 80 * NGATE, GSPLIT);
  __syncthreads();
  if (threadIdx.x == 0 && atomicAdd(&g_ticket, 1u) == NCTA + NGATE - 1) { g_ticket = 0; g_epoch = epoch + 1; }
}

__global__ void __cluster_dims__(2, 1, 1) __launch_bounds__(640, 1)
ssm_kernel(const __grid_constant__ Params p, const __grid_constant__ CUtensorMap tm_in, const __grid_constant__ CUtensorMap tm_out) {
  extern __shared__ __align__(1024) unsigned char smem_raw[];
  const uint32_t sb = (uint32_t)__cvta_generic_to_shared(smem_raw);
  const int tid = threadIdx.x, lane = tid & 31;
  const int warp = __shfl_sync(0xffffffffu, tid >> 5, 0);
  const int ch = warp >> 2, wq = warp & 3, br = wq >> 1, hf = wq & 1;
  const int g = lane >> 2, t = lane & 3;
  if (__builtin_expect(blockIdx.x < NGATE, 0)) { gate_cta(&p); return; }
  const int bid = blockIdx.x - NGATE;
  const uint32_t rank = blockIdx.x & 1;
  const uint32_t cb = sb + CH_OFF + ch * CH_BYTES;
  const int wtid = tid & 127;
  const int oc0 = (bid >> 1) * 8;
  STAMP(0); GT(0);

  if (warp >= 16) {
    if (wtid == 0) {
      mbar_init_expect(sb + B_RAW, 32768);
#pragma unroll
      for (int i = 0; i < 4; i++) mbar_init_expect(sb + B_X + 8 * i, 2048);
      asm volatile("mbarrier.init.shared::cta.b64 [%0], 128;" ::"r"(sb + B_U) : "memory");
      asm volatile("mbarrier.init.shared::cta.b64 [%0], 128;" ::"r"(sb + B_W) : "memory");
#pragma unroll
      for (int i = 0; i < 7; i++) asm volatile("mbarrier.init.shared::cta.b64 [%0], 16;" ::"r"(sb + B_ST + 8 * i) : "memory");
      asm volatile("fence.mbarrier_init.release.cluster;" ::: "memory");
      asm volatile("fence.proxy.async.shared::cta;" ::: "memory");
    }
    __syncwarp();
    asm volatile("barrier.cluster.arrive.relaxed.aligned;" ::: "memory");
    if (wq >= 4 - GW) gate_rows(&p, GSPLIT + (bid * GW + 3 - wq) * 4, L, L);
    unsigned int epoch;
    asm volatile("ld.relaxed.gpu.global.u32 %0, [%1];" : "=r"(epoch) : "l"(&g_epoch) : "memory");
    asm volatile("barrier.cluster.wait.aligned;" ::: "memory");
    if (wtid == 0) {
      asm volatile("cp.async.bulk.tensor.5d.shared::cluster.global.mbarrier::complete_tx::bytes.multicast::cluster [%0], [%1, {%3, %4, %4, %4, %5}], [%2], %6;"
                   ::"r"(sb + RAW_OFF + rank * 16384), "l"(&tm_in), "r"(sb + B_RAW), "r"(oc0), "r"(0), "r"((int)rank * 32), "h"((unsigned short)3) : "memory");
    }
    sts128(sb + CH_OFF + wq * CH_BYTES + U_OFF + (lane >> 3) * U_CS + (64 + (lane & 7)) * 16, 0, 0, 0, 0);
    const uint2 dA = ldg64(p.A_D + bid * 4), dB = ldg64(p.B_D + bid * 4);
    uint32_t BA[3][4], BB[4][4];
    {
      const int l1 = br ? 3 : 6, h1 = br ? 5 : 10, l2 = br ? 5 : 12, h2 = br ? 11 : 20;
#pragma unroll
      for (int i = 0; i < 4; i++) {
        const int e = 16 * hf + g - 2 * t + 32 - 16 * i;
        BB[i][0] = band2(e, l2, h2); BB[i][1] = band2(e + 8, l2, h2); BB[i][2] = band2(e - 8, l2, h2); BB[i][3] = BB[i][0];
        if (i) { BA[i - 1][0] = band2(e, l1, h1); BA[i - 1][1] = band2(e + 8, l1, h1); BA[i - 1][2] = band2(e - 8, l1, h1); BA[i - 1][3] = BA[i - 1][0]; }
      }
    }
    const uint32_t tag = (epoch + 1) & 0xffffu;
    if (wtid == 0) { sts32(sb + TAG_OFF, tag); sts128(sb + DSK_OFF, dA.x, dA.y, dB.x, dB.y); }
    STAMP(3);
    mbar_wait(sb + B_RAW);
    STAMP(4);
    {
      const uint32_t dst = sb + CH_OFF + (g & 3) * CH_BYTES + U_OFF + t * U_CS + (63 - wq * 16) * 16;
#pragma unroll
      for (int h = 0; h < 2; h++) {
        uint32_t r[8][4];
#pragma unroll
        for (int i = 0; i < 8; i++) ldsm4t(sb + RAW_OFF + (wq * 16 + h * 8 + i) * 512 + lane * 16, r[i][0], r[i][1], r[i][2], r[i][3]);
        if ((uint32_t)(g >> 2) == rank) {
#pragma unroll
          for (int i = 0; i < 8; i++) sts128(dst - (h * 8 + i) * 16, r[i][0], r[i][1], r[i][2], r[i][3]);
        }
      }
    }
    fence_async();
    asm volatile("mbarrier.arrive.shared::cta.b64 _, [%0];" ::"r"(sb + B_U) : "memory");
    bar_sync(5, 128);
    STAMP(5);
    {
      const int mrow = lane & 7, mi = lane >> 3;
      const uint64_t ub0 = mkdesc(sb + CH_OFF + U_OFF, U_CS, 128);
      uint32_t wa, wb;
      {
        const int c = 4 * (47 - 8 * (mi >> 1) - mrow) + 2 * hf + (mi & 1);
        wa = sb + CH_OFF + (br ? W3_OFF : W5_OFF) + (5 - (c >> 5)) * 576 + ((c & 31) >> 3) * 144 + (c & 7) * 16;
        const int c2 = c - 64, pp = c2 >> 1;
        wb = sb + CH_OFF + (br ? W7_OFF : W9_OFF) + (1 - (pp >> 5)) * 1152 + (c2 & 1) * 576 + ((pp & 31) >> 3) * 144 + (pp & 7) * 16;
      }
      {
        float w1[24];
#pragma unroll
        for (int i = 0; i < 24; i++) w1[i] = 0.f;
#pragma unroll 1
        for (int k = 0; k < 4; k++) {
          wg_fence();
#pragma unroll
          for (int i = 0; i < 3; i++)
            wgmma_rs<48, 0>(w1, BA[i][0], BA[i][1], BA[i][2], BA[i][3],
                            ub0 + (uint64_t)((k * CH_BYTES + ((2 * i + 2) & 3) * U_CS + (16 + (i == 0)) * 16) >> 4), i);
          wg_commit();
          wg_wait0();
#pragma unroll
          for (int i = 0; i < 3; i++) stsm4t(wa + k * CH_BYTES + i * 1152, PK2(w1, 8 * i), PK2(w1, 8 * i + 2), PK2(w1, 8 * i + 4), PK2(w1, 8 * i + 6));
        }
      }
      {
        float w2[2][16];
#pragma unroll
        for (int i = 0; i < 16; i++) { w2[0][i] = 0.f; w2[1][i] = 0.f; }
#pragma unroll 1
        for (int kp = 0; kp < 2; kp++) {
          wg_fence();
#pragma unroll
          for (int k = 0; k < 2; k++)
#pragma unroll
            for (int i = 0; i < 4; i++)
              wgmma_rs<32, 0>(w2[k], BB[i][0], BB[i][1], BB[i][2], BB[i][3],
                              ub0 + (uint64_t)(((2 * kp + k) * CH_BYTES + ((2 * i) & 3) * U_CS + (32 + (i < 2)) * 16) >> 4), i);
          wg_commit();
          wg_wait0();
#pragma unroll
          for (int k = 0; k < 2; k++)
#pragma unroll
            for (int i = 0; i < 2; i++)
              stsm4t(wb + (2 * kp + k) * CH_BYTES + i * 1152, PK2(w2[k], 8 * i), PK2(w2[k], 8 * i + 2), PK2(w2[k], 8 * i + 4), PK2(w2[k], 8 * i + 6));
        }
      }
    }
    fence_async();
    asm volatile("mbarrier.arrive.shared::cta.b64 _, [%0];" ::"r"(sb + B_W) : "memory");
    STAMP(7);
    {
      const int bsel = (int)rank ^ br ^ 1, xl = wtid & 63;
      uint2 gl[4];
      uint32_t ua[4][4], ub[4][4];
#pragma unroll
      for (int i = 0; i < 4; i++) skip_terms(ua[i], ub[i], sb, (2 * (i >> 1) + bsel) * 128 + (i & 1) * 64 + xl, dA, dB);
      const uint32_t yo = sb + CH_OFF + (xl & 3) * 4 + ysw(xl >> 2) + bsel * 512;
#pragma unroll
      for (int i = 0; i < 2; i++) gl[i] = gate_ld(bsel * 128 + i * 64 + xl);
#pragma unroll
      for (int slot = 0; slot < 2; slot++) {
        const int box = 2 * slot + bsel;
        uint32_t g2[2], ya[2][4], yb[2][4];
#pragma unroll
        for (int h = 0; h < 2; h++) g2[h] = gate_fin(p, gl[2 * slot + h], box * 128 + h * 64 + xl, tag);
        mbar_wait(sb + B_ST + 8 * box);
        STAMP(8 + slot);
        if (slot == 0) { gl[2] = gate_ld((2 + bsel) * 128 + xl); gl[3] = gate_ld((2 + bsel) * 128 + 64 + xl); }
#pragma unroll
        for (int h = 0; h < 2; h++) {
          const uint32_t yh = (yo ^ (h * 32)) + h * 256 + slot * 1024;
          ld4ch(ya[h], yh + Y0_OFF); ld4ch(yb[h], yh + Y0_OFF + 4096);
          if (slot) {
            uint32_t a2[4], b2[4];
            ld4ch(a2, yh + Y2_OFF - 1024); ld4ch(b2, yh + Y2_OFF - 1024 + 3072);
#pragma unroll
            for (int k = 0; k < 4; k++) { ya[h][k] = hadd2(ya[h][k], a2[k]); yb[h][k] = hadd2(yb[h][k], b2[k]); }
          }
        }
        const uint4 r0 = mix(ya[0], yb[0], ua[2 * slot], ub[2 * slot], g2[0]), r1 = mix(ya[1], yb[1], ua[2 * slot + 1], ub[2 * slot + 1], g2[1]);
        if (br == 0) { send_box(sb, slot, xl, rank, r0); send_box(sb, slot, xl + 64, rank, r1); }
        else {
          const uint32_t st = sb + RAW_OFF + slot * 4096 + xl * 16, xin = sb + XIN_OFF + slot * 2048 + xl * 16;
          mbar_wait(sb + B_X + slot * 8);
          const uint4 q0 = lds128(xin), q1 = lds128(xin + 1024);
          merge_rows(st, rank, r0, q0); merge_rows(st + 1024, rank, r1, q1);
          fence_async();
          bar_sync(6, 64);
          if (xl == 0) {
            asm volatile("cp.async.bulk.tensor.3d.global.shared::cta.bulk_group [%0, {%2, %3, %4}], [%1];"
                         ::"l"(&tm_out), "r"(sb + RAW_OFF + slot * 4096), "r"(oc0), "r"(box * 128), "r"(0) : "memory");
            asm volatile("cp.async.bulk.commit_group;" ::: "memory");
          }
        }
        STAMP(10 + slot);
      }
    }
    if (wtid == 0 && atomicAdd(&g_ticket, 1u) == NCTA + NGATE - 1) { g_ticket = 0; g_epoch = epoch + 1; }
    if (wtid == 64) asm volatile("cp.async.bulk.wait_group.read 0;" ::: "memory");
    STAMP(15);
    return;
  }
  asm volatile("barrier.cluster.arrive.relaxed.aligned;" ::: "memory");

  const int moff = (bid * 4 + (tid >> 7)) * NM + (tid & 63) * 2;
  const int brt = (tid >> 6) & 1;
  const __nv_bfloat16* const* tp = p.t + (brt ? 0 : 6);
  const uint32_t q0 = *(const uint32_t*)(tp[0] + moff), q1 = *(const uint32_t*)(tp[1] + moff);
  const uint32_t q2 = *(const uint32_t*)(tp[2] + moff), q3 = *(const uint32_t*)(tp[3] + moff);
  const uint2 ldt4 = *(const uint2*)(tp[4] + bid * 4);
  const uint32_t q4 = *(const uint32_t*)(tp[brt ? 2 : 5] + moff), q5 = *(const uint32_t*)(tp[brt ? 3 : 6] + moff);

  for (int i = wtid & 63; i < R_BR / 16; i += 64) sts128(cb + R_OFF + br * R_BR + i * 16, 0, 0, 0, 0);
  STAMP(1);

  float acc[5][4];
  float k2048 = 0.f;
  const uint32_t scr = cb + Y0_OFF + wq * SCR_BYTES;
  const uint32_t scr2 = sb + SC2_OFF + warp * 640;
  {
    const uint32_t ldt2 = (ch & 2) ? ldt4.y : ldt4.x;
    const float dt = bf_round(expf((ch & 1) ? bf_hi(ldt2) : bf_lo(ldt2)));
#pragma unroll
    for (int i = 0; i < 5; i++) acc[i][0] = acc[i][1] = acc[i][2] = acc[i][3] = 0.f;
    STAMP(2);
    const uint32_t tb = scr + lane * 16;
    const uint32_t tb1 = tb + hf * 512, tb2 = tb + (hf ^ 1) * 512;
    const uint32_t ta = scr + (lane >> 3) * 512 + (lane & 7) * 16;
    const uint32_t tc = ((lane & 8) ? scr2 : scr + 4096) + (lane >> 4) * 128 + (lane & 7) * 16;
    const uint32_t tm = scr2 + 512 + ((lane >> 3) & 1) * 64 + (lane >> 4) * 16;
#pragma unroll 1
    for (int r = 0; r < 2; r++) {
      cf c, z1, z128;
      {
        const uint32_t sh = r ? 0x3244u : 0x1044u;
        float v0 = __uint_as_float(__byte_perm(q0, 0, sh));
        const float v1 = __uint_as_float(__byte_perm(q1, 0, sh)), v2 = __uint_as_float(__byte_perm(q2, 0, sh)), v3 = __uint_as_float(__byte_perm(q3, 0, sh));
        if (br == 0) { c = cmul(cf{v2, v3}, cf{dt * __uint_as_float(__byte_perm(q4, 0, sh)), dt * __uint_as_float(__byte_perm(q5, 0, sh))}); }
        else { v0 = -bf_round(expf(v0)); c = cf{2.f * dt * v2, 2.f * dt * v3}; }
        const float xl = (dt * v0) * 1.4426950408889634f, y = dt * v1;
        z1 = cexp_p(xl, y, 1.f); z128 = cexp_p(xl, y, 128.f);
      }
      const cf z2 = csq(z1), z4 = csq(z2), z8 = csq(z4);
      const cf w8 = {z8.re, -z8.im};
      const cf z16 = csq(w8), z24 = cmul(z16, w8), z32 = csq(z16), z40 = cmul(z32, w8), z48 = csq(z24), z56 = cmul(z32, z24), z64 = csq(z32);
      const cf z256 = csq(z128), z512 = csq(z256), z1024 = csq(z512), z2048 = csq(z1024);
      {
        k2048 += fmaf(c.re, z2048.re, -c.im * z2048.im);
        if (r) {
#pragma unroll
          for (int o = 16; o; o >>= 1) k2048 += __shfl_xor_sync(0xffffffffu, k2048, o);
        }
      }
      __syncwarp();
      {
        uint32_t xr[4] = {pack_bf16(1.f, z8.re), pack_bf16(z16.re, z24.re), pack_bf16(z32.re, z40.re), pack_bf16(z48.re, z56.re)};
        uint32_t xi[4] = {pack_bf16(0.f, w8.im), pack_bf16(z16.im, z24.im), pack_bf16(z32.im, z40.im), pack_bf16(z48.im, z56.im)};
        sts128(tb1, xr[0], xr[1], xr[2], xr[3]);
        sts128(tb1 + 1024, xi[0], xi[1], xi[2], xi[3]);
        const uint32_t yr = pack_bf16(z64.re, z64.re), yi = pack_bf16(z64.im, z64.im), nyi = yi ^ 0x80008000u;
        uint32_t o[4], q[4];
#pragma unroll
        for (int i = 0; i < 4; i++) CMUL2(o[i], q[i], xr[i], xi[i], yr, yi, nyi);
        sts128(tb2, o[0], o[1], o[2], o[3]);
        sts128(tb2 + 1024, q[0], q[1], q[2], q[3]);
      }
      {
        const cf h1 = cmul(c, z128), h2 = cmul(c, z256), h3 = cmul(h1, z256), h4 = cmul(c, z512), h5 = cmul(h1, z512), h6 = cmul(h2, z512), h7 = cmul(h3, z512);
        const cf e1 = cmul(c, z1), e2 = cmul(c, z2), e3 = cmul(e1, z2), e129 = cmul(h1, z1), e130 = cmul(h1, z2), e131 = cmul(e129, z2);
        const cf e258 = cmul(h2, z2), e386 = cmul(h3, z2);
        const uint32_t pr0 = pack_bf16(c.re, e1.re), pr2 = pack_bf16(h1.re, e129.re), pi0 = pack_bf16(c.im, e1.im), pi2 = pack_bf16(h1.im, e129.im);
        sts128(tb + 4 * 512, pr0, pack_bf16(e2.re, e3.re), pr2, pack_bf16(e130.re, e131.re));
        sts128(tb + 5 * 512, pi0, pack_bf16(e2.im, e3.im), pi2, pack_bf16(e130.im, e131.im));
        uint32_t xr[4] = {pack_bf16(h2.re, e258.re), pack_bf16(h3.re, e386.re), pack_bf16(h4.re, h5.re), pack_bf16(h6.re, h7.re)};
        uint32_t xi[4] = {pack_bf16(h2.im, e258.im), pack_bf16(h3.im, e386.im), pack_bf16(h4.im, h5.im), pack_bf16(h6.im, h7.im)};
        sts128(tb + 6 * 512, xr[0], xr[1], xr[2], xr[3]);
        sts128(tb + 7 * 512, xi[0], xi[1], xi[2], xi[3]);
        xr[1] = __byte_perm(xr[0], xr[1], 0x5410); xi[1] = __byte_perm(xi[0], xi[1], 0x5410);
        xr[0] = __byte_perm(pr0, pr2, 0x5410); xi[0] = __byte_perm(pi0, pi2, 0x5410);
        const uint32_t yr = pack_bf16(z1024.re, z1024.re), yi = pack_bf16(z1024.im, z1024.im), nyi = yi ^ 0x80008000u;
        uint32_t o[4], q[4];
#pragma unroll
        for (int i = 0; i < 4; i++) CMUL2(o[i], q[i], xr[i], xi[i], yr, yi, nyi);
        sts128(tb + 8 * 512, o[0], o[1], o[2], o[3]);
        sts128(scr2 + lane * 16, q[0], q[1], q[2], q[3]);
        const uint32_t m4 = pack_bf16(z4.re, z4.im);
        sts16(scr2 + 512 + lane * 2, m4); sts16(scr2 + 576 + lane * 2, m4 >> 16);
      }
      __syncwarp();
#pragma unroll
      for (int kp = 0; kp < 2; kp++) {
        uint32_t rr[2], ri[2], yr[2], yi[2];
        ldsm4t(tc + kp * 256, rr[0], ri[0], rr[1], ri[1]);
        ldsm4(tm + kp * 32, yr[0], yi[0], yr[1], yi[1]);
#pragma unroll
        for (int k2 = 0; k2 < 2; k2++) {
          const int kk = kp * 2 + k2;
          uint32_t a0, a1, a2, a3, pr, pi, qr, qi, xr, xi;
          ldsm4t(ta + kk * 128, a0, a1, a2, a3);
          ldsm4t(ta + 2048 + kk * 128, pr, pi, qr, qi);
          const uint32_t nyi = yi[k2] ^ 0x80008000u;
          mma16816(acc[0], a0, a1, a2, a3, pr, pi);
          mma16816(acc[2], a0, a1, a2, a3, qr, qi);
          mma16816(acc[4], a0, a1, a2, a3, rr[k2], ri[k2]);
          CMUL2(xr, xi, pr, pi, yr[k2], yi[k2], nyi);
          mma16816(acc[1], a0, a1, a2, a3, xr, xi);
          CMUL2(xr, xi, qr, qi, yr[k2], yi[k2], nyi);
          mma16816(acc[3], a0, a1, a2, a3, xr, xi);
        }
      }
    }
  }
  STAMP(3);
  __syncwarp();
  {
    const uint32_t xs = scr + lane * 16;
#define OTH(i, k) __float_as_uint(acc[i][2 + (k)])
    sts128(xs, OTH(0, 0), OTH(0, 1), OTH(1, 0), OTH(1, 1));
    sts128(xs + 512, OTH(2, 0), OTH(2, 1), OTH(3, 0), OTH(3, 1));
    sts64(scr + 1024 + lane * 8, OTH(4, 0), OTH(4, 1));
    if (lane == 0) sts32(scr + 1280, __float_as_uint(k2048));
#undef OTH
  }

  bar_sync(7 + (warp >> 1), 64);
  STAMP(4);
  {
    const uint32_t xo = cb + Y0_OFF + (wq ^ 1) * SCR_BYTES + lane * 16;
    const uint4 o0 = lds128(xo), o1 = lds128(xo + 512);
    const uint2 o2 = lds64(xo + 1024 - lane * 8);
    const uint32_t rb = cb + R_OFF + br * R_BR;
#define OWN(i, k) acc[i][k]
    const uint32_t vP = pack_bf16(OWN(0, 1) + __uint_as_float(o0.y), OWN(0, 0) + __uint_as_float(o0.x));
    const uint32_t vP4 = pack_bf16(OWN(1, 1) + __uint_as_float(o0.w), OWN(1, 0) + __uint_as_float(o0.z));
    const uint32_t vQ = pack_bf16(OWN(2, 1) + __uint_as_float(o1.y), OWN(2, 0) + __uint_as_float(o1.x));
    const uint32_t vQ4 = pack_bf16(OWN(3, 1) + __uint_as_float(o1.w), OWN(3, 0) + __uint_as_float(o1.z));
    const uint32_t vR = pack_bf16(OWN(4, 1) + __uint_as_float(o2.y), OWN(4, 0) + __uint_as_float(o2.x));
#undef OWN
    const int j = g + 8 * hf;
    {
      const int a = 2 * (t & 1) + 64 * (t & 2) + 8 * j;
      const uint32_t ad = rb + 2 * (RD_X0 - 1 - a);
      const uint32_t a1 = (t & 2) ? ad - 8 : ad, a2 = (t & 2) ? ad : ad - 8;
      const uint32_t w1 = (t & 2) ? vP4 : vP, w2 = (t & 2) ? vP : vP4;
      sts32(a1, w1); sts32(a2, w2);
      sts16(a1 + RD_CS + 2, w1); sts16(a1 + RD_CS + 4, w1 >> 16);
      sts16(a2 + RD_CS + 2, w2); sts16(a2 + RD_CS + 4, w2 >> 16);
    }
    if (t < 2) {
      const int b = 256 + 128 * t + 8 * j;
      const uint32_t ad = rb + 2 * (RD_X0 - 6 - b);
      const uint32_t v22 = __byte_perm(vQ4, 0, 0x3232), v00 = __byte_perm(vQ, 0, 0x3232);
      sts16(ad, vQ4);
      sts64(ad + 2, v22, __byte_perm(vQ4, vQ, 0x5432));
      sts32(ad + 10, v00);
      if (b != 256) { sts16(ad + 14, v00); sts128(ad + RD_CS + 2, vQ4, v22, vQ, v00); }
      else { sts64(ad + RD_CS + 2, vQ4, v22); sts32(ad + RD_CS + 10, vQ); sts16(ad + RD_CS + 14, v00); }
    } else {
      const uint32_t ao = rb + R_O2 + 2 * (159 - (32 * t + j)), ae = ao - (R_O2 - R_E2) + 2;
      sts16(ao, vQ4 >> 16); sts16(ao + RS_CS + 2, vQ4 >> 16); sts16(ao - 32, vQ4); sts16(ao - 32 + RS_CS + 2, vQ4);
      sts16(ae - 32, vQ); sts16(ae - 32 + RS_CS + 2, vQ);
      if (lane != 2 || hf) { sts16(ae, vQ >> 16); sts16(ae + RS_CS + 2, vQ >> 16); }
      else {
        const uint32_t vv = __byte_perm(vQ, 0, 0x3232), ad = rb + 2 * (RD_X0 - 514);
        sts16(ad, vv); sts32(ad + 2, vv); sts16(ad + 6, vv); sts64(ad + RD_CS + 2, vv, vv);
      }
    }
    {
      const uint32_t a = rb + ((g & 1) ? R_O3 : R_E3 + 2) + 2 * (159 - (64 + 16 * t + (j >> 1)));
      const bool p1024 = (lane == 0) && (hf == 0);
      const uint32_t a00 = p1024 ? rb + R_E2 + 2 * (159 - 127) : a;
      sts16(a00, vR >> 16); sts16(a00 + RS_CS + 2, vR >> 16);
      sts16(a - 16, vR); sts16(a - 16 + RS_CS + 2, vR);
      if (p1024) {
        sts32(sb + K1024_OFF + (ch * 2 + br) * 4, __byte_perm(vR, 0, 0x3232));
        const uint32_t kv = pack_bf16(k2048 + __uint_as_float(lds32(xo + 1280)), 0.f);
        sts16(rb + R_E3 + 2 * (159 - 127), kv); sts16(rb + R_E3 + 2 * (159 - 127) + RS_CS + 2, kv);
      }
    }
  }
  STAMP(5);
  asm volatile("barrier.cluster.wait.aligned;" ::: "memory");
  bar_sync(7 + (warp >> 1), 64);
  mbar_wait(sb + B_U);
  STAMP(6);

  const uint32_t zz = lds32(cb + R_OFF + br * R_BR);
  conv_dense(sb, cb, zz);
  STAMP(8);
  {
    const int x = (4 + ch) * 128 + wtid, c = x >> 2;
    const uint32_t rb = cb + R_OFF + br * R_BR;
    float e48[24], e40[20], e32[16], h32[16], h16[8];
    const int x1 = 159 - (16 * hf + g - 2 * t + 136);
    const uint32_t fs = rb + ((g & 1) ? 2 * x1 : RS_CS + 2 * x1 + 2);
    uint32_t A[2][4][4];
    auto loadA = [&](int buf, uint32_t oe, uint32_t oo, int i0) {
#pragma unroll
      for (int a = 0; a < 2; a++) {
        const uint32_t base = fs + (a ? oo : oe);
        uint32_t* k0 = A[buf][2 * a];
        uint32_t* k1 = A[buf][2 * a + 1];
        k0[1] = ldf(base, i0, 1, 9, hf); k0[0] = ldf(base, i0 + 1, 1, 9, hf); k0[2] = ldf(base, i0 + 2, 1, 9, hf);
        k1[0] = ldf(base, i0 + 3, 1, 9, hf); k1[2] = (i0 == 8) ? 0u : A[buf ^ 1][2 * a][1];
        k0[3] = k0[0]; k1[1] = k0[2]; k1[3] = k1[0];
      }
    };
    loadA(0, R_E2, R_O2, 8);
    loadA(1, R_E2, R_O2, 4);
    mbar_wait(sb + B_W);
    const uint64_t d5 = mkdesc(cb + W5_OFF, 144, 576), d3 = mkdesc(cb + W3_OFF, 144, 576);
    const uint64_t d9 = mkdesc(cb + W9_OFF, 144, 576), d7 = mkdesc(cb + W7_OFF, 144, 576);
    const uint32_t y2d = cb + Y2_OFF + br * 3072 + ysw(32 * (5 - (lane >> 4)) + 16 * hf + (lane & 15));
    const uint32_t y3d = cb + Y3_OFF + br * 2048 + ysw(2 * (16 * hf + (lane & 15)) + (lane >> 4));
#define FAR4(N, ACC, BUF, DA, DB, OFF, FIRST)                                                            \
    wg_fence();                                                                                           \
    _Pragma("unroll") for (int k = 0; k < 4; k++) {                                                      \
      const uint32_t* a = A[BUF][k];                                                                      \
      wgmma_rs<N, 1>(ACC, a[0], a[1], a[2], a[3], ((k >> 1) ? DB : DA) + (k & 1) * 18 + (OFF), !(FIRST) || k); \
    }                                                                                                     \
    wg_commit();
    FAR4(48, e48, 0, d5, d3, 0, 1)
    wg_wait0();
    loadA(0, R_E2, R_O2, 0);
    stsm2(y2d - 5 * 512, PK2(e48, 20), PK2(e48, 22));
#pragma unroll
    for (int i = 0; i < 20; i++) e40[i] = FCPY(e48, i);
    stage_done(sb, 2, lane);
    FAR4(40, e40, 1, d5, d3, 36, 0)
    wg_wait0();
    loadA(1, R_E3, R_O3, 8);
    stsm2(y2d - 4 * 512, PK2(e40, 16), PK2(e40, 18));
#pragma unroll
    for (int i = 0; i < 16; i++) e32[i] = FCPY(e40, i);
    stage_done(sb, 3, lane);
    FAR4(32, e32, 0, d5, d3, 72, 0)
    FAR4(32, h32, 1, d9, d7, 0, 1)
    wg_wait1();
    loadA(0, R_E3, R_O3, 4);
    stsm4(y2d, PK2(e32, 0), PK2(e32, 2), PK2(e32, 4), PK2(e32, 6));
    stsm4(y2d - 2 * 512, PK2(e32, 8), PK2(e32, 10), PK2(e32, 12), PK2(e32, 14));
    stage_done(sb, 4, lane);
    const uint2 gl = gate_ld(x);
    STAMP(9);
    wg_wait0();
    stsm4(y3d, PK2(h32, 8), PK2(h32, 10), PK2(h32, 12), PK2(h32, 14));
#pragma unroll
    for (int i = 0; i < 8; i++) h16[i] = FCPY(h32, i);
    stage_done(sb, 5, lane);
    FAR4(16, h16, 0, d9, d7, 72, 0)
#undef FAR4
    const uint32_t yo = sb + CH_OFF + (x & 3) * 4 + ysw(c);
    uint32_t ua[4], ub[4], ya[4], yb[4], a2[4], b2[4], a3[4], b3[4], s2[4];
    const uint4 dd = lds128(sb + DSK_OFF);
    skip_terms(ua, ub, sb, x, make_uint2(dd.x, dd.y), make_uint2(dd.z, dd.w));
    {
      const int xa = x - 514, xb = x - 513, ca = xa >> 2, cb2 = xb >> 2;
      ld4ch(s2, sb + CH_OFF + U_OFF + (xa & 3) * 4 + (ca & 3) * U_CS + (63 - (ca >> 2)) * 16);
      ld4ch(a3, sb + CH_OFF + U_OFF + (xb & 3) * 4 + (cb2 & 3) * U_CS + (63 - (cb2 >> 2)) * 16);
#pragma unroll
      for (int k = 0; k < 4; k++) s2[k] = hadd2(s2[k], __byte_perm(s2[k], a3[k], 0x5432));
    }
    const uint32_t tag = lds32(sb + TAG_OFF);
    wg_wait0();
    stsm4(y3d + 1024, PK2(h16, 0), PK2(h16, 2), PK2(h16, 4), PK2(h16, 6));
    stage_done(sb, 6, lane);
    STAMP(10);
    const uint32_t g2 = gate_fin(p, gl, x, tag);
    mbar_wait(sb + B_ST + 8 * 4);
    const uint4 k0 = lds128(sb + K1024_OFF), k1 = lds128(sb + K1024_OFF + 16);
    const uint32_t kk[8] = {k0.x, k0.y, k0.z, k0.w, k1.x, k1.y, k1.z, k1.w};
    ld4ch(ya, yo + Y0_OFF); ld4ch(yb, yo + Y0_OFF + 4096);
    ld4ch(a2, yo + Y2_OFF - 1024); ld4ch(b2, yo + Y2_OFF - 1024 + 3072);
    mbar_wait(sb + B_ST + 8 * (5 + (ch >> 1)));
    STAMP(12);
    ld4ch(a3, yo + Y3_OFF - 2048); ld4ch(b3, yo + Y3_OFF - 2048 + 2048);
#pragma unroll
    for (int k = 0; k < 4; k++) {
      ya[k] = hadd2(ya[k], hadd2(hfma2(kk[2 * k], s2[k], a2[k]), a3[k]));
      yb[k] = hadd2(yb[k], hadd2(hfma2(kk[2 * k + 1], s2[k], b2[k]), b3[k]));
    }
    const uint4 r = mix(ya, yb, ua, ub, g2);
    if ((uint32_t)(ch & 1) != rank) send_box(sb, 2 + (ch >> 1), wtid, rank, r);
    else merge_box(sb, &tm_out, 2 + (ch >> 1), wtid, rank, oc0, r, 1 + ch);
  }
  STAMP(14);
  if (wtid == 0) asm volatile("cp.async.bulk.wait_group.read 0;" ::: "memory");
  STAMP(15); GT(1);
}

typedef CUresult (*EncodeFn)(CUtensorMap*, CUtensorMapDataType, cuuint32_t, void*, const cuuint64_t*, const cuuint64_t*,
                             const cuuint32_t*, const cuuint32_t*, CUtensorMapInterleave, CUtensorMapSwizzle,
                             CUtensorMapL2promotion, CUtensorMapFloatOOBfill);

}

extern "C" void kernel_launch(void* const* d_in, const int* in_sizes, int n_in, void* d_out, int out_size) {
  (void)in_sizes; (void)n_in; (void)out_size;
  typedef const __nv_bfloat16* bp;
  Params p;
  p.t[0] = (bp)d_in[10]; p.t[1] = (bp)d_in[11]; p.t[2] = (bp)d_in[12]; p.t[3] = (bp)d_in[13]; p.t[4] = (bp)d_in[14]; p.t[5] = nullptr;
  p.t[6] = (bp)d_in[1]; p.t[7] = (bp)d_in[2]; p.t[8] = (bp)d_in[5]; p.t[9] = (bp)d_in[6]; p.t[10] = (bp)d_in[7];
  p.t[11] = (bp)d_in[3]; p.t[12] = (bp)d_in[4]; p.t[13] = nullptr;
  p.u = (bp)d_in[0]; p.gw = (bp)d_in[16]; p.A_D = (bp)d_in[8]; p.B_D = (bp)d_in[15];
  static EncodeFn enc = nullptr;
  if (!enc) {
    cudaDriverEntryPointQueryResult qr;
    cudaGetDriverEntryPoint("cuTensorMapEncodeTiled", (void**)&enc, cudaEnableDefault, &qr);
    cudaFuncSetAttribute(ssm_kernel, cudaFuncAttributeMaxDynamicSharedMemorySize, SMEM_BYTES);
  }
  CUtensorMap tm_in, tm_out;
  {
    cuuint64_t gd[5] = {512, 2, 4, 4, 64};
    cuuint64_t gs[4] = {1024, 8192, 2048, 32768};
    cuuint32_t bx[5] = {8, 2, 4, 4, 32};
    cuuint32_t es[5] = {1, 1, 1, 1, 1};
    enc(&tm_in, CU_TENSOR_MAP_DATA_TYPE_BFLOAT16, 5, d_in[0], gd, gs, bx, es, CU_TENSOR_MAP_INTERLEAVE_NONE,
        CU_TENSOR_MAP_SWIZZLE_NONE, CU_TENSOR_MAP_L2_PROMOTION_NONE, CU_TENSOR_MAP_FLOAT_OOB_FILL_NONE);
  }
  {
    cuuint64_t gd[3] = {512, 1024, 2};
    cuuint64_t gs[2] = {2048, 1024};
    cuuint32_t bx[3] = {8, 128, 2};
    cuuint32_t es[3] = {1, 1, 1};
    enc(&tm_out, CU_TENSOR_MAP_DATA_TYPE_BFLOAT16, 3, d_out, gd, gs, bx, es, CU_TENSOR_MAP_INTERLEAVE_NONE,
        CU_TENSOR_MAP_SWIZZLE_NONE, CU_TENSOR_MAP_L2_PROMOTION_NONE, CU_TENSOR_MAP_FLOAT_OOB_FILL_NONE);
  }
  ssm_kernel<<<NCTA + NGATE, 640, SMEM_BYTES, cudaStreamPerThread>>>(p, tm_in, tm_out);
}
```

```cpp
#include <cuda_runtime.h>
#include <cuda.h>
#include <cuda_bf16.h>
#include <stdint.h>

namespace {
#define PREDLD 1
#define FCPY(v, i) (((i) % 3 == 2) ? __uint_as_float(opq(__float_as_uint(v[i]), zz)) : opqf(v[i], zz))

constexpr int L = 2048, D = 512, NM = 128;
constexpr int NCTA = 128;
constexpr int NGATE = 4;

constexpr int RAW_OFF = 0;
constexpr int XIN_OFF = 32768;
constexpr int SC2_OFF = XIN_OFF + 8192;
constexpr int BAR_OFF = SC2_OFF + 10240;
constexpr int CH_OFF = BAR_OFF + 256;
constexpr int U_CS = 1184;
constexpr int U_OFF = 0;
constexpr int R_OFF = 4736;
constexpr int RD_X0 = 565;
constexpr int RD_CS = 1216;
constexpr int RS_CS = 320;
constexpr int R_E2 = 2 * RD_CS, R_O2 = R_E2 + 2 * RS_CS, R_E3 = R_O2 + 2 * RS_CS, R_O3 = R_E3 + 2 * RS_CS + 16;
constexpr int R_BR = R_O3 + 2 * RS_CS - 16;
constexpr int W5_OFF = R_OFF + 2 * R_BR;
constexpr int W3_OFF = W5_OFF + 3456;
constexpr int W9_OFF = W3_OFF + 3456;
constexpr int W7_OFF = W9_OFF + 2304;
constexpr int Y0_OFF = W7_OFF + 2304;
constexpr int Y2_OFF = Y0_OFF + 8192, Y3_OFF = Y2_OFF + 6144;
constexpr int CH_BYTES = Y0_OFF + 18432 + 16;
constexpr int SCR_BYTES = 4608;
constexpr int SMEM_BYTES = CH_OFF + 4 * CH_BYTES;
static_assert(CH_BYTES % 128 == 16, "bank staggering of the channel blocks");
static_assert(SMEM_BYTES <= 232448, "smem");
constexpr int B_RAW = BAR_OFF, B_X = BAR_OFF + 8, B_U = BAR_OFF + 40, B_W = BAR_OFF + 48;
constexpr int TAG_OFF = BAR_OFF + 56;
constexpr int K1024_OFF = BAR_OFF + 64;
constexpr int DSK_OFF = BAR_OFF + 160;
constexpr int B_ST = BAR_OFF + 96;

__device__ __align__(16) unsigned int g_gate[L];
__device__ unsigned int g_epoch;
__device__ unsigned int g_ticket;

#define STAMP(k)
#define GT(k)

struct Params {
  const __nv_bfloat16* t[14];
  const __nv_bfloat16 *u, *gw, *A_D, *B_D;
};

template <int N, int TB> __device__ __forceinline__ void wgmma_rs(float* d, uint32_t a0, uint32_t a1, uint32_t a2, uint32_t a3, uint64_t desc, int sc);
template <> __device__ __forceinline__ void wgmma_rs<64, 0>(float* d, uint32_t a0, uint32_t a1, uint32_t a2, uint32_t a3, uint64_t desc, int sc) {
  asm volatile("{\n.reg .pred p;\nsetp.ne.b32 p, %37, 0;\n"
    "wgmma.mma_async.sync.aligned.m64n64k16.f32.bf16.bf16 {%0,%1,%2,%3,%4,%5,%6,%7,%8,%9,%10,%11,%12,%13,%14,%15,%16,%17,%18,%19,%20,%21,%22,%23,%24,%25,%26,%27,%28,%29,%30,%31}, {%32,%33,%34,%35}, %36, p, 1, 1, 0;\n}"
    : "+f"(d[0]), "+f"(d[1]), "+f"(d[2]), "+f"(d[3]), "+f"(d[4]), "+f"(d[5]), "+f"(d[6]), "+f"(d[7]), "+f"(d[8]), "+f"(d[9]), "+f"(d[10]), "+f"(d[11]), "+f"(d[12]), "+f"(d[13]), "+f"(d[14]), "+f"(d[15]), "+f"(d[16]), "+f"(d[17]), "+f"(d[18]), "+f"(d[19]), "+f"(d[20]), "+f"(d[21]), "+f"(d[22]), "+f"(d[23]), "+f"(d[24]), "+f"(d[25]), "+f"(d[26]), "+f"(d[27]), "+f"(d[28]), "+f"(d[29]), "+f"(d[30]), "+f"(d[31]) : "r"(a0), "r"(a1), "r"(a2), "r"(a3), "l"(desc), "r"(sc));
}
template <> __device__ __forceinline__ void wgmma_rs<56, 0>(float* d, uint32_t a0, uint32_t a1, uint32_t a2, uint32_t a3, uint64_t desc, int sc) {
  asm volatile("{\n.reg .pred p;\nsetp.ne.b32 p, %33, 0;\n"
    "wgmma.mma_async.sync.aligned.m64n56k16.f32.bf16.bf16 {%0,%1,%2,%3,%4,%5,%6,%7,%8,%9,%10,%11,%12,%13,%14,%15,%16,%17,%18,%19,%20,%21,%22,%23,%24,%25,%26,%27}, {%28,%29,%30,%31}, %32, p, 1, 1, 0;\n}"
    : "+f"(d[0]), "+f"(d[1]), "+f"(d[2]), "+f"(d[3]), "+f"(d[4]), "+f"(d[5]), "+f"(d[6]), "+f"(d[7]), "+f"(d[8]), "+f"(d[9]), "+f"(d[10]), "+f"(d[11]), "+f"(d[12]), "+f"(d[13]), "+f"(d[14]), "+f"(d[15]), "+f"(d[16]), "+f"(d[17]), "+f"(d[18]), "+f"(d[19]), "+f"(d[20]), "+f"(d[21]), "+f"(d[22]), "+f"(d[23]), "+f"(d[24]), "+f"(d[25]), "+f"(d[26]), "+f"(d[27]) : "r"(a0), "r"(a1), "r"(a2), "r"(a3), "l"(desc), "r"(sc));
}
template <> __device__ __forceinline__ void wgmma_rs<48, 0>(float* d, uint32_t a0, uint32_t a1, uint32_t a2, uint32_t a3, uint64_t desc, int sc) {
  asm volatile("{\n.reg .pred p;\nsetp.ne.b32 p, %29, 0;\n"
    "wgmma.mma_async.sync.aligned.m64n48k16.f32.bf16.bf16 {%0,%1,%2,%3,%4,%5,%6,%7,%8,%9,%10,%11,%12,%13,%14,%15,%16,%17,%18,%19,%20,%21,%22,%23}, {%24,%25,%26,%27}, %28, p, 1, 1, 0;\n}"
    : "+f"(d[0]), "+f"(d[1]), "+f"(d[2]), "+f"(d[3]), "+f"(d[4]), "+f"(d[5]), "+f"(d[6]), "+f"(d[7]), "+f"(d[8]), "+f"(d[9]), "+f"(d[10]), "+f"(d[11]), "+f"(d[12]), "+f"(d[13]), "+f"(d[14]), "+f"(d[15]), "+f"(d[16]), "+f"(d[17]), "+f"(d[18]), "+f"(d[19]), "+f"(d[20]), "+f"(d[21]), "+f"(d[22]), "+f"(d[23]) : "r"(a0), "r"(a1), "r"(a2), "r"(a3), "l"(desc), "r"(sc));
}
template <> __device__ __forceinline__ void wgmma_rs<32, 0>(float* d, uint32_t a0, uint32_t a1, uint32_t a2, uint32_t a3, uint64_t desc, int sc) {
  asm volatile("{\n.reg .pred p;\nsetp.ne.b32 p, %21, 0;\n"
    "wgmma.mma_async.sync.aligned.m64n32k16.f32.bf16.bf16 {%0,%1,%2,%3,%4,%5,%6,%7,%8,%9,%10,%11,%12,%13,%14,%15}, {%16,%17,%18,%19}, %20, p, 1, 1, 0;\n}"
    : "+f"(d[0]), "+f"(d[1]), "+f"(d[2]), "+f"(d[3]), "+f"(d[4]), "+f"(d[5]), "+f"(d[6]), "+f"(d[7]), "+f"(d[8]), "+f"(d[9]), "+f"(d[10]), "+f"(d[11]), "+f"(d[12]), "+f"(d[13]), "+f"(d[14]), "+f"(d[15]) : "r"(a0), "r"(a1), "r"(a2), "r"(a3), "l"(desc), "r"(sc));
}
template <> __device__ __forceinline__ void wgmma_rs<48, 1>(float* d, uint32_t a0, uint32_t a1, uint32_t a2, uint32_t a3, uint64_t desc, int sc) {
  asm volatile("{\n.reg .pred p;\nsetp.ne.b32 p, %29, 0;\n"
    "wgmma.mma_async.sync.aligned.m64n48k16.f32.bf16.bf16 {%0,%1,%2,%3,%4,%5,%6,%7,%8,%9,%10,%11,%12,%13,%14,%15,%16,%17,%18,%19,%20,%21,%22,%23}, {%24,%25,%26,%27}, %28, p, 1, 1, 1;\n}"
    : "+f"(d[0]), "+f"(d[1]), "+f"(d[2]), "+f"(d[3]), "+f"(d[4]), "+f"(d[5]), "+f"(d[6]), "+f"(d[7]), "+f"(d[8]), "+f"(d[9]), "+f"(d[10]), "+f"(d[11]), "+f"(d[12]), "+f"(d[13]), "+f"(d[14]), "+f"(d[15]), "+f"(d[16]), "+f"(d[17]), "+f"(d[18]), "+f"(d[19]), "+f"(d[20]), "+f"(d[21]), "+f"(d[22]), "+f"(d[23]) : "r"(a0), "r"(a1), "r"(a2), "r"(a3), "l"(desc), "r"(sc));
}
template <> __device__ __forceinline__ void wgmma_rs<40, 1>(float* d, uint32_t a0, uint32_t a1, uint32_t a2, uint32_t a3, uint64_t desc, int sc) {
  asm volatile("{\n.reg .pred p;\nsetp.ne.b32 p, %25, 0;\n"
    "wgmma.mma_async.sync.aligned.m64n40k16.f32.bf16.bf16 {%0,%1,%2,%3,%4,%5,%6,%7,%8,%9,%10,%11,%12,%13,%14,%15,%16,%17,%18,%19}, {%20,%21,%22,%23}, %24, p, 1, 1, 1;\n}"
    : "+f"(d[0]), "+f"(d[1]), "+f"(d[2]), "+f"(d[3]), "+f"(d[4]), "+f"(d[5]), "+f"(d[6]), "+f"(d[7]), "+f"(d[8]), "+f"(d[9]), "+f"(d[10]), "+f"(d[11]), "+f"(d[12]), "+f"(d[13]), "+f"(d[14]), "+f"(d[15]), "+f"(d[16]), "+f"(d[17]), "+f"(d[18]), "+f"(d[19]) : "r"(a0), "r"(a1), "r"(a2), "r"(a3), "l"(desc), "r"(sc));
}
template <> __device__ __forceinline__ void wgmma_rs<32, 1>(float* d, uint32_t a0, uint32_t a1, uint32_t a2, uint32_t a3, uint64_t desc, int sc) {
  asm volatile("{\n.reg .pred p;\nsetp.ne.b32 p, %21, 0;\n"
    "wgmma.mma_async.sync.aligned.m64n32k16.f32.bf16.bf16 {%0,%1,%2,%3,%4,%5,%6,%7,%8,%9,%10,%11,%12,%13,%14,%15}, {%16,%17,%18,%19}, %20, p, 1, 1, 1;\n}"
    : "+f"(d[0]), "+f"(d[1]), "+f"(d[2]), "+f"(d[3]), "+f"(d[4]), "+f"(d[5]), "+f"(d[6]), "+f"(d[7]), "+f"(d[8]), "+f"(d[9]), "+f"(d[10]), "+f"(d[11]), "+f"(d[12]), "+f"(d[13]), "+f"(d[14]), "+f"(d[15]) : "r"(a0), "r"(a1), "r"(a2), "r"(a3), "l"(desc), "r"(sc));
}
template <> __device__ __forceinline__ void wgmma_rs<16, 1>(float* d, uint32_t a0, uint32_t a1, uint32_t a2, uint32_t a3, uint64_t desc, int sc) {
  asm volatile("{\n.reg .pred p;\nsetp.ne.b32 p, %13, 0;\n"
    "wgmma.mma_async.sync.aligned.m64n16k16.f32.bf16.bf16 {%0,%1,%2,%3,%4,%5,%6,%7}, {%8,%9,%10,%11}, %12, p, 1, 1, 1;\n}"
    : "+f"(d[0]), "+f"(d[1]), "+f"(d[2]), "+f"(d[3]), "+f"(d[4]), "+f"(d[5]), "+f"(d[6]), "+f"(d[7]) : "r"(a0), "r"(a1), "r"(a2), "r"(a3), "l"(desc), "r"(sc));
}

__device__ __forceinline__ uint32_t pack_bf16(float lo, float hi) {
  uint32_t r; asm("cvt.rn.bf16x2.f32 %0, %1, %2;" : "=r"(r) : "f"(hi), "f"(lo)); return r;
}
__device__ __forceinline__ float bf_lo(uint32_t v) { return __uint_as_float(v << 16); }
__device__ __forceinline__ float bf_hi(uint32_t v) { return __uint_as_float(v & 0xffff0000u); }
__device__ __forceinline__ float bf_round(float x) { return bf_lo(pack_bf16(x, 0.f)); }
__device__ __forceinline__ uint32_t hmul2(uint32_t a, uint32_t b) { uint32_t r; asm("mul.rn.bf16x2 %0, %1, %2;" : "=r"(r) : "r"(a), "r"(b)); return r; }
__device__ __forceinline__ uint32_t hadd2(uint32_t a, uint32_t b) { uint32_t r; asm("add.rn.bf16x2 %0, %1, %2;" : "=r"(r) : "r"(a), "r"(b)); return r; }
__device__ __forceinline__ uint32_t hsub2(uint32_t a, uint32_t b) { uint32_t r; asm("sub.rn.bf16x2 %0, %1, %2;" : "=r"(r) : "r"(a), "r"(b)); return r; }
__device__ __forceinline__ uint32_t hfma2(uint32_t a, uint32_t b, uint32_t c) { uint32_t r; asm("fma.rn.bf16x2 %0, %1, %2, %3;" : "=r"(r) : "r"(a), "r"(b), "r"(c)); return r; }

__device__ __forceinline__ void sts16(uint32_t a, uint32_t v) { asm volatile("st.shared.b16 [%0], %1;" ::"r"(a), "h"((unsigned short)v) : "memory"); }
__device__ __forceinline__ void sts32(uint32_t a, uint32_t v) { asm volatile("st.shared.b32 [%0], %1;" ::"r"(a), "r"(v) : "memory"); }
__device__ __forceinline__ void sts64(uint32_t a, uint32_t x, uint32_t y) { asm volatile("st.shared.v2.b32 [%0], {%1,%2};" ::"r"(a), "r"(x), "r"(y) : "memory"); }
__device__ __forceinline__ void sts128(uint32_t a, uint32_t x, uint32_t y, uint32_t z, uint32_t w) {
  asm volatile("st.shared.v4.b32 [%0], {%1,%2,%3,%4};" ::"r"(a), "r"(x), "r"(y), "r"(z), "r"(w) : "memory");
}
__device__ __forceinline__ uint32_t lds32(uint32_t a) { uint32_t v; asm volatile("ld.shared.b32 %0, [%1];" : "=r"(v) : "r"(a) : "memory"); return v; }
__device__ __forceinline__ uint32_t ldf(uint32_t base, int i, int lo0, int hi0, int hf) {
  if (i < lo0 || i > hi0 + 2) return 0u;
  if (i < lo0 + 2 || i > hi0) {
    uint32_t v;
    asm volatile("{\n.reg .pred p;\nsetp.eq.b32 p, %2, %3;\nmov.b32 %0, 0;\n@p ld.shared.b32 %0, [%1];\n}" : "=r"(v) : "r"(base + i * 16), "r"(hf), "r"(i > hi0 ? 1 : 0) : "memory");
    return v;
  }
  return lds32(base + i * 16);
}
__device__ __forceinline__ uint2 lds64(uint32_t a) { uint2 v; asm volatile("ld.shared.v2.b32 {%0,%1}, [%2];" : "=r"(v.x), "=r"(v.y) : "r"(a) : "memory"); return v; }
__device__ __forceinline__ uint4 lds128(uint32_t a) {
  uint4 v; asm volatile("ld.shared.v4.b32 {%0,%1,%2,%3}, [%4];" : "=r"(v.x), "=r"(v.y), "=r"(v.z), "=r"(v.w) : "r"(a) : "memory"); return v;
}
__device__ __forceinline__ uint4 ldg128(const void* a) {
  uint4 v; asm volatile("ld.global.nc.v4.b32 {%0,%1,%2,%3}, [%4];" : "=r"(v.x), "=r"(v.y), "=r"(v.z), "=r"(v.w) : "l"(a) : "memory"); return v;
}
__device__ __forceinline__ uint2 ldg64(const void* a) {
  uint2 v; asm volatile("ld.global.nc.v2.b32 {%0,%1}, [%2];" : "=r"(v.x), "=r"(v.y) : "l"(a) : "memory"); return v;
}
__device__ __forceinline__ void ldsm4(uint32_t a, uint32_t& r0, uint32_t& r1, uint32_t& r2, uint32_t& r3) {
  asm volatile("ldmatrix.sync.aligned.m8n8.x4.shared.b16 {%0,%1,%2,%3}, [%4];" : "=r"(r0), "=r"(r1), "=r"(r2), "=r"(r3) : "r"(a) : "memory");
}
__device__ __forceinline__ void ldsm4t(uint32_t a, uint32_t& r0, uint32_t& r1, uint32_t& r2, uint32_t& r3) {
  asm volatile("ldmatrix.sync.aligned.m8n8.x4.trans.shared.b16 {%0,%1,%2,%3}, [%4];" : "=r"(r0), "=r"(r1), "=r"(r2), "=r"(r3) : "r"(a) : "memory");
}
__device__ __forceinline__ void stsm4(uint32_t a, uint32_t r0, uint32_t r1, uint32_t r2, uint32_t r3) {
  asm volatile("stmatrix.sync.aligned.m8n8.x4.shared.b16 [%0], {%1,%2,%3,%4};" ::"r"(a), "r"(r0), "r"(r1), "r"(r2), "r"(r3) : "memory");
}
__device__ __forceinline__ void stsm4t(uint32_t a, uint32_t r0, uint32_t r1, uint32_t r2, uint32_t r3) {
  asm volatile("stmatrix.sync.aligned.m8n8.x4.trans.shared.b16 [%0], {%1,%2,%3,%4};" ::"r"(a), "r"(r0), "r"(r1), "r"(r2), "r"(r3) : "memory");
}
__device__ __forceinline__ void stsm2(uint32_t a, uint32_t r0, uint32_t r1) {
  asm volatile("stmatrix.sync.aligned.m8n8.x2.shared.b16 [%0], {%1,%2};" ::"r"(a), "r"(r0), "r"(r1) : "memory");
}
__device__ __forceinline__ void stsm2t(uint32_t a, uint32_t r0, uint32_t r1) {
  asm volatile("stmatrix.sync.aligned.m8n8.x2.trans.shared.b16 [%0], {%1,%2};" ::"r"(a), "r"(r0), "r"(r1) : "memory");
}
__device__ __forceinline__ void mma16816(float* c, uint32_t a0, uint32_t a1, uint32_t a2, uint32_t a3, uint32_t b0, uint32_t b1) {
  asm("mma.sync.aligned.m16n8k16.row.col.f32.bf16.bf16.f32 {%0,%1,%2,%3}, {%4,%5,%6,%7}, {%8,%9}, {%0,%1,%2,%3};"
      : "+f"(c[0]), "+f"(c[1]), "+f"(c[2]), "+f"(c[3]) : "r"(a0), "r"(a1), "r"(a2), "r"(a3), "r"(b0), "r"(b1));
}
__device__ __forceinline__ void bar_sync(int id, int n) { asm volatile("bar.sync %0, %1;" ::"r"(id), "r"(n) : "memory"); }
__device__ __forceinline__ void wg_fence() { asm volatile("wgmma.fence.sync.aligned;" ::: "memory"); }
__device__ __forceinline__ void wg_commit() { asm volatile("wgmma.commit_group.sync.aligned;" ::: "memory"); }
__device__ __forceinline__ void wg_wait0() { asm volatile("wgmma.wait_group.sync.aligned 0;" ::: "memory"); }
__device__ __forceinline__ void wg_wait1() { asm volatile("wgmma.wait_group.sync.aligned 1;" ::: "memory"); }
__device__ __forceinline__ void fence_async() { asm volatile("fence.proxy.async.shared::cta;" ::: "memory"); }
__device__ __forceinline__ uint32_t opq(uint32_t x, uint32_t z) { uint32_t r; asm volatile("xor.b32 %0, %1, %2;" : "=r"(r) : "r"(x), "r"(z)); return r; }
__device__ __forceinline__ float opqf(float x, uint32_t z) { float r; asm volatile("add.rn.f32 %0, %1, %2;" : "=f"(r) : "f"(x), "f"(__uint_as_float(z))); return r; }
__device__ __forceinline__ int fresh_tid() { int v; asm volatile("mov.u32 %0, %%tid.x;" : "=r"(v)); return v; }
#define FRESH_IDS const int tid = fresh_tid(), lane = tid & 31, g = lane >> 2, t = lane & 3, wtid = tid & 127; (void)g; (void)t; (void)wtid
__device__ __forceinline__ uint64_t mkdesc(uint32_t addr, uint32_t lbo, uint32_t sbo) {
  return (uint64_t)((addr & 0x3FFFF) >> 4) | ((uint64_t)(lbo >> 4) << 16) | ((uint64_t)(sbo >> 4) << 32);
}
__device__ __forceinline__ uint32_t mapa(uint32_t a, uint32_t rank) {
  uint32_t r; asm("mapa.shared::cluster.u32 %0, %1, %2;" : "=r"(r) : "r"(a), "r"(rank)); return r;
}
__device__ __forceinline__ void mbar_init_expect(uint32_t bar, uint32_t bytes) {
  asm volatile("mbarrier.init.shared::cta.b64 [%0], 1;" ::"r"(bar) : "memory");
  asm volatile("mbarrier.arrive.expect_tx.shared::cta.b64 _, [%0], %1;" ::"r"(bar), "r"(bytes) : "memory");
}
__device__ __forceinline__ void mbar_wait(uint32_t bar) {
#pragma unroll 1
  for (int it = 0; it < (1 << 22); it++) {
    uint32_t ok;
    asm volatile("{\n.reg .pred p;\nmbarrier.try_wait.parity.acquire.cluster.shared::cta.b64 p, [%1], 0;\nselp.u32 %0, 1, 0, p;\n}"
                 : "=r"(ok) : "r"(bar) : "memory");
    if (ok) return;
  }
  __trap();
}
__device__ __forceinline__ void st_async4(uint32_t a, uint32_t bar, uint32_t x, uint32_t y, uint32_t z, uint32_t w) {
  asm volatile("st.async.weak.shared::cluster.mbarrier::complete_tx::bytes.v4.b32 [%0], {%2,%3,%4,%5}, [%1];"
               ::"r"(a), "r"(bar), "r"(x), "r"(y), "r"(z), "r"(w) : "memory");
}

struct cf { float re, im; };
__device__ __forceinline__ cf cmul(cf a, cf b) { return {fmaf(a.re, b.re, -a.im * b.im), fmaf(a.re, b.im, a.im * b.re)}; }
__device__ __forceinline__ cf csq(cf a) { return {fmaf(a.re, a.re, -a.im * a.im), (a.re + a.re) * a.im}; }
__device__ __forceinline__ cf cexp_p(float xl, float y, float p) {
  float mag; asm("ex2.approx.ftz.f32 %0, %1;" : "=f"(mag) : "f"(xl * p));
  const float th = y * p;
  const float k = __fadd_rn(fmaf(th, 0.15915494309189535f, 12582912.f), -12582912.f);
  float r = fmaf(k, -6.2831854820251465f, th);
  r = fmaf(k, 1.7484555314695172e-07f, r);
  return {mag * __cosf(r), mag * __sinf(r)};
}
__device__ __forceinline__ uint32_t ysw(int c) { return (uint32_t)(c ^ ((c >> 3) & 3)) * 16u; }

#define CMUL2(OR, OI, xr, xi, yr, yi, nyi) do { OR = hfma2(xr, yr, hmul2(xi, nyi)); OI = hfma2(xr, yi, hmul2(xi, yr)); } while (0)

__device__ __forceinline__ uint32_t gate_slow(const __nv_bfloat16* u, const __nv_bfloat16* gw, int row) {
  float s = 0.f;
  const uint32_t* xr = (const uint32_t*)(u + (size_t)row * D);
  const uint32_t* wr = (const uint32_t*)gw;
#pragma unroll 1
  for (int j = 0; j < D / 2; j++) { const uint32_t pr = hmul2(xr[j], wr[j]); s += bf_lo(pr); s += bf_hi(pr); }
  s = bf_round(s);
  return pack_bf16(1.f / (1.f + expf(-s)), 0.f);
}

__device__ __forceinline__ uint2 gate_ld(int x) {
  uint2 gv;
  asm volatile("ld.relaxed.gpu.global.v2.u32 {%0,%1}, [%2];" : "=r"(gv.x), "=r"(gv.y) : "l"(g_gate + x * 2) : "memory");
  return gv;
}
__device__ __noinline__ uint32_t gate_poll(const Params* pp, int x, uint32_t tag) {
  uint2 gv;
#pragma unroll 1
  for (int spins = 0; spins < (1 << 16); spins++) {
    gv = gate_ld(x);
    if ((gv.x >> 16) == tag && (gv.y >> 16) == tag) return __byte_perm(gv.x, gv.y, 0x5410);
  }
  return __byte_perm(gate_slow(pp->u, pp->gw, x * 2), gate_slow(pp->u, pp->gw, x * 2 + 1), 0x5410);
}
__device__ __forceinline__ uint32_t gate_fin(const Params& p, uint2 gv, int x, uint32_t tag) {
  if ((gv.x >> 16) == tag && (gv.y >> 16) == tag) return __byte_perm(gv.x, gv.y, 0x5410);
  return gate_poll(&p, x, tag);
}

__device__ __forceinline__ void ld4ch(uint32_t* v, uint32_t addr) {
#pragma unroll
  for (int k = 0; k < 4; k++) v[k] = lds32(addr + k * CH_BYTES);
}
__device__ __forceinline__ void skip_terms(uint32_t* ua, uint32_t* ub, uint32_t sb, int x, uint2 dA, uint2 dB) {
  const int c = x >> 2;
  uint32_t uu[4];
  ld4ch(uu, sb + CH_OFF + (x & 3) * 4 + U_OFF + (c & 3) * U_CS + (63 - (c >> 2)) * 16);
#pragma unroll
  for (int k = 0; k < 4; k++) {
    ua[k] = hmul2(uu[k], __byte_perm((k & 2) ? dA.y : dA.x, 0, (k & 1) ? 0x3232 : 0x1010));
    ub[k] = hmul2(uu[k], __byte_perm((k & 2) ? dB.y : dB.x, 0, (k & 1) ? 0x3232 : 0x1010));
  }
}
__device__ __forceinline__ uint4 mix(const uint32_t* a, const uint32_t* b, const uint32_t* ua, const uint32_t* ub, uint32_t g2) {
  const uint32_t h2 = hsub2(0x3f803f80u, g2);
  uint32_t o[4];
#pragma unroll
  for (int k = 0; k < 4; k++) o[k] = hadd2(hmul2(g2, hadd2(a[k], ua[k])), hmul2(h2, hadd2(b[k], ub[k])));
  return make_uint4(__byte_perm(o[0], o[1], 0x5410), __byte_perm(o[2], o[3], 0x5410), __byte_perm(o[0], o[1], 0x7632), __byte_perm(o[2], o[3], 0x7632));
}
__device__ __forceinline__ void send_box(uint32_t sb, int slot, int wtid, uint32_t rank, uint4 r) {
  st_async4(mapa(sb + XIN_OFF + slot * 2048 + wtid * 16, rank ^ 1), mapa(sb + B_X + slot * 8, rank ^ 1), r.x, r.y, r.z, r.w);
}
__device__ __forceinline__ void merge_rows(uint32_t st, uint32_t rank, uint4 r, uint4 q) {
  const uint4 lo = rank ? q : r, hi = rank ? r : q;
  sts128(st, lo.x, lo.y, hi.x, hi.y); sts128(st + 2048, lo.z, lo.w, hi.z, hi.w);
}
__device__ __forceinline__ void merge_box(uint32_t sb, const CUtensorMap* tm_out, int slot, int wtid, uint32_t rank, int oc0, uint4 r, int barid) {
  const uint32_t st = sb + RAW_OFF + slot * 4096 + wtid * 16;
  mbar_wait(sb + B_X + slot * 8);
  merge_rows(st, rank, r, lds128(sb + XIN_OFF + slot * 2048 + wtid * 16));
  fence_async();
  bar_sync(barid, 128);
  if (wtid == 0) {
    asm volatile("cp.async.bulk.tensor.3d.global.shared::cta.bulk_group [%0, {%2, %3, %4}], [%1];"
                 ::"l"(tm_out), "r"(sb + RAW_OFF + slot * 4096), "r"(oc0), "r"((2 * slot + (int)rank) * 128), "r"(0) : "memory");
    asm volatile("cp.async.bulk.commit_group;" ::: "memory");
  }
}

__device__ __forceinline__ uint32_t band2(int e, int lo, int hi) {
  uint32_t r = ((uint32_t)(e - lo) <= (uint32_t)(hi - lo) ? 0x3f80u : 0u) | ((uint32_t)(e - 1 - lo) <= (uint32_t)(hi - lo) ? 0x3f800000u : 0u);
  asm volatile("" : "+r"(r));
  return r;
}

__device__ __forceinline__ void stage_done(uint32_t sb, int stage, int lane) {
  __syncwarp();
  if (lane == 0) asm volatile("mbarrier.arrive.shared::cta.b64 _, [%0];" ::"r"(sb + B_ST + 8 * stage) : "memory");
}
#define PK2(v, i) pack_bf16(v[i], v[(i) + 1])

__device__ __forceinline__ void conv_dense(uint32_t sb, uint32_t cb, uint32_t zz, int br, int hf) {
  FRESH_IDS;
  const uint32_t rb = cb + R_OFF + br * R_BR;
  const int eo = 16 * hf + g - 2 * t;
  const int x0 = RD_X0 - (eo + 536);
  const uint32_t fa = rb + ((g & 1) ? 2 * x0 : RD_CS + 2 * x0 + 2);
  const uint64_t ub = mkdesc(cb + U_OFF, U_CS, 128);
  const uint32_t yd = cb + Y0_OFF + br * 4096 + ysw(4 * (63 - 8 * (lane >> 4) - (lane & 7)) + 2 * hf + ((lane >> 3) & 1));
  uint32_t A[2][4][4];
  float e64[32], e56[28];
  auto loadA = [&](int j) {
#pragma unroll
    for (int k = 0; k < 4; k++) {
      const int s = 34 - 4 * j - k;
      if (s >= 0) {
        if (k == 0 && j == 0) A[0][0][2] = ldf(fa, 2 * s + 2, 2, 67, hf);
        A[j & 1][k][0] = ldf(fa, 2 * s + 1, 2, 67, hf);
        A[j & 1][k][1] = ldf(fa, 2 * s, 2, 67, hf);
      }
    }
#pragma unroll
    for (int k = 0; k < 4; k++) {
      if (34 - 4 * j - k >= 0) {
        A[j & 1][k][3] = A[j & 1][k][0];
        if (k) A[j & 1][k][2] = A[j & 1][k - 1][1];
        else if (j) A[j & 1][0][2] = A[(j - 1) & 1][3][1];
      }
    }
  };
  loadA(0); loadA(1);
#pragma unroll
  for (int j = 0; j < 9; j++) {
    if (j == 4) {
      wg_wait0();
      stsm2t(yd - 7 * 512, PK2(e64, 28), PK2(e64, 30));
#pragma unroll
      for (int i = 0; i < 28; i++) e56[i] = FCPY(e64, i);
      stage_done(sb, 0, lane);
    }
    if (j == 8) {
      wg_wait0();
      stsm2t(yd - 6 * 512, PK2(e56, 24), PK2(e56, 26));
      stage_done(sb, 1, lane);
    }
    wg_fence();
#pragma unroll
    for (int k = 0; k < 4; k++) {
      const int s = 34 - 4 * j - k;
      if (s >= 0) {
        const int o = 2 * s - 66 + 128;
        const int cc = o & 3, rs = (o >> 2) - 32;
        const uint64_t desc = ub + (uint64_t)((cc * U_CS - rs * 16) >> 4);
        const uint32_t* a = A[j & 1][k];
        if (j < 4) wgmma_rs<64, 0>(e64, a[0], a[1], a[2], a[3], desc, s != 34);
        else wgmma_rs<56, 0>(e56, a[0], a[1], a[2], a[3], desc, 1);
      }
    }
    wg_commit();
    if (j >= 1 && j < 8) { wg_wait1(); loadA(j + 1); }
  }
  wg_wait0();
#pragma unroll
  for (int i = 0; i < 6; i += 2) stsm4t(yd - i * 512, PK2(e56, 4 * i), PK2(e56, 4 * i + 2), PK2(e56, 4 * i + 4), PK2(e56, 4 * i + 6));
}

__device__ __noinline__ unsigned int gate_rows(const Params* pp, int grow, int step, int rend) {
  const __nv_bfloat16 *u = pp->u, *gw = pp->gw;
  const int lane = threadIdx.x & 31;
  uint4 nx[4][2];
#pragma unroll
  for (int i = 0; i < 4; i++) {
    nx[i][0] = ldg128(u + (size_t)(grow + i) * D + lane * 8);
    nx[i][1] = ldg128(u + (size_t)(grow + i) * D + 256 + lane * 8);
  }
  const uint4 gw0 = ldg128(gw + lane * 8), gw1 = ldg128(gw + 256 + lane * 8);
  const uint32_t ws[8] = {gw0.x, gw0.y, gw0.z, gw0.w, gw1.x, gw1.y, gw1.z, gw1.w};
  unsigned int epoch;
  asm volatile("ld.relaxed.gpu.global.u32 %0, [%1];" : "=r"(epoch) : "l"(&g_epoch) : "memory");
#pragma unroll 1
  for (; grow < rend; grow += step) {
    const int nrow = (grow + step < rend) ? grow + step : grow;
    float c[2][4];
#pragma unroll
    for (int i = 0; i < 2; i++) {
      const uint4 *x = nx[2 * i], *y = nx[2 * i + 1];
      const uint32_t xs[8] = {x[0].x, x[0].y, x[0].z, x[0].w, x[1].x, x[1].y, x[1].z, x[1].w};
      const uint32_t ys[8] = {y[0].x, y[0].y, y[0].z, y[0].w, y[1].x, y[1].y, y[1].z, y[1].w};
      uint32_t px[8], py[8];
#pragma unroll
      for (int j = 0; j < 8; j++) { px[j] = hmul2(xs[j], ws[j]); py[j] = hmul2(ys[j], ws[j]); }
      if (nrow != grow) {
#pragma unroll
        for (int k = 2 * i; k < 2 * i + 2; k++) {
          nx[k][0] = ldg128(u + (size_t)(nrow + k) * D + lane * 8);
          nx[k][1] = ldg128(u + (size_t)(nrow + k) * D + 256 + lane * 8);
        }
      }
      c[i][0] = c[i][1] = c[i][2] = c[i][3] = 0.f;
#pragma unroll
      for (int j = 0; j < 8; j += 2) mma16816(c[i], px[j], py[j], px[j + 1], py[j + 1], 0x3f803f80u, 0x3f803f80u);
    }
    float s = (lane & 2) ? ((lane & 1) ? c[1][2] : c[1][0]) : ((lane & 1) ? c[0][2] : c[0][0]);
#pragma unroll
    for (int o = 4; o < 32; o <<= 1) s += __shfl_xor_sync(0xffffffffu, s, o);
    s = bf_round(s);
    const float gv = 1.f / (1.f + expf(-s));
    const uint32_t w = ((epoch + 1) << 16) | (pack_bf16(gv, 0.f) & 0xffffu);
    if (lane < 4) asm volatile("st.relaxed.gpu.global.u32 [%0], %1;" ::"l"(&g_gate[grow + lane]), "r"(w) : "memory");
  }
  return epoch;
}
#define GW 1
constexpr int GSPLIT = L - 4 * GW * NCTA;
__device__ __noinline__ void gate_cta(const Params* pp) {
  const unsigned int epoch = gate_rows(pp, (blockIdx.x * 20 + (threadIdx.x >> 5)) * 4, 80 * NGATE, GSPLIT);
  __syncthreads();
  if (threadIdx.x == 0 && atomicAdd(&g_ticket, 1u) == NCTA + NGATE - 1) { g_ticket = 0; g_epoch = epoch + 1; }
}

__global__ void __cluster_dims__(2, 1, 1) __launch_bounds__(640, 1)
ssm_kernel(const __grid_constant__ Params p, const __grid_constant__ CUtensorMap tm_in, const __grid_constant__ CUtensorMap tm_out) {
  extern __shared__ __align__(1024) unsigned char smem_raw[];
  const uint32_t sb = (uint32_t)__cvta_generic_to_shared(smem_raw);
  const int tid = threadIdx.x, lane = tid & 31;
  const int warp = __shfl_sync(0xffffffffu, tid >> 5, 0);
  const int ch = warp >> 2, wq = warp & 3, br = wq >> 1, hf = wq & 1;
  const int g = lane >> 2, t = lane & 3;
  if (__builtin_expect(blockIdx.x < NGATE, 0)) { gate_cta(&p); return; }
  const int bid = blockIdx.x - NGATE;
  const uint32_t rank = blockIdx.x & 1;
  const uint32_t cb = sb + CH_OFF + ch * CH_BYTES;
  const int wtid = tid & 127;
  const int oc0 = (bid >> 1) * 8;
  STAMP(0); GT(0);

  if (warp >= 16) {
    if (wtid == 0) {
      mbar_init_expect(sb + B_RAW, 32768);
#pragma unroll
      for (int i = 0; i < 4; i++) mbar_init_expect(sb + B_X + 8 * i, 2048);
      asm volatile("mbarrier.init.shared::cta.b64 [%0], 128;" ::"r"(sb + B_U) : "memory");
      asm volatile("mbarrier.init.shared::cta.b64 [%0], 128;" ::"r"(sb + B_W) : "memory");
#pragma unroll
      for (int i = 0; i < 7; i++) asm volatile("mbarrier.init.shared::cta.b64 [%0], 16;" ::"r"(sb + B_ST + 8 * i) : "memory");
      asm volatile("fence.mbarrier_init.release.cluster;" ::: "memory");
      asm volatile("fence.proxy.async.shared::cta;" ::: "memory");
    }
    __syncwarp();
    asm volatile("barrier.cluster.arrive.relaxed.aligned;" ::: "memory");
    if (wq >= 4 - GW) gate_rows(&p, GSPLIT + (bid * GW + 3 - wq) * 4, L, L);
    unsigned int epoch;
    asm volatile("ld.relaxed.gpu.global.u32 %0, [%1];" : "=r"(epoch) : "l"(&g_epoch) : "memory");
    asm volatile("barrier.cluster.wait.aligned;" ::: "memory");
    if (wtid == 0) {
      asm volatile("cp.async.bulk.tensor.5d.shared::cluster.global.mbarrier::complete_tx::bytes.multicast::cluster [%0], [%1, {%3, %4, %4, %4, %5}], [%2], %6;"
                   ::"r"(sb + RAW_OFF + rank * 16384), "l"(&tm_in), "r"(sb + B_RAW), "r"(oc0), "r"(0), "r"((int)rank * 32), "h"((unsigned short)3) : "memory");
    }
    sts128(sb + CH_OFF + wq * CH_BYTES + U_OFF + (lane >> 3) * U_CS + (64 + (lane & 7)) * 16, 0, 0, 0, 0);
    const uint2 dA = ldg64(p.A_D + bid * 4), dB = ldg64(p.B_D + bid * 4);
    uint32_t BA[3][4], BB[4][4];
    {
      const int l1 = br ? 3 : 6, h1 = br ? 5 : 10, l2 = br ? 5 : 12, h2 = br ? 11 : 20;
#pragma unroll
      for (int i = 0; i < 4; i++) {
        const int e = 16 * hf + g - 2 * t + 32 - 16 * i;
        BB[i][0] = band2(e, l2, h2); BB[i][1] = band2(e + 8, l2, h2); BB[i][2] = band2(e - 8, l2, h2); BB[i][3] = BB[i][0];
        if (i) { BA[i - 1][0] = band2(e, l1, h1); BA[i - 1][1] = band2(e + 8, l1, h1); BA[i - 1][2] = band2(e - 8, l1, h1); BA[i - 1][3] = BA[i - 1][0]; }
      }
    }
    const uint32_t tag = (epoch + 1) & 0xffffu;
    if (wtid == 0) { sts32(sb + TAG_OFF, tag); sts128(sb + DSK_OFF, dA.x, dA.y, dB.x, dB.y); }
    STAMP(3);
    mbar_wait(sb + B_RAW);
    STAMP(4);
    {
      const uint32_t dst = sb + CH_OFF + (g & 3) * CH_BYTES + U_OFF + t * U_CS + (63 - wq * 16) * 16;
#pragma unroll
      for (int h = 0; h < 2; h++) {
        uint32_t r[8][4];
#pragma unroll
        for (int i = 0; i < 8; i++) ldsm4t(sb + RAW_OFF + (wq * 16 + h * 8 + i) * 512 + lane * 16, r[i][0], r[i][1], r[i][2], r[i][3]);
        if ((uint32_t)(g >> 2) == rank) {
#pragma unroll
          for (int i = 0; i < 8; i++) sts128(dst - (h * 8 + i) * 16, r[i][0], r[i][1], r[i][2], r[i][3]);
        }
      }
    }
    fence_async();
    asm volatile("mbarrier.arrive.shared::cta.b64 _, [%0];" ::"r"(sb + B_U) : "memory");
    bar_sync(5, 128);
    STAMP(5);
    {
      const int mrow = lane & 7, mi = lane >> 3;
      const uint64_t ub0 = mkdesc(sb + CH_OFF + U_OFF, U_CS, 128);
      uint32_t wa, wb;
      {
        const int c = 4 * (47 - 8 * (mi >> 1) - mrow) + 2 * hf + (mi & 1);
        wa = sb + CH_OFF + (br ? W3_OFF : W5_OFF) + (5 - (c >> 5)) * 576 + ((c & 31) >> 3) * 144 + (c & 7) * 16;
        const int c2 = c - 64, pp = c2 >> 1;
        wb = sb + CH_OFF + (br ? W7_OFF : W9_OFF) + (1 - (pp >> 5)) * 1152 + (c2 & 1) * 576 + ((pp & 31) >> 3) * 144 + (pp & 7) * 16;
      }
      {
        float w1[24];
#pragma unroll
        for (int i = 0; i < 24; i++) w1[i] = 0.f;
#pragma unroll 1
        for (int k = 0; k < 4; k++) {
          wg_fence();
#pragma unroll
          for (int i = 0; i < 3; i++)
            wgmma_rs<48, 0>(w1, BA[i][0], BA[i][1], BA[i][2], BA[i][3],
                            ub0 + (uint64_t)((k * CH_BYTES + ((2 * i + 2) & 3) * U_CS + (16 + (i == 0)) * 16) >> 4), i);
          wg_commit();
          wg_wait0();
#pragma unroll
          for (int i = 0; i < 3; i++) stsm4t(wa + k * CH_BYTES + i * 1152, PK2(w1, 8 * i), PK2(w1, 8 * i + 2), PK2(w1, 8 * i + 4), PK2(w1, 8 * i + 6));
        }
      }
      {
        float w2[2][16];
#pragma unroll
        for (int i = 0; i < 16; i++) { w2[0][i] = 0.f; w2[1][i] = 0.f; }
#pragma unroll 1
        for (int kp = 0; kp < 2; kp++) {
          wg_fence();
#pragma unroll
          for (int k = 0; k < 2; k++)
#pragma unroll
            for (int i = 0; i < 4; i++)
              wgmma_rs<32, 0>(w2[k], BB[i][0], BB[i][1], BB[i][2], BB[i][3],
                              ub0 + (uint64_t)(((2 * kp + k) * CH_BYTES + ((2 * i) & 3) * U_CS + (32 + (i < 2)) * 16) >> 4), i);
          wg_commit();
          wg_wait0();
#pragma unroll
          for (int k = 0; k < 2; k++)
#pragma unroll
            for (int i = 0; i < 2; i++)
              stsm4t(wb + (2 * kp + k) * CH_BYTES + i * 1152, PK2(w2[k], 8 * i), PK2(w2[k], 8 * i + 2), PK2(w2[k], 8 * i + 4), PK2(w2[k], 8 * i + 6));
        }
      }
    }
    fence_async();
    asm volatile("mbarrier.arrive.shared::cta.b64 _, [%0];" ::"r"(sb + B_W) : "memory");
    STAMP(7);
    {
      const int bsel = (int)rank ^ br ^ 1, xl = wtid & 63;
      uint2 gl[4];
      uint32_t ua[4][4], ub[4][4];
#pragma unroll
      for (int i = 0; i < 4; i++) skip_terms(ua[i], ub[i], sb, (2 * (i >> 1) + bsel) * 128 + (i & 1) * 64 + xl, dA, dB);
      const uint32_t yo = sb + CH_OFF + (xl & 3) * 4 + ysw(xl >> 2) + bsel * 512;
#pragma unroll
      for (int i = 0; i < 2; i++) gl[i] = gate_ld(bsel * 128 + i * 64 + xl);
#pragma unroll
      for (int slot = 0; slot < 2; slot++) {
        const int box = 2 * slot + bsel;
        uint32_t g2[2], ya[2][4], yb[2][4];
#pragma unroll
        for (int h = 0; h < 2; h++) g2[h] = gate_fin(p, gl[2 * slot + h], box * 128 + h * 64 + xl, tag);
        mbar_wait(sb + B_ST + 8 * box);
        STAMP(8 + slot);
        if (slot == 0) { gl[2] = gate_ld((2 + bsel) * 128 + xl); gl[3] = gate_ld((2 + bsel) * 128 + 64 + xl); }
#pragma unroll
        for (int h = 0; h < 2; h++) {
          const uint32_t yh = (yo ^ (h * 32)) + h * 256 + slot * 1024;
          ld4ch(ya[h], yh + Y0_OFF); ld4ch(yb[h], yh + Y0_OFF + 4096);
          if (slot) {
            uint32_t a2[4], b2[4];
            ld4ch(a2, yh + Y2_OFF - 1024); ld4ch(b2, yh + Y2_OFF - 1024 + 3072);
#pragma unroll
            for (int k = 0; k < 4; k++) { ya[h][k] = hadd2(ya[h][k], a2[k]); yb[h][k] = hadd2(yb[h][k], b2[k]); }
          }
        }
        const uint4 r0 = mix(ya[0], yb[0], ua[2 * slot], ub[2 * slot], g2[0]), r1 = mix(ya[1], yb[1], ua[2 * slot + 1], ub[2 * slot + 1], g2[1]);
        if (br == 0) { send_box(sb, slot, xl, rank, r0); send_box(sb, slot, xl + 64, rank, r1); }
        else {
          const uint32_t st = sb + RAW_OFF + slot * 4096 + xl * 16, xin = sb + XIN_OFF + slot * 2048 + xl * 16;
          mbar_wait(sb + B_X + slot * 8);
          const uint4 q0 = lds128(xin), q1 = lds128(xin + 1024);
          merge_rows(st, rank, r0, q0); merge_rows(st + 1024, rank, r1, q1);
          fence_async();
          bar_sync(6, 64);
          if (xl == 0) {
            asm volatile("cp.async.bulk.tensor.3d.global.shared::cta.bulk_group [%0, {%2, %3, %4}], [%1];"
                         ::"l"(&tm_out), "r"(sb + RAW_OFF + slot * 4096), "r"(oc0), "r"(box * 128), "r"(0) : "memory");
            asm volatile("cp.async.bulk.commit_group;" ::: "memory");
          }
        }
        STAMP(10 + slot);
      }
    }
    if (wtid == 0 && atomicAdd(&g_ticket, 1u) == NCTA + NGATE - 1) { g_ticket = 0; g_epoch = epoch + 1; }
    if (wtid == 64) asm volatile("cp.async.bulk.wait_group.read 0;" ::: "memory");
    STAMP(15);
    return;
  }
  asm volatile("barrier.cluster.arrive.relaxed.aligned;" ::: "memory");

  const int moff = (bid * 4 + (tid >> 7)) * NM + (tid & 63) * 2;
  const int brt = (tid >> 6) & 1;
  const __nv_bfloat16* const* tp = p.t + (brt ? 0 : 6);
  const uint32_t q0 = *(const uint32_t*)(tp[0] + moff), q1 = *(const uint32_t*)(tp[1] + moff);
  const uint32_t q2 = *(const uint32_t*)(tp[2] + moff), q3 = *(const uint32_t*)(tp[3] + moff);
  const uint2 ldt4 = *(const uint2*)(tp[4] + bid * 4);
  const uint32_t q4 = *(const uint32_t*)(tp[brt ? 2 : 5] + moff), q5 = *(const uint32_t*)(tp[brt ? 3 : 6] + moff);

  for (int i = wtid & 63; i < R_BR / 16; i += 64) sts128(cb + R_OFF + br * R_BR + i * 16, 0, 0, 0, 0);
  STAMP(1);

  float acc[5][4];
  float k2048 = 0.f;
  const uint32_t scr = cb + Y0_OFF + wq * SCR_BYTES;
  const uint32_t scr2 = sb + SC2_OFF + warp * 640;
  {
    const uint32_t ldt2 = (ch & 2) ? ldt4.y : ldt4.x;
    const float dt = bf_round(expf((ch & 1) ? bf_hi(ldt2) : bf_lo(ldt2)));
#pragma unroll
    for (int i = 0; i < 5; i++) acc[i][0] = acc[i][1] = acc[i][2] = acc[i][3] = 0.f;
    STAMP(2);
    const uint32_t tb = scr + lane * 16;
    const uint32_t tb1 = tb + hf * 512, tb2 = tb + (hf ^ 1) * 512;
    const uint32_t ta = scr + (lane >> 3) * 512 + (lane & 7) * 16;
    const uint32_t tc = ((lane & 8) ? scr2 : scr + 4096) + (lane >> 4) * 128 + (lane & 7) * 16;
    const uint32_t tm = scr2 + 512 + ((lane >> 3) & 1) * 64 + (lane >> 4) * 16;
#pragma unroll 1
    for (int r = 0; r < 2; r++) {
      cf c, z1, z128;
      {
        const uint32_t sh = r ? 0x3244u : 0x1044u;
        float v0 = __uint_as_float(__byte_perm(q0, 0, sh));
        const float v1 = __uint_as_float(__byte_perm(q1, 0, sh)), v2 = __uint_as_float(__byte_perm(q2, 0, sh)), v3 = __uint_as_float(__byte_perm(q3, 0, sh));
        if (br == 0) { c = cmul(cf{v2, v3}, cf{dt * __uint_as_float(__byte_perm(q4, 0, sh)), dt * __uint_as_float(__byte_perm(q5, 0, sh))}); }
        else { v0 = -bf_round(expf(v0)); c = cf{2.f * dt * v2, 2.f * dt * v3}; }
        const float xl = (dt * v0) * 1.4426950408889634f, y = dt * v1;
        z1 = cexp_p(xl, y, 1.f); z128 = cexp_p(xl, y, 128.f);
      }
      const cf z2 = csq(z1), z4 = csq(z2), z8 = csq(z4);
      const cf w8 = {z8.re, -z8.im};
      const cf z16 = csq(w8), z24 = cmul(z16, w8), z32 = csq(z16), z40 = cmul(z32, w8), z48 = csq(z24), z56 = cmul(z32, z24), z64 = csq(z32);
      const cf z256 = csq(z128), z512 = csq(z256), z1024 = csq(z512), z2048 = csq(z1024);
      {
        k2048 += fmaf(c.re, z2048.re, -c.im * z2048.im);
        if (r) {
#pragma unroll
          for (int o = 16; o; o >>= 1) k2048 += __shfl_xor_sync(0xffffffffu, k2048, o);
        }
      }
      __syncwarp();
      {
        uint32_t xr[4] = {pack_bf16(1.f, z8.re), pack_bf16(z16.re, z24.re), pack_bf16(z32.re, z40.re), pack_bf16(z48.re, z56.re)};
        uint32_t xi[4] = {pack_bf16(0.f, w8.im), pack_bf16(z16.im, z24.im), pack_bf16(z32.im, z40.im), pack_bf16(z48.im, z56.im)};
        sts128(tb1, xr[0], xr[1], xr[2], xr[3]);
        sts128(tb1 + 1024, xi[0], xi[1], xi[2], xi[3]);
        const uint32_t yr = pack_bf16(z64.re, z64.re), yi = pack_bf16(z64.im, z64.im), nyi = yi ^ 0x80008000u;
        uint32_t o[4], q[4];
#pragma unroll
        for (int i = 0; i < 4; i++) CMUL2(o[i], q[i], xr[i], xi[i], yr, yi, nyi);
        sts128(tb2, o[0], o[1], o[2], o[3]);
        sts128(tb2 + 1024, q[0], q[1], q[2], q[3]);
      }
      {
        const cf h1 = cmul(c, z128), h2 = cmul(c, z256), h3 = cmul(h1, z256), h4 = cmul(c, z512), h5 = cmul(h1, z512), h6 = cmul(h2, z512), h7 = cmul(h3, z512);
        const cf e1 = cmul(c, z1), e2 = cmul(c, z2), e3 = cmul(e1, z2), e129 = cmul(h1, z1), e130 = cmul(h1, z2), e131 = cmul(e129, z2);
        const cf e258 = cmul(h2, z2), e386 = cmul(h3, z2);
        const uint32_t pr0 = pack_bf16(c.re, e1.re), pr2 = pack_bf16(h1.re, e129.re), pi0 = pack_bf16(c.im, e1.im), pi2 = pack_bf16(h1.im, e129.im);
        sts128(tb + 4 * 512, pr0, pack_bf16(e2.re, e3.re), pr2, pack_bf16(e130.re, e131.re));
        sts128(tb + 5 * 512, pi0, pack_bf16(e2.im, e3.im), pi2, pack_bf16(e130.im, e131.im));
        uint32_t xr[4] = {pack_bf16(h2.re, e258.re), pack_bf16(h3.re, e386.re), pack_bf16(h4.re, h5.re), pack_bf16(h6.re, h7.re)};
        uint32_t xi[4] = {pack_bf16(h2.im, e258.im), pack_bf16(h3.im, e386.im), pack_bf16(h4.im, h5.im), pack_bf16(h6.im, h7.im)};
        sts128(tb + 6 * 512, xr[0], xr[1], xr[2], xr[3]);
        sts128(tb + 7 * 512, xi[0], xi[1], xi[2], xi[3]);
        xr[1] = __byte_perm(xr[0], xr[1], 0x5410); xi[1] = __byte_perm(xi[0], xi[1], 0x5410);
        xr[0] = __byte_perm(pr0, pr2, 0x5410); xi[0] = __byte_perm(pi0, pi2, 0x5410);
        const uint32_t yr = pack_bf16(z1024.re, z1024.re), yi = pack_bf16(z1024.im, z1024.im), nyi = yi ^ 0x80008000u;
        uint32_t o[4], q[4];
#pragma unroll
        for (int i = 0; i < 4; i++) CMUL2(o[i], q[i], xr[i], xi[i], yr, yi, nyi);
        sts128(tb + 8 * 512, o[0], o[1], o[2], o[3]);
        sts128(scr2 + lane * 16, q[0], q[1], q[2], q[3]);
        const uint32_t m4 = pack_bf16(z4.re, z4.im);
        sts16(scr2 + 512 + lane * 2, m4); sts16(scr2 + 576 + lane * 2, m4 >> 16);
      }
      __syncwarp();
#pragma unroll
      for (int kp = 0; kp < 2; kp++) {
        uint32_t rr[2], ri[2], yr[2], yi[2];
        ldsm4t(tc + kp * 256, rr[0], ri[0], rr[1], ri[1]);
        ldsm4(tm + kp * 32, yr[0], yi[0], yr[1], yi[1]);
#pragma unroll
        for (int k2 = 0; k2 < 2; k2++) {
          const int kk = kp * 2 + k2;
          uint32_t a0, a1, a2, a3, pr, pi, qr, qi, xr, xi;
          ldsm4t(ta + kk * 128, a0, a1, a2, a3);
          ldsm4t(ta + 2048 + kk * 128, pr, pi, qr, qi);
          const uint32_t nyi = yi[k2] ^ 0x80008000u;
          mma16816(acc[0], a0, a1, a2, a3, pr, pi);
          mma16816(acc[2], a0, a1, a2, a3, qr, qi);
          mma16816(acc[4], a0, a1, a2, a3, rr[k2], ri[k2]);
          CMUL2(xr, xi, pr, pi, yr[k2], yi[k2], nyi);
          mma16816(acc[1], a0, a1, a2, a3, xr, xi);
          CMUL2(xr, xi, qr, qi, yr[k2], yi[k2], nyi);
          mma16816(acc[3], a0, a1, a2, a3, xr, xi);
        }
      }
    }
  }
  STAMP(3);
  __syncwarp();
  {
    const uint32_t xs = scr + lane * 16;
#define OTH(i, k) __float_as_uint(acc[i][2 + (k)])
    sts128(xs, OTH(0, 0), OTH(0, 1), OTH(1, 0), OTH(1, 1));
    sts128(xs + 512, OTH(2, 0), OTH(2, 1), OTH(3, 0), OTH(3, 1));
    sts64(scr + 1024 + lane * 8, OTH(4, 0), OTH(4, 1));
    if (lane == 0) sts32(scr + 1280, __float_as_uint(k2048));
#undef OTH
  }

  bar_sync(7 + (warp >> 1), 64);
  STAMP(4);
  {
    FRESH_IDS;
    const uint32_t xo = cb + Y0_OFF + (wq ^ 1) * SCR_BYTES + lane * 16;
    const uint4 o0 = lds128(xo), o1 = lds128(xo + 512);
    const uint2 o2 = lds64(xo + 1024 - lane * 8);
    const uint32_t rb = cb + R_OFF + br * R_BR;
#define OWN(i, k) acc[i][k]
    const uint32_t vP = pack_bf16(OWN(0, 1) + __uint_as_float(o0.y), OWN(0, 0) + __uint_as_float(o0.x));
    const uint32_t vP4 = pack_bf16(OWN(1, 1) + __uint_as_float(o0.w), OWN(1, 0) + __uint_as_float(o0.z));
    const uint32_t vQ = pack_bf16(OWN(2, 1) + __uint_as_float(o1.y), OWN(2, 0) + __uint_as_float(o1.x));
    const uint32_t vQ4 = pack_bf16(OWN(3, 1) + __uint_as_float(o1.w), OWN(3, 0) + __uint_as_float(o1.z));
    const uint32_t vR = pack_bf16(OWN(4, 1) + __uint_as_float(o2.y), OWN(4, 0) + __uint_as_float(o2.x));
#undef OWN
    const int j = g + 8 * hf;
    {
      const int a = 2 * (t & 1) + 64 * (t & 2) + 8 * j;
      const uint32_t ad = rb + 2 * (RD_X0 - 1 - a);
      const uint32_t a1 = (t & 2) ? ad - 8 : ad, a2 = (t & 2) ? ad : ad - 8;
      const uint32_t w1 = (t & 2) ? vP4 : vP, w2 = (t & 2) ? vP : vP4;
      sts32(a1, w1); sts32(a2, w2);
      sts16(a1 + RD_CS + 2, w1); sts16(a1 + RD_CS + 4, w1 >> 16);
      sts16(a2 + RD_CS + 2, w2); sts16(a2 + RD_CS + 4, w2 >> 16);
    }
    if (t < 2) {
      const int b = 256 + 128 * t + 8 * j;
      const uint32_t ad = rb + 2 * (RD_X0 - 6 - b);
      const uint32_t v22 = __byte_perm(vQ4, 0, 0x3232), v00 = __byte_perm(vQ, 0, 0x3232);
      sts16(ad, vQ4);
      sts64(ad + 2, v22, __byte_perm(vQ4, vQ, 0x5432));
      sts32(ad + 10, v00);
      if (b != 256) { sts16(ad + 14, v00); sts128(ad + RD_CS + 2, vQ4, v22, vQ, v00); }
      else { sts64(ad + RD_CS + 2, vQ4, v22); sts32(ad + RD_CS + 10, vQ); sts16(ad + RD_CS + 14, v00); }
    } else {
      const uint32_t ao = rb + R_O2 + 2 * (159 - (32 * t + j)), ae = ao - (R_O2 - R_E2) + 2;
      sts16(ao, vQ4 >> 16); sts16(ao + RS_CS + 2, vQ4 >> 16); sts16(ao - 32, vQ4); sts16(ao - 32 + RS_CS + 2, vQ4);
      sts16(ae - 32, vQ); sts16(ae - 32 + RS_CS + 2, vQ);
      if (lane != 2 || hf) { sts16(ae, vQ >> 16); sts16(ae + RS_CS + 2, vQ >> 16); }
      else {
        const uint32_t vv = __byte_perm(vQ, 0, 0x3232), ad = rb + 2 * (RD_X0 - 514);
        sts16(ad, vv); sts32(ad + 2, vv); sts16(ad + 6, vv); sts64(ad + RD_CS + 2, vv, vv);
      }
    }
    {
      const uint32_t a = rb + ((g & 1) ? R_O3 : R_E3 + 2) + 2 * (159 - (64 + 16 * t + (j >> 1)));
      const bool p1024 = (lane == 0) && (hf == 0);
      const uint32_t a00 = p1024 ? rb + R_E2 + 2 * (159 - 127) : a;
      sts16(a00, vR >> 16); sts16(a00 + RS_CS + 2, vR >> 16);
      sts16(a - 16, vR); sts16(a - 16 + RS_CS + 2, vR);
      if (p1024) {
        sts32(sb + K1024_OFF + (ch * 2 + br) * 4, __byte_perm(vR, 0, 0x3232));
        const uint32_t kv = pack_bf16(k2048 + __uint_as_float(lds32(xo + 1280)), 0.f);
        sts16(rb + R_E3 + 2 * (159 - 127), kv); sts16(rb + R_E3 + 2 * (159 - 127) + RS_CS + 2, kv);
      }
    }
  }
  STAMP(5);
  asm volatile("barrier.cluster.wait.aligned;" ::: "memory");
  bar_sync(7 + (warp >> 1), 64);
  mbar_wait(sb + B_U);
  STAMP(6);

  const uint32_t zz = lds32(cb + R_OFF + br * R_BR);
  conv_dense(sb, cb, zz, br, hf);
  STAMP(8);
  {
    FRESH_IDS;
    const uint32_t rb = cb + R_OFF + br * R_BR;
    float e48[24], e32[16], h32[16], h16[8];
    const int x1 = 159 - (16 * hf + g - 2 * t + 136);
    const uint32_t fs = rb + ((g & 1) ? 2 * x1 : RS_CS + 2 * x1 + 2);
    uint32_t A[2][4][4];
    auto loadA = [&](int buf, uint32_t oe, uint32_t oo, int i0) {
#pragma unroll
      for (int a = 0; a < 2; a++) {
        const uint32_t base = fs + (a ? oo : oe);
        uint32_t* k0 = A[buf][2 * a];
        uint32_t* k1 = A[buf][2 * a + 1];
        k0[1] = ldf(base, i0, 1, 9, hf); k0[0] = ldf(base, i0 + 1, 1, 9, hf); k0[2] = ldf(base, i0 + 2, 1, 9, hf);
        k1[0] = ldf(base, i0 + 3, 1, 9, hf); k1[2] = (i0 == 8) ? 0u : A[buf ^ 1][2 * a][1];
        k0[3] = k0[0]; k1[1] = k0[2]; k1[3] = k1[0];
      }
    };
    loadA(0, R_E2, R_O2, 8);
    loadA(1, R_E2, R_O2, 4);
    mbar_wait(sb + B_W);
    const uint64_t d5 = mkdesc(cb + W5_OFF, 144, 576), d3 = mkdesc(cb + W3_OFF, 144, 576);
    const uint64_t d9 = mkdesc(cb + W9_OFF, 144, 576), d7 = mkdesc(cb + W7_OFF, 144, 576);
    const uint32_t y2d = cb + Y2_OFF + br * 3072 + ysw(32 * (5 - (lane >> 4)) + 16 * hf + (lane & 15));
    const uint32_t y3d = cb + Y3_OFF + br * 2048 + ysw(2 * (16 * hf + (lane & 15)) + (lane >> 4));
#define FAR4(N, ACC, BUF, DA, DB, OFF, FIRST)                                                            \
    wg_fence();                                                                                           \
    _Pragma("unroll") for (int k = 0; k < 4; k++) {                                                      \
      const uint32_t* a = A[BUF][k];                                                                      \
      wgmma_rs<N, 1>(ACC, a[0], a[1], a[2], a[3], ((k >> 1) ? DB : DA) + (k & 1) * 18 + (OFF), !(FIRST) || k); \
    }                                                                                                     \
    wg_commit();
    FAR4(48, e48, 0, d5, d3, 0, 1)
    wg_wait0();
    loadA(0, R_E2, R_O2, 0);
    stsm2(y2d - 5 * 512, PK2(e48, 20), PK2(e48, 22));
    stage_done(sb, 2, lane);
    FAR4(48, e48, 1, d5, d3, 36, 0)
    wg_wait0();
    loadA(1, R_E3, R_O3, 8);
    stsm2(y2d - 4 * 512, PK2(e48, 16), PK2(e48, 18));
#pragma unroll
    for (int i = 0; i < 16; i++) e32[i] = FCPY(e48, i);
    stage_done(sb, 3, lane);
    FAR4(32, e32, 0, d5, d3, 72, 0)
    FAR4(32, h32, 1, d9, d7, 0, 1)
    wg_wait1();
    loadA(0, R_E3, R_O3, 4);
    stsm4(y2d, PK2(e32, 0), PK2(e32, 2), PK2(e32, 4), PK2(e32, 6));
    stsm4(y2d - 2 * 512, PK2(e32, 8), PK2(e32, 10), PK2(e32, 12), PK2(e32, 14));
    stage_done(sb, 4, lane);
    const int wt2 = fresh_tid() & 127;
    const int x = (4 + ch) * 128 + wt2, c = x >> 2;
    const uint2 gl = gate_ld(x);
    STAMP(9);
    wg_wait0();
    stsm4(y3d, PK2(h32, 8), PK2(h32, 10), PK2(h32, 12), PK2(h32, 14));
#pragma unroll
    for (int i = 0; i < 8; i++) h16[i] = FCPY(h32, i);
    stage_done(sb, 5, lane);
    FAR4(16, h16, 0, d9, d7, 72, 0)
#undef FAR4
    const uint32_t yo = sb + CH_OFF + (x & 3) * 4 + ysw(c);
    uint32_t ua[4], ub[4], ya[4], yb[4], a2[4], b2[4], a3[4], b3[4], s2[4];
    const uint4 dd = lds128(sb + DSK_OFF);
    skip_terms(ua, ub, sb, x, make_uint2(dd.x, dd.y), make_uint2(dd.z, dd.w));
    {
      const int xa = x - 514, xb = x - 513, ca = xa >> 2, cb2 = xb >> 2;
      ld4ch(s2, sb + CH_OFF + U_OFF + (xa & 3) * 4 + (ca & 3) * U_CS + (63 - (ca >> 2)) * 16);
      ld4ch(a3, sb + CH_OFF + U_OFF + (xb & 3) * 4 + (cb2 & 3) * U_CS + (63 - (cb2 >> 2)) * 16);
#pragma unroll
      for (int k = 0; k < 4; k++) s2[k] = hadd2(s2[k], __byte_perm(s2[k], a3[k], 0x5432));
    }
    const uint32_t tag = lds32(sb + TAG_OFF);
    wg_wait0();
    stsm4(y3d + 1024, PK2(h16, 0), PK2(h16, 2), PK2(h16, 4), PK2(h16, 6));
    stage_done(sb, 6, lane);
    STAMP(10);
    const uint32_t g2 = gate_fin(p, gl, x, tag);
    mbar_wait(sb + B_ST + 8 * 4);
    const uint4 k0 = lds128(sb + K1024_OFF), k1 = lds128(sb + K1024_OFF + 16);
    const uint32_t kk[8] = {k0.x, k0.y, k0.z, k0.w, k1.x, k1.y, k1.z, k1.w};
    ld4ch(ya, yo + Y0_OFF); ld4ch(yb, yo + Y0_OFF + 4096);
    ld4ch(a2, yo + Y2_OFF - 1024); ld4ch(b2, yo + Y2_OFF - 1024 + 3072);
    mbar_wait(sb + B_ST + 8 * (5 + (ch >> 1)));
    STAMP(12);
    ld4ch(a3, yo + Y3_OFF - 2048); ld4ch(b3, yo + Y3_OFF - 2048 + 2048);
#pragma unroll
    for (int k = 0; k < 4; k++) {
      ya[k] = hadd2(ya[k], hadd2(hfma2(kk[2 * k], s2[k], a2[k]), a3[k]));
      yb[k] = hadd2(yb[k], hadd2(hfma2(kk[2 * k + 1], s2[k], b2[k]), b3[k]));
    }
    const uint4 r = mix(ya, yb, ua, ub, g2);
    if ((uint32_t)(ch & 1) != rank) send_box(sb, 2 + (ch >> 1), wt2, rank, r);
    else merge_box(sb, &tm_out, 2 + (ch >> 1), wt2, rank, oc0, r, 1 + ch);
    if (wt2 == 0) asm volatile("cp.async.bulk.wait_group.read 0;" ::: "memory");
  }
  STAMP(14);
  STAMP(15); GT(1);
}

typedef CUresult (*EncodeFn)(CUtensorMap*, CUtensorMapDataType, cuuint32_t, void*, const cuuint64_t*, const cuuint64_t*,
                             const cuuint32_t*, const cuuint32_t*, CUtensorMapInterleave, CUtensorMapSwizzle,
                             CUtensorMapL2promotion, CUtensorMapFloatOOBfill);

}

extern "C" void kernel_launch(void* const* d_in, const int* in_sizes, int n_in, void* d_out, int out_size) {
  (void)in_sizes; (void)n_in; (void)out_size;
  typedef const __nv_bfloat16* bp;
  Params p;
  p.t[0] = (bp)d_in[10]; p.t[1] = (bp)d_in[11]; p.t[2] = (bp)d_in[12]; p.t[3] = (bp)d_in[13]; p.t[4] = (bp)d_in[14]; p.t[5] = nullptr;
  p.t[6] = (bp)d_in[1]; p.t[7] = (bp)d_in[2]; p.t[8] = (bp)d_in[5]; p.t[9] = (bp)d_in[6]; p.t[10] = (bp)d_in[7];
  p.t[11] = (bp)d_in[3]; p.t[12] = (bp)d_in[4]; p.t[13] = nullptr;
  p.u = (bp)d_in[0]; p.gw = (bp)d_in[16]; p.A_D = (bp)d_in[8]; p.B_D = (bp)d_in[15];
  static EncodeFn enc = nullptr;
  if (!enc) {
    cudaDriverEntryPointQueryResult qr;
    cudaGetDriverEntryPoint("cuTensorMapEncodeTiled", (void**)&enc, cudaEnableDefault, &qr);
    cudaFuncSetAttribute(ssm_kernel, cudaFuncAttributeMaxDynamicSharedMemorySize, SMEM_BYTES);
  }
  CUtensorMap tm_in, tm_out;
  {
    cuuint64_t gd[5] = {512, 2, 4, 4, 64};
    cuuint64_t gs[4] = {1024, 8192, 2048, 32768};
    cuuint32_t bx[5] = {8, 2, 4, 4, 32};
    cuuint32_t es[5] = {1, 1, 1, 1, 1};
    enc(&tm_in, CU_TENSOR_MAP_DATA_TYPE_BFLOAT16, 5, d_in[0], gd, gs, bx, es, CU_TENSOR_MAP_INTERLEAVE_NONE,
        CU_TENSOR_MAP_SWIZZLE_NONE, CU_TENSOR_MAP_L2_PROMOTION_NONE, CU_TENSOR_MAP_FLOAT_OOB_FILL_NONE);
  }
  {
    cuuint64_t gd[3] = {512, 1024, 2};
    cuuint64_t gs[2] = {2048, 1024};
    cuuint32_t bx[3] = {8, 128, 2};
    cuuint32_t es[3] = {1, 1, 1};
    enc(&tm_out, CU_TENSOR_MAP_DATA_TYPE_BFLOAT16, 3, d_out, gd, gs, bx, es, CU_TENSOR_MAP_INTERLEAVE_NONE,
        CU_TENSOR_MAP_SWIZZLE_NONE, CU_TENSOR_MAP_L2_PROMOTION_NONE, CU_TENSOR_MAP_FLOAT_OOB_FILL_NONE);
  }
  ssm_kernel<<<NCTA + NGATE, 640, SMEM_BYTES, cudaStreamPerThread>>>(p, tm_in, tm_out);
}
```

```cpp
#include <cuda_runtime.h>
#include <cuda.h>
#include <cuda_bf16.h>
#include <stdint.h>

namespace {
#define PREDLD 1
#define FCPY(v, i) (((i) % 3 == 2) ? __uint_as_float(opq(__float_as_uint(v[i]), zz)) : opqf(v[i], zz))

constexpr int L = 2048, D = 512, NM = 128;
constexpr int NCTA = 128;
constexpr int NGATE = 4;

constexpr int RAW_OFF = 0;
constexpr int XIN_OFF = 32768;
constexpr int SC2_OFF = XIN_OFF + 8192;
constexpr int BAR_OFF = SC2_OFF + 10240;
constexpr int CH_OFF = BAR_OFF + 256;
constexpr int U_CS = 1184;
constexpr int U_OFF = 0;
constexpr int R_OFF = 4736;
constexpr int RD_X0 = 565;
constexpr int RD_CS = 1216;
constexpr int RS_CS = 320;
constexpr int R_E2 = 2 * RD_CS, R_O2 = R_E2 + 2 * RS_CS, R_E3 = R_O2 + 2 * RS_CS, R_O3 = R_E3 + 2 * RS_CS + 16;
constexpr int R_BR = R_O3 + 2 * RS_CS - 16;
constexpr int W5_OFF = R_OFF + 2 * R_BR;
constexpr int W3_OFF = W5_OFF + 3456;
constexpr int W9_OFF = W3_OFF + 3456;
constexpr int W7_OFF = W9_OFF + 2304;
constexpr int Y0_OFF = W7_OFF + 2304;
constexpr int Y2_OFF = Y0_OFF + 8192, Y3_OFF = Y2_OFF + 6144;
constexpr int CH_BYTES = Y0_OFF + 18432 + 16;
constexpr int SCR_BYTES = 4608;
constexpr int SMEM_BYTES = CH_OFF + 4 * CH_BYTES;
static_assert(CH_BYTES % 128 == 16, "bank staggering of the channel blocks");
static_assert(SMEM_BYTES <= 232448, "smem");
constexpr int B_RAW = BAR_OFF, B_X = BAR_OFF + 8, B_U = BAR_OFF + 40, B_W = BAR_OFF + 48;
constexpr int TAG_OFF = BAR_OFF + 56;
constexpr int K1024_OFF = BAR_OFF + 64;
constexpr int DSK_OFF = BAR_OFF + 160;
constexpr int B_ST = BAR_OFF + 96;

__device__ __align__(16) unsigned int g_gate[L];
__device__ unsigned int g_epoch;
__device__ unsigned int g_ticket;

#define STAMP(k)
#define GT(k)

struct Params {
  const __nv_bfloat16* t[14];
  const __nv_bfloat16 *u, *gw, *A_D, *B_D;
};

template <int N, int TB> __device__ __forceinline__ void wgmma_rs(float* d, uint32_t a0, uint32_t a1, uint32_t a2, uint32_t a3, uint64_t desc, int sc);
template <> __device__ __forceinline__ void wgmma_rs<64, 0>(float* d, uint32_t a0, uint32_t a1, uint32_t a2, uint32_t a3, uint64_t desc, int sc) {
  asm volatile("{\n.reg .pred p;\nsetp.ne.b32 p, %37, 0;\n"
    "wgmma.mma_async.sync.aligned.m64n64k16.f32.bf16.bf16 {%0,%1,%2,%3,%4,%5,%6,%7,%8,%9,%10,%11,%12,%13,%14,%15,%16,%17,%18,%19,%20,%21,%22,%23,%24,%25,%26,%27,%28,%29,%30,%31}, {%32,%33,%34,%35}, %36, p, 1, 1, 0;\n}"
    : "+f"(d[0]), "+f"(d[1]), "+f"(d[2]), "+f"(d[3]), "+f"(d[4]), "+f"(d[5]), "+f"(d[6]), "+f"(d[7]), "+f"(d[8]), "+f"(d[9]), "+f"(d[10]), "+f"(d[11]), "+f"(d[12]), "+f"(d[13]), "+f"(d[14]), "+f"(d[15]), "+f"(d[16]), "+f"(d[17]), "+f"(d[18]), "+f"(d[19]), "+f"(d[20]), "+f"(d[21]), "+f"(d[22]), "+f"(d[23]), "+f"(d[24]), "+f"(d[25]), "+f"(d[26]), "+f"(d[27]), "+f"(d[28]), "+f"(d[29]), "+f"(d[30]), "+f"(d[31]) : "r"(a0), "r"(a1), "r"(a2), "r"(a3), "l"(desc), "r"(sc));
}
template <> __device__ __forceinline__ void wgmma_rs<56, 0>(float* d, uint32_t a0, uint32_t a1, uint32_t a2, uint32_t a3, uint64_t desc, int sc) {
  asm volatile("{\n.reg .pred p;\nsetp.ne.b32 p, %33, 0;\n"
    "wgmma.mma_async.sync.aligned.m64n56k16.f32.bf16.bf16 {%0,%1,%2,%3,%4,%5,%6,%7,%8,%9,%10,%11,%12,%13,%14,%15,%16,%17,%18,%19,%20,%21,%22,%23,%24,%25,%26,%27}, {%28,%29,%30,%31}, %32, p, 1, 1, 0;\n}"
    : "+f"(d[0]), "+f"(d[1]), "+f"(d[2]), "+f"(d[3]), "+f"(d[4]), "+f"(d[5]), "+f"(d[6]), "+f"(d[7]), "+f"(d[8]), "+f"(d[9]), "+f"(d[10]), "+f"(d[11]), "+f"(d[12]), "+f"(d[13]), "+f"(d[14]), "+f"(d[15]), "+f"(d[16]), "+f"(d[17]), "+f"(d[18]), "+f"(d[19]), "+f"(d[20]), "+f"(d[21]), "+f"(d[22]), "+f"(d[23]), "+f"(d[24]), "+f"(d[25]), "+f"(d[26]), "+f"(d[27]) : "r"(a0), "r"(a1), "r"(a2), "r"(a3), "l"(desc), "r"(sc));
}
template <> __device__ __forceinline__ void wgmma_rs<48, 0>(float* d, uint32_t a0, uint32_t a1, uint32_t a2, uint32_t a3, uint64_t desc, int sc) {
  asm volatile("{\n.reg .pred p;\nsetp.ne.b32 p, %29, 0;\n"
    "wgmma.mma_async.sync.aligned.m64n48k16.f32.bf16.bf16 {%0,%1,%2,%3,%4,%5,%6,%7,%8,%9,%10,%11,%12,%13,%14,%15,%16,%17,%18,%19,%20,%21,%22,%23}, {%24,%25,%26,%27}, %28, p, 1, 1, 0;\n}"
    : "+f"(d[0]), "+f"(d[1]), "+f"(d[2]), "+f"(d[3]), "+f"(d[4]), "+f"(d[5]), "+f"(d[6]), "+f"(d[7]), "+f"(d[8]), "+f"(d[9]), "+f"(d[10]), "+f"(d[11]), "+f"(d[12]), "+f"(d[13]), "+f"(d[14]), "+f"(d[15]), "+f"(d[16]), "+f"(d[17]), "+f"(d[18]), "+f"(d[19]), "+f"(d[20]), "+f"(d[21]), "+f"(d[22]), "+f"(d[23]) : "r"(a0), "r"(a1), "r"(a2), "r"(a3), "l"(desc), "r"(sc));
}
template <> __device__ __forceinline__ void wgmma_rs<32, 0>(float* d, uint32_t a0, uint32_t a1, uint32_t a2, uint32_t a3, uint64_t desc, int sc) {
  asm volatile("{\n.reg .pred p;\nsetp.ne.b32 p, %21, 0;\n"
    "wgmma.mma_async.sync.aligned.m64n32k16.f32.bf16.bf16 {%0,%1,%2,%3,%4,%5,%6,%7,%8,%9,%10,%11,%12,%13,%14,%15}, {%16,%17,%18,%19}, %20, p, 1, 1, 0;\n}"
    : "+f"(d[0]), "+f"(d[1]), "+f"(d[2]), "+f"(d[3]), "+f"(d[4]), "+f"(d[5]), "+f"(d[6]), "+f"(d[7]), "+f"(d[8]), "+f"(d[9]), "+f"(d[10]), "+f"(d[11]), "+f"(d[12]), "+f"(d[13]), "+f"(d[14]), "+f"(d[15]) : "r"(a0), "r"(a1), "r"(a2), "r"(a3), "l"(desc), "r"(sc));
}
template <> __device__ __forceinline__ void wgmma_rs<48, 1>(float* d, uint32_t a0, uint32_t a1, uint32_t a2, uint32_t a3, uint64_t desc, int sc) {
  asm volatile("{\n.reg .pred p;\nsetp.ne.b32 p, %29, 0;\n"
    "wgmma.mma_async.sync.aligned.m64n48k16.f32.bf16.bf16 {%0,%1,%2,%3,%4,%5,%6,%7,%8,%9,%10,%11,%12,%13,%14,%15,%16,%17,%18,%19,%20,%21,%22,%23}, {%24,%25,%26,%27}, %28, p, 1, 1, 1;\n}"
    : "+f"(d[0]), "+f"(d[1]), "+f"(d[2]), "+f"(d[3]), "+f"(d[4]), "+f"(d[5]), "+f"(d[6]), "+f"(d[7]), "+f"(d[8]), "+f"(d[9]), "+f"(d[10]), "+f"(d[11]), "+f"(d[12]), "+f"(d[13]), "+f"(d[14]), "+f"(d[15]), "+f"(d[16]), "+f"(d[17]), "+f"(d[18]), "+f"(d[19]), "+f"(d[20]), "+f"(d[21]), "+f"(d[22]), "+f"(d[23]) : "r"(a0), "r"(a1), "r"(a2), "r"(a3), "l"(desc), "r"(sc));
}
template <> __device__ __forceinline__ void wgmma_rs<32, 1>(float* d, uint32_t a0, uint32_t a1, uint32_t a2, uint32_t a3, uint64_t desc, int sc) {
  asm volatile("{\n.reg .pred p;\nsetp.ne.b32 p, %21, 0;\n"
    "wgmma.mma_async.sync.aligned.m64n32k16.f32.bf16.bf16 {%0,%1,%2,%3,%4,%5,%6,%7,%8,%9,%10,%11,%12,%13,%14,%15}, {%16,%17,%18,%19}, %20, p, 1, 1, 1;\n}"
    : "+f"(d[0]), "+f"(d[1]), "+f"(d[2]), "+f"(d[3]), "+f"(d[4]), "+f"(d[5]), "+f"(d[6]), "+f"(d[7]), "+f"(d[8]), "+f"(d[9]), "+f"(d[10]), "+f"(d[11]), "+f"(d[12]), "+f"(d[13]), "+f"(d[14]), "+f"(d[15]) : "r"(a0), "r"(a1), "r"(a2), "r"(a3), "l"(desc), "r"(sc));
}
template <> __device__ __forceinline__ void wgmma_rs<16, 1>(float* d, uint32_t a0, uint32_t a1, uint32_t a2, uint32_t a3, uint64_t desc, int sc) {
  asm volatile("{\n.reg .pred p;\nsetp.ne.b32 p, %13, 0;\n"
    "wgmma.mma_async.sync.aligned.m64n16k16.f32.bf16.bf16 {%0,%1,%2,%3,%4,%5,%6,%7}, {%8,%9,%10,%11}, %12, p, 1, 1, 1;\n}"
    : "+f"(d[0]), "+f"(d[1]), "+f"(d[2]), "+f"(d[3]), "+f"(d[4]), "+f"(d[5]), "+f"(d[6]), "+f"(d[7]) : "r"(a0), "r"(a1), "r"(a2), "r"(a3), "l"(desc), "r"(sc));
}

__device__ __forceinline__ uint32_t pack_bf16(float lo, float hi) {
  uint32_t r; asm("cvt.rn.bf16x2.f32 %0, %1, %2;" : "=r"(r) : "f"(hi), "f"(lo)); return r;
}
__device__ __forceinline__ float bf_lo(uint32_t v) { return __uint_as_float(v << 16); }
__device__ __forceinline__ float bf_hi(uint32_t v) { return __uint_as_float(v & 0xffff0000u); }
__device__ __forceinline__ float bf_round(float x) { return bf_lo(pack_bf16(x, 0.f)); }
__device__ __forceinline__ uint32_t hmul2(uint32_t a, uint32_t b) { uint32_t r; asm("mul.rn.bf16x2 %0, %1, %2;" : "=r"(r) : "r"(a), "r"(b)); return r; }
__device__ __forceinline__ uint32_t hadd2(uint32_t a, uint32_t b) { uint32_t r; asm("add.rn.bf16x2 %0, %1, %2;" : "=r"(r) : "r"(a), "r"(b)); return r; }
__device__ __forceinline__ uint32_t hsub2(uint32_t a, uint32_t b) { uint32_t r; asm("sub.rn.bf16x2 %0, %1, %2;" : "=r"(r) : "r"(a), "r"(b)); return r; }
__device__ __forceinline__ uint32_t hfma2(uint32_t a, uint32_t b, uint32_t c) { uint32_t r; asm("fma.rn.bf16x2 %0, %1, %2, %3;" : "=r"(r) : "r"(a), "r"(b), "r"(c)); return r; }

__device__ __forceinline__ void sts16(uint32_t a, uint32_t v) { asm volatile("st.shared.b16 [%0], %1;" ::"r"(a), "h"((unsigned short)v) : "memory"); }
__device__ __forceinline__ void sts32(uint32_t a, uint32_t v) { asm volatile("st.shared.b32 [%0], %1;" ::"r"(a), "r"(v) : "memory"); }
__device__ __forceinline__ void sts64(uint32_t a, uint32_t x, uint32_t y) { asm volatile("st.shared.v2.b32 [%0], {%1,%2};" ::"r"(a), "r"(x), "r"(y) : "memory"); }
__device__ __forceinline__ void sts128(uint32_t a, uint32_t x, uint32_t y, uint32_t z, uint32_t w) {
  asm volatile("st.shared.v4.b32 [%0], {%1,%2,%3,%4};" ::"r"(a), "r"(x), "r"(y), "r"(z), "r"(w) : "memory");
}
__device__ __forceinline__ uint32_t lds32(uint32_t a) { uint32_t v; asm volatile("ld.shared.b32 %0, [%1];" : "=r"(v) : "r"(a) : "memory"); return v; }
__device__ __forceinline__ uint32_t ldf(uint32_t base, int i, int lo0, int hi0, int hf) {
  if (i < lo0 || i > hi0 + 2) return 0u;
  if (i < lo0 + 2 || i > hi0) {
    uint32_t v;
    asm volatile("{\n.reg .pred p;\nsetp.eq.b32 p, %2, %3;\nmov.b32 %0, 0;\n@p ld.shared.b32 %0, [%1];\n}" : "=r"(v) : "r"(base + i * 16), "r"(hf), "r"(i > hi0 ? 1 : 0) : "memory");
    return v;
  }
  return lds32(base + i * 16);
}
__device__ __forceinline__ uint2 lds64(uint32_t a) { uint2 v; asm volatile("ld.shared.v2.b32 {%0,%1}, [%2];" : "=r"(v.x), "=r"(v.y) : "r"(a) : "memory"); return v; }
__device__ __forceinline__ uint4 lds128(uint32_t a) {
  uint4 v; asm volatile("ld.shared.v4.b32 {%0,%1,%2,%3}, [%4];" : "=r"(v.x), "=r"(v.y), "=r"(v.z), "=r"(v.w) : "r"(a) : "memory"); return v;
}
__device__ __forceinline__ uint4 ldg128(const void* a) {
  uint4 v; asm volatile("ld.global.nc.v4.b32 {%0,%1,%2,%3}, [%4];" : "=r"(v.x), "=r"(v.y), "=r"(v.z), "=r"(v.w) : "l"(a) : "memory"); return v;
}
__device__ __forceinline__ uint2 ldg64(const void* a) {
  uint2 v; asm volatile("ld.global.nc.v2.b32 {%0,%1}, [%2];" : "=r"(v.x), "=r"(v.y) : "l"(a) : "memory"); return v;
}
__device__ __forceinline__ void ldsm4(uint32_t a, uint32_t& r0, uint32_t& r1, uint32_t& r2, uint32_t& r3) {
  asm volatile("ldmatrix.sync.aligned.m8n8.x4.shared.b16 {%0,%1,%2,%3}, [%4];" : "=r"(r0), "=r"(r1), "=r"(r2), "=r"(r3) : "r"(a) : "memory");
}
__device__ __forceinline__ void ldsm4t(uint32_t a, uint32_t& r0, uint32_t& r1, uint32_t& r2, uint32_t& r3) {
  asm volatile("ldmatrix.sync.aligned.m8n8.x4.trans.shared.b16 {%0,%1,%2,%3}, [%4];" : "=r"(r0), "=r"(r1), "=r"(r2), "=r"(r3) : "r"(a) : "memory");
}
__device__ __forceinline__ void stsm4(uint32_t a, uint32_t r0, uint32_t r1, uint32_t r2, uint32_t r3) {
  asm volatile("stmatrix.sync.aligned.m8n8.x4.shared.b16 [%0], {%1,%2,%3,%4};" ::"r"(a), "r"(r0), "r"(r1), "r"(r2), "r"(r3) : "memory");
}
__device__ __forceinline__ void stsm4t(uint32_t a, uint32_t r0, uint32_t r1, uint32_t r2, uint32_t r3) {
  asm volatile("stmatrix.sync.aligned.m8n8.x4.trans.shared.b16 [%0], {%1,%2,%3,%4};" ::"r"(a), "r"(r0), "r"(r1), "r"(r2), "r"(r3) : "memory");
}
__device__ __forceinline__ void stsm2(uint32_t a, uint32_t r0, uint32_t r1) {
  asm volatile("stmatrix.sync.aligned.m8n8.x2.shared.b16 [%0], {%1,%2};" ::"r"(a), "r"(r0), "r"(r1) : "memory");
}
__device__ __forceinline__ void stsm2t(uint32_t a, uint32_t r0, uint32_t r1) {
  asm volatile("stmatrix.sync.aligned.m8n8.x2.trans.shared.b16 [%0], {%1,%2};" ::"r"(a), "r"(r0), "r"(r1) : "memory");
}
__device__ __forceinline__ void mma16816(float* c, uint32_t a0, uint32_t a1, uint32_t a2, uint32_t a3, uint32_t b0, uint32_t b1) {
  asm("mma.sync.aligned.m16n8k16.row.col.f32.bf16.bf16.f32 {%0,%1,%2,%3}, {%4,%5,%6,%7}, {%8,%9}, {%0,%1,%2,%3};"
      : "+f"(c[0]), "+f"(c[1]), "+f"(c[2]), "+f"(c[3]) : "r"(a0), "r"(a1), "r"(a2), "r"(a3), "r"(b0), "r"(b1));
}
__device__ __forceinline__ void bar_sync(int id, int n) { asm volatile("bar.sync %0, %1;" ::"r"(id), "r"(n) : "memory"); }
__device__ __forceinline__ void wg_fence() { asm volatile("wgmma.fence.sync.aligned;" ::: "memory"); }
__device__ __forceinline__ void wg_commit() { asm volatile("wgmma.commit_group.sync.aligned;" ::: "memory"); }
__device__ __forceinline__ void wg_wait0() { asm volatile("wgmma.wait_group.sync.aligned 0;" ::: "memory"); }
__device__ __forceinline__ void wg_wait1() { asm volatile("wgmma.wait_group.sync.aligned 1;" ::: "memory"); }
__device__ __forceinline__ void fence_async() { asm volatile("fence.proxy.async.shared::cta;" ::: "memory"); }
__device__ __forceinline__ uint32_t opq(uint32_t x, uint32_t z) { uint32_t r; asm volatile("xor.b32 %0, %1, %2;" : "=r"(r) : "r"(x), "r"(z)); return r; }
__device__ __forceinline__ float opqf(float x, uint32_t z) { float r; asm volatile("add.rn.f32 %0, %1, %2;" : "=f"(r) : "f"(x), "f"(__uint_as_float(z))); return r; }
__device__ __forceinline__ int fresh_tid() { int v; asm volatile("mov.u32 %0, %%tid.x;" : "=r"(v)); return v; }
#define FRESH_IDS const int tid = fresh_tid(), lane = tid & 31, g = lane >> 2, t = lane & 3, wtid = tid & 127; (void)g; (void)t; (void)wtid
__device__ __forceinline__ uint64_t mkdesc(uint32_t addr, uint32_t lbo, uint32_t sbo) {
  return (uint64_t)((addr & 0x3FFFF) >> 4) | ((uint64_t)(lbo >> 4) << 16) | ((uint64_t)(sbo >> 4) << 32);
}
__device__ __forceinline__ uint32_t mapa(uint32_t a, uint32_t rank) {
  uint32_t r; asm("mapa.shared::cluster.u32 %0, %1, %2;" : "=r"(r) : "r"(a), "r"(rank)); return r;
}
__device__ __forceinline__ void mbar_init_expect(uint32_t bar, uint32_t bytes) {
  asm volatile("mbarrier.init.shared::cta.b64 [%0], 1;" ::"r"(bar) : "memory");
  asm volatile("mbarrier.arrive.expect_tx.shared::cta.b64 _, [%0], %1;" ::"r"(bar), "r"(bytes) : "memory");
}
__device__ __forceinline__ void mbar_wait(uint32_t bar) {
#pragma unroll 1
  for (int it = 0; it < (1 << 22); it++) {
    uint32_t ok;
    asm volatile("{\n.reg .pred p;\nmbarrier.try_wait.parity.acquire.cluster.shared::cta.b64 p, [%1], 0;\nselp.u32 %0, 1, 0, p;\n}"
                 : "=r"(ok) : "r"(bar) : "memory");
    if (ok) return;
  }
  __trap();
}
__device__ __forceinline__ void st_async4(uint32_t a, uint32_t bar, uint32_t x, uint32_t y, uint32_t z, uint32_t w) {
  asm volatile("st.async.weak.shared::cluster.mbarrier::complete_tx::bytes.v4.b32 [%0], {%2,%3,%4,%5}, [%1];"
               ::"r"(a), "r"(bar), "r"(x), "r"(y), "r"(z), "r"(w) : "memory");
}

struct cf { float re, im; };
__device__ __forceinline__ cf cmul(cf a, cf b) { return {fmaf(a.re, b.re, -a.im * b.im), fmaf(a.re, b.im, a.im * b.re)}; }
__device__ __forceinline__ cf csq(cf a) { return {fmaf(a.re, a.re, -a.im * a.im), (a.re + a.re) * a.im}; }
__device__ __forceinline__ cf cexp_p(float xl, float y, float p) {
  float mag; asm("ex2.approx.ftz.f32 %0, %1;" : "=f"(mag) : "f"(xl * p));
  const float th = y * p;
  const float k = __fadd_rn(fmaf(th, 0.15915494309189535f, 12582912.f), -12582912.f);
  float r = fmaf(k, -6.2831854820251465f, th);
  r = fmaf(k, 1.7484555314695172e-07f, r);
  return {mag * __cosf(r), mag * __sinf(r)};
}
__device__ __forceinline__ uint32_t ysw(int c) { return (uint32_t)(c ^ ((c >> 3) & 3)) * 16u; }

#define CMUL2(OR, OI, xr, xi, yr, yi, nyi) do { OR = hfma2(xr, yr, hmul2(xi, nyi)); OI = hfma2(xr, yi, hmul2(xi, yr)); } while (0)

__device__ __forceinline__ uint32_t gate_slow(const __nv_bfloat16* u, const __nv_bfloat16* gw, int row) {
  float s = 0.f;
  const uint32_t* xr = (const uint32_t*)(u + (size_t)row * D);
  const uint32_t* wr = (const uint32_t*)gw;
#pragma unroll 1
  for (int j = 0; j < D / 2; j++) { const uint32_t pr = hmul2(xr[j], wr[j]); s += bf_lo(pr); s += bf_hi(pr); }
  s = bf_round(s);
  return pack_bf16(1.f / (1.f + expf(-s)), 0.f);
}

__device__ __forceinline__ uint2 gate_ld(int x) {
  uint2 gv;
  asm volatile("ld.relaxed.gpu.global.v2.u32 {%0,%1}, [%2];" : "=r"(gv.x), "=r"(gv.y) : "l"(g_gate + x * 2) : "memory");
  return gv;
}
__device__ __noinline__ uint32_t gate_poll(const Params* pp, int x, uint32_t tag) {
  uint2 gv;
#pragma unroll 1
  for (int spins = 0; spins < (1 << 16); spins++) {
    gv = gate_ld(x);
    if ((gv.x >> 16) == tag && (gv.y >> 16) == tag) return __byte_perm(gv.x, gv.y, 0x5410);
  }
  return __byte_perm(gate_slow(pp->u, pp->gw, x * 2), gate_slow(pp->u, pp->gw, x * 2 + 1), 0x5410);
}
__device__ __forceinline__ uint32_t gate_fin(const Params& p, uint2 gv, int x, uint32_t tag) {
  if ((gv.x >> 16) == tag && (gv.y >> 16) == tag) return __byte_perm(gv.x, gv.y, 0x5410);
  return gate_poll(&p, x, tag);
}

__device__ __forceinline__ void ld4ch(uint32_t* v, uint32_t addr) {
#pragma unroll
  for (int k = 0; k < 4; k++) v[k] = lds32(addr + k * CH_BYTES);
}
__device__ __forceinline__ void skip_terms(uint32_t* ua, uint32_t* ub, uint32_t sb, int x, uint2 dA, uint2 dB) {
  const int c = x >> 2;
  uint32_t uu[4];
  ld4ch(uu, sb + CH_OFF + (x & 3) * 4 + U_OFF + (c & 3) * U_CS + (63 - (c >> 2)) * 16);
#pragma unroll
  for (int k = 0; k < 4; k++) {
    ua[k] = hmul2(uu[k], __byte_perm((k & 2) ? dA.y : dA.x, 0, (k & 1) ? 0x3232 : 0x1010));
    ub[k] = hmul2(uu[k], __byte_perm((k & 2) ? dB.y : dB.x, 0, (k & 1) ? 0x3232 : 0x1010));
  }
}
__device__ __forceinline__ uint4 mix(const uint32_t* a, const uint32_t* b, const uint32_t* ua, const uint32_t* ub, uint32_t g2) {
  const uint32_t h2 = hsub2(0x3f803f80u, g2);
  uint32_t o[4];
#pragma unroll
  for (int k = 0; k < 4; k++) o[k] = hadd2(hmul2(g2, hadd2(a[k], ua[k])), hmul2(h2, hadd2(b[k], ub[k])));
  return make_uint4(__byte_perm(o[0], o[1], 0x5410), __byte_perm(o[2], o[3], 0x5410), __byte_perm(o[0], o[1], 0x7632), __byte_perm(o[2], o[3], 0x7632));
}
__device__ __forceinline__ void send_box(uint32_t sb, int slot, int wtid, uint32_t rank, uint4 r) {
  st_async4(mapa(sb + XIN_OFF + slot * 2048 + wtid * 16, rank ^ 1), mapa(sb + B_X + slot * 8, rank ^ 1), r.x, r.y, r.z, r.w);
}
__device__ __forceinline__ void merge_rows(uint32_t st, uint32_t rank, uint4 r, uint4 q) {
  const uint4 lo = rank ? q : r, hi = rank ? r : q;
  sts128(st, lo.x, lo.y, hi.x, hi.y); sts128(st + 2048, lo.z, lo.w, hi.z, hi.w);
}
__device__ __forceinline__ void merge_box(uint32_t sb, const CUtensorMap* tm_out, int slot, int wtid, uint32_t rank, int oc0, uint4 r, int barid) {
  const uint32_t st = sb + RAW_OFF + slot * 4096 + wtid * 16;
  mbar_wait(sb + B_X + slot * 8);
  merge_rows(st, rank, r, lds128(sb + XIN_OFF + slot * 2048 + wtid * 16));
  fence_async();
  bar_sync(barid, 128);
  if (wtid == 0) {
    asm volatile("cp.async.bulk.tensor.3d.global.shared::cta.bulk_group [%0, {%2, %3, %4}], [%1];"
                 ::"l"(tm_out), "r"(sb + RAW_OFF + slot * 4096), "r"(oc0), "r"((2 * slot + (int)rank) * 128), "r"(0) : "memory");
    asm volatile("cp.async.bulk.commit_group;" ::: "memory");
  }
}

__device__ __forceinline__ uint32_t band2(int e, int lo, int hi) {
  uint32_t r = ((uint32_t)(e - lo) <= (uint32_t)(hi - lo) ? 0x3f80u : 0u) | ((uint32_t)(e - 1 - lo) <= (uint32_t)(hi - lo) ? 0x3f800000u : 0u);
  asm volatile("" : "+r"(r));
  return r;
}

__device__ __forceinline__ void stage_done(uint32_t sb, int stage, int lane) {
  __syncwarp();
  if (lane == 0) asm volatile("mbarrier.arrive.shared::cta.b64 _, [%0];" ::"r"(sb + B_ST + 8 * stage) : "memory");
}
#define PK2(v, i) pack_bf16(v[i], v[(i) + 1])

__device__ __forceinline__ void conv_dense(uint32_t sb, uint32_t cb, uint32_t zz, int br, int hf) {
  FRESH_IDS;
  const uint32_t rb = cb + R_OFF + br * R_BR;
  const int eo = 16 * hf + g - 2 * t;
  const int x0 = RD_X0 - (eo + 536);
  const uint32_t fa = rb + ((g & 1) ? 2 * x0 : RD_CS + 2 * x0 + 2);
  const uint64_t ub = mkdesc(cb + U_OFF, U_CS, 128);
  const uint32_t yd = cb + Y0_OFF + br * 4096 + ysw(4 * (63 - 8 * (lane >> 4) - (lane & 7)) + 2 * hf + ((lane >> 3) & 1));
  uint32_t A[2][4][4];
  float e64[32], e56[28];
  auto loadA = [&](int j) {
#pragma unroll
    for (int k = 0; k < 4; k++) {
      const int s = 34 - 4 * j - k;
      if (s >= 0) {
        if (k == 0 && j == 0) A[0][0][2] = ldf(fa, 2 * s + 2, 2, 67, hf);
        A[j & 1][k][0] = ldf(fa, 2 * s + 1, 2, 67, hf);
        A[j & 1][k][1] = ldf(fa, 2 * s, 2, 67, hf);
      }
    }
#pragma unroll
    for (int k = 0; k < 4; k++) {
      if (34 - 4 * j - k >= 0) {
        A[j & 1][k][3] = A[j & 1][k][0];
        if (k) A[j & 1][k][2] = A[j & 1][k - 1][1];
        else if (j) A[j & 1][0][2] = A[(j - 1) & 1][3][1];
      }
    }
  };
  loadA(0); loadA(1);
#pragma unroll
  for (int j = 0; j < 9; j++) {
    if (j == 4) {
      wg_wait0();
      stsm2t(yd - 7 * 512, PK2(e64, 28), PK2(e64, 30));
#pragma unroll
      for (int i = 0; i < 28; i++) e56[i] = FCPY(e64, i);
      stage_done(sb, 0, lane);
    }
    if (j == 8) {
      wg_wait0();
      stsm2t(yd - 6 * 512, PK2(e56, 24), PK2(e56, 26));
      stage_done(sb, 1, lane);
    }
    wg_fence();
#pragma unroll
    for (int k = 0; k < 4; k++) {
      const int s = 34 - 4 * j - k;
      if (s >= 0) {
        const int o = 2 * s - 66 + 128;
        const int cc = o & 3, rs = (o >> 2) - 32;
        const uint64_t desc = ub + (uint64_t)((cc * U_CS - rs * 16) >> 4);
        const uint32_t* a = A[j & 1][k];
        if (j < 4) wgmma_rs<64, 0>(e64, a[0], a[1], a[2], a[3], desc, s != 34);
        else wgmma_rs<56, 0>(e56, a[0], a[1], a[2], a[3], desc, 1);
      }
    }
    wg_commit();
    if (j >= 1 && j < 8) { wg_wait1(); loadA(j + 1); }
  }
  wg_wait0();
#pragma unroll
  for (int i = 0; i < 6; i += 2) stsm4t(yd - i * 512, PK2(e56, 4 * i), PK2(e56, 4 * i + 2), PK2(e56, 4 * i + 4), PK2(e56, 4 * i + 6));
}

__device__ __noinline__ unsigned int gate_rows(const Params* pp, int grow, int step, int rend) {
  const __nv_bfloat16 *u = pp->u, *gw = pp->gw;
  const int lane = threadIdx.x & 31;
  uint4 nx[4][2];
#pragma unroll
  for (int i = 0; i < 4; i++) {
    nx[i][0] = ldg128(u + (size_t)(grow + i) * D + lane * 8);
    nx[i][1] = ldg128(u + (size_t)(grow + i) * D + 256 + lane * 8);
  }
  const uint4 gw0 = ldg128(gw + lane * 8), gw1 = ldg128(gw + 256 + lane * 8);
  const uint32_t ws[8] = {gw0.x, gw0.y, gw0.z, gw0.w, gw1.x, gw1.y, gw1.z, gw1.w};
  unsigned int epoch;
  asm volatile("ld.relaxed.gpu.global.u32 %0, [%1];" : "=r"(epoch) : "l"(&g_epoch) : "memory");
#pragma unroll 1
  for (; grow < rend; grow += step) {
    const int nrow = (grow + step < rend) ? grow + step : grow;
    float c[2][4];
#pragma unroll
    for (int i = 0; i < 2; i++) {
      const uint4 *x = nx[2 * i], *y = nx[2 * i + 1];
      const uint32_t xs[8] = {x[0].x, x[0].y, x[0].z, x[0].w, x[1].x, x[1].y, x[1].z, x[1].w};
      const uint32_t ys[8] = {y[0].x, y[0].y, y[0].z, y[0].w, y[1].x, y[1].y, y[1].z, y[1].w};
      uint32_t px[8], py[8];
#pragma unroll
      for (int j = 0; j < 8; j++) { px[j] = hmul2(xs[j], ws[j]); py[j] = hmul2(ys[j], ws[j]); }
      if (nrow != grow) {
#pragma unroll
        for (int k = 2 * i; k < 2 * i + 2; k++) {
          nx[k][0] = ldg128(u + (size_t)(nrow + k) * D + lane * 8);
          nx[k][1] = ldg128(u + (size_t)(nrow + k) * D + 256 + lane * 8);
        }
      }
      c[i][0] = c[i][1] = c[i][2] = c[i][3] = 0.f;
#pragma unroll
      for (int j = 0; j < 8; j += 2) mma16816(c[i], px[j], py[j], px[j + 1], py[j + 1], 0x3f803f80u, 0x3f803f80u);
    }
    float s = (lane & 2) ? ((lane & 1) ? c[1][2] : c[1][0]) : ((lane & 1) ? c[0][2] : c[0][0]);
#pragma unroll
    for (int o = 4; o < 32; o <<= 1) s += __shfl_xor_sync(0xffffffffu, s, o);
    s = bf_round(s);
    const float gv = 1.f / (1.f + expf(-s));
    const uint32_t w = ((epoch + 1) << 16) | (pack_bf16(gv, 0.f) & 0xffffu);
    if (lane < 4) asm volatile("st.relaxed.gpu.global.u32 [%0], %1;" ::"l"(&g_gate[grow + lane]), "r"(w) : "memory");
  }
  return epoch;
}
#define GW 1
constexpr int GSPLIT = L - 4 * GW * NCTA;
__device__ __noinline__ void gate_cta(const Params* pp) {
  const unsigned int epoch = gate_rows(pp, (blockIdx.x * 20 + (threadIdx.x >> 5)) * 4, 80 * NGATE, GSPLIT);
  __syncthreads();
  if (threadIdx.x == 0 && atomicAdd(&g_ticket, 1u) == NCTA + NGATE - 1) { g_ticket = 0; g_epoch = epoch + 1; }
}

__global__ void __cluster_dims__(2, 1, 1) __launch_bounds__(640, 1)
ssm_kernel(const __grid_constant__ Params p, const __grid_constant__ CUtensorMap tm_in, const __grid_constant__ CUtensorMap tm_out) {
  extern __shared__ __align__(1024) unsigned char smem_raw[];
  const uint32_t sb = (uint32_t)__cvta_generic_to_shared(smem_raw);
  const int tid = threadIdx.x, lane = tid & 31;
  const int warp = __shfl_sync(0xffffffffu, tid >> 5, 0);
  const int ch = warp >> 2, wq = warp & 3, br = wq >> 1, hf = wq & 1;
  const int g = lane >> 2, t = lane & 3;
  if (__builtin_expect(blockIdx.x < NGATE, 0)) { gate_cta(&p); return; }
  const int bid = blockIdx.x - NGATE;
  const uint32_t rank = blockIdx.x & 1;
  const uint32_t cb = sb + CH_OFF + ch * CH_BYTES;
  const int wtid = tid & 127;
  const int oc0 = (bid >> 1) * 8;
  STAMP(0); GT(0);

  if (warp >= 16) {
    if (wtid == 0) {
      mbar_init_expect(sb + B_RAW, 32768);
#pragma unroll
      for (int i = 0; i < 4; i++) mbar_init_expect(sb + B_X + 8 * i, 2048);
      asm volatile("mbarrier.init.shared::cta.b64 [%0], 128;" ::"r"(sb + B_U) : "memory");
      asm volatile("mbarrier.init.shared::cta.b64 [%0], 128;" ::"r"(sb + B_W) : "memory");
#pragma unroll
      for (int i = 0; i < 7; i++) asm volatile("mbarrier.init.shared::cta.b64 [%0], 16;" ::"r"(sb + B_ST + 8 * i) : "memory");
      asm volatile("fence.mbarrier_init.release.cluster;" ::: "memory");
      asm volatile("fence.proxy.async.shared::cta;" ::: "memory");
    }
    __syncwarp();
    asm volatile("barrier.cluster.arrive.relaxed.aligned;" ::: "memory");
    if (wq >= 4 - GW) gate_rows(&p, GSPLIT + (bid * GW + 3 - wq) * 4, L, L);
    unsigned int epoch;
    asm volatile("ld.relaxed.gpu.global.u32 %0, [%1];" : "=r"(epoch) : "l"(&g_epoch) : "memory");
    asm volatile("barrier.cluster.wait.aligned;" ::: "memory");
    if (wtid == 0) {
      asm volatile("cp.async.bulk.tensor.5d.shared::cluster.global.mbarrier::complete_tx::bytes.multicast::cluster [%0], [%1, {%3, %4, %4, %4, %5}], [%2], %6;"
                   ::"r"(sb + RAW_OFF + rank * 16384), "l"(&tm_in), "r"(sb + B_RAW), "r"(oc0), "r"(0), "r"((int)rank * 32), "h"((unsigned short)3) : "memory");
    }
    sts128(sb + CH_OFF + wq * CH_BYTES + U_OFF + (lane >> 3) * U_CS + (64 + (lane & 7)) * 16, 0, 0, 0, 0);
    const uint2 dA = ldg64(p.A_D + bid * 4), dB = ldg64(p.B_D + bid * 4);
    uint32_t BA[3][4], BB[4][4];
    {
      const int l1 = br ? 3 : 6, h1 = br ? 5 : 10, l2 = br ? 5 : 12, h2 = br ? 11 : 20;
#pragma unroll
      for (int i = 0; i < 4; i++) {
        const int e = 16 * hf + g - 2 * t + 32 - 16 * i;
        BB[i][0] = band2(e, l2, h2); BB[i][1] = band2(e + 8, l2, h2); BB[i][2] = band2(e - 8, l2, h2); BB[i][3] = BB[i][0];
        if (i) { BA[i - 1][0] = band2(e, l1, h1); BA[i - 1][1] = band2(e + 8, l1, h1); BA[i - 1][2] = band2(e - 8, l1, h1); BA[i - 1][3] = BA[i - 1][0]; }
      }
    }
    const uint32_t tag = (epoch + 1) & 0xffffu;
    if (wtid == 0) { sts32(sb + TAG_OFF, tag); sts128(sb + DSK_OFF, dA.x, dA.y, dB.x, dB.y); }
    STAMP(3);
    mbar_wait(sb + B_RAW);
    STAMP(4);
    {
      const uint32_t dst = sb + CH_OFF + (g & 3) * CH_BYTES + U_OFF + t * U_CS + (63 - wq * 16) * 16;
#pragma unroll
      for (int h = 0; h < 2; h++) {
        uint32_t r[8][4];
#pragma unroll
        for (int i = 0; i < 8; i++) ldsm4t(sb + RAW_OFF + (wq * 16 + h * 8 + i) * 512 + lane * 16, r[i][0], r[i][1], r[i][2], r[i][3]);
        if ((uint32_t)(g >> 2) == rank) {
#pragma unroll
          for (int i = 0; i < 8; i++) sts128(dst - (h * 8 + i) * 16, r[i][0], r[i][1], r[i][2], r[i][3]);
        }
      }
    }
    fence_async();
    asm volatile("mbarrier.arrive.shared::cta.b64 _, [%0];" ::"r"(sb + B_U) : "memory");
    bar_sync(5, 128);
    STAMP(5);
    {
      const int mrow = lane & 7, mi = lane >> 3;
      const uint64_t ub0 = mkdesc(sb + CH_OFF + U_OFF, U_CS, 128);
      uint32_t wa, wb;
      {
        const int c = 4 * (47 - 8 * (mi >> 1) - mrow) + 2 * hf + (mi & 1);
        wa = sb + CH_OFF + (br ? W3_OFF : W5_OFF) + (5 - (c >> 5)) * 576 + ((c & 31) >> 3) * 144 + (c & 7) * 16;
        const int c2 = c - 64, pp = c2 >> 1;
        wb = sb + CH_OFF + (br ? W7_OFF : W9_OFF) + (1 - (pp >> 5)) * 1152 + (c2 & 1) * 576 + ((pp & 31) >> 3) * 144 + (pp & 7) * 16;
      }
      {
        float w1[24];
#pragma unroll
        for (int i = 0; i < 24; i++) w1[i] = 0.f;
#pragma unroll 1
        for (int k = 0; k < 4; k++) {
          wg_fence();
#pragma unroll
          for (int i = 0; i < 3; i++)
            wgmma_rs<48, 0>(w1, BA[i][0], BA[i][1], BA[i][2], BA[i][3],
                            ub0 + (uint64_t)((k * CH_BYTES + ((2 * i + 2) & 3) * U_CS + (16 + (i == 0)) * 16) >> 4), i);
          wg_commit();
          wg_wait0();
#pragma unroll
          for (int i = 0; i < 3; i++) stsm4t(wa + k * CH_BYTES + i * 1152, PK2(w1, 8 * i), PK2(w1, 8 * i + 2), PK2(w1, 8 * i + 4), PK2(w1, 8 * i + 6));
        }
      }
      {
        float w2[2][16];
#pragma unroll
        for (int i = 0; i < 16; i++) { w2[0][i] = 0.f; w2[1][i] = 0.f; }
#pragma unroll 1
        for (int kp = 0; kp < 2; kp++) {
          wg_fence();
#pragma unroll
          for (int k = 0; k < 2; k++)
#pragma unroll
            for (int i = 0; i < 4; i++)
              wgmma_rs<32, 0>(w2[k], BB[i][0], BB[i][1], BB[i][2], BB[i][3],
                              ub0 + (uint64_t)(((2 * kp + k) * CH_BYTES + ((2 * i) & 3) * U_CS + (32 + (i < 2)) * 16) >> 4), i);
          wg_commit();
          wg_wait0();
#pragma unroll
          for (int k = 0; k < 2; k++)
#pragma unroll
            for (int i = 0; i < 2; i++)
              stsm4t(wb + (2 * kp + k) * CH_BYTES + i * 1152, PK2(w2[k], 8 * i), PK2(w2[k], 8 * i + 2), PK2(w2[k], 8 * i + 4), PK2(w2[k], 8 * i + 6));
        }
      }
    }
    fence_async();
    asm volatile("mbarrier.arrive.shared::cta.b64 _, [%0];" ::"r"(sb + B_W) : "memory");
    STAMP(7);
    {
      const int bsel = (int)rank ^ br ^ 1, xl = wtid & 63;
      uint2 gl[4];
      uint32_t ua[4][4], ub[4][4];
#pragma unroll
      for (int i = 0; i < 4; i++) skip_terms(ua[i], ub[i], sb, (2 * (i >> 1) + bsel) * 128 + (i & 1) * 64 + xl, dA, dB);
      const uint32_t yo = sb + CH_OFF + (xl & 3) * 4 + ysw(xl >> 2) + bsel * 512;
#pragma unroll
      for (int i = 0; i < 2; i++) gl[i] = gate_ld(bsel * 128 + i * 64 + xl);
#pragma unroll
      for (int slot = 0; slot < 2; slot++) {
        const int box = 2 * slot + bsel;
        uint32_t g2[2], ya[2][4], yb[2][4];
#pragma unroll
        for (int h = 0; h < 2; h++) g2[h] = gate_fin(p, gl[2 * slot + h], box * 128 + h * 64 + xl, tag);
        mbar_wait(sb + B_ST + 8 * box);
        STAMP(8 + slot);
        if (slot == 0) { gl[2] = gate_ld((2 + bsel) * 128 + xl); gl[3] = gate_ld((2 + bsel) * 128 + 64 + xl); }
#pragma unroll
        for (int h = 0; h < 2; h++) {
          const uint32_t yh = (yo ^ (h * 32)) + h * 256 + slot * 1024;
          ld4ch(ya[h], yh + Y0_OFF); ld4ch(yb[h], yh + Y0_OFF + 4096);
          if (slot) {
            uint32_t a2[4], b2[4];
            ld4ch(a2, yh + Y2_OFF - 1024); ld4ch(b2, yh + Y2_OFF - 1024 + 3072);
#pragma unroll
            for (int k = 0; k < 4; k++) { ya[h][k] = hadd2(ya[h][k], a2[k]); yb[h][k] = hadd2(yb[h][k], b2[k]); }
          }
        }
        const uint4 r0 = mix(ya[0], yb[0], ua[2 * slot], ub[2 * slot], g2[0]), r1 = mix(ya[1], yb[1], ua[2 * slot + 1], ub[2 * slot + 1], g2[1]);
        if (br == 0) { send_box(sb, slot, xl, rank, r0); send_box(sb, slot, xl + 64, rank, r1); }
        else {
          const uint32_t st = sb + RAW_OFF + slot * 4096 + xl * 16, xin = sb + XIN_OFF + slot * 2048 + xl * 16;
          mbar_wait(sb + B_X + slot * 8);
          const uint4 q0 = lds128(xin), q1 = lds128(xin + 1024);
          merge_rows(st, rank, r0, q0); merge_rows(st + 1024, rank, r1, q1);
          fence_async();
          bar_sync(6, 64);
          if (xl == 0) {
            asm volatile("cp.async.bulk.tensor.3d.global.shared::cta.bulk_group [%0, {%2, %3, %4}], [%1];"
                         ::"l"(&tm_out), "r"(sb + RAW_OFF + slot * 4096), "r"(oc0), "r"(box * 128), "r"(0) : "memory");
            asm volatile("cp.async.bulk.commit_group;" ::: "memory");
          }
        }
        STAMP(10 + slot);
      }
    }
    if (wtid == 0 && atomicAdd(&g_ticket, 1u) == NCTA + NGATE - 1) { g_ticket = 0; g_epoch = epoch + 1; }
    if (wtid == 64) asm volatile("cp.async.bulk.wait_group.read 0;" ::: "memory");
    STAMP(15);
    return;
  }
  asm volatile("barrier.cluster.arrive.relaxed.aligned;" ::: "memory");

  const int moff = (bid * 4 + (tid >> 7)) * NM + (tid & 63) * 2;
  const int brt = (tid >> 6) & 1;
  const __nv_bfloat16* const* tp = p.t + (brt ? 0 : 6);
  const uint32_t q0 = *(const uint32_t*)(tp[0] + moff), q1 = *(const uint32_t*)(tp[1] + moff);
  const uint32_t q2 = *(const uint32_t*)(tp[2] + moff), q3 = *(const uint32_t*)(tp[3] + moff);
  const uint2 ldt4 = *(const uint2*)(tp[4] + bid * 4);
  const uint32_t q4 = *(const uint32_t*)(tp[brt ? 2 : 5] + moff), q5 = *(const uint32_t*)(tp[brt ? 3 : 6] + moff);

  for (int i = wtid & 63; i < R_BR / 16; i += 64) sts128(cb + R_OFF + br * R_BR + i * 16, 0, 0, 0, 0);
  STAMP(1);

  float acc[5][4];
  float k2048 = 0.f;
  const uint32_t scr = cb + Y0_OFF + wq * SCR_BYTES;
  const uint32_t scr2 = sb + SC2_OFF + warp * 640;
  {
    const uint32_t ldt2 = (ch & 2) ? ldt4.y : ldt4.x;
    const float dt = bf_round(expf((ch & 1) ? bf_hi(ldt2) : bf_lo(ldt2)));
#pragma unroll
    for (int i = 0; i < 5; i++) acc[i][0] = acc[i][1] = acc[i][2] = acc[i][3] = 0.f;
    STAMP(2);
    const uint32_t tb = scr + lane * 16;
    const uint32_t tb1 = tb + hf * 512, tb2 = tb + (hf ^ 1) * 512;
    const uint32_t ta = scr + (lane >> 3) * 512 + (lane & 7) * 16;
    const uint32_t tc = ((lane & 8) ? scr2 : scr + 4096) + (lane >> 4) * 128 + (lane & 7) * 16;
    const uint32_t tm = scr2 + 512 + ((lane >> 3) & 1) * 64 + (lane >> 4) * 16;
#pragma unroll 1
    for (int r = 0; r < 2; r++) {
      cf c, z1, z128;
      {
        const uint32_t sh = r ? 0x3244u : 0x1044u;
        float v0 = __uint_as_float(__byte_perm(q0, 0, sh));
        const float v1 = __uint_as_float(__byte_perm(q1, 0, sh)), v2 = __uint_as_float(__byte_perm(q2, 0, sh)), v3 = __uint_as_float(__byte_perm(q3, 0, sh));
        if (br == 0) { c = cmul(cf{v2, v3}, cf{dt * __uint_as_float(__byte_perm(q4, 0, sh)), dt * __uint_as_float(__byte_perm(q5, 0, sh))}); }
        else { v0 = -bf_round(expf(v0)); c = cf{2.f * dt * v2, 2.f * dt * v3}; }
        const float xl = (dt * v0) * 1.4426950408889634f, y = dt * v1;
        z1 = cexp_p(xl, y, 1.f); z128 = cexp_p(xl, y, 128.f);
      }
      const cf z2 = csq(z1), z4 = csq(z2), z8 = csq(z4);
      const cf w8 = {z8.re, -z8.im};
      const cf z16 = csq(w8), z24 = cmul(z16, w8), z32 = csq(z16), z40 = cmul(z32, w8), z48 = csq(z24), z56 = cmul(z32, z24), z64 = csq(z32);
      const cf z256 = csq(z128), z512 = csq(z256), z1024 = csq(z512), z2048 = csq(z1024);
      {
        k2048 += fmaf(c.re, z2048.re, -c.im * z2048.im);
        if (r) {
#pragma unroll
          for (int o = 16; o; o >>= 1) k2048 += __shfl_xor_sync(0xffffffffu, k2048, o);
        }
      }
      __syncwarp();
      {
        uint32_t xr[4] = {pack_bf16(1.f, z8.re), pack_bf16(z16.re, z24.re), pack_bf16(z32.re, z40.re), pack_bf16(z48.re, z56.re)};
        uint32_t xi[4] = {pack_bf16(0.f, w8.im), pack_bf16(z16.im, z24.im), pack_bf16(z32.im, z40.im), pack_bf16(z48.im, z56.im)};
        sts128(tb1, xr[0], xr[1], xr[2], xr[3]);
        sts128(tb1 + 1024, xi[0], xi[1], xi[2], xi[3]);
        const uint32_t yr = pack_bf16(z64.re, z64.re), yi = pack_bf16(z64.im, z64.im), nyi = yi ^ 0x80008000u;
        uint32_t o[4], q[4];
#pragma unroll
        for (int i = 0; i < 4; i++) CMUL2(o[i], q[i], xr[i], xi[i], yr, yi, nyi);
        sts128(tb2, o[0], o[1], o[2], o[3]);
        sts128(tb2 + 1024, q[0], q[1], q[2], q[3]);
      }
      {
        const cf h1 = cmul(c, z128), h2 = cmul(c, z256), h3 = cmul(h1, z256), h4 = cmul(c, z512), h5 = cmul(h1, z512), h6 = cmul(h2, z512), h7 = cmul(h3, z512);
        const cf e1 = cmul(c, z1), e2 = cmul(c, z2), e3 = cmul(e1, z2), e129 = cmul(h1, z1), e130 = cmul(h1, z2), e131 = cmul(e129, z2);
        const cf e258 = cmul(h2, z2), e386 = cmul(h3, z2);
        const uint32_t pr0 = pack_bf16(c.re, e1.re), pr2 = pack_bf16(h1.re, e129.re), pi0 = pack_bf16(c.im, e1.im), pi2 = pack_bf16(h1.im, e129.im);
        sts128(tb + 4 * 512, pr0, pack_bf16(e2.re, e3.re), pr2, pack_bf16(e130.re, e131.re));
        sts128(tb + 5 * 512, pi0, pack_bf16(e2.im, e3.im), pi2, pack_bf16(e130.im, e131.im));
        uint32_t xr[4] = {pack_bf16(h2.re, e258.re), pack_bf16(h3.re, e386.re), pack_bf16(h4.re, h5.re), pack_bf16(h6.re, h7.re)};
        uint32_t xi[4] = {pack_bf16(h2.im, e258.im), pack_bf16(h3.im, e386.im), pack_bf16(h4.im, h5.im), pack_bf16(h6.im, h7.im)};
        sts128(tb + 6 * 512, xr[0], xr[1], xr[2], xr[3]);
        sts128(tb + 7 * 512, xi[0], xi[1], xi[2], xi[3]);
        xr[1] = __byte_perm(xr[0], xr[1], 0x5410); xi[1] = __byte_perm(xi[0], xi[1], 0x5410);
        xr[0] = __byte_perm(pr0, pr2, 0x5410); xi[0] = __byte_perm(pi0, pi2, 0x5410);
        const uint32_t yr = pack_bf16(z1024.re, z1024.re), yi = pack_bf16(z1024.im, z1024.im), nyi = yi ^ 0x80008000u;
        uint32_t o[4], q[4];
#pragma unroll
        for (int i = 0; i < 4; i++) CMUL2(o[i], q[i], xr[i], xi[i], yr, yi, nyi);
        sts128(tb + 8 * 512, o[0], o[1], o[2], o[3]);
        sts128(scr2 + lane * 16, q[0], q[1], q[2], q[3]);
        const uint32_t m4 = pack_bf16(z4.re, z4.im);
        sts16(scr2 + 512 + lane * 2, m4); sts16(scr2 + 576 + lane * 2, m4 >> 16);
      }
      __syncwarp();
#pragma unroll
      for (int kp = 0; kp < 2; kp++) {
        uint32_t rr[2], ri[2], yr[2], yi[2];
        ldsm4t(tc + kp * 256, rr[0], ri[0], rr[1], ri[1]);
        ldsm4(tm + kp * 32, yr[0], yi[0], yr[1], yi[1]);
#pragma unroll
        for (int k2 = 0; k2 < 2; k2++) {
          const int kk = kp * 2 + k2;
          uint32_t a0, a1, a2, a3, pr, pi, qr, qi, xr, xi;
          ldsm4t(ta + kk * 128, a0, a1, a2, a3);
          ldsm4t(ta + 2048 + kk * 128, pr, pi, qr, qi);
          const uint32_t nyi = yi[k2] ^ 0x80008000u;
          mma16816(acc[0], a0, a1, a2, a3, pr, pi);
          mma16816(acc[2], a0, a1, a2, a3, qr, qi);
          mma16816(acc[4], a0, a1, a2, a3, rr[k2], ri[k2]);
          CMUL2(xr, xi, pr, pi, yr[k2], yi[k2], nyi);
          mma16816(acc[1], a0, a1, a2, a3, xr, xi);
          CMUL2(xr, xi, qr, qi, yr[k2], yi[k2], nyi);
          mma16816(acc[3], a0, a1, a2, a3, xr, xi);
        }
      }
    }
  }
  STAMP(3);
  __syncwarp();
  {
    const uint32_t xs = scr + lane * 16;
#define OTH(i, k) __float_as_uint(acc[i][2 + (k)])
    sts128(xs, OTH(0, 0), OTH(0, 1), OTH(1, 0), OTH(1, 1));
    sts128(xs + 512, OTH(2, 0), OTH(2, 1), OTH(3, 0), OTH(3, 1));
    sts64(scr + 1024 + lane * 8, OTH(4, 0), OTH(4, 1));
    if (lane == 0) sts32(scr + 1280, __float_as_uint(k2048));
#undef OTH
  }

  bar_sync(7 + (warp >> 1), 64);
  STAMP(4);
  {
    FRESH_IDS;
    const uint32_t xo = cb + Y0_OFF + (wq ^ 1) * SCR_BYTES + lane * 16;
    const uint4 o0 = lds128(xo), o1 = lds128(xo + 512);
    const uint2 o2 = lds64(xo + 1024 - lane * 8);
    const uint32_t rb = cb + R_OFF + br * R_BR;
#define OWN(i, k) acc[i][k]
    const uint32_t vP = pack_bf16(OWN(0, 1) + __uint_as_float(o0.y), OWN(0, 0) + __uint_as_float(o0.x));
    const uint32_t vP4 = pack_bf16(OWN(1, 1) + __uint_as_float(o0.w), OWN(1, 0) + __uint_as_float(o0.z));
    const uint32_t vQ = pack_bf16(OWN(2, 1) + __uint_as_float(o1.y), OWN(2, 0) + __uint_as_float(o1.x));
    const uint32_t vQ4 = pack_bf16(OWN(3, 1) + __uint_as_float(o1.w), OWN(3, 0) + __uint_as_float(o1.z));
    const uint32_t vR = pack_bf16(OWN(4, 1) + __uint_as_float(o2.y), OWN(4, 0) + __uint_as_float(o2.x));
#undef OWN
    const int j = g + 8 * hf;
    {
      const int a = 2 * (t & 1) + 64 * (t & 2) + 8 * j;
      const uint32_t ad = rb + 2 * (RD_X0 - 1 - a);
      const uint32_t a1 = (t & 2) ? ad - 8 : ad, a2 = (t & 2) ? ad : ad - 8;
      const uint32_t w1 = (t & 2) ? vP4 : vP, w2 = (t & 2) ? vP : vP4;
      sts32(a1, w1); sts32(a2, w2);
      sts16(a1 + RD_CS + 2, w1); sts16(a1 + RD_CS + 4, w1 >> 16);
      sts16(a2 + RD_CS + 2, w2); sts16(a2 + RD_CS + 4, w2 >> 16);
    }
    if (t < 2) {
      const int b = 256 + 128 * t + 8 * j;
      const uint32_t ad = rb + 2 * (RD_X0 - 6 - b);
      const uint32_t v22 = __byte_perm(vQ4, 0, 0x3232), v00 = __byte_perm(vQ, 0, 0x3232);
      sts16(ad, vQ4);
      sts64(ad + 2, v22, __byte_perm(vQ4, vQ, 0x5432));
      sts32(ad + 10, v00);
      if (b != 256) { sts16(ad + 14, v00); sts128(ad + RD_CS + 2, vQ4, v22, vQ, v00); }
      else { sts64(ad + RD_CS + 2, vQ4, v22); sts32(ad + RD_CS + 10, vQ); sts16(ad + RD_CS + 14, v00); }
    } else {
      const uint32_t ao = rb + R_O2 + 2 * (159 - (32 * t + j)), ae = ao - (R_O2 - R_E2) + 2;
      sts16(ao, vQ4 >> 16); sts16(ao + RS_CS + 2, vQ4 >> 16); sts16(ao - 32, vQ4); sts16(ao - 32 + RS_CS + 2, vQ4);
      sts16(ae - 32, vQ); sts16(ae - 32 + RS_CS + 2, vQ);
      if (lane != 2 || hf) { sts16(ae, vQ >> 16); sts16(ae + RS_CS + 2, vQ >> 16); }
      else {
        const uint32_t vv = __byte_perm(vQ, 0, 0x3232), ad = rb + 2 * (RD_X0 - 514);
        sts16(ad, vv); sts32(ad + 2, vv); sts16(ad + 6, vv); sts64(ad + RD_CS + 2, vv, vv);
      }
    }
    {
      const uint32_t a = rb + ((g & 1) ? R_O3 : R_E3 + 2) + 2 * (159 - (64 + 16 * t + (j >> 1)));
      const bool p1024 = (lane == 0) && (hf == 0);
      const uint32_t a00 = p1024 ? rb + R_E2 + 2 * (159 - 127) : a;
      sts16(a00, vR >> 16); sts16(a00 + RS_CS + 2, vR >> 16);
      sts16(a - 16, vR); sts16(a - 16 + RS_CS + 2, vR);
      if (p1024) {
        sts32(sb + K1024_OFF + (ch * 2 + br) * 4, __byte_perm(vR, 0, 0x3232));
        const uint32_t kv = pack_bf16(k2048 + __uint_as_float(lds32(xo + 1280)), 0.f);
        sts16(rb + R_E3 + 2 * (159 - 127), kv); sts16(rb + R_E3 + 2 * (159 - 127) + RS_CS + 2, kv);
      }
    }
  }
  STAMP(5);
  asm volatile("barrier.cluster.wait.aligned;" ::: "memory");
  bar_sync(7 + (warp >> 1), 64);
  mbar_wait(sb + B_U);
  STAMP(6);

  const uint32_t zz = lds32(cb + R_OFF + br * R_BR);
  conv_dense(sb, cb, zz, br, hf);
  STAMP(8);
  {
    FRESH_IDS;
    const uint32_t rb = cb + R_OFF + br * R_BR;
    float e48[24], e32[16], h32[16], h16[8];
    const int x1 = 159 - (16 * hf + g - 2 * t + 136);
    const uint32_t fs = rb + ((g & 1) ? 2 * x1 : RS_CS + 2 * x1 + 2);
    uint32_t A[2][4][4];
    auto loadA = [&](int buf, uint32_t oe, uint32_t oo, int i0) {
#pragma unroll
      for (int a = 0; a < 2; a++) {
        const uint32_t base = fs + (a ? oo : oe);
        uint32_t* k0 = A[buf][2 * a];
        uint32_t* k1 = A[buf][2 * a + 1];
        k0[1] = ldf(base, i0, 1, 9, hf); k0[0] = ldf(base, i0 + 1, 1, 9, hf); k0[2] = ldf(base, i0 + 2, 1, 9, hf);
        k1[0] = ldf(base, i0 + 3, 1, 9, hf); k1[2] = (i0 == 8) ? 0u : A[buf ^ 1][2 * a][1];
        k0[3] = k0[0]; k1[1] = k0[2]; k1[3] = k1[0];
      }
    };
    loadA(0, R_E2, R_O2, 8);
    loadA(1, R_E2, R_O2, 4);
    mbar_wait(sb + B_W);
    const uint64_t d5 = mkdesc(cb + W5_OFF, 144, 576), d3 = mkdesc(cb + W3_OFF, 144, 576);
    const uint64_t d9 = mkdesc(cb + W9_OFF, 144, 576), d7 = mkdesc(cb + W7_OFF, 144, 576);
    const uint32_t y2d = cb + Y2_OFF + br * 3072 + ysw(32 * (5 - (lane >> 4)) + 16 * hf + (lane & 15));
    const uint32_t y3d = cb + Y3_OFF + br * 2048 + ysw(2 * (16 * hf + (lane & 15)) + (lane >> 4));
#define FAR4(N, ACC, BUF, DA, DB, OFF, FIRST)                                                            \
    wg_fence();                                                                                           \
    _Pragma("unroll") for (int k = 0; k < 4; k++) {                                                      \
      const uint32_t* a = A[BUF][k];                                                                      \
      wgmma_rs<N, 1>(ACC, a[0], a[1], a[2], a[3], ((k >> 1) ? DB : DA) + (k & 1) * 18 + (OFF), !(FIRST) || k); \
    }                                                                                                     \
    wg_commit();
    FAR4(48, e48, 0, d5, d3, 0, 1)
    wg_wait0();
    loadA(0, R_E2, R_O2, 0);
    stsm2(y2d - 5 * 512, PK2(e48, 20), PK2(e48, 22));
    stage_done(sb, 2, lane);
    FAR4(48, e48, 1, d5, d3, 36, 0)
    wg_wait0();
    loadA(1, R_E3, R_O3, 8);
    stsm2(y2d - 4 * 512, PK2(e48, 16), PK2(e48, 18));
#pragma unroll
    for (int i = 0; i < 16; i++) e32[i] = FCPY(e48, i);
    stage_done(sb, 3, lane);
    FAR4(32, e32, 0, d5, d3, 72, 0)
    FAR4(32, h32, 1, d9, d7, 0, 1)
    wg_wait1();
    loadA(0, R_E3, R_O3, 4);
    stsm4(y2d, PK2(e32, 0), PK2(e32, 2), PK2(e32, 4), PK2(e32, 6));
    stsm4(y2d - 2 * 512, PK2(e32, 8), PK2(e32, 10), PK2(e32, 12), PK2(e32, 14));
    stage_done(sb, 4, lane);
    const int wt2 = fresh_tid() & 127;
    const int x = (4 + ch) * 128 + wt2, c = x >> 2;
    const uint2 gl = gate_ld(x);
    STAMP(9);
    wg_wait0();
    stsm4(y3d, PK2(h32, 8), PK2(h32, 10), PK2(h32, 12), PK2(h32, 14));
#pragma unroll
    for (int i = 0; i < 8; i++) h16[i] = FCPY(h32, i);
    stage_done(sb, 5, lane);
    FAR4(16, h16, 0, d9, d7, 72, 0)
#undef FAR4
    const uint32_t yo = sb + CH_OFF + (x & 3) * 4 + ysw(c);
    uint32_t ua[4], ub[4], ya[4], yb[4], a2[4], b2[4], a3[4], b3[4], s2[4];
    const uint4 dd = lds128(sb + DSK_OFF);
    skip_terms(ua, ub, sb, x, make_uint2(dd.x, dd.y), make_uint2(dd.z, dd.w));
    {
      const int xa = x - 514, xb = x - 513, ca = xa >> 2, cb2 = xb >> 2;
      ld4ch(s2, sb + CH_OFF + U_OFF + (xa & 3) * 4 + (ca & 3) * U_CS + (63 - (ca >> 2)) * 16);
      ld4ch(a3, sb + CH_OFF + U_OFF + (xb & 3) * 4 + (cb2 & 3) * U_CS + (63 - (cb2 >> 2)) * 16);
#pragma unroll
      for (int k = 0; k < 4; k++) s2[k] = hadd2(s2[k], __byte_perm(s2[k], a3[k], 0x5432));
    }
    const uint32_t tag = lds32(sb + TAG_OFF);
    wg_wait0();
    stsm4(y3d + 1024, PK2(h16, 0), PK2(h16, 2), PK2(h16, 4), PK2(h16, 6));
    stage_done(sb, 6, lane);
    STAMP(10);
    const uint32_t g2 = gate_fin(p, gl, x, tag);
    mbar_wait(sb + B_ST + 8 * 4);
    const uint4 k0 = lds128(sb + K1024_OFF), k1 = lds128(sb + K1024_OFF + 16);
    const uint32_t kk[8] = {k0.x, k0.y, k0.z, k0.w, k1.x, k1.y, k1.z, k1.w};
    ld4ch(ya, yo + Y0_OFF); ld4ch(yb, yo + Y0_OFF + 4096);
    ld4ch(a2, yo + Y2_OFF - 1024); ld4ch(b2, yo + Y2_OFF - 1024 + 3072);
    mbar_wait(sb + B_ST + 8 * (5 + (ch >> 1)));
    STAMP(12);
    ld4ch(a3, yo + Y3_OFF - 2048); ld4ch(b3, yo + Y3_OFF - 2048 + 2048);
#pragma unroll
    for (int k = 0; k < 4; k++) {
      ya[k] = hadd2(ya[k], hadd2(hfma2(kk[2 * k], s2[k], a2[k]), a3[k]));
      yb[k] = hadd2(yb[k], hadd2(hfma2(kk[2 * k + 1], s2[k], b2[k]), b3[k]));
    }
    const uint4 r = mix(ya, yb, ua, ub, g2);
    if ((uint32_t)(ch & 1) != rank) send_box(sb, 2 + (ch >> 1), wt2, rank, r);
    else merge_box(sb, &tm_out, 2 + (ch >> 1), wt2, rank, oc0, r, 1 + ch);
    if (wt2 == 0) asm volatile("cp.async.bulk.wait_group.read 0;" ::: "memory");
  }
  STAMP(14);
  STAMP(15); GT(1);
}

typedef CUresult (*EncodeFn)(CUtensorMap*, CUtensorMapDataType, cuuint32_t, void*, const cuuint64_t*, const cuuint64_t*,
                             const cuuint32_t*, const cuuint32_t*, CUtensorMapInterleave, CUtensorMapSwizzle,
                             CUtensorMapL2promotion, CUtensorMapFloatOOBfill);

}

extern "C" void kernel_launch(void* const* d_in, const int* in_sizes, int n_in, void* d_out, int out_size) {
  (void)in_sizes; (void)n_in; (void)out_size;
  typedef const __nv_bfloat16* bp;
  Params p;
  p.t[0] = (bp)d_in[10]; p.t[1] = (bp)d_in[11]; p.t[2] = (bp)d_in[12]; p.t[3] = (bp)d_in[13]; p.t[4] = (bp)d_in[14]; p.t[5] = nullptr;
  p.t[6] = (bp)d_in[1]; p.t[7] = (bp)d_in[2]; p.t[8] = (bp)d_in[5]; p.t[9] = (bp)d_in[6]; p.t[10] = (bp)d_in[7];
  p.t[11] = (bp)d_in[3]; p.t[12] = (bp)d_in[4]; p.t[13] = nullptr;
  p.u = (bp)d_in[0]; p.gw = (bp)d_in[16]; p.A_D = (bp)d_in[8]; p.B_D = (bp)d_in[15];
  static EncodeFn enc = nullptr;
  if (!enc) {
    cudaDriverEntryPointQueryResult qr;
    cudaGetDriverEntryPoint("cuTensorMapEncodeTiled", (void**)&enc, cudaEnableDefault, &qr);
    cudaFuncSetAttribute(ssm_kernel, cudaFuncAttributeMaxDynamicSharedMemorySize, SMEM_BYTES);
  }
  CUtensorMap tm_in, tm_out;
  {
    cuuint64_t gd[5] = {512, 2, 4, 4, 64};
    cuuint64_t gs[4] = {1024, 8192, 2048, 32768};
    cuuint32_t bx[5] = {8, 2, 4, 4, 32};
    cuuint32_t es[5] = {1, 1, 1, 1, 1};
    enc(&tm_in, CU_TENSOR_MAP_DATA_TYPE_BFLOAT16, 5, d_in[0], gd, gs, bx, es, CU_TENSOR_MAP_INTERLEAVE_NONE,
        CU_TENSOR_MAP_SWIZZLE_NONE, CU_TENSOR_MAP_L2_PROMOTION_NONE, CU_TENSOR_MAP_FLOAT_OOB_FILL_NONE);
  }
  {
    cuuint64_t gd[3] = {512, 1024, 2};
    cuuint64_t gs[2] = {2048, 1024};
    cuuint32_t bx[3] = {8, 128, 2};
    cuuint32_t es[3] = {1, 1, 1};
    enc(&tm_out, CU_TENSOR_MAP_DATA_TYPE_BFLOAT16, 3, d_out, gd, gs, bx, es, CU_TENSOR_MAP_INTERLEAVE_NONE,
        CU_TENSOR_MAP_SWIZZLE_NONE, CU_TENSOR_MAP_L2_PROMOTION_NONE, CU_TENSOR_MAP_FLOAT_OOB_FILL_NONE);
  }
  ssm_kernel<<<NCTA + NGATE, 640, SMEM_BYTES, cudaStreamPerThread>>>(p, tm_in, tm_out);
}
```
